```python
import torch

def _softmax(x, axis=-1):
    return torch.softmax(x, dim=axis)
def _gelu(x):
    return torch.nn.functional.gelu(x, approximate="tanh")
def _silu(x):
    return torch.nn.functional.silu(x)
def _sigmoid(x):
    return torch.sigmoid(x)
def _layernorm(x, axis=-1, eps=1e-5):
    m = x.mean(dim=axis, keepdim=True)
    v = x.var(dim=axis, keepdim=True, unbiased=False)
    return (x - m) / torch.sqrt(v + eps)
def _scatter_add(tgt, idx, src, axis=0):
    return tgt.clone().index_add_(axis, idx, src)
def _segment_sum(src, seg, n):
    out = torch.zeros((n,) + src.shape[1:], dtype=src.dtype)
    return out.index_add_(0, seg, src)
def _pad(x, pw):
    flat = tuple(v for pair in reversed(pw) for v in pair)
    return torch.nn.functional.pad(x, flat)

kernel_name = 'sequential_preLN__linear_kernel_hedgehog__moe_arch_mod__prompt'

def setup_inputs():

    _w = (lambda a: (lambda t: t.to(torch.bfloat16) if t.is_floating_point() else t)(torch.as_tensor(a)))
    def _A_setup():
        B, S, D, H = 1, 2048, 1024, 32
        Dh = D // H
        return {
            "x": _w((lambda *s: torch.randn(*s, dtype=torch.bfloat16) * 0.05)(B, S, D)),
            "wqkv": _w((lambda *s: torch.randn(*s, dtype=torch.bfloat16) * 0.2)(D, 3 * D)),
            "w_phi": _w((lambda *s: torch.randn(*s, dtype=torch.bfloat16) * 0.2)(H, Dh, Dh) * (Dh ** -0.5)),
            "wo": _w((lambda *s: torch.randn(*s, dtype=torch.bfloat16) * 0.05)(D, D)),
        }
    _A_in = _A_setup()

    def _B_setup():
        B, S, D, F, C = 1, 2048, 1024, 3584, 1
        return {
            "x": _w((lambda *s: torch.randn(*s, dtype=torch.bfloat16) * 0.05)(B, S, D)),
            "w_r": _w((lambda *s: torch.randn(*s, dtype=torch.bfloat16) * 0.1)(D)),
            "w_gate": _w((lambda *s: torch.randn(*s, dtype=torch.bfloat16) * 0.05)(D, F)),
            "w_up": _w((lambda *s: torch.randn(*s, dtype=torch.bfloat16) * 0.05)(D, F)),
            "w_down": _w((lambda *s: torch.randn(*s, dtype=torch.bfloat16) * 0.05)(F, D)),
        }
    _B_in = _B_setup()

    return {
        "A_x": _A_in["x"],
        "A_wqkv": _A_in["wqkv"],
        "A_w_phi": _A_in["w_phi"],
        "A_wo": _A_in["wo"],
        "B_x": _B_in["x"],
        "B_w_r": _B_in["w_r"],
        "B_w_gate": _B_in["w_gate"],
        "B_w_up": _B_in["w_up"],
        "B_w_down": _B_in["w_down"],
    }

def reference(A_x, A_wqkv, A_w_phi, A_wo, B_x, B_w_r, B_w_gate, B_w_up, B_w_down):
    def _A_ref(x, wqkv, w_phi, wo):
        B, S, D = x.shape
        H = 32; Dh = D // H
        qkv = (lambda x, *d: x.permute(*d))((x @ wqkv).reshape(B, S, 3, H, Dh), 2, 0, 3, 1, 4)
        q, k, v = qkv[0], qkv[1], qkv[2]
        pq = torch.einsum("bhsd,hdf->bhsf", q, w_phi)
        pk = torch.einsum("bhsd,hdf->bhsf", k, w_phi)
        phi_q = torch.concatenate([_softmax(pq, axis=-1), _softmax(-pq, axis=-1)], axis=-1)
        phi_k = torch.concatenate([_softmax(pk, axis=-1), _softmax(-pk, axis=-1)], axis=-1)
        kv = torch.einsum("bhsf,bhsd->bhfd", phi_k, v)
        z  = torch.einsum("bhsf->bhf", phi_k)
        num = torch.einsum("bhqf,bhfd->bhqd", phi_q, kv)
        den = torch.einsum("bhqf,bhf->bhq", phi_q, z)[..., None] + 1e-6
        o = num / den
        return (lambda x, *d: x.permute(*d))(o, 0, 2, 1, 3).reshape(B, S, D) @ wo

    def _B_ref(x, w_r, w_gate, w_up, w_down):
        B, S, D = x.shape
        C = 1
        r = x @ w_r
        idx = torch.argsort(-r, axis=-1)[:, :C]
        idx_e = (lambda x, n, axis: torch.repeat_interleave(x, n, dim=axis))(idx.reshape(B, C, 1), D, axis=2)
        x_sel = (lambda x, i, axis: torch.take_along_dim(x, i, dim=axis))(x, idx_e, axis=1)
        g = _silu(x_sel @ w_gate)
        u = x_sel @ w_up
        y = (g * u) @ w_down
        r_sel = _sigmoid((lambda x, i, axis: torch.take_along_dim(x, i, dim=axis))(r, idx, axis=1))
        y = y * r_sel.reshape(B, C, 1)
        b_off = (torch.arange(B) * S).reshape(B, 1)
        flat_idx = (idx + b_off).reshape(B * C)
        zero = (x * 0.0).reshape(B * S, D)
        upd = _scatter_add(zero, flat_idx, y.reshape(B * C, D), axis=0)
        return x + upd.reshape(B, S, D)

    x = A_x
    h = x + _A_ref(_layernorm(x, axis=-1), A_wqkv, A_w_phi, A_wo)
    h2 = h + _B_ref(_layernorm(h, axis=-1), B_w_r, B_w_gate, B_w_up, B_w_down)
    return h2
```

```cpp
#include <cuda_runtime.h>
#include <cuda.h>
#include <cuda_bf16.h>
#include <stdint.h>

namespace {

typedef __nv_bfloat16 bf16;

__device__ __forceinline__ uint32_t smem_u32(const void* p){ return (uint32_t)__cvta_generic_to_shared(p); }
__device__ __forceinline__ void mbar_init(uint32_t bar, uint32_t cnt){ asm volatile("mbarrier.init.shared::cta.b64 [%0], %1;"::"r"(bar),"r"(cnt):"memory"); }
__device__ __forceinline__ void mbar_expect_tx(uint32_t bar, uint32_t bytes){ asm volatile("mbarrier.arrive.expect_tx.shared::cta.b64 _, [%0], %1;"::"r"(bar),"r"(bytes):"memory"); }
__device__ __forceinline__ void mbar_arrive(uint32_t bar){ asm volatile("mbarrier.arrive.shared::cta.b64 _, [%0];"::"r"(bar):"memory"); }
__device__ __forceinline__ void mbar_arrive_n(uint32_t bar, uint32_t cnt){ asm volatile("mbarrier.arrive.shared::cta.b64 _, [%0], %1;"::"r"(bar),"r"(cnt):"memory"); }
__device__ __forceinline__ uint32_t mapa(uint32_t addr, uint32_t cta){ uint32_t r; asm volatile("mapa.shared::cluster.u32 %0, %1, %2;":"=r"(r):"r"(addr),"r"(cta)); return r; }
__device__ __forceinline__ void mbar_arrive_at(uint32_t bar, uint32_t cta, uint32_t cnt){
  asm volatile("{\n.reg .b32 ra;\nmapa.shared::cluster.u32 ra, %0, %1;\nmbarrier.arrive.shared::cluster.b64 _, [ra], %2;\n}\n"::"r"(bar),"r"(cta),"r"(cnt):"memory"); }
__device__ __forceinline__ void mbar_arrive_remote(uint32_t cluster_addr, uint32_t cnt){
  asm volatile("mbarrier.arrive.shared::cluster.b64 _, [%0], %1;"::"r"(cluster_addr),"r"(cnt):"memory"); }
__device__ __forceinline__ void mbar_wait(uint32_t bar, uint32_t parity){
  asm volatile("{\n.reg .pred p;\n.reg .u32 c;\nmov.u32 c, 0;\nLW:\nmbarrier.try_wait.parity.shared::cta.b64 p, [%0], %1;\n@p bra LD;\nadd.u32 c, c, 1;\nsetp.lt.u32 p, c, 2000000;\n@p bra LW;\ntrap;\nLD:\n}\n"::"r"(bar),"r"(parity):"memory"); }
__device__ __forceinline__ void mbar_wait2(uint32_t bar0, uint32_t par0, uint32_t bar1, uint32_t par1){
  asm volatile("{\n.reg .pred p, q;\n.reg .u32 c;\nmov.u32 c, 0;\nLW:\nmbarrier.try_wait.parity.shared::cta.b64 p, [%0], %1;\nmbarrier.try_wait.parity.shared::cta.b64 q, [%2], %3;\nand.pred p, p, q;\n@p bra LD;\nadd.u32 c, c, 1;\nsetp.lt.u32 p, c, 2000000;\n@p bra LW;\ntrap;\nLD:\n}\n"::"r"(bar0),"r"(par0),"r"(bar1),"r"(par1):"memory"); }
__device__ __forceinline__ void tma_2d(uint32_t dst, const CUtensorMap* m, int c0, int c1, uint32_t bar){
  asm volatile("cp.async.bulk.tensor.2d.shared::cluster.global.mbarrier::complete_tx::bytes [%0], [%1, {%3, %4}], [%2];"::"r"(dst),"l"(m),"r"(bar),"r"(c0),"r"(c1):"memory"); }
__device__ __forceinline__ void tma_2d_mc(uint32_t dst, const CUtensorMap* m, int c0, int c1, uint32_t bar){
  asm volatile("cp.async.bulk.tensor.2d.shared::cluster.global.mbarrier::complete_tx::bytes.multicast::cluster [%0], [%1, {%3, %4}], [%2], %5;"::"r"(dst),"l"(m),"r"(bar),"r"(c0),"r"(c1),"h"((uint16_t)3):"memory"); }
__device__ __forceinline__ void tma_4d(uint32_t dst, const CUtensorMap* m, int c0, int c1, int c2, int c3, uint32_t bar){
  asm volatile("cp.async.bulk.tensor.4d.shared::cluster.global.mbarrier::complete_tx::bytes [%0], [%1, {%3, %4, %5, %6}], [%2];"::"r"(dst),"l"(m),"r"(bar),"r"(c0),"r"(c1),"r"(c2),"r"(c3):"memory"); }
__device__ __forceinline__ uint64_t policy_evict_first(){ uint64_t p; asm volatile("createpolicy.fractional.L2::evict_first.b64 %0, 1.0;":"=l"(p)); return p; }
__device__ __forceinline__ void tma_3d_h(uint32_t dst, const CUtensorMap* m, int c0, int c1, int c2, uint32_t bar, uint64_t pol){
  asm volatile("cp.async.bulk.tensor.3d.shared::cluster.global.mbarrier::complete_tx::bytes.L2::cache_hint [%0], [%1, {%3, %4, %5}], [%2], %6;"::"r"(dst),"l"(m),"r"(bar),"r"(c0),"r"(c1),"r"(c2),"l"(pol):"memory"); }
__device__ __forceinline__ void tma_4d_h(uint32_t dst, const CUtensorMap* m, int c0, int c1, int c2, int c3, uint32_t bar, uint64_t pol){
  asm volatile("cp.async.bulk.tensor.4d.shared::cluster.global.mbarrier::complete_tx::bytes.L2::cache_hint [%0], [%1, {%3, %4, %5, %6}], [%2], %7;"::"r"(dst),"l"(m),"r"(bar),"r"(c0),"r"(c1),"r"(c2),"r"(c3),"l"(pol):"memory"); }
__device__ __forceinline__ void tma_store_3d_h(const CUtensorMap* m, int c0, int c1, int c2, uint32_t src, uint64_t pol){
  asm volatile("cp.async.bulk.tensor.3d.global.shared::cta.bulk_group.L2::cache_hint [%0, {%2, %3, %4}], [%1], %5;"::"l"(m),"r"(src),"r"(c0),"r"(c1),"r"(c2),"l"(pol):"memory"); }
__device__ __forceinline__ void red_add_f32x4(float4* p, float x, float y, float z, float w){ asm volatile("red.relaxed.gpu.global.add.v4.f32 [%0], {%1,%2,%3,%4};"::"l"(p),"f"(x),"f"(y),"f"(z),"f"(w):"memory"); }
__device__ __forceinline__ void tma_store_2d_h(const CUtensorMap* m, int c0, int c1, uint32_t src, uint64_t pol){
  asm volatile("cp.async.bulk.tensor.2d.global.shared::cta.bulk_group.L2::cache_hint [%0, {%2, %3}], [%1], %4;"::"l"(m),"r"(src),"r"(c0),"r"(c1),"l"(pol):"memory"); }
__device__ __forceinline__ bool elect_one(){ uint32_t p; asm volatile("{\n.reg .pred P;\nelect.sync _|P, 0xffffffff;\nselp.b32 %0, 1, 0, P;\n}\n":"=r"(p)); return p; }
__device__ __forceinline__ void bulk_prefetch(const void* p, uint32_t bytes){
  asm volatile("cp.async.bulk.prefetch.L2.global [%0], %1;"::"l"(p),"r"(bytes):"memory"); }
__device__ __forceinline__ void bulk_s2peer(uint32_t dst_cluster, uint32_t src, uint32_t bytes, uint32_t bar_cluster){
  asm volatile("cp.async.bulk.shared::cluster.shared::cta.mbarrier::complete_tx::bytes [%0], [%1], %2, [%3];"::"r"(dst_cluster),"r"(src),"r"(bytes),"r"(bar_cluster):"memory"); }
__device__ __forceinline__ void bulk_g2s_mc(uint32_t dst, const void* src, uint32_t bytes, uint32_t bar, uint64_t pol){
  asm volatile("cp.async.bulk.shared::cluster.global.mbarrier::complete_tx::bytes.multicast::cluster.L2::cache_hint [%0], [%1], %2, [%3], %4, %5;"::"r"(dst),"l"(src),"r"(bytes),"r"(bar),"h"((uint16_t)3),"l"(pol):"memory"); }
__device__ __forceinline__ void bulk_s2g(void* dst, uint32_t src, uint32_t bytes){
  asm volatile("cp.async.bulk.global.shared::cta.bulk_group [%0], [%1], %2;"::"l"(dst),"r"(src),"r"(bytes):"memory"); }
__device__ __forceinline__ void bulk_commit(){ asm volatile("cp.async.bulk.commit_group;":::"memory"); }
__device__ __forceinline__ void bulk_wait_read(){ asm volatile("cp.async.bulk.wait_group.read 0;":::"memory"); }
__device__ __forceinline__ void bulk_wait_all(){ asm volatile("cp.async.bulk.wait_group 0;":::"memory"); }
__device__ __forceinline__ void prefetch_map(const CUtensorMap* m){ asm volatile("prefetch.tensormap [%0];"::"l"(m):"memory"); }
__device__ __forceinline__ void fence_async_smem(){ asm volatile("fence.proxy.async.shared::cta;":::"memory"); }
__device__ __forceinline__ void fence_acquire_gpu(){ asm volatile("fence.acquire.gpu;":::"memory"); }
__device__ __forceinline__ void fence_gpu(){ asm volatile("fence.acq_rel.gpu;":::"memory"); }
__device__ __forceinline__ void wg_fence(){ asm volatile("wgmma.fence.sync.aligned;":::"memory"); }
__device__ __forceinline__ void wg_commit(){ asm volatile("wgmma.commit_group.sync.aligned;":::"memory"); }
template<int N> __device__ __forceinline__ void wg_wait(){ asm volatile("wgmma.wait_group.sync.aligned %0;"::"n"(N):"memory"); }
template<int N> __device__ __forceinline__ void fence_regs(float (&d)[N]){
  #pragma unroll
  for(int i=0;i<N;i++) asm volatile("":"+f"(d[i])::"memory"); }
__device__ __forceinline__ void bar_sync(int id, int n){ asm volatile("bar.sync %0, %1;"::"r"(id),"r"(n):"memory"); }
__device__ __forceinline__ void bar_arrive(int id, int n){ asm volatile("bar.arrive %0, %1;"::"r"(id),"r"(n):"memory"); }
__device__ __forceinline__ void cluster_arrive(){ asm volatile("barrier.cluster.arrive.relaxed.aligned;":::"memory"); }
__device__ __forceinline__ void cluster_wait(){ asm volatile("barrier.cluster.wait.aligned;":::"memory"); }
__host__ __device__ constexpr uint32_t dlo(uint32_t addr, uint32_t lbo){ return (addr >> 4) | ((lbo >> 4) << 16); }
__host__ __device__ constexpr uint32_t dhi(uint32_t sbo, uint32_t sw){ return (sbo >> 4) | (sw << 30); }
constexpr uint32_t H128 = dhi(1024, 1), H64 = dhi(512, 2), H0 = dhi(128, 0);
__device__ __forceinline__ uint32_t pack_bf16(float lo, float hi){ uint32_t r; asm("cvt.rn.bf16x2.f32 %0, %1, %2;":"=r"(r):"f"(hi),"f"(lo)); return r; }
__device__ __forceinline__ float bf_lo(uint32_t v){ return __uint_as_float(v<<16); }
__device__ __forceinline__ float bf_hi(uint32_t v){ return __uint_as_float(v&0xffff0000u); }
__device__ __forceinline__ float ex2(float x){ float r; asm("ex2.approx.ftz.f32 %0, %1;":"=f"(r):"f"(x)); return r; }
__device__ __forceinline__ float rcp(float x){ float r; asm("rcp.approx.ftz.f32 %0, %1;":"=f"(r):"f"(x)); return r; }
__device__ __forceinline__ void stsm4(uint32_t addr, uint32_t a, uint32_t b, uint32_t c, uint32_t d){
  asm volatile("stmatrix.sync.aligned.m8n8.x4.shared.b16 [%0], {%1,%2,%3,%4};"::"r"(addr),"r"(a),"r"(b),"r"(c),"r"(d)); }
__device__ __forceinline__ void stsm2(uint32_t addr, uint32_t a, uint32_t b){
  asm volatile("stmatrix.sync.aligned.m8n8.x2.shared.b16 [%0], {%1,%2};"::"r"(addr),"r"(a),"r"(b)); }
__device__ __forceinline__ void mma16816(float& d0, float& d1, float& d2, float& d3, uint32_t a0, uint32_t a1, uint32_t a2, uint32_t a3, uint32_t b0, uint32_t b1){
  asm volatile("mma.sync.aligned.m16n8k16.row.col.f32.bf16.bf16.f32 {%0,%1,%2,%3}, {%4,%5,%6,%7}, {%8,%9}, {%0,%1,%2,%3};"
               : "+f"(d0), "+f"(d1), "+f"(d2), "+f"(d3) : "r"(a0), "r"(a1), "r"(a2), "r"(a3), "r"(b0), "r"(b1)); }
__device__ __forceinline__ void ldsm4(uint32_t addr, uint32_t& a, uint32_t& b, uint32_t& c, uint32_t& d){
  asm volatile("ldmatrix.sync.aligned.m8n8.x4.shared.b16 {%0,%1,%2,%3}, [%4];":"=r"(a),"=r"(b),"=r"(c),"=r"(d):"r"(addr):"memory"); }
__device__ __forceinline__ void sts32(uint32_t a, uint32_t v){ asm volatile("st.shared.b32 [%0], %1;"::"r"(a),"r"(v):"memory"); }
__device__ __forceinline__ void stsf(uint32_t a, float v){ asm volatile("st.shared.f32 [%0], %1;"::"r"(a),"f"(v):"memory"); }
__device__ __forceinline__ void sts64(uint32_t a, uint32_t x, uint32_t y){ asm volatile("st.shared.v2.b32 [%0], {%1,%2};"::"r"(a),"r"(x),"r"(y):"memory"); }
__device__ __forceinline__ void sts128(uint32_t a, uint32_t x, uint32_t y, uint32_t z, uint32_t w){ asm volatile("st.shared.v4.b32 [%0], {%1,%2,%3,%4};"::"r"(a),"r"(x),"r"(y),"r"(z),"r"(w):"memory"); }
__device__ __forceinline__ float ldsf(uint32_t a){ float v; asm volatile("ld.shared.f32 %0, [%1];":"=f"(v):"r"(a):"memory"); return v; }
__device__ __forceinline__ float2 lds64f(uint32_t a){ float2 v; asm volatile("ld.shared.v2.f32 {%0,%1}, [%2];":"=f"(v.x),"=f"(v.y):"r"(a):"memory"); return v; }
__device__ __forceinline__ uint4 lds128(uint32_t a){ uint4 v; asm volatile("ld.shared.v4.u32 {%0,%1,%2,%3}, [%4];":"=r"(v.x),"=r"(v.y),"=r"(v.z),"=r"(v.w):"r"(a):"memory"); return v; }
__device__ __forceinline__ uint4 ld128_weak(const void* p){ uint4 v; asm volatile("ld.global.L1::no_allocate.v4.u32 {%0,%1,%2,%3}, [%4];":"=r"(v.x),"=r"(v.y),"=r"(v.z),"=r"(v.w):"l"(p):"memory"); return v; }
__device__ __forceinline__ uint4 ld128_keep(const void* p){ uint4 v; asm volatile("ld.global.v4.u32 {%0,%1,%2,%3}, [%4];":"=r"(v.x),"=r"(v.y),"=r"(v.z),"=r"(v.w):"l"(p):"memory"); return v; }
__device__ __forceinline__ uint4 ld128_rlx(const void* p){ uint4 v; asm volatile("ld.relaxed.gpu.global.v4.u32 {%0,%1,%2,%3}, [%4];":"=r"(v.x),"=r"(v.y),"=r"(v.z),"=r"(v.w):"l"(p):"memory"); return v; }
__device__ __forceinline__ uint2 ld64_rlx(const void* p){ uint2 v; asm volatile("ld.relaxed.gpu.global.v2.u32 {%0,%1}, [%2];":"=r"(v.x),"=r"(v.y):"l"(p):"memory"); return v; }
__device__ __forceinline__ uint32_t ld32_rlx(const void* p){ uint32_t v; asm volatile("ld.relaxed.gpu.global.u32 %0, [%1];":"=r"(v):"l"(p):"memory"); return v; }
__device__ __forceinline__ void st128_rlx(void* p, uint32_t x, uint32_t y, uint32_t z, uint32_t w){ asm volatile("st.relaxed.gpu.global.v4.u32 [%0], {%1,%2,%3,%4};"::"l"(p),"r"(x),"r"(y),"r"(z),"r"(w):"memory"); }
__device__ __forceinline__ void st64_rlx(void* p, uint32_t x, uint32_t y){ asm volatile("st.relaxed.gpu.global.v2.u32 [%0], {%1,%2};"::"l"(p),"r"(x),"r"(y):"memory"); }
__device__ __forceinline__ void st32_rlx(void* p, uint32_t x){ asm volatile("st.relaxed.gpu.global.u32 [%0], %1;"::"l"(p),"r"(x):"memory"); }
__device__ __forceinline__ uint32_t tagw(float x, uint32_t t){ return (__float_as_uint(x) & ~3u) | t; }
__device__ __forceinline__ float untag(uint32_t w){ return __uint_as_float(w & ~3u); }

template<int TA, int TB, uint32_t HA, uint32_t HB> __device__ __forceinline__ void wgmma_ss_n128(float (&d)[64], uint32_t da, uint32_t db, int scale_d){
  asm volatile("{\n.reg .pred p;\n.reg .b64 a, b;\nsetp.ne.b32 p, %70, 0;\nmov.b64 a, {%64, %68};\nmov.b64 b, {%65, %69};\n"
  "wgmma.mma_async.sync.aligned.m64n128k16.f32.bf16.bf16 {%0, %1, %2, %3, %4, %5, %6, %7, %8, %9, %10, %11, %12, %13, %14, %15, %16, %17, %18, %19, %20, %21, %22, %23, %24, %25, %26, %27, %28, %29, %30, %31, %32, %33, %34, %35, %36, %37, %38, %39, %40, %41, %42, %43, %44, %45, %46, %47, %48, %49, %50, %51, %52, %53, %54, %55, %56, %57, %58, %59, %60, %61, %62, %63}, a, b, p, 1, 1, %66, %67;\n}\n"
  : "+f"(d[0]), "+f"(d[1]), "+f"(d[2]), "+f"(d[3]), "+f"(d[4]), "+f"(d[5]), "+f"(d[6]), "+f"(d[7]), "+f"(d[8]), "+f"(d[9]), "+f"(d[10]), "+f"(d[11]), "+f"(d[12]), "+f"(d[13]), "+f"(d[14]), "+f"(d[15]), "+f"(d[16]), "+f"(d[17]), "+f"(d[18]), "+f"(d[19]), "+f"(d[20]), "+f"(d[21]), "+f"(d[22]), "+f"(d[23]), "+f"(d[24]), "+f"(d[25]), "+f"(d[26]), "+f"(d[27]), "+f"(d[28]), "+f"(d[29]), "+f"(d[30]), "+f"(d[31]), "+f"(d[32]), "+f"(d[33]), "+f"(d[34]), "+f"(d[35]), "+f"(d[36]), "+f"(d[37]), "+f"(d[38]), "+f"(d[39]), "+f"(d[40]), "+f"(d[41]), "+f"(d[42]), "+f"(d[43]), "+f"(d[44]), "+f"(d[45]), "+f"(d[46]), "+f"(d[47]), "+f"(d[48]), "+f"(d[49]), "+f"(d[50]), "+f"(d[51]), "+f"(d[52]), "+f"(d[53]), "+f"(d[54]), "+f"(d[55]), "+f"(d[56]), "+f"(d[57]), "+f"(d[58]), "+f"(d[59]), "+f"(d[60]), "+f"(d[61]), "+f"(d[62]), "+f"(d[63])
  : "r"(da), "r"(db), "n"(TA), "n"(TB), "n"(HA), "n"(HB), "r"(scale_d));
}
template<int TA, int TB, uint32_t HA, uint32_t HB> __device__ __forceinline__ void wgmma_sa_n128(float (&d)[64], uint32_t da, uint32_t db){
  asm volatile("{\n.reg .pred p;\n.reg .b64 a, b;\nsetp.ne.b32 p, 1, 0;\nmov.b64 a, {%64, %68};\nmov.b64 b, {%65, %69};\n"
  "wgmma.mma_async.sync.aligned.m64n128k16.f32.bf16.bf16 {%0, %1, %2, %3, %4, %5, %6, %7, %8, %9, %10, %11, %12, %13, %14, %15, %16, %17, %18, %19, %20, %21, %22, %23, %24, %25, %26, %27, %28, %29, %30, %31, %32, %33, %34, %35, %36, %37, %38, %39, %40, %41, %42, %43, %44, %45, %46, %47, %48, %49, %50, %51, %52, %53, %54, %55, %56, %57, %58, %59, %60, %61, %62, %63}, a, b, p, 1, 1, %66, %67;\n}\n"
  : "+f"(d[0]), "+f"(d[1]), "+f"(d[2]), "+f"(d[3]), "+f"(d[4]), "+f"(d[5]), "+f"(d[6]), "+f"(d[7]), "+f"(d[8]), "+f"(d[9]), "+f"(d[10]), "+f"(d[11]), "+f"(d[12]), "+f"(d[13]), "+f"(d[14]), "+f"(d[15]), "+f"(d[16]), "+f"(d[17]), "+f"(d[18]), "+f"(d[19]), "+f"(d[20]), "+f"(d[21]), "+f"(d[22]), "+f"(d[23]), "+f"(d[24]), "+f"(d[25]), "+f"(d[26]), "+f"(d[27]), "+f"(d[28]), "+f"(d[29]), "+f"(d[30]), "+f"(d[31]), "+f"(d[32]), "+f"(d[33]), "+f"(d[34]), "+f"(d[35]), "+f"(d[36]), "+f"(d[37]), "+f"(d[38]), "+f"(d[39]), "+f"(d[40]), "+f"(d[41]), "+f"(d[42]), "+f"(d[43]), "+f"(d[44]), "+f"(d[45]), "+f"(d[46]), "+f"(d[47]), "+f"(d[48]), "+f"(d[49]), "+f"(d[50]), "+f"(d[51]), "+f"(d[52]), "+f"(d[53]), "+f"(d[54]), "+f"(d[55]), "+f"(d[56]), "+f"(d[57]), "+f"(d[58]), "+f"(d[59]), "+f"(d[60]), "+f"(d[61]), "+f"(d[62]), "+f"(d[63])
  : "r"(da), "r"(db), "n"(TA), "n"(TB), "n"(HA), "n"(HB));
}
template<int TA, int TB, uint32_t HA, uint32_t HB> __device__ __forceinline__ void wgmma_sa_n40(float (&d)[20], uint32_t da, uint32_t db){
  asm volatile("{\n.reg .pred p;\n.reg .b64 a, b;\nsetp.ne.b32 p, 1, 0;\nmov.b64 a, {%20, %24};\nmov.b64 b, {%21, %25};\n"
  "wgmma.mma_async.sync.aligned.m64n40k16.f32.bf16.bf16 {%0, %1, %2, %3, %4, %5, %6, %7, %8, %9, %10, %11, %12, %13, %14, %15, %16, %17, %18, %19}, a, b, p, 1, 1, %22, %23;\n}\n"
  : "+f"(d[0]), "+f"(d[1]), "+f"(d[2]), "+f"(d[3]), "+f"(d[4]), "+f"(d[5]), "+f"(d[6]), "+f"(d[7]), "+f"(d[8]), "+f"(d[9]), "+f"(d[10]), "+f"(d[11]), "+f"(d[12]), "+f"(d[13]), "+f"(d[14]), "+f"(d[15]), "+f"(d[16]), "+f"(d[17]), "+f"(d[18]), "+f"(d[19])
  : "r"(da), "r"(db), "n"(TA), "n"(TB), "n"(HA), "n"(HB));
}
template<int TA, int TB, uint32_t HA, uint32_t HB> __device__ __forceinline__ void wgmma_sz_n40(float (&d)[20], uint32_t da, uint32_t db){
  asm volatile("{\n.reg .pred p;\n.reg .b64 a, b;\nsetp.ne.b32 p, 0, 0;\nmov.b64 a, {%20, %24};\nmov.b64 b, {%21, %25};\n"
  "wgmma.mma_async.sync.aligned.m64n40k16.f32.bf16.bf16 {%0, %1, %2, %3, %4, %5, %6, %7, %8, %9, %10, %11, %12, %13, %14, %15, %16, %17, %18, %19}, a, b, p, 1, 1, %22, %23;\n}\n"
  : "=f"(d[0]), "=f"(d[1]), "=f"(d[2]), "=f"(d[3]), "=f"(d[4]), "=f"(d[5]), "=f"(d[6]), "=f"(d[7]), "=f"(d[8]), "=f"(d[9]), "=f"(d[10]), "=f"(d[11]), "=f"(d[12]), "=f"(d[13]), "=f"(d[14]), "=f"(d[15]), "=f"(d[16]), "=f"(d[17]), "=f"(d[18]), "=f"(d[19])
  : "r"(da), "r"(db), "n"(TA), "n"(TB), "n"(HA), "n"(HB));
}
template<int TA, int TB, uint32_t HA, uint32_t HB> __device__ __forceinline__ void wgmma_sa_n32(float (&d)[16], uint32_t da, uint32_t db){
  asm volatile("{\n.reg .pred p;\n.reg .b64 a, b;\nsetp.ne.b32 p, 1, 0;\nmov.b64 a, {%16, %20};\nmov.b64 b, {%17, %21};\n"
  "wgmma.mma_async.sync.aligned.m64n32k16.f32.bf16.bf16 {%0, %1, %2, %3, %4, %5, %6, %7, %8, %9, %10, %11, %12, %13, %14, %15}, a, b, p, 1, 1, %18, %19;\n}\n"
  : "+f"(d[0]), "+f"(d[1]), "+f"(d[2]), "+f"(d[3]), "+f"(d[4]), "+f"(d[5]), "+f"(d[6]), "+f"(d[7]), "+f"(d[8]), "+f"(d[9]), "+f"(d[10]), "+f"(d[11]), "+f"(d[12]), "+f"(d[13]), "+f"(d[14]), "+f"(d[15])
  : "r"(da), "r"(db), "n"(TA), "n"(TB), "n"(HA), "n"(HB));
}
template<int TA, int TB, uint32_t HA, uint32_t HB> __device__ __forceinline__ void wgmma_ss_n32(float (&d)[16], uint32_t da, uint32_t db, int scale_d){
  asm volatile("{\n.reg .pred p;\n.reg .b64 a, b;\nsetp.ne.b32 p, %22, 0;\nmov.b64 a, {%16, %20};\nmov.b64 b, {%17, %21};\n"
  "wgmma.mma_async.sync.aligned.m64n32k16.f32.bf16.bf16 {%0, %1, %2, %3, %4, %5, %6, %7, %8, %9, %10, %11, %12, %13, %14, %15}, a, b, p, 1, 1, %18, %19;\n}\n"
  : "+f"(d[0]), "+f"(d[1]), "+f"(d[2]), "+f"(d[3]), "+f"(d[4]), "+f"(d[5]), "+f"(d[6]), "+f"(d[7]), "+f"(d[8]), "+f"(d[9]), "+f"(d[10]), "+f"(d[11]), "+f"(d[12]), "+f"(d[13]), "+f"(d[14]), "+f"(d[15])
  : "r"(da), "r"(db), "n"(TA), "n"(TB), "n"(HA), "n"(HB), "r"(scale_d));
}
template<int TA, int TB, uint32_t HA, uint32_t HB> __device__ __forceinline__ void wgmma_ss_n8(float (&d)[4], uint32_t da, uint32_t db, int scale_d){
  asm volatile("{\n.reg .pred p;\n.reg .b64 a, b;\nsetp.ne.b32 p, %10, 0;\nmov.b64 a, {%4, %8};\nmov.b64 b, {%5, %9};\n"
  "wgmma.mma_async.sync.aligned.m64n8k16.f32.bf16.bf16 {%0, %1, %2, %3}, a, b, p, 1, 1, %6, %7;\n}\n"
  : "+f"(d[0]), "+f"(d[1]), "+f"(d[2]), "+f"(d[3])
  : "r"(da), "r"(db), "n"(TA), "n"(TB), "n"(HA), "n"(HB), "r"(scale_d));
}
template<int TB, uint32_t HB> __device__ __forceinline__ void wgmma_ra_n32(float (&d)[16], uint32_t a0, uint32_t a1, uint32_t a2, uint32_t a3, uint32_t db){
  asm volatile("{\n.reg .pred p;\n.reg .b64 a, b;\nsetp.ne.b32 p, 1, 0;\nmov.b64 b, {%20, %22};\n"
  "wgmma.mma_async.sync.aligned.m64n32k16.f32.bf16.bf16 {%0, %1, %2, %3, %4, %5, %6, %7, %8, %9, %10, %11, %12, %13, %14, %15}, {%16,%17,%18,%19}, b, p, 1, 1, %21;\n}\n"
  : "+f"(d[0]), "+f"(d[1]), "+f"(d[2]), "+f"(d[3]), "+f"(d[4]), "+f"(d[5]), "+f"(d[6]), "+f"(d[7]), "+f"(d[8]), "+f"(d[9]), "+f"(d[10]), "+f"(d[11]), "+f"(d[12]), "+f"(d[13]), "+f"(d[14]), "+f"(d[15])
  : "r"(a0), "r"(a1), "r"(a2), "r"(a3), "r"(db), "n"(TB), "n"(HB));
}
template<int TB, uint32_t HB> __device__ __forceinline__ void wgmma_rs_n32(float (&d)[16], uint32_t a0, uint32_t a1, uint32_t a2, uint32_t a3, uint32_t db, int scale_d){
  asm volatile("{\n.reg .pred p;\n.reg .b64 a, b;\nsetp.ne.b32 p, %23, 0;\nmov.b64 b, {%20, %22};\n"
  "wgmma.mma_async.sync.aligned.m64n32k16.f32.bf16.bf16 {%0, %1, %2, %3, %4, %5, %6, %7, %8, %9, %10, %11, %12, %13, %14, %15}, {%16,%17,%18,%19}, b, p, 1, 1, %21;\n}\n"
  : "+f"(d[0]), "+f"(d[1]), "+f"(d[2]), "+f"(d[3]), "+f"(d[4]), "+f"(d[5]), "+f"(d[6]), "+f"(d[7]), "+f"(d[8]), "+f"(d[9]), "+f"(d[10]), "+f"(d[11]), "+f"(d[12]), "+f"(d[13]), "+f"(d[14]), "+f"(d[15])
  : "r"(a0), "r"(a1), "r"(a2), "r"(a3), "r"(db), "n"(TB), "n"(HB), "r"(scale_d));
}
template<int TB, uint32_t HB> __device__ __forceinline__ void wgmma_ra_n40(float (&d)[20], uint32_t a0, uint32_t a1, uint32_t a2, uint32_t a3, uint32_t db){
  asm volatile("{\n.reg .pred p;\n.reg .b64 a, b;\nsetp.ne.b32 p, 1, 0;\nmov.b64 b, {%24, %26};\n"
  "wgmma.mma_async.sync.aligned.m64n40k16.f32.bf16.bf16 {%0, %1, %2, %3, %4, %5, %6, %7, %8, %9, %10, %11, %12, %13, %14, %15, %16, %17, %18, %19}, {%20,%21,%22,%23}, b, p, 1, 1, %25;\n}\n"
  : "+f"(d[0]), "+f"(d[1]), "+f"(d[2]), "+f"(d[3]), "+f"(d[4]), "+f"(d[5]), "+f"(d[6]), "+f"(d[7]), "+f"(d[8]), "+f"(d[9]), "+f"(d[10]), "+f"(d[11]), "+f"(d[12]), "+f"(d[13]), "+f"(d[14]), "+f"(d[15]), "+f"(d[16]), "+f"(d[17]), "+f"(d[18]), "+f"(d[19])
  : "r"(a0), "r"(a1), "r"(a2), "r"(a3), "r"(db), "n"(TB), "n"(HB));
}
template<int TB, uint32_t HB> __device__ __forceinline__ void wgmma_rz_n40(float (&d)[20], uint32_t a0, uint32_t a1, uint32_t a2, uint32_t a3, uint32_t db){
  asm volatile("{\n.reg .pred p;\n.reg .b64 a, b;\nsetp.ne.b32 p, 0, 0;\nmov.b64 b, {%24, %26};\n"
  "wgmma.mma_async.sync.aligned.m64n40k16.f32.bf16.bf16 {%0, %1, %2, %3, %4, %5, %6, %7, %8, %9, %10, %11, %12, %13, %14, %15, %16, %17, %18, %19}, {%20,%21,%22,%23}, b, p, 1, 1, %25;\n}\n"
  : "=f"(d[0]), "=f"(d[1]), "=f"(d[2]), "=f"(d[3]), "=f"(d[4]), "=f"(d[5]), "=f"(d[6]), "=f"(d[7]), "=f"(d[8]), "=f"(d[9]), "=f"(d[10]), "=f"(d[11]), "=f"(d[12]), "=f"(d[13]), "=f"(d[14]), "=f"(d[15]), "=f"(d[16]), "=f"(d[17]), "=f"(d[18]), "=f"(d[19])
  : "r"(a0), "r"(a1), "r"(a2), "r"(a3), "r"(db), "n"(TB), "n"(HB));
}
template<int TB, uint32_t HB> __device__ __forceinline__ void wgmma_ra_n8(float (&d)[4], uint32_t a0, uint32_t a1, uint32_t a2, uint32_t a3, uint32_t db){
  asm volatile("{\n.reg .pred p;\n.reg .b64 a, b;\nsetp.ne.b32 p, 1, 0;\nmov.b64 b, {%8, %10};\n"
  "wgmma.mma_async.sync.aligned.m64n8k16.f32.bf16.bf16 {%0, %1, %2, %3}, {%4,%5,%6,%7}, b, p, 1, 1, %9;\n}\n"
  : "+f"(d[0]), "+f"(d[1]), "+f"(d[2]), "+f"(d[3])
  : "r"(a0), "r"(a1), "r"(a2), "r"(a3), "r"(db), "n"(TB), "n"(HB));
}
template<int TB, uint32_t HB> __device__ __forceinline__ void wgmma_rz_n8(float (&d)[4], uint32_t a0, uint32_t a1, uint32_t a2, uint32_t a3, uint32_t db){
  asm volatile("{\n.reg .pred p;\n.reg .b64 a, b;\nsetp.ne.b32 p, 0, 0;\nmov.b64 b, {%8, %10};\n"
  "wgmma.mma_async.sync.aligned.m64n8k16.f32.bf16.bf16 {%0, %1, %2, %3}, {%4,%5,%6,%7}, b, p, 1, 1, %9;\n}\n"
  : "=f"(d[0]), "=f"(d[1]), "=f"(d[2]), "=f"(d[3])
  : "r"(a0), "r"(a1), "r"(a2), "r"(a3), "r"(db), "n"(TB), "n"(HB));
}

constexpr int SEQ = 2048, DM = 1024, FF = 3584;
constexpr float LOG2E = 1.4426950408889634f;
constexpr uint32_t POLL_LIMIT = 1u << 22;
constexpr int NPRE = 2;
#define TRK_SLEEP 0
#define QG 1
#define RST_STEP 100
#define PFK 10
#define PFM 1
#define TFK 100
#define PFN 2
#define WD_STEP 300
#define FQ0 8
#define FQ1 15
#define WD_DELAY 0
#define SKM 0x251
#define LAG 1
#define PWO 8
#define BPOLL 6
#define PZ 4
constexpr int NFFN = 112;

constexpr uint32_t SB0 = 1024;
constexpr uint32_t KV_STAGE = 49152, R5 = 32768;
constexpr uint32_t OFF_X = 163840, OFF_S = 196608, OFF_WPHI = OFF_S + 20480, OFF_M = 229376, SMEM_BYTES = 232448;
constexpr uint32_t OFF_RS256 = 212992, OFF_ONES = OFF_RS256 + 1024, OFF_WPHIK1 = OFF_ONES + 1024, OFF_KVZ = OFF_S;
constexpr uint32_t OFF_WPHIK = OFF_S, OFF_BXK = OFF_S + 2048, OFF_AXK = OFF_S + 4096;
constexpr uint32_t OFF_AXQ = OFF_WPHI, OFF_BXQ = OFF_WPHI + 2048, OFF_WPHIQ = OFF_WPHI + 4096;
constexpr uint32_t B_FULLKV = OFF_M, B_EMPTYKV = OFF_M + 32, B_FULL5 = OFF_M + 64, B_EMPTY5 = OFF_M + 104;
constexpr uint32_t B_W = OFF_M + 144, B_X = OFF_M + 152, B_R = OFF_M + 160, B_AUX = OFF_M + 168, B_AUXQ = OFF_M + 176, B_KD = OFF_M + 184, B_RC = OFF_M + 192;
constexpr uint32_t B_FULLA = OFF_M + 768, B_QL = B_FULLA + 80, B_T = B_FULLA + 88, B_UB = B_FULLA + 96, B_UA = B_FULLA + 112, OFF_T = OFF_M + 1024;
constexpr uint32_t OFF_SUMWR = OFF_M + 960, OFF_EP = OFF_M + 208, OFF_KEY = OFF_M + 216, OFF_H8 = OFF_M + 224;
constexpr uint32_t OFF_RSQ = OFF_M + 256, OFF_WR = OFF_M + 1792, OFF_XSEL = 4 * R5;
constexpr uint32_t OFF_ACT = OFF_M + 2304, OFF_SCR = OFF_M + 2432, B_F = OFF_M + 896;
constexpr int KVP = 6 * 128;

enum { NB_G2E = 1, NB_XS = 2, NB_WG01 = 3, NB_ACT = 4, NB_Q0 = 5  , NB_ST = 14, NB_DN = 8, NB_OUT = 9, NB_ZERO = 10, NB_PUB = 11, NB_TOK = 10  , NB_L0 = 12  , NB_WG2 = 7, NB_QGO = 15 };

struct Scratch {
  bf16     o[SEQ * DM];
  uint4    part[16 * 8 * 128];
  uint32_t key[32 * 128];
  uint32_t cand[128 * (DM + 32)];
  uint32_t ypart[NFFN * DM];
  float4   kvacc[32 * KVP];
  uint2    stats[SEQ];
  uint32_t cskv[2 * DM];
  uint32_t csq[4 * DM];
  uint32_t oset[16 * 32];
  uint32_t epoch;
};
__device__ __align__(1024) Scratch g_scr;
#define TS(id)
#define TDUMP()
#define TS0_DECL()
#define TS0_READ()
#define TS0_WRITE()
#define TK(id)
#define TSW(id)

struct Params {
  CUtensorMap x128, x64, wkv, wq, wo, out, out16, wg, wu, phi, tg, tu, td;
  const bf16 *x, *wqkv, *wo_p, *wg_p, *wu_p, *wd_p, *wr;
  bf16* out_p;
  Scratch* g;
};

__device__ __forceinline__ void ffn_prefetch(const Params& P, int c, int step) {
  #pragma unroll 1
  for (int i = PFM * step; i < PFM * step + PFM; i++)
    if ((uint32_t)i < 24u) bulk_prefetch((i >= 16 ? P.wd_p + (size_t)(i - 16) * 458752 : ((i & 1) ? P.wu_p : P.wg_p) + (size_t)(i >> 1) * 458752) + c * 3584, 7168);
}
__device__ __forceinline__ void ffn_touch(const Params& P, uint32_t sb, int c, int step) {
  if (c >= NFFN) return;
  #pragma unroll 1
  for (int i = PFN * step; i < PFN * step + PFN; i++) {
    if ((uint32_t)i < 32u) tma_2d(sb + OFF_T, (c & 1) ? &P.tu : &P.tg, 32 * (c & ~1), 32 * i, sb + B_T);
    else if ((uint32_t)i < 40u) tma_2d(sb + OFF_T, &P.td, 0, 256 * c + 32 * (i - 32), sb + B_T);
  }
}
constexpr float EXP_LIM = 1.1529215e18f, ARG_LIM2 = 3600.f;
__device__ __forceinline__ void dual_exp2(const float (&p)[2][16], uint32_t (&ph)[4][8]) {
  #pragma unroll
  for (int h = 0; h < 2; h++)
    #pragma unroll
    for (int k = 0; k < 8; k++) { ph[2*h][k] = pack_bf16(ex2(p[h][2*k]), ex2(p[h][2*k+1])); ph[2*h+1][k] = pack_bf16(ex2(-p[h][2*k]), ex2(-p[h][2*k+1])); }
}
__device__ __forceinline__ void row_extremes(const float (&p)[16], const float (&c)[2], float (&m)[4]) {
  m[0] = m[2] = p[0]; m[1] = m[3] = p[2];
  #pragma unroll
  for (int i = 0; i < 16; i++) { m[(i >> 1) & 1] = fmaxf(m[(i >> 1) & 1], p[i]); m[2 + ((i >> 1) & 1)] = fminf(m[2 + ((i >> 1) & 1)], p[i]); }
  #pragma unroll
  for (int o = 1; o < 4; o <<= 1) {
    m[0] = fmaxf(m[0], __shfl_xor_sync(~0u, m[0], o)); m[1] = fmaxf(m[1], __shfl_xor_sync(~0u, m[1], o));
    m[2] = fminf(m[2], __shfl_xor_sync(~0u, m[2], o)); m[3] = fminf(m[3], __shfl_xor_sync(~0u, m[3], o));
  }
  m[0] *= -c[0]; m[1] *= -c[1]; m[2] *= c[0]; m[3] *= c[1];
}
__device__ __forceinline__ void dual_exp2_shifted(const float (&p)[2][16], uint32_t (&ph)[4][8]) {
  #pragma unroll
  for (int h = 0; h < 2; h++) {
    const float one[2] = {1.f, 1.f};
    float m[4];
    row_extremes(p[h], one, m);
    #pragma unroll
    for (int k = 0; k < 8; k++) {
      ph[2*h][k] = pack_bf16(ex2(p[h][2*k] + m[k & 1]), ex2(p[h][2*k+1] + m[k & 1]));
      ph[2*h+1][k] = pack_bf16(ex2(m[2 + (k & 1)] - p[h][2*k]), ex2(m[2 + (k & 1)] - p[h][2*k+1]));
    }
  }
}
__device__ __forceinline__ void row_sums(float (&s)[4][4], const uint32_t (&ph)[4][8], uint32_t ones) {
  #pragma unroll
  for (int i = 0; i < 4; i++) wgmma_rz_n8<0, H0>(s[i], ph[i][0], ph[i][1], ph[i][2], ph[i][3], ones);
  #pragma unroll
  for (int i = 0; i < 4; i++) wgmma_ra_n8<0, H0>(s[i], ph[i][4], ph[i][5], ph[i][6], ph[i][7], ones);
}
__device__ __forceinline__ uint32_t mul_bf16x2(uint32_t a, uint32_t b) { uint32_t r; asm("mul.rn.bf16x2 %0, %1, %2;" : "=r"(r) : "r"(a), "r"(b)); return r; }
__device__ __forceinline__ void normalize(uint32_t (&ph)[4][8], const float (&s)[4][4]) {
  #pragma unroll
  for (int i = 0; i < 4; i++) {
    const float i0 = rcp(s[i][0]), i1 = rcp(s[i][2]);
    const uint32_t n0 = pack_bf16(i0, i0), n1 = pack_bf16(i1, i1);
    #pragma unroll
    for (int k = 0; k < 4; k++) { ph[i][2*k] = mul_bf16x2(ph[i][2*k], n0); ph[i][2*k+1] = mul_bf16x2(ph[i][2*k+1], n1); }
  }
}
__device__ __forceinline__ void split_bf16(float a, float b, uint32_t& hi, uint32_t& lo) { hi = pack_bf16(a, b); lo = pack_bf16(a - bf_lo(hi), b - bf_hi(hi)); }
__device__ __forceinline__ void put_colsums(uint32_t base, int lane, float a, float b, float c, float d) {
  uint32_t h0, l0, h1, l1;
  split_bf16(a, b, h0, l0); split_bf16(c, d, h1, l1);
  const uint32_t ad = base + (lane >> 1) * 128 + (lane & 1) * 8;
  sts64(ad, h0, h1); sts64(ad + 16, l0, l1); sts64(ad + 32, h0, h1); sts64(ad + 48, l0, l1);
  sts128(base + (lane >> 1) * 128 + 64 + (lane & 1) * 32, 0, 0, 0, 0); sts128(base + (lane >> 1) * 128 + 80 + (lane & 1) * 32, 0, 0, 0, 0);
}
__device__ __forceinline__ float reduce8(const float (&v)[8], int lane) {
  const bool b4 = lane & 16, b3 = lane & 8, b2 = lane & 4;
  float a[4], b[2];
  #pragma unroll
  for (int i = 0; i < 4; i++) a[i] = (b4 ? v[4 + i] : v[i]) + __shfl_xor_sync(~0u, b4 ? v[i] : v[4 + i], 16);
  #pragma unroll
  for (int i = 0; i < 2; i++) b[i] = (b3 ? a[2 + i] : a[i]) + __shfl_xor_sync(~0u, b3 ? a[i] : a[2 + i], 8);
  return (b2 ? b[1] : b[0]) + __shfl_xor_sync(~0u, b2 ? b[0] : b[1], 4);
}
__device__ __forceinline__ bool tag_bad(uint4 v, uint32_t tg) { return (((v.x ^ tg) | (v.y ^ tg) | (v.z ^ tg) | (v.w ^ tg)) & 3) != 0; }

__device__ __forceinline__ int g2_kblock(int i, int p) { return 2 * ((2 * p + i) & 7) + (i >> 3); }

__global__ void __launch_bounds__(512, 1) fused_kernel(const __grid_constant__ Params P) {
  extern __shared__ __align__(1024) uint8_t smem_raw[];
  const uint32_t sb = smem_u32(smem_raw);
  const int tid = threadIdx.x, lane = tid & 31;
  const int warp = __shfl_sync(~0u, tid >> 5, 0), wg = warp >> 2, wp = warp & 3;
  const int c = blockIdx.x, rank = c & 1;
  const int m256 = c >> 4, nkv = c & 15, m128 = c >> 3, j = c & 7;
  const int ha = 4 * (nkv >> 1) + (nkv & 1);

  Scratch* const G = P.g;
  if ((sb & 0x3ffff) != SB0) asm volatile("trap;");

  TS0_DECL();
  if (warp == 12) {
    const bool el = elect_one();
    TS0_READ();
    if (el) {
      #pragma unroll
      for (int i = 0; i < 4; i++) mbar_init(sb + B_FULLKV + 8 * i, 1);
      asm volatile("fence.mbarrier_init.release.cluster;" ::: "memory");
      fence_async_smem();
      #pragma unroll
      for (int s = 0; s < NPRE; s++) {
        const uint32_t st = sb + s * KV_STAGE, fb = sb + B_FULLKV + 8 * s;
        mbar_expect_tx(fb, KV_STAGE);
        tma_4d(st + 32768, &P.wkv, 0, 64 * s, nkv, 1, fb);
        tma_2d(st, &P.x128, 64 * s, 256 * m256, fb);
        tma_2d(st + 16384, &P.x128, 64 * s, 256 * m256 + 128, fb);
      }
    }
  } else if (tid == 0) {
    #pragma unroll
    for (int i = 0; i < 22; i++) mbar_init(sb + B_EMPTYKV + 8 * i, i == 20 ? 8 : i < 4 ? 12 : (i >= 9 && i < 14) ? 5 : i == 17 || i == 18 ? 2 : 1);
    #pragma unroll
    for (int i = 0; i < 7; i++) mbar_init(sb + B_F + 8 * i, 1);
    #pragma unroll
    for (int i = 0; i < 15; i++) mbar_init(sb + B_FULLA + 8 * i, i < 10 ? 5 : i < 12 ? 1 : i < 14 ? 4 : 8);
    asm volatile("fence.mbarrier_init.release.cluster;" ::: "memory");
    fence_async_smem();
  }
  __syncthreads();
  cluster_arrive();

  if (wg == 3) {
    asm volatile("setmaxnreg.dec.sync.aligned.u32 32;");
    cluster_wait();
    const bool el = elect_one();
    const uint64_t ef = policy_evict_first();
    auto fetch_o = [&](int i0, int i1, int s, int u) {
      uint32_t ready = 0;
      const bf16* hint = G->o + (m128 * 16 + 2 * (lane >> 2) + (i0 >> 3)) * 8192 + rank * 4096 + (lane & 3) * 1024 + 1022;
      #pragma unroll 1
      for (int i = i0; i < i1; i++) {
        const int kb = g2_kblock(i, j >> 1);
        uint32_t it = 0;
        while (((ready >> (2 * (kb & ~1))) & 15) != 15 && ++it < POLL_LIMIT) ready = __ballot_sync(~0u, ld32_rlx(hint) != ~0u);
        if (i == 8) bar_sync(NB_L0, 64);
        mbar_wait(sb + B_EMPTY5 + 8 * s, (u - 1) & 1);
        if (el) {
          bulk_g2s_mc(sb + s * R5 + rank * 8192, G->o + (m128 * 16 + kb) * 8192 + rank * 4096, 8192, sb + B_FULLA + 16 * s + 8 * rank, ef);
          if (i == 2) TS(rank ? 4 : 12);
          if (i == 8) TS(rank ? 9 : 13);
        }
        if (++s == 5) { s = 0; u++; }
      }
    };
    if (wp == 0) {
      #pragma unroll 1
      for (int kb = NPRE; kb < 16; kb++) {
        const int s = kb & 3;
        const uint32_t st = sb + s * KV_STAGE, fb = sb + B_FULLKV + 8 * s;
        if (kb >= 4) mbar_wait(sb + B_EMPTYKV + 8 * s, ((kb >> 2) - 1) & 1);
        if (el) {
          mbar_expect_tx(fb, KV_STAGE);
          tma_2d_mc(st + rank * 16384, &P.x128, 64 * kb, 256 * m256 + 128 * rank, fb);
          tma_4d_h(st + 32768, &P.wkv, 0, 64 * kb, nkv, 1, fb, ef);
          if (kb >= 4 && kb < 8) {
            bulk_prefetch(P.wqkv + (size_t)(256 * (kb - 4) + c) * (3 * DM), 2048); bulk_prefetch(P.wqkv + (size_t)(256 * (kb - 4) + 128 + c) * (3 * DM), 2048);
            if (PWO == 4) bulk_prefetch(P.wo_p + (size_t)c * 8192 + (kb - 4) * 2048, 4096);
          }
          if (PWO != 4 && kb >= PWO && kb < PWO + 2) bulk_prefetch(P.wo_p + (size_t)c * 8192 + (kb - PWO) * 4096, 8192);
          ffn_prefetch(P, c, kb - PFK);
          ffn_touch(P, sb, c, kb - TFK);
        }
      }
      TS0_WRITE();
      int s = 0, u = 0;
      #pragma unroll 1
      for (int i = 0; i < 16; i++) {
        const uint32_t st = sb + s * R5, fb = sb + B_FULL5 + 8 * s, eb = sb + B_EMPTY5 + 8 * s;
        mbar_wait(u ? eb : sb + B_EMPTYKV + 8 * ((2 * i + 1) / 3), u ? (u - 1) & 1 : 1);
        if (el) {
          mbar_expect_tx(fb, R5);
          const int kb = (4 * (j >> 1) + (i < 11 ? i + 4 : (0xf3120 >> (4 * i - 44)))) & 15;
          tma_2d_mc(st + rank * 8192, &P.x64, 64 * kb, 128 * m128 + 64 * rank, fb);
          tma_3d_h(st + 16384, &P.wq, 0, 64 * kb, 2 * j, fb, ef);
          mbar_arrive(eb);
          ffn_prefetch(P, c, 16 - PFK + i);
          ffn_touch(P, sb, c, 16 - TFK + i);
        }
        if (++s == 5) { s = 0; u++; }
      }
      #pragma unroll 1
      for (int i = 0; i < 16; i++) {
        const uint32_t st = sb + s * R5, fb = sb + B_FULL5 + 8 * s, eb = sb + B_EMPTY5 + 8 * s;
        if (el) ffn_prefetch(P, c, 32 - PFK + i);
        mbar_wait(eb, (u - 1) & 1);
        if (el) {
          mbar_expect_tx(fb, 16384);
          const int kb = g2_kblock(i, j >> 1);
          tma_4d_h(st + 16384, &P.wo, 0, 128 * (kb >> 1) + 32 * (kb & 1), 0, 2 * j, fb, ef);
          const uint32_t fa = sb + B_FULLA + 16 * s;
          if (i == rank) { mbar_arrive(fa); mbar_arrive(fa + 8); }
          else { mbar_expect_tx(fa, 8192); mbar_expect_tx(fa + 8, 8192); mbar_arrive_n(fa, 4); mbar_arrive_n(fa + 8, 4); }
          if (i >= 2) mbar_arrive(eb);
          if (i == 0 || i == FQ1) mbar_arrive(sb + B_QL);
        }
        if (++s == 5) { s = 0; u++; }
      }
      if (c < NFFN) {
        #pragma unroll 1
        for (int i = 2; i < 6; i++) {
          const int ch = i >> 1;
          const uint32_t st = sb + (1 + ch) * R5 + (i & 1) * 16384, fb = sb + B_F + 8 * i;
          if (!(i & 1)) mbar_wait(sb + B_EMPTY5 + 8 * (1 + ch), 1);
          if (i == PZ) mbar_wait(sb + B_F + 48, 0);
          mbar_wait(fb - 16, 0);
          if (el) { mbar_expect_tx(fb, 16384); tma_2d(st, (i & 1) ? &P.wu : &P.wg, 32 * c, 256 + 256 * ch, fb); }
        }
      }
    } else if (wp == 3) {
      if (el) {
        mbar_expect_tx(sb + B_W, 12288);
        #pragma unroll 1
        for (int i = 0; i < 6; i++) tma_2d(sb + (i == 0 ? OFF_WPHIK : i == 1 ? OFF_WPHIK1 : OFF_WPHIQ + 2048 * (i - 2)), &P.phi, 0, 32 * (i < 2 ? 2 * nkv + i : 4 * j + 2 * (i & 1) + ((i - 2) >> 1)), sb + B_W);
        prefetch_map(&P.x64); prefetch_map(&P.wq); prefetch_map(&P.wo);
        prefetch_map(&P.out); prefetch_map(&P.wg); prefetch_map(&P.wu);
      }
      const uint32_t ep1 = ld32_rlx(&G->epoch) + 1, nt = (ep1 + 2) & 3;
      #pragma unroll 1
      for (int i = lane; i < 128; i += 32) st128_rlx(&G->part[c * 128 + i], nt, nt, nt, nt);
      #pragma unroll 1
      for (int i = 0; i < 8; i++) {
        st128_rlx(&G->cand[(m128 * 8 + i) * (DM + 32) + 128 * j + 4 * lane], nt, nt, nt, nt);
        if (c < NFFN) st128_rlx(&G->ypart[c * DM + 128 * i + 4 * lane], nt, nt, nt, nt);
      }
      if (lane < 16 && j == 0) st128_rlx(&G->cand[(m128 * 8 + (lane >> 1)) * (DM + 32) + DM + 4 * (lane & 1)], nt, nt, nt, nt);
      if (lane < 8) st128_rlx(&G->key[(4 * j + (lane >> 1)) * 128 + m128 * 8 + 4 * (lane & 1)], nt, nt, nt, nt);
      if (c < 32) {
        #pragma unroll 1
        for (int i = lane; i < KVP; i += 32) st128_rlx(&G->kvacc[(ha + 2 * m256) * KVP + i], 0, 0, 0, 0);
      }
      fence_gpu();
      bar_arrive(NB_ZERO, 160);
      mbar_wait(sb + B_AUXQ, 0);
      for (uint32_t it = 0; __any_sync(~0u, ld32_rlx(&G->oset[m128 * 32 + (lane & 15)]) != ep1) && it < POLL_LIMIT; it++) {}
      fence_acquire_gpu();
      bar_arrive(NB_G2E, 64);
      mbar_wait2(sb + B_FULLA + 16 + 8 * rank, 0, sb + B_FULLA + 32 + 8 * rank, 0);
      fetch_o(2, 8, 3, 3);
      bar_arrive(NB_L0, 64);
    } else {
      const int half = wp - 1;
      const uint32_t ep1 = ld32_rlx(&G->epoch) + 1, tg = ep1 & 3;
      {
        uint32_t it = 0;
        sts128(sb + OFF_ONES + half * 512 + lane * 16, 0x3f803f80u, 0x3f803f80u, 0x3f803f80u, 0x3f803f80u);
        mbar_wait(sb + B_W, 0);
        #pragma unroll 1
        for (int i = lane; i < 1024; i += 32) { st128_rlx(G->o + (m128 * 16 + 2 * j + half) * 8192 + 8 * i, ~0u, ~0u, ~0u, ~0u); __nanosleep(RST_STEP); }
        bar_sync(NB_PUB, 192);
        const uint4* src = reinterpret_cast<const uint4*>(&G->stats[256 * m256 + 128 * half]) + lane;
        const uint4* srk = reinterpret_cast<const uint4*>(&G->cskv[128 * nkv]) + lane;
        uint4 v0, v1, vk;
        it = 0;
        do { v0 = ld128_rlx(src); v1 = ld128_rlx(src + 32); vk = ld128_rlx(srk); }
        while ((tag_bad(v0, tg) || tag_bad(v1, tg) || tag_bad(vk, tg)) && ++it < POLL_LIMIT);
        fence_acquire_gpu();
        if (half) put_colsums(sb + OFF_BXK, lane, untag(vk.x), untag(vk.y), untag(vk.z), untag(vk.w));
        #pragma unroll
        for (int i = 0; i < 2; i++) {
          const uint4 v = i ? v1 : v0;
          uint32_t hi, lo;
          split_bf16(-0.5f * untag(v.x), -0.5f * untag(v.z), hi, lo);
          const uint32_t h0 = __byte_perm(hi, hi, 0x1010), h1 = __byte_perm(hi, hi, 0x3232), l0 = __byte_perm(lo, lo, 0x1010), l1 = __byte_perm(lo, lo, 0x3232);
          const uint32_t a = sb + OFF_AXK + half * 2048 + i * 1024 + lane * 32;
          sts128(a, h0, l0, 0, 0); sts128(a + 16, h1, l1, 0, 0);
          sts64(sb + OFF_RS256 + half * 512 + i * 256 + lane * 8, v.y & ~3u, v.w & ~3u);
          if (half == (m128 & 1)) {
            const uint32_t aq = sb + OFF_AXQ + i * 1024 + lane * 32;
            sts128(aq, h0, l0, 0, 0); sts128(aq + 16, h1, l1, 0, 0);
            sts64(sb + OFF_RSQ + i * 256 + lane * 8, v.y & ~3u, v.w & ~3u);
          }
        }
        fence_async_smem();
        __syncwarp();
        if (el) { sts32(sb + OFF_EP, ep1); mbar_arrive(sb + B_AUX); if (!half) TS(1); }
        fence_gpu();
        __syncwarp();
        if (el) { st32_rlx(&G->oset[m128 * 32 + 2 * j + half], ep1); if (half) mbar_arrive(sb + B_AUXQ); }
        if (!half) {
          const uint4* src = reinterpret_cast<const uint4*>(&G->csq[128 * j]) + lane;
          uint4 v0, v1, v2, v3;
          do { v0 = ld128_rlx(src); v1 = ld128_rlx(src + DM / 4); v2 = ld128_rlx(src + DM / 2); v3 = ld128_rlx(src + 3 * DM / 4); }
          while ((tag_bad(v0, tg) || tag_bad(v1, tg) || tag_bad(v2, tg) || tag_bad(v3, tg)) && ++it < POLL_LIMIT);
          put_colsums(sb + OFF_BXQ, lane, (untag(v0.x) + untag(v1.x)) + (untag(v2.x) + untag(v3.x)), (untag(v0.y) + untag(v1.y)) + (untag(v2.y) + untag(v3.y)),
                      (untag(v0.z) + untag(v1.z)) + (untag(v2.z) + untag(v3.z)), (untag(v0.w) + untag(v1.w)) + (untag(v2.w) + untag(v3.w)));
          fence_async_smem();
          __syncwarp();
          if (el) mbar_arrive(sb + B_AUXQ);
        }
      }
      if (half == 0) bar_sync(NB_G2E, 64);
      else if (c < NFFN) {
        mbar_wait2(sb + B_KD, 0, sb + B_QL, 0);
        if (el) { mbar_expect_tx(sb + B_X, R5); tma_2d(sb + OFF_X, &P.wg, 32 * c, 0, sb + B_X); tma_2d(sb + OFF_X + 16384, &P.wu, 32 * c, 0, sb + B_X); }
      }
      {
        #pragma unroll 1
        for (int hh = 0; hh < 2; hh++) {
          const uint32_t src = sb + (half ? (hh ? OFF_KVZ : OFF_WPHI) : (1 + rank) * R5 + hh * 8192), fa = sb + (half ? B_UB : B_FULLA + 16 + 16 * rank) + 8 * hh;
          mbar_wait(fa, 0);
          if (el) {
            bulk_s2g(G->o + (m128 * 16 + 2 * j + half) * 8192 + hh * 4096, src, 8192);
            if (!half) bulk_s2peer(mapa(src, rank ^ 1), src, 8192, mapa(fa, rank ^ 1));
          }
        }
        if (el) {
          bulk_commit(); bulk_wait_read();
          if (!half) { mbar_arrive_at(sb + B_EMPTY5 + 8 + 8 * rank, 0, 1); mbar_arrive_at(sb + B_EMPTY5 + 8 + 8 * rank, 1, 1); }
        }
        __syncwarp();
      }
      if (!half) fetch_o(8, 16, 4, 4);
      else if (c < NFFN) {
        mbar_wait(sb + B_QL, 1);
        if (el) {
          mbar_expect_tx(sb + B_F, 16384); tma_2d(sb + OFF_S, &P.wg, 32 * c, 256, sb + B_F);
          mbar_expect_tx(sb + B_F + 8, 16384); tma_2d(sb + OFF_S + 16384, &P.wu, 32 * c, 256, sb + B_F + 8);
        }
      }
      __syncwarp();
      if (half == 0) {
        bar_sync(NB_OUT, 288);
        bar_sync(NB_XS, 416);
        const int row = (int)__float_as_uint(ldsf(sb + OFF_KEY)) - 128 * m128;
        if ((uint32_t)row >= 128u) {
          if (el) tma_store_3d_h(&P.out, 0, 128 * m128, 2 * j, sb + R5, ef);
        } else {
          #pragma unroll 1
          for (int i = 0; i < 16; i++)
            if (el && (i & 7) != (row >> 4)) tma_store_2d_h(&P.out16, 128 * j + 64 * (i >> 3), 128 * m128 + 16 * (i & 7), sb + R5 + 2048 * i, ef);
          #pragma unroll 1
          for (int i = 0; i < 8; i++) {
            const int r = (row & ~15) + 2 * i + (lane >> 4), ch = lane & 15;
            const uint4 v = lds128(sb + R5 + (ch >> 3) * 16384 + r * 128 + (((ch & 7) ^ (r & 7)) << 4));
            if (r != row) *reinterpret_cast<uint4*>(P.out_p + (size_t)(128 * m128 + r) * DM + 128 * j + 8 * ch) = v;
          }
        }
        if (el) { bulk_commit(); bulk_wait_all(); }
      }
    }
    __syncwarp();
    cluster_arrive(); cluster_wait();
    return;
  }

  asm volatile("setmaxnreg.inc.sync.aligned.u32 160;");
  cluster_wait();
  const int t = tid & 127, g = lane >> 2;
  const uint32_t sa = (16 * wp + (lane & 15)) * 128 + (((lane >> 4) ^ (lane & 7)) << 4);

  if (wg == 2) {
    float s[2] = {0.f, 0.f}, s2[2] = {0.f, 0.f}, ck[8] = {0.f, 0.f, 0.f, 0.f, 0.f, 0.f, 0.f, 0.f}, cs[8] = {0.f, 0.f, 0.f, 0.f, 0.f, 0.f, 0.f, 0.f};
    const uint32_t ebr = mapa(sb + B_EMPTYKV, lane & 1), tg = (ld32_rlx(&G->epoch) + 1) & 3;
    auto addx = [&](const uint4 v) {
      const uint32_t w[4] = {v.x, v.y, v.z, v.w};
      #pragma unroll
      for (int e = 0; e < 4; e++) { const float a = bf_lo(w[e]), d = bf_hi(w[e]); s[0] += a; s[1] += d; s2[0] = fmaf(a, a, s2[0]); s2[1] = fmaf(d, d, s2[1]); }
    };
    auto addc = [&](const uint4 v, float (&o)[8]) {
      o[0] += bf_lo(v.x); o[1] += bf_hi(v.x); o[2] += bf_lo(v.y); o[3] += bf_hi(v.y); o[4] += bf_lo(v.z); o[5] += bf_hi(v.z); o[6] += bf_lo(v.w); o[7] += bf_hi(v.w);
    };
    {
      const uint32_t ra = (16 * nkv + (t >> 3)) * 128 + (t & 7) * 16;
      const uint32_t ca = 32768 + (m256 >> 2) * 8192 + (t >> 1) * 128 + (((2 * (m256 & 3) + (t & 1)) ^ ((t >> 1) & 7)) << 4);
      const bf16* gx = P.x + (size_t)(256 * m256 + 16 * nkv + (t >> 3)) * DM + 640 + (t & 7) * 8;
      const bf16* gw = P.wqkv + (size_t)(640 + (t >> 1)) * (3 * DM) + (1 + (m256 >> 2)) * DM + 64 * nkv + 16 * (m256 & 3) + 8 * (t & 1);
      uint4 u[4];
      #pragma unroll
      for (int e = 0; e < 4; e++) u[e] = make_uint4(0, 0, 0, 0);
      #pragma unroll 1
      for (int kb = 0; kb < 10; kb++) {
        const uint32_t st = sb + (kb & 3) * KV_STAGE;
        mbar_wait(sb + B_FULLKV + 8 * (kb & 3), (kb >> 2) & 1);
        const uint4 x0 = lds128(st + ra), w0 = lds128(st + ca);
        addx(x0); addc(w0, ck);
        __syncwarp();
        if (lane < 2) mbar_arrive_remote(ebr + 8 * (kb & 3), 1);
        if ((SKM >> kb) & 1) {
          addx(u[0]); addx(u[1]); addc(u[2], ck); addc(u[3], ck);
          if (kb < 9) {
            u[0] = ld128_keep(gx); u[1] = ld128_keep(gx + 64); u[2] = ld128_keep(gw); u[3] = ld128_keep(gw + 64 * 3 * DM);
            gx += 128; gw += 128 * 3 * DM;
          }
        }
      }
    }
    TK(82);
    const uint32_t scr = sb + OFF_SCR + 128;
    float sx = s[0] + s[1], sq = s2[0] + s2[1];
    #pragma unroll
    for (int o = 1; o < 8; o <<= 1) { sx += __shfl_xor_sync(~0u, sx, o); sq += __shfl_xor_sync(~0u, sq, o); }
    float v = reduce8(ck, lane);
    v += __shfl_xor_sync(~0u, v, 2);
    if (!(lane & 2)) stsf(scr + (wp * 16 + 8 * (lane & 1) + (lane >> 2)) * 4, v);

    bar_sync(NB_ZERO, 160);
    if ((lane & 7) == 0) {
      const float mean = sx * (1.f / DM);
      st64_rlx(&G->stats[256 * m256 + 16 * nkv + (t >> 3)], tagw(mean, tg), tagw(rsqrtf(fmaxf(sq * (1.f / DM) - mean * mean, 0.f) + 1e-5f), tg));
    }
    if (wp == 1 && lane < 16) {
      const uint32_t a = scr + lane * 4;
      st32_rlx(&G->cskv[128 * nkv + 16 * m256 + lane], tagw((ldsf(a) + ldsf(a + 64)) + (ldsf(a + 128) + ldsf(a + 192)), tg));
    }
    __syncwarp();
    bar_arrive(NB_PUB, 192);
    TSW(23);
    const uint4 wv = ld128_keep(P.wr + t * 8);
    #pragma unroll 1
    for (int i = 0; i < 2; i++) {
      const bf16* gq = P.wqkv + (size_t)(256 * (c >> 5) + 128 * i + (t >> 2)) * (3 * DM) + 32 * (c & 31) + 8 * (t & 3);
      const uint4 u0 = ld128_keep(gq), u1 = ld128_keep(gq + 32 * 3 * DM), u2 = ld128_keep(gq + 64 * 3 * DM), u3 = ld128_keep(gq + 96 * 3 * DM);
      addc(u0, cs); addc(u1, cs); addc(u2, cs); addc(u3, cs);
    }
    float sw = (bf_lo(wv.x) + bf_hi(wv.x)) + (bf_lo(wv.y) + bf_hi(wv.y)) + (bf_lo(wv.z) + bf_hi(wv.z)) + (bf_lo(wv.w) + bf_hi(wv.w));
    #pragma unroll
    for (int o = 16; o; o >>= 1) sw += __shfl_xor_sync(~0u, sw, o);
    if (lane == 0) stsf(sb + OFF_SUMWR + wp * 4, sw);
    if ((t >> 4) == j) {
      const uint32_t a = sb + OFF_WR + (t & 15) * 32;
      sts128(a, wv.x << 16, wv.x & 0xffff0000u, wv.y << 16, wv.y & 0xffff0000u);
      sts128(a + 16, wv.z << 16, wv.z & 0xffff0000u, wv.w << 16, wv.w & 0xffff0000u);
    }
    v = reduce8(cs, lane);
    bar_sync(NB_WG2, 128);
    stsf(scr + (wp * 32 + 8 * (lane & 3) + (lane >> 2)) * 4, v);
    bar_sync(NB_WG2, 128);
    if (wp == 0) {
      const uint32_t a = scr + lane * 4;
      st32_rlx(&G->csq[(c >> 5) * DM + 32 * (c & 31) + lane], tagw((ldsf(a) + ldsf(a + 128)) + (ldsf(a + 256) + ldsf(a + 384)), tg));
    }
    TSW(15);
  }

  uint32_t xr[32];
  {
    const bool isq = wg == 2;
    float acc[2][64];
    {
      const uint32_t emptyb = mapa(sb + (isq ? B_EMPTY5 : B_EMPTYKV), t & 1);
      if (!isq) {
        mbar_wait(sb + B_FULLKV, 0);
        if (wg == 0) { TSW(2); }
        #pragma unroll 1
        for (int kb = 0; kb < 16; kb++) {
          if (wg == 0) { TK(kb); }
          const uint32_t da = dlo(SB0, 16) + wg * 1024 + (kb & 3) * (KV_STAGE >> 4), db = dlo(SB0 + 32768, 8192) + (kb & 3) * (KV_STAGE >> 4);
          wg_fence();
          #pragma unroll
          for (int k = 0; k < 4; k++) {
            wgmma_ss_n128<0, 1, H128, H128>(acc[0], da + 2 * k, db + 128 * k, k > 0 || kb != 0);
            wgmma_ss_n128<0, 1, H128, H128>(acc[1], da + 512 + 2 * k, db + 128 * k, k > 0 || kb != 0);
          }
          wg_commit();
          wg_wait<1>();
          if (kb > 0 && t < 2) mbar_arrive_remote(emptyb + 8 * ((kb - 1) & 3), kb > 10 ? 3 : 1);
          if (kb < 15) mbar_wait(sb + B_FULLKV + 8 * ((kb + 1) & 3), ((kb + 1) >> 2) & 1);
          if (kb == 15 - LAG && wg == 1) bar_sync(NB_WG01, 256);
        }
        bar_arrive(wg ? NB_QGO : NB_WG01, 256);
      } else {
        uint32_t so = 0, po = 0, par = 0;
        mbar_wait(sb + B_FULL5, 0);
        bar_sync(NB_QGO, 256);
        TSW(11);
        #pragma unroll 1
        for (int kb = 0; kb < 16; kb++) {
          TK(16 + kb);
          const uint32_t da = dlo(SB0, 16) + so * 256, db = dlo(SB0 + 16384, 8192) + so * 256;
          #pragma unroll
          for (int k = 0; k < 4; k++) {
            if (QG == 1 || !(k & 1)) wg_fence();
            wgmma_ss_n128<0, 1, H128, H128>(acc[0], da + 2 * k, db + 128 * k, k > 0 || kb != 0);
            wgmma_ss_n128<0, 1, H128, H128>(acc[1], da + 512 + 2 * k, db + 128 * k, k > 0 || kb != 0);
            if (QG == 1 || (k & 1)) {
              wg_commit();
              if (k == 3) {
                po = so; so += 8;
                if (so == 40) { so = 0; par ^= 1; }
                if (kb < 15) mbar_wait(sb + B_FULL5 + so, par);
                if (kb == 13 && t == 0) mbar_arrive(sb + B_R);
              }
              wg_wait<1>();
              if (k == QG - 1 && kb > 0 && t < 2) mbar_arrive_remote(emptyb + po, 2);
            }
          }
        }
        mbar_wait2(sb + B_AUXQ, 0, sb + B_RC, 0);
      }
      mbar_wait(sb + B_AUX, 0);
      const uint32_t xa = dlo(SB0, 0) + (isq ? OFF_AXQ >> 4 : (OFF_AXK >> 4) + wg * 128), xb = dlo(SB0, 0) + (isq ? OFF_BXQ >> 4 : OFF_BXK >> 4);
      wg_fence();
      wgmma_sa_n128<0, 1, H0, H0>(acc[0], xa, xb);
      wgmma_sa_n128<0, 1, H0, H0>(acc[1], xa + 64, xb);
      wg_commit();
      wg_wait<0>();
      if (t < 2) mbar_arrive_remote(emptyb + (isq ? 0 : 24), isq ? 2 : 3);
      if (wg != 1) { TSW(wg ? 8 : 3); }
      fence_regs(acc[0]); fence_regs(acc[1]);
    }
    if (isq) {
      #pragma unroll
      for (int i = 0; i < 2; i++) {
        const uint32_t ta = sb + (1 + rank) * R5 + sa + i * 8192;
        #pragma unroll
        for (int k = 0; k < 4; k++) {
          const float* a = &acc[i][32 * (k >> 1) + 8 * (k & 1)];
          stsm4(ta ^ (k << 5), pack_bf16(a[0], a[1]), pack_bf16(a[2], a[3]), pack_bf16(a[4], a[5]), pack_bf16(a[6], a[7]));
        }
        fence_async_smem();
        bar_arrive(NB_Q0 + i, 256);
      }
      #pragma unroll
      for (int i = 0; i < 32; i++) { const float* a = &acc[i >> 4][16 + 32 * ((i >> 3) & 1) + 2 * (i & 7)]; xr[i] = pack_bf16(a[0], a[1]); }
      TSW(26);
    } else {
      const uint32_t stg = sb + OFF_X + (1 - wg) * 24576;
      const uint32_t va = stg + 16384 + (16 * wp + (lane & 15)) * 64 + (((lane >> 4) ^ ((lane >> 1) & 3)) << 4);
      const uint32_t ra = sb + OFF_RS256 + (128 * wg + 16 * wp + g) * 4;
      const float rs[4] = {ldsf(ra), ldsf(ra + 32), ldsf(ra + 256), ldsf(ra + 288)};
      float p[2][16];
      uint32_t vf[16], kf[2][16];
      auto project = [&](const uint32_t (&f)[16], uint32_t db) {
        wg_fence();
        #pragma unroll
        for (int i = 0; i < 2; i++) {
          wgmma_rs_n32<1, H64>(p[i], f[8*i], f[8*i+1], f[8*i+2], f[8*i+3], db, 0);
          wgmma_ra_n32<1, H64>(p[i], f[8*i+4], f[8*i+5], f[8*i+6], f[8*i+7], db + 64);
        }
        wg_commit();
      };
      auto fold = [&](uint32_t (&f)[16], int col, float sc) {
        #pragma unroll
        for (int i = 0; i < 16; i++) {
          const float r = rs[2 * (i >> 3) + (i & 1)] * sc;
          f[i] = pack_bf16(acc[i >> 3][col + 2 * (i & 7)] * r, acc[i >> 3][col + 2 * (i & 7) + 1] * r);
          asm volatile("" : "+r"(f[i]));
        }
      };
      auto put_v = [&](const uint32_t (&f)[16]) {
        #pragma unroll
        for (int k = 0; k < 4; k++) stsm4((va ^ ((k & 1) << 5)) + (k >> 1) * 4096, f[4*k], f[4*k+1], f[4*k+2], f[4*k+3]);
      };
      fold(vf, 48, 1.f);
      mbar_wait(sb + B_W, 0);
      fold(kf[0], 0, LOG2E);
      #pragma unroll
      for (int i = 0; i < 32; i++) p[i >> 4][i & 15] = acc[i >> 4][i & 15];
      project(kf[0], dlo(SB0 + OFF_WPHIK, 16));
      mbar_wait(sb + B_W, 0);
      {
        uint32_t v0[16];
        fold(kf[1], 16, LOG2E);
        fold(v0, 32, 1.f);
        if (wg == 1) bar_sync(NB_DN, 256);
        put_v(v0);
      }
      wg_wait<0>();
      fence_regs(p[0]); fence_regs(p[1]);
      if (wg == 1) bar_arrive(NB_WG01, 256);
      #pragma unroll 1
      for (int h = 0; h < 2; h++) {
        uint32_t ph[4][8];
        float rsum[4][4];
        dual_exp2(p, ph);
        wg_fence();
        row_sums(rsum, ph, dlo(SB0 + OFF_ONES, 128));
        wg_commit();
        if (wg == 0 && h == 0) { bar_arrive(NB_DN, 256); bar_sync(NB_WG01, 256); }
        if (h == 1) {
          if (wg == 1) bar_sync(NB_DN, 256);
          put_v(vf);
        }
        wg_wait<0>();
        #pragma unroll
        for (int i = 0; i < 4; i++) fence_regs(rsum[i]);
        if (__builtin_expect(__any_sync(~0u, !((rsum[0][0] + rsum[0][2]) + (rsum[1][0] + rsum[1][2]) + (rsum[2][0] + rsum[2][2]) + (rsum[3][0] + rsum[3][2]) < EXP_LIM)), 0)) {
          dual_exp2_shifted(p, ph);
          #pragma unroll
          for (int i = 0; i < 8; i++) {
            const uint32_t* f = &ph[i >> 1][i & 1];
            float a = (bf_lo(f[0]) + bf_hi(f[0])) + (bf_lo(f[2]) + bf_hi(f[2])) + (bf_lo(f[4]) + bf_hi(f[4])) + (bf_lo(f[6]) + bf_hi(f[6]));
            a += __shfl_xor_sync(~0u, a, 1);
            rsum[i >> 1][2 * (i & 1)] = a + __shfl_xor_sync(~0u, a, 2);
          }
        }
        if (h == 0) project(kf[1], dlo(SB0 + OFF_WPHIK1, 16));
        normalize(ph, rsum);
        #pragma unroll
        for (int i = 0; i < 8; i++) {
          const uint32_t* f = &ph[i >> 1][4 * (i & 1)];
          stsm4(((stg + sa) ^ ((i & 3) << 5)) + (i >> 2) * 8192, f[0], f[1], f[2], f[3]);
        }
        fence_async_smem();
        TK(50 + 8 * wg + 4 * h);
        if (wg == h) {
          float kv[20];
          #pragma unroll
          for (int w = 0; w < 2; w++) {
            const uint32_t da = dlo(SB0 + OFF_X, 16) + (h ^ w ^ 1) * 1536, db = dlo(SB0 + OFF_X + 16384, OFF_ONES - OFF_X - 16384) - (h ^ w ^ 1) * (1536 * 65535);
            if (w) bar_sync(NB_ST, 256); else bar_sync(NB_L0 + h, 128);
            wg_fence();
            #pragma unroll
            for (int k = 0; k < 8; k++) {
              if (k == 0 && w == 0) wgmma_sz_n40<1, 1, H128, H64>(kv, da, db);
              else wgmma_sa_n40<1, 1, H128, H64>(kv, da + k * 128, db - k * (64 * 65535));
            }
            wg_commit();
          }
          float4* dst = &G->kvacc[(ha + 2 * h) * KVP + t];
          wg_wait<0>();
          fence_regs(kv);
          TK(51 + 8 * wg + 4 * h);
          if (h == 0) bar_arrive(NB_DN, 256); else if (t == 0) mbar_arrive(sb + B_KD);
          kv[17] = kv[18];
          #pragma unroll
          for (int i = 0; i < 6; i++) red_add_f32x4(dst + 128 * i, kv[3*i], kv[3*i+1], kv[3*i+2], 1.f);
          TSW(29 + h);
        } else bar_arrive(NB_ST, 256);
        wg_wait<0>();
        fence_regs(p[0]); fence_regs(p[1]);
      }
      #pragma unroll
      for (int i = 0; i < 32; i++) asm volatile("mov.b32 %0, 0;" : "=r"(xr[i]));
    }
    if (wg != 1) {
      const uint4* src = reinterpret_cast<const uint4*>(&G->kvacc[(4 * j + wg) * KVP + t]);
      uint4 v[12];
      uint32_t it = 0;
      bool wait = false;
      do {
        while (wait && __any_sync(~0u, ((ld128_rlx(src + 128 * 5).w ^ 0x41000000u) | (ld128_rlx(src + 128 * 11).w ^ 0x41000000u)) != 0) && ++it < POLL_LIMIT) {}
        TK(48 + 4 * wg);
        uint32_t bad = 0;
        #pragma unroll
        for (int i = 0; i < 12; i++) { v[i] = ld128_rlx(src + 128 * i); bad |= v[i].w ^ 0x41000000u; }
        wait = __any_sync(~0u, bad != 0);
      } while (wait && ++it < POLL_LIMIT);
      TK(49 + 4 * wg);
      mbar_wait(sb + B_KD, 0);
      #pragma unroll
      for (int e = 0; e < 2; e++) {
        float f[18];
        #pragma unroll
        for (int i = 0; i < 6; i++) { f[3*i] = __uint_as_float(v[6*e+i].x); f[3*i+1] = __uint_as_float(v[6*e+i].y); f[3*i+2] = __uint_as_float(v[6*e+i].z); }
        const uint32_t ka = sb + OFF_KVZ + (wg + e) * 5120 + wp * 1280 + lane * 16;
        stsm4(ka, pack_bf16(f[0], f[1]), pack_bf16(f[2], f[3]), pack_bf16(f[4], f[5]), pack_bf16(f[6], f[7]));
        stsm4(ka + 512, pack_bf16(f[8], f[9]), pack_bf16(f[10], f[11]), pack_bf16(f[12], f[13]), pack_bf16(f[14], f[15]));
        stsm2(ka + 1024, pack_bf16(f[16], 1.f), pack_bf16(f[17], 1.f));
      }
    }
    if (wg != 1) { TSW(wg ? 6 : 5); }
    if (!isq) {
      mbar_wait(sb + B_R, 0);
      #pragma unroll
      for (int k = 0; k < 8; k++) ldsm4(((sb + (1 + rank) * R5 + wg * 8192 + sa) ^ ((k & 3) << 5)) + (k >> 2) * 2 * R5, xr[4*k], xr[4*k+1], xr[4*k+2], xr[4*k+3]);
      fence_async_smem();
      __syncwarp();
      if (lane == 0) mbar_arrive(sb + B_RC);
    }
    #pragma unroll 1
    for (int e = wg; e < wg + 1 + (wg >> 1); e++) {
      const int half = e >> 1, hh = e & 1, turn = e;
      const uint32_t ao = half ? (hh ? OFF_KVZ : OFF_WPHI) : (1 + rank) * R5 + hh * 8192, at = sb + ao + sa;
      if (isq) {
        if (hh) mbar_wait(sb + B_UA, 0); else bar_sync(NB_TOK + 1, 256);
        #pragma unroll
        for (int k = 0; k < 4; k++) stsm4(at ^ (k << 5), xr[4*k], xr[4*k+1], xr[4*k+2], xr[4*k+3]);
        #pragma unroll
        for (int i = 0; i < 16; i++) xr[i] = xr[16 + i];
        fence_async_smem();
      }
      float p[2][16];
      #pragma unroll
      for (int i = 0; i < 32; i++) asm volatile("mov.b32 %0, 0;" : "=f"(p[i >> 4][i & 15]));
      const float cc[2] = {ldsf(sb + OFF_RSQ + (64 * hh + 16 * wp + g) * 4) * LOG2E, ldsf(sb + OFF_RSQ + (64 * hh + 16 * wp + g + 8) * 4) * LOG2E};
      float m[2][4] = {{0.f, 0.f, 0.f, 0.f}, {0.f, 0.f, 0.f, 0.f}};
      uint32_t ph[2][8];
      auto exps = [&](int h) {
        #pragma unroll
        for (int k = 0; k < 8; k++) {
          const float c = cc[k & 1], mp = m[h][k & 1], mm = m[h][2 + (k & 1)];
          ph[0][k] = pack_bf16(ex2(fmaf(p[h][2*k], c, mp)), ex2(fmaf(p[h][2*k+1], c, mp)));
          ph[1][k] = pack_bf16(ex2(fmaf(p[h][2*k], -c, mm)), ex2(fmaf(p[h][2*k+1], -c, mm)));
        }
      };
      uint32_t shifted = 0;
      asm volatile("" : "+r"(shifted));
      #pragma unroll 1
      for (;;) {
        if (shifted) { row_extremes(p[0], cc, m[0]); row_extremes(p[1], cc, m[1]); }
        uint32_t first = shifted ^ 1;
        asm volatile("" : "+r"(first));
        if (first) {
          bar_sync(NB_Q0 + wg, isq ? 128 : 256);
          if (wg == 0) { TSW(7); }
          const uint32_t da = dlo(SB0, 16) + (ao >> 4), db = dlo(SB0 + OFF_WPHIQ, 16) + half * 256;
          wg_fence();
          #pragma unroll
          for (int h = 0; h < 2; h++) {
            wgmma_ss_n32<0, 1, H128, H64>(p[h], da + 4 * h, db + 128 * h, 0);
            wgmma_sa_n32<0, 1, H128, H64>(p[h], da + 4 * h + 2, db + 128 * h + 64);
          }
          wg_commit();
          if (wg == 1) bar_sync(NB_TOK, 256);
          wg_wait<0>();
        }
        TK(64 + 4 * turn);
        fence_regs(p[0]); fence_regs(p[1]);
        exps(0);
        float s2[4] = {0.f, 0.f, 0.f, 0.f};
        #pragma unroll
        for (int i = 0; i < 32; i++) s2[((i >> 1) & 1) + 2 * (i >> 4)] = fmaf(p[i >> 4][i & 15], p[i >> 4][i & 15], s2[((i >> 1) & 1) + 2 * (i >> 4)]);
        const float l0 = cc[0] * cc[0], l1 = cc[1] * cc[1];
        if (!__any_sync(~0u, !shifted & !((s2[0] * l0 < ARG_LIM2) & (s2[1] * l1 < ARG_LIM2) & (s2[2] * l0 < ARG_LIM2) & (s2[3] * l1 < ARG_LIM2)))) break;
        shifted = 1;
      }
      const uint32_t db = dlo(SB0 + OFF_KVZ, 128) + half * 640;
      float ac[4][20];
      auto numer = [&](int h, const uint32_t (&f)[2][8]) {
        wg_fence();
        #pragma unroll
        for (int i = 0; i < 2; i++) {
          wgmma_rz_n40<1, dhi(256, 0)>(ac[2*h+i], f[i][0], f[i][1], f[i][2], f[i][3], db + (2*h+i) * 160);
          wgmma_ra_n40<1, dhi(256, 0)>(ac[2*h+i], f[i][4], f[i][5], f[i][6], f[i][7], db + ((2*h+i) * 160 + 80));
        }
        wg_commit();
      };
      auto finish = [&](int h) {
        const float* ap = ac[2 * h]; const float* am = ac[2 * h + 1];
        const float ip0 = rcp(ap[17]), im0 = rcp(am[17]), ip1 = rcp(ap[19]), im1 = rcp(am[19]);
        const float d0 = rcp(fmaf(ap[16], ip0, fmaf(am[16], im0, 1e-6f))), d1 = rcp(fmaf(ap[18], ip1, fmaf(am[18], im1, 1e-6f)));
        const float a0 = ip0 * d0, b0 = im0 * d0, a1 = ip1 * d1, b1 = im1 * d1;
        #pragma unroll
        for (int k = 0; k < 2; k++)
          stsm4(at ^ ((2 * h + k) << 5),
                pack_bf16(fmaf(ap[8*k], a0, am[8*k] * b0),     fmaf(ap[8*k+1], a0, am[8*k+1] * b0)),
                pack_bf16(fmaf(ap[8*k+2], a1, am[8*k+2] * b1), fmaf(ap[8*k+3], a1, am[8*k+3] * b1)),
                pack_bf16(fmaf(ap[8*k+4], a0, am[8*k+4] * b0), fmaf(ap[8*k+5], a0, am[8*k+5] * b0)),
                pack_bf16(fmaf(ap[8*k+6], a1, am[8*k+6] * b1), fmaf(ap[8*k+7], a1, am[8*k+7] * b1)));
      };
      numer(0, ph);
      exps(1);
      numer(1, ph);
      if (turn < 2) bar_arrive(NB_TOK + turn, 256);
      wg_wait<1>();
      TK(65 + 4 * turn);
      fence_regs(ac[0]); fence_regs(ac[1]);
      finish(0);
      wg_wait<0>();
      fence_regs(ac[2]); fence_regs(ac[3]);
      finish(1);
      TK(66 + 4 * turn);
      fence_async_smem();
      __syncwarp();
      if (lane == 0) { mbar_arrive(sb + (half ? B_UB : B_FULLA + 16 + 16 * rank) + 8 * hh); if (!half) mbar_arrive(sb + B_UA); }
      TK(67 + 4 * turn);
    }
    if (isq) cluster_arrive();
  }

  {
  int lane;
  asm volatile("mov.u32 %0, %%laneid;" : "=r"(lane));
  const int g = lane >> 2, q = lane & 3;
  const uint32_t ep1 = __float_as_uint(ldsf(sb + OFF_EP));
  if (wg < 2) {
    const uint32_t tg = ep1 & 3;
    float h[64];
    {
      if (wg == 0) { TK(83); }
      #pragma unroll
      for (int i = 0; i < 32; i++) { h[2*i] = bf_lo(xr[i]); h[2*i+1] = bf_hi(xr[i]); }
      fence_regs(h);
      asm volatile("setmaxnreg.dec.sync.aligned.u32 128;" ::: "memory");
      TK(80 + wg);
      const uint64_t seq = rank ? 0x1043210432104312ull : 0x1043210432104321ull;
      const uint32_t emptyb = mapa(sb + B_EMPTY5, t & 1);
      uint32_t s = 1 + rank, ps = 0;
      mbar_wait2(sb + B_FULL5 + 8 * s, 1, sb + B_FULLA + 16 * s + 8 * wg, 0);
      if (wg == 0) { TSW(14); }
      #pragma unroll 1
      for (int i = 0; i < 16; i++) {
        if (wg == 1 && i < 4) { TK(84 + i); }
        if (wg == 0) { TK(32 + i); }
        const uint32_t da = dlo(SB0, 16) + s * 2048 + wg * 512, db = dlo(SB0 + 16384, 8192) + s * 2048;
        wg_fence();
        #pragma unroll
        for (int k = 0; k < 4; k++) wgmma_sa_n128<0, 1, H128, H128>(h, da + k * 2, db + k * 128);
        wg_commit();
        const uint32_t ns = (uint32_t)(seq >> (4 * i + 4)) & 15;
        wg_wait<1>();
        if (i > 0 && t < 2) mbar_arrive_remote(emptyb + 8 * ps, 1);
        if (i < 15) mbar_wait2(sb + B_FULL5 + 8 * ns, (0x1f07 >> i) & 1, sb + B_FULLA + 16 * ns + 8 * wg, (0x41f0 >> i) & 1);
        ps = s; s = ns;
      }
      wg_wait<0>();
      if (t < 2) mbar_arrive_remote(emptyb + 8 * ps, 1);
      fence_regs(h);
    }
    cluster_arrive();
    if (wg == 0) { TSW(16); }
    if (__builtin_expect(__any_sync(~0u, h[0] != h[0] || h[2] != h[2]), 0)) {
      const int r = 64 * wg + 16 * wp + g;
      #pragma unroll 1
      for (int n = 0; n < 16; n++) {
        const uint32_t* xp = reinterpret_cast<const uint32_t*>(P.x + (size_t)(128 * m128 + r) * DM + 128 * j + 8 * n) + q;
        const uint32_t x0 = xp[0], x1 = xp[4 * DM];
        float d0 = bf_lo(x0), d1 = bf_hi(x0), d2 = bf_lo(x1), d3 = bf_hi(x1);
        #pragma unroll 1
        for (int ks = 0; ks < 64; ks++) {
          const int kb = ks >> 2, kk = 16 * (ks & 3);
          const bf16* op = G->o + (m128 * 16 + kb) * 8192 + r * 64 + 2 * q;
          const int o0 = ((kk >> 3) ^ g) << 3;
          const uint16_t* w = reinterpret_cast<const uint16_t*>(P.wo_p) + (size_t)(128 * (kb >> 1) + 32 * (kb & 1) + (kk & 31) + 2 * (kk & 32) + 2 * q) * DM + 128 * j + 8 * n + g;
          const uint32_t b0 = w[0] | (w[DM] << 16), b1 = w[8 * DM] | (w[9 * DM] << 16);
          uint32_t a0, a1, a2, a3, it = 0;
          do { a0 = ld32_rlx(op + o0); a1 = ld32_rlx(op + 512 + o0); a2 = ld32_rlx(op + (o0 ^ 8)); a3 = ld32_rlx(op + 512 + (o0 ^ 8)); }
          while (max(max(a0, a1), max(a2, a3)) == ~0u && ++it < POLL_LIMIT);
          __syncwarp();
          mma16816(d0, d1, d2, d3, a0, a1, a2, a3, b0, b1);
        }
        #pragma unroll
        for (int i = 0; i < 60; i++) h[i] = h[i + 4];
        h[60] = d0; h[61] = d1; h[62] = d2; h[63] = d3;
      }
    }
    float sum0 = 0.f, sum1 = 0.f, dot0 = 0.f, dot1 = 0.f, sq0 = 0.f, sq1 = 0.f;
    #pragma unroll
    for (int i = 0; i < 16; i++) {
      const float2 w = reinterpret_cast<const float2*>(smem_raw + OFF_WR)[4 * i + q];
      sum0 += h[4*i] + h[4*i+1]; sum1 += h[4*i+2] + h[4*i+3];
      sq0 = fmaf(h[4*i], h[4*i], fmaf(h[4*i+1], h[4*i+1], sq0)); sq1 = fmaf(h[4*i+2], h[4*i+2], fmaf(h[4*i+3], h[4*i+3], sq1));
      dot0 = fmaf(h[4*i], w.x, fmaf(h[4*i+1], w.y, dot0)); dot1 = fmaf(h[4*i+2], w.x, fmaf(h[4*i+3], w.y, dot1));
    }
    const int r0 = 64 * wg + 16 * wp + g;
    {
      const bool up = q & 2;
      float a = up ? sum1 : sum0, b = up ? sq1 : sq0, d = up ? dot1 : dot0;
      a += __shfl_xor_sync(~0u, up ? sum0 : sum1, 2); b += __shfl_xor_sync(~0u, up ? sq0 : sq1, 2); d += __shfl_xor_sync(~0u, up ? dot0 : dot1, 2);
      a += __shfl_xor_sync(~0u, a, 1); b += __shfl_xor_sync(~0u, b, 1); d += __shfl_xor_sync(~0u, d, 1);
      if ((q & 1) == 0) st128_rlx(&G->part[(m128 * 8 + j) * 128 + r0 + 4 * q], tagw(a, tg), tagw(b, tg), tagw(d, tg), tg);
    }
    if (wg == 0) { TSW(24); }
    float mean, rstd, rr;
    {
      uint4 a0, a1, a2, a3; uint32_t it = 0;
      const uint4* pp = &G->part[(m128 * 8 + (q & 1)) * 128 + r0 + 4 * (q & 2)];
      do {
        a0 = ld128_rlx(pp); a1 = ld128_rlx(pp + 256); a2 = ld128_rlx(pp + 512); a3 = ld128_rlx(pp + 768);
      } while ((((a0.x ^ tg) | (a0.y ^ tg) | (a0.z ^ tg) | (a1.x ^ tg) | (a1.y ^ tg) | (a1.z ^ tg) |
                 (a2.x ^ tg) | (a2.y ^ tg) | (a2.z ^ tg) | (a3.x ^ tg) | (a3.y ^ tg) | (a3.z ^ tg)) & 3) && ++it < POLL_LIMIT);
      __syncwarp();
      float s = (untag(a0.x) + untag(a1.x)) + (untag(a2.x) + untag(a3.x));
      float s2 = (untag(a0.y) + untag(a1.y)) + (untag(a2.y) + untag(a3.y));
      float d = (untag(a0.z) + untag(a1.z)) + (untag(a2.z) + untag(a3.z));
      s += __shfl_xor_sync(~0u, s, 1); s2 += __shfl_xor_sync(~0u, s2, 1); d += __shfl_xor_sync(~0u, d, 1);
      mean = s * (1.f / DM);
      rstd = rsqrtf(fmaxf(s2 * (1.f / DM) - mean * mean, 0.f) + 1e-5f);
      const float2 swa = lds64f(sb + OFF_SUMWR), swb = lds64f(sb + OFF_SUMWR + 8);
      rr = (d - mean * ((swa.x + swa.y) + (swb.x + swb.y))) * rstd;
    }
    if (wg == 0) { TSW(17); }
    {
      const int rl = g + 4 * (q & 2);
      const uint32_t ob = __float_as_uint(rr) ^ ((uint32_t)((int32_t)__float_as_uint(rr) >> 31) | 0x80000000u);
      const uint32_t key = (ob & ~63u) | ((15 - rl) << 2) | tg;
      uint32_t best;
      asm volatile("redux.sync.max.u32 %0, %1, 0xffffffff;" : "=r"(best) : "r"(key));
      const int slot = m128 * 8 + (tid >> 5), win = 15 - ((best >> 2) & 15);
      if (lane < 4) st32_rlx(&G->key[(4 * j + lane) * 128 + slot], best);
      if ((win & 7) == g) {
        const bool up = win & 8;
        uint32_t* dst = &G->cand[slot * (DM + 32) + 128 * j + 2 * q];
        if (j == 0 && rl == win) st64_rlx(&G->cand[slot * (DM + 32) + DM], tagw(mean, tg), tagw(rstd, tg));
        #pragma unroll
        for (int i = 0; i < 16; i++) st64_rlx(dst + 8 * i, tagw(up ? h[4*i+2] : h[4*i], tg), tagw(up ? h[4*i+3] : h[4*i+1], tg));
      }
      __syncwarp();
    }
    if (wg == 0) { TSW(27); }
    if (wg == 0) bar_arrive(NB_G2E, 256);
    if (tid == 0) mbar_arrive(sb + B_F + 48);
    {
      bar_sync(NB_WG01, 256);
      const float am = 1.f + rstd, bm = -mean * rstd;
      const float a0 = __shfl_sync(~0u, am, lane & ~3), b0 = __shfl_sync(~0u, bm, lane & ~3), a1 = __shfl_sync(~0u, am, lane | 3), b1 = __shfl_sync(~0u, bm, lane | 3);
      #pragma unroll
      for (int k = 0; k < 8; k++)
        stsm4(((sb + R5 + wg * 8192 + sa) ^ ((k & 3) << 5)) + (k >> 2) * 16384,
              pack_bf16(fmaf(h[8*k], a0, b0), fmaf(h[8*k+1], a0, b0)),     pack_bf16(fmaf(h[8*k+2], a1, b1), fmaf(h[8*k+3], a1, b1)),
              pack_bf16(fmaf(h[8*k+4], a0, b0), fmaf(h[8*k+5], a0, b0)),   pack_bf16(fmaf(h[8*k+6], a1, b1), fmaf(h[8*k+7], a1, b1)));
      fence_async_smem();
      bar_arrive(NB_OUT, 288);
    }
    if (wg == 0) { TSW(28); }
    if (c < NFFN) { mbar_wait(sb + (wg ? B_F : B_X), 0); if (wg) mbar_wait(sb + B_F + 8, 0); }
    bar_sync(NB_XS, 416);
    if (wg == 0) { TSW(19); }
    if (c < NFFN) {
      float ga[4], gb[4];
      uint32_t da = dlo(SB0 + OFF_X, 16384) + wg * 2048, db = dlo(SB0 + OFF_XSEL, 16) + wg * 32;
      #pragma unroll 1
      for (int k = 0; k < 8; k++) {
        if (k == 4) { mbar_wait(sb + B_F + 16 + 16 * wg, 0); mbar_wait(sb + B_F + 24 + 16 * wg, 0); da = dlo(SB0 + 2 * R5, 16384) + wg * 2048; db += 32; }
        wg_fence();
        wgmma_ss_n8<1, 0, H64, H0>(ga, da, db, k); wgmma_ss_n8<1, 0, H64, H0>(gb, da + 64, db + 2, k);
        wgmma_ss_n8<1, 0, H64, H0>(ga, da + 128, db + 4, 1); wgmma_ss_n8<1, 0, H64, H0>(gb, da + 192, db + 6, 1);
        wg_commit();
        da += 256; db += 8;
      }
      wg_wait<0>();
      fence_regs(ga); fence_regs(gb);
      if (q == 0) { stsf(sb + OFF_SCR + 128 + r0 * 4, ga[0] + gb[0]); stsf(sb + OFF_SCR + 128 + r0 * 4 + 32, ga[2] + gb[2]); }
      bar_arrive(NB_ACT, 384);
    }
    {
      float y0 = 0.f, y1 = 0.f, y2 = 0.f, y3 = 0.f;
      const float2 ky = lds64f(sb + OFF_KEY);
      const int kidx = __float_as_int(ky.x);
      const float kr = ky.y;
      uint32_t it = 0;
      if (tid < 2 * NFFN) {
        uint4 v;
        do { v = ld128_rlx(&G->ypart[(tid >> 1) * DM + 8 * c + 4 * (tid & 1)]); } while (tag_bad(v, tg) && ++it < POLL_LIMIT);
        y0 = untag(v.x); y1 = untag(v.y); y2 = untag(v.z); y3 = untag(v.w);
      }
      __syncwarp();
      const bool b4 = lane & 16, b3 = lane & 8;
      const float u0 = (b4 ? y1 : y0) + __shfl_xor_sync(~0u, b4 ? y0 : y1, 16), u1 = (b4 ? y3 : y2) + __shfl_xor_sync(~0u, b4 ? y2 : y3, 16);
      float ys = (b3 ? u1 : u0) + __shfl_xor_sync(~0u, b3 ? u0 : u1, 8);
      ys += __shfl_xor_sync(~0u, ys, 4); ys += __shfl_xor_sync(~0u, ys, 2);
      if (!(lane & 6)) stsf(sb + OFF_ACT + (warp * 8 + 4 * (lane & 1) + ((lane >> 3) & 1) * 2 + (lane >> 4)) * 4, ys);
      const float sg = __fdividef(1.f, 1.f + __expf(-kr));
      bar_sync(NB_WG01, 256);
      if (tid < 8) {
        float t8 = 0.f;
        #pragma unroll
        for (int w = 0; w < 7; w++) t8 += ldsf(sb + OFF_ACT + w * 32 + tid * 4);
        P.out_p[(size_t)kidx * DM + 8 * c + tid] = __float2bfloat16(fmaf(t8, sg, ldsf(sb + OFF_H8 + tid * 4)));
      }
      if (c == 0 && tid == 0) st32_rlx(&G->epoch, ep1);
      if (wg == 0) { TSW(22); }
    }
  }
  if (wg == 2) {
    const uint32_t tg = ep1 & 3;
    uint32_t wf[4][2][2][8];
    {
      const bf16* wp0 = P.wd_p + (size_t)(32 * c + 2 * q) * DM + 256 * wp + 8 * g;
      uint4 u[4][8];
      asm volatile("setmaxnreg.inc.sync.aligned.u32 224;");
      __nanosleep(WD_DELAY);
      #pragma unroll
      for (int r = 0; r < 8; r++) {
        __nanosleep(WD_STEP);
        #pragma unroll
        for (int s4 = 0; s4 < 4; s4++) u[s4][r] = c < NFFN ? ld128_weak(wp0 + ((r >> 1) * 8 + (r & 1)) * DM + 64 * s4) : make_uint4(0, 0, 0, 0);
      }
      #pragma unroll
      for (int s4 = 0; s4 < 4; s4++)
        #pragma unroll
        for (int r2 = 0; r2 < 4; r2++) {
          const uint32_t a[4] = {u[s4][2*r2].x, u[s4][2*r2].y, u[s4][2*r2].z, u[s4][2*r2].w}, b[4] = {u[s4][2*r2+1].x, u[s4][2*r2+1].y, u[s4][2*r2+1].z, u[s4][2*r2+1].w};
          #pragma unroll
          for (int e = 0; e < 4; e++) { wf[s4][r2 >> 1][r2 & 1][2*e] = __byte_perm(a[e], b[e], 0x5410); wf[s4][r2 >> 1][r2 & 1][2*e+1] = __byte_perm(a[e], b[e], 0x7632); }
        }
    }
    uint32_t* const dst = &G->ypart[c * DM + 256 * wp + 64 * (q >> 1) + 8 * g + 4 * (q & 1)];
    #pragma unroll 1
    for (int pass = 0; pass < 2; pass++) {
    if (pass) {
      bar_sync(NB_G2E, 256);
      TDUMP();
      int cur = -1, have = -1;
      uint32_t kw = 0, xs[4];
      float base[4];
      for (uint32_t it = 0; it < POLL_LIMIT; it++) {
        uint4 kx = ld128_rlx(&G->key[(c & 31) * 128 + 4 * lane]);
        if (cur != have) {
          const uint32_t* cp = &G->cand[cur * (DM + 32)];
          const uint4 v0 = ld128_rlx(cp + 256 * wp + 4 * lane), v1 = ld128_rlx(cp + 256 * wp + 128 + 4 * lane);
          const uint2 ms = ld64_rlx(cp + DM);
          if (!__any_sync(~0u, tag_bad(v0, tg) || tag_bad(v1, tg) || (((ms.x ^ tg) | (ms.y ^ tg)) & 3))) {
            have = cur;
            const float rs = untag(ms.y), bm = -untag(ms.x) * rs;
            xs[0] = pack_bf16(fmaf(untag(v0.x), rs, bm), fmaf(untag(v0.y), rs, bm)); xs[1] = pack_bf16(fmaf(untag(v0.z), rs, bm), fmaf(untag(v0.w), rs, bm));
            xs[2] = pack_bf16(fmaf(untag(v1.x), rs, bm), fmaf(untag(v1.y), rs, bm)); xs[3] = pack_bf16(fmaf(untag(v1.z), rs, bm), fmaf(untag(v1.w), rs, bm));
            const uint4 vb = (c & 16) ? v1 : v0;
            base[0] = fmaf(untag(vb.x), 1.f + rs, bm); base[1] = fmaf(untag(vb.y), 1.f + rs, bm); base[2] = fmaf(untag(vb.z), 1.f + rs, bm); base[3] = fmaf(untag(vb.w), 1.f + rs, bm);
          }
        }
        const bool all = !__any_sync(~0u, tag_bad(kx, tg));
        if ((kx.x ^ tg) & 3) kx.x = 0;
        if ((kx.y ^ tg) & 3) kx.y = 0;
        if ((kx.z ^ tg) & 3) kx.z = 0;
        if ((kx.w ^ tg) & 3) kx.w = 0;
        const uint32_t km = max(max(kx.x, kx.y), max(kx.z, kx.w)) >> 6;
        uint32_t best;
        asm volatile("redux.sync.max.u32 %0, %1, 0xffffffff;" : "=r"(best) : "r"(km));
        if (TRK_SLEEP && !all) __nanosleep(TRK_SLEEP);
        if (best == 0 && !all) continue;
        const int src = __ffs(__ballot_sync(~0u, km == best)) - 1;
        const int e = (kx.x >> 6) == best ? 0 : (kx.y >> 6) == best ? 1 : (kx.z >> 6) == best ? 2 : 3;
        kw = __shfl_sync(~0u, e == 0 ? kx.x : e == 1 ? kx.y : e == 2 ? kx.z : kx.w, src);
        cur = 4 * src + __shfl_sync(~0u, e, src);
        if (all && cur == have) break;
      }
      sts64(sb + OFF_XSEL + 512 * wp + 8 * lane, xs[0], xs[1]); sts64(sb + OFF_XSEL + 512 * wp + 256 + 8 * lane, xs[2], xs[3]);
      if (wp == (c >> 5) && (lane >> 1) == (c & 15)) {
        sts128(sb + OFF_H8 + (lane & 1) * 16, __float_as_uint(base[0]), __float_as_uint(base[1]), __float_as_uint(base[2]), __float_as_uint(base[3]));
        sts64(sb + OFF_KEY, 16 * cur + 15 - ((kw >> 2) & 15), (kw & ~63u) ^ ((kw >> 31) ? 0x80000000u : 0xffffffc0u));
      }
      fence_async_smem();
      bar_arrive(NB_XS, 416);
      TSW(18);
      if (c >= NFFN) break;
      bar_sync(NB_ACT, 384);
    }
    const uint32_t a = sb + OFF_SCR + 128 + lane * 4;
    const float gv = ldsf(a) + ldsf(a + 256), uv = ldsf(a + 128) + ldsf(a + 384);
    const float act = __fdividef(gv, 1.f + __expf(-gv)) * uv;
    const uint32_t ap = pack_bf16(act, __shfl_down_sync(~0u, act, 1));
    uint32_t bf[4];
    #pragma unroll
    for (int i = 0; i < 4; i++) bf[i] = __shfl_sync(~0u, ap, 2 * q + 8 * i);
    if (pass) { TSW(20); }
    float d[16][4];
    #pragma unroll
    for (int k = 0; k < 2; k++)
      #pragma unroll
      for (int i = 0; i < 16; i++) {
        if (k == 0) { d[i][0] = 0.f; d[i][1] = 0.f; d[i][2] = 0.f; d[i][3] = 0.f; }
        const uint32_t* w0 = &wf[i >> 2][k][0][2 * (i & 3)]; const uint32_t* w1 = &wf[i >> 2][k][1][2 * (i & 3)];
        asm volatile("mma.sync.aligned.m16n8k16.row.col.f32.bf16.bf16.f32 {%0,%1,%2,%3}, {%4,%5,%6,%7}, {%8,%9}, {%0,%1,%2,%3};"
                     : "+f"(d[i][0]), "+f"(d[i][1]), "+f"(d[i][2]), "+f"(d[i][3])
                     : "r"(w0[0]), "r"(w0[1]), "r"(w1[0]), "r"(w1[1]), "r"(bf[2*k]), "r"(bf[2*k+1]));
      }
    float y[8];
    #pragma unroll
    for (int i = 0; i < 8; i++) {
      const int e = (i & 1) * 2, n = 8 * (i >> 2) + ((i >> 1) & 1);
      const float lo = (q & 1) ? d[n + 2][e] : d[n][e], hi = (q & 1) ? d[n + 6][e] : d[n + 4][e];
      y[i] = (q & 2) ? hi : lo;
    }
    asm volatile("{\n.reg .pred p;\nsetp.ne.s32 p, %9, 0;\n@p st.relaxed.gpu.global.v4.u32 [%0], {%1,%2,%3,%4};\n@p st.relaxed.gpu.global.v4.u32 [%0+512], {%5,%6,%7,%8};\n}\n"
                 :: "l"(dst), "r"(tagw(y[0], tg)), "r"(tagw(y[1], tg)), "r"(tagw(y[2], tg)), "r"(tagw(y[3], tg)),
                    "r"(tagw(y[4], tg)), "r"(tagw(y[5], tg)), "r"(tagw(y[6], tg)), "r"(tagw(y[7], tg)), "r"(pass) : "memory");
    if (pass) { TSW(21); }
    }
  }
  }
  cluster_wait();
}

typedef CUresult (*EncodeFn)(CUtensorMap*, CUtensorMapDataType, cuuint32_t, void*, const cuuint64_t*, const cuuint64_t*,
                             const cuuint32_t*, const cuuint32_t*, CUtensorMapInterleave, CUtensorMapSwizzle,
                             CUtensorMapL2promotion, CUtensorMapFloatOOBfill);

void make_map(EncodeFn enc, CUtensorMap* m, const void* p, int n, const cuuint64_t* dims, const cuuint64_t* str, const cuuint32_t* box,
              CUtensorMapSwizzle sw, CUtensorMapL2promotion promo) {
  cuuint32_t es[5] = {1, 1, 1, 1, 1};
  enc(m, CU_TENSOR_MAP_DATA_TYPE_BFLOAT16, n, const_cast<void*>(p), dims, str, box, es, CU_TENSOR_MAP_INTERLEAVE_NONE, sw, promo,
      CU_TENSOR_MAP_FLOAT_OOB_FILL_NONE);
}
void map2(EncodeFn enc, CUtensorMap* m, const void* p, uint64_t cols, uint64_t rows, uint32_t bc, uint32_t br, CUtensorMapSwizzle sw,
          CUtensorMapL2promotion promo) {
  const cuuint64_t dims[2] = {cols, rows}, str[1] = {cols * 2};
  const cuuint32_t box[2] = {bc, br};
  make_map(enc, m, p, 2, dims, str, box, sw, promo);
}
void map3(EncodeFn enc, CUtensorMap* m, const void* p, uint64_t cols, uint64_t rows, uint32_t br, uint32_t nb) {
  const cuuint64_t dims[3] = {64, rows, cols / 64}, str[2] = {cols * 2, 128};
  const cuuint32_t box[3] = {64, br, nb};
  make_map(enc, m, p, 3, dims, str, box, CU_TENSOR_MAP_SWIZZLE_128B, CU_TENSOR_MAP_L2_PROMOTION_L2_128B);
}

}

extern "C" void kernel_launch(void* const* d_in, const int* in_sizes, int n_in, void* d_out, int out_size) {
  (void)in_sizes; (void)n_in; (void)out_size;
  static EncodeFn enc = nullptr;
  static void* o_ptr = nullptr;
  if (!enc) {
    void* f = nullptr; cudaDriverEntryPointQueryResult qr;
    cudaGetDriverEntryPoint("cuTensorMapEncodeTiled", &f, cudaEnableDefault, &qr);
    enc = (EncodeFn)f;
    cudaGetSymbolAddress(&o_ptr, g_scr);
    cudaFuncSetAttribute(fused_kernel, cudaFuncAttributeMaxDynamicSharedMemorySize, SMEM_BYTES);
  }
  const bf16* x = (const bf16*)d_in[0];
  const bf16* wqkv = (const bf16*)d_in[1];
  const bf16* wphi = (const bf16*)d_in[2];
  const bf16* wo = (const bf16*)d_in[3];
  const bf16* wr = (const bf16*)d_in[5];
  const bf16* wgate = (const bf16*)d_in[6];
  const bf16* wup = (const bf16*)d_in[7];
  const bf16* wdown = (const bf16*)d_in[8];
  Params P;
  const CUtensorMapSwizzle S128 = CU_TENSOR_MAP_SWIZZLE_128B, S64 = CU_TENSOR_MAP_SWIZZLE_64B;
  const CUtensorMapL2promotion L128 = CU_TENSOR_MAP_L2_PROMOTION_L2_128B, L256 = CU_TENSOR_MAP_L2_PROMOTION_L2_256B,
                               L64 = CU_TENSOR_MAP_L2_PROMOTION_L2_64B;
  map2(enc, &P.x128, x, DM, SEQ, 64, 128, S128, L256);
  map2(enc, &P.x64, x, DM, SEQ, 64, 64, S128, L128);
  {
    const cuuint64_t dims[4] = {64, DM, 16, 3}, str[3] = {6 * DM, 128, 2 * DM};
    const cuuint32_t box[4] = {64, 64, 1, 2};
    make_map(enc, &P.wkv, wqkv, 4, dims, str, box, S128, L128);
  }
  map3(enc, &P.wq, wqkv, 3 * DM, DM, 64, 2);
  {
    const cuuint64_t dims[4] = {64, DM - 64, 2, 16}, str[3] = {2 * DM, 128 * DM, 128};
    const cuuint32_t box[4] = {64, 32, 2, 2};
    make_map(enc, &P.wo, wo, 4, dims, str, box, S128, L128);
  }
  map3(enc, &P.out, d_out, DM, SEQ, 128, 2);
  map2(enc, &P.out16, d_out, DM, SEQ, 64, 16, S128, L128);
  map2(enc, &P.wg, wgate, FF, DM, 32, 256, S64, L64);
  map2(enc, &P.wu, wup, FF, DM, 32, 256, S64, L64);
  map2(enc, &P.tg, wgate, FF, DM, 8, 32, CU_TENSOR_MAP_SWIZZLE_NONE, L128);
  map2(enc, &P.tu, wup, FF, DM, 8, 32, CU_TENSOR_MAP_SWIZZLE_NONE, L128);
  map2(enc, &P.td, wdown, 128, FF * 8, 8, 32, CU_TENSOR_MAP_SWIZZLE_NONE, L256);
  map2(enc, &P.phi, wphi, 32, 1024, 32, 32, S64, L64);
  P.x = x; P.wqkv = wqkv; P.wo_p = wo; P.wd_p = wdown; P.wg_p = wgate; P.wu_p = wup; P.wr = wr; P.out_p = (bf16*)d_out; P.g = (Scratch*)o_ptr;

  cudaLaunchConfig_t cfg = {};
  cfg.gridDim = dim3(128); cfg.blockDim = dim3(512); cfg.dynamicSmemBytes = SMEM_BYTES; cfg.stream = cudaStreamPerThread;
  cudaLaunchAttribute at[1];
  at[0].id = cudaLaunchAttributeClusterDimension; at[0].val.clusterDim.x = 2; at[0].val.clusterDim.y = 1; at[0].val.clusterDim.z = 1;
  cfg.attrs = at; cfg.numAttrs = 1;
  cudaLaunchKernelEx(&cfg, fused_kernel, P);
}
```

```cpp
#include <cuda_runtime.h>
#include <cuda.h>
#include <cuda_bf16.h>
#include <stdint.h>

namespace {

typedef __nv_bfloat16 bf16;

__device__ __forceinline__ uint32_t smem_u32(const void* p){ return (uint32_t)__cvta_generic_to_shared(p); }
__device__ __forceinline__ void mbar_init(uint32_t bar, uint32_t cnt){ asm volatile("mbarrier.init.shared::cta.b64 [%0], %1;"::"r"(bar),"r"(cnt):"memory"); }
__device__ __forceinline__ void mbar_expect_tx(uint32_t bar, uint32_t bytes){ asm volatile("mbarrier.arrive.expect_tx.shared::cta.b64 _, [%0], %1;"::"r"(bar),"r"(bytes):"memory"); }
__device__ __forceinline__ void mbar_arrive(uint32_t bar){ asm volatile("mbarrier.arrive.shared::cta.b64 _, [%0];"::"r"(bar):"memory"); }
__device__ __forceinline__ uint32_t mapa(uint32_t addr, uint32_t cta){ uint32_t r; asm volatile("mapa.shared::cluster.u32 %0, %1, %2;":"=r"(r):"r"(addr),"r"(cta)); return r; }
__device__ __forceinline__ void mbar_arrive_at(uint32_t bar, uint32_t cta, uint32_t cnt){
  asm volatile("{\n.reg .b32 ra;\nmapa.shared::cluster.u32 ra, %0, %1;\nmbarrier.arrive.shared::cluster.b64 _, [ra], %2;\n}\n"::"r"(bar),"r"(cta),"r"(cnt):"memory"); }
__device__ __forceinline__ void mbar_arrive_remote(uint32_t cluster_addr, uint32_t cnt){
  asm volatile("mbarrier.arrive.shared::cluster.b64 _, [%0], %1;"::"r"(cluster_addr),"r"(cnt):"memory"); }
__device__ __forceinline__ void mbar_wait(uint32_t bar, uint32_t parity){
  asm volatile("{\n.reg .pred p;\n.reg .u32 c;\nmov.u32 c, 0;\nLW:\nmbarrier.try_wait.parity.shared::cta.b64 p, [%0], %1;\n@p bra LD;\nadd.u32 c, c, 1;\nsetp.lt.u32 p, c, 2000000;\n@p bra LW;\ntrap;\nLD:\n}\n"::"r"(bar),"r"(parity):"memory"); }
__device__ __forceinline__ void mbar_wait2(uint32_t bar0, uint32_t par0, uint32_t bar1, uint32_t par1){
  asm volatile("{\n.reg .pred p, q;\n.reg .u32 c;\nmov.u32 c, 0;\nLW:\nmbarrier.try_wait.parity.shared::cta.b64 p, [%0], %1;\nmbarrier.try_wait.parity.shared::cta.b64 q, [%2], %3;\nand.pred p, p, q;\n@p bra LD;\nadd.u32 c, c, 1;\nsetp.lt.u32 p, c, 2000000;\n@p bra LW;\ntrap;\nLD:\n}\n"::"r"(bar0),"r"(par0),"r"(bar1),"r"(par1):"memory"); }
__device__ __forceinline__ void tma_2d(uint32_t dst, const CUtensorMap* m, int c0, int c1, uint32_t bar){
  asm volatile("cp.async.bulk.tensor.2d.shared::cluster.global.mbarrier::complete_tx::bytes [%0], [%1, {%3, %4}], [%2];"::"r"(dst),"l"(m),"r"(bar),"r"(c0),"r"(c1):"memory"); }
__device__ __forceinline__ void tma_2d_mc(uint32_t dst, const CUtensorMap* m, int c0, int c1, uint32_t bar){
  asm volatile("cp.async.bulk.tensor.2d.shared::cluster.global.mbarrier::complete_tx::bytes.multicast::cluster [%0], [%1, {%3, %4}], [%2], %5;"::"r"(dst),"l"(m),"r"(bar),"r"(c0),"r"(c1),"h"((uint16_t)3):"memory"); }
__device__ __forceinline__ void tma_2d_mc_h(uint32_t dst, const CUtensorMap* m, int c0, int c1, uint32_t bar, uint64_t pol){
  asm volatile("cp.async.bulk.tensor.2d.shared::cluster.global.mbarrier::complete_tx::bytes.multicast::cluster.L2::cache_hint [%0], [%1, {%3, %4}], [%2], %5, %6;"::"r"(dst),"l"(m),"r"(bar),"r"(c0),"r"(c1),"h"((uint16_t)3),"l"(pol):"memory"); }
__device__ __forceinline__ void tma_4d(uint32_t dst, const CUtensorMap* m, int c0, int c1, int c2, int c3, uint32_t bar){
  asm volatile("cp.async.bulk.tensor.4d.shared::cluster.global.mbarrier::complete_tx::bytes [%0], [%1, {%3, %4, %5, %6}], [%2];"::"r"(dst),"l"(m),"r"(bar),"r"(c0),"r"(c1),"r"(c2),"r"(c3):"memory"); }
__device__ __forceinline__ uint64_t policy_evict_first(){ uint64_t p; asm volatile("createpolicy.fractional.L2::evict_first.b64 %0, 1.0;":"=l"(p)); return p; }
__device__ __forceinline__ void tma_3d_h(uint32_t dst, const CUtensorMap* m, int c0, int c1, int c2, uint32_t bar, uint64_t pol){
  asm volatile("cp.async.bulk.tensor.3d.shared::cluster.global.mbarrier::complete_tx::bytes.L2::cache_hint [%0], [%1, {%3, %4, %5}], [%2], %6;"::"r"(dst),"l"(m),"r"(bar),"r"(c0),"r"(c1),"r"(c2),"l"(pol):"memory"); }
__device__ __forceinline__ void tma_4d_h(uint32_t dst, const CUtensorMap* m, int c0, int c1, int c2, int c3, uint32_t bar, uint64_t pol){
  asm volatile("cp.async.bulk.tensor.4d.shared::cluster.global.mbarrier::complete_tx::bytes.L2::cache_hint [%0], [%1, {%3, %4, %5, %6}], [%2], %7;"::"r"(dst),"l"(m),"r"(bar),"r"(c0),"r"(c1),"r"(c2),"r"(c3),"l"(pol):"memory"); }
__device__ __forceinline__ void tma_store_3d_h(const CUtensorMap* m, int c0, int c1, int c2, uint32_t src, uint64_t pol){
  asm volatile("cp.async.bulk.tensor.3d.global.shared::cta.bulk_group.L2::cache_hint [%0, {%2, %3, %4}], [%1], %5;"::"l"(m),"r"(src),"r"(c0),"r"(c1),"r"(c2),"l"(pol):"memory"); }
__device__ __forceinline__ void red_add_f32x4(float4* p, float x, float y, float z, float w){ asm volatile("red.relaxed.gpu.global.add.v4.f32 [%0], {%1,%2,%3,%4};"::"l"(p),"f"(x),"f"(y),"f"(z),"f"(w):"memory"); }
__device__ __forceinline__ void tma_store_2d_h(const CUtensorMap* m, int c0, int c1, uint32_t src, uint64_t pol){
  asm volatile("cp.async.bulk.tensor.2d.global.shared::cta.bulk_group.L2::cache_hint [%0, {%2, %3}], [%1], %4;"::"l"(m),"r"(src),"r"(c0),"r"(c1),"l"(pol):"memory"); }
__device__ __forceinline__ bool elect_one(){ uint32_t p; asm volatile("{\n.reg .pred P;\nelect.sync _|P, 0xffffffff;\nselp.b32 %0, 1, 0, P;\n}\n":"=r"(p)); return p; }
__device__ __forceinline__ void bulk_prefetch(const void* p, uint32_t bytes){
  asm volatile("cp.async.bulk.prefetch.L2.global [%0], %1;"::"l"(p),"r"(bytes):"memory"); }
__device__ __forceinline__ void bulk_s2peer(uint32_t dst_cluster, uint32_t src, uint32_t bytes, uint32_t bar_cluster){
  asm volatile("cp.async.bulk.shared::cluster.shared::cta.mbarrier::complete_tx::bytes [%0], [%1], %2, [%3];"::"r"(dst_cluster),"r"(src),"r"(bytes),"r"(bar_cluster):"memory"); }
__device__ __forceinline__ void bulk_g2s_mc(uint32_t dst, const void* src, uint32_t bytes, uint32_t bar, uint64_t pol){
  asm volatile("cp.async.bulk.shared::cluster.global.mbarrier::complete_tx::bytes.multicast::cluster.L2::cache_hint [%0], [%1], %2, [%3], %4, %5;"::"r"(dst),"l"(src),"r"(bytes),"r"(bar),"h"((uint16_t)3),"l"(pol):"memory"); }
__device__ __forceinline__ void bulk_s2g(void* dst, uint32_t src, uint32_t bytes){
  asm volatile("cp.async.bulk.global.shared::cta.bulk_group [%0], [%1], %2;"::"l"(dst),"r"(src),"r"(bytes):"memory"); }
__device__ __forceinline__ void bulk_commit(){ asm volatile("cp.async.bulk.commit_group;":::"memory"); }
__device__ __forceinline__ void bulk_wait_read(){ asm volatile("cp.async.bulk.wait_group.read 0;":::"memory"); }
__device__ __forceinline__ void bulk_wait_all(){ asm volatile("cp.async.bulk.wait_group 0;":::"memory"); }
__device__ __forceinline__ void prefetch_map(const CUtensorMap* m){ asm volatile("prefetch.tensormap [%0];"::"l"(m):"memory"); }
__device__ __forceinline__ void fence_async_smem(){ asm volatile("fence.proxy.async.shared::cta;":::"memory"); }
__device__ __forceinline__ void fence_acquire_gpu(){ asm volatile("fence.acquire.gpu;":::"memory"); }
__device__ __forceinline__ void fence_gpu(){ asm volatile("fence.acq_rel.gpu;":::"memory"); }
__device__ __forceinline__ void wg_fence(){ asm volatile("wgmma.fence.sync.aligned;":::"memory"); }
__device__ __forceinline__ void wg_commit(){ asm volatile("wgmma.commit_group.sync.aligned;":::"memory"); }
template<int N> __device__ __forceinline__ void wg_wait(){ asm volatile("wgmma.wait_group.sync.aligned %0;"::"n"(N):"memory"); }
template<int N> __device__ __forceinline__ void fence_regs(float (&d)[N]){
  #pragma unroll
  for(int i=0;i<N;i++) asm volatile("":"+f"(d[i])::"memory"); }
__device__ __forceinline__ void bar_sync(int id, int n){ asm volatile("bar.sync %0, %1;"::"r"(id),"r"(n):"memory"); }
__device__ __forceinline__ void bar_arrive(int id, int n){ asm volatile("bar.arrive %0, %1;"::"r"(id),"r"(n):"memory"); }
__device__ __forceinline__ void cluster_arrive(){ asm volatile("barrier.cluster.arrive.relaxed.aligned;":::"memory"); }
__device__ __forceinline__ void cluster_wait(){ asm volatile("barrier.cluster.wait.aligned;":::"memory"); }
__host__ __device__ constexpr uint32_t dlo(uint32_t addr, uint32_t lbo){ return (addr >> 4) | ((lbo >> 4) << 16); }
__host__ __device__ constexpr uint32_t dhi(uint32_t sbo, uint32_t sw){ return (sbo >> 4) | (sw << 30); }
constexpr uint32_t H128 = dhi(1024, 1), H64 = dhi(512, 2), H0 = dhi(128, 0);
__device__ __forceinline__ uint32_t pack_bf16(float lo, float hi){ uint32_t r; asm("cvt.rn.bf16x2.f32 %0, %1, %2;":"=r"(r):"f"(hi),"f"(lo)); return r; }
__device__ __forceinline__ float bf_lo(uint32_t v){ return __uint_as_float(v<<16); }
__device__ __forceinline__ float bf_hi(uint32_t v){ return __uint_as_float(v&0xffff0000u); }
__device__ __forceinline__ float ex2(float x){ float r; asm("ex2.approx.ftz.f32 %0, %1;":"=f"(r):"f"(x)); return r; }
__device__ __forceinline__ float rcp(float x){ float r; asm("rcp.approx.ftz.f32 %0, %1;":"=f"(r):"f"(x)); return r; }
__device__ __forceinline__ void stsm4(uint32_t addr, uint32_t a, uint32_t b, uint32_t c, uint32_t d){
  asm volatile("stmatrix.sync.aligned.m8n8.x4.shared.b16 [%0], {%1,%2,%3,%4};"::"r"(addr),"r"(a),"r"(b),"r"(c),"r"(d)); }
__device__ __forceinline__ void stsm2(uint32_t addr, uint32_t a, uint32_t b){
  asm volatile("stmatrix.sync.aligned.m8n8.x2.shared.b16 [%0], {%1,%2};"::"r"(addr),"r"(a),"r"(b)); }
__device__ __forceinline__ void mma16816(float& d0, float& d1, float& d2, float& d3, uint32_t a0, uint32_t a1, uint32_t a2, uint32_t a3, uint32_t b0, uint32_t b1){
  asm volatile("mma.sync.aligned.m16n8k16.row.col.f32.bf16.bf16.f32 {%0,%1,%2,%3}, {%4,%5,%6,%7}, {%8,%9}, {%0,%1,%2,%3};"
               : "+f"(d0), "+f"(d1), "+f"(d2), "+f"(d3) : "r"(a0), "r"(a1), "r"(a2), "r"(a3), "r"(b0), "r"(b1)); }
__device__ __forceinline__ void ldsm4(uint32_t addr, uint32_t& a, uint32_t& b, uint32_t& c, uint32_t& d){
  asm volatile("ldmatrix.sync.aligned.m8n8.x4.shared.b16 {%0,%1,%2,%3}, [%4];":"=r"(a),"=r"(b),"=r"(c),"=r"(d):"r"(addr):"memory"); }
__device__ __forceinline__ void sts32(uint32_t a, uint32_t v){ asm volatile("st.shared.b32 [%0], %1;"::"r"(a),"r"(v):"memory"); }
__device__ __forceinline__ void stsf(uint32_t a, float v){ asm volatile("st.shared.f32 [%0], %1;"::"r"(a),"f"(v):"memory"); }
__device__ __forceinline__ void sts64(uint32_t a, uint32_t x, uint32_t y){ asm volatile("st.shared.v2.b32 [%0], {%1,%2};"::"r"(a),"r"(x),"r"(y):"memory"); }
__device__ __forceinline__ void sts128(uint32_t a, uint32_t x, uint32_t y, uint32_t z, uint32_t w){ asm volatile("st.shared.v4.b32 [%0], {%1,%2,%3,%4};"::"r"(a),"r"(x),"r"(y),"r"(z),"r"(w):"memory"); }
__device__ __forceinline__ float ldsf(uint32_t a){ float v; asm volatile("ld.shared.f32 %0, [%1];":"=f"(v):"r"(a):"memory"); return v; }
__device__ __forceinline__ float2 lds64f(uint32_t a){ float2 v; asm volatile("ld.shared.v2.f32 {%0,%1}, [%2];":"=f"(v.x),"=f"(v.y):"r"(a):"memory"); return v; }
__device__ __forceinline__ uint4 lds128(uint32_t a){ uint4 v; asm volatile("ld.shared.v4.u32 {%0,%1,%2,%3}, [%4];":"=r"(v.x),"=r"(v.y),"=r"(v.z),"=r"(v.w):"r"(a):"memory"); return v; }
__device__ __forceinline__ uint4 ld128_weak(const void* p){ uint4 v; asm volatile("ld.global.L1::no_allocate.v4.u32 {%0,%1,%2,%3}, [%4];":"=r"(v.x),"=r"(v.y),"=r"(v.z),"=r"(v.w):"l"(p):"memory"); return v; }
__device__ __forceinline__ uint4 ld128_keep(const void* p){ uint4 v; asm volatile("ld.global.v4.u32 {%0,%1,%2,%3}, [%4];":"=r"(v.x),"=r"(v.y),"=r"(v.z),"=r"(v.w):"l"(p):"memory"); return v; }
__device__ __forceinline__ uint4 ld128_rlx(const void* p){ uint4 v; asm volatile("ld.relaxed.gpu.global.v4.u32 {%0,%1,%2,%3}, [%4];":"=r"(v.x),"=r"(v.y),"=r"(v.z),"=r"(v.w):"l"(p):"memory"); return v; }
__device__ __forceinline__ uint2 ld64_rlx(const void* p){ uint2 v; asm volatile("ld.relaxed.gpu.global.v2.u32 {%0,%1}, [%2];":"=r"(v.x),"=r"(v.y):"l"(p):"memory"); return v; }
__device__ __forceinline__ uint32_t ld32_rlx(const void* p){ uint32_t v; asm volatile("ld.relaxed.gpu.global.u32 %0, [%1];":"=r"(v):"l"(p):"memory"); return v; }
__device__ __forceinline__ void st128_rlx(void* p, uint32_t x, uint32_t y, uint32_t z, uint32_t w){ asm volatile("st.relaxed.gpu.global.v4.u32 [%0], {%1,%2,%3,%4};"::"l"(p),"r"(x),"r"(y),"r"(z),"r"(w):"memory"); }
__device__ __forceinline__ void st64_rlx(void* p, uint32_t x, uint32_t y){ asm volatile("st.relaxed.gpu.global.v2.u32 [%0], {%1,%2};"::"l"(p),"r"(x),"r"(y):"memory"); }
__device__ __forceinline__ void st32_rlx(void* p, uint32_t x){ asm volatile("st.relaxed.gpu.global.u32 [%0], %1;"::"l"(p),"r"(x):"memory"); }
__device__ __forceinline__ uint32_t tagw(float x, uint32_t t){ return (__float_as_uint(x) & ~3u) | t; }
__device__ __forceinline__ float untag(uint32_t w){ return __uint_as_float(w & ~3u); }

template<int TA, int TB, uint32_t HA, uint32_t HB> __device__ __forceinline__ void wgmma_ss_n128(float (&d)[64], uint32_t da, uint32_t db, int scale_d){
  asm volatile("{\n.reg .pred p;\n.reg .b64 a, b;\nsetp.ne.b32 p, %70, 0;\nmov.b64 a, {%64, %68};\nmov.b64 b, {%65, %69};\n"
  "wgmma.mma_async.sync.aligned.m64n128k16.f32.bf16.bf16 {%0, %1, %2, %3, %4, %5, %6, %7, %8, %9, %10, %11, %12, %13, %14, %15, %16, %17, %18, %19, %20, %21, %22, %23, %24, %25, %26, %27, %28, %29, %30, %31, %32, %33, %34, %35, %36, %37, %38, %39, %40, %41, %42, %43, %44, %45, %46, %47, %48, %49, %50, %51, %52, %53, %54, %55, %56, %57, %58, %59, %60, %61, %62, %63}, a, b, p, 1, 1, %66, %67;\n}\n"
  : "+f"(d[0]), "+f"(d[1]), "+f"(d[2]), "+f"(d[3]), "+f"(d[4]), "+f"(d[5]), "+f"(d[6]), "+f"(d[7]), "+f"(d[8]), "+f"(d[9]), "+f"(d[10]), "+f"(d[11]), "+f"(d[12]), "+f"(d[13]), "+f"(d[14]), "+f"(d[15]), "+f"(d[16]), "+f"(d[17]), "+f"(d[18]), "+f"(d[19]), "+f"(d[20]), "+f"(d[21]), "+f"(d[22]), "+f"(d[23]), "+f"(d[24]), "+f"(d[25]), "+f"(d[26]), "+f"(d[27]), "+f"(d[28]), "+f"(d[29]), "+f"(d[30]), "+f"(d[31]), "+f"(d[32]), "+f"(d[33]), "+f"(d[34]), "+f"(d[35]), "+f"(d[36]), "+f"(d[37]), "+f"(d[38]), "+f"(d[39]), "+f"(d[40]), "+f"(d[41]), "+f"(d[42]), "+f"(d[43]), "+f"(d[44]), "+f"(d[45]), "+f"(d[46]), "+f"(d[47]), "+f"(d[48]), "+f"(d[49]), "+f"(d[50]), "+f"(d[51]), "+f"(d[52]), "+f"(d[53]), "+f"(d[54]), "+f"(d[55]), "+f"(d[56]), "+f"(d[57]), "+f"(d[58]), "+f"(d[59]), "+f"(d[60]), "+f"(d[61]), "+f"(d[62]), "+f"(d[63])
  : "r"(da), "r"(db), "n"(TA), "n"(TB), "n"(HA), "n"(HB), "r"(scale_d));
}
template<int TA, int TB, uint32_t HA, uint32_t HB> __device__ __forceinline__ void wgmma_sa_n128(float (&d)[64], uint32_t da, uint32_t db){
  asm volatile("{\n.reg .pred p;\n.reg .b64 a, b;\nsetp.ne.b32 p, 1, 0;\nmov.b64 a, {%64, %68};\nmov.b64 b, {%65, %69};\n"
  "wgmma.mma_async.sync.aligned.m64n128k16.f32.bf16.bf16 {%0, %1, %2, %3, %4, %5, %6, %7, %8, %9, %10, %11, %12, %13, %14, %15, %16, %17, %18, %19, %20, %21, %22, %23, %24, %25, %26, %27, %28, %29, %30, %31, %32, %33, %34, %35, %36, %37, %38, %39, %40, %41, %42, %43, %44, %45, %46, %47, %48, %49, %50, %51, %52, %53, %54, %55, %56, %57, %58, %59, %60, %61, %62, %63}, a, b, p, 1, 1, %66, %67;\n}\n"
  : "+f"(d[0]), "+f"(d[1]), "+f"(d[2]), "+f"(d[3]), "+f"(d[4]), "+f"(d[5]), "+f"(d[6]), "+f"(d[7]), "+f"(d[8]), "+f"(d[9]), "+f"(d[10]), "+f"(d[11]), "+f"(d[12]), "+f"(d[13]), "+f"(d[14]), "+f"(d[15]), "+f"(d[16]), "+f"(d[17]), "+f"(d[18]), "+f"(d[19]), "+f"(d[20]), "+f"(d[21]), "+f"(d[22]), "+f"(d[23]), "+f"(d[24]), "+f"(d[25]), "+f"(d[26]), "+f"(d[27]), "+f"(d[28]), "+f"(d[29]), "+f"(d[30]), "+f"(d[31]), "+f"(d[32]), "+f"(d[33]), "+f"(d[34]), "+f"(d[35]), "+f"(d[36]), "+f"(d[37]), "+f"(d[38]), "+f"(d[39]), "+f"(d[40]), "+f"(d[41]), "+f"(d[42]), "+f"(d[43]), "+f"(d[44]), "+f"(d[45]), "+f"(d[46]), "+f"(d[47]), "+f"(d[48]), "+f"(d[49]), "+f"(d[50]), "+f"(d[51]), "+f"(d[52]), "+f"(d[53]), "+f"(d[54]), "+f"(d[55]), "+f"(d[56]), "+f"(d[57]), "+f"(d[58]), "+f"(d[59]), "+f"(d[60]), "+f"(d[61]), "+f"(d[62]), "+f"(d[63])
  : "r"(da), "r"(db), "n"(TA), "n"(TB), "n"(HA), "n"(HB));
}
template<int TA, int TB, uint32_t HA, uint32_t HB> __device__ __forceinline__ void wgmma_sa_n40(float (&d)[20], uint32_t da, uint32_t db){
  asm volatile("{\n.reg .pred p;\n.reg .b64 a, b;\nsetp.ne.b32 p, 1, 0;\nmov.b64 a, {%20, %24};\nmov.b64 b, {%21, %25};\n"
  "wgmma.mma_async.sync.aligned.m64n40k16.f32.bf16.bf16 {%0, %1, %2, %3, %4, %5, %6, %7, %8, %9, %10, %11, %12, %13, %14, %15, %16, %17, %18, %19}, a, b, p, 1, 1, %22, %23;\n}\n"
  : "+f"(d[0]), "+f"(d[1]), "+f"(d[2]), "+f"(d[3]), "+f"(d[4]), "+f"(d[5]), "+f"(d[6]), "+f"(d[7]), "+f"(d[8]), "+f"(d[9]), "+f"(d[10]), "+f"(d[11]), "+f"(d[12]), "+f"(d[13]), "+f"(d[14]), "+f"(d[15]), "+f"(d[16]), "+f"(d[17]), "+f"(d[18]), "+f"(d[19])
  : "r"(da), "r"(db), "n"(TA), "n"(TB), "n"(HA), "n"(HB));
}
template<int TA, int TB, uint32_t HA, uint32_t HB> __device__ __forceinline__ void wgmma_sz_n40(float (&d)[20], uint32_t da, uint32_t db){
  asm volatile("{\n.reg .pred p;\n.reg .b64 a, b;\nsetp.ne.b32 p, 0, 0;\nmov.b64 a, {%20, %24};\nmov.b64 b, {%21, %25};\n"
  "wgmma.mma_async.sync.aligned.m64n40k16.f32.bf16.bf16 {%0, %1, %2, %3, %4, %5, %6, %7, %8, %9, %10, %11, %12, %13, %14, %15, %16, %17, %18, %19}, a, b, p, 1, 1, %22, %23;\n}\n"
  : "=f"(d[0]), "=f"(d[1]), "=f"(d[2]), "=f"(d[3]), "=f"(d[4]), "=f"(d[5]), "=f"(d[6]), "=f"(d[7]), "=f"(d[8]), "=f"(d[9]), "=f"(d[10]), "=f"(d[11]), "=f"(d[12]), "=f"(d[13]), "=f"(d[14]), "=f"(d[15]), "=f"(d[16]), "=f"(d[17]), "=f"(d[18]), "=f"(d[19])
  : "r"(da), "r"(db), "n"(TA), "n"(TB), "n"(HA), "n"(HB));
}
template<int TA, int TB, uint32_t HA, uint32_t HB> __device__ __forceinline__ void wgmma_sa_n32(float (&d)[16], uint32_t da, uint32_t db){
  asm volatile("{\n.reg .pred p;\n.reg .b64 a, b;\nsetp.ne.b32 p, 1, 0;\nmov.b64 a, {%16, %20};\nmov.b64 b, {%17, %21};\n"
  "wgmma.mma_async.sync.aligned.m64n32k16.f32.bf16.bf16 {%0, %1, %2, %3, %4, %5, %6, %7, %8, %9, %10, %11, %12, %13, %14, %15}, a, b, p, 1, 1, %18, %19;\n}\n"
  : "+f"(d[0]), "+f"(d[1]), "+f"(d[2]), "+f"(d[3]), "+f"(d[4]), "+f"(d[5]), "+f"(d[6]), "+f"(d[7]), "+f"(d[8]), "+f"(d[9]), "+f"(d[10]), "+f"(d[11]), "+f"(d[12]), "+f"(d[13]), "+f"(d[14]), "+f"(d[15])
  : "r"(da), "r"(db), "n"(TA), "n"(TB), "n"(HA), "n"(HB));
}
template<int TA, int TB, uint32_t HA, uint32_t HB> __device__ __forceinline__ void wgmma_ss_n32(float (&d)[16], uint32_t da, uint32_t db, int scale_d){
  asm volatile("{\n.reg .pred p;\n.reg .b64 a, b;\nsetp.ne.b32 p, %22, 0;\nmov.b64 a, {%16, %20};\nmov.b64 b, {%17, %21};\n"
  "wgmma.mma_async.sync.aligned.m64n32k16.f32.bf16.bf16 {%0, %1, %2, %3, %4, %5, %6, %7, %8, %9, %10, %11, %12, %13, %14, %15}, a, b, p, 1, 1, %18, %19;\n}\n"
  : "+f"(d[0]), "+f"(d[1]), "+f"(d[2]), "+f"(d[3]), "+f"(d[4]), "+f"(d[5]), "+f"(d[6]), "+f"(d[7]), "+f"(d[8]), "+f"(d[9]), "+f"(d[10]), "+f"(d[11]), "+f"(d[12]), "+f"(d[13]), "+f"(d[14]), "+f"(d[15])
  : "r"(da), "r"(db), "n"(TA), "n"(TB), "n"(HA), "n"(HB), "r"(scale_d));
}
template<int TA, int TB, uint32_t HA, uint32_t HB> __device__ __forceinline__ void wgmma_ss_n8(float (&d)[4], uint32_t da, uint32_t db, int scale_d){
  asm volatile("{\n.reg .pred p;\n.reg .b64 a, b;\nsetp.ne.b32 p, %10, 0;\nmov.b64 a, {%4, %8};\nmov.b64 b, {%5, %9};\n"
  "wgmma.mma_async.sync.aligned.m64n8k16.f32.bf16.bf16 {%0, %1, %2, %3}, a, b, p, 1, 1, %6, %7;\n}\n"
  : "+f"(d[0]), "+f"(d[1]), "+f"(d[2]), "+f"(d[3])
  : "r"(da), "r"(db), "n"(TA), "n"(TB), "n"(HA), "n"(HB), "r"(scale_d));
}
template<int TB, uint32_t HB> __device__ __forceinline__ void wgmma_ra_n32(float (&d)[16], uint32_t a0, uint32_t a1, uint32_t a2, uint32_t a3, uint32_t db){
  asm volatile("{\n.reg .pred p;\n.reg .b64 a, b;\nsetp.ne.b32 p, 1, 0;\nmov.b64 b, {%20, %22};\n"
  "wgmma.mma_async.sync.aligned.m64n32k16.f32.bf16.bf16 {%0, %1, %2, %3, %4, %5, %6, %7, %8, %9, %10, %11, %12, %13, %14, %15}, {%16,%17,%18,%19}, b, p, 1, 1, %21;\n}\n"
  : "+f"(d[0]), "+f"(d[1]), "+f"(d[2]), "+f"(d[3]), "+f"(d[4]), "+f"(d[5]), "+f"(d[6]), "+f"(d[7]), "+f"(d[8]), "+f"(d[9]), "+f"(d[10]), "+f"(d[11]), "+f"(d[12]), "+f"(d[13]), "+f"(d[14]), "+f"(d[15])
  : "r"(a0), "r"(a1), "r"(a2), "r"(a3), "r"(db), "n"(TB), "n"(HB));
}
template<int TB, uint32_t HB> __device__ __forceinline__ void wgmma_rs_n32(float (&d)[16], uint32_t a0, uint32_t a1, uint32_t a2, uint32_t a3, uint32_t db, int scale_d){
  asm volatile("{\n.reg .pred p;\n.reg .b64 a, b;\nsetp.ne.b32 p, %23, 0;\nmov.b64 b, {%20, %22};\n"
  "wgmma.mma_async.sync.aligned.m64n32k16.f32.bf16.bf16 {%0, %1, %2, %3, %4, %5, %6, %7, %8, %9, %10, %11, %12, %13, %14, %15}, {%16,%17,%18,%19}, b, p, 1, 1, %21;\n}\n"
  : "+f"(d[0]), "+f"(d[1]), "+f"(d[2]), "+f"(d[3]), "+f"(d[4]), "+f"(d[5]), "+f"(d[6]), "+f"(d[7]), "+f"(d[8]), "+f"(d[9]), "+f"(d[10]), "+f"(d[11]), "+f"(d[12]), "+f"(d[13]), "+f"(d[14]), "+f"(d[15])
  : "r"(a0), "r"(a1), "r"(a2), "r"(a3), "r"(db), "n"(TB), "n"(HB), "r"(scale_d));
}
template<int TB, uint32_t HB> __device__ __forceinline__ void wgmma_ra_n40(float (&d)[20], uint32_t a0, uint32_t a1, uint32_t a2, uint32_t a3, uint32_t db){
  asm volatile("{\n.reg .pred p;\n.reg .b64 a, b;\nsetp.ne.b32 p, 1, 0;\nmov.b64 b, {%24, %26};\n"
  "wgmma.mma_async.sync.aligned.m64n40k16.f32.bf16.bf16 {%0, %1, %2, %3, %4, %5, %6, %7, %8, %9, %10, %11, %12, %13, %14, %15, %16, %17, %18, %19}, {%20,%21,%22,%23}, b, p, 1, 1, %25;\n}\n"
  : "+f"(d[0]), "+f"(d[1]), "+f"(d[2]), "+f"(d[3]), "+f"(d[4]), "+f"(d[5]), "+f"(d[6]), "+f"(d[7]), "+f"(d[8]), "+f"(d[9]), "+f"(d[10]), "+f"(d[11]), "+f"(d[12]), "+f"(d[13]), "+f"(d[14]), "+f"(d[15]), "+f"(d[16]), "+f"(d[17]), "+f"(d[18]), "+f"(d[19])
  : "r"(a0), "r"(a1), "r"(a2), "r"(a3), "r"(db), "n"(TB), "n"(HB));
}
template<int TB, uint32_t HB> __device__ __forceinline__ void wgmma_rz_n40(float (&d)[20], uint32_t a0, uint32_t a1, uint32_t a2, uint32_t a3, uint32_t db){
  asm volatile("{\n.reg .pred p;\n.reg .b64 a, b;\nsetp.ne.b32 p, 0, 0;\nmov.b64 b, {%24, %26};\n"
  "wgmma.mma_async.sync.aligned.m64n40k16.f32.bf16.bf16 {%0, %1, %2, %3, %4, %5, %6, %7, %8, %9, %10, %11, %12, %13, %14, %15, %16, %17, %18, %19}, {%20,%21,%22,%23}, b, p, 1, 1, %25;\n}\n"
  : "=f"(d[0]), "=f"(d[1]), "=f"(d[2]), "=f"(d[3]), "=f"(d[4]), "=f"(d[5]), "=f"(d[6]), "=f"(d[7]), "=f"(d[8]), "=f"(d[9]), "=f"(d[10]), "=f"(d[11]), "=f"(d[12]), "=f"(d[13]), "=f"(d[14]), "=f"(d[15]), "=f"(d[16]), "=f"(d[17]), "=f"(d[18]), "=f"(d[19])
  : "r"(a0), "r"(a1), "r"(a2), "r"(a3), "r"(db), "n"(TB), "n"(HB));
}
template<int TB, uint32_t HB> __device__ __forceinline__ void wgmma_ra_n8(float (&d)[4], uint32_t a0, uint32_t a1, uint32_t a2, uint32_t a3, uint32_t db){
  asm volatile("{\n.reg .pred p;\n.reg .b64 a, b;\nsetp.ne.b32 p, 1, 0;\nmov.b64 b, {%8, %10};\n"
  "wgmma.mma_async.sync.aligned.m64n8k16.f32.bf16.bf16 {%0, %1, %2, %3}, {%4,%5,%6,%7}, b, p, 1, 1, %9;\n}\n"
  : "+f"(d[0]), "+f"(d[1]), "+f"(d[2]), "+f"(d[3])
  : "r"(a0), "r"(a1), "r"(a2), "r"(a3), "r"(db), "n"(TB), "n"(HB));
}
template<int TB, uint32_t HB> __device__ __forceinline__ void wgmma_rz_n8(float (&d)[4], uint32_t a0, uint32_t a1, uint32_t a2, uint32_t a3, uint32_t db){
  asm volatile("{\n.reg .pred p;\n.reg .b64 a, b;\nsetp.ne.b32 p, 0, 0;\nmov.b64 b, {%8, %10};\n"
  "wgmma.mma_async.sync.aligned.m64n8k16.f32.bf16.bf16 {%0, %1, %2, %3}, {%4,%5,%6,%7}, b, p, 1, 1, %9;\n}\n"
  : "=f"(d[0]), "=f"(d[1]), "=f"(d[2]), "=f"(d[3])
  : "r"(a0), "r"(a1), "r"(a2), "r"(a3), "r"(db), "n"(TB), "n"(HB));
}

constexpr int SEQ = 2048, DM = 1024, FF = 3584;
constexpr float LOG2E = 1.4426950408889634f;
constexpr uint32_t POLL_LIMIT = 1u << 22;
constexpr int NPRE = 2;
#define TRK_SLEEP 0
#define QW 12
#define RST_STEP 100
#define WD_STEP 300
#define WD_DELAY 0
#define SKM 0x251
#define LAG 1
#define PF_T0 6500
#define PF_DT 800
#define Q0L 1
#define NFFN_L NFFN
#define MAP 1
#define MAPC (64 * (gi & 1) + 8 * gx + (gi & 6) + rank)
#define PZ 4
constexpr int NFFN = 112;

constexpr uint32_t SB0 = 1024;
constexpr uint32_t KV_STAGE = 49152, R5 = 32768;
constexpr uint32_t OFF_X = 163840, OFF_S = 196608, OFF_WPHI = OFF_S + 20480, OFF_M = 229376, SMEM_BYTES = 232448;
constexpr uint32_t OFF_RS256 = 212992, OFF_ONES = OFF_RS256 + 1024, OFF_WPHIK1 = OFF_ONES + 1024, OFF_KVZ = OFF_S;
constexpr uint32_t OFF_WPHIK = OFF_S, OFF_BXK = OFF_S + 2048, OFF_AXK = OFF_S + 4096;
constexpr uint32_t OFF_AXQ = OFF_WPHI, OFF_BXQ = OFF_WPHI + 2048, OFF_WPHIQ = OFF_WPHI + 4096;
constexpr uint32_t B_FULLKV = OFF_M, B_EMPTYKV = OFF_M + 32, B_FULL5 = OFF_M + 64, B_EMPTY5 = OFF_M + 104;
constexpr uint32_t B_W = OFF_M + 144, B_X = OFF_M + 152, B_R = OFF_M + 160, B_AUX = OFF_M + 168, B_AUXQ = OFF_M + 176, B_KD = OFF_M + 184, B_RC = OFF_M + 192  ;
constexpr uint32_t B_FULLA = OFF_M + 768, B_QL = B_FULLA + 80, B_PUB = B_FULLA + 88, B_UO = B_FULLA + 96  ;
constexpr uint32_t OFF_SUMWR = OFF_M + 960, OFF_EP = OFF_M + 208, OFF_KEY = OFF_M + 216, OFF_H8 = OFF_M + 224;
constexpr uint32_t OFF_RSQ = OFF_M + 256, OFF_WR = OFF_M + 2048, OFF_XSEL = 4 * R5;
constexpr uint32_t OFF_ACT = OFF_XSEL + 4096, OFF_SCR = OFF_M + 2432, B_F = OFF_M + 896;
constexpr int KVP = 6 * 128;

enum { NB_G2E = 1, NB_XS = 2, NB_WG01 = 3, NB_ACT = 4, NB_Q0 = 5  , NB_ST = 14, NB_DN = 8, NB_OUT = 9, NB_ZERO = 10, NB_PUB = 11, NB_TOK = 10  , NB_L0 = 12  , NB_WG2 = 7, NB_QGO = 15 };

struct Scratch {
  bf16     o[SEQ * DM];
  uint4    part[16 * 8 * 128];
  uint32_t key[32 * 128];
  uint32_t cand[128 * (DM + 32)];
  uint32_t ypart[NFFN * DM];
  float4   kvacc[32 * KVP];
  uint2    stats[SEQ];
  uint32_t cskv[2 * DM];
  uint32_t csq[4 * DM];
  uint32_t oset[16 * 32];
  uint32_t epoch;
};
__device__ __align__(1024) Scratch g_scr;
#define TS(id)
#define TDUMP()
#define TS0_DECL()
#define TS0_READ()
#define TS0_WRITE()
#define TK(id)
#define TSW(id)

struct Params {
  CUtensorMap x128, x64, wkv, wq, wo, out, out16, wg, wu, phi;
  const bf16 *x, *wqkv, *wo_p, *wg_p, *wu_p, *wd_p, *wr;
  bf16* out_p;
  Scratch* g;
};

constexpr float EXP_LIM = 1.1529215e18f, ARG_LIM2 = 3600.f;
__device__ __forceinline__ void dual_exp2(const float (&p)[2][16], uint32_t (&ph)[4][8]) {
  #pragma unroll
  for (int h = 0; h < 2; h++)
    #pragma unroll
    for (int k = 0; k < 8; k++) { ph[2*h][k] = pack_bf16(ex2(p[h][2*k]), ex2(p[h][2*k+1])); ph[2*h+1][k] = pack_bf16(ex2(-p[h][2*k]), ex2(-p[h][2*k+1])); }
}
__device__ __forceinline__ void row_extremes(const float (&p)[16], const float (&c)[2], float (&m)[4]) {
  m[0] = m[2] = p[0]; m[1] = m[3] = p[2];
  #pragma unroll
  for (int i = 0; i < 16; i++) { m[(i >> 1) & 1] = fmaxf(m[(i >> 1) & 1], p[i]); m[2 + ((i >> 1) & 1)] = fminf(m[2 + ((i >> 1) & 1)], p[i]); }
  #pragma unroll
  for (int o = 1; o < 4; o <<= 1) {
    m[0] = fmaxf(m[0], __shfl_xor_sync(~0u, m[0], o)); m[1] = fmaxf(m[1], __shfl_xor_sync(~0u, m[1], o));
    m[2] = fminf(m[2], __shfl_xor_sync(~0u, m[2], o)); m[3] = fminf(m[3], __shfl_xor_sync(~0u, m[3], o));
  }
  m[0] *= -c[0]; m[1] *= -c[1]; m[2] *= c[0]; m[3] *= c[1];
}
__device__ __forceinline__ void dual_exp2_shifted(const float (&p)[2][16], uint32_t (&ph)[4][8]) {
  #pragma unroll
  for (int h = 0; h < 2; h++) {
    const float one[2] = {1.f, 1.f};
    float m[4];
    row_extremes(p[h], one, m);
    #pragma unroll
    for (int k = 0; k < 8; k++) {
      ph[2*h][k] = pack_bf16(ex2(p[h][2*k] + m[k & 1]), ex2(p[h][2*k+1] + m[k & 1]));
      ph[2*h+1][k] = pack_bf16(ex2(m[2 + (k & 1)] - p[h][2*k]), ex2(m[2 + (k & 1)] - p[h][2*k+1]));
    }
  }
}
__device__ __forceinline__ void row_sums(float (&s)[4][4], const uint32_t (&ph)[4][8], uint32_t ones) {
  #pragma unroll
  for (int i = 0; i < 4; i++) wgmma_rz_n8<0, H0>(s[i], ph[i][0], ph[i][1], ph[i][2], ph[i][3], ones);
  #pragma unroll
  for (int i = 0; i < 4; i++) wgmma_ra_n8<0, H0>(s[i], ph[i][4], ph[i][5], ph[i][6], ph[i][7], ones);
}
__device__ __forceinline__ uint32_t mul_bf16x2(uint32_t a, uint32_t b) { uint32_t r; asm("mul.rn.bf16x2 %0, %1, %2;" : "=r"(r) : "r"(a), "r"(b)); return r; }
__device__ __forceinline__ void normalize(uint32_t (&ph)[4][8], const float (&s)[4][4]) {
  #pragma unroll
  for (int i = 0; i < 4; i++) {
    const float i0 = rcp(s[i][0]), i1 = rcp(s[i][2]);
    const uint32_t n0 = pack_bf16(i0, i0), n1 = pack_bf16(i1, i1);
    #pragma unroll
    for (int k = 0; k < 4; k++) { ph[i][2*k] = mul_bf16x2(ph[i][2*k], n0); ph[i][2*k+1] = mul_bf16x2(ph[i][2*k+1], n1); }
  }
}
__device__ __forceinline__ void split_bf16(float a, float b, uint32_t& hi, uint32_t& lo) { hi = pack_bf16(a, b); lo = pack_bf16(a - bf_lo(hi), b - bf_hi(hi)); }
__device__ __forceinline__ void put_colsums(uint32_t base, int lane, float a, float b, float c, float d) {
  uint32_t h0, l0, h1, l1;
  split_bf16(a, b, h0, l0); split_bf16(c, d, h1, l1);
  const uint32_t ad = base + (lane >> 1) * 128 + (lane & 1) * 8;
  sts64(ad, h0, h1); sts64(ad + 16, l0, l1); sts64(ad + 32, h0, h1); sts64(ad + 48, l0, l1);
  sts128(base + (lane >> 1) * 128 + 64 + (lane & 1) * 32, 0, 0, 0, 0); sts128(base + (lane >> 1) * 128 + 80 + (lane & 1) * 32, 0, 0, 0, 0);
}
__device__ __forceinline__ float reduce8(const float (&v)[8], int lane) {
  const bool b4 = lane & 16, b3 = lane & 8, b2 = lane & 4;
  float a[4], b[2];
  #pragma unroll
  for (int i = 0; i < 4; i++) a[i] = (b4 ? v[4 + i] : v[i]) + __shfl_xor_sync(~0u, b4 ? v[i] : v[4 + i], 16);
  #pragma unroll
  for (int i = 0; i < 2; i++) b[i] = (b3 ? a[2 + i] : a[i]) + __shfl_xor_sync(~0u, b3 ? a[i] : a[2 + i], 8);
  return (b2 ? b[1] : b[0]) + __shfl_xor_sync(~0u, b2 ? b[0] : b[1], 4);
}
__device__ __forceinline__ bool tag_bad(uint4 v, uint32_t tg) { return (((v.x ^ tg) | (v.y ^ tg) | (v.z ^ tg) | (v.w ^ tg)) & 3) != 0; }

__global__ void __launch_bounds__(512, 1) fused_kernel(const __grid_constant__ Params P) {
  extern __shared__ __align__(1024) uint8_t smem_raw[];
  const uint32_t sb = smem_u32(smem_raw);
  const int tid = threadIdx.x, lane = tid & 31;
  const int warp = __shfl_sync(~0u, tid >> 5, 0), wg = warp >> 2, wp = warp & 3;
  const int cp = blockIdx.x >> 1, cu = cp - 36, cd = (cu * 37) >> 8;
  const int gi = cp < 4 ? 0 : cu < 0 ? (cp - 4) & 7 : 1 + cu - 7 * cd, gx = cp < 4 ? 4 + cp : cu < 0 ? (cp - 4) >> 3 : 4 + cd;
  const int rank = blockIdx.x & 1, c = MAPC;
  const int m256 = c >> 4, nkv = c & 15, m128 = c >> 3, j = c & 7;
  const int ha = 4 * (nkv >> 1) + (nkv & 1);

  Scratch* const G = P.g;
  if ((sb & 0x3ffff) != SB0) asm volatile("trap;");

  TS0_DECL();
  if (warp == 12) {
    const bool el = elect_one();
    TS0_READ();
    if (el) {
      #pragma unroll
      for (int i = 0; i < 4; i++) mbar_init(sb + B_FULLKV + 8 * i, 1);
      asm volatile("fence.mbarrier_init.release.cluster;" ::: "memory");
      fence_async_smem();
      #pragma unroll
      for (int s = 0; s < NPRE; s++) {
        const uint32_t st = sb + s * KV_STAGE, fb = sb + B_FULLKV + 8 * s;
        mbar_expect_tx(fb, KV_STAGE);
        tma_4d(st + 32768, &P.wkv, 0, 64 * s, nkv, 1, fb);
        tma_2d(st, &P.x128, 64 * s, 256 * m256, fb);
        tma_2d(st + 16384, &P.x128, 64 * s, 256 * m256 + 128, fb);
      }
    }
  } else if (tid == 0) {
    #pragma unroll
    for (int i = 0; i < 22; i++) mbar_init(sb + B_EMPTYKV + 8 * i, i >= 20 ? 4 : i < 4 ? 12 : (i >= 9 && i < 14) ? 4 : i == 17 || i == 18 ? 2 : 1);
    #pragma unroll
    for (int i = 0; i < 7; i++) mbar_init(sb + B_F + 8 * i, 1);
    #pragma unroll
    for (int i = 0; i < 16; i++) mbar_init(sb + B_FULLA + 8 * i, i < 11 ? 1 : i == 11 ? 2 : 4);
    asm volatile("fence.mbarrier_init.release.cluster;" ::: "memory");
    fence_async_smem();
  }
  __syncthreads();
  cluster_arrive();

  if (wg == 3) {
    asm volatile("setmaxnreg.dec.sync.aligned.u32 32;");
    cluster_wait();
    const bool el = elect_one();
    const uint64_t ef = policy_evict_first();
    auto fetch_o = [&](int i0, uint32_t so, uint32_t par) {
      uint32_t ready = 0;
      const bf16* base = G->o + (m128 * 16 + (i0 >> 3)) * 8192 + rank * 4096;
      const bf16* hint = base + (((j & 6) + (lane >> 2)) & 7) * 16384 + (lane & 3) * 1024 + 1022;
      #pragma unroll 1
      for (int i = i0 & 7; i < 8; i++) {
        uint32_t it = 0;
        while (((ready >> (4 * i)) & 15) != 15 && ++it < POLL_LIMIT) ready = __ballot_sync(~0u, ld32_rlx(hint) != ~0u);
        if (i0 == 2) {
          if (i == 2 && el) TS(rank ? 31 : 10);
          if (i == 2) mbar_wait2(sb + B_UO + 8 * rank, 0, sb + B_FULLA + 32 - 8 * rank, 0);
          if (i == 5) mbar_wait(sb + B_PUB, 0);
        } else if (i == 0) bar_sync(NB_L0, 64);
        mbar_wait(sb + B_EMPTY5 + so, par);
        if (el) {
          bulk_g2s_mc(sb + so * 4096 + rank * 8192, base + (((j & 6) + i) & 7) * 16384, 8192, sb + B_FULLA + 2 * so + 8 * rank, ef);
          if (i == (i0 & 7)) TS(i0 == 2 ? (rank ? 4 : 12) : (rank ? 9 : 13));
        }
        so += 8;
        if (so == 40) { so = 0; par ^= 1; }
      }
    };
    if (wp == 0) {
      {
        #pragma unroll 1
        for (int kb = NPRE; kb < 16; kb++) {
          const uint32_t st = sb + (kb & 3) * KV_STAGE, fb = sb + B_FULLKV + 8 * (kb & 3);
          mbar_wait(fb + (B_EMPTYKV - B_FULLKV), ~(kb >> 2) & 1);
          if (el) {
            mbar_expect_tx(fb, KV_STAGE);
            tma_2d_mc(st + rank * 16384, &P.x128, 64 * kb, 256 * m256 + 128 * rank, fb);
            tma_4d_h(st + 32768, &P.wkv, 0, 64 * kb, nkv, 1, fb, ef);
          }
        }
        TS0_WRITE();
        uint64_t ord = 0xf3120edcba987654ull;
        uint32_t so = 0, par = 1;
        #pragma unroll 1
        for (int i = 0; i < 16; i++) {
          const uint32_t st = sb + so * 4096, fb = sb + B_FULL5 + so;
          const int k0 = (64 * (uint32_t)ord + 128 * (j & 6)) & 960;
          mbar_wait(i < 5 ? sb + B_EMPTYKV + so - (i > 1 ? 8 : 0) : fb + (B_EMPTY5 - B_FULL5), par);
          if (el) {
            mbar_expect_tx(fb, R5);
            tma_2d_mc_h(st + rank * 8192, &P.x64, k0, 128 * m128 + 64 * rank, fb, ef);
            tma_3d_h(st + 16384, &P.wq, 0, k0, 2 * j, fb, ef);
          }
          ord >>= 4; so += 8;
          if (so == 40) { so = 0; par ^= 1; }
        }
        #pragma unroll 1
        for (int i = 0; i < 16; i++) {
          const uint32_t fb = sb + B_FULL5 + so, fa = sb + B_FULLA + 2 * so, na = i == rank ? 0 : 8192;
          if (i == 1) { if (el) mbar_arrive(sb + B_QL); mbar_wait2(sb + B_FULL5 + 16, 0, sb + B_FULL5 + 24, 0); mbar_wait(sb + B_FULL5 + 32, 0); if (el) mbar_arrive(sb + B_R); }
          mbar_wait(fb + (B_EMPTY5 - B_FULL5), par);
          if (el) {
            mbar_expect_tx(fb, 16384);
            tma_4d_h(sb + so * 4096 + 16384, &P.wo, 0, 128 * (((j & 6) + i) & 7) + 4 * (i & 8), 0, 2 * j, fb, ef);
            mbar_expect_tx(fa, na); mbar_expect_tx(fa + 8, na);
          }
          so += 8;
          if (so == 40) { so = 0; par ^= 1; }
        }
        if (el) mbar_arrive(sb + B_QL);
        if (c < NFFN_L) {
          #pragma unroll 1
          for (int i = 2; i < 6; i++) {
            const int ch = i >> 1;
            const uint32_t st = sb + (1 + ch) * R5 + (i & 1) * 16384, fb = sb + B_F + 8 * i;
            if (!(i & 1)) mbar_wait(sb + B_EMPTY5 + 8 * (1 + ch), 1);
            if (i == PZ) mbar_wait(sb + B_F + 48, 0);
            mbar_wait(fb - 16, 0);
            if (el) { mbar_expect_tx(fb, 16384); tma_2d(st, (i & 1) ? &P.wu : &P.wg, 32 * c, 256 + 256 * ch, fb); }
          }
        }
      }
    } else if (wp == 3) {
      const uint32_t t_start = (uint32_t)clock();
      if (el) {
        mbar_expect_tx(sb + B_W, 12288);
        #pragma unroll 1
        for (int i = 0; i < 6; i++) tma_2d(sb + (i == 0 ? OFF_WPHIK : i == 1 ? OFF_WPHIK1 : OFF_WPHIQ + 2048 * (i - 2)), &P.phi, 0, 32 * (i < 2 ? 2 * nkv + i : 4 * j + 2 * (i & 1) + ((i - 2) >> 1)), sb + B_W);
        prefetch_map(&P.x64); prefetch_map(&P.wq); prefetch_map(&P.wo);
        prefetch_map(&P.out); prefetch_map(&P.wg); prefetch_map(&P.wu);
      }
      const uint32_t ep1 = ld32_rlx(&G->epoch) + 1, nt = (ep1 + 2) & 3;
      #pragma unroll 1
      for (int i = lane; i < 128; i += 32) st128_rlx(&G->part[c * 128 + i], nt, nt, nt, nt);
      #pragma unroll 1
      for (int i = 0; i < 8; i++) {
        st128_rlx(&G->cand[(m128 * 8 + i) * (DM + 32) + 128 * j + 4 * lane], nt, nt, nt, nt);
        if (c < NFFN) st128_rlx(&G->ypart[c * DM + 128 * i + 4 * lane], nt, nt, nt, nt);
      }
      if (lane < 16 && j == 0) st128_rlx(&G->cand[(m128 * 8 + (lane >> 1)) * (DM + 32) + DM + 4 * (lane & 1)], nt, nt, nt, nt);
      if (lane < 8) st128_rlx(&G->key[(4 * j + (lane >> 1)) * 128 + m128 * 8 + 4 * (lane & 1)], nt, nt, nt, nt);
      if (c < 32) {
        #pragma unroll 1
        for (int i = lane; i < KVP; i += 32) st128_rlx(&G->kvacc[(ha + 2 * m256) * KVP + i], 0, 0, 0, 0);
      }
      fence_gpu();
      bar_arrive(NB_ZERO, 160);
      if (el) {
        #pragma unroll 1
        for (int i = 0; i < 30; i++) {
          while ((uint32_t)clock() - t_start < (uint32_t)(PF_T0 + PF_DT * i)) __nanosleep(64);
          if (i < 4) { bulk_prefetch(P.wqkv + (size_t)(256 * i + c) * (3 * DM), 2048); bulk_prefetch(P.wqkv + (size_t)(256 * i + 128 + c) * (3 * DM), 2048); }
          else if (i < 6) bulk_prefetch(P.wo_p + (size_t)c * 8192 + (i - 4) * 4096, 8192);
          else if (i < 22) bulk_prefetch(((i & 1) ? P.wu_p : P.wg_p) + (size_t)((i - 6) >> 1) * 458752 + c * 3584, 7168);
          else if (c < NFFN) bulk_prefetch(P.wd_p + (size_t)c * 32768 + (i - 22) * 4096, 8192);
        }
      }
      __syncwarp();
      mbar_wait(sb + B_AUXQ, 0);
      for (uint32_t it = 0; __any_sync(~0u, ld32_rlx(&G->oset[m128 * 32 + (lane & 15)]) != ep1) && it < POLL_LIMIT; it++) {}
      fence_acquire_gpu();
      bar_arrive(NB_G2E, 64);
      mbar_wait(sb + B_RC, 0);
      fetch_o(2, 24, 0);
      bar_arrive(NB_L0, 64);
    } else {
      const int half = wp - 1;
      const uint32_t ep1 = ld32_rlx(&G->epoch) + 1, tg = ep1 & 3;
      {
        uint32_t it = 0;
        sts128(sb + OFF_ONES + half * 512 + lane * 16, 0x3f803f80u, 0x3f803f80u, 0x3f803f80u, 0x3f803f80u);
        mbar_wait(sb + B_W, 0);
        #pragma unroll 1
        for (int i = lane; i < 1024; i += 32) { st128_rlx(G->o + (m128 * 16 + 2 * j + half) * 8192 + 8 * i, ~0u, ~0u, ~0u, ~0u); __nanosleep(RST_STEP); }
        bar_sync(NB_PUB, 192);
        const uint4* src = reinterpret_cast<const uint4*>(&G->stats[256 * m256 + 128 * half]) + lane;
        const uint4* srk = reinterpret_cast<const uint4*>(&G->cskv[128 * nkv]) + lane;
        uint4 v0, v1, vk;
        it = 0;
        do { v0 = ld128_rlx(src); v1 = ld128_rlx(src + 32); vk = ld128_rlx(srk); }
        while ((tag_bad(v0, tg) || tag_bad(v1, tg) || tag_bad(vk, tg)) && ++it < POLL_LIMIT);
        fence_acquire_gpu();
        if (half) put_colsums(sb + OFF_BXK, lane, untag(vk.x), untag(vk.y), untag(vk.z), untag(vk.w));
        #pragma unroll
        for (int i = 0; i < 2; i++) {
          const uint4 v = i ? v1 : v0;
          uint32_t hi, lo;
          split_bf16(-0.5f * untag(v.x), -0.5f * untag(v.z), hi, lo);
          const uint32_t h0 = __byte_perm(hi, hi, 0x1010), h1 = __byte_perm(hi, hi, 0x3232), l0 = __byte_perm(lo, lo, 0x1010), l1 = __byte_perm(lo, lo, 0x3232);
          const uint32_t a = sb + OFF_AXK + half * 2048 + i * 1024 + lane * 32;
          sts128(a, h0, l0, 0, 0); sts128(a + 16, h1, l1, 0, 0);
          sts64(sb + OFF_RS256 + half * 512 + i * 256 + lane * 8, v.y & ~3u, v.w & ~3u);
          if (half == (m128 & 1)) {
            const uint32_t aq = sb + OFF_AXQ + i * 1024 + lane * 32;
            sts128(aq, h0, l0, 0, 0); sts128(aq + 16, h1, l1, 0, 0);
            sts64(sb + OFF_RSQ + i * 256 + lane * 8, v.y & ~3u, v.w & ~3u);
          }
        }
        fence_async_smem();
        __syncwarp();
        if (el) { sts32(sb + OFF_EP, ep1); mbar_arrive(sb + B_AUX); if (!half) TS(1); }
        fence_gpu();
        __syncwarp();
        if (el) { st32_rlx(&G->oset[m128 * 32 + 2 * j + half], ep1); if (half) mbar_arrive(sb + B_AUXQ); }
        if (!half) {
          const uint4* src = reinterpret_cast<const uint4*>(&G->csq[128 * j]) + lane;
          uint4 v0, v1, v2, v3;
          do { v0 = ld128_rlx(src); v1 = ld128_rlx(src + DM / 4); v2 = ld128_rlx(src + DM / 2); v3 = ld128_rlx(src + 3 * DM / 4); }
          while ((tag_bad(v0, tg) || tag_bad(v1, tg) || tag_bad(v2, tg) || tag_bad(v3, tg)) && ++it < POLL_LIMIT);
          put_colsums(sb + OFF_BXQ, lane, (untag(v0.x) + untag(v1.x)) + (untag(v2.x) + untag(v3.x)), (untag(v0.y) + untag(v1.y)) + (untag(v2.y) + untag(v3.y)),
                      (untag(v0.z) + untag(v1.z)) + (untag(v2.z) + untag(v3.z)), (untag(v0.w) + untag(v1.w)) + (untag(v2.w) + untag(v3.w)));
          fence_async_smem();
          __syncwarp();
          if (el) mbar_arrive(sb + B_AUXQ);
        }
      }
      if (half == 0) bar_sync(NB_G2E, 64);
      else if (c < NFFN_L) {
        if (Q0L) mbar_wait(sb + B_PUB, 0);
        mbar_wait2(sb + B_KD, 0, sb + B_QL, 0);
        if (el) { mbar_expect_tx(sb + B_X, R5); tma_2d(sb + OFF_X, &P.wg, 32 * c, 0, sb + B_X); tma_2d(sb + OFF_X + 16384, &P.wu, 32 * c, 0, sb + B_X); }
      }
      {
        #pragma unroll 1
        for (int hh = 0; hh < 2; hh++) {
          const uint32_t src = sb + (half ? (hh ? OFF_KVZ : OFF_WPHI) : (1 + rank) * R5 + hh * 8192), fa = sb + B_FULLA + 16 + 16 * rank + 8 * hh;
          if (!half) mbar_wait(fa, 0);
          mbar_wait(sb + B_UO + 16 * half + 8 * hh, 0);
          if (el) {
            bulk_s2g(G->o + (m128 * 16 + 2 * j + half) * 8192 + hh * 4096, src, 8192);
            if (!half) bulk_s2peer(mapa(src, rank ^ 1), src, 8192, mapa(fa, rank ^ 1));
            if (!half && !hh) TS(7);
          }
        }
        if (el) {
          bulk_commit(); bulk_wait_read();
          if (!half) { mbar_arrive_at(sb + B_PUB, 0, 1); mbar_arrive_at(sb + B_PUB, 1, 1); }
        }
        __syncwarp();
      }
      if (!half) fetch_o(8, 32, 1);
      else if (c < NFFN_L) {
        mbar_wait(sb + B_QL, 1);
        if (el) {
          mbar_expect_tx(sb + B_F, 16384); tma_2d(sb + OFF_S, &P.wg, 32 * c, 256, sb + B_F);
          mbar_expect_tx(sb + B_F + 8, 16384); tma_2d(sb + OFF_S + 16384, &P.wu, 32 * c, 256, sb + B_F + 8);
        }
      }
      __syncwarp();
      if (half == 0) {
        bar_sync(NB_OUT, 288);
        bar_sync(NB_XS, 416);
        const int row = (int)__float_as_uint(ldsf(sb + OFF_KEY)) - 128 * m128;
        if ((uint32_t)row >= 128u) {
          if (el) tma_store_3d_h(&P.out, 0, 128 * m128, 2 * j, sb + R5, ef);
        } else {
          #pragma unroll 1
          for (int i = 0; i < 16; i++)
            if (el && (i & 7) != (row >> 4)) tma_store_2d_h(&P.out16, 128 * j + 64 * (i >> 3), 128 * m128 + 16 * (i & 7), sb + R5 + 2048 * i, ef);
          #pragma unroll 1
          for (int i = 0; i < 8; i++) {
            const int r = (row & ~15) + 2 * i + (lane >> 4), ch = lane & 15;
            const uint4 v = lds128(sb + R5 + (ch >> 3) * 16384 + r * 128 + (((ch & 7) ^ (r & 7)) << 4));
            if (r != row) *reinterpret_cast<uint4*>(P.out_p + (size_t)(128 * m128 + r) * DM + 128 * j + 8 * ch) = v;
          }
        }
        if (el) { bulk_commit(); bulk_wait_all(); }
      }
    }
    __syncwarp();
    cluster_arrive(); cluster_wait();
    return;
  }

  asm volatile("setmaxnreg.inc.sync.aligned.u32 160;");
  cluster_wait();
  const int t = tid & 127, g = lane >> 2;
  const uint32_t sa = (16 * wp + (lane & 15)) * 128 + (((lane >> 4) ^ (lane & 7)) << 4);

  if (wg == 2) {
    float s[2] = {0.f, 0.f}, s2[2] = {0.f, 0.f}, ck[8] = {0.f, 0.f, 0.f, 0.f, 0.f, 0.f, 0.f, 0.f}, cs[8] = {0.f, 0.f, 0.f, 0.f, 0.f, 0.f, 0.f, 0.f};
    const uint32_t ebr = mapa(sb + B_EMPTYKV, lane & 1), tg = (ld32_rlx(&G->epoch) + 1) & 3;
    auto addx = [&](const uint4 v) {
      const uint32_t w[4] = {v.x, v.y, v.z, v.w};
      #pragma unroll
      for (int e = 0; e < 4; e++) { const float a = bf_lo(w[e]), d = bf_hi(w[e]); s[0] += a; s[1] += d; s2[0] = fmaf(a, a, s2[0]); s2[1] = fmaf(d, d, s2[1]); }
    };
    auto addc = [&](const uint4 v, float (&o)[8]) {
      o[0] += bf_lo(v.x); o[1] += bf_hi(v.x); o[2] += bf_lo(v.y); o[3] += bf_hi(v.y); o[4] += bf_lo(v.z); o[5] += bf_hi(v.z); o[6] += bf_lo(v.w); o[7] += bf_hi(v.w);
    };
    {
      const uint32_t ra = (16 * nkv + (t >> 3)) * 128 + (t & 7) * 16;
      const uint32_t ca = 32768 + (m256 >> 2) * 8192 + (t >> 1) * 128 + (((2 * (m256 & 3) + (t & 1)) ^ ((t >> 1) & 7)) << 4);
      const bf16* gx = P.x + (size_t)(256 * m256 + 16 * nkv + (t >> 3)) * DM + 640 + (t & 7) * 8;
      const bf16* gw = P.wqkv + (size_t)(640 + (t >> 1)) * (3 * DM) + (1 + (m256 >> 2)) * DM + 64 * nkv + 16 * (m256 & 3) + 8 * (t & 1);
      uint4 u[4];
      #pragma unroll
      for (int e = 0; e < 4; e++) u[e] = make_uint4(0, 0, 0, 0);
      #pragma unroll 1
      for (int kb = 0; kb < 10; kb++) {
        const uint32_t st = sb + (kb & 3) * KV_STAGE;
        mbar_wait(sb + B_FULLKV + 8 * (kb & 3), (kb >> 2) & 1);
        const uint4 x0 = lds128(st + ra), w0 = lds128(st + ca);
        addx(x0); addc(w0, ck);
        __syncwarp();
        if (lane < 2) mbar_arrive_remote(ebr + 8 * (kb & 3), 1);
        if ((SKM >> kb) & 1) {
          addx(u[0]); addx(u[1]); addc(u[2], ck); addc(u[3], ck);
          if (kb < 9) {
            u[0] = ld128_keep(gx); u[1] = ld128_keep(gx + 64); u[2] = ld128_keep(gw); u[3] = ld128_keep(gw + 64 * 3 * DM);
            gx += 128; gw += 128 * 3 * DM;
          }
        }
      }
    }
    TK(82);
    const uint32_t scr = sb + OFF_SCR + 128;
    float sx = s[0] + s[1], sq = s2[0] + s2[1];
    #pragma unroll
    for (int o = 1; o < 8; o <<= 1) { sx += __shfl_xor_sync(~0u, sx, o); sq += __shfl_xor_sync(~0u, sq, o); }
    float v = reduce8(ck, lane);
    v += __shfl_xor_sync(~0u, v, 2);
    if (!(lane & 2)) stsf(scr + (wp * 16 + 8 * (lane & 1) + (lane >> 2)) * 4, v);

    bar_sync(NB_ZERO, 160);
    if ((lane & 7) == 0) {
      const float mean = sx * (1.f / DM);
      st64_rlx(&G->stats[256 * m256 + 16 * nkv + (t >> 3)], tagw(mean, tg), tagw(rsqrtf(fmaxf(sq * (1.f / DM) - mean * mean, 0.f) + 1e-5f), tg));
    }
    if (wp == 1 && lane < 16) {
      const uint32_t a = scr + lane * 4;
      st32_rlx(&G->cskv[128 * nkv + 16 * m256 + lane], tagw((ldsf(a) + ldsf(a + 64)) + (ldsf(a + 128) + ldsf(a + 192)), tg));
    }
    __syncwarp();
    bar_arrive(NB_PUB, 192);
    TSW(23);
    const uint4 wv = ld128_keep(P.wr + t * 8);
    #pragma unroll 1
    for (int i = 0; i < 2; i++) {
      const bf16* gq = P.wqkv + (size_t)(256 * (c >> 5) + 128 * i + (t >> 2)) * (3 * DM) + 32 * (c & 31) + 8 * (t & 3);
      const uint4 u0 = ld128_keep(gq), u1 = ld128_keep(gq + 32 * 3 * DM), u2 = ld128_keep(gq + 64 * 3 * DM), u3 = ld128_keep(gq + 96 * 3 * DM);
      addc(u0, cs); addc(u1, cs); addc(u2, cs); addc(u3, cs);
    }
    float sw = (bf_lo(wv.x) + bf_hi(wv.x)) + (bf_lo(wv.y) + bf_hi(wv.y)) + (bf_lo(wv.z) + bf_hi(wv.z)) + (bf_lo(wv.w) + bf_hi(wv.w));
    #pragma unroll
    for (int o = 16; o; o >>= 1) sw += __shfl_xor_sync(~0u, sw, o);
    if (lane == 0) stsf(sb + OFF_SUMWR + wp * 4, sw);
    if ((t >> 4) == j) {
      const uint32_t a = sb + OFF_WR + (t & 15) * 32;
      sts128(a, wv.x << 16, wv.x & 0xffff0000u, wv.y << 16, wv.y & 0xffff0000u);
      sts128(a + 16, wv.z << 16, wv.z & 0xffff0000u, wv.w << 16, wv.w & 0xffff0000u);
    }
    v = reduce8(cs, lane);
    bar_sync(NB_WG2, 128);
    stsf(scr + (wp * 32 + 8 * (lane & 3) + (lane >> 2)) * 4, v);
    bar_sync(NB_WG2, 128);
    if (wp == 0) {
      const uint32_t a = scr + lane * 4;
      st32_rlx(&G->csq[(c >> 5) * DM + 32 * (c & 31) + lane], tagw((ldsf(a) + ldsf(a + 128)) + (ldsf(a + 256) + ldsf(a + 384)), tg));
    }
    TSW(15);
  }

  uint32_t xr[32];
  {
    const bool isq = wg == 2;
    float acc[2][64];
    {
      const uint32_t emptyb = mapa(sb + (isq ? B_EMPTY5 : B_EMPTYKV), t & 1);
      if (!isq) {
        mbar_wait(sb + B_FULLKV, 0);
        if (wg == 0) { TSW(2); }
        #pragma unroll 1
        for (int kb = 0; kb < 16; kb++) {
          if (wg == 0) { TK(kb); }
          const uint32_t da = dlo(SB0, 16) + wg * 1024 + (kb & 3) * (KV_STAGE >> 4), db = dlo(SB0 + 32768, 8192) + (kb & 3) * (KV_STAGE >> 4);
          wg_fence();
          #pragma unroll
          for (int k = 0; k < 4; k++) {
            wgmma_ss_n128<0, 1, H128, H128>(acc[0], da + 2 * k, db + 128 * k, k > 0 || kb != 0);
            wgmma_ss_n128<0, 1, H128, H128>(acc[1], da + 512 + 2 * k, db + 128 * k, k > 0 || kb != 0);
          }
          wg_commit();
          wg_wait<1>();
          if (kb > 0 && t < 2) mbar_arrive_remote(emptyb + 8 * ((kb - 1) & 3), kb > 10 ? 3 : 1);
          if (kb < 15) mbar_wait(sb + B_FULLKV + 8 * ((kb + 1) & 3), ((kb + 1) >> 2) & 1);
          if (kb == 15 - LAG && wg == 1) bar_sync(NB_WG01, 256);
        }
        bar_arrive(wg ? NB_QGO : NB_WG01, 256);
      } else {
        uint32_t so = 0, po = 0, par = 0;
        mbar_wait(sb + B_FULL5, 0);
        bar_sync(NB_QGO, 256);
        TSW(11);
        #pragma unroll 1
        for (int kb = 0; kb < 16; kb++) {
          TK(16 + kb);
          const uint32_t da = dlo(SB0, 16) + so * 256, db = dlo(SB0 + 16384, 8192) + so * 256;
          #pragma unroll
          for (int k = 0; k < 4; k++) {
            wg_fence();
            wgmma_ss_n128<0, 1, H128, H128>(acc[0], da + 2 * k, db + 128 * k, k > 0 || kb != 0);
            wgmma_ss_n128<0, 1, H128, H128>(acc[1], da + 512 + 2 * k, db + 128 * k, k > 0 || kb != 0);
            wg_commit();
            if (k == 1 && kb > 0 && t < 2) mbar_arrive_remote(emptyb + po, 2);
            if (k == 3) {
              po = so; so += 8;
              if (so == 40) { so = 0; par ^= 1; }
              if (kb < 15) mbar_wait(sb + B_FULL5 + so, par);
            }
            if ((QW >> k) & 1) wg_wait<2>(); else wg_wait<1>();
          }
        }
        mbar_wait(sb + B_AUXQ, 0);
      }
      mbar_wait(sb + B_AUX, 0);
      const uint32_t xa = dlo(SB0, 0) + (isq ? OFF_AXQ >> 4 : (OFF_AXK >> 4) + wg * 128), xb = dlo(SB0, 0) + (isq ? OFF_BXQ >> 4 : OFF_BXK >> 4);
      wg_fence();
      wgmma_sa_n128<0, 1, H0, H0>(acc[0], xa, xb);
      wgmma_sa_n128<0, 1, H0, H0>(acc[1], xa + 64, xb);
      wg_commit();
      if (isq) mbar_wait(sb + B_RC, 0);
      wg_wait<0>();
      if (t < 2) mbar_arrive_remote(emptyb + (isq ? 0 : 24), isq ? 2 : 3);
      if (wg != 1) { TSW(wg ? 8 : 3); }
      fence_regs(acc[0]); fence_regs(acc[1]);
    }
    if (isq) {
      #pragma unroll
      for (int i = 0; i < 2; i++) {
        const uint32_t ta = sb + (1 + rank) * R5 + sa + i * 8192;
        if (i) mbar_wait(sb + B_RC + 8, 0);
        #pragma unroll
        for (int k = 0; k < 4; k++) {
          const float* a = &acc[i][32 * (k >> 1) + 8 * (k & 1)];
          stsm4(ta ^ (k << 5), pack_bf16(a[0], a[1]), pack_bf16(a[2], a[3]), pack_bf16(a[4], a[5]), pack_bf16(a[6], a[7]));
        }
        fence_async_smem();
        bar_arrive(NB_Q0 + i, 256);
      }
      #pragma unroll
      for (int i = 0; i < 32; i++) { const float* a = &acc[i >> 4][16 + 32 * ((i >> 3) & 1) + 2 * (i & 7)]; xr[i] = pack_bf16(a[0], a[1]); }
      TSW(26);
    } else {
      const uint32_t stg = sb + OFF_X + (1 - wg) * 24576;
      const uint32_t va = stg + 16384 + (16 * wp + (lane & 15)) * 64 + (((lane >> 4) ^ ((lane >> 1) & 3)) << 4);
      const uint32_t ra = sb + OFF_RS256 + (128 * wg + 16 * wp + g) * 4;
      const float rs[4] = {ldsf(ra), ldsf(ra + 32), ldsf(ra + 256), ldsf(ra + 288)};
      float p[2][16];
      uint32_t vf[16], kf[2][16];
      auto project = [&](const uint32_t (&f)[16], uint32_t db) {
        wg_fence();
        #pragma unroll
        for (int i = 0; i < 2; i++) {
          wgmma_rs_n32<1, H64>(p[i], f[8*i], f[8*i+1], f[8*i+2], f[8*i+3], db, 0);
          wgmma_ra_n32<1, H64>(p[i], f[8*i+4], f[8*i+5], f[8*i+6], f[8*i+7], db + 64);
        }
        wg_commit();
      };
      auto fold = [&](uint32_t (&f)[16], int col, float sc) {
        #pragma unroll
        for (int i = 0; i < 16; i++) {
          const float r = rs[2 * (i >> 3) + (i & 1)] * sc;
          f[i] = pack_bf16(acc[i >> 3][col + 2 * (i & 7)] * r, acc[i >> 3][col + 2 * (i & 7) + 1] * r);
          asm volatile("" : "+r"(f[i]));
        }
      };
      auto put_v = [&](const uint32_t (&f)[16]) {
        #pragma unroll
        for (int k = 0; k < 4; k++) stsm4((va ^ ((k & 1) << 5)) + (k >> 1) * 4096, f[4*k], f[4*k+1], f[4*k+2], f[4*k+3]);
      };
      fold(vf, 48, 1.f);
      mbar_wait(sb + B_W, 0);
      fold(kf[0], 0, LOG2E);
      #pragma unroll
      for (int i = 0; i < 32; i++) p[i >> 4][i & 15] = acc[i >> 4][i & 15];
      project(kf[0], dlo(SB0 + OFF_WPHIK, 16));
      mbar_wait(sb + B_W, 0);
      {
        uint32_t v0[16];
        fold(kf[1], 16, LOG2E);
        fold(v0, 32, 1.f);
        if (wg == 1) bar_sync(NB_DN, 256);
        put_v(v0);
      }
      wg_wait<0>();
      fence_regs(p[0]); fence_regs(p[1]);
      if (wg == 1) bar_arrive(NB_WG01, 256);
      #pragma unroll 1
      for (int h = 0; h < 2; h++) {
        uint32_t ph[4][8];
        float rsum[4][4];
        dual_exp2(p, ph);
        wg_fence();
        row_sums(rsum, ph, dlo(SB0 + OFF_ONES, 128));
        wg_commit();
        if (wg == 0 && h == 0) { bar_arrive(NB_DN, 256); bar_sync(NB_WG01, 256); }
        if (h == 1) {
          if (wg == 1) bar_sync(NB_DN, 256);
          put_v(vf);
        }
        wg_wait<0>();
        #pragma unroll
        for (int i = 0; i < 4; i++) fence_regs(rsum[i]);
        if (__builtin_expect(__any_sync(~0u, !((rsum[0][0] + rsum[0][2]) + (rsum[1][0] + rsum[1][2]) + (rsum[2][0] + rsum[2][2]) + (rsum[3][0] + rsum[3][2]) < EXP_LIM)), 0)) {
          dual_exp2_shifted(p, ph);
          #pragma unroll
          for (int i = 0; i < 8; i++) {
            const uint32_t* f = &ph[i >> 1][i & 1];
            float a = (bf_lo(f[0]) + bf_hi(f[0])) + (bf_lo(f[2]) + bf_hi(f[2])) + (bf_lo(f[4]) + bf_hi(f[4])) + (bf_lo(f[6]) + bf_hi(f[6]));
            a += __shfl_xor_sync(~0u, a, 1);
            rsum[i >> 1][2 * (i & 1)] = a + __shfl_xor_sync(~0u, a, 2);
          }
        }
        if (h == 0) project(kf[1], dlo(SB0 + OFF_WPHIK1, 16));
        normalize(ph, rsum);
        #pragma unroll
        for (int i = 0; i < 8; i++) {
          const uint32_t* f = &ph[i >> 1][4 * (i & 1)];
          stsm4(((stg + sa) ^ ((i & 3) << 5)) + (i >> 2) * 8192, f[0], f[1], f[2], f[3]);
        }
        fence_async_smem();
        TK(50 + 8 * wg + 4 * h);
        if (wg == h) {
          float kv[20];
          #pragma unroll
          for (int w = 0; w < 2; w++) {
            const uint32_t da = dlo(SB0 + OFF_X, 16) + (h ^ w ^ 1) * 1536, db = dlo(SB0 + OFF_X + 16384, OFF_ONES - OFF_X - 16384) - (h ^ w ^ 1) * (1536 * 65535);
            if (w) bar_sync(NB_ST, 256); else bar_sync(NB_L0 + h, 128);
            wg_fence();
            #pragma unroll
            for (int k = 0; k < 8; k++) {
              if (k == 0 && w == 0) wgmma_sz_n40<1, 1, H128, H64>(kv, da, db);
              else wgmma_sa_n40<1, 1, H128, H64>(kv, da + k * 128, db - k * (64 * 65535));
            }
            wg_commit();
          }
          float4* dst = &G->kvacc[(ha + 2 * h) * KVP + t];
          wg_wait<0>();
          fence_regs(kv);
          TK(51 + 8 * wg + 4 * h);
          if (h == 0) bar_arrive(NB_DN, 256); else if (t == 0) mbar_arrive(sb + B_KD);
          kv[17] = kv[18];
          #pragma unroll
          for (int i = 0; i < 6; i++) red_add_f32x4(dst + 128 * i, kv[3*i], kv[3*i+1], kv[3*i+2], 1.f);
          TSW(29 + h);
        } else bar_arrive(NB_ST, 256);
        wg_wait<0>();
        fence_regs(p[0]); fence_regs(p[1]);
      }
      #pragma unroll
      for (int i = 0; i < 32; i++) asm volatile("mov.b32 %0, 0;" : "=r"(xr[i]));
    }
    #pragma unroll 1
    for (int e = wg; e < wg + 1 + (wg >> 1); e++) {
      const uint4* src = reinterpret_cast<const uint4*>(&G->kvacc[(4 * j + e) * KVP + t]);
      uint4 v[6];
      uint32_t it = 0, bad;
      TK(48 + 4 * e);
      do {
        bad = 0;
        #pragma unroll
        for (int i = 0; i < 6; i++) { v[i] = ld128_rlx(src + 128 * i); bad |= v[i].w ^ 0x41000000u; }
      } while (__any_sync(~0u, bad != 0) && ++it < POLL_LIMIT);
      TK(49 + 4 * e);
      mbar_wait(sb + B_KD, 0);
      float f[18];
      #pragma unroll
      for (int i = 0; i < 6; i++) { f[3*i] = __uint_as_float(v[i].x); f[3*i+1] = __uint_as_float(v[i].y); f[3*i+2] = __uint_as_float(v[i].z); }
      const uint32_t ka = sb + OFF_KVZ + e * 5120 + wp * 1280 + lane * 16;
      stsm4(ka, pack_bf16(f[0], f[1]), pack_bf16(f[2], f[3]), pack_bf16(f[4], f[5]), pack_bf16(f[6], f[7]));
      stsm4(ka + 512, pack_bf16(f[8], f[9]), pack_bf16(f[10], f[11]), pack_bf16(f[12], f[13]), pack_bf16(f[14], f[15]));
      stsm2(ka + 1024, pack_bf16(f[16], 1.f), pack_bf16(f[17], 1.f));
    }
    if (!isq) {
      mbar_wait(sb + B_R, 0);
      #pragma unroll
      for (int k = 0; k < 8; k++) ldsm4(((sb + (1 + rank) * R5 + wg * 8192 + sa) ^ ((k & 3) << 5)) + (k >> 2) * 2 * R5, xr[4*k], xr[4*k+1], xr[4*k+2], xr[4*k+3]);
      fence_async_smem();
      __syncwarp();
      if (lane == 0) mbar_arrive(sb + B_RC + 8 * wg);
      if (wg == 1) bar_arrive(NB_DN, 256);
    }
    TSW(wg == 0 ? 5 : wg == 1 ? 25 : 6);
    #pragma unroll 1
    for (int e = wg; e < wg + 1 + (wg >> 1); e++) {
      const int half = e >> 1, hh = e & 1, turn = e;
      const uint32_t ao = half ? (hh ? OFF_KVZ : OFF_WPHI) : (1 + rank) * R5 + hh * 8192, at = sb + ao + sa;
      if (isq) {
        if (hh) mbar_wait2(sb + B_UO, 0, sb + B_UO + 8, 0); else bar_sync(NB_TOK + 1, 256);
        #pragma unroll
        for (int k = 0; k < 4; k++) stsm4(at ^ (k << 5), xr[4*k], xr[4*k+1], xr[4*k+2], xr[4*k+3]);
        #pragma unroll
        for (int i = 0; i < 16; i++) xr[i] = xr[16 + i];
        fence_async_smem();
      }
      float p[2][16];
      #pragma unroll
      for (int i = 0; i < 32; i++) asm volatile("mov.b32 %0, 0;" : "=f"(p[i >> 4][i & 15]));
      const float cc[2] = {ldsf(sb + OFF_RSQ + (64 * hh + 16 * wp + g) * 4) * LOG2E, ldsf(sb + OFF_RSQ + (64 * hh + 16 * wp + g + 8) * 4) * LOG2E};
      float m[2][4] = {{0.f, 0.f, 0.f, 0.f}, {0.f, 0.f, 0.f, 0.f}};
      uint32_t ph[2][8];
      auto exps = [&](int h) {
        #pragma unroll
        for (int k = 0; k < 8; k++) {
          const float c = cc[k & 1], mp = m[h][k & 1], mm = m[h][2 + (k & 1)];
          ph[0][k] = pack_bf16(ex2(fmaf(p[h][2*k], c, mp)), ex2(fmaf(p[h][2*k+1], c, mp)));
          ph[1][k] = pack_bf16(ex2(fmaf(p[h][2*k], -c, mm)), ex2(fmaf(p[h][2*k+1], -c, mm)));
        }
      };
      uint32_t shifted = 0;
      asm volatile("" : "+r"(shifted));
      #pragma unroll 1
      for (;;) {
        if (shifted) { row_extremes(p[0], cc, m[0]); row_extremes(p[1], cc, m[1]); }
        uint32_t first = shifted ^ 1;
        asm volatile("" : "+r"(first));
        if (first) {
          bar_sync(NB_Q0 + wg, isq ? 128 : 256);
          const uint32_t da = dlo(SB0, 16) + (ao >> 4), db = dlo(SB0 + OFF_WPHIQ, 16) + half * 256;
          wg_fence();
          #pragma unroll
          for (int h = 0; h < 2; h++) {
            wgmma_ss_n32<0, 1, H128, H64>(p[h], da + 4 * h, db + 128 * h, 0);
            wgmma_sa_n32<0, 1, H128, H64>(p[h], da + 4 * h + 2, db + 128 * h + 64);
          }
          wg_commit();
          if (wg == 1) bar_sync(NB_TOK, 256);
          wg_wait<0>();
        }
        TK(64 + 4 * turn);
        fence_regs(p[0]); fence_regs(p[1]);
        exps(0);
        float s2[4] = {0.f, 0.f, 0.f, 0.f};
        #pragma unroll
        for (int i = 0; i < 32; i++) s2[((i >> 1) & 1) + 2 * (i >> 4)] = fmaf(p[i >> 4][i & 15], p[i >> 4][i & 15], s2[((i >> 1) & 1) + 2 * (i >> 4)]);
        const float l0 = cc[0] * cc[0], l1 = cc[1] * cc[1];
        if (!__any_sync(~0u, !shifted & !((s2[0] * l0 < ARG_LIM2) & (s2[1] * l1 < ARG_LIM2) & (s2[2] * l0 < ARG_LIM2) & (s2[3] * l1 < ARG_LIM2)))) break;
        shifted = 1;
      }
      const uint32_t db = dlo(SB0 + OFF_KVZ, 128) + half * 640;
      float ac[4][20];
      auto numer = [&](int h, const uint32_t (&f)[2][8]) {
        wg_fence();
        #pragma unroll
        for (int i = 0; i < 2; i++) {
          wgmma_rz_n40<1, dhi(256, 0)>(ac[2*h+i], f[i][0], f[i][1], f[i][2], f[i][3], db + (2*h+i) * 160);
          wgmma_ra_n40<1, dhi(256, 0)>(ac[2*h+i], f[i][4], f[i][5], f[i][6], f[i][7], db + ((2*h+i) * 160 + 80));
        }
        wg_commit();
      };
      auto finish = [&](int h) {
        const float* ap = ac[2 * h]; const float* am = ac[2 * h + 1];
        const float ip0 = rcp(ap[17]), im0 = rcp(am[17]), ip1 = rcp(ap[19]), im1 = rcp(am[19]);
        const float d0 = rcp(fmaf(ap[16], ip0, fmaf(am[16], im0, 1e-6f))), d1 = rcp(fmaf(ap[18], ip1, fmaf(am[18], im1, 1e-6f)));
        const float a0 = ip0 * d0, b0 = im0 * d0, a1 = ip1 * d1, b1 = im1 * d1;
        #pragma unroll
        for (int k = 0; k < 2; k++)
          stsm4(at ^ ((2 * h + k) << 5),
                pack_bf16(fmaf(ap[8*k], a0, am[8*k] * b0),     fmaf(ap[8*k+1], a0, am[8*k+1] * b0)),
                pack_bf16(fmaf(ap[8*k+2], a1, am[8*k+2] * b1), fmaf(ap[8*k+3], a1, am[8*k+3] * b1)),
                pack_bf16(fmaf(ap[8*k+4], a0, am[8*k+4] * b0), fmaf(ap[8*k+5], a0, am[8*k+5] * b0)),
                pack_bf16(fmaf(ap[8*k+6], a1, am[8*k+6] * b1), fmaf(ap[8*k+7], a1, am[8*k+7] * b1)));
      };
      numer(0, ph);
      exps(1);
      if (wg == 0) bar_sync(NB_DN, 256);
      numer(1, ph);
      if (turn < 2) bar_arrive(NB_TOK + turn, 256);
      wg_wait<1>();
      TK(65 + 4 * turn);
      fence_regs(ac[0]); fence_regs(ac[1]);
      finish(0);
      wg_wait<0>();
      fence_regs(ac[2]); fence_regs(ac[3]);
      finish(1);
      TK(66 + 4 * turn);
      fence_async_smem();
      __syncwarp();
      if (lane == 0) mbar_arrive(sb + B_UO + 8 * e);
      TK(67 + 4 * turn);
    }
    if (isq) cluster_arrive();
  }

  {
  int lane;
  asm volatile("mov.u32 %0, %%laneid;" : "=r"(lane));
  const int g = lane >> 2, q = lane & 3;
  const uint32_t ep1 = __float_as_uint(ldsf(sb + OFF_EP));
  if (wg < 2) {
    const uint32_t tg = ep1 & 3;
    float h[64];
    {
      if (wg == 0) { TK(83); }
      #pragma unroll
      for (int i = 0; i < 32; i++) { h[2*i] = bf_lo(xr[i]); h[2*i+1] = bf_hi(xr[i]); }
      fence_regs(h);
      asm volatile("setmaxnreg.dec.sync.aligned.u32 128;" ::: "memory");
      TK(80 + wg);
      const uint64_t seq = rank ? 0x1043210432104312ull : 0x1043210432104321ull;
      const uint32_t emptyb = mapa(sb + B_EMPTY5, t & 1);
      uint32_t s = 1 + rank, ps = 0;
      mbar_wait2(sb + B_FULL5 + 8 * s, 1, sb + B_UO + 8 * wg, 0);
      if (wg == 0) { TSW(14); }
      #pragma unroll 1
      for (int i = 0; i < 16; i++) {
        if (wg == 1 && i < 4) { TK(84 + i); }
        if (wg == 0) { TK(32 + i); }
        const uint32_t da = dlo(SB0, 16) + s * 2048 + wg * 512, db = dlo(SB0 + 16384, 8192) + s * 2048;
        wg_fence();
        #pragma unroll
        for (int k = 0; k < 4; k++) wgmma_sa_n128<0, 1, H128, H128>(h, da + k * 2, db + k * 128);
        wg_commit();
        const uint32_t ns = (uint32_t)(seq >> (4 * i + 4)) & 15;
        wg_wait<1>();
        if (i > 0 && t < 2) mbar_arrive_remote(emptyb + 8 * ps, 1);
        if (i < 15) mbar_wait2(sb + B_FULL5 + 8 * ns, (0x1f07 >> i) & 1, sb + B_FULLA + 16 * ns + 8 * wg, (0x41f0 >> i) & 1);
        ps = s; s = ns;
      }
      wg_wait<0>();
      if (t < 2) mbar_arrive_remote(emptyb + 8 * ps, 1);
      fence_regs(h);
    }
    cluster_arrive();
    if (wg == 0) { TSW(16); }
    if (__builtin_expect(__any_sync(~0u, h[0] != h[0] || h[2] != h[2]), 0)) {
      const int r = 64 * wg + 16 * wp + g;
      #pragma unroll 1
      for (int n = 0; n < 16; n++) {
        const uint32_t* xp = reinterpret_cast<const uint32_t*>(P.x + (size_t)(128 * m128 + r) * DM + 128 * j + 8 * n) + q;
        const uint32_t x0 = xp[0], x1 = xp[4 * DM];
        float d0 = bf_lo(x0), d1 = bf_hi(x0), d2 = bf_lo(x1), d3 = bf_hi(x1);
        #pragma unroll 1
        for (int ks = 0; ks < 64; ks++) {
          const int kb = ks >> 2, kk = 16 * (ks & 3);
          const bf16* op = G->o + (m128 * 16 + kb) * 8192 + r * 64 + 2 * q;
          const int o0 = ((kk >> 3) ^ g) << 3;
          const uint16_t* w = reinterpret_cast<const uint16_t*>(P.wo_p) + (size_t)(128 * (kb >> 1) + 32 * (kb & 1) + (kk & 31) + 2 * (kk & 32) + 2 * q) * DM + 128 * j + 8 * n + g;
          const uint32_t b0 = w[0] | (w[DM] << 16), b1 = w[8 * DM] | (w[9 * DM] << 16);
          uint32_t a0, a1, a2, a3, it = 0;
          do { a0 = ld32_rlx(op + o0); a1 = ld32_rlx(op + 512 + o0); a2 = ld32_rlx(op + (o0 ^ 8)); a3 = ld32_rlx(op + 512 + (o0 ^ 8)); }
          while (max(max(a0, a1), max(a2, a3)) == ~0u && ++it < POLL_LIMIT);
          __syncwarp();
          mma16816(d0, d1, d2, d3, a0, a1, a2, a3, b0, b1);
        }
        #pragma unroll
        for (int i = 0; i < 60; i++) h[i] = h[i + 4];
        h[60] = d0; h[61] = d1; h[62] = d2; h[63] = d3;
      }
    }
    float sum0 = 0.f, sum1 = 0.f, dot0 = 0.f, dot1 = 0.f, sq0 = 0.f, sq1 = 0.f;
    #pragma unroll
    for (int i = 0; i < 16; i++) {
      const float2 w = reinterpret_cast<const float2*>(smem_raw + OFF_WR)[4 * i + q];
      sum0 += h[4*i] + h[4*i+1]; sum1 += h[4*i+2] + h[4*i+3];
      sq0 = fmaf(h[4*i], h[4*i], fmaf(h[4*i+1], h[4*i+1], sq0)); sq1 = fmaf(h[4*i+2], h[4*i+2], fmaf(h[4*i+3], h[4*i+3], sq1));
      dot0 = fmaf(h[4*i], w.x, fmaf(h[4*i+1], w.y, dot0)); dot1 = fmaf(h[4*i+2], w.x, fmaf(h[4*i+3], w.y, dot1));
    }
    const int r0 = 64 * wg + 16 * wp + g;
    {
      const bool up = q & 2;
      float a = up ? sum1 : sum0, b = up ? sq1 : sq0, d = up ? dot1 : dot0;
      a += __shfl_xor_sync(~0u, up ? sum0 : sum1, 2); b += __shfl_xor_sync(~0u, up ? sq0 : sq1, 2); d += __shfl_xor_sync(~0u, up ? dot0 : dot1, 2);
      a += __shfl_xor_sync(~0u, a, 1); b += __shfl_xor_sync(~0u, b, 1); d += __shfl_xor_sync(~0u, d, 1);
      if ((q & 1) == 0) st128_rlx(&G->part[(m128 * 8 + j) * 128 + r0 + 4 * q], tagw(a, tg), tagw(b, tg), tagw(d, tg), tg);
    }
    if (wg == 0) { TSW(24); }
    float mean, rstd, rr;
    {
      uint4 a0, a1, a2, a3; uint32_t it = 0;
      const uint4* pp = &G->part[(m128 * 8 + (q & 1)) * 128 + r0 + 4 * (q & 2)];
      do {
        a0 = ld128_rlx(pp); a1 = ld128_rlx(pp + 256); a2 = ld128_rlx(pp + 512); a3 = ld128_rlx(pp + 768);
      } while ((((a0.x ^ tg) | (a0.y ^ tg) | (a0.z ^ tg) | (a1.x ^ tg) | (a1.y ^ tg) | (a1.z ^ tg) |
                 (a2.x ^ tg) | (a2.y ^ tg) | (a2.z ^ tg) | (a3.x ^ tg) | (a3.y ^ tg) | (a3.z ^ tg)) & 3) && ++it < POLL_LIMIT);
      __syncwarp();
      float s = (untag(a0.x) + untag(a1.x)) + (untag(a2.x) + untag(a3.x));
      float s2 = (untag(a0.y) + untag(a1.y)) + (untag(a2.y) + untag(a3.y));
      float d = (untag(a0.z) + untag(a1.z)) + (untag(a2.z) + untag(a3.z));
      s += __shfl_xor_sync(~0u, s, 1); s2 += __shfl_xor_sync(~0u, s2, 1); d += __shfl_xor_sync(~0u, d, 1);
      mean = s * (1.f / DM);
      rstd = rsqrtf(fmaxf(s2 * (1.f / DM) - mean * mean, 0.f) + 1e-5f);
      const float2 swa = lds64f(sb + OFF_SUMWR), swb = lds64f(sb + OFF_SUMWR + 8);
      rr = (d - mean * ((swa.x + swa.y) + (swb.x + swb.y))) * rstd;
    }
    if (wg == 0) { TSW(17); }
    {
      const int rl = g + 4 * (q & 2);
      const uint32_t ob = __float_as_uint(rr) ^ ((uint32_t)((int32_t)__float_as_uint(rr) >> 31) | 0x80000000u);
      const uint32_t key = (ob & ~63u) | ((15 - rl) << 2) | tg;
      uint32_t best;
      asm volatile("redux.sync.max.u32 %0, %1, 0xffffffff;" : "=r"(best) : "r"(key));
      const int slot = m128 * 8 + (tid >> 5), win = 15 - ((best >> 2) & 15);
      if (lane < 4) st32_rlx(&G->key[(4 * j + lane) * 128 + slot], best);
      if ((win & 7) == g) {
        const bool up = win & 8;
        uint32_t* dst = &G->cand[slot * (DM + 32) + 128 * j + 2 * q];
        if (j == 0 && rl == win) st64_rlx(&G->cand[slot * (DM + 32) + DM], tagw(mean, tg), tagw(rstd, tg));
        #pragma unroll
        for (int i = 0; i < 16; i++) st64_rlx(dst + 8 * i, tagw(up ? h[4*i+2] : h[4*i], tg), tagw(up ? h[4*i+3] : h[4*i+1], tg));
      }
      __syncwarp();
    }
    if (wg == 0) { TSW(27); }
    if (wg == 0) bar_arrive(NB_G2E, 256);
    if (tid == 0) mbar_arrive(sb + B_F + 48);
    {
      bar_sync(NB_WG01, 256);
      const float am = 1.f + rstd, bm = -mean * rstd;
      const float a0 = __shfl_sync(~0u, am, lane & ~3), b0 = __shfl_sync(~0u, bm, lane & ~3), a1 = __shfl_sync(~0u, am, lane | 3), b1 = __shfl_sync(~0u, bm, lane | 3);
      #pragma unroll
      for (int k = 0; k < 8; k++)
        stsm4(((sb + R5 + wg * 8192 + sa) ^ ((k & 3) << 5)) + (k >> 2) * 16384,
              pack_bf16(fmaf(h[8*k], a0, b0), fmaf(h[8*k+1], a0, b0)),     pack_bf16(fmaf(h[8*k+2], a1, b1), fmaf(h[8*k+3], a1, b1)),
              pack_bf16(fmaf(h[8*k+4], a0, b0), fmaf(h[8*k+5], a0, b0)),   pack_bf16(fmaf(h[8*k+6], a1, b1), fmaf(h[8*k+7], a1, b1)));
      fence_async_smem();
      bar_arrive(NB_OUT, 288);
    }
    if (wg == 0) { TSW(28); }
    if (c < NFFN_L) { mbar_wait(sb + (wg ? B_F : B_X), 0); if (wg) mbar_wait(sb + B_F + 8, 0); }
    bar_sync(NB_XS, 416);
    if (wg == 0) { TSW(19); }
    if (c < NFFN) {
      float ga[4], gb[4];
      uint32_t da = dlo(SB0 + OFF_X, 16384) + wg * 2048, db = dlo(SB0 + OFF_XSEL, 16) + wg * 32;
      #pragma unroll 1
      for (int k = 0; k < 8; k++) {
        if (k == 4) { if (c < NFFN_L) { mbar_wait(sb + B_F + 16 + 16 * wg, 0); mbar_wait(sb + B_F + 24 + 16 * wg, 0); } da = dlo(SB0 + 2 * R5, 16384) + wg * 2048; db += 32; }
        wg_fence();
        wgmma_ss_n8<1, 0, H64, H0>(ga, da, db, k); wgmma_ss_n8<1, 0, H64, H0>(gb, da + 64, db + 2, k);
        wgmma_ss_n8<1, 0, H64, H0>(ga, da + 128, db + 4, 1); wgmma_ss_n8<1, 0, H64, H0>(gb, da + 192, db + 6, 1);
        wg_commit();
        da += 256; db += 8;
      }
      wg_wait<0>();
      fence_regs(ga); fence_regs(gb);
      if (q == 0) { stsf(sb + OFF_SCR + 128 + r0 * 4, ga[0] + gb[0]); stsf(sb + OFF_SCR + 128 + r0 * 4 + 32, ga[2] + gb[2]); }
      bar_arrive(NB_ACT, 384);
    }
    {
      float y0 = 0.f, y1 = 0.f, y2 = 0.f, y3 = 0.f;
      const float2 ky = lds64f(sb + OFF_KEY);
      const int kidx = __float_as_int(ky.x);
      const float kr = ky.y;
      uint32_t it = 0;
      if (tid < 2 * NFFN) {
        uint4 v;
        do { v = ld128_rlx(&G->ypart[(tid >> 1) * DM + 8 * c + 4 * (tid & 1)]); } while (tag_bad(v, tg) && ++it < POLL_LIMIT);
        y0 = untag(v.x); y1 = untag(v.y); y2 = untag(v.z); y3 = untag(v.w);
      }
      __syncwarp();
      const bool b4 = lane & 16, b3 = lane & 8;
      const float u0 = (b4 ? y1 : y0) + __shfl_xor_sync(~0u, b4 ? y0 : y1, 16), u1 = (b4 ? y3 : y2) + __shfl_xor_sync(~0u, b4 ? y2 : y3, 16);
      float ys = (b3 ? u1 : u0) + __shfl_xor_sync(~0u, b3 ? u0 : u1, 8);
      ys += __shfl_xor_sync(~0u, ys, 4); ys += __shfl_xor_sync(~0u, ys, 2);
      if (!(lane & 6)) stsf(sb + OFF_ACT + (warp * 8 + 4 * (lane & 1) + ((lane >> 3) & 1) * 2 + (lane >> 4)) * 4, ys);
      const float sg = __fdividef(1.f, 1.f + __expf(-kr));
      bar_sync(NB_WG01, 256);
      if (tid < 8) {
        float t8 = 0.f;
        #pragma unroll
        for (int w = 0; w < 7; w++) t8 += ldsf(sb + OFF_ACT + w * 32 + tid * 4);
        P.out_p[(size_t)kidx * DM + 8 * c + tid] = __float2bfloat16(fmaf(t8, sg, ldsf(sb + OFF_H8 + tid * 4)));
      }
      if (c == 0 && tid == 0) st32_rlx(&G->epoch, ep1);
      if (wg == 0) { TSW(22); }
    }
  }
  if (wg == 2) {
    const uint32_t tg = ep1 & 3;
    uint32_t wf[4][2][2][8];
    {
      const bf16* wp0 = P.wd_p + (size_t)(32 * c + 2 * q) * DM + 256 * wp + 8 * g;
      uint4 u[4][8];
      asm volatile("setmaxnreg.inc.sync.aligned.u32 224;");
      __nanosleep(WD_DELAY);
      #pragma unroll
      for (int r = 0; r < 8; r++) {
        __nanosleep(WD_STEP);
        #pragma unroll
        for (int s4 = 0; s4 < 4; s4++) u[s4][r] = c < NFFN_L ? ld128_weak(wp0 + ((r >> 1) * 8 + (r & 1)) * DM + 64 * s4) : make_uint4(0, 0, 0, 0);
      }
      #pragma unroll
      for (int s4 = 0; s4 < 4; s4++)
        #pragma unroll
        for (int r2 = 0; r2 < 4; r2++) {
          const uint32_t a[4] = {u[s4][2*r2].x, u[s4][2*r2].y, u[s4][2*r2].z, u[s4][2*r2].w}, b[4] = {u[s4][2*r2+1].x, u[s4][2*r2+1].y, u[s4][2*r2+1].z, u[s4][2*r2+1].w};
          #pragma unroll
          for (int e = 0; e < 4; e++) { wf[s4][r2 >> 1][r2 & 1][2*e] = __byte_perm(a[e], b[e], 0x5410); wf[s4][r2 >> 1][r2 & 1][2*e+1] = __byte_perm(a[e], b[e], 0x7632); }
        }
    }
    uint32_t* const dst = &G->ypart[c * DM + 256 * wp + 64 * (q >> 1) + 8 * g + 4 * (q & 1)];
    #pragma unroll 1
    for (int pass = 0; pass < 2; pass++) {
    if (pass) {
      bar_sync(NB_G2E, 256);
      TDUMP();
      int cur = -1, have = -1;
      uint32_t kw = 0, xs[4];
      float base[4];
      for (uint32_t it = 0; it < POLL_LIMIT; it++) {
        uint4 kx = ld128_rlx(&G->key[(c & 31) * 128 + 4 * lane]);
        if (cur != have) {
          const uint32_t* cp = &G->cand[cur * (DM + 32)];
          const uint4 v0 = ld128_rlx(cp + 256 * wp + 4 * lane), v1 = ld128_rlx(cp + 256 * wp + 128 + 4 * lane);
          const uint2 ms = ld64_rlx(cp + DM);
          if (!__any_sync(~0u, tag_bad(v0, tg) || tag_bad(v1, tg) || (((ms.x ^ tg) | (ms.y ^ tg)) & 3))) {
            have = cur;
            const float rs = untag(ms.y), bm = -untag(ms.x) * rs;
            xs[0] = pack_bf16(fmaf(untag(v0.x), rs, bm), fmaf(untag(v0.y), rs, bm)); xs[1] = pack_bf16(fmaf(untag(v0.z), rs, bm), fmaf(untag(v0.w), rs, bm));
            xs[2] = pack_bf16(fmaf(untag(v1.x), rs, bm), fmaf(untag(v1.y), rs, bm)); xs[3] = pack_bf16(fmaf(untag(v1.z), rs, bm), fmaf(untag(v1.w), rs, bm));
            const uint4 vb = (c & 16) ? v1 : v0;
            base[0] = fmaf(untag(vb.x), 1.f + rs, bm); base[1] = fmaf(untag(vb.y), 1.f + rs, bm); base[2] = fmaf(untag(vb.z), 1.f + rs, bm); base[3] = fmaf(untag(vb.w), 1.f + rs, bm);
          }
        }
        const bool all = !__any_sync(~0u, tag_bad(kx, tg));
        if ((kx.x ^ tg) & 3) kx.x = 0;
        if ((kx.y ^ tg) & 3) kx.y = 0;
        if ((kx.z ^ tg) & 3) kx.z = 0;
        if ((kx.w ^ tg) & 3) kx.w = 0;
        const uint32_t km = max(max(kx.x, kx.y), max(kx.z, kx.w)) >> 6;
        uint32_t best;
        asm volatile("redux.sync.max.u32 %0, %1, 0xffffffff;" : "=r"(best) : "r"(km));
        if (TRK_SLEEP && !all) __nanosleep(TRK_SLEEP);
        if (best == 0 && !all) continue;
        const int src = __ffs(__ballot_sync(~0u, km == best)) - 1;
        const int e = (kx.x >> 6) == best ? 0 : (kx.y >> 6) == best ? 1 : (kx.z >> 6) == best ? 2 : 3;
        kw = __shfl_sync(~0u, e == 0 ? kx.x : e == 1 ? kx.y : e == 2 ? kx.z : kx.w, src);
        cur = 4 * src + __shfl_sync(~0u, e, src);
        if (all && cur == have) break;
      }
      sts64(sb + OFF_XSEL + 512 * wp + 8 * lane, xs[0], xs[1]); sts64(sb + OFF_XSEL + 512 * wp + 256 + 8 * lane, xs[2], xs[3]);
      if (wp == (c >> 5) && (lane >> 1) == (c & 15)) {
        sts128(sb + OFF_H8 + (lane & 1) * 16, __float_as_uint(base[0]), __float_as_uint(base[1]), __float_as_uint(base[2]), __float_as_uint(base[3]));
        sts64(sb + OFF_KEY, 16 * cur + 15 - ((kw >> 2) & 15), (kw & ~63u) ^ ((kw >> 31) ? 0x80000000u : 0xffffffc0u));
      }
      fence_async_smem();
      bar_arrive(NB_XS, 416);
      TSW(18);
      if (c >= NFFN) break;
      bar_sync(NB_ACT, 384);
    }
    const uint32_t a = sb + OFF_SCR + 128 + lane * 4;
    const float gv = ldsf(a) + ldsf(a + 256), uv = ldsf(a + 128) + ldsf(a + 384);
    const float act = __fdividef(gv, 1.f + __expf(-gv)) * uv;
    const uint32_t ap = pack_bf16(act, __shfl_down_sync(~0u, act, 1));
    uint32_t bf[4];
    #pragma unroll
    for (int i = 0; i < 4; i++) bf[i] = __shfl_sync(~0u, ap, 2 * q + 8 * i);
    if (pass) { TSW(20); }
    float d[16][4];
    #pragma unroll
    for (int k = 0; k < 2; k++)
      #pragma unroll
      for (int i = 0; i < 16; i++) {
        if (k == 0) { d[i][0] = 0.f; d[i][1] = 0.f; d[i][2] = 0.f; d[i][3] = 0.f; }
        const uint32_t* w0 = &wf[i >> 2][k][0][2 * (i & 3)]; const uint32_t* w1 = &wf[i >> 2][k][1][2 * (i & 3)];
        asm volatile("mma.sync.aligned.m16n8k16.row.col.f32.bf16.bf16.f32 {%0,%1,%2,%3}, {%4,%5,%6,%7}, {%8,%9}, {%0,%1,%2,%3};"
                     : "+f"(d[i][0]), "+f"(d[i][1]), "+f"(d[i][2]), "+f"(d[i][3])
                     : "r"(w0[0]), "r"(w0[1]), "r"(w1[0]), "r"(w1[1]), "r"(bf[2*k]), "r"(bf[2*k+1]));
      }
    float y[8];
    #pragma unroll
    for (int i = 0; i < 8; i++) {
      const int e = (i & 1) * 2, n = 8 * (i >> 2) + ((i >> 1) & 1);
      const float lo = (q & 1) ? d[n + 2][e] : d[n][e], hi = (q & 1) ? d[n + 6][e] : d[n + 4][e];
      y[i] = (q & 2) ? hi : lo;
    }
    asm volatile("{\n.reg .pred p;\nsetp.ne.s32 p, %9, 0;\n@p st.relaxed.gpu.global.v4.u32 [%0], {%1,%2,%3,%4};\n@p st.relaxed.gpu.global.v4.u32 [%0+512], {%5,%6,%7,%8};\n}\n"
                 :: "l"(dst), "r"(tagw(y[0], tg)), "r"(tagw(y[1], tg)), "r"(tagw(y[2], tg)), "r"(tagw(y[3], tg)),
                    "r"(tagw(y[4], tg)), "r"(tagw(y[5], tg)), "r"(tagw(y[6], tg)), "r"(tagw(y[7], tg)), "r"(pass) : "memory");
    if (pass) { TSW(21); }
    }
  }
  }
  cluster_wait();
}

typedef CUresult (*EncodeFn)(CUtensorMap*, CUtensorMapDataType, cuuint32_t, void*, const cuuint64_t*, const cuuint64_t*,
                             const cuuint32_t*, const cuuint32_t*, CUtensorMapInterleave, CUtensorMapSwizzle,
                             CUtensorMapL2promotion, CUtensorMapFloatOOBfill);

void make_map(EncodeFn enc, CUtensorMap* m, const void* p, int n, const cuuint64_t* dims, const cuuint64_t* str, const cuuint32_t* box,
              CUtensorMapSwizzle sw, CUtensorMapL2promotion promo) {
  cuuint32_t es[5] = {1, 1, 1, 1, 1};
  enc(m, CU_TENSOR_MAP_DATA_TYPE_BFLOAT16, n, const_cast<void*>(p), dims, str, box, es, CU_TENSOR_MAP_INTERLEAVE_NONE, sw, promo,
      CU_TENSOR_MAP_FLOAT_OOB_FILL_NONE);
}
void map2(EncodeFn enc, CUtensorMap* m, const void* p, uint64_t cols, uint64_t rows, uint32_t bc, uint32_t br, CUtensorMapSwizzle sw,
          CUtensorMapL2promotion promo) {
  const cuuint64_t dims[2] = {cols, rows}, str[1] = {cols * 2};
  const cuuint32_t box[2] = {bc, br};
  make_map(enc, m, p, 2, dims, str, box, sw, promo);
}
void map3(EncodeFn enc, CUtensorMap* m, const void* p, uint64_t cols, uint64_t rows, uint32_t br, uint32_t nb) {
  const cuuint64_t dims[3] = {64, rows, cols / 64}, str[2] = {cols * 2, 128};
  const cuuint32_t box[3] = {64, br, nb};
  make_map(enc, m, p, 3, dims, str, box, CU_TENSOR_MAP_SWIZZLE_128B, CU_TENSOR_MAP_L2_PROMOTION_L2_128B);
}

}

extern "C" void kernel_launch(void* const* d_in, const int* in_sizes, int n_in, void* d_out, int out_size) {
  (void)in_sizes; (void)n_in; (void)out_size;
  static EncodeFn enc = nullptr;
  static void* o_ptr = nullptr;
  if (!enc) {
    void* f = nullptr; cudaDriverEntryPointQueryResult qr;
    cudaGetDriverEntryPoint("cuTensorMapEncodeTiled", &f, cudaEnableDefault, &qr);
    enc = (EncodeFn)f;
    cudaGetSymbolAddress(&o_ptr, g_scr);
    cudaFuncSetAttribute(fused_kernel, cudaFuncAttributeMaxDynamicSharedMemorySize, SMEM_BYTES);
  }
  const bf16* x = (const bf16*)d_in[0];
  const bf16* wqkv = (const bf16*)d_in[1];
  const bf16* wphi = (const bf16*)d_in[2];
  const bf16* wo = (const bf16*)d_in[3];
  const bf16* wr = (const bf16*)d_in[5];
  const bf16* wgate = (const bf16*)d_in[6];
  const bf16* wup = (const bf16*)d_in[7];
  const bf16* wdown = (const bf16*)d_in[8];
  Params P;
  const CUtensorMapSwizzle S128 = CU_TENSOR_MAP_SWIZZLE_128B, S64 = CU_TENSOR_MAP_SWIZZLE_64B;
  const CUtensorMapL2promotion L128 = CU_TENSOR_MAP_L2_PROMOTION_L2_128B, L256 = CU_TENSOR_MAP_L2_PROMOTION_L2_256B,
                               L64 = CU_TENSOR_MAP_L2_PROMOTION_L2_64B;
  map2(enc, &P.x128, x, DM, SEQ, 64, 128, S128, L256);
  map2(enc, &P.x64, x, DM, SEQ, 64, 64, S128, L128);
  {
    const cuuint64_t dims[4] = {64, DM, 16, 3}, str[3] = {6 * DM, 128, 2 * DM};
    const cuuint32_t box[4] = {64, 64, 1, 2};
    make_map(enc, &P.wkv, wqkv, 4, dims, str, box, S128, L128);
  }
  map3(enc, &P.wq, wqkv, 3 * DM, DM, 64, 2);
  {
    const cuuint64_t dims[4] = {64, DM - 64, 2, 16}, str[3] = {2 * DM, 128 * DM, 128};
    const cuuint32_t box[4] = {64, 32, 2, 2};
    make_map(enc, &P.wo, wo, 4, dims, str, box, S128, L128);
  }
  map3(enc, &P.out, d_out, DM, SEQ, 128, 2);
  map2(enc, &P.out16, d_out, DM, SEQ, 64, 16, S128, L128);
  map2(enc, &P.wg, wgate, FF, DM, 32, 256, S64, L64);
  map2(enc, &P.wu, wup, FF, DM, 32, 256, S64, L64);
  map2(enc, &P.phi, wphi, 32, 1024, 32, 32, S64, L64);
  P.x = x; P.wqkv = wqkv; P.wo_p = wo; P.wd_p = wdown; P.wg_p = wgate; P.wu_p = wup; P.wr = wr; P.out_p = (bf16*)d_out; P.g = (Scratch*)o_ptr;

  cudaLaunchConfig_t cfg = {};
  cfg.gridDim = dim3(128); cfg.blockDim = dim3(512); cfg.dynamicSmemBytes = SMEM_BYTES; cfg.stream = cudaStreamPerThread;
  cudaLaunchAttribute at[1];
  at[0].id = cudaLaunchAttributeClusterDimension; at[0].val.clusterDim.x = 2; at[0].val.clusterDim.y = 1; at[0].val.clusterDim.z = 1;
  cfg.attrs = at; cfg.numAttrs = 1;
  cudaLaunchKernelEx(&cfg, fused_kernel, P);
}
```

```cpp
#include <cuda_runtime.h>
#include <cuda.h>
#include <cuda_bf16.h>
#include <stdint.h>

namespace {

typedef __nv_bfloat16 bf16;

__device__ __forceinline__ uint32_t smem_u32(const void* p){ return (uint32_t)__cvta_generic_to_shared(p); }
__device__ __forceinline__ void mbar_init(uint32_t bar, uint32_t cnt){ asm volatile("mbarrier.init.shared::cta.b64 [%0], %1;"::"r"(bar),"r"(cnt):"memory"); }
__device__ __forceinline__ void mbar_expect_tx(uint32_t bar, uint32_t bytes){ asm volatile("mbarrier.arrive.expect_tx.shared::cta.b64 _, [%0], %1;"::"r"(bar),"r"(bytes):"memory"); }
__device__ __forceinline__ void mbar_arrive(uint32_t bar){ asm volatile("mbarrier.arrive.shared::cta.b64 _, [%0];"::"r"(bar):"memory"); }
__device__ __forceinline__ uint32_t mapa(uint32_t addr, uint32_t cta){ uint32_t r; asm volatile("mapa.shared::cluster.u32 %0, %1, %2;":"=r"(r):"r"(addr),"r"(cta)); return r; }
__device__ __forceinline__ void mbar_arrive_at(uint32_t bar, uint32_t cta, uint32_t cnt){
  asm volatile("{\n.reg .b32 ra;\nmapa.shared::cluster.u32 ra, %0, %1;\nmbarrier.arrive.shared::cluster.b64 _, [ra], %2;\n}\n"::"r"(bar),"r"(cta),"r"(cnt):"memory"); }
__device__ __forceinline__ void mbar_arrive_remote(uint32_t cluster_addr, uint32_t cnt){
  asm volatile("mbarrier.arrive.shared::cluster.b64 _, [%0], %1;"::"r"(cluster_addr),"r"(cnt):"memory"); }
__device__ __forceinline__ void mbar_wait(uint32_t bar, uint32_t parity){
  asm volatile("{\n.reg .pred p;\n.reg .u32 c;\nmov.u32 c, 0;\nLW:\nmbarrier.try_wait.parity.shared::cta.b64 p, [%0], %1;\n@p bra LD;\nadd.u32 c, c, 1;\nsetp.lt.u32 p, c, 2000000;\n@p bra LW;\ntrap;\nLD:\n}\n"::"r"(bar),"r"(parity):"memory"); }
__device__ __forceinline__ void mbar_wait2(uint32_t bar0, uint32_t par0, uint32_t bar1, uint32_t par1){
  asm volatile("{\n.reg .pred p, q;\n.reg .u32 c;\nmov.u32 c, 0;\nLW:\nmbarrier.try_wait.parity.shared::cta.b64 p, [%0], %1;\nmbarrier.try_wait.parity.shared::cta.b64 q, [%2], %3;\nand.pred p, p, q;\n@p bra LD;\nadd.u32 c, c, 1;\nsetp.lt.u32 p, c, 2000000;\n@p bra LW;\ntrap;\nLD:\n}\n"::"r"(bar0),"r"(par0),"r"(bar1),"r"(par1):"memory"); }
__device__ __forceinline__ void tma_2d(uint32_t dst, const CUtensorMap* m, int c0, int c1, uint32_t bar){
  asm volatile("cp.async.bulk.tensor.2d.shared::cluster.global.mbarrier::complete_tx::bytes [%0], [%1, {%3, %4}], [%2];"::"r"(dst),"l"(m),"r"(bar),"r"(c0),"r"(c1):"memory"); }
__device__ __forceinline__ void tma_2d_mc(uint32_t dst, const CUtensorMap* m, int c0, int c1, uint32_t bar){
  asm volatile("cp.async.bulk.tensor.2d.shared::cluster.global.mbarrier::complete_tx::bytes.multicast::cluster [%0], [%1, {%3, %4}], [%2], %5;"::"r"(dst),"l"(m),"r"(bar),"r"(c0),"r"(c1),"h"((uint16_t)3):"memory"); }
__device__ __forceinline__ void tma_2d_mc_h(uint32_t dst, const CUtensorMap* m, int c0, int c1, uint32_t bar, uint64_t pol){
  asm volatile("cp.async.bulk.tensor.2d.shared::cluster.global.mbarrier::complete_tx::bytes.multicast::cluster.L2::cache_hint [%0], [%1, {%3, %4}], [%2], %5, %6;"::"r"(dst),"l"(m),"r"(bar),"r"(c0),"r"(c1),"h"((uint16_t)3),"l"(pol):"memory"); }
__device__ __forceinline__ void tma_4d(uint32_t dst, const CUtensorMap* m, int c0, int c1, int c2, int c3, uint32_t bar){
  asm volatile("cp.async.bulk.tensor.4d.shared::cluster.global.mbarrier::complete_tx::bytes [%0], [%1, {%3, %4, %5, %6}], [%2];"::"r"(dst),"l"(m),"r"(bar),"r"(c0),"r"(c1),"r"(c2),"r"(c3):"memory"); }
__device__ __forceinline__ uint64_t policy_evict_first(){ uint64_t p; asm volatile("createpolicy.fractional.L2::evict_first.b64 %0, 1.0;":"=l"(p)); return p; }
__device__ __forceinline__ void tma_3d_h(uint32_t dst, const CUtensorMap* m, int c0, int c1, int c2, uint32_t bar, uint64_t pol){
  asm volatile("cp.async.bulk.tensor.3d.shared::cluster.global.mbarrier::complete_tx::bytes.L2::cache_hint [%0], [%1, {%3, %4, %5}], [%2], %6;"::"r"(dst),"l"(m),"r"(bar),"r"(c0),"r"(c1),"r"(c2),"l"(pol):"memory"); }
__device__ __forceinline__ void tma_4d_h(uint32_t dst, const CUtensorMap* m, int c0, int c1, int c2, int c3, uint32_t bar, uint64_t pol){
  asm volatile("cp.async.bulk.tensor.4d.shared::cluster.global.mbarrier::complete_tx::bytes.L2::cache_hint [%0], [%1, {%3, %4, %5, %6}], [%2], %7;"::"r"(dst),"l"(m),"r"(bar),"r"(c0),"r"(c1),"r"(c2),"r"(c3),"l"(pol):"memory"); }
__device__ __forceinline__ void red_add_f32x4(float4* p, float x, float y, float z, float w){ asm volatile("red.relaxed.gpu.global.add.v4.f32 [%0], {%1,%2,%3,%4};"::"l"(p),"f"(x),"f"(y),"f"(z),"f"(w):"memory"); }
__device__ __forceinline__ bool elect_one(){ uint32_t p; asm volatile("{\n.reg .pred P;\nelect.sync _|P, 0xffffffff;\nselp.b32 %0, 1, 0, P;\n}\n":"=r"(p)); return p; }
__device__ __forceinline__ void bulk_prefetch(const void* p, uint32_t bytes){
  asm volatile("cp.async.bulk.prefetch.L2.global [%0], %1;"::"l"(p),"r"(bytes):"memory"); }
__device__ __forceinline__ void bulk_s2peer(uint32_t dst_cluster, uint32_t src, uint32_t bytes, uint32_t bar_cluster){
  asm volatile("cp.async.bulk.shared::cluster.shared::cta.mbarrier::complete_tx::bytes [%0], [%1], %2, [%3];"::"r"(dst_cluster),"r"(src),"r"(bytes),"r"(bar_cluster):"memory"); }
__device__ __forceinline__ void bulk_g2s_mc(uint32_t dst, const void* src, uint32_t bytes, uint32_t bar, uint64_t pol){
  asm volatile("cp.async.bulk.shared::cluster.global.mbarrier::complete_tx::bytes.multicast::cluster.L2::cache_hint [%0], [%1], %2, [%3], %4, %5;"::"r"(dst),"l"(src),"r"(bytes),"r"(bar),"h"((uint16_t)3),"l"(pol):"memory"); }
__device__ __forceinline__ void bulk_s2g(void* dst, uint32_t src, uint32_t bytes){
  asm volatile("cp.async.bulk.global.shared::cta.bulk_group [%0], [%1], %2;"::"l"(dst),"r"(src),"r"(bytes):"memory"); }
__device__ __forceinline__ void bulk_commit(){ asm volatile("cp.async.bulk.commit_group;":::"memory"); }
__device__ __forceinline__ void bulk_wait_read(){ asm volatile("cp.async.bulk.wait_group.read 0;":::"memory"); }
__device__ __forceinline__ void prefetch_map(const CUtensorMap* m){ asm volatile("prefetch.tensormap [%0];"::"l"(m):"memory"); }
__device__ __forceinline__ void fence_async_smem(){ asm volatile("fence.proxy.async.shared::cta;":::"memory"); }
__device__ __forceinline__ void fence_acquire_gpu(){ asm volatile("fence.acquire.gpu;":::"memory"); }
__device__ __forceinline__ void fence_gpu(){ asm volatile("fence.acq_rel.gpu;":::"memory"); }
__device__ __forceinline__ void wg_fence(){ asm volatile("wgmma.fence.sync.aligned;":::"memory"); }
__device__ __forceinline__ void wg_commit(){ asm volatile("wgmma.commit_group.sync.aligned;":::"memory"); }
template<int N> __device__ __forceinline__ void wg_wait(){ asm volatile("wgmma.wait_group.sync.aligned %0;"::"n"(N):"memory"); }
template<int N> __device__ __forceinline__ void fence_regs(float (&d)[N]){
  #pragma unroll
  for(int i=0;i<N;i++) asm volatile("":"+f"(d[i])::"memory"); }
__device__ __forceinline__ void bar_sync(int id, int n){ asm volatile("bar.sync %0, %1;"::"r"(id),"r"(n):"memory"); }
__device__ __forceinline__ void bar_arrive(int id, int n){ asm volatile("bar.arrive %0, %1;"::"r"(id),"r"(n):"memory"); }
__device__ __forceinline__ void cluster_arrive(){ asm volatile("barrier.cluster.arrive.relaxed.aligned;":::"memory"); }
__device__ __forceinline__ void cluster_wait(){ asm volatile("barrier.cluster.wait.aligned;":::"memory"); }
__host__ __device__ constexpr uint32_t dlo(uint32_t addr, uint32_t lbo){ return (addr >> 4) | ((lbo >> 4) << 16); }
__host__ __device__ constexpr uint32_t dhi(uint32_t sbo, uint32_t sw){ return (sbo >> 4) | (sw << 30); }
constexpr uint32_t H128 = dhi(1024, 1), H64 = dhi(512, 2), H0 = dhi(128, 0);
__device__ __forceinline__ uint32_t pack_bf16(float lo, float hi){ uint32_t r; asm("cvt.rn.bf16x2.f32 %0, %1, %2;":"=r"(r):"f"(hi),"f"(lo)); return r; }
__device__ __forceinline__ float bf_lo(uint32_t v){ return __uint_as_float(v<<16); }
__device__ __forceinline__ float bf_hi(uint32_t v){ return __uint_as_float(v&0xffff0000u); }
__device__ __forceinline__ float ex2(float x){ float r; asm("ex2.approx.ftz.f32 %0, %1;":"=f"(r):"f"(x)); return r; }
__device__ __forceinline__ float rcp(float x){ float r; asm("rcp.approx.ftz.f32 %0, %1;":"=f"(r):"f"(x)); return r; }
__device__ __forceinline__ void stsm4(uint32_t addr, uint32_t a, uint32_t b, uint32_t c, uint32_t d){
  asm volatile("stmatrix.sync.aligned.m8n8.x4.shared.b16 [%0], {%1,%2,%3,%4};"::"r"(addr),"r"(a),"r"(b),"r"(c),"r"(d)); }
__device__ __forceinline__ void stsm2(uint32_t addr, uint32_t a, uint32_t b){
  asm volatile("stmatrix.sync.aligned.m8n8.x2.shared.b16 [%0], {%1,%2};"::"r"(addr),"r"(a),"r"(b)); }
__device__ __forceinline__ void mma16816(float& d0, float& d1, float& d2, float& d3, uint32_t a0, uint32_t a1, uint32_t a2, uint32_t a3, uint32_t b0, uint32_t b1){
  asm volatile("mma.sync.aligned.m16n8k16.row.col.f32.bf16.bf16.f32 {%0,%1,%2,%3}, {%4,%5,%6,%7}, {%8,%9}, {%0,%1,%2,%3};"
               : "+f"(d0), "+f"(d1), "+f"(d2), "+f"(d3) : "r"(a0), "r"(a1), "r"(a2), "r"(a3), "r"(b0), "r"(b1)); }
__device__ __forceinline__ void ldsm4(uint32_t addr, uint32_t& a, uint32_t& b, uint32_t& c, uint32_t& d){
  asm volatile("ldmatrix.sync.aligned.m8n8.x4.shared.b16 {%0,%1,%2,%3}, [%4];":"=r"(a),"=r"(b),"=r"(c),"=r"(d):"r"(addr):"memory"); }
__device__ __forceinline__ void ldsm4t(uint32_t addr, uint32_t& a, uint32_t& b, uint32_t& c, uint32_t& d){
  asm volatile("ldmatrix.sync.aligned.m8n8.x4.trans.shared.b16 {%0,%1,%2,%3}, [%4];":"=r"(a),"=r"(b),"=r"(c),"=r"(d):"r"(addr):"memory"); }
__device__ __forceinline__ void sts32(uint32_t a, uint32_t v){ asm volatile("st.shared.b32 [%0], %1;"::"r"(a),"r"(v):"memory"); }
__device__ __forceinline__ void stsf(uint32_t a, float v){ asm volatile("st.shared.f32 [%0], %1;"::"r"(a),"f"(v):"memory"); }
__device__ __forceinline__ void sts64(uint32_t a, uint32_t x, uint32_t y){ asm volatile("st.shared.v2.b32 [%0], {%1,%2};"::"r"(a),"r"(x),"r"(y):"memory"); }
__device__ __forceinline__ void sts128(uint32_t a, uint32_t x, uint32_t y, uint32_t z, uint32_t w){ asm volatile("st.shared.v4.b32 [%0], {%1,%2,%3,%4};"::"r"(a),"r"(x),"r"(y),"r"(z),"r"(w):"memory"); }
__device__ __forceinline__ float ldsf(uint32_t a){ float v; asm volatile("ld.shared.f32 %0, [%1];":"=f"(v):"r"(a):"memory"); return v; }
__device__ __forceinline__ float2 lds64f(uint32_t a){ float2 v; asm volatile("ld.shared.v2.f32 {%0,%1}, [%2];":"=f"(v.x),"=f"(v.y):"r"(a):"memory"); return v; }
__device__ __forceinline__ uint4 lds128(uint32_t a){ uint4 v; asm volatile("ld.shared.v4.u32 {%0,%1,%2,%3}, [%4];":"=r"(v.x),"=r"(v.y),"=r"(v.z),"=r"(v.w):"r"(a):"memory"); return v; }
__device__ __forceinline__ uint4 ld128_keep(const void* p){ uint4 v; asm volatile("ld.global.v4.u32 {%0,%1,%2,%3}, [%4];":"=r"(v.x),"=r"(v.y),"=r"(v.z),"=r"(v.w):"l"(p):"memory"); return v; }
__device__ __forceinline__ uint4 ld128_rlx(const void* p){ uint4 v; asm volatile("ld.relaxed.gpu.global.v4.u32 {%0,%1,%2,%3}, [%4];":"=r"(v.x),"=r"(v.y),"=r"(v.z),"=r"(v.w):"l"(p):"memory"); return v; }
__device__ __forceinline__ uint32_t ld32_rlx(const void* p){ uint32_t v; asm volatile("ld.relaxed.gpu.global.u32 %0, [%1];":"=r"(v):"l"(p):"memory"); return v; }
__device__ __forceinline__ void st128_rlx(void* p, uint32_t x, uint32_t y, uint32_t z, uint32_t w){ asm volatile("st.relaxed.gpu.global.v4.u32 [%0], {%1,%2,%3,%4};"::"l"(p),"r"(x),"r"(y),"r"(z),"r"(w):"memory"); }
__device__ __forceinline__ void st64_rlx(void* p, uint32_t x, uint32_t y){ asm volatile("st.relaxed.gpu.global.v2.u32 [%0], {%1,%2};"::"l"(p),"r"(x),"r"(y):"memory"); }
__device__ __forceinline__ void st32_rlx(void* p, uint32_t x){ asm volatile("st.relaxed.gpu.global.u32 [%0], %1;"::"l"(p),"r"(x):"memory"); }
__device__ __forceinline__ uint32_t tagw(float x, uint32_t t){ return (__float_as_uint(x) & ~3u) | t; }
__device__ __forceinline__ float untag(uint32_t w){ return __uint_as_float(w & ~3u); }

template<int TA, int TB, uint32_t HA, uint32_t HB> __device__ __forceinline__ void wgmma_ss_n128(float (&d)[64], uint32_t da, uint32_t db, int scale_d){
  asm volatile("{\n.reg .pred p;\n.reg .b64 a, b;\nsetp.ne.b32 p, %70, 0;\nmov.b64 a, {%64, %68};\nmov.b64 b, {%65, %69};\n"
  "wgmma.mma_async.sync.aligned.m64n128k16.f32.bf16.bf16 {%0, %1, %2, %3, %4, %5, %6, %7, %8, %9, %10, %11, %12, %13, %14, %15, %16, %17, %18, %19, %20, %21, %22, %23, %24, %25, %26, %27, %28, %29, %30, %31, %32, %33, %34, %35, %36, %37, %38, %39, %40, %41, %42, %43, %44, %45, %46, %47, %48, %49, %50, %51, %52, %53, %54, %55, %56, %57, %58, %59, %60, %61, %62, %63}, a, b, p, 1, 1, %66, %67;\n}\n"
  : "+f"(d[0]), "+f"(d[1]), "+f"(d[2]), "+f"(d[3]), "+f"(d[4]), "+f"(d[5]), "+f"(d[6]), "+f"(d[7]), "+f"(d[8]), "+f"(d[9]), "+f"(d[10]), "+f"(d[11]), "+f"(d[12]), "+f"(d[13]), "+f"(d[14]), "+f"(d[15]), "+f"(d[16]), "+f"(d[17]), "+f"(d[18]), "+f"(d[19]), "+f"(d[20]), "+f"(d[21]), "+f"(d[22]), "+f"(d[23]), "+f"(d[24]), "+f"(d[25]), "+f"(d[26]), "+f"(d[27]), "+f"(d[28]), "+f"(d[29]), "+f"(d[30]), "+f"(d[31]), "+f"(d[32]), "+f"(d[33]), "+f"(d[34]), "+f"(d[35]), "+f"(d[36]), "+f"(d[37]), "+f"(d[38]), "+f"(d[39]), "+f"(d[40]), "+f"(d[41]), "+f"(d[42]), "+f"(d[43]), "+f"(d[44]), "+f"(d[45]), "+f"(d[46]), "+f"(d[47]), "+f"(d[48]), "+f"(d[49]), "+f"(d[50]), "+f"(d[51]), "+f"(d[52]), "+f"(d[53]), "+f"(d[54]), "+f"(d[55]), "+f"(d[56]), "+f"(d[57]), "+f"(d[58]), "+f"(d[59]), "+f"(d[60]), "+f"(d[61]), "+f"(d[62]), "+f"(d[63])
  : "r"(da), "r"(db), "n"(TA), "n"(TB), "n"(HA), "n"(HB), "r"(scale_d));
}
template<int TA, int TB, uint32_t HA, uint32_t HB> __device__ __forceinline__ void wgmma_sa_n128(float (&d)[64], uint32_t da, uint32_t db){
  asm volatile("{\n.reg .pred p;\n.reg .b64 a, b;\nsetp.ne.b32 p, 1, 0;\nmov.b64 a, {%64, %68};\nmov.b64 b, {%65, %69};\n"
  "wgmma.mma_async.sync.aligned.m64n128k16.f32.bf16.bf16 {%0, %1, %2, %3, %4, %5, %6, %7, %8, %9, %10, %11, %12, %13, %14, %15, %16, %17, %18, %19, %20, %21, %22, %23, %24, %25, %26, %27, %28, %29, %30, %31, %32, %33, %34, %35, %36, %37, %38, %39, %40, %41, %42, %43, %44, %45, %46, %47, %48, %49, %50, %51, %52, %53, %54, %55, %56, %57, %58, %59, %60, %61, %62, %63}, a, b, p, 1, 1, %66, %67;\n}\n"
  : "+f"(d[0]), "+f"(d[1]), "+f"(d[2]), "+f"(d[3]), "+f"(d[4]), "+f"(d[5]), "+f"(d[6]), "+f"(d[7]), "+f"(d[8]), "+f"(d[9]), "+f"(d[10]), "+f"(d[11]), "+f"(d[12]), "+f"(d[13]), "+f"(d[14]), "+f"(d[15]), "+f"(d[16]), "+f"(d[17]), "+f"(d[18]), "+f"(d[19]), "+f"(d[20]), "+f"(d[21]), "+f"(d[22]), "+f"(d[23]), "+f"(d[24]), "+f"(d[25]), "+f"(d[26]), "+f"(d[27]), "+f"(d[28]), "+f"(d[29]), "+f"(d[30]), "+f"(d[31]), "+f"(d[32]), "+f"(d[33]), "+f"(d[34]), "+f"(d[35]), "+f"(d[36]), "+f"(d[37]), "+f"(d[38]), "+f"(d[39]), "+f"(d[40]), "+f"(d[41]), "+f"(d[42]), "+f"(d[43]), "+f"(d[44]), "+f"(d[45]), "+f"(d[46]), "+f"(d[47]), "+f"(d[48]), "+f"(d[49]), "+f"(d[50]), "+f"(d[51]), "+f"(d[52]), "+f"(d[53]), "+f"(d[54]), "+f"(d[55]), "+f"(d[56]), "+f"(d[57]), "+f"(d[58]), "+f"(d[59]), "+f"(d[60]), "+f"(d[61]), "+f"(d[62]), "+f"(d[63])
  : "r"(da), "r"(db), "n"(TA), "n"(TB), "n"(HA), "n"(HB));
}
template<int TA, int TB, uint32_t HA, uint32_t HB> __device__ __forceinline__ void wgmma_sa_n40(float (&d)[20], uint32_t da, uint32_t db){
  asm volatile("{\n.reg .pred p;\n.reg .b64 a, b;\nsetp.ne.b32 p, 1, 0;\nmov.b64 a, {%20, %24};\nmov.b64 b, {%21, %25};\n"
  "wgmma.mma_async.sync.aligned.m64n40k16.f32.bf16.bf16 {%0, %1, %2, %3, %4, %5, %6, %7, %8, %9, %10, %11, %12, %13, %14, %15, %16, %17, %18, %19}, a, b, p, 1, 1, %22, %23;\n}\n"
  : "+f"(d[0]), "+f"(d[1]), "+f"(d[2]), "+f"(d[3]), "+f"(d[4]), "+f"(d[5]), "+f"(d[6]), "+f"(d[7]), "+f"(d[8]), "+f"(d[9]), "+f"(d[10]), "+f"(d[11]), "+f"(d[12]), "+f"(d[13]), "+f"(d[14]), "+f"(d[15]), "+f"(d[16]), "+f"(d[17]), "+f"(d[18]), "+f"(d[19])
  : "r"(da), "r"(db), "n"(TA), "n"(TB), "n"(HA), "n"(HB));
}
template<int TA, int TB, uint32_t HA, uint32_t HB> __device__ __forceinline__ void wgmma_sz_n40(float (&d)[20], uint32_t da, uint32_t db){
  asm volatile("{\n.reg .pred p;\n.reg .b64 a, b;\nsetp.ne.b32 p, 0, 0;\nmov.b64 a, {%20, %24};\nmov.b64 b, {%21, %25};\n"
  "wgmma.mma_async.sync.aligned.m64n40k16.f32.bf16.bf16 {%0, %1, %2, %3, %4, %5, %6, %7, %8, %9, %10, %11, %12, %13, %14, %15, %16, %17, %18, %19}, a, b, p, 1, 1, %22, %23;\n}\n"
  : "=f"(d[0]), "=f"(d[1]), "=f"(d[2]), "=f"(d[3]), "=f"(d[4]), "=f"(d[5]), "=f"(d[6]), "=f"(d[7]), "=f"(d[8]), "=f"(d[9]), "=f"(d[10]), "=f"(d[11]), "=f"(d[12]), "=f"(d[13]), "=f"(d[14]), "=f"(d[15]), "=f"(d[16]), "=f"(d[17]), "=f"(d[18]), "=f"(d[19])
  : "r"(da), "r"(db), "n"(TA), "n"(TB), "n"(HA), "n"(HB));
}
template<int TA, int TB, uint32_t HA, uint32_t HB> __device__ __forceinline__ void wgmma_sa_n32(float (&d)[16], uint32_t da, uint32_t db){
  asm volatile("{\n.reg .pred p;\n.reg .b64 a, b;\nsetp.ne.b32 p, 1, 0;\nmov.b64 a, {%16, %20};\nmov.b64 b, {%17, %21};\n"
  "wgmma.mma_async.sync.aligned.m64n32k16.f32.bf16.bf16 {%0, %1, %2, %3, %4, %5, %6, %7, %8, %9, %10, %11, %12, %13, %14, %15}, a, b, p, 1, 1, %18, %19;\n}\n"
  : "+f"(d[0]), "+f"(d[1]), "+f"(d[2]), "+f"(d[3]), "+f"(d[4]), "+f"(d[5]), "+f"(d[6]), "+f"(d[7]), "+f"(d[8]), "+f"(d[9]), "+f"(d[10]), "+f"(d[11]), "+f"(d[12]), "+f"(d[13]), "+f"(d[14]), "+f"(d[15])
  : "r"(da), "r"(db), "n"(TA), "n"(TB), "n"(HA), "n"(HB));
}
template<int TA, int TB, uint32_t HA, uint32_t HB> __device__ __forceinline__ void wgmma_ss_n32(float (&d)[16], uint32_t da, uint32_t db, int scale_d){
  asm volatile("{\n.reg .pred p;\n.reg .b64 a, b;\nsetp.ne.b32 p, %22, 0;\nmov.b64 a, {%16, %20};\nmov.b64 b, {%17, %21};\n"
  "wgmma.mma_async.sync.aligned.m64n32k16.f32.bf16.bf16 {%0, %1, %2, %3, %4, %5, %6, %7, %8, %9, %10, %11, %12, %13, %14, %15}, a, b, p, 1, 1, %18, %19;\n}\n"
  : "+f"(d[0]), "+f"(d[1]), "+f"(d[2]), "+f"(d[3]), "+f"(d[4]), "+f"(d[5]), "+f"(d[6]), "+f"(d[7]), "+f"(d[8]), "+f"(d[9]), "+f"(d[10]), "+f"(d[11]), "+f"(d[12]), "+f"(d[13]), "+f"(d[14]), "+f"(d[15])
  : "r"(da), "r"(db), "n"(TA), "n"(TB), "n"(HA), "n"(HB), "r"(scale_d));
}
template<int TB, uint32_t HB> __device__ __forceinline__ void wgmma_ra_n32(float (&d)[16], uint32_t a0, uint32_t a1, uint32_t a2, uint32_t a3, uint32_t db){
  asm volatile("{\n.reg .pred p;\n.reg .b64 a, b;\nsetp.ne.b32 p, 1, 0;\nmov.b64 b, {%20, %22};\n"
  "wgmma.mma_async.sync.aligned.m64n32k16.f32.bf16.bf16 {%0, %1, %2, %3, %4, %5, %6, %7, %8, %9, %10, %11, %12, %13, %14, %15}, {%16,%17,%18,%19}, b, p, 1, 1, %21;\n}\n"
  : "+f"(d[0]), "+f"(d[1]), "+f"(d[2]), "+f"(d[3]), "+f"(d[4]), "+f"(d[5]), "+f"(d[6]), "+f"(d[7]), "+f"(d[8]), "+f"(d[9]), "+f"(d[10]), "+f"(d[11]), "+f"(d[12]), "+f"(d[13]), "+f"(d[14]), "+f"(d[15])
  : "r"(a0), "r"(a1), "r"(a2), "r"(a3), "r"(db), "n"(TB), "n"(HB));
}
template<int TB, uint32_t HB> __device__ __forceinline__ void wgmma_rs_n32(float (&d)[16], uint32_t a0, uint32_t a1, uint32_t a2, uint32_t a3, uint32_t db, int scale_d){
  asm volatile("{\n.reg .pred p;\n.reg .b64 a, b;\nsetp.ne.b32 p, %23, 0;\nmov.b64 b, {%20, %22};\n"
  "wgmma.mma_async.sync.aligned.m64n32k16.f32.bf16.bf16 {%0, %1, %2, %3, %4, %5, %6, %7, %8, %9, %10, %11, %12, %13, %14, %15}, {%16,%17,%18,%19}, b, p, 1, 1, %21;\n}\n"
  : "+f"(d[0]), "+f"(d[1]), "+f"(d[2]), "+f"(d[3]), "+f"(d[4]), "+f"(d[5]), "+f"(d[6]), "+f"(d[7]), "+f"(d[8]), "+f"(d[9]), "+f"(d[10]), "+f"(d[11]), "+f"(d[12]), "+f"(d[13]), "+f"(d[14]), "+f"(d[15])
  : "r"(a0), "r"(a1), "r"(a2), "r"(a3), "r"(db), "n"(TB), "n"(HB), "r"(scale_d));
}
template<int TB, uint32_t HB> __device__ __forceinline__ void wgmma_ra_n40(float (&d)[20], uint32_t a0, uint32_t a1, uint32_t a2, uint32_t a3, uint32_t db){
  asm volatile("{\n.reg .pred p;\n.reg .b64 a, b;\nsetp.ne.b32 p, 1, 0;\nmov.b64 b, {%24, %26};\n"
  "wgmma.mma_async.sync.aligned.m64n40k16.f32.bf16.bf16 {%0, %1, %2, %3, %4, %5, %6, %7, %8, %9, %10, %11, %12, %13, %14, %15, %16, %17, %18, %19}, {%20,%21,%22,%23}, b, p, 1, 1, %25;\n}\n"
  : "+f"(d[0]), "+f"(d[1]), "+f"(d[2]), "+f"(d[3]), "+f"(d[4]), "+f"(d[5]), "+f"(d[6]), "+f"(d[7]), "+f"(d[8]), "+f"(d[9]), "+f"(d[10]), "+f"(d[11]), "+f"(d[12]), "+f"(d[13]), "+f"(d[14]), "+f"(d[15]), "+f"(d[16]), "+f"(d[17]), "+f"(d[18]), "+f"(d[19])
  : "r"(a0), "r"(a1), "r"(a2), "r"(a3), "r"(db), "n"(TB), "n"(HB));
}
template<int TB, uint32_t HB> __device__ __forceinline__ void wgmma_rz_n40(float (&d)[20], uint32_t a0, uint32_t a1, uint32_t a2, uint32_t a3, uint32_t db){
  asm volatile("{\n.reg .pred p;\n.reg .b64 a, b;\nsetp.ne.b32 p, 0, 0;\nmov.b64 b, {%24, %26};\n"
  "wgmma.mma_async.sync.aligned.m64n40k16.f32.bf16.bf16 {%0, %1, %2, %3, %4, %5, %6, %7, %8, %9, %10, %11, %12, %13, %14, %15, %16, %17, %18, %19}, {%20,%21,%22,%23}, b, p, 1, 1, %25;\n}\n"
  : "=f"(d[0]), "=f"(d[1]), "=f"(d[2]), "=f"(d[3]), "=f"(d[4]), "=f"(d[5]), "=f"(d[6]), "=f"(d[7]), "=f"(d[8]), "=f"(d[9]), "=f"(d[10]), "=f"(d[11]), "=f"(d[12]), "=f"(d[13]), "=f"(d[14]), "=f"(d[15]), "=f"(d[16]), "=f"(d[17]), "=f"(d[18]), "=f"(d[19])
  : "r"(a0), "r"(a1), "r"(a2), "r"(a3), "r"(db), "n"(TB), "n"(HB));
}
template<int TB, uint32_t HB> __device__ __forceinline__ void wgmma_ra_n8(float (&d)[4], uint32_t a0, uint32_t a1, uint32_t a2, uint32_t a3, uint32_t db){
  asm volatile("{\n.reg .pred p;\n.reg .b64 a, b;\nsetp.ne.b32 p, 1, 0;\nmov.b64 b, {%8, %10};\n"
  "wgmma.mma_async.sync.aligned.m64n8k16.f32.bf16.bf16 {%0, %1, %2, %3}, {%4,%5,%6,%7}, b, p, 1, 1, %9;\n}\n"
  : "+f"(d[0]), "+f"(d[1]), "+f"(d[2]), "+f"(d[3])
  : "r"(a0), "r"(a1), "r"(a2), "r"(a3), "r"(db), "n"(TB), "n"(HB));
}
template<int TB, uint32_t HB> __device__ __forceinline__ void wgmma_rz_n8(float (&d)[4], uint32_t a0, uint32_t a1, uint32_t a2, uint32_t a3, uint32_t db){
  asm volatile("{\n.reg .pred p;\n.reg .b64 a, b;\nsetp.ne.b32 p, 0, 0;\nmov.b64 b, {%8, %10};\n"
  "wgmma.mma_async.sync.aligned.m64n8k16.f32.bf16.bf16 {%0, %1, %2, %3}, {%4,%5,%6,%7}, b, p, 1, 1, %9;\n}\n"
  : "=f"(d[0]), "=f"(d[1]), "=f"(d[2]), "=f"(d[3])
  : "r"(a0), "r"(a1), "r"(a2), "r"(a3), "r"(db), "n"(TB), "n"(HB));
}

constexpr int SEQ = 2048, DM = 1024, FF = 3584;
constexpr float LOG2E = 1.4426950408889634f;
constexpr uint32_t POLL_LIMIT = 1u << 22;
constexpr int NPRE = 2;
#define QW 12
#define RST_STEP 100
#define SKM 0x251
#define LAG 1
#define PF_T0 6500
#define PF_DT 800
#define Q0L 1
#define NFFN_L NFFN
#define FF_DT 600
#define OUT_NS 0
constexpr int NFFN = 112;

constexpr uint32_t SB0 = 1024;
constexpr uint32_t KV_STAGE = 49152, R5 = 32768;
constexpr uint32_t OFF_X = 163840, OFF_S = 196608, OFF_WPHI = OFF_S + 20480, OFF_M = 229376, SMEM_BYTES = 232448;
constexpr uint32_t OFF_RS256 = 212992, OFF_ONES = OFF_RS256 + 1024, OFF_WPHIK1 = OFF_ONES + 1024, OFF_KVZ = OFF_S;
constexpr uint32_t OFF_WPHIK = OFF_S, OFF_BXK = OFF_S + 2048, OFF_AXK = OFF_S + 4096;
constexpr uint32_t OFF_AXQ = OFF_WPHI, OFF_BXQ = OFF_WPHI + 2048, OFF_WPHIQ = OFF_WPHI + 4096;
constexpr uint32_t B_FULLKV = OFF_M, B_EMPTYKV = OFF_M + 32, B_FULL5 = OFF_M + 64, B_EMPTY5 = OFF_M + 104;
constexpr uint32_t B_W = OFF_M + 144, B_OS = OFF_M + 152, B_R = OFF_M + 160, B_AUX = OFF_M + 168, B_AUXQ = OFF_M + 176, B_KD = OFF_M + 184, B_RC = OFF_M + 192  ;
constexpr uint32_t B_FULLA = OFF_M + 768, B_QL = B_FULLA + 80, B_PUB = B_FULLA + 88, B_UO = B_FULLA + 96  ;
constexpr uint32_t OFF_SUMWR = OFF_M + 896, OFF_EP = OFF_M + 208, OFF_KEY = OFF_M + 216, OFF_EXC = OFF_M + 224;
constexpr uint32_t OFF_RSQ = OFF_M + 256, OFF_WR = OFF_M + 2048, OFF_XSEL = 4 * R5;
constexpr uint32_t OFF_ACT = OFF_XSEL + 2048, OFF_GU = OFF_XSEL + 4096, OFF_SCR = OFF_M + 2432, B_F = OFF_M + 1536  , B_WD = B_F + 64  , B_WC = B_F + 96  , B_DR = B_F + 128  , B_RX = B_F + 144;
constexpr int KVP = 6 * 128;

enum { NB_G2E = 1, NB_XS = 2, NB_WG01 = 3, NB_ACT = 4, NB_Q0 = 5  , NB_ST = 14, NB_DN = 9, NB_OUT = 8  , NB_ZERO = 10, NB_PUB = 11, NB_TOK = 10  , NB_L0 = 12  , NB_WG2 = 7, NB_QGO = 15 };

struct Scratch {
  bf16     o[SEQ * DM];
  float4   rstat[SEQ];
  uint32_t key[32 * 128];
  uint32_t cand[128 * DM];
  uint32_t ypart[NFFN * DM];
  float4   kvacc[32 * KVP];
  uint2    stats[SEQ];
  uint32_t cskv[2 * DM];
  uint32_t csq[4 * DM];
  uint32_t oset[16 * 32];
  uint32_t epoch;
};
__device__ __align__(1024) Scratch g_scr;
#define TS(id)
#define TDUMP()
#define TS0_DECL()
#define TS0_READ()
#define TS0_WRITE()
#define TK(id)
#define TSW(id)

struct Params {
  CUtensorMap x128, x64, wkv, wq, wo, wd, wg, wu, phi;
  const bf16 *x, *wqkv, *wo_p, *wg_p, *wu_p, *wd_p, *wr;
  bf16* out_p;
  Scratch* g;
};

constexpr float EXP_LIM = 1.1529215e18f, ARG_LIM2 = 3600.f;
__device__ __forceinline__ void dual_exp2(const float (&p)[2][16], uint32_t (&ph)[4][8]) {
  #pragma unroll
  for (int h = 0; h < 2; h++)
    #pragma unroll
    for (int k = 0; k < 8; k++) { ph[2*h][k] = pack_bf16(ex2(p[h][2*k]), ex2(p[h][2*k+1])); ph[2*h+1][k] = pack_bf16(ex2(-p[h][2*k]), ex2(-p[h][2*k+1])); }
}
__device__ __forceinline__ void row_extremes(const float (&p)[16], const float (&c)[2], float (&m)[4]) {
  m[0] = m[2] = p[0]; m[1] = m[3] = p[2];
  #pragma unroll
  for (int i = 0; i < 16; i++) { m[(i >> 1) & 1] = fmaxf(m[(i >> 1) & 1], p[i]); m[2 + ((i >> 1) & 1)] = fminf(m[2 + ((i >> 1) & 1)], p[i]); }
  #pragma unroll
  for (int o = 1; o < 4; o <<= 1) {
    m[0] = fmaxf(m[0], __shfl_xor_sync(~0u, m[0], o)); m[1] = fmaxf(m[1], __shfl_xor_sync(~0u, m[1], o));
    m[2] = fminf(m[2], __shfl_xor_sync(~0u, m[2], o)); m[3] = fminf(m[3], __shfl_xor_sync(~0u, m[3], o));
  }
  m[0] *= -c[0]; m[1] *= -c[1]; m[2] *= c[0]; m[3] *= c[1];
}
__device__ __forceinline__ void dual_exp2_shifted(const float (&p)[2][16], uint32_t (&ph)[4][8]) {
  #pragma unroll
  for (int h = 0; h < 2; h++) {
    const float one[2] = {1.f, 1.f};
    float m[4];
    row_extremes(p[h], one, m);
    #pragma unroll
    for (int k = 0; k < 8; k++) {
      ph[2*h][k] = pack_bf16(ex2(p[h][2*k] + m[k & 1]), ex2(p[h][2*k+1] + m[k & 1]));
      ph[2*h+1][k] = pack_bf16(ex2(m[2 + (k & 1)] - p[h][2*k]), ex2(m[2 + (k & 1)] - p[h][2*k+1]));
    }
  }
}
__device__ __forceinline__ void row_sums(float (&s)[4][4], const uint32_t (&ph)[4][8], uint32_t ones) {
  #pragma unroll
  for (int i = 0; i < 4; i++) wgmma_rz_n8<0, H0>(s[i], ph[i][0], ph[i][1], ph[i][2], ph[i][3], ones);
  #pragma unroll
  for (int i = 0; i < 4; i++) wgmma_ra_n8<0, H0>(s[i], ph[i][4], ph[i][5], ph[i][6], ph[i][7], ones);
}
__device__ __forceinline__ uint32_t mul_bf16x2(uint32_t a, uint32_t b) { uint32_t r; asm("mul.rn.bf16x2 %0, %1, %2;" : "=r"(r) : "r"(a), "r"(b)); return r; }
__device__ __forceinline__ void normalize(uint32_t (&ph)[4][8], const float (&s)[4][4]) {
  #pragma unroll
  for (int i = 0; i < 4; i++) {
    const float i0 = rcp(s[i][0]), i1 = rcp(s[i][2]);
    const uint32_t n0 = pack_bf16(i0, i0), n1 = pack_bf16(i1, i1);
    #pragma unroll
    for (int k = 0; k < 4; k++) { ph[i][2*k] = mul_bf16x2(ph[i][2*k], n0); ph[i][2*k+1] = mul_bf16x2(ph[i][2*k+1], n1); }
  }
}
__device__ __forceinline__ void split_bf16(float a, float b, uint32_t& hi, uint32_t& lo) { hi = pack_bf16(a, b); lo = pack_bf16(a - bf_lo(hi), b - bf_hi(hi)); }
__device__ __forceinline__ void put_colsums(uint32_t base, int lane, float a, float b, float c, float d) {
  uint32_t h0, l0, h1, l1;
  split_bf16(a, b, h0, l0); split_bf16(c, d, h1, l1);
  const uint32_t ad = base + (lane >> 1) * 128 + (lane & 1) * 8;
  sts64(ad, h0, h1); sts64(ad + 16, l0, l1); sts64(ad + 32, h0, h1); sts64(ad + 48, l0, l1);
  sts128(base + (lane >> 1) * 128 + 64 + (lane & 1) * 32, 0, 0, 0, 0); sts128(base + (lane >> 1) * 128 + 80 + (lane & 1) * 32, 0, 0, 0, 0);
}
__device__ __forceinline__ float reduce8(const float (&v)[8], int lane) {
  const bool b4 = lane & 16, b3 = lane & 8, b2 = lane & 4;
  float a[4], b[2];
  #pragma unroll
  for (int i = 0; i < 4; i++) a[i] = (b4 ? v[4 + i] : v[i]) + __shfl_xor_sync(~0u, b4 ? v[i] : v[4 + i], 16);
  #pragma unroll
  for (int i = 0; i < 2; i++) b[i] = (b3 ? a[2 + i] : a[i]) + __shfl_xor_sync(~0u, b3 ? a[i] : a[2 + i], 8);
  return (b2 ? b[1] : b[0]) + __shfl_xor_sync(~0u, b2 ? b[0] : b[1], 4);
}
__device__ __forceinline__ bool tag_bad(uint4 v, uint32_t tg) { return (((v.x ^ tg) | (v.y ^ tg) | (v.z ^ tg) | (v.w ^ tg)) & 3) != 0; }

__global__ void __launch_bounds__(512, 1) fused_kernel(const __grid_constant__ Params P) {
  extern __shared__ __align__(1024) uint8_t smem_raw[];
  const uint32_t sb = smem_u32(smem_raw);
  const int tid = threadIdx.x, lane = tid & 31;
  const int warp = __shfl_sync(~0u, tid >> 5, 0), wg = warp >> 2, wp = warp & 3;
  const int cp = blockIdx.x >> 1, cu = cp - 36, cd = (cu * 37) >> 8;
  const int gi = cp < 4 ? 0 : cu < 0 ? (cp - 4) & 7 : 1 + cu - 7 * cd, gx = cp < 4 ? 4 + cp : cu < 0 ? (cp - 4) >> 3 : 4 + cd;
  const int rank = blockIdx.x & 1, c = 64 * (gi & 1) + 8 * gx + (gi & 6) + rank;
  const int f = 16 * ((gi + 7) & 7) + 2 * gx + rank;
  const int m256 = c >> 4, nkv = c & 15, m128 = c >> 3, j = c & 7;
  const int ha = 4 * (nkv >> 1) + (nkv & 1);

  Scratch* const G = P.g;
  if ((sb & 0x3ffff) != SB0) asm volatile("trap;");

  TS0_DECL();
  if (warp == 12) {
    const bool el = elect_one();
    TS0_READ();
    if (el) {
      #pragma unroll
      for (int i = 0; i < 4; i++) mbar_init(sb + B_FULLKV + 8 * i, 1);
      asm volatile("fence.mbarrier_init.release.cluster;" ::: "memory");
      fence_async_smem();
      #pragma unroll
      for (int s = 0; s < NPRE; s++) {
        const uint32_t st = sb + s * KV_STAGE, fb = sb + B_FULLKV + 8 * s;
        mbar_expect_tx(fb, KV_STAGE);
        tma_4d(st + 32768, &P.wkv, 0, 64 * s, nkv, 1, fb);
        tma_2d(st, &P.x128, 64 * s, 256 * m256, fb);
        tma_2d(st + 16384, &P.x128, 64 * s, 256 * m256 + 128, fb);
      }
    }
  } else if (tid == 0) {
    #pragma unroll
    for (int i = 0; i < 22; i++) mbar_init(sb + B_EMPTYKV + 8 * i, i >= 20 ? 4 : i < 4 ? 12 : (i >= 9 && i < 14) ? 4 : i == 17 || i == 18 ? 2 : 1);
    #pragma unroll
    for (int i = 0; i < 19; i++) mbar_init(sb + B_F + 8 * i, i < 18 ? 1 : 8);
    #pragma unroll
    for (int i = 0; i < 16; i++) mbar_init(sb + B_FULLA + 8 * i, i < 11 ? 1 : i == 11 ? 2 : 4);
    asm volatile("fence.mbarrier_init.release.cluster;" ::: "memory");
    fence_async_smem();
  }
  __syncthreads();
  cluster_arrive();

  if (wg == 3) {
    asm volatile("setmaxnreg.dec.sync.aligned.u32 32;");
    cluster_wait();
    const bool el = elect_one();
    const uint64_t ef = policy_evict_first();
    auto fetch_o = [&](int i0, uint32_t so, uint32_t par) {
      uint32_t ready = 0;
      const bf16* base = G->o + (m128 * 16 + (i0 >> 3)) * 8192 + rank * 4096;
      const bf16* hint = base + (((j & 6) + (lane >> 2)) & 7) * 16384 + (lane & 3) * 1024 + 1022;
      #pragma unroll 1
      for (int i = i0 & 7; i < 8; i++) {
        uint32_t it = 0;
        while (((ready >> (4 * i)) & 15) != 15 && ++it < POLL_LIMIT) ready = __ballot_sync(~0u, ld32_rlx(hint) != ~0u);
        if (i0 == 2) {
          if (i == 2 && el) TS(rank ? 31 : 10);
          if (i == 5) mbar_wait(sb + B_PUB, 0);
        } else if (i == 0) bar_sync(NB_L0, 64);
        mbar_wait(sb + B_EMPTY5 + so, par);
        if (el) {
          bulk_g2s_mc(sb + so * 4096 + rank * 8192, base + (((j & 6) + i) & 7) * 16384, 8192, sb + B_FULLA + 2 * so + 8 * rank, ef);
          if (i == (i0 & 7)) TS(i0 == 2 ? (rank ? 4 : 12) : (rank ? 9 : 13));
        }
        so += 8;
        if (so == 40) { so = 0; par ^= 1; }
      }
    };
    if (wp == 0) {
      {
        #pragma unroll 1
        for (int kb = NPRE; kb < 16; kb++) {
          const uint32_t st = sb + (kb & 3) * KV_STAGE, fb = sb + B_FULLKV + 8 * (kb & 3);
          mbar_wait(fb + (B_EMPTYKV - B_FULLKV), ~(kb >> 2) & 1);
          if (el) {
            mbar_expect_tx(fb, KV_STAGE);
            tma_2d_mc(st + rank * 16384, &P.x128, 64 * kb, 256 * m256 + 128 * rank, fb);
            tma_4d_h(st + 32768, &P.wkv, 0, 64 * kb, nkv, 1, fb, ef);
          }
        }
        TS0_WRITE();
        uint64_t ord = 0xf3120edcba987654ull;
        uint32_t so = 0, par = 1;
        #pragma unroll 1
        for (int i = 0; i < 16; i++) {
          const uint32_t st = sb + so * 4096, fb = sb + B_FULL5 + so;
          const int k0 = (64 * (uint32_t)ord + 128 * (j & 6)) & 960;
          mbar_wait(i < 5 ? sb + B_EMPTYKV + so - (i > 1 ? 8 : 0) : fb + (B_EMPTY5 - B_FULL5), par);
          if (el) {
            mbar_expect_tx(fb, R5);
            tma_2d_mc_h(st + rank * 8192, &P.x64, k0, 128 * m128 + 64 * rank, fb, ef);
            tma_3d_h(st + 16384, &P.wq, 0, k0, 2 * j, fb, ef);
          }
          ord >>= 4; so += 8;
          if (so == 40) { so = 0; par ^= 1; }
        }
        #pragma unroll 1
        for (int i = 0; i < 16; i++) {
          const uint32_t fb = sb + B_FULL5 + so, fa = sb + B_FULLA + 2 * so, na = i == rank ? 0 : 8192;
          if (i == 1) { if (el) mbar_arrive(sb + B_QL); mbar_wait2(sb + B_FULL5 + 16, 0, sb + B_FULL5 + 24, 0); mbar_wait(sb + B_FULL5 + 32, 0); if (el) mbar_arrive(sb + B_R); }
          mbar_wait(fb + (B_EMPTY5 - B_FULL5), par);
          if (el) {
            mbar_expect_tx(fb, 16384);
            tma_4d_h(sb + so * 4096 + 16384, &P.wo, 0, 128 * (((j & 6) + i) & 7) + 4 * (i & 8), 0, 2 * j, fb, ef);
            mbar_expect_tx(fa, na); mbar_expect_tx(fa + 8, na);
          }
          so += 8;
          if (so == 40) { so = 0; par ^= 1; }
        }
        mbar_wait(sb + B_EMPTY5 + 16, 1); if (el) mbar_arrive(sb + B_DR);
        mbar_wait(sb + B_EMPTY5 + 24, 1); if (el) mbar_arrive(sb + B_DR + 8);
      }
    } else if (wp == 3) {
      const uint32_t t_start = (uint32_t)clock();
      if (el) {
        mbar_expect_tx(sb + B_W, 12288);
        #pragma unroll 1
        for (int i = 0; i < 6; i++) tma_2d(sb + (i == 0 ? OFF_WPHIK : i == 1 ? OFF_WPHIK1 : OFF_WPHIQ + 2048 * (i - 2)), &P.phi, 0, 32 * (i < 2 ? 2 * nkv + i : 4 * j + 2 * (i & 1) + ((i - 2) >> 1)), sb + B_W);
        prefetch_map(&P.x64); prefetch_map(&P.wq); prefetch_map(&P.wo);
        prefetch_map(&P.wd); prefetch_map(&P.wg); prefetch_map(&P.wu);
      }
      const uint32_t ep1 = ld32_rlx(&G->epoch) + 1;
      #pragma unroll 1
      for (int i = 0; i < 8; i++) {
        st128_rlx(&G->cand[(m128 * 8 + i) * DM + (lane >> 4) * 512 + 64 * j + 4 * (lane & 15)], ~0u, ~0u, ~0u, ~0u);
        if (f < NFFN) st128_rlx(&G->ypart[f * DM + 128 * i + 4 * lane], ~0u, ~0u, ~0u, ~0u);
      }
      if (lane < 16) st128_rlx(&G->rstat[16 * c + lane], 0, 0, 0, 0);
      if (lane < 8) st128_rlx(&G->key[(4 * j + (lane >> 1)) * 128 + m128 * 8 + 4 * (lane & 1)], 0, 0, 0, 0);
      if (c < 32) {
        #pragma unroll 1
        for (int i = lane; i < KVP; i += 32) st128_rlx(&G->kvacc[(ha + 2 * m256) * KVP + i], 0, 0, 0, 0);
      }
      fence_gpu();
      bar_arrive(NB_ZERO, 160);
      if (el) {
        #pragma unroll 1
        for (int i = 0; i < 30; i++) {
          while ((uint32_t)clock() - t_start < (uint32_t)(PF_T0 + PF_DT * i)) __nanosleep(64);
          if (i < 4) { bulk_prefetch(P.wqkv + (size_t)(256 * i + c) * (3 * DM), 2048); bulk_prefetch(P.wqkv + (size_t)(256 * i + 128 + c) * (3 * DM), 2048); }
          else if (i < 6) bulk_prefetch(P.wo_p + (size_t)c * 8192 + (i - 4) * 4096, 8192);
          else if (i < 22) bulk_prefetch(((i & 1) ? P.wu_p : P.wg_p) + (size_t)((i - 6) >> 1) * 458752 + c * 3584, 7168);
          else bulk_prefetch(P.wd_p + (size_t)(i - 22) * 458752 + c * 3584, 7168);
        }
      }
      __syncwarp();
      mbar_wait(sb + B_AUXQ, 0);
      for (uint32_t it = 0; __any_sync(~0u, ld32_rlx(&G->oset[m128 * 32 + (lane & 15)]) != ep1) && it < POLL_LIMIT; it++) {}
      fence_acquire_gpu();
      if (el) mbar_arrive(sb + B_OS);
      mbar_wait(sb + B_RX, 0);
      fetch_o(2, 24, 0);
      bar_arrive(NB_L0, 64);
    } else {
      const int half = wp - 1;
      const uint32_t ep1 = ld32_rlx(&G->epoch) + 1, tg = ep1 & 3;
      {
        uint32_t it = 0;
        sts128(sb + OFF_ONES + half * 512 + lane * 16, 0x3f803f80u, 0x3f803f80u, 0x3f803f80u, 0x3f803f80u);
        mbar_wait(sb + B_W, 0);
        #pragma unroll 1
        for (int i = lane; i < 1024; i += 32) { st128_rlx(G->o + (m128 * 16 + 2 * j + half) * 8192 + 8 * i, ~0u, ~0u, ~0u, ~0u); __nanosleep(RST_STEP); }
        bar_sync(NB_PUB, 192);
        const uint4* src = reinterpret_cast<const uint4*>(&G->stats[256 * m256 + 128 * half]) + lane;
        const uint4* srk = reinterpret_cast<const uint4*>(&G->cskv[128 * nkv]) + lane;
        uint4 v0, v1, vk;
        it = 0;
        do { v0 = ld128_rlx(src); v1 = ld128_rlx(src + 32); vk = ld128_rlx(srk); }
        while ((tag_bad(v0, tg) || tag_bad(v1, tg) || tag_bad(vk, tg)) && ++it < POLL_LIMIT);
        fence_acquire_gpu();
        if (half) put_colsums(sb + OFF_BXK, lane, untag(vk.x), untag(vk.y), untag(vk.z), untag(vk.w));
        #pragma unroll
        for (int i = 0; i < 2; i++) {
          const uint4 v = i ? v1 : v0;
          uint32_t hi, lo;
          split_bf16(-0.5f * untag(v.x), -0.5f * untag(v.z), hi, lo);
          const uint32_t h0 = __byte_perm(hi, hi, 0x1010), h1 = __byte_perm(hi, hi, 0x3232), l0 = __byte_perm(lo, lo, 0x1010), l1 = __byte_perm(lo, lo, 0x3232);
          const uint32_t a = sb + OFF_AXK + half * 2048 + i * 1024 + lane * 32;
          sts128(a, h0, l0, 0, 0); sts128(a + 16, h1, l1, 0, 0);
          sts64(sb + OFF_RS256 + half * 512 + i * 256 + lane * 8, v.y & ~3u, v.w & ~3u);
          if (half == (m128 & 1)) {
            const uint32_t aq = sb + OFF_AXQ + i * 1024 + lane * 32;
            sts128(aq, h0, l0, 0, 0); sts128(aq + 16, h1, l1, 0, 0);
            sts64(sb + OFF_RSQ + i * 256 + lane * 8, v.y & ~3u, v.w & ~3u);
          }
        }
        fence_async_smem();
        __syncwarp();
        if (el) { sts32(sb + OFF_EP, ep1); mbar_arrive(sb + B_AUX); if (!half) TS(1); }
        fence_gpu();
        __syncwarp();
        if (el) { st32_rlx(&G->oset[m128 * 32 + 2 * j + half], ep1); if (half) mbar_arrive(sb + B_AUXQ); }
        if (!half) {
          const uint4* src = reinterpret_cast<const uint4*>(&G->csq[128 * j]) + lane;
          uint4 v0, v1, v2, v3;
          do { v0 = ld128_rlx(src); v1 = ld128_rlx(src + DM / 4); v2 = ld128_rlx(src + DM / 2); v3 = ld128_rlx(src + 3 * DM / 4); }
          while ((tag_bad(v0, tg) || tag_bad(v1, tg) || tag_bad(v2, tg) || tag_bad(v3, tg)) && ++it < POLL_LIMIT);
          put_colsums(sb + OFF_BXQ, lane, (untag(v0.x) + untag(v1.x)) + (untag(v2.x) + untag(v3.x)), (untag(v0.y) + untag(v1.y)) + (untag(v2.y) + untag(v3.y)),
                      (untag(v0.z) + untag(v1.z)) + (untag(v2.z) + untag(v3.z)), (untag(v0.w) + untag(v1.w)) + (untag(v2.w) + untag(v3.w)));
          fence_async_smem();
          __syncwarp();
          if (el) mbar_arrive(sb + B_AUXQ);
        }
      }
      if (half == 0) mbar_wait(sb + B_OS, 0);
      auto put_gu = [&](int e, uint32_t dst) { mbar_expect_tx(sb + B_F + 8 * e, 16384); tma_2d(dst, &P.wg, 32 * f, 128 * e, sb + B_F + 8 * e); tma_2d(dst + 8192, &P.wu, 32 * f, 128 * e, sb + B_F + 8 * e); };
      if (half && f < NFFN_L) {
        if (Q0L) mbar_wait(sb + B_PUB, 0);
        mbar_wait2(sb + B_KD, 0, sb + B_QL, 0);
        if (el) put_gu(0, sb + OFF_X + 16384);
      }
      {
        #pragma unroll 1
        for (int hh = 0; hh < 2; hh++) {
          const uint32_t src = sb + (half ? OFF_X : (1 + rank) * R5) + hh * 8192, fa = sb + B_FULLA + 16 + 16 * rank + 8 * hh;
          if (!half) mbar_wait(fa, 0);
          mbar_wait(sb + B_UO + 16 * half + 8 * hh, 0);
          if (el) {
            bulk_s2g(G->o + (m128 * 16 + 2 * j + half) * 8192 + hh * 4096, src, 8192);
            if (!half) bulk_s2peer(mapa(src, rank ^ 1), src, 8192, mapa(fa, rank ^ 1));
            if (!half && !hh) TS(7);
          }
        }
        if (el) {
          bulk_commit(); bulk_wait_read();
          if (!half) { mbar_arrive_at(sb + B_PUB, 0, 1); mbar_arrive_at(sb + B_PUB, 1, 1); }
        }
        __syncwarp();
      }
      if (!half) fetch_o(8, 32, 1);
      else if (f < NFFN_L) {
        mbar_wait2(sb + B_UO, 0, sb + B_UO + 8, 0);
        uint32_t t0 = (uint32_t)clock() - FF_DT;
        #pragma unroll 1
        for (int i = 0; i < 11; i++) {
          const uint32_t dst = sb + 16384 * ((0x7654cadcadcull >> (4 * i)) & 15);
          if (i >= 3) mbar_wait(sb + B_WC + 8 * (i < 7 ? i - 3 : (i + 1) >> 1), 0);
          while ((uint32_t)clock() - t0 < (uint32_t)FF_DT) __nanosleep(32);
          t0 = (uint32_t)clock();
          if (el) {
            if (i < 4) { mbar_expect_tx(sb + B_WD + 8 * i, 16384); tma_3d_h(dst, &P.wd, 0, 32 * f, 4 * i, sb + B_WD + 8 * i, ef); }
            else put_gu(i - 3, dst);
          }
        }
      }
      __syncwarp();
    }
    if (wp & 1) {
      const int hw = wp >> 1, ch = lane & 15;
      const uint32_t src = sb + R5 + (ch >> 3) * 16384;
      bf16* dst = P.out_p + (size_t)(128 * m128) * DM + 128 * j + 8 * ch;
      bar_sync(NB_OUT + hw, 160);
      const uint4 ex = lds128(sb + OFF_EXC + 16 * hw);
      #pragma unroll 2
      for (int i = 0; i < 32; i++) {
        const int r = 64 * hw + 2 * i + (lane >> 4);
        const uint4 v = lds128(src + r * 128 + (((ch & 7) ^ (r & 7)) << 4));
        if (r != ex.x && r != ex.y && r != ex.z && r != ex.w) *reinterpret_cast<uint4*>(dst + r * DM) = v;
        if (OUT_NS) __nanosleep(OUT_NS);
      }
      bar_sync(NB_XS, 448);
      const int row = 2047 - (__float_as_uint(ldsf(sb + OFF_KEY)) & 2047) - 128 * m128;
      #pragma unroll
      for (int i = 0; i < 2; i++) {
        const int r = i ? (lane < 16 ? ex.z : ex.w) : (lane < 16 ? ex.x : ex.y);
        if (r != row) *reinterpret_cast<uint4*>(dst + r * DM) = lds128(src + r * 128 + (((ch & 7) ^ (r & 7)) << 4));
      }
    }
    __syncwarp();
    cluster_arrive(); cluster_wait();
    return;
  }

  asm volatile("setmaxnreg.inc.sync.aligned.u32 160;");
  cluster_wait();
  const int t = tid & 127, g = lane >> 2;
  const uint32_t sa = (16 * wp + (lane & 15)) * 128 + (((lane >> 4) ^ (lane & 7)) << 4);

  if (wg == 2) {
    float s[2] = {0.f, 0.f}, s2[2] = {0.f, 0.f}, ck[8] = {0.f, 0.f, 0.f, 0.f, 0.f, 0.f, 0.f, 0.f}, cs[8] = {0.f, 0.f, 0.f, 0.f, 0.f, 0.f, 0.f, 0.f};
    const uint32_t ebr = mapa(sb + B_EMPTYKV, lane & 1), tg = (ld32_rlx(&G->epoch) + 1) & 3;
    auto addx = [&](const uint4 v) {
      const uint32_t w[4] = {v.x, v.y, v.z, v.w};
      #pragma unroll
      for (int e = 0; e < 4; e++) { const float a = bf_lo(w[e]), d = bf_hi(w[e]); s[0] += a; s[1] += d; s2[0] = fmaf(a, a, s2[0]); s2[1] = fmaf(d, d, s2[1]); }
    };
    auto addc = [&](const uint4 v, float (&o)[8]) {
      o[0] += bf_lo(v.x); o[1] += bf_hi(v.x); o[2] += bf_lo(v.y); o[3] += bf_hi(v.y); o[4] += bf_lo(v.z); o[5] += bf_hi(v.z); o[6] += bf_lo(v.w); o[7] += bf_hi(v.w);
    };
    {
      const uint32_t ra = (16 * nkv + (t >> 3)) * 128 + (t & 7) * 16;
      const uint32_t ca = 32768 + (m256 >> 2) * 8192 + (t >> 1) * 128 + (((2 * (m256 & 3) + (t & 1)) ^ ((t >> 1) & 7)) << 4);
      const bf16* gx = P.x + (size_t)(256 * m256 + 16 * nkv + (t >> 3)) * DM + 640 + (t & 7) * 8;
      const bf16* gw = P.wqkv + (size_t)(640 + (t >> 1)) * (3 * DM) + (1 + (m256 >> 2)) * DM + 64 * nkv + 16 * (m256 & 3) + 8 * (t & 1);
      uint4 u[4];
      #pragma unroll
      for (int e = 0; e < 4; e++) u[e] = make_uint4(0, 0, 0, 0);
      #pragma unroll 1
      for (int kb = 0; kb < 10; kb++) {
        const uint32_t st = sb + (kb & 3) * KV_STAGE;
        mbar_wait(sb + B_FULLKV + 8 * (kb & 3), (kb >> 2) & 1);
        const uint4 x0 = lds128(st + ra), w0 = lds128(st + ca);
        addx(x0); addc(w0, ck);
        __syncwarp();
        if (lane < 2) mbar_arrive_remote(ebr + 8 * (kb & 3), 1);
        if ((SKM >> kb) & 1) {
          addx(u[0]); addx(u[1]); addc(u[2], ck); addc(u[3], ck);
          if (kb < 9) {
            u[0] = ld128_keep(gx); u[1] = ld128_keep(gx + 64); u[2] = ld128_keep(gw); u[3] = ld128_keep(gw + 64 * 3 * DM);
            gx += 128; gw += 128 * 3 * DM;
          }
        }
      }
    }
    TK(82);
    const uint32_t scr = sb + OFF_SCR + 128;
    float sx = s[0] + s[1], sq = s2[0] + s2[1];
    #pragma unroll
    for (int o = 1; o < 8; o <<= 1) { sx += __shfl_xor_sync(~0u, sx, o); sq += __shfl_xor_sync(~0u, sq, o); }
    float v = reduce8(ck, lane);
    v += __shfl_xor_sync(~0u, v, 2);
    if (!(lane & 2)) stsf(scr + (wp * 16 + 8 * (lane & 1) + (lane >> 2)) * 4, v);

    bar_sync(NB_ZERO, 160);
    if ((lane & 7) == 0) {
      const float mean = sx * (1.f / DM);
      st64_rlx(&G->stats[256 * m256 + 16 * nkv + (t >> 3)], tagw(mean, tg), tagw(rsqrtf(fmaxf(sq * (1.f / DM) - mean * mean, 0.f) + 1e-5f), tg));
    }
    if (wp == 1 && lane < 16) {
      const uint32_t a = scr + lane * 4;
      st32_rlx(&G->cskv[128 * nkv + 16 * m256 + lane], tagw((ldsf(a) + ldsf(a + 64)) + (ldsf(a + 128) + ldsf(a + 192)), tg));
    }
    __syncwarp();
    bar_arrive(NB_PUB, 192);
    TSW(23);
    const uint4 wv = ld128_keep(P.wr + t * 8);
    #pragma unroll 1
    for (int i = 0; i < 2; i++) {
      const bf16* gq = P.wqkv + (size_t)(256 * (c >> 5) + 128 * i + (t >> 2)) * (3 * DM) + 32 * (c & 31) + 8 * (t & 3);
      const uint4 u0 = ld128_keep(gq), u1 = ld128_keep(gq + 32 * 3 * DM), u2 = ld128_keep(gq + 64 * 3 * DM), u3 = ld128_keep(gq + 96 * 3 * DM);
      addc(u0, cs); addc(u1, cs); addc(u2, cs); addc(u3, cs);
    }
    float sw = (bf_lo(wv.x) + bf_hi(wv.x)) + (bf_lo(wv.y) + bf_hi(wv.y)) + (bf_lo(wv.z) + bf_hi(wv.z)) + (bf_lo(wv.w) + bf_hi(wv.w));
    #pragma unroll
    for (int o = 16; o; o >>= 1) sw += __shfl_xor_sync(~0u, sw, o);
    if (lane == 0) stsf(sb + OFF_SUMWR + wp * 4, sw);
    if ((t >> 4) == j) {
      const uint32_t a = sb + OFF_WR + (t & 15) * 32;
      sts128(a, wv.x << 16, wv.x & 0xffff0000u, wv.y << 16, wv.y & 0xffff0000u);
      sts128(a + 16, wv.z << 16, wv.z & 0xffff0000u, wv.w << 16, wv.w & 0xffff0000u);
    }
    v = reduce8(cs, lane);
    bar_sync(NB_WG2, 128);
    stsf(scr + (wp * 32 + 8 * (lane & 3) + (lane >> 2)) * 4, v);
    bar_sync(NB_WG2, 128);
    if (wp == 0) {
      const uint32_t a = scr + lane * 4;
      st32_rlx(&G->csq[(c >> 5) * DM + 32 * (c & 31) + lane], tagw((ldsf(a) + ldsf(a + 128)) + (ldsf(a + 256) + ldsf(a + 384)), tg));
    }
  }

  uint32_t xr[32];
  {
    const bool isq = wg == 2;
    float acc[2][64];
    {
      const uint32_t emptyb = mapa(sb + (isq ? B_EMPTY5 : B_EMPTYKV), t & 1);
      if (!isq) {
        mbar_wait(sb + B_FULLKV, 0);
        if (wg == 0) { TSW(2); }
        #pragma unroll 1
        for (int kb = 0; kb < 16; kb++) {
          if (wg == 0) { TK(kb); }
          const uint32_t da = dlo(SB0, 16) + wg * 1024 + (kb & 3) * (KV_STAGE >> 4), db = dlo(SB0 + 32768, 8192) + (kb & 3) * (KV_STAGE >> 4);
          wg_fence();
          #pragma unroll
          for (int k = 0; k < 4; k++) {
            wgmma_ss_n128<0, 1, H128, H128>(acc[0], da + 2 * k, db + 128 * k, k > 0 || kb != 0);
            wgmma_ss_n128<0, 1, H128, H128>(acc[1], da + 512 + 2 * k, db + 128 * k, k > 0 || kb != 0);
          }
          wg_commit();
          wg_wait<1>();
          if (kb > 0 && t < 2) mbar_arrive_remote(emptyb + 8 * ((kb - 1) & 3), kb > 10 ? 3 : 1);
          if (kb < 15) mbar_wait(sb + B_FULLKV + 8 * ((kb + 1) & 3), ((kb + 1) >> 2) & 1);
          if (kb == 15 - LAG && wg == 1) bar_sync(NB_WG01, 256);
        }
        bar_arrive(wg ? NB_QGO : NB_WG01, 256);
      } else {
        uint32_t so = 0, po = 0, par = 0;
        mbar_wait(sb + B_FULL5, 0);
        bar_sync(NB_QGO, 256);
        TSW(11);
        #pragma unroll 1
        for (int kb = 0; kb < 16; kb++) {
          TK(16 + kb);
          const uint32_t da = dlo(SB0, 16) + so * 256, db = dlo(SB0 + 16384, 8192) + so * 256;
          #pragma unroll
          for (int k = 0; k < 4; k++) {
            wg_fence();
            wgmma_ss_n128<0, 1, H128, H128>(acc[0], da + 2 * k, db + 128 * k, k > 0 || kb != 0);
            wgmma_ss_n128<0, 1, H128, H128>(acc[1], da + 512 + 2 * k, db + 128 * k, k > 0 || kb != 0);
            wg_commit();
            if (k == 1 && kb > 0 && t < 2) mbar_arrive_remote(emptyb + po, 2);
            if (k == 3) {
              po = so; so += 8;
              if (so == 40) { so = 0; par ^= 1; }
              if (kb < 15) mbar_wait(sb + B_FULL5 + so, par);
            }
            if ((QW >> k) & 1) wg_wait<2>(); else wg_wait<1>();
          }
        }
        mbar_wait(sb + B_AUXQ, 0);
      }
      mbar_wait(sb + B_AUX, 0);
      const uint32_t xa = dlo(SB0, 0) + (isq ? OFF_AXQ >> 4 : (OFF_AXK >> 4) + wg * 128), xb = dlo(SB0, 0) + (isq ? OFF_BXQ >> 4 : OFF_BXK >> 4);
      wg_fence();
      wgmma_sa_n128<0, 1, H0, H0>(acc[0], xa, xb);
      wgmma_sa_n128<0, 1, H0, H0>(acc[1], xa + 64, xb);
      wg_commit();
      if (isq) mbar_wait(sb + B_RC, 0);
      wg_wait<0>();
      if (t < 2) mbar_arrive_remote(emptyb + (isq ? 0 : 24), isq ? 2 : 3);
      if (wg != 1) { TSW(wg ? 8 : 3); }
      fence_regs(acc[0]); fence_regs(acc[1]);
    }
    if (isq) {
      #pragma unroll
      for (int i = 0; i < 4; i++) {
        const uint32_t ta = sb + (i < 2 ? (1 + rank) * R5 : OFF_X) + sa + (i & 1) * 8192;
        if (i == 1) mbar_wait(sb + B_RC + 8, 0);
        #pragma unroll
        for (int k = 0; k < 4; k++) {
          const float* a = &acc[i & 1][16 * (i >> 1) + 32 * (k >> 1) + 8 * (k & 1)];
          stsm4(ta ^ (k << 5), pack_bf16(a[0], a[1]), pack_bf16(a[2], a[3]), pack_bf16(a[4], a[5]), pack_bf16(a[6], a[7]));
        }
        if (i < 2) { fence_async_smem(); bar_arrive(NB_Q0 + i, 256); }
      }
      TSW(26);
    } else {
      const uint32_t stg = sb + OFF_X + (1 - wg) * 24576;
      const uint32_t va = stg + 16384 + (16 * wp + (lane & 15)) * 64 + (((lane >> 4) ^ ((lane >> 1) & 3)) << 4);
      const uint32_t ra = sb + OFF_RS256 + (128 * wg + 16 * wp + g) * 4;
      const float rs[4] = {ldsf(ra), ldsf(ra + 32), ldsf(ra + 256), ldsf(ra + 288)};
      float p[2][16];
      uint32_t vf[16], kf[2][16];
      auto project = [&](const uint32_t (&f)[16], uint32_t db) {
        wg_fence();
        #pragma unroll
        for (int i = 0; i < 2; i++) {
          wgmma_rs_n32<1, H64>(p[i], f[8*i], f[8*i+1], f[8*i+2], f[8*i+3], db, 0);
          wgmma_ra_n32<1, H64>(p[i], f[8*i+4], f[8*i+5], f[8*i+6], f[8*i+7], db + 64);
        }
        wg_commit();
      };
      auto fold = [&](uint32_t (&f)[16], int col, float sc) {
        #pragma unroll
        for (int i = 0; i < 16; i++) {
          const float r = rs[2 * (i >> 3) + (i & 1)] * sc;
          f[i] = pack_bf16(acc[i >> 3][col + 2 * (i & 7)] * r, acc[i >> 3][col + 2 * (i & 7) + 1] * r);
          asm volatile("" : "+r"(f[i]));
        }
      };
      auto put_v = [&](const uint32_t (&f)[16]) {
        #pragma unroll
        for (int k = 0; k < 4; k++) stsm4((va ^ ((k & 1) << 5)) + (k >> 1) * 4096, f[4*k], f[4*k+1], f[4*k+2], f[4*k+3]);
      };
      fold(vf, 48, 1.f);
      mbar_wait(sb + B_W, 0);
      fold(kf[0], 0, LOG2E);
      #pragma unroll
      for (int i = 0; i < 32; i++) p[i >> 4][i & 15] = acc[i >> 4][i & 15];
      project(kf[0], dlo(SB0 + OFF_WPHIK, 16));
      mbar_wait(sb + B_W, 0);
      {
        uint32_t v0[16];
        fold(kf[1], 16, LOG2E);
        fold(v0, 32, 1.f);
        if (wg == 1) bar_sync(NB_DN, 256);
        put_v(v0);
      }
      wg_wait<0>();
      fence_regs(p[0]); fence_regs(p[1]);
      if (wg == 1) bar_arrive(NB_WG01, 256);
      #pragma unroll 1
      for (int h = 0; h < 2; h++) {
        uint32_t ph[4][8];
        float rsum[4][4];
        dual_exp2(p, ph);
        wg_fence();
        row_sums(rsum, ph, dlo(SB0 + OFF_ONES, 128));
        wg_commit();
        if (wg == 0 && h == 0) { bar_arrive(NB_DN, 256); bar_sync(NB_WG01, 256); }
        if (h == 1) {
          if (wg == 1) bar_sync(NB_DN, 256);
          put_v(vf);
        }
        wg_wait<0>();
        #pragma unroll
        for (int i = 0; i < 4; i++) fence_regs(rsum[i]);
        if (__builtin_expect(__any_sync(~0u, !((rsum[0][0] + rsum[0][2]) + (rsum[1][0] + rsum[1][2]) + (rsum[2][0] + rsum[2][2]) + (rsum[3][0] + rsum[3][2]) < EXP_LIM)), 0)) {
          dual_exp2_shifted(p, ph);
          #pragma unroll
          for (int i = 0; i < 8; i++) {
            const uint32_t* f = &ph[i >> 1][i & 1];
            float a = (bf_lo(f[0]) + bf_hi(f[0])) + (bf_lo(f[2]) + bf_hi(f[2])) + (bf_lo(f[4]) + bf_hi(f[4])) + (bf_lo(f[6]) + bf_hi(f[6]));
            a += __shfl_xor_sync(~0u, a, 1);
            rsum[i >> 1][2 * (i & 1)] = a + __shfl_xor_sync(~0u, a, 2);
          }
        }
        if (h == 0) project(kf[1], dlo(SB0 + OFF_WPHIK1, 16));
        normalize(ph, rsum);
        #pragma unroll
        for (int i = 0; i < 8; i++) {
          const uint32_t* f = &ph[i >> 1][4 * (i & 1)];
          stsm4(((stg + sa) ^ ((i & 3) << 5)) + (i >> 2) * 8192, f[0], f[1], f[2], f[3]);
        }
        fence_async_smem();
        TK(50 + 8 * wg + 4 * h);
        if (wg == h) {
          float kv[20];
          #pragma unroll
          for (int w = 0; w < 2; w++) {
            const uint32_t da = dlo(SB0 + OFF_X, 16) + (h ^ w ^ 1) * 1536, db = dlo(SB0 + OFF_X + 16384, OFF_ONES - OFF_X - 16384) - (h ^ w ^ 1) * (1536 * 65535);
            if (w) bar_sync(NB_ST, 256); else bar_sync(NB_L0 + h, 128);
            wg_fence();
            #pragma unroll
            for (int k = 0; k < 8; k++) {
              if (k == 0 && w == 0) wgmma_sz_n40<1, 1, H128, H64>(kv, da, db);
              else wgmma_sa_n40<1, 1, H128, H64>(kv, da + k * 128, db - k * (64 * 65535));
            }
            wg_commit();
          }
          float4* dst = &G->kvacc[(ha + 2 * h) * KVP + t];
          wg_wait<0>();
          fence_regs(kv);
          TK(51 + 8 * wg + 4 * h);
          if (h == 0) bar_arrive(NB_DN, 256); else if (t == 0) mbar_arrive(sb + B_KD);
          kv[17] = kv[18];
          #pragma unroll
          for (int i = 0; i < 6; i++) red_add_f32x4(dst + 128 * i, kv[3*i], kv[3*i+1], kv[3*i+2], 1.f);
          TSW(29 + h);
        } else bar_arrive(NB_ST, 256);
        wg_wait<0>();
        fence_regs(p[0]); fence_regs(p[1]);
      }
    }
    #pragma unroll 1
    for (int e = wg; e < wg + 1 + (wg >> 1); e++) {
      const uint4* src = reinterpret_cast<const uint4*>(&G->kvacc[(4 * j + e) * KVP + t]);
      uint4 v[6];
      uint32_t it = 0, bad;
      TK(48 + 4 * e);
      do {
        bad = 0;
        #pragma unroll
        for (int i = 0; i < 6; i++) { v[i] = ld128_rlx(src + 128 * i); bad |= v[i].w ^ 0x41000000u; }
      } while (__any_sync(~0u, bad != 0) && ++it < POLL_LIMIT);
      TK(49 + 4 * e);
      mbar_wait(sb + B_KD, 0);
      float f[18];
      #pragma unroll
      for (int i = 0; i < 6; i++) { f[3*i] = __uint_as_float(v[i].x); f[3*i+1] = __uint_as_float(v[i].y); f[3*i+2] = __uint_as_float(v[i].z); }
      const uint32_t ka = sb + OFF_KVZ + e * 5120 + wp * 1280 + lane * 16;
      stsm4(ka, pack_bf16(f[0], f[1]), pack_bf16(f[2], f[3]), pack_bf16(f[4], f[5]), pack_bf16(f[6], f[7]));
      stsm4(ka + 512, pack_bf16(f[8], f[9]), pack_bf16(f[10], f[11]), pack_bf16(f[12], f[13]), pack_bf16(f[14], f[15]));
      stsm2(ka + 1024, pack_bf16(f[16], 1.f), pack_bf16(f[17], 1.f));
    }
    if (!isq) {
      mbar_wait(sb + B_R, 0);
      #pragma unroll
      for (int k = 0; k < 8; k++) ldsm4(((sb + (1 + rank) * R5 + wg * 8192 + sa) ^ ((k & 3) << 5)) + (k >> 2) * 2 * R5, xr[4*k], xr[4*k+1], xr[4*k+2], xr[4*k+3]);
      fence_async_smem();
      __syncwarp();
      if (lane == 0) { mbar_arrive(sb + B_RC + 8 * wg); mbar_arrive_at(sb + B_RX, wg, 1); }
      if (wg == 1) bar_arrive(NB_DN, 256);
    } else {
      fence_async_smem();
      #pragma unroll
      for (int i = 0; i < 32; i++) asm volatile("mov.b32 %0, 0;" : "=r"(xr[i]));
    }
    TSW(wg == 0 ? 5 : wg == 1 ? 25 : 6);
    #pragma unroll 1
    for (int e = wg; e < wg + 1 + (wg >> 1); e++) {
      const int half = e >> 1, hh = e & 1, turn = e;
      const uint32_t ao = (half ? OFF_X : (1 + rank) * R5) + hh * 8192, at = sb + ao + sa;
      float p[2][16];
      #pragma unroll
      for (int i = 0; i < 32; i++) asm volatile("mov.b32 %0, 0;" : "=f"(p[i >> 4][i & 15]));
      const float cc[2] = {ldsf(sb + OFF_RSQ + (64 * hh + 16 * wp + g) * 4) * LOG2E, ldsf(sb + OFF_RSQ + (64 * hh + 16 * wp + g + 8) * 4) * LOG2E};
      float m[2][4] = {{0.f, 0.f, 0.f, 0.f}, {0.f, 0.f, 0.f, 0.f}};
      uint32_t ph[2][8];
      auto exps = [&](int h) {
        #pragma unroll
        for (int k = 0; k < 8; k++) {
          const float c = cc[k & 1], mp = m[h][k & 1], mm = m[h][2 + (k & 1)];
          ph[0][k] = pack_bf16(ex2(fmaf(p[h][2*k], c, mp)), ex2(fmaf(p[h][2*k+1], c, mp)));
          ph[1][k] = pack_bf16(ex2(fmaf(p[h][2*k], -c, mm)), ex2(fmaf(p[h][2*k+1], -c, mm)));
        }
      };
      uint32_t shifted = 0;
      asm volatile("" : "+r"(shifted));
      #pragma unroll 1
      for (;;) {
        if (shifted) { row_extremes(p[0], cc, m[0]); row_extremes(p[1], cc, m[1]); }
        uint32_t first = shifted ^ 1;
        asm volatile("" : "+r"(first));
        if (first) {
          bar_sync(NB_Q0 + wg, isq ? 128 : 256);
          const uint32_t da = dlo(SB0, 16) + (ao >> 4), db = dlo(SB0 + OFF_WPHIQ, 16) + half * 256;
          wg_fence();
          #pragma unroll
          for (int h = 0; h < 2; h++) {
            wgmma_ss_n32<0, 1, H128, H64>(p[h], da + 4 * h, db + 128 * h, 0);
            wgmma_sa_n32<0, 1, H128, H64>(p[h], da + 4 * h + 2, db + 128 * h + 64);
          }
          wg_commit();
          if (e == 1 || e == 2) bar_sync(NB_TOK + e - 1, 256);
          wg_wait<0>();
        }
        TK(64 + 4 * turn);
        fence_regs(p[0]); fence_regs(p[1]);
        exps(0);
        float s2[4] = {0.f, 0.f, 0.f, 0.f};
        #pragma unroll
        for (int i = 0; i < 32; i++) s2[((i >> 1) & 1) + 2 * (i >> 4)] = fmaf(p[i >> 4][i & 15], p[i >> 4][i & 15], s2[((i >> 1) & 1) + 2 * (i >> 4)]);
        const float l0 = cc[0] * cc[0], l1 = cc[1] * cc[1];
        if (!__any_sync(~0u, !shifted & !((s2[0] * l0 < ARG_LIM2) & (s2[1] * l1 < ARG_LIM2) & (s2[2] * l0 < ARG_LIM2) & (s2[3] * l1 < ARG_LIM2)))) break;
        shifted = 1;
      }
      const uint32_t db = dlo(SB0 + OFF_KVZ, 128) + half * 640;
      float ac[4][20];
      auto numer = [&](int h, const uint32_t (&f)[2][8]) {
        wg_fence();
        #pragma unroll
        for (int i = 0; i < 2; i++) {
          wgmma_rz_n40<1, dhi(256, 0)>(ac[2*h+i], f[i][0], f[i][1], f[i][2], f[i][3], db + (2*h+i) * 160);
          wgmma_ra_n40<1, dhi(256, 0)>(ac[2*h+i], f[i][4], f[i][5], f[i][6], f[i][7], db + ((2*h+i) * 160 + 80));
        }
        wg_commit();
      };
      auto finish = [&](int h) {
        const float* ap = ac[2 * h]; const float* am = ac[2 * h + 1];
        const float ip0 = rcp(ap[17]), im0 = rcp(am[17]), ip1 = rcp(ap[19]), im1 = rcp(am[19]);
        const float d0 = rcp(fmaf(ap[16], ip0, fmaf(am[16], im0, 1e-6f))), d1 = rcp(fmaf(ap[18], ip1, fmaf(am[18], im1, 1e-6f)));
        const float a0 = ip0 * d0, b0 = im0 * d0, a1 = ip1 * d1, b1 = im1 * d1;
        #pragma unroll
        for (int k = 0; k < 2; k++)
          stsm4(at ^ ((2 * h + k) << 5),
                pack_bf16(fmaf(ap[8*k], a0, am[8*k] * b0),     fmaf(ap[8*k+1], a0, am[8*k+1] * b0)),
                pack_bf16(fmaf(ap[8*k+2], a1, am[8*k+2] * b1), fmaf(ap[8*k+3], a1, am[8*k+3] * b1)),
                pack_bf16(fmaf(ap[8*k+4], a0, am[8*k+4] * b0), fmaf(ap[8*k+5], a0, am[8*k+5] * b0)),
                pack_bf16(fmaf(ap[8*k+6], a1, am[8*k+6] * b1), fmaf(ap[8*k+7], a1, am[8*k+7] * b1)));
      };
      numer(0, ph);
      exps(1);
      if (wg == 0) bar_sync(NB_DN, 256);
      numer(1, ph);
      if (turn < 2) bar_arrive(NB_TOK + turn, 256);
      wg_wait<1>();
      TK(65 + 4 * turn);
      fence_regs(ac[0]); fence_regs(ac[1]);
      finish(0);
      wg_wait<0>();
      fence_regs(ac[2]); fence_regs(ac[3]);
      finish(1);
      TK(66 + 4 * turn);
      fence_async_smem();
      __syncwarp();
      if (lane == 0) mbar_arrive(sb + B_UO + 8 * e);
      TK(67 + 4 * turn);
    }
    if (isq) cluster_arrive();
  }

  {
  int lane;
  asm volatile("mov.u32 %0, %%laneid;" : "=r"(lane));
  const int g = lane >> 2, q = lane & 3;
  if (wg < 2) {
    float h[64];
    {
      if (wg == 0) { TK(83); }
      #pragma unroll
      for (int i = 0; i < 32; i++) { h[2*i] = bf_lo(xr[i]); h[2*i+1] = bf_hi(xr[i]); }
      fence_regs(h);
      TK(80 + wg);
      const uint64_t seq = rank ? 0x1043210432104312ull : 0x1043210432104321ull;
      const uint32_t emptyb = mapa(sb + B_EMPTY5, t & 1);
      uint32_t s = 1 + rank, ps = 0;
      mbar_wait2(sb + B_FULL5 + 8 * s, 1, sb + B_UO + 8 * wg, 0);
      if (wg == 0) { TSW(14); }
      #pragma unroll 1
      for (int i = 0; i < 16; i++) {
        if (wg == 1 && i < 4) { TK(84 + i); }
        if (wg == 0) { TK(32 + i); }
        const uint32_t da = dlo(SB0, 16) + s * 2048 + wg * 512, db = dlo(SB0 + 16384, 8192) + s * 2048;
        wg_fence();
        #pragma unroll
        for (int k = 0; k < 4; k++) wgmma_sa_n128<0, 1, H128, H128>(h, da + k * 2, db + k * 128);
        wg_commit();
        const uint32_t ns = (uint32_t)(seq >> (4 * i + 4)) & 15;
        wg_wait<1>();
        if (i > 0 && t < 2) mbar_arrive_remote(emptyb + 8 * ps, 1);
        if (i < 15) mbar_wait2(sb + B_FULL5 + 8 * ns, (0x1f07 >> i) & 1, sb + B_FULLA + 16 * ns + 8 * wg, (0x41f0 >> i) & 1);
        ps = s; s = ns;
      }
    }
    cluster_arrive();
    float2 wr[16];
    #pragma unroll
    for (int i = 0; i < 16; i++) wr[i] = lds64f(sb + OFF_WR + 32 * i + 8 * q);
    const int r0 = 64 * wg + 16 * wp + g;
    float sum0, sum1, dot0, dot1, sq0, sq1;
    uint32_t redo = 0;
    asm volatile("" : "+r"(redo));
    #pragma unroll 1
    for (;;) {
    if (redo) {
      wg_wait<0>();
      const int r = r0;
      #pragma unroll 1
      for (int n = 0; n < 16; n++) {
        const uint32_t* xp = reinterpret_cast<const uint32_t*>(P.x + (size_t)(128 * m128 + r) * DM + 128 * j + 8 * n) + q;
        const uint32_t x0 = xp[0], x1 = xp[4 * DM];
        float d0 = bf_lo(x0), d1 = bf_hi(x0), d2 = bf_lo(x1), d3 = bf_hi(x1);
        #pragma unroll 1
        for (int ks = 0; ks < 64; ks++) {
          const int kb = ks >> 2, kk = 16 * (ks & 3);
          const bf16* op = G->o + (m128 * 16 + kb) * 8192 + r * 64 + 2 * q;
          const int o0 = ((kk >> 3) ^ g) << 3;
          const uint16_t* w = reinterpret_cast<const uint16_t*>(P.wo_p) + (size_t)(128 * (kb >> 1) + 32 * (kb & 1) + (kk & 31) + 2 * (kk & 32) + 2 * q) * DM + 128 * j + 8 * n + g;
          const uint32_t b0 = w[0] | (w[DM] << 16), b1 = w[8 * DM] | (w[9 * DM] << 16);
          uint32_t a0, a1, a2, a3, it = 0;
          do { a0 = ld32_rlx(op + o0); a1 = ld32_rlx(op + 512 + o0); a2 = ld32_rlx(op + (o0 ^ 8)); a3 = ld32_rlx(op + 512 + (o0 ^ 8)); }
          while (max(max(a0, a1), max(a2, a3)) == ~0u && ++it < POLL_LIMIT);
          __syncwarp();
          mma16816(d0, d1, d2, d3, a0, a1, a2, a3, b0, b1);
        }
        #pragma unroll
        for (int i = 0; i < 60; i++) h[i] = h[i + 4];
        h[60] = d0; h[61] = d1; h[62] = d2; h[63] = d3;
      }
    }
    wg_wait<0>();
    fence_regs(h);
    if (wg == 0) { TSW(16); }
    sum0 = 0.f, sum1 = 0.f, dot0 = 0.f, dot1 = 0.f, sq0 = 0.f, sq1 = 0.f;
    #pragma unroll
    for (int i = 0; i < 16; i++) {
      sum0 += h[4*i] + h[4*i+1]; sum1 += h[4*i+2] + h[4*i+3];
      sq0 = fmaf(h[4*i], h[4*i], fmaf(h[4*i+1], h[4*i+1], sq0)); sq1 = fmaf(h[4*i+2], h[4*i+2], fmaf(h[4*i+3], h[4*i+3], sq1));
      dot0 = fmaf(h[4*i], wr[i].x, fmaf(h[4*i+1], wr[i].y, dot0)); dot1 = fmaf(h[4*i+2], wr[i].x, fmaf(h[4*i+3], wr[i].y, dot1));
    }
    if (!__any_sync(~0u, !redo & (h[0] != h[0] | h[2] != h[2]))) break;
    redo = 1;
    }
    float4* const rs = &G->rstat[128 * m128 + r0];
    {
      const bool up = q & 2;
      float a = up ? sum1 : sum0, b = up ? sq1 : sq0, d = up ? dot1 : dot0;
      a += __shfl_xor_sync(~0u, up ? sum0 : sum1, 2); b += __shfl_xor_sync(~0u, up ? sq0 : sq1, 2); d += __shfl_xor_sync(~0u, up ? dot0 : dot1, 2);
      a += __shfl_xor_sync(~0u, a, 1); b += __shfl_xor_sync(~0u, b, 1); d += __shfl_xor_sync(~0u, d, 1);
      if ((q & 1) == 0) red_add_f32x4(rs + 4 * q, a, b, d, 1.f);
    }
    bar_arrive(NB_G2E, 384);
    if (wg == 0) { TSW(24); }
    float rstd[2], bm[2];
    uint32_t best;
    {
      const float2 swa = lds64f(sb + OFF_SUMWR), swb = lds64f(sb + OFF_SUMWR + 8);
      const float sw = (swa.x + swa.y) + (swb.x + swb.y);
      uint4 a[2]; uint32_t it = 0, key[2];
      do { a[0] = ld128_rlx(rs); a[1] = ld128_rlx(rs + 8); } while (__any_sync(~0u, (a[0].w & a[1].w) != 0x41000000u) && ++it < POLL_LIMIT);
      #pragma unroll
      for (int i = 0; i < 2; i++) {
        const float mean = __uint_as_float(a[i].x) * (1.f / DM);
        rstd[i] = rsqrtf(fmaxf(__uint_as_float(a[i].y) * (1.f / DM) - mean * mean, 0.f) + 1e-5f);
        bm[i] = -mean * rstd[i];
        const uint32_t rr = __float_as_uint(fmaf(__uint_as_float(a[i].z), rstd[i], sw * bm[i]));
        key[i] = ((rr ^ ((uint32_t)((int32_t)rr >> 31) | 0x80000000u)) & ~2047u) | (2047 - 128 * m128 - r0 - 8 * i);
      }
      asm volatile("redux.sync.max.u32 %0, %1, 0xffffffff;" : "=r"(best) : "r"(max(key[0], key[1])));
    }
    if (wg == 0) { TSW(17); }
    const int slot = m128 * 8 + warp, win = ~best & 15;
    if (lane < 4) st32_rlx(&G->key[(4 * j + lane) * 128 + slot], best);
    if ((win & 7) == g) {
      const bool up = win & 8;
      const float ra = up ? rstd[1] : rstd[0], rb = up ? bm[1] : bm[0];
      uint32_t x[16];
      #pragma unroll
      for (int i = 0; i < 16; i++) x[i] = pack_bf16(fmaf(up ? h[4*i+2] : h[4*i], ra, rb), fmaf(up ? h[4*i+3] : h[4*i+1], ra, rb));
      #pragma unroll
      for (int i = 0; i < 4; i++) st128_rlx(&G->cand[slot * DM + 64 * j + 16 * i + 4 * q], x[4*i], x[4*i+1], x[4*i+2], x[4*i+3]);
    }
    __syncwarp();
    if (wg == 0) { TSW(27); }
    {
      bar_sync(NB_WG01, 256);
      const float a0 = 1.f + rstd[0], b0 = bm[0], a1 = 1.f + rstd[1], b1 = bm[1];
      #pragma unroll
      for (int k = 0; k < 8; k++)
        stsm4(((sb + R5 + wg * 8192 + sa) ^ ((k & 3) << 5)) + (k >> 2) * 16384,
              pack_bf16(fmaf(h[8*k], a0, b0), fmaf(h[8*k+1], a0, b0)),     pack_bf16(fmaf(h[8*k+2], a1, b1), fmaf(h[8*k+3], a1, b1)),
              pack_bf16(fmaf(h[8*k+4], a0, b0), fmaf(h[8*k+5], a0, b0)),   pack_bf16(fmaf(h[8*k+6], a1, b1), fmaf(h[8*k+7], a1, b1)));
      sts32(sb + OFF_EXC + 4 * warp, 16 * warp + win);
      bar_arrive(NB_OUT + wg, 160);
      __syncwarp();
      if (lane < 16) {
        const uint4 v = lds128(sb + R5 + (lane >> 3) * 16384 + (16 * warp + win) * 128 + (((lane & 7) ^ (win & 7)) << 4));
        st128_rlx(&G->cand[slot * DM + 512 + 64 * j + 4 * lane], v.x, v.y, v.z, v.w);
      }
    }
    if (wg == 0) { TSW(28); }
    {
      uint32_t wa[8][4][4];
      const uint32_t wb = sb + 16384 * ((0x7654cadb >> (4 * warp)) & 15) + ((lane & 7) + ((lane >> 4) << 3)) * 64 + ((((lane >> 3) & 1) ^ ((lane >> 1) & 3)) << 4);
      auto getw = [&](int ks) {
        #pragma unroll
        for (int m = 0; m < 4; m++) ldsm4t((wb ^ ((m & 1) << 5)) + (m >> 1) * 8192 + ks * 1024, wa[ks][m][0], wa[ks][m][1], wa[ks][m][2], wa[ks][m][3]);
      };
      if (f < NFFN_L) mbar_wait(sb + B_F + 8 * warp, 0);
      #pragma unroll
      for (int ks = 0; ks < 6; ks++) getw(ks);
      if (wg == 0) { TSW(15); }
      bar_sync(NB_XS, 448);
      if (wg == 0) { TSW(19); }
      uint4 xs[4];
      #pragma unroll
      for (int i = 0; i < 4; i++) xs[i] = lds128(sb + OFF_XSEL + 256 * warp + 64 * i + 16 * q);
      float d[4][4];
      #pragma unroll
      for (int ks = 0; ks < 8; ks++) {
        if (ks == 1) getw(6);
        if (ks == 2) getw(7);
        #pragma unroll
        for (int m = 0; m < 4; m++) {
          if (ks == 0) { d[m][0] = 0.f; d[m][1] = 0.f; d[m][2] = 0.f; d[m][3] = 0.f; }
          mma16816(d[m][0], d[m][1], d[m][2], d[m][3], wa[ks][m][0], wa[ks][m][1], wa[ks][m][2], wa[ks][m][3],
                   (ks & 1) ? xs[ks >> 1].z : xs[ks >> 1].x, (ks & 1) ? xs[ks >> 1].w : xs[ks >> 1].y);
        }
      }
      if (q == 0) {
        #pragma unroll
        for (int m = 0; m < 8; m++) stsf(sb + OFF_GU + (8 * m + g) * 48 + 4 * warp, d[m >> 1][2 * (m & 1)]);
      }
      bar_arrive(NB_ACT, 384);
    }
    {
      float y0 = 0.f, y1 = 0.f, y2 = 0.f, y3 = 0.f;
      const uint32_t ky = __float_as_uint(ldsf(sb + OFF_KEY));
      const int kidx = 2047 - (ky & 2047);
      const float kr = __uint_as_float((ky & ~2047u) ^ ((ky >> 31) ? 0x80000000u : 0xfffff800u));
      const int col = 128 * (c >> 4) + 32 * (c & 1) + 16 * ((tid >> 2) & 1) + 64 * ((tid >> 1) & 1) + 8 * (tid & 1) + ((c >> 1) & 7);
      uint32_t it = 0, base = 0;
      if (tid < 8) {
        do { base = ld32_rlx(&G->cand[(kidx >> 4) * DM + 512 + (col >> 1)]); } while (base == ~0u && ++it < POLL_LIMIT);
      }
      if (tid < 2 * NFFN) {
        uint4 v;
        do { v = ld128_rlx(&G->ypart[(tid >> 1) * DM + 8 * c + 4 * (tid & 1)]); } while (v.w == ~0u && ++it < POLL_LIMIT);
        y0 = __uint_as_float(v.x); y1 = __uint_as_float(v.y); y2 = __uint_as_float(v.z); y3 = __uint_as_float(v.w);
      }
      __syncwarp();
      const bool b4 = lane & 16, b3 = lane & 8;
      const float u0 = (b4 ? y1 : y0) + __shfl_xor_sync(~0u, b4 ? y0 : y1, 16), u1 = (b4 ? y3 : y2) + __shfl_xor_sync(~0u, b4 ? y2 : y3, 16);
      float ys = (b3 ? u1 : u0) + __shfl_xor_sync(~0u, b3 ? u0 : u1, 8);
      ys += __shfl_xor_sync(~0u, ys, 4); ys += __shfl_xor_sync(~0u, ys, 2);
      if (!(lane & 6)) stsf(sb + OFF_ACT + ((4 * (lane & 1) + ((lane >> 3) & 1) * 2 + (lane >> 4)) * 8 + warp) * 4, ys);
      const float sg = __fdividef(1.f, 1.f + __expf(-kr));
      bar_sync(NB_WG01, 256);
      if (tid < 8) {
        const uint4 v0 = lds128(sb + OFF_ACT + tid * 32), v1 = lds128(sb + OFF_ACT + tid * 32 + 16);
        const float t8 = ((__uint_as_float(v0.x) + __uint_as_float(v0.y)) + (__uint_as_float(v0.z) + __uint_as_float(v0.w))) +
                         ((__uint_as_float(v1.x) + __uint_as_float(v1.y)) + __uint_as_float(v1.z));
        P.out_p[(size_t)kidx * DM + col] = __float2bfloat16(fmaf(t8, sg, (col & 1) ? bf_hi(base) : bf_lo(base)));
      }
      if (c == 0 && tid == 0) st32_rlx(&G->epoch, __float_as_uint(ldsf(sb + OFF_EP)));
      if (wg == 0) { TSW(22); TDUMP(); }
    }
  }
  if (wg == 2) {
    uint32_t wf[16][2][4];
    {
      const uint32_t wb = sb + 16384 * ((0xcadc >> (4 * wp)) & 15) + ((lane & 7) + ((lane >> 4) << 3)) * 128 + ((((lane >> 3) & 1) ^ (lane & 7)) << 4);
      if (f < NFFN_L) mbar_wait(sb + B_WD + 8 * wp, 0);
      #pragma unroll
      for (int i = 0; i < 32; i++) ldsm4t((wb ^ (((i >> 1) & 3) << 5)) + (i >> 3) * 4096 + (i & 1) * 2048, wf[i >> 1][i & 1][0], wf[i >> 1][i & 1][1], wf[i >> 1][i & 1][2], wf[i >> 1][i & 1][3]);
      fence_async_smem();
      __syncwarp();
      if (lane == 0) mbar_arrive(sb + B_WC + 8 * wp);
    }
    uint32_t* const dst = &G->ypart[f * DM + 256 * wp + 4 * lane];
    bar_sync(NB_G2E, 384);
    #pragma unroll 1
    for (int pass = 0; pass < 2; pass++) {
    if (pass) {
      uint32_t cur = 0;
      uint4 v;
      for (uint32_t it = 0; it < POLL_LIMIT; it++) {
        const uint4 kx = ld128_rlx(&G->key[(c & 31) * 128 + 4 * lane]);
        v = ld128_rlx(&G->cand[((~cur >> 4) & 127) * DM + 4 * t]);
        uint32_t best;
        asm volatile("redux.sync.max.u32 %0, %1, 0xffffffff;" : "=r"(best) : "r"(max(max(kx.x, kx.y), max(kx.z, kx.w))));
        if (!__any_sync(~0u, min(min(kx.x, kx.y), min(kx.z, kx.w)) == 0 || v.w == ~0u) && best == cur) break;
        cur = best;
      }
      sts128(sb + OFF_XSEL + 16 * t, v.x, v.y, v.z, v.w);
      sts32(sb + OFF_KEY, cur);
      bar_arrive(NB_XS, 448);
      TSW(18);
      bar_sync(NB_ACT, 384);
    }
    float gu[2];
    #pragma unroll
    for (int i = 0; i < 2; i++) {
      const uint4 v0 = lds128(sb + OFF_GU + (32 * i + lane) * 48), v1 = lds128(sb + OFF_GU + (32 * i + lane) * 48 + 16);
      gu[i] = ((__uint_as_float(v0.x) + __uint_as_float(v0.y)) + (__uint_as_float(v0.z) + __uint_as_float(v0.w))) +
              ((__uint_as_float(v1.x) + __uint_as_float(v1.y)) + (__uint_as_float(v1.z) + __uint_as_float(v1.w)));
    }
    const float act = __fdividef(gu[0], 1.f + __expf(-gu[0])) * gu[1];
    const uint32_t ap = pack_bf16(act, __shfl_down_sync(~0u, act, 1));
    uint32_t bf[4];
    #pragma unroll
    for (int i = 0; i < 4; i++) bf[i] = __shfl_sync(~0u, ap, 2 * q + 8 * i);
    if (pass) { TSW(20); }
    #pragma unroll
    for (int n2 = 0; n2 < 2; n2++) {
      float y[4];
      #pragma unroll
      for (int n = 0; n < 2; n++) {
        float d[4][4];
        #pragma unroll
        for (int k = 0; k < 2; k++)
          #pragma unroll
          for (int i = 0; i < 4; i++) {
            if (k == 0) { d[i][0] = 0.f; d[i][1] = 0.f; d[i][2] = 0.f; d[i][3] = 0.f; }
            const uint32_t* w = wf[8 * n2 + 4 * n + i][k];
            mma16816(d[i][0], d[i][1], d[i][2], d[i][3], w[0], w[1], w[2], w[3], bf[2*k], bf[2*k+1]);
          }
        #pragma unroll
        for (int e = 0; e < 2; e++) {
          const float lo = (q & 1) ? d[1][2*e] : d[0][2*e], hi = (q & 1) ? d[3][2*e] : d[2][2*e];
          y[2*n+e] = (q & 2) ? hi : lo;
        }
      }
      asm volatile("{\n.reg .pred p;\nsetp.ne.s32 p, %5, 0;\n@p st.relaxed.gpu.global.v4.u32 [%0], {%1,%2,%3,%4};\n}\n"
                   :: "l"(dst + 128 * n2), "r"(__float_as_uint(y[0])), "r"(__float_as_uint(y[1])), "r"(__float_as_uint(y[2])), "r"(min(__float_as_uint(y[3]), ~1u)),
                      "r"(pass & (f < NFFN)) : "memory");
    }
    if (pass) { TSW(21); }
    }
  }
  }
  cluster_wait();
}

typedef CUresult (*EncodeFn)(CUtensorMap*, CUtensorMapDataType, cuuint32_t, void*, const cuuint64_t*, const cuuint64_t*,
                             const cuuint32_t*, const cuuint32_t*, CUtensorMapInterleave, CUtensorMapSwizzle,
                             CUtensorMapL2promotion, CUtensorMapFloatOOBfill);

void make_map(EncodeFn enc, CUtensorMap* m, const void* p, int n, const cuuint64_t* dims, const cuuint64_t* str, const cuuint32_t* box,
              CUtensorMapSwizzle sw, CUtensorMapL2promotion promo) {
  cuuint32_t es[5] = {1, 1, 1, 1, 1};
  enc(m, CU_TENSOR_MAP_DATA_TYPE_BFLOAT16, n, const_cast<void*>(p), dims, str, box, es, CU_TENSOR_MAP_INTERLEAVE_NONE, sw, promo,
      CU_TENSOR_MAP_FLOAT_OOB_FILL_NONE);
}
void map2(EncodeFn enc, CUtensorMap* m, const void* p, uint64_t cols, uint64_t rows, uint32_t bc, uint32_t br, CUtensorMapSwizzle sw,
          CUtensorMapL2promotion promo) {
  const cuuint64_t dims[2] = {cols, rows}, str[1] = {cols * 2};
  const cuuint32_t box[2] = {bc, br};
  make_map(enc, m, p, 2, dims, str, box, sw, promo);
}
void map3(EncodeFn enc, CUtensorMap* m, const void* p, uint64_t cols, uint64_t rows, uint32_t br, uint32_t nb) {
  const cuuint64_t dims[3] = {64, rows, cols / 64}, str[2] = {cols * 2, 128};
  const cuuint32_t box[3] = {64, br, nb};
  make_map(enc, m, p, 3, dims, str, box, CU_TENSOR_MAP_SWIZZLE_128B, CU_TENSOR_MAP_L2_PROMOTION_L2_128B);
}

}

extern "C" void kernel_launch(void* const* d_in, const int* in_sizes, int n_in, void* d_out, int out_size) {
  (void)in_sizes; (void)n_in; (void)out_size;
  static EncodeFn enc = nullptr;
  static void* o_ptr = nullptr;
  if (!enc) {
    void* f = nullptr; cudaDriverEntryPointQueryResult qr;
    cudaGetDriverEntryPoint("cuTensorMapEncodeTiled", &f, cudaEnableDefault, &qr);
    enc = (EncodeFn)f;
    cudaGetSymbolAddress(&o_ptr, g_scr);
    cudaFuncSetAttribute(fused_kernel, cudaFuncAttributeMaxDynamicSharedMemorySize, SMEM_BYTES);
  }
  const bf16* x = (const bf16*)d_in[0];
  const bf16* wqkv = (const bf16*)d_in[1];
  const bf16* wphi = (const bf16*)d_in[2];
  const bf16* wo = (const bf16*)d_in[3];
  const bf16* wr = (const bf16*)d_in[5];
  const bf16* wgate = (const bf16*)d_in[6];
  const bf16* wup = (const bf16*)d_in[7];
  const bf16* wdown = (const bf16*)d_in[8];
  Params P;
  const CUtensorMapSwizzle S128 = CU_TENSOR_MAP_SWIZZLE_128B, S64 = CU_TENSOR_MAP_SWIZZLE_64B;
  const CUtensorMapL2promotion L128 = CU_TENSOR_MAP_L2_PROMOTION_L2_128B, L256 = CU_TENSOR_MAP_L2_PROMOTION_L2_256B,
                               L64 = CU_TENSOR_MAP_L2_PROMOTION_L2_64B;
  map2(enc, &P.x128, x, DM, SEQ, 64, 128, S128, L256);
  map2(enc, &P.x64, x, DM, SEQ, 64, 64, S128, L128);
  {
    const cuuint64_t dims[4] = {64, DM, 16, 3}, str[3] = {6 * DM, 128, 2 * DM};
    const cuuint32_t box[4] = {64, 64, 1, 2};
    make_map(enc, &P.wkv, wqkv, 4, dims, str, box, S128, L128);
  }
  map3(enc, &P.wq, wqkv, 3 * DM, DM, 64, 2);
  {
    const cuuint64_t dims[4] = {64, DM - 64, 2, 16}, str[3] = {2 * DM, 128 * DM, 128};
    const cuuint32_t box[4] = {64, 32, 2, 2};
    make_map(enc, &P.wo, wo, 4, dims, str, box, S128, L128);
  }
  map3(enc, &P.wd, wdown, DM, FF, 32, 4);
  map2(enc, &P.wg, wgate, FF, DM, 32, 128, S64, L64);
  map2(enc, &P.wu, wup, FF, DM, 32, 128, S64, L64);
  map2(enc, &P.phi, wphi, 32, 1024, 32, 32, S64, L64);
  P.x = x; P.wqkv = wqkv; P.wo_p = wo; P.wd_p = wdown; P.wg_p = wgate; P.wu_p = wup; P.wr = wr; P.out_p = (bf16*)d_out; P.g = (Scratch*)o_ptr;

  cudaLaunchConfig_t cfg = {};
  cfg.gridDim = dim3(128); cfg.blockDim = dim3(512); cfg.dynamicSmemBytes = SMEM_BYTES; cfg.stream = cudaStreamPerThread;
  cudaLaunchAttribute at[1];
  at[0].id = cudaLaunchAttributeClusterDimension; at[0].val.clusterDim.x = 2; at[0].val.clusterDim.y = 1; at[0].val.clusterDim.z = 1;
  cfg.attrs = at; cfg.numAttrs = 1;
  cudaLaunchKernelEx(&cfg, fused_kernel, P);
}
```

```cpp
#include <cuda_runtime.h>
#include <cuda.h>
#include <cuda_bf16.h>
#include <stdint.h>

namespace {

typedef __nv_bfloat16 bf16;

__device__ __forceinline__ uint32_t smem_u32(const void* p){ return (uint32_t)__cvta_generic_to_shared(p); }
__device__ __forceinline__ void mbar_init(uint32_t bar, uint32_t cnt){ asm volatile("mbarrier.init.shared::cta.b64 [%0], %1;"::"r"(bar),"r"(cnt):"memory"); }
__device__ __forceinline__ void mbar_expect_tx(uint32_t bar, uint32_t bytes){ asm volatile("mbarrier.arrive.expect_tx.shared::cta.b64 _, [%0], %1;"::"r"(bar),"r"(bytes):"memory"); }
__device__ __forceinline__ void mbar_arrive(uint32_t bar){ asm volatile("mbarrier.arrive.shared::cta.b64 _, [%0];"::"r"(bar):"memory"); }
__device__ __forceinline__ uint32_t mapa(uint32_t addr, uint32_t cta){ uint32_t r; asm volatile("mapa.shared::cluster.u32 %0, %1, %2;":"=r"(r):"r"(addr),"r"(cta)); return r; }
__device__ __forceinline__ void mbar_arrive_at(uint32_t bar, uint32_t cta, uint32_t cnt){
  asm volatile("{\n.reg .b32 ra;\nmapa.shared::cluster.u32 ra, %0, %1;\nmbarrier.arrive.shared::cluster.b64 _, [ra], %2;\n}\n"::"r"(bar),"r"(cta),"r"(cnt):"memory"); }
__device__ __forceinline__ void mbar_arrive_remote(uint32_t cluster_addr, uint32_t cnt){
  asm volatile("mbarrier.arrive.shared::cluster.b64 _, [%0], %1;"::"r"(cluster_addr),"r"(cnt):"memory"); }
__device__ __forceinline__ void mbar_wait(uint32_t bar, uint32_t parity){
  asm volatile("{\n.reg .pred p;\n.reg .u32 c;\nmov.u32 c, 0;\nLW:\nmbarrier.try_wait.parity.shared::cta.b64 p, [%0], %1;\n@p bra LD;\nadd.u32 c, c, 1;\nsetp.lt.u32 p, c, 2000000;\n@p bra LW;\ntrap;\nLD:\n}\n"::"r"(bar),"r"(parity):"memory"); }
__device__ __forceinline__ void mbar_wait2(uint32_t bar0, uint32_t par0, uint32_t bar1, uint32_t par1){
  asm volatile("{\n.reg .pred p, q;\n.reg .u32 c;\nmov.u32 c, 0;\nLW:\nmbarrier.try_wait.parity.shared::cta.b64 p, [%0], %1;\nmbarrier.try_wait.parity.shared::cta.b64 q, [%2], %3;\nand.pred p, p, q;\n@p bra LD;\nadd.u32 c, c, 1;\nsetp.lt.u32 p, c, 2000000;\n@p bra LW;\ntrap;\nLD:\n}\n"::"r"(bar0),"r"(par0),"r"(bar1),"r"(par1):"memory"); }
__device__ __forceinline__ void tma_2d(uint32_t dst, const CUtensorMap* m, int c0, int c1, uint32_t bar){
  asm volatile("cp.async.bulk.tensor.2d.shared::cluster.global.mbarrier::complete_tx::bytes [%0], [%1, {%3, %4}], [%2];"::"r"(dst),"l"(m),"r"(bar),"r"(c0),"r"(c1):"memory"); }
__device__ __forceinline__ void tma_2d_mc(uint32_t dst, const CUtensorMap* m, int c0, int c1, uint32_t bar){
  asm volatile("cp.async.bulk.tensor.2d.shared::cluster.global.mbarrier::complete_tx::bytes.multicast::cluster [%0], [%1, {%3, %4}], [%2], %5;"::"r"(dst),"l"(m),"r"(bar),"r"(c0),"r"(c1),"h"((uint16_t)3):"memory"); }
__device__ __forceinline__ void tma_2d_mc_h(uint32_t dst, const CUtensorMap* m, int c0, int c1, uint32_t bar, uint64_t pol){
  asm volatile("cp.async.bulk.tensor.2d.shared::cluster.global.mbarrier::complete_tx::bytes.multicast::cluster.L2::cache_hint [%0], [%1, {%3, %4}], [%2], %5, %6;"::"r"(dst),"l"(m),"r"(bar),"r"(c0),"r"(c1),"h"((uint16_t)3),"l"(pol):"memory"); }
__device__ __forceinline__ void tma_4d(uint32_t dst, const CUtensorMap* m, int c0, int c1, int c2, int c3, uint32_t bar){
  asm volatile("cp.async.bulk.tensor.4d.shared::cluster.global.mbarrier::complete_tx::bytes [%0], [%1, {%3, %4, %5, %6}], [%2];"::"r"(dst),"l"(m),"r"(bar),"r"(c0),"r"(c1),"r"(c2),"r"(c3):"memory"); }
__device__ __forceinline__ uint64_t policy_evict_first(){ uint64_t p; asm volatile("createpolicy.fractional.L2::evict_first.b64 %0, 1.0;":"=l"(p)); return p; }
__device__ __forceinline__ void tma_3d_h(uint32_t dst, const CUtensorMap* m, int c0, int c1, int c2, uint32_t bar, uint64_t pol){
  asm volatile("cp.async.bulk.tensor.3d.shared::cluster.global.mbarrier::complete_tx::bytes.L2::cache_hint [%0], [%1, {%3, %4, %5}], [%2], %6;"::"r"(dst),"l"(m),"r"(bar),"r"(c0),"r"(c1),"r"(c2),"l"(pol):"memory"); }
__device__ __forceinline__ void tma_4d_h(uint32_t dst, const CUtensorMap* m, int c0, int c1, int c2, int c3, uint32_t bar, uint64_t pol){
  asm volatile("cp.async.bulk.tensor.4d.shared::cluster.global.mbarrier::complete_tx::bytes.L2::cache_hint [%0], [%1, {%3, %4, %5, %6}], [%2], %7;"::"r"(dst),"l"(m),"r"(bar),"r"(c0),"r"(c1),"r"(c2),"r"(c3),"l"(pol):"memory"); }
__device__ __forceinline__ void red_add_f32x4(float4* p, float x, float y, float z, float w){ asm volatile("red.relaxed.gpu.global.add.v4.f32 [%0], {%1,%2,%3,%4};"::"l"(p),"f"(x),"f"(y),"f"(z),"f"(w):"memory"); }
__device__ __forceinline__ void tma_5d_h(uint32_t dst, const CUtensorMap* m, int c0, int c1, uint32_t bar, uint64_t pol){
  asm volatile("cp.async.bulk.tensor.5d.shared::cluster.global.mbarrier::complete_tx::bytes.L2::cache_hint [%0], [%1, {%3, %4, 0, 0, 0}], [%2], %5;"::"r"(dst),"l"(m),"r"(bar),"r"(c0),"r"(c1),"l"(pol):"memory"); }
__device__ __forceinline__ void st_async128(uint32_t dst_cluster, uint32_t x, uint32_t y, uint32_t z, uint32_t w, uint32_t bar_cluster){
  asm volatile("st.async.weak.shared::cluster.mbarrier::complete_tx::bytes.v4.b32 [%0], {%1,%2,%3,%4}, [%5];"::"r"(dst_cluster),"r"(x),"r"(y),"r"(z),"r"(w),"r"(bar_cluster):"memory"); }
__device__ __forceinline__ bool elect_one(){ uint32_t p; asm volatile("{\n.reg .pred P;\nelect.sync _|P, 0xffffffff;\nselp.b32 %0, 1, 0, P;\n}\n":"=r"(p)); return p; }
__device__ __forceinline__ void bulk_prefetch(const void* p, uint32_t bytes){
  asm volatile("cp.async.bulk.prefetch.L2.global [%0], %1;"::"l"(p),"r"(bytes):"memory"); }
__device__ __forceinline__ void bulk_g2s_mc(uint32_t dst, const void* src, uint32_t bytes, uint32_t bar, uint64_t pol){
  asm volatile("cp.async.bulk.shared::cluster.global.mbarrier::complete_tx::bytes.multicast::cluster.L2::cache_hint [%0], [%1], %2, [%3], %4, %5;"::"r"(dst),"l"(src),"r"(bytes),"r"(bar),"h"((uint16_t)3),"l"(pol):"memory"); }
__device__ __forceinline__ void prefetch_map(const CUtensorMap* m){ asm volatile("prefetch.tensormap [%0];"::"l"(m):"memory"); }
__device__ __forceinline__ void fence_async_smem(){ asm volatile("fence.proxy.async.shared::cta;":::"memory"); }
__device__ __forceinline__ void fence_acquire_gpu(){ asm volatile("fence.acquire.gpu;":::"memory"); }
__device__ __forceinline__ void fence_gpu(){ asm volatile("fence.acq_rel.gpu;":::"memory"); }
__device__ __forceinline__ void wg_fence(){ asm volatile("wgmma.fence.sync.aligned;":::"memory"); }
__device__ __forceinline__ void wg_commit(){ asm volatile("wgmma.commit_group.sync.aligned;":::"memory"); }
template<int N> __device__ __forceinline__ void wg_wait(){ asm volatile("wgmma.wait_group.sync.aligned %0;"::"n"(N):"memory"); }
template<int N> __device__ __forceinline__ void fence_regs(float (&d)[N]){
  #pragma unroll
  for(int i=0;i<N;i++) asm volatile("":"+f"(d[i])::"memory"); }
__device__ __forceinline__ void bar_sync(int id, int n){ asm volatile("bar.sync %0, %1;"::"r"(id),"r"(n):"memory"); }
__device__ __forceinline__ void bar_arrive(int id, int n){ asm volatile("bar.arrive %0, %1;"::"r"(id),"r"(n):"memory"); }
__device__ __forceinline__ void cluster_arrive(){ asm volatile("barrier.cluster.arrive.relaxed.aligned;":::"memory"); }
__device__ __forceinline__ void cluster_wait(){ asm volatile("barrier.cluster.wait.aligned;":::"memory"); }
__host__ __device__ constexpr uint32_t dlo(uint32_t addr, uint32_t lbo){ return (addr >> 4) | ((lbo >> 4) << 16); }
__host__ __device__ constexpr uint32_t dhi(uint32_t sbo, uint32_t sw){ return (sbo >> 4) | (sw << 30); }
constexpr uint32_t H128 = dhi(1024, 1), H64 = dhi(512, 2), H0 = dhi(128, 0);
__device__ __forceinline__ uint32_t pack_bf16(float lo, float hi){ uint32_t r; asm("cvt.rn.bf16x2.f32 %0, %1, %2;":"=r"(r):"f"(hi),"f"(lo)); return r; }
__device__ __forceinline__ float bf_lo(uint32_t v){ return __uint_as_float(v<<16); }
__device__ __forceinline__ float bf_hi(uint32_t v){ return __uint_as_float(v&0xffff0000u); }
__device__ __forceinline__ float ex2(float x){ float r; asm("ex2.approx.ftz.f32 %0, %1;":"=f"(r):"f"(x)); return r; }
__device__ __forceinline__ float rcp(float x){ float r; asm("rcp.approx.ftz.f32 %0, %1;":"=f"(r):"f"(x)); return r; }
__device__ __forceinline__ void stsm4(uint32_t addr, uint32_t a, uint32_t b, uint32_t c, uint32_t d){
  asm volatile("stmatrix.sync.aligned.m8n8.x4.shared.b16 [%0], {%1,%2,%3,%4};"::"r"(addr),"r"(a),"r"(b),"r"(c),"r"(d)); }
__device__ __forceinline__ void stsm2(uint32_t addr, uint32_t a, uint32_t b){
  asm volatile("stmatrix.sync.aligned.m8n8.x2.shared.b16 [%0], {%1,%2};"::"r"(addr),"r"(a),"r"(b)); }
__device__ __forceinline__ void mma16816(float& d0, float& d1, float& d2, float& d3, uint32_t a0, uint32_t a1, uint32_t a2, uint32_t a3, uint32_t b0, uint32_t b1){
  asm volatile("mma.sync.aligned.m16n8k16.row.col.f32.bf16.bf16.f32 {%0,%1,%2,%3}, {%4,%5,%6,%7}, {%8,%9}, {%0,%1,%2,%3};"
               : "+f"(d0), "+f"(d1), "+f"(d2), "+f"(d3) : "r"(a0), "r"(a1), "r"(a2), "r"(a3), "r"(b0), "r"(b1)); }
__device__ __forceinline__ void ldsm4(uint32_t addr, uint32_t& a, uint32_t& b, uint32_t& c, uint32_t& d){
  asm volatile("ldmatrix.sync.aligned.m8n8.x4.shared.b16 {%0,%1,%2,%3}, [%4];":"=r"(a),"=r"(b),"=r"(c),"=r"(d):"r"(addr):"memory"); }
__device__ __forceinline__ void ldsm4t(uint32_t addr, uint32_t& a, uint32_t& b, uint32_t& c, uint32_t& d){
  asm volatile("ldmatrix.sync.aligned.m8n8.x4.trans.shared.b16 {%0,%1,%2,%3}, [%4];":"=r"(a),"=r"(b),"=r"(c),"=r"(d):"r"(addr):"memory"); }
__device__ __forceinline__ void sts32(uint32_t a, uint32_t v){ asm volatile("st.shared.b32 [%0], %1;"::"r"(a),"r"(v):"memory"); }
__device__ __forceinline__ void stsf(uint32_t a, float v){ asm volatile("st.shared.f32 [%0], %1;"::"r"(a),"f"(v):"memory"); }
__device__ __forceinline__ void sts64(uint32_t a, uint32_t x, uint32_t y){ asm volatile("st.shared.v2.b32 [%0], {%1,%2};"::"r"(a),"r"(x),"r"(y):"memory"); }
__device__ __forceinline__ void sts128(uint32_t a, uint32_t x, uint32_t y, uint32_t z, uint32_t w){ asm volatile("st.shared.v4.b32 [%0], {%1,%2,%3,%4};"::"r"(a),"r"(x),"r"(y),"r"(z),"r"(w):"memory"); }
__device__ __forceinline__ float ldsf(uint32_t a){ float v; asm volatile("ld.shared.f32 %0, [%1];":"=f"(v):"r"(a):"memory"); return v; }
__device__ __forceinline__ float2 lds64f(uint32_t a){ float2 v; asm volatile("ld.shared.v2.f32 {%0,%1}, [%2];":"=f"(v.x),"=f"(v.y):"r"(a):"memory"); return v; }
__device__ __forceinline__ uint4 lds128(uint32_t a){ uint4 v; asm volatile("ld.shared.v4.u32 {%0,%1,%2,%3}, [%4];":"=r"(v.x),"=r"(v.y),"=r"(v.z),"=r"(v.w):"r"(a):"memory"); return v; }
__device__ __forceinline__ uint4 ld128_keep(const void* p){ uint4 v; asm volatile("ld.global.v4.u32 {%0,%1,%2,%3}, [%4];":"=r"(v.x),"=r"(v.y),"=r"(v.z),"=r"(v.w):"l"(p):"memory"); return v; }
__device__ __forceinline__ uint4 ld128_rlx(const void* p){ uint4 v; asm volatile("ld.relaxed.gpu.global.v4.u32 {%0,%1,%2,%3}, [%4];":"=r"(v.x),"=r"(v.y),"=r"(v.z),"=r"(v.w):"l"(p):"memory"); return v; }
__device__ __forceinline__ uint32_t ld32_rlx(const void* p){ uint32_t v; asm volatile("ld.relaxed.gpu.global.u32 %0, [%1];":"=r"(v):"l"(p):"memory"); return v; }
__device__ __forceinline__ void st128_rlx(void* p, uint32_t x, uint32_t y, uint32_t z, uint32_t w){ asm volatile("st.relaxed.gpu.global.v4.u32 [%0], {%1,%2,%3,%4};"::"l"(p),"r"(x),"r"(y),"r"(z),"r"(w):"memory"); }
__device__ __forceinline__ void st64_rlx(void* p, uint32_t x, uint32_t y){ asm volatile("st.relaxed.gpu.global.v2.u32 [%0], {%1,%2};"::"l"(p),"r"(x),"r"(y):"memory"); }
__device__ __forceinline__ void st32_rlx(void* p, uint32_t x){ asm volatile("st.relaxed.gpu.global.u32 [%0], %1;"::"l"(p),"r"(x):"memory"); }
__device__ __forceinline__ uint32_t tagw(float x, uint32_t t){ return (__float_as_uint(x) & ~3u) | t; }
__device__ __forceinline__ float untag(uint32_t w){ return __uint_as_float(w & ~3u); }

template<int TA, int TB, uint32_t HA, uint32_t HB> __device__ __forceinline__ void wgmma_ss_n128(float (&d)[64], uint32_t da, uint32_t db, int scale_d){
  asm volatile("{\n.reg .pred p;\n.reg .b64 a, b;\nsetp.ne.b32 p, %70, 0;\nmov.b64 a, {%64, %68};\nmov.b64 b, {%65, %69};\n"
  "wgmma.mma_async.sync.aligned.m64n128k16.f32.bf16.bf16 {%0, %1, %2, %3, %4, %5, %6, %7, %8, %9, %10, %11, %12, %13, %14, %15, %16, %17, %18, %19, %20, %21, %22, %23, %24, %25, %26, %27, %28, %29, %30, %31, %32, %33, %34, %35, %36, %37, %38, %39, %40, %41, %42, %43, %44, %45, %46, %47, %48, %49, %50, %51, %52, %53, %54, %55, %56, %57, %58, %59, %60, %61, %62, %63}, a, b, p, 1, 1, %66, %67;\n}\n"
  : "+f"(d[0]), "+f"(d[1]), "+f"(d[2]), "+f"(d[3]), "+f"(d[4]), "+f"(d[5]), "+f"(d[6]), "+f"(d[7]), "+f"(d[8]), "+f"(d[9]), "+f"(d[10]), "+f"(d[11]), "+f"(d[12]), "+f"(d[13]), "+f"(d[14]), "+f"(d[15]), "+f"(d[16]), "+f"(d[17]), "+f"(d[18]), "+f"(d[19]), "+f"(d[20]), "+f"(d[21]), "+f"(d[22]), "+f"(d[23]), "+f"(d[24]), "+f"(d[25]), "+f"(d[26]), "+f"(d[27]), "+f"(d[28]), "+f"(d[29]), "+f"(d[30]), "+f"(d[31]), "+f"(d[32]), "+f"(d[33]), "+f"(d[34]), "+f"(d[35]), "+f"(d[36]), "+f"(d[37]), "+f"(d[38]), "+f"(d[39]), "+f"(d[40]), "+f"(d[41]), "+f"(d[42]), "+f"(d[43]), "+f"(d[44]), "+f"(d[45]), "+f"(d[46]), "+f"(d[47]), "+f"(d[48]), "+f"(d[49]), "+f"(d[50]), "+f"(d[51]), "+f"(d[52]), "+f"(d[53]), "+f"(d[54]), "+f"(d[55]), "+f"(d[56]), "+f"(d[57]), "+f"(d[58]), "+f"(d[59]), "+f"(d[60]), "+f"(d[61]), "+f"(d[62]), "+f"(d[63])
  : "r"(da), "r"(db), "n"(TA), "n"(TB), "n"(HA), "n"(HB), "r"(scale_d));
}
template<int TA, int TB, uint32_t HA, uint32_t HB> __device__ __forceinline__ void wgmma_sa_n128(float (&d)[64], uint32_t da, uint32_t db){
  asm volatile("{\n.reg .pred p;\n.reg .b64 a, b;\nsetp.ne.b32 p, 1, 0;\nmov.b64 a, {%64, %68};\nmov.b64 b, {%65, %69};\n"
  "wgmma.mma_async.sync.aligned.m64n128k16.f32.bf16.bf16 {%0, %1, %2, %3, %4, %5, %6, %7, %8, %9, %10, %11, %12, %13, %14, %15, %16, %17, %18, %19, %20, %21, %22, %23, %24, %25, %26, %27, %28, %29, %30, %31, %32, %33, %34, %35, %36, %37, %38, %39, %40, %41, %42, %43, %44, %45, %46, %47, %48, %49, %50, %51, %52, %53, %54, %55, %56, %57, %58, %59, %60, %61, %62, %63}, a, b, p, 1, 1, %66, %67;\n}\n"
  : "+f"(d[0]), "+f"(d[1]), "+f"(d[2]), "+f"(d[3]), "+f"(d[4]), "+f"(d[5]), "+f"(d[6]), "+f"(d[7]), "+f"(d[8]), "+f"(d[9]), "+f"(d[10]), "+f"(d[11]), "+f"(d[12]), "+f"(d[13]), "+f"(d[14]), "+f"(d[15]), "+f"(d[16]), "+f"(d[17]), "+f"(d[18]), "+f"(d[19]), "+f"(d[20]), "+f"(d[21]), "+f"(d[22]), "+f"(d[23]), "+f"(d[24]), "+f"(d[25]), "+f"(d[26]), "+f"(d[27]), "+f"(d[28]), "+f"(d[29]), "+f"(d[30]), "+f"(d[31]), "+f"(d[32]), "+f"(d[33]), "+f"(d[34]), "+f"(d[35]), "+f"(d[36]), "+f"(d[37]), "+f"(d[38]), "+f"(d[39]), "+f"(d[40]), "+f"(d[41]), "+f"(d[42]), "+f"(d[43]), "+f"(d[44]), "+f"(d[45]), "+f"(d[46]), "+f"(d[47]), "+f"(d[48]), "+f"(d[49]), "+f"(d[50]), "+f"(d[51]), "+f"(d[52]), "+f"(d[53]), "+f"(d[54]), "+f"(d[55]), "+f"(d[56]), "+f"(d[57]), "+f"(d[58]), "+f"(d[59]), "+f"(d[60]), "+f"(d[61]), "+f"(d[62]), "+f"(d[63])
  : "r"(da), "r"(db), "n"(TA), "n"(TB), "n"(HA), "n"(HB));
}
template<int TA, int TB, uint32_t HA, uint32_t HB> __device__ __forceinline__ void wgmma_sa_n40(float (&d)[20], uint32_t da, uint32_t db){
  asm volatile("{\n.reg .pred p;\n.reg .b64 a, b;\nsetp.ne.b32 p, 1, 0;\nmov.b64 a, {%20, %24};\nmov.b64 b, {%21, %25};\n"
  "wgmma.mma_async.sync.aligned.m64n40k16.f32.bf16.bf16 {%0, %1, %2, %3, %4, %5, %6, %7, %8, %9, %10, %11, %12, %13, %14, %15, %16, %17, %18, %19}, a, b, p, 1, 1, %22, %23;\n}\n"
  : "+f"(d[0]), "+f"(d[1]), "+f"(d[2]), "+f"(d[3]), "+f"(d[4]), "+f"(d[5]), "+f"(d[6]), "+f"(d[7]), "+f"(d[8]), "+f"(d[9]), "+f"(d[10]), "+f"(d[11]), "+f"(d[12]), "+f"(d[13]), "+f"(d[14]), "+f"(d[15]), "+f"(d[16]), "+f"(d[17]), "+f"(d[18]), "+f"(d[19])
  : "r"(da), "r"(db), "n"(TA), "n"(TB), "n"(HA), "n"(HB));
}
template<int TA, int TB, uint32_t HA, uint32_t HB> __device__ __forceinline__ void wgmma_sz_n40(float (&d)[20], uint32_t da, uint32_t db){
  asm volatile("{\n.reg .pred p;\n.reg .b64 a, b;\nsetp.ne.b32 p, 0, 0;\nmov.b64 a, {%20, %24};\nmov.b64 b, {%21, %25};\n"
  "wgmma.mma_async.sync.aligned.m64n40k16.f32.bf16.bf16 {%0, %1, %2, %3, %4, %5, %6, %7, %8, %9, %10, %11, %12, %13, %14, %15, %16, %17, %18, %19}, a, b, p, 1, 1, %22, %23;\n}\n"
  : "=f"(d[0]), "=f"(d[1]), "=f"(d[2]), "=f"(d[3]), "=f"(d[4]), "=f"(d[5]), "=f"(d[6]), "=f"(d[7]), "=f"(d[8]), "=f"(d[9]), "=f"(d[10]), "=f"(d[11]), "=f"(d[12]), "=f"(d[13]), "=f"(d[14]), "=f"(d[15]), "=f"(d[16]), "=f"(d[17]), "=f"(d[18]), "=f"(d[19])
  : "r"(da), "r"(db), "n"(TA), "n"(TB), "n"(HA), "n"(HB));
}
template<int TA, int TB, uint32_t HA, uint32_t HB> __device__ __forceinline__ void wgmma_sa_n32(float (&d)[16], uint32_t da, uint32_t db){
  asm volatile("{\n.reg .pred p;\n.reg .b64 a, b;\nsetp.ne.b32 p, 1, 0;\nmov.b64 a, {%16, %20};\nmov.b64 b, {%17, %21};\n"
  "wgmma.mma_async.sync.aligned.m64n32k16.f32.bf16.bf16 {%0, %1, %2, %3, %4, %5, %6, %7, %8, %9, %10, %11, %12, %13, %14, %15}, a, b, p, 1, 1, %18, %19;\n}\n"
  : "+f"(d[0]), "+f"(d[1]), "+f"(d[2]), "+f"(d[3]), "+f"(d[4]), "+f"(d[5]), "+f"(d[6]), "+f"(d[7]), "+f"(d[8]), "+f"(d[9]), "+f"(d[10]), "+f"(d[11]), "+f"(d[12]), "+f"(d[13]), "+f"(d[14]), "+f"(d[15])
  : "r"(da), "r"(db), "n"(TA), "n"(TB), "n"(HA), "n"(HB));
}
template<int TA, int TB, uint32_t HA, uint32_t HB> __device__ __forceinline__ void wgmma_ss_n32(float (&d)[16], uint32_t da, uint32_t db, int scale_d){
  asm volatile("{\n.reg .pred p;\n.reg .b64 a, b;\nsetp.ne.b32 p, %22, 0;\nmov.b64 a, {%16, %20};\nmov.b64 b, {%17, %21};\n"
  "wgmma.mma_async.sync.aligned.m64n32k16.f32.bf16.bf16 {%0, %1, %2, %3, %4, %5, %6, %7, %8, %9, %10, %11, %12, %13, %14, %15}, a, b, p, 1, 1, %18, %19;\n}\n"
  : "+f"(d[0]), "+f"(d[1]), "+f"(d[2]), "+f"(d[3]), "+f"(d[4]), "+f"(d[5]), "+f"(d[6]), "+f"(d[7]), "+f"(d[8]), "+f"(d[9]), "+f"(d[10]), "+f"(d[11]), "+f"(d[12]), "+f"(d[13]), "+f"(d[14]), "+f"(d[15])
  : "r"(da), "r"(db), "n"(TA), "n"(TB), "n"(HA), "n"(HB), "r"(scale_d));
}
template<int TB, uint32_t HB> __device__ __forceinline__ void wgmma_ra_n32(float (&d)[16], uint32_t a0, uint32_t a1, uint32_t a2, uint32_t a3, uint32_t db){
  asm volatile("{\n.reg .pred p;\n.reg .b64 a, b;\nsetp.ne.b32 p, 1, 0;\nmov.b64 b, {%20, %22};\n"
  "wgmma.mma_async.sync.aligned.m64n32k16.f32.bf16.bf16 {%0, %1, %2, %3, %4, %5, %6, %7, %8, %9, %10, %11, %12, %13, %14, %15}, {%16,%17,%18,%19}, b, p, 1, 1, %21;\n}\n"
  : "+f"(d[0]), "+f"(d[1]), "+f"(d[2]), "+f"(d[3]), "+f"(d[4]), "+f"(d[5]), "+f"(d[6]), "+f"(d[7]), "+f"(d[8]), "+f"(d[9]), "+f"(d[10]), "+f"(d[11]), "+f"(d[12]), "+f"(d[13]), "+f"(d[14]), "+f"(d[15])
  : "r"(a0), "r"(a1), "r"(a2), "r"(a3), "r"(db), "n"(TB), "n"(HB));
}
template<int TB, uint32_t HB> __device__ __forceinline__ void wgmma_rs_n32(float (&d)[16], uint32_t a0, uint32_t a1, uint32_t a2, uint32_t a3, uint32_t db, int scale_d){
  asm volatile("{\n.reg .pred p;\n.reg .b64 a, b;\nsetp.ne.b32 p, %23, 0;\nmov.b64 b, {%20, %22};\n"
  "wgmma.mma_async.sync.aligned.m64n32k16.f32.bf16.bf16 {%0, %1, %2, %3, %4, %5, %6, %7, %8, %9, %10, %11, %12, %13, %14, %15}, {%16,%17,%18,%19}, b, p, 1, 1, %21;\n}\n"
  : "+f"(d[0]), "+f"(d[1]), "+f"(d[2]), "+f"(d[3]), "+f"(d[4]), "+f"(d[5]), "+f"(d[6]), "+f"(d[7]), "+f"(d[8]), "+f"(d[9]), "+f"(d[10]), "+f"(d[11]), "+f"(d[12]), "+f"(d[13]), "+f"(d[14]), "+f"(d[15])
  : "r"(a0), "r"(a1), "r"(a2), "r"(a3), "r"(db), "n"(TB), "n"(HB), "r"(scale_d));
}
template<int TB, uint32_t HB> __device__ __forceinline__ void wgmma_ra_n40(float (&d)[20], uint32_t a0, uint32_t a1, uint32_t a2, uint32_t a3, uint32_t db){
  asm volatile("{\n.reg .pred p;\n.reg .b64 a, b;\nsetp.ne.b32 p, 1, 0;\nmov.b64 b, {%24, %26};\n"
  "wgmma.mma_async.sync.aligned.m64n40k16.f32.bf16.bf16 {%0, %1, %2, %3, %4, %5, %6, %7, %8, %9, %10, %11, %12, %13, %14, %15, %16, %17, %18, %19}, {%20,%21,%22,%23}, b, p, 1, 1, %25;\n}\n"
  : "+f"(d[0]), "+f"(d[1]), "+f"(d[2]), "+f"(d[3]), "+f"(d[4]), "+f"(d[5]), "+f"(d[6]), "+f"(d[7]), "+f"(d[8]), "+f"(d[9]), "+f"(d[10]), "+f"(d[11]), "+f"(d[12]), "+f"(d[13]), "+f"(d[14]), "+f"(d[15]), "+f"(d[16]), "+f"(d[17]), "+f"(d[18]), "+f"(d[19])
  : "r"(a0), "r"(a1), "r"(a2), "r"(a3), "r"(db), "n"(TB), "n"(HB));
}
template<int TB, uint32_t HB> __device__ __forceinline__ void wgmma_rz_n40(float (&d)[20], uint32_t a0, uint32_t a1, uint32_t a2, uint32_t a3, uint32_t db){
  asm volatile("{\n.reg .pred p;\n.reg .b64 a, b;\nsetp.ne.b32 p, 0, 0;\nmov.b64 b, {%24, %26};\n"
  "wgmma.mma_async.sync.aligned.m64n40k16.f32.bf16.bf16 {%0, %1, %2, %3, %4, %5, %6, %7, %8, %9, %10, %11, %12, %13, %14, %15, %16, %17, %18, %19}, {%20,%21,%22,%23}, b, p, 1, 1, %25;\n}\n"
  : "=f"(d[0]), "=f"(d[1]), "=f"(d[2]), "=f"(d[3]), "=f"(d[4]), "=f"(d[5]), "=f"(d[6]), "=f"(d[7]), "=f"(d[8]), "=f"(d[9]), "=f"(d[10]), "=f"(d[11]), "=f"(d[12]), "=f"(d[13]), "=f"(d[14]), "=f"(d[15]), "=f"(d[16]), "=f"(d[17]), "=f"(d[18]), "=f"(d[19])
  : "r"(a0), "r"(a1), "r"(a2), "r"(a3), "r"(db), "n"(TB), "n"(HB));
}
template<int TB, uint32_t HB> __device__ __forceinline__ void wgmma_ra_n8(float (&d)[4], uint32_t a0, uint32_t a1, uint32_t a2, uint32_t a3, uint32_t db){
  asm volatile("{\n.reg .pred p;\n.reg .b64 a, b;\nsetp.ne.b32 p, 1, 0;\nmov.b64 b, {%8, %10};\n"
  "wgmma.mma_async.sync.aligned.m64n8k16.f32.bf16.bf16 {%0, %1, %2, %3}, {%4,%5,%6,%7}, b, p, 1, 1, %9;\n}\n"
  : "+f"(d[0]), "+f"(d[1]), "+f"(d[2]), "+f"(d[3])
  : "r"(a0), "r"(a1), "r"(a2), "r"(a3), "r"(db), "n"(TB), "n"(HB));
}
template<int TB, uint32_t HB> __device__ __forceinline__ void wgmma_rz_n8(float (&d)[4], uint32_t a0, uint32_t a1, uint32_t a2, uint32_t a3, uint32_t db){
  asm volatile("{\n.reg .pred p;\n.reg .b64 a, b;\nsetp.ne.b32 p, 0, 0;\nmov.b64 b, {%8, %10};\n"
  "wgmma.mma_async.sync.aligned.m64n8k16.f32.bf16.bf16 {%0, %1, %2, %3}, {%4,%5,%6,%7}, b, p, 1, 1, %9;\n}\n"
  : "=f"(d[0]), "=f"(d[1]), "=f"(d[2]), "=f"(d[3])
  : "r"(a0), "r"(a1), "r"(a2), "r"(a3), "r"(db), "n"(TB), "n"(HB));
}

constexpr int SEQ = 2048, DM = 1024, FF = 3584;
constexpr float LOG2E = 1.4426950408889634f;
constexpr uint32_t POLL_LIMIT = 1u << 22;
constexpr int NPRE = 2;
#define QW 12
#define RST_STEP 100
#define SKM 0x251
#define LAG 1
#define PF_T0 6500
#define PF_DT 800
#define Q0L 3
#define NFFN_L NFFN
#define FF_DT 800
#define OUT_U 1
#define GRES 8
#define OUT_L 0
#define TMASK 0xffffff
#define PMASK 0xffffff
#define FF_T0 0
#define OUT_NS 0
constexpr int NFFN = 112;

constexpr uint32_t SB0 = 1024;
constexpr uint32_t KV_STAGE = 49152, R5 = 32768;
constexpr uint32_t OFF_X = 163840, OFF_S = 196608, OFF_WPHI = OFF_S + 20480, OFF_M = 229376, SMEM_BYTES = 232448;
constexpr uint32_t OFF_RS256 = 212992, OFF_ONES = OFF_RS256 + 1024, OFF_WPHIK1 = OFF_ONES + 1024, OFF_KVZ = OFF_S;
constexpr uint32_t OFF_WPHIK = OFF_S, OFF_BXK = OFF_S + 2048, OFF_AXK = OFF_S + 4096;
constexpr uint32_t OFF_AXQ = OFF_WPHI, OFF_BXQ = OFF_WPHI + 2048, OFF_WPHIQ = OFF_WPHI + 4096;
constexpr uint32_t B_FULLKV = OFF_M, B_EMPTYKV = OFF_M + 32, B_FULL5 = OFF_M + 64, B_EMPTY5 = OFF_M + 104;
constexpr uint32_t B_W = OFF_M + 144, B_OS = OFF_M + 152, B_R = OFF_M + 160, B_AUX = OFF_M + 168, B_AUXQ = OFF_M + 176, B_KD = OFF_M + 184, B_RC = OFF_M + 192  ;
constexpr uint32_t B_FULLA = OFF_M + 768, B_QL = B_FULLA + 80, B_UO = B_FULLA + 96  ;
constexpr uint32_t OFF_SUMWR = OFF_M + 896, OFF_EP = OFF_M + 208, OFF_KEY = OFF_M + 216, OFF_EXC = OFF_M + 224;
constexpr uint32_t OFF_RSQ = OFF_M + 256, OFF_WR = OFF_M + 2048, OFF_XSEL = 4 * R5;
constexpr uint32_t OFF_ACT = OFF_XSEL + 2048, OFF_GU = OFF_XSEL + 4096, OFF_SCR = OFF_M + 2432, B_F = OFF_M + 1536  , B_WD = B_F + 64  , B_WC = B_F + 96  , B_DR = B_F + 128  , B_RX = B_F + 144, B_XS = B_F + 152, B_T = B_F + 160, B_OUT = B_F + 168  , OFF_T = OFF_M + 1792;
constexpr int KVP = 6 * 128;

enum { NB_G2E = 1, NB_XS = 2, NB_WG01 = 3, NB_ACT = 4, NB_Q0 = 5  , NB_ST = 14, NB_DN = 9, NB_ZERO = 10, NB_PUB = 11, NB_TOK = 10  , NB_L0 = 12  , NB_WG2 = 7, NB_QGO = 15 };

struct Scratch {
  bf16     o[SEQ * DM];
  float4   rstat[SEQ];
  uint32_t key[32 * 128];
  uint32_t cand[128 * DM];
  uint32_t ypart[NFFN * DM];
  float4   kvacc[32 * KVP];
  uint2    stats[SEQ];
  uint32_t cskv[2 * DM];
  uint32_t csq[4 * DM];
  uint32_t oset[16 * 32];
  uint32_t epoch;
};
__device__ __align__(1024) Scratch g_scr;
#define TS(id)
#define TDUMP()
#define TS0_DECL()
#define TS0_READ()
#define TS0_WRITE()
#define TK(id)
#define TSW(id)

struct Params {
  CUtensorMap x128, x64, wkv, wq, wo, wd, wg, wu, phi, tg, tu, td;
  const bf16 *x, *wqkv, *wo_p, *wg_p, *wu_p, *wd_p, *wr;
  bf16* out_p;
  Scratch* g;
};

constexpr float EXP_LIM = 1.1529215e18f, ARG_LIM2 = 3600.f;
__device__ __forceinline__ void dual_exp2(const float (&p)[2][16], uint32_t (&ph)[4][8]) {
  #pragma unroll
  for (int h = 0; h < 2; h++)
    #pragma unroll
    for (int k = 0; k < 8; k++) { ph[2*h][k] = pack_bf16(ex2(p[h][2*k]), ex2(p[h][2*k+1])); ph[2*h+1][k] = pack_bf16(ex2(-p[h][2*k]), ex2(-p[h][2*k+1])); }
}
__device__ __forceinline__ void row_extremes(const float (&p)[16], const float (&c)[2], float (&m)[4]) {
  m[0] = m[2] = p[0]; m[1] = m[3] = p[2];
  #pragma unroll
  for (int i = 0; i < 16; i++) { m[(i >> 1) & 1] = fmaxf(m[(i >> 1) & 1], p[i]); m[2 + ((i >> 1) & 1)] = fminf(m[2 + ((i >> 1) & 1)], p[i]); }
  #pragma unroll
  for (int o = 1; o < 4; o <<= 1) {
    m[0] = fmaxf(m[0], __shfl_xor_sync(~0u, m[0], o)); m[1] = fmaxf(m[1], __shfl_xor_sync(~0u, m[1], o));
    m[2] = fminf(m[2], __shfl_xor_sync(~0u, m[2], o)); m[3] = fminf(m[3], __shfl_xor_sync(~0u, m[3], o));
  }
  m[0] *= -c[0]; m[1] *= -c[1]; m[2] *= c[0]; m[3] *= c[1];
}
__device__ __forceinline__ void dual_exp2_shifted(const float (&p)[2][16], uint32_t (&ph)[4][8]) {
  #pragma unroll
  for (int h = 0; h < 2; h++) {
    const float one[2] = {1.f, 1.f};
    float m[4];
    row_extremes(p[h], one, m);
    #pragma unroll
    for (int k = 0; k < 8; k++) {
      ph[2*h][k] = pack_bf16(ex2(p[h][2*k] + m[k & 1]), ex2(p[h][2*k+1] + m[k & 1]));
      ph[2*h+1][k] = pack_bf16(ex2(m[2 + (k & 1)] - p[h][2*k]), ex2(m[2 + (k & 1)] - p[h][2*k+1]));
    }
  }
}
__device__ __forceinline__ void row_sums(float (&s)[4][4], const uint32_t (&ph)[4][8], uint32_t ones) {
  #pragma unroll
  for (int i = 0; i < 4; i++) wgmma_rz_n8<0, H0>(s[i], ph[i][0], ph[i][1], ph[i][2], ph[i][3], ones);
  #pragma unroll
  for (int i = 0; i < 4; i++) wgmma_ra_n8<0, H0>(s[i], ph[i][4], ph[i][5], ph[i][6], ph[i][7], ones);
}
__device__ __forceinline__ uint32_t mul_bf16x2(uint32_t a, uint32_t b) { uint32_t r; asm("mul.rn.bf16x2 %0, %1, %2;" : "=r"(r) : "r"(a), "r"(b)); return r; }
__device__ __forceinline__ void normalize(uint32_t (&ph)[4][8], const float (&s)[4][4]) {
  #pragma unroll
  for (int i = 0; i < 4; i++) {
    const float i0 = rcp(s[i][0]), i1 = rcp(s[i][2]);
    const uint32_t n0 = pack_bf16(i0, i0), n1 = pack_bf16(i1, i1);
    #pragma unroll
    for (int k = 0; k < 4; k++) { ph[i][2*k] = mul_bf16x2(ph[i][2*k], n0); ph[i][2*k+1] = mul_bf16x2(ph[i][2*k+1], n1); }
  }
}
__device__ __forceinline__ void split_bf16(float a, float b, uint32_t& hi, uint32_t& lo) { hi = pack_bf16(a, b); lo = pack_bf16(a - bf_lo(hi), b - bf_hi(hi)); }
__device__ __forceinline__ void put_colsums(uint32_t base, int lane, float a, float b, float c, float d) {
  uint32_t h0, l0, h1, l1;
  split_bf16(a, b, h0, l0); split_bf16(c, d, h1, l1);
  const uint32_t ad = base + (lane >> 1) * 128 + (lane & 1) * 8;
  sts64(ad, h0, h1); sts64(ad + 16, l0, l1); sts64(ad + 32, h0, h1); sts64(ad + 48, l0, l1);
  sts128(base + (lane >> 1) * 128 + 64 + (lane & 1) * 32, 0, 0, 0, 0); sts128(base + (lane >> 1) * 128 + 80 + (lane & 1) * 32, 0, 0, 0, 0);
}
__device__ __forceinline__ float reduce8(const float (&v)[8], int lane) {
  const bool b4 = lane & 16, b3 = lane & 8, b2 = lane & 4;
  float a[4], b[2];
  #pragma unroll
  for (int i = 0; i < 4; i++) a[i] = (b4 ? v[4 + i] : v[i]) + __shfl_xor_sync(~0u, b4 ? v[i] : v[4 + i], 16);
  #pragma unroll
  for (int i = 0; i < 2; i++) b[i] = (b3 ? a[2 + i] : a[i]) + __shfl_xor_sync(~0u, b3 ? a[i] : a[2 + i], 8);
  return (b2 ? b[1] : b[0]) + __shfl_xor_sync(~0u, b2 ? b[0] : b[1], 4);
}
__device__ __forceinline__ bool tag_bad(uint4 v, uint32_t tg) { return (((v.x ^ tg) | (v.y ^ tg) | (v.z ^ tg) | (v.w ^ tg)) & 3) != 0; }

__global__ void __launch_bounds__(512, 1) fused_kernel(const __grid_constant__ Params P) {
  extern __shared__ __align__(1024) uint8_t smem_raw[];
  const uint32_t sb = smem_u32(smem_raw);
  const int tid = threadIdx.x, lane = tid & 31;
  const int warp = __shfl_sync(~0u, tid >> 5, 0), wg = warp >> 2, wp = warp & 3;
  const int cp = blockIdx.x >> 1, cu = cp - 36, cd = (cu * 37) >> 8;
  const int gi = cp < 4 ? 0 : cu < 0 ? (cp - 4) & 7 : 1 + cu - 7 * cd, gx = cp < 4 ? 4 + cp : cu < 0 ? (cp - 4) >> 3 : 4 + cd;
  const int rank = blockIdx.x & 1, c = 64 * (gi & 1) + 8 * gx + (gi & 6) + rank;
  const int f = 16 * ((gi + 7) & 7) + 2 * gx + rank;
  const int m256 = c >> 4, nkv = c & 15, m128 = c >> 3, j = c & 7;
  const int ha = 4 * (nkv >> 1) + (nkv & 1);

  Scratch* const G = P.g;
  if ((sb & 0x3ffff) != SB0) asm volatile("trap;");

  TS0_DECL();
  if (warp == 12) {
    const bool el = elect_one();
    TS0_READ();
    if (el) {
      #pragma unroll
      for (int i = 0; i < 4; i++) mbar_init(sb + B_FULLKV + 8 * i, 1);
      asm volatile("fence.mbarrier_init.release.cluster;" ::: "memory");
      fence_async_smem();
      #pragma unroll
      for (int s = 0; s < NPRE; s++) {
        const uint32_t st = sb + s * KV_STAGE, fb = sb + B_FULLKV + 8 * s;
        mbar_expect_tx(fb, KV_STAGE);
        tma_4d(st + 32768, &P.wkv, 0, 64 * s, nkv, 1, fb);
        tma_2d(st, &P.x128, 64 * s, 256 * m256, fb);
        tma_2d(st + 16384, &P.x128, 64 * s, 256 * m256 + 128, fb);
      }
    }
  } else if (tid == 0) {
    #pragma unroll
    for (int i = 0; i < 22; i++) mbar_init(sb + B_EMPTYKV + 8 * i, i >= 20 ? 4 : i < 4 ? 12 : (i >= 9 && i < 14) ? 4 : i == 17 || i == 18 ? 2 : 1);
    #pragma unroll
    for (int i = 0; i < 25; i++) mbar_init(sb + B_F + 8 * i, i > 20 ? 2 : i != 18 ? 1 : 8);
    #pragma unroll
    for (int i = 0; i < 16; i++) mbar_init(sb + B_FULLA + 8 * i, i < 11 ? 1 : i == 11 ? 2 : 4);
    asm volatile("fence.mbarrier_init.release.cluster;" ::: "memory");
    fence_async_smem();
  }
  __syncthreads();
  cluster_arrive();

  if (wg == 3) {
    asm volatile("setmaxnreg.dec.sync.aligned.u32 32;");
    cluster_wait();
    const bool el = elect_one();
    const uint64_t ef = policy_evict_first();
    auto fetch_o = [&](int i0, uint32_t so, uint32_t par) {
      uint32_t ready = 0;
      const bf16* base = G->o + (m128 * 16 + (i0 >> 3)) * 8192 + rank * 4096;
      const bf16* hint = base + (((j & 6) + (lane >> 2)) & 7) * 16384 + (lane & 3) * 1024 + 966;
      #pragma unroll 1
      for (int i = i0 & 7; i < 8; i++) {
        uint32_t it = 0;
        while (((ready >> (4 * i)) & 15) != 15 && ++it < POLL_LIMIT) ready = __ballot_sync(~0u, ld32_rlx(hint) != ~0u);
        if (i0 == 2) {
          if (i == 2 && el) TS(rank ? 31 : 10);
        } else if (i == 0) bar_sync(NB_L0, 64);
        mbar_wait(sb + B_EMPTY5 + so, par);
        if (el) {
          bulk_g2s_mc(sb + so * 4096 + rank * 8192, base + (((j & 6) + i) & 7) * 16384, 8192, sb + B_FULLA + 2 * so + 8 * rank, ef);
          if (i == (i0 & 7)) TS(i0 == 2 ? (rank ? 4 : 12) : (rank ? 9 : 13));
        }
        so += 8;
        if (so == 40) { so = 0; par ^= 1; }
      }
    };
    if (wp == 0) {
      {
        #pragma unroll 1
        for (int kb = NPRE; kb < 16; kb++) {
          const uint32_t st = sb + (kb & 3) * KV_STAGE, fb = sb + B_FULLKV + 8 * (kb & 3);
          mbar_wait(fb + (B_EMPTYKV - B_FULLKV), ~(kb >> 2) & 1);
          if (el) {
            mbar_expect_tx(fb, KV_STAGE);
            tma_2d_mc(st + rank * 16384, &P.x128, 64 * kb, 256 * m256 + 128 * rank, fb);
            tma_4d_h(st + 32768, &P.wkv, 0, 64 * kb, nkv, 1, fb, ef);
          }
        }
        TS0_WRITE();
        uint64_t ord = 0xf3120edcba987654ull;
        uint32_t so = 0, par = 1;
        #pragma unroll 1
        for (int i = 0; i < 16; i++) {
          const uint32_t st = sb + so * 4096, fb = sb + B_FULL5 + so;
          const int k0 = (64 * (uint32_t)ord + 128 * (j & 6)) & 960;
          mbar_wait(i < 5 ? sb + B_EMPTYKV + so - (i > 1 ? 8 : 0) : fb + (B_EMPTY5 - B_FULL5), par);
          if (el) {
            mbar_expect_tx(fb, R5);
            tma_2d_mc_h(st + rank * 8192, &P.x64, k0, 128 * m128 + 64 * rank, fb, ef);
            tma_3d_h(st + 16384, &P.wq, 0, k0, 2 * j, fb, ef);
          }
          ord >>= 4; so += 8;
          if (so == 40) { so = 0; par ^= 1; }
        }
        #pragma unroll 1
        for (int i = 0; i < 16; i++) {
          const uint32_t fb = sb + B_FULL5 + so, fa = sb + B_FULLA + 2 * so, na = i == rank ? 0 : 8192;
          if (i == 1) { if (el) mbar_arrive(sb + B_QL); mbar_wait2(sb + B_FULL5 + 16, 0, sb + B_FULL5 + 24, 0); mbar_wait(sb + B_FULL5 + 32, 0); if (el) mbar_arrive(sb + B_R); }
          mbar_wait(fb + (B_EMPTY5 - B_FULL5), par);
          if (el) {
            mbar_expect_tx(fb, 16384);
            tma_5d_h(sb + so * 4096 + 16384, &P.wo, 128 * j, 128 * (((j & 6) + i) & 7) + 4 * (i & 8), fb, ef);
            tma_5d_h(sb + so * 4096 + 24576, &P.wo, 128 * j + 64, 128 * (((j & 6) + i) & 7) + 4 * (i & 8), fb, ef);
            mbar_expect_tx(fa, na); mbar_expect_tx(fa + 8, na);
          }
          so += 8;
          if (so == 40) { so = 0; par ^= 1; }
        }
        mbar_wait(sb + B_EMPTY5 + 16, 1); if (el) mbar_arrive(sb + B_DR);
        mbar_wait(sb + B_EMPTY5 + 24, 1); if (el) mbar_arrive(sb + B_DR + 8);
      }
    } else if (wp == 3) {
      const uint32_t t_start = (uint32_t)clock();
      if (el) {
        mbar_expect_tx(sb + B_W, 12288);
        #pragma unroll 1
        for (int i = 0; i < 6; i++) tma_2d(sb + (i == 0 ? OFF_WPHIK : i == 1 ? OFF_WPHIK1 : OFF_WPHIQ + 2048 * (i - 2)), &P.phi, 0, 32 * (i < 2 ? 2 * nkv + i : 4 * j + 2 * (i & 1) + ((i - 2) >> 1)), sb + B_W);
        prefetch_map(&P.x64); prefetch_map(&P.wq); prefetch_map(&P.wo);
        prefetch_map(&P.wd); prefetch_map(&P.wg); prefetch_map(&P.wu);
      }
      const uint32_t ep1 = ld32_rlx(&G->epoch) + 1;
      #pragma unroll 1
      for (int i = 0; i < 8; i++) {
        st128_rlx(&G->cand[(m128 * 8 + i) * DM + (lane >> 4) * 512 + 64 * j + 4 * (lane & 15)], ~0u, ~0u, ~0u, ~0u);
        if (f < NFFN) st128_rlx(&G->ypart[f * DM + 128 * i + 4 * lane], ~0u, ~0u, ~0u, ~0u);
      }
      if (lane < 16) st128_rlx(&G->rstat[16 * c + lane], 0, 0, 0, 0);
      if (lane < 8) st128_rlx(&G->key[(4 * j + (lane >> 1)) * 128 + m128 * 8 + 4 * (lane & 1)], 0, 0, 0, 0);
      if (c < 32) {
        #pragma unroll 1
        for (int i = lane; i < KVP; i += 32) st128_rlx(&G->kvacc[(ha + 2 * m256) * KVP + i], 0, 0, 0, 0);
      }
      fence_gpu();
      bar_arrive(NB_ZERO, 160);
      if (el) {
        #pragma unroll 1
        for (int i = 0; i < 30; i++) {
          while ((uint32_t)clock() - t_start < (uint32_t)(PF_T0 + PF_DT * i)) __nanosleep(64);
          if (i < 4) { bulk_prefetch(P.wqkv + (size_t)(256 * i + c) * (3 * DM), 2048); bulk_prefetch(P.wqkv + (size_t)(256 * i + 128 + c) * (3 * DM), 2048); }
          else if (i < 6) bulk_prefetch(P.wo_p + (size_t)c * 8192 + (i - 4) * 4096, 8192);
          else if ((TMASK >> (i - 6)) & 1) {
            const int k = i - 6;
            if (f < NFFN) {
              if (k < 16) {
                #pragma unroll 1
                for (int e = 0; e < 4; e++) tma_2d(sb + OFF_T, rank ? &P.tu : &P.tg, 32 * (f & ~1), 64 * k + 16 * e, sb + B_T);
              } else { tma_2d(sb + OFF_T, &P.td, 0, 256 * f + 32 * (k - 16), sb + B_T); tma_2d(sb + OFF_T, &P.td, 0, 256 * f + 32 * (k - 16) + 16, sb + B_T); }
            }
          }
          else if (!((PMASK >> (i - 6)) & 1)) {}
          else if (i < 22) bulk_prefetch(((i & 1) ? P.wu_p : P.wg_p) + (size_t)((i - 6) >> 1) * 458752 + c * 3584, 7168);
          else bulk_prefetch(P.wd_p + (size_t)(i - 22) * 458752 + c * 3584, 7168);
        }
      }
      __syncwarp();
      mbar_wait(sb + B_AUXQ, 0);
      for (uint32_t it = 0; __any_sync(~0u, ld32_rlx(&G->oset[m128 * 32 + (lane & 15)]) != ep1) && it < POLL_LIMIT; it++) {}
      fence_acquire_gpu();
      if (el) mbar_arrive(sb + B_OS);
      mbar_wait(sb + B_RX, 0);
      fetch_o(2, 24, 0);
      bar_arrive(NB_L0, 64);
    } else {
      const int half = wp - 1;
      const uint32_t ep1 = ld32_rlx(&G->epoch) + 1, tg = ep1 & 3;
      {
        uint32_t it = 0;
        sts128(sb + OFF_ONES + half * 512 + lane * 16, 0x3f803f80u, 0x3f803f80u, 0x3f803f80u, 0x3f803f80u);
        mbar_wait(sb + B_W, 0);
        #pragma unroll 1
        for (int i = lane; i < 1024; i += 32) { st128_rlx(G->o + (m128 * 16 + 2 * j + half) * 8192 + 8 * i, ~0u, ~0u, ~0u, ~0u); __nanosleep(RST_STEP); }
        bar_sync(NB_PUB, 192);
        const uint4* src = reinterpret_cast<const uint4*>(&G->stats[256 * m256 + 128 * half]) + lane;
        const uint4* srk = reinterpret_cast<const uint4*>(&G->cskv[128 * nkv]) + lane;
        uint4 v0, v1, vk;
        it = 0;
        do { v0 = ld128_rlx(src); v1 = ld128_rlx(src + 32); vk = ld128_rlx(srk); }
        while ((tag_bad(v0, tg) || tag_bad(v1, tg) || tag_bad(vk, tg)) && ++it < POLL_LIMIT);
        fence_acquire_gpu();
        if (half) put_colsums(sb + OFF_BXK, lane, untag(vk.x), untag(vk.y), untag(vk.z), untag(vk.w));
        #pragma unroll
        for (int i = 0; i < 2; i++) {
          const uint4 v = i ? v1 : v0;
          uint32_t hi, lo;
          split_bf16(-0.5f * untag(v.x), -0.5f * untag(v.z), hi, lo);
          const uint32_t h0 = __byte_perm(hi, hi, 0x1010), h1 = __byte_perm(hi, hi, 0x3232), l0 = __byte_perm(lo, lo, 0x1010), l1 = __byte_perm(lo, lo, 0x3232);
          const uint32_t a = sb + OFF_AXK + half * 2048 + i * 1024 + lane * 32;
          sts128(a, h0, l0, 0, 0); sts128(a + 16, h1, l1, 0, 0);
          sts64(sb + OFF_RS256 + half * 512 + i * 256 + lane * 8, v.y & ~3u, v.w & ~3u);
          if (half == (m128 & 1)) {
            const uint32_t aq = sb + OFF_AXQ + i * 1024 + lane * 32;
            sts128(aq, h0, l0, 0, 0); sts128(aq + 16, h1, l1, 0, 0);
            sts64(sb + OFF_RSQ + i * 256 + lane * 8, v.y & ~3u, v.w & ~3u);
          }
        }
        fence_async_smem();
        __syncwarp();
        if (el) { sts32(sb + OFF_EP, ep1); mbar_arrive(sb + B_AUX); if (!half) TS(1); }
        fence_gpu();
        __syncwarp();
        if (el) { st32_rlx(&G->oset[m128 * 32 + 2 * j + half], ep1); if (half) mbar_arrive(sb + B_AUXQ); }
        if (!half) {
          const uint4* src = reinterpret_cast<const uint4*>(&G->csq[128 * j]) + lane;
          uint4 v0, v1, v2, v3;
          do { v0 = ld128_rlx(src); v1 = ld128_rlx(src + DM / 4); v2 = ld128_rlx(src + DM / 2); v3 = ld128_rlx(src + 3 * DM / 4); }
          while ((tag_bad(v0, tg) || tag_bad(v1, tg) || tag_bad(v2, tg) || tag_bad(v3, tg)) && ++it < POLL_LIMIT);
          put_colsums(sb + OFF_BXQ, lane, (untag(v0.x) + untag(v1.x)) + (untag(v2.x) + untag(v3.x)), (untag(v0.y) + untag(v1.y)) + (untag(v2.y) + untag(v3.y)),
                      (untag(v0.z) + untag(v1.z)) + (untag(v2.z) + untag(v3.z)), (untag(v0.w) + untag(v1.w)) + (untag(v2.w) + untag(v3.w)));
          fence_async_smem();
          __syncwarp();
          if (el) mbar_arrive(sb + B_AUXQ);
        }
      }
      if (half == 0) mbar_wait(sb + B_OS, 0);
      auto put_gu = [&](int e, uint32_t dst) { mbar_expect_tx(sb + B_F + 8 * e, 16384); tma_2d(dst, &P.wg, 32 * f, 128 * e, sb + B_F + 8 * e); tma_2d(dst + 8192, &P.wu, 32 * f, 128 * e, sb + B_F + 8 * e); };
      if (half && f < NFFN_L) {
        if (Q0L) mbar_wait(sb + B_UO + 8 * Q0L - 8, 0);
        mbar_wait2(sb + B_KD, 0, sb + B_QL, 0);
        if (el) put_gu(0, sb + OFF_X + 16384);
      }
      if (!half) { mbar_wait(sb + B_UO + 8 + 8 * rank, 0); fetch_o(8, 32, 1); }
      else if (f < NFFN_L) {
        mbar_wait2(sb + B_UO, 0, sb + B_UO + 8, 0);
        mbar_wait(sb + B_UO + 24, 0);
        uint32_t t0 = (uint32_t)clock() - FF_DT + FF_T0;
        #pragma unroll 1
        for (int i = 0; i < 11; i++) {
          const uint32_t dst = sb + 16384 * ((0x7654cadcadcull >> (4 * i)) & 15);
          if (i >= 3) mbar_wait(sb + B_WC + 8 * (i < 7 ? i - 3 : (i + 1) >> 1), 0);
          while ((uint32_t)clock() - t0 < (uint32_t)FF_DT) __nanosleep(32);
          t0 = (uint32_t)clock();
          TK(48 + i);
          if (el) {
            if (i < 4) { mbar_expect_tx(sb + B_WD + 8 * i, 16384); tma_3d_h(dst, &P.wd, 0, 32 * f, 4 * i, sb + B_WD + 8 * i, ef); }
            else put_gu(i - 3, dst);
          }
        }
      }
      __syncwarp();
    }
    {
      const int ch = lane & 15, rb = 32 * wp + (lane >> 4);
      const uint32_t src = sb + R5 + (ch >> 3) * 16384;
      bf16* dst = P.out_p + (size_t)(128 * m128) * DM + 128 * j + 8 * ch;
      __syncwarp();
      mbar_wait(sb + B_OUT + 8 * wp, 0);
      const float2 ex = lds64f(sb + OFF_EXC + 8 * wp);
      if (OUT_L) mbar_wait(sb + B_XS, 0);
      #pragma unroll 1
      for (int i = 0; i < 32; i += 2 * OUT_U) {
        uint4 v[OUT_U];
        #pragma unroll
        for (int e = 0; e < OUT_U; e++) { const int r = rb + i + 2 * e; v[e] = lds128(src + r * 128 + (((ch ^ r) & 7) << 4)); }
        #pragma unroll
        for (int e = 0; e < OUT_U; e++) { const int r = rb + i + 2 * e; if (r != __float_as_int(i < 16 ? ex.x : ex.y)) *reinterpret_cast<uint4*>(dst + r * DM) = v[e]; }
        if (OUT_NS) __nanosleep(OUT_NS);
      }
      if (wp == 0) { TK(63); }
      mbar_wait(sb + B_XS, 0);
      const int row = 2047 - (__float_as_uint(ldsf(sb + OFF_KEY)) & 2047) - 128 * m128, r = __float_as_int(lane < 16 ? ex.x : ex.y);
      if (r != row) *reinterpret_cast<uint4*>(dst + r * DM) = lds128(src + r * 128 + (((ch ^ r) & 7) << 4));
    }
    __syncwarp();
    cluster_arrive(); cluster_wait();
    return;
  }

  asm volatile("setmaxnreg.inc.sync.aligned.u32 160;");
  cluster_wait();
  const int t = tid & 127, g = lane >> 2;
  const uint32_t sa = (16 * wp + (lane & 15)) * 128 + (((lane >> 4) ^ (lane & 7)) << 4);

  if (wg == 2) {
    float s[2] = {0.f, 0.f}, s2[2] = {0.f, 0.f}, ck[8] = {0.f, 0.f, 0.f, 0.f, 0.f, 0.f, 0.f, 0.f}, cs[8] = {0.f, 0.f, 0.f, 0.f, 0.f, 0.f, 0.f, 0.f};
    const uint32_t ebr = mapa(sb + B_EMPTYKV, lane & 1), tg = (ld32_rlx(&G->epoch) + 1) & 3;
    auto addx = [&](const uint4 v) {
      const uint32_t w[4] = {v.x, v.y, v.z, v.w};
      #pragma unroll
      for (int e = 0; e < 4; e++) { const float a = bf_lo(w[e]), d = bf_hi(w[e]); s[0] += a; s[1] += d; s2[0] = fmaf(a, a, s2[0]); s2[1] = fmaf(d, d, s2[1]); }
    };
    auto addc = [&](const uint4 v, float (&o)[8]) {
      o[0] += bf_lo(v.x); o[1] += bf_hi(v.x); o[2] += bf_lo(v.y); o[3] += bf_hi(v.y); o[4] += bf_lo(v.z); o[5] += bf_hi(v.z); o[6] += bf_lo(v.w); o[7] += bf_hi(v.w);
    };
    {
      const uint32_t ra = (16 * nkv + (t >> 3)) * 128 + (t & 7) * 16;
      const uint32_t ca = 32768 + (m256 >> 2) * 8192 + (t >> 1) * 128 + (((2 * (m256 & 3) + (t & 1)) ^ ((t >> 1) & 7)) << 4);
      const bf16* gx = P.x + (size_t)(256 * m256 + 16 * nkv + (t >> 3)) * DM + 640 + (t & 7) * 8;
      const bf16* gw = P.wqkv + (size_t)(640 + (t >> 1)) * (3 * DM) + (1 + (m256 >> 2)) * DM + 64 * nkv + 16 * (m256 & 3) + 8 * (t & 1);
      uint4 u[4];
      #pragma unroll
      for (int e = 0; e < 4; e++) u[e] = make_uint4(0, 0, 0, 0);
      #pragma unroll 1
      for (int kb = 0; kb < 10; kb++) {
        const uint32_t st = sb + (kb & 3) * KV_STAGE;
        mbar_wait(sb + B_FULLKV + 8 * (kb & 3), (kb >> 2) & 1);
        const uint4 x0 = lds128(st + ra), w0 = lds128(st + ca);
        addx(x0); addc(w0, ck);
        __syncwarp();
        if (lane < 2) mbar_arrive_remote(ebr + 8 * (kb & 3), 1);
        if ((SKM >> kb) & 1) {
          addx(u[0]); addx(u[1]); addc(u[2], ck); addc(u[3], ck);
          if (kb < 9) {
            u[0] = ld128_keep(gx); u[1] = ld128_keep(gx + 64); u[2] = ld128_keep(gw); u[3] = ld128_keep(gw + 64 * 3 * DM);
            gx += 128; gw += 128 * 3 * DM;
          }
        }
      }
    }
    TK(82);
    const uint32_t scr = sb + OFF_SCR + 128;
    float sx = s[0] + s[1], sq = s2[0] + s2[1];
    #pragma unroll
    for (int o = 1; o < 8; o <<= 1) { sx += __shfl_xor_sync(~0u, sx, o); sq += __shfl_xor_sync(~0u, sq, o); }
    float v = reduce8(ck, lane);
    v += __shfl_xor_sync(~0u, v, 2);
    if (!(lane & 2)) stsf(scr + (wp * 16 + 8 * (lane & 1) + (lane >> 2)) * 4, v);

    bar_sync(NB_ZERO, 160);
    if ((lane & 7) == 0) {
      const float mean = sx * (1.f / DM);
      st64_rlx(&G->stats[256 * m256 + 16 * nkv + (t >> 3)], tagw(mean, tg), tagw(rsqrtf(fmaxf(sq * (1.f / DM) - mean * mean, 0.f) + 1e-5f), tg));
    }
    if (wp == 1 && lane < 16) {
      const uint32_t a = scr + lane * 4;
      st32_rlx(&G->cskv[128 * nkv + 16 * m256 + lane], tagw((ldsf(a) + ldsf(a + 64)) + (ldsf(a + 128) + ldsf(a + 192)), tg));
    }
    __syncwarp();
    bar_arrive(NB_PUB, 192);
    TSW(23);
    const uint4 wv = ld128_keep(P.wr + t * 8);
    #pragma unroll 1
    for (int i = 0; i < 2; i++) {
      const bf16* gq = P.wqkv + (size_t)(256 * (c >> 5) + 128 * i + (t >> 2)) * (3 * DM) + 32 * (c & 31) + 8 * (t & 3);
      const uint4 u0 = ld128_keep(gq), u1 = ld128_keep(gq + 32 * 3 * DM), u2 = ld128_keep(gq + 64 * 3 * DM), u3 = ld128_keep(gq + 96 * 3 * DM);
      addc(u0, cs); addc(u1, cs); addc(u2, cs); addc(u3, cs);
    }
    float sw = (bf_lo(wv.x) + bf_hi(wv.x)) + (bf_lo(wv.y) + bf_hi(wv.y)) + (bf_lo(wv.z) + bf_hi(wv.z)) + (bf_lo(wv.w) + bf_hi(wv.w));
    #pragma unroll
    for (int o = 16; o; o >>= 1) sw += __shfl_xor_sync(~0u, sw, o);
    if (lane == 0) stsf(sb + OFF_SUMWR + wp * 4, sw);
    if ((t >> 4) == j) {
      const uint32_t a = sb + OFF_WR + (t & 15) * 32;
      sts128(a, wv.x << 16, wv.x & 0xffff0000u, wv.y << 16, wv.y & 0xffff0000u);
      sts128(a + 16, wv.z << 16, wv.z & 0xffff0000u, wv.w << 16, wv.w & 0xffff0000u);
    }
    v = reduce8(cs, lane);
    bar_sync(NB_WG2, 128);
    stsf(scr + (wp * 32 + 8 * (lane & 3) + (lane >> 2)) * 4, v);
    bar_sync(NB_WG2, 128);
    if (wp == 0) {
      const uint32_t a = scr + lane * 4;
      st32_rlx(&G->csq[(c >> 5) * DM + 32 * (c & 31) + lane], tagw((ldsf(a) + ldsf(a + 128)) + (ldsf(a + 256) + ldsf(a + 384)), tg));
    }
  }

  uint32_t xr[32];
  {
    const bool isq = wg == 2;
    float acc[2][64];
    {
      const uint32_t emptyb = mapa(sb + (isq ? B_EMPTY5 : B_EMPTYKV), t & 1);
      if (!isq) {
        mbar_wait(sb + B_FULLKV, 0);
        if (wg == 0) { TSW(2); }
        #pragma unroll 1
        for (int kb = 0; kb < 16; kb++) {
          if (wg == 0) { TK(kb); }
          const uint32_t da = dlo(SB0, 16) + wg * 1024 + (kb & 3) * (KV_STAGE >> 4), db = dlo(SB0 + 32768, 8192) + (kb & 3) * (KV_STAGE >> 4);
          wg_fence();
          #pragma unroll
          for (int k = 0; k < 4; k++) {
            wgmma_ss_n128<0, 1, H128, H128>(acc[0], da + 2 * k, db + 128 * k, k > 0 || kb != 0);
            wgmma_ss_n128<0, 1, H128, H128>(acc[1], da + 512 + 2 * k, db + 128 * k, k > 0 || kb != 0);
          }
          wg_commit();
          wg_wait<1>();
          if (kb > 0 && t < 2) mbar_arrive_remote(emptyb + 8 * ((kb - 1) & 3), kb > 10 ? 3 : 1);
          if (kb < 15) mbar_wait(sb + B_FULLKV + 8 * ((kb + 1) & 3), ((kb + 1) >> 2) & 1);
          if (kb == 15 - LAG && wg == 1) bar_sync(NB_WG01, 256);
        }
        bar_arrive(wg ? NB_QGO : NB_WG01, 256);
      } else {
        uint32_t so = 0, po = 0, par = 0;
        mbar_wait(sb + B_FULL5, 0);
        bar_sync(NB_QGO, 256);
        TSW(11);
        #pragma unroll 1
        for (int kb = 0; kb < 16; kb++) {
          TK(16 + kb);
          const uint32_t da = dlo(SB0, 16) + so * 256, db = dlo(SB0 + 16384, 8192) + so * 256;
          #pragma unroll
          for (int k = 0; k < 4; k++) {
            wg_fence();
            wgmma_ss_n128<0, 1, H128, H128>(acc[0], da + 2 * k, db + 128 * k, k > 0 || kb != 0);
            wgmma_ss_n128<0, 1, H128, H128>(acc[1], da + 512 + 2 * k, db + 128 * k, k > 0 || kb != 0);
            wg_commit();
            if (k == 1 && kb > 0 && t < 2) mbar_arrive_remote(emptyb + po, 2);
            if (k == 3) {
              po = so; so += 8;
              if (so == 40) { so = 0; par ^= 1; }
              if (kb < 15) mbar_wait(sb + B_FULL5 + so, par);
            }
            if ((QW >> k) & 1) wg_wait<2>(); else wg_wait<1>();
          }
        }
        mbar_wait(sb + B_AUXQ, 0);
      }
      mbar_wait(sb + B_AUX, 0);
      const uint32_t xa = dlo(SB0, 0) + (isq ? OFF_AXQ >> 4 : (OFF_AXK >> 4) + wg * 128), xb = dlo(SB0, 0) + (isq ? OFF_BXQ >> 4 : OFF_BXK >> 4);
      wg_fence();
      wgmma_sa_n128<0, 1, H0, H0>(acc[0], xa, xb);
      wgmma_sa_n128<0, 1, H0, H0>(acc[1], xa + 64, xb);
      wg_commit();
      if (isq) mbar_wait(sb + B_RC, 0);
      wg_wait<0>();
      if (t < 2) mbar_arrive_remote(emptyb + (isq ? 0 : 24), isq ? 2 : 3);
      if (wg != 1) { TSW(wg ? 8 : 3); }
      fence_regs(acc[0]); fence_regs(acc[1]);
    }
    if (isq) {
      #pragma unroll
      for (int i = 0; i < 4; i++) {
        const uint32_t ta = sb + (i < 2 ? (1 + rank) * R5 : OFF_X) + sa + (i & 1) * 8192;
        if (i == 1) mbar_wait(sb + B_RC + 8, 0);
        #pragma unroll
        for (int k = 0; k < 4; k++) {
          const float* a = &acc[i & 1][16 * (i >> 1) + 32 * (k >> 1) + 8 * (k & 1)];
          stsm4(ta ^ (k << 5), pack_bf16(a[0], a[1]), pack_bf16(a[2], a[3]), pack_bf16(a[4], a[5]), pack_bf16(a[6], a[7]));
        }
        if (i < 2) { fence_async_smem(); bar_arrive(NB_Q0 + i, 256); }
      }
      TSW(26);
    } else {
      const uint32_t stg = sb + OFF_X + (1 - wg) * 24576;
      const uint32_t va = stg + 16384 + (16 * wp + (lane & 15)) * 64 + (((lane >> 4) ^ ((lane >> 1) & 3)) << 4);
      const uint32_t ra = sb + OFF_RS256 + (128 * wg + 16 * wp + g) * 4;
      const float rs[4] = {ldsf(ra), ldsf(ra + 32), ldsf(ra + 256), ldsf(ra + 288)};
      float p[2][16];
      uint32_t vf[16], kf[2][16];
      auto project = [&](const uint32_t (&f)[16], uint32_t db) {
        wg_fence();
        #pragma unroll
        for (int i = 0; i < 2; i++) {
          wgmma_rs_n32<1, H64>(p[i], f[8*i], f[8*i+1], f[8*i+2], f[8*i+3], db, 0);
          wgmma_ra_n32<1, H64>(p[i], f[8*i+4], f[8*i+5], f[8*i+6], f[8*i+7], db + 64);
        }
        wg_commit();
      };
      auto fold = [&](uint32_t (&f)[16], int col, float sc) {
        #pragma unroll
        for (int i = 0; i < 16; i++) {
          const float r = rs[2 * (i >> 3) + (i & 1)] * sc;
          f[i] = pack_bf16(acc[i >> 3][col + 2 * (i & 7)] * r, acc[i >> 3][col + 2 * (i & 7) + 1] * r);
          asm volatile("" : "+r"(f[i]));
        }
      };
      auto put_v = [&](const uint32_t (&f)[16]) {
        #pragma unroll
        for (int k = 0; k < 4; k++) stsm4((va ^ ((k & 1) << 5)) + (k >> 1) * 4096, f[4*k], f[4*k+1], f[4*k+2], f[4*k+3]);
      };
      fold(vf, 48, 1.f);
      mbar_wait(sb + B_W, 0);
      fold(kf[0], 0, LOG2E);
      #pragma unroll
      for (int i = 0; i < 32; i++) p[i >> 4][i & 15] = acc[i >> 4][i & 15];
      project(kf[0], dlo(SB0 + OFF_WPHIK, 16));
      mbar_wait(sb + B_W, 0);
      {
        uint32_t v0[16];
        fold(kf[1], 16, LOG2E);
        fold(v0, 32, 1.f);
        if (wg == 1) bar_sync(NB_DN, 256);
        put_v(v0);
      }
      wg_wait<0>();
      fence_regs(p[0]); fence_regs(p[1]);
      if (wg == 1) bar_arrive(NB_WG01, 256);
      #pragma unroll 1
      for (int h = 0; h < 2; h++) {
        uint32_t ph[4][8];
        float rsum[4][4];
        dual_exp2(p, ph);
        wg_fence();
        row_sums(rsum, ph, dlo(SB0 + OFF_ONES, 128));
        wg_commit();
        if (wg == 0 && h == 0) { bar_arrive(NB_DN, 256); bar_sync(NB_WG01, 256); }
        if (h == 1) {
          if (wg == 1) bar_sync(NB_DN, 256);
          put_v(vf);
        }
        wg_wait<0>();
        #pragma unroll
        for (int i = 0; i < 4; i++) fence_regs(rsum[i]);
        if (__builtin_expect(__any_sync(~0u, !((rsum[0][0] + rsum[0][2]) + (rsum[1][0] + rsum[1][2]) + (rsum[2][0] + rsum[2][2]) + (rsum[3][0] + rsum[3][2]) < EXP_LIM)), 0)) {
          dual_exp2_shifted(p, ph);
          #pragma unroll
          for (int i = 0; i < 8; i++) {
            const uint32_t* f = &ph[i >> 1][i & 1];
            float a = (bf_lo(f[0]) + bf_hi(f[0])) + (bf_lo(f[2]) + bf_hi(f[2])) + (bf_lo(f[4]) + bf_hi(f[4])) + (bf_lo(f[6]) + bf_hi(f[6]));
            a += __shfl_xor_sync(~0u, a, 1);
            rsum[i >> 1][2 * (i & 1)] = a + __shfl_xor_sync(~0u, a, 2);
          }
        }
        if (h == 0) project(kf[1], dlo(SB0 + OFF_WPHIK1, 16));
        normalize(ph, rsum);
        #pragma unroll
        for (int i = 0; i < 8; i++) {
          const uint32_t* f = &ph[i >> 1][4 * (i & 1)];
          stsm4(((stg + sa) ^ ((i & 3) << 5)) + (i >> 2) * 8192, f[0], f[1], f[2], f[3]);
        }
        fence_async_smem();
        if (wg == h) {
          float kv[20];
          #pragma unroll
          for (int w = 0; w < 2; w++) {
            const uint32_t da = dlo(SB0 + OFF_X, 16) + (h ^ w ^ 1) * 1536, db = dlo(SB0 + OFF_X + 16384, OFF_ONES - OFF_X - 16384) - (h ^ w ^ 1) * (1536 * 65535);
            if (w) bar_sync(NB_ST, 256); else bar_sync(NB_L0 + h, 128);
            wg_fence();
            #pragma unroll
            for (int k = 0; k < 8; k++) {
              if (k == 0 && w == 0) wgmma_sz_n40<1, 1, H128, H64>(kv, da, db);
              else wgmma_sa_n40<1, 1, H128, H64>(kv, da + k * 128, db - k * (64 * 65535));
            }
            wg_commit();
          }
          float4* dst = &G->kvacc[(ha + 2 * h) * KVP + t];
          wg_wait<0>();
          fence_regs(kv);
          if (h == 0) bar_arrive(NB_DN, 256); else if (t == 0) mbar_arrive(sb + B_KD);
          kv[17] = kv[18];
          #pragma unroll
          for (int i = 0; i < 6; i++) red_add_f32x4(dst + 128 * i, kv[3*i], kv[3*i+1], kv[3*i+2], 1.f);
          TSW(29 + h);
        } else bar_arrive(NB_ST, 256);
        wg_wait<0>();
        fence_regs(p[0]); fence_regs(p[1]);
      }
    }
    {
      const uint4* src = reinterpret_cast<const uint4*>(&G->kvacc[(4 * j + wg) * KVP + t]);
      uint4 v[12];
      uint32_t it = 0, bad;
      do {
        bad = 0;
        #pragma unroll
        for (int i = 0; i < 12; i++) {
          v[i] = make_uint4(0, 0, 0, 0x41000000u);
          if (i < 6 || isq) v[i] = ld128_rlx(src + 128 * i);
          bad |= v[i].w ^ 0x41000000u;
        }
      } while (__any_sync(~0u, bad != 0) && ++it < POLL_LIMIT);
      mbar_wait(sb + B_KD, 0);
      #pragma unroll
      for (int e = 0; e < 2; e++) {
        if (e == 0 || isq) {
          float f[18];
          #pragma unroll
          for (int i = 0; i < 6; i++) { f[3*i] = __uint_as_float(v[6*e+i].x); f[3*i+1] = __uint_as_float(v[6*e+i].y); f[3*i+2] = __uint_as_float(v[6*e+i].z); }
          const uint32_t ka = sb + OFF_KVZ + (wg + e) * 5120 + wp * 1280 + lane * 16;
          stsm4(ka, pack_bf16(f[0], f[1]), pack_bf16(f[2], f[3]), pack_bf16(f[4], f[5]), pack_bf16(f[6], f[7]));
          stsm4(ka + 512, pack_bf16(f[8], f[9]), pack_bf16(f[10], f[11]), pack_bf16(f[12], f[13]), pack_bf16(f[14], f[15]));
          stsm2(ka + 1024, pack_bf16(f[16], 1.f), pack_bf16(f[17], 1.f));
        }
      }
    }
    if (!isq) {
      mbar_wait(sb + B_R, 0);
      #pragma unroll
      for (int k = 0; k < 8; k++) ldsm4(((sb + (1 + rank) * R5 + wg * 8192 + sa) ^ ((k & 3) << 5)) + (k >> 2) * 2 * R5, xr[4*k], xr[4*k+1], xr[4*k+2], xr[4*k+3]);
      fence_async_smem();
      __syncwarp();
      if (lane == 0) { mbar_arrive(sb + B_RC + 8 * wg); mbar_arrive_at(sb + B_RX, wg, 1); }
      if (wg == 1) bar_arrive(NB_DN, 256);
    } else {
      fence_async_smem();
      #pragma unroll
      for (int i = 0; i < 32; i++) asm volatile("mov.b32 %0, 0;" : "=r"(xr[i]));
    }
    TSW(wg == 0 ? 5 : wg == 1 ? 25 : 6);
    #pragma unroll 1
    for (int e = wg; e < wg + 1 + (wg >> 1); e++) {
      const int half = e >> 1, hh = e & 1, turn = e;
      const uint32_t ao = (half ? OFF_X : (1 + rank) * R5) + hh * 8192;
      float p[2][16];
      #pragma unroll
      for (int i = 0; i < 32; i++) asm volatile("mov.b32 %0, 0;" : "=f"(p[i >> 4][i & 15]));
      const float cc[2] = {ldsf(sb + OFF_RSQ + (64 * hh + 16 * wp + g) * 4) * LOG2E, ldsf(sb + OFF_RSQ + (64 * hh + 16 * wp + g + 8) * 4) * LOG2E};
      float m[2][4] = {{0.f, 0.f, 0.f, 0.f}, {0.f, 0.f, 0.f, 0.f}};
      uint32_t ph[2][8];
      auto exps = [&](int h) {
        #pragma unroll
        for (int k = 0; k < 8; k++) {
          const float c = cc[k & 1], mp = m[h][k & 1], mm = m[h][2 + (k & 1)];
          ph[0][k] = pack_bf16(ex2(fmaf(p[h][2*k], c, mp)), ex2(fmaf(p[h][2*k+1], c, mp)));
          ph[1][k] = pack_bf16(ex2(fmaf(p[h][2*k], -c, mm)), ex2(fmaf(p[h][2*k+1], -c, mm)));
        }
      };
      uint32_t shifted = 0;
      asm volatile("" : "+r"(shifted));
      #pragma unroll 1
      for (;;) {
        if (shifted) { row_extremes(p[0], cc, m[0]); row_extremes(p[1], cc, m[1]); }
        uint32_t first = shifted ^ 1;
        asm volatile("" : "+r"(first));
        if (first) {
          bar_sync(NB_Q0 + wg, isq ? 128 : 256);
          const uint32_t da = dlo(SB0, 16) + (ao >> 4), db = dlo(SB0 + OFF_WPHIQ, 16) + half * 256;
          wg_fence();
          #pragma unroll
          for (int h = 0; h < 2; h++) {
            wgmma_ss_n32<0, 1, H128, H64>(p[h], da + 4 * h, db + 128 * h, 0);
            wgmma_sa_n32<0, 1, H128, H64>(p[h], da + 4 * h + 2, db + 128 * h + 64);
          }
          wg_commit();
          if (e == 1 || e == 2) bar_sync(NB_TOK + e - 1, 256);
          wg_wait<0>();
        }
        TK(64 + 4 * turn);
        fence_regs(p[0]); fence_regs(p[1]);
        exps(0);
        float s2[4] = {0.f, 0.f, 0.f, 0.f};
        #pragma unroll
        for (int i = 0; i < 32; i++) s2[((i >> 1) & 1) + 2 * (i >> 4)] = fmaf(p[i >> 4][i & 15], p[i >> 4][i & 15], s2[((i >> 1) & 1) + 2 * (i >> 4)]);
        const float l0 = cc[0] * cc[0], l1 = cc[1] * cc[1];
        if (!__any_sync(~0u, !shifted & !((s2[0] * l0 < ARG_LIM2) & (s2[1] * l1 < ARG_LIM2) & (s2[2] * l0 < ARG_LIM2) & (s2[3] * l1 < ARG_LIM2)))) break;
        shifted = 1;
      }
      const uint32_t db = dlo(SB0 + OFF_KVZ, 128) + half * 640;
      float ac[4][20];
      auto numer = [&](int h, const uint32_t (&f)[2][8]) {
        wg_fence();
        #pragma unroll
        for (int i = 0; i < 2; i++) {
          wgmma_rz_n40<1, dhi(256, 0)>(ac[2*h+i], f[i][0], f[i][1], f[i][2], f[i][3], db + (2*h+i) * 160);
          wgmma_ra_n40<1, dhi(256, 0)>(ac[2*h+i], f[i][4], f[i][5], f[i][6], f[i][7], db + ((2*h+i) * 160 + 80));
        }
        wg_commit();
      };
      const uint32_t oa = (16 * wp + g) * 128 + (((lane & 3) ^ g) << 4), pb = mapa(sb, rank ^ 1);
      auto finish = [&](int h) {
        const float* ap = ac[2 * h]; const float* am = ac[2 * h + 1];
        const float ip0 = rcp(ap[17]), im0 = rcp(am[17]), ip1 = rcp(ap[19]), im1 = rcp(am[19]);
        const float d0 = rcp(fmaf(ap[16], ip0, fmaf(am[16], im0, 1e-6f))), d1 = rcp(fmaf(ap[18], ip1, fmaf(am[18], im1, 1e-6f)));
        const float a0 = ip0 * d0, b0 = im0 * d0, a1 = ip1 * d1, b1 = im1 * d1;
        #pragma unroll
        for (int r = 0; r < 2; r++) {
          const float a = r ? a1 : a0, b = r ? b1 : b0;
          uint32_t w[4];
          #pragma unroll
          for (int k = 0; k < 4; k++) w[k] = pack_bf16(fmaf(ap[4*k+2*r], a, am[4*k+2*r] * b), fmaf(ap[4*k+2*r+1], a, am[4*k+2*r+1] * b));
          const uint32_t off = (oa ^ (h << 6)) + r * 1024;
          st128_rlx(reinterpret_cast<uint8_t*>(G->o + (m128 * 16 + 2 * j + half) * 8192 + hh * 4096) + off, w[0], w[1], w[2], w[3]);
          if (!half) {
            sts128(sb + ao + off, w[0], w[1], w[2], w[3]);
            st_async128(pb + ao + off, w[0], w[1], w[2], w[3], pb + B_FULLA + 16 + 16 * rank + 8 * hh);
          }
        }
      };
      numer(0, ph);
      exps(1);
      if (wg == 0) bar_sync(NB_DN, 256);
      numer(1, ph);
      if (turn < 2) bar_arrive(NB_TOK + turn, 256);
      if (!half) mbar_wait(sb + B_FULLA + 16 + 16 * rank + 8 * hh, 0);
      wg_wait<1>();
      TK(65 + 4 * turn);
      fence_regs(ac[0]); fence_regs(ac[1]);
      finish(0);
      wg_wait<0>();
      fence_regs(ac[2]); fence_regs(ac[3]);
      finish(1);
      TK(66 + 4 * turn);
      fence_async_smem();
      __syncwarp();
      if (lane == 0) mbar_arrive(sb + B_UO + 8 * e);
      TK(67 + 4 * turn);
    }
    if (isq) cluster_arrive();
  }

  {
  int lane;
  asm volatile("mov.u32 %0, %%laneid;" : "=r"(lane));
  const int g = lane >> 2, q = lane & 3;
  if (wg < 2) {
    float h[64];
    {
      if (wg == 0) { TK(83); }
      #pragma unroll
      for (int i = 0; i < 32; i++) { h[2*i] = bf_lo(xr[i]); h[2*i+1] = bf_hi(xr[i]); }
      fence_regs(h);
      TK(80 + wg);
      const uint64_t seq = rank ? 0x1043210432104312ull : 0x1043210432104321ull;
      const uint32_t emptyb = mapa(sb + B_EMPTY5, t & 1);
      uint32_t s = 1 + rank, ps = 0;
      mbar_wait2(sb + B_FULL5 + 8 * s, 1, sb + B_UO + 8 * wg, 0);
      if (wg == 0) { TSW(14); }
      #pragma unroll 1
      for (int i = 0; i < 16; i++) {
        if (wg == 1 && i < 4) { TK(84 + i); }
        if (wg == 0) { TK(32 + i); }
        const uint32_t da = dlo(SB0, 16) + s * 2048 + wg * 512, db = dlo(SB0 + 16384, 8192) + s * 2048;
        wg_fence();
        #pragma unroll
        for (int k = 0; k < 4; k++) wgmma_sa_n128<0, 1, H128, H128>(h, da + k * 2, db + k * 128);
        wg_commit();
        const uint32_t ns = (uint32_t)(seq >> (4 * i + 4)) & 15;
        wg_wait<1>();
        if (i > 0 && t < 2) mbar_arrive_remote(emptyb + 8 * ps, 1);
        if (i < 15) mbar_wait2(sb + B_FULL5 + 8 * ns, (0x1f07 >> i) & 1, sb + B_FULLA + 16 * ns + 8 * wg, (0x41f0 >> i) & 1);
        if (i == 0) fence_async_smem();
        ps = s; s = ns;
      }
    }
    cluster_arrive();
    float2 wr[16];
    #pragma unroll
    for (int i = 0; i < 16; i++) wr[i] = lds64f(sb + OFF_WR + 32 * i + 8 * q);
    const int r0 = 64 * wg + 16 * wp + g;
    float sum0, sum1, dot0, dot1, sq0, sq1;
    uint32_t redo = 0;
    asm volatile("" : "+r"(redo));
    #pragma unroll 1
    for (;;) {
    if (redo) {
      wg_wait<0>();
      const int r = r0;
      #pragma unroll 1
      for (int n = 0; n < 16; n++) {
        const uint32_t* xp = reinterpret_cast<const uint32_t*>(P.x + (size_t)(128 * m128 + r) * DM + 128 * j + 8 * n) + q;
        const uint32_t x0 = xp[0], x1 = xp[4 * DM];
        float d0 = bf_lo(x0), d1 = bf_hi(x0), d2 = bf_lo(x1), d3 = bf_hi(x1);
        #pragma unroll 1
        for (int ks = 0; ks < 64; ks++) {
          const int kb = ks >> 2, kk = 16 * (ks & 3);
          const bf16* op = G->o + (m128 * 16 + kb) * 8192 + r * 64 + 2 * q;
          const int o0 = ((kk >> 3) ^ g) << 3;
          const uint16_t* w = reinterpret_cast<const uint16_t*>(P.wo_p) + (size_t)(128 * (kb >> 1) + 32 * (kb & 1) + ((kk & 16) >> 2) + 2 * (kk & 32) + 8 * q) * DM + 128 * j + 8 * n + g;
          const uint32_t b0 = w[0] | (w[DM] << 16), b1 = w[2 * DM] | (w[3 * DM] << 16);
          uint32_t a0, a1, a2, a3, it = 0;
          do { a0 = ld32_rlx(op + o0); a1 = ld32_rlx(op + 512 + o0); a2 = ld32_rlx(op + (o0 ^ 8)); a3 = ld32_rlx(op + 512 + (o0 ^ 8)); }
          while (max(max(a0, a1), max(a2, a3)) == ~0u && ++it < POLL_LIMIT);
          __syncwarp();
          mma16816(d0, d1, d2, d3, a0, a1, a2, a3, b0, b1);
        }
        #pragma unroll
        for (int i = 0; i < 60; i++) h[i] = h[i + 4];
        h[60] = d0; h[61] = d1; h[62] = d2; h[63] = d3;
      }
    }
    wg_wait<0>();
    fence_regs(h);
    if (wg == 0) { TSW(16); }
    sum0 = 0.f, sum1 = 0.f, dot0 = 0.f, dot1 = 0.f, sq0 = 0.f, sq1 = 0.f;
    #pragma unroll
    for (int i = 0; i < 16; i++) {
      sum0 += h[4*i] + h[4*i+1]; sum1 += h[4*i+2] + h[4*i+3];
      sq0 = fmaf(h[4*i], h[4*i], fmaf(h[4*i+1], h[4*i+1], sq0)); sq1 = fmaf(h[4*i+2], h[4*i+2], fmaf(h[4*i+3], h[4*i+3], sq1));
      dot0 = fmaf(h[4*i], wr[i].x, fmaf(h[4*i+1], wr[i].y, dot0)); dot1 = fmaf(h[4*i+2], wr[i].x, fmaf(h[4*i+3], wr[i].y, dot1));
    }
    if (!__any_sync(~0u, !redo & (h[0] != h[0] | h[2] != h[2]))) break;
    redo = 1;
    }
    float4* const rs = &G->rstat[128 * m128 + r0];
    {
      const bool up = q & 2;
      float a = up ? sum1 : sum0, b = up ? sq1 : sq0, d = up ? dot1 : dot0;
      a += __shfl_xor_sync(~0u, up ? sum0 : sum1, 2); b += __shfl_xor_sync(~0u, up ? sq0 : sq1, 2); d += __shfl_xor_sync(~0u, up ? dot0 : dot1, 2);
      a += __shfl_xor_sync(~0u, a, 1); b += __shfl_xor_sync(~0u, b, 1); d += __shfl_xor_sync(~0u, d, 1);
      if ((q & 1) == 0) red_add_f32x4(rs + 4 * q, a, b, d, 1.f);
    }
    bar_arrive(NB_G2E, 384);
    if (wg == 0) { TSW(24); }
    float rstd[2], bm[2];
    uint32_t best;
    {
      const float2 swa = lds64f(sb + OFF_SUMWR), swb = lds64f(sb + OFF_SUMWR + 8);
      const float sw = (swa.x + swa.y) + (swb.x + swb.y);
      uint4 a[2]; uint32_t it = 0, key[2];
      do { a[0] = ld128_rlx(rs); a[1] = ld128_rlx(rs + 8); } while (__any_sync(~0u, (a[0].w & a[1].w) != 0x41000000u) && ++it < POLL_LIMIT);
      #pragma unroll
      for (int i = 0; i < 2; i++) {
        const float mean = __uint_as_float(a[i].x) * (1.f / DM);
        rstd[i] = rsqrtf(fmaxf(__uint_as_float(a[i].y) * (1.f / DM) - mean * mean, 0.f) + 1e-5f);
        bm[i] = -mean * rstd[i];
        const uint32_t rr = __float_as_uint(fmaf(__uint_as_float(a[i].z), rstd[i], sw * bm[i]));
        key[i] = ((rr ^ ((uint32_t)((int32_t)rr >> 31) | 0x80000000u)) & ~2047u) | (2047 - 128 * m128 - r0 - 8 * i);
      }
      asm volatile("redux.sync.max.u32 %0, %1, 0xffffffff;" : "=r"(best) : "r"(max(key[0], key[1])));
    }
    if (wg == 0) { TSW(17); }
    const int slot = m128 * 8 + warp, win = ~best & 15;
    if (lane < 4) st32_rlx(&G->key[(4 * j + lane) * 128 + slot], best);
    if ((win & 7) == g) {
      const bool up = win & 8;
      const float ra = up ? rstd[1] : rstd[0], rb = up ? bm[1] : bm[0];
      uint32_t x[16];
      #pragma unroll
      for (int i = 0; i < 16; i++) x[i] = pack_bf16(fmaf(up ? h[4*i+2] : h[4*i], ra, rb), fmaf(up ? h[4*i+3] : h[4*i+1], ra, rb));
      #pragma unroll
      for (int i = 0; i < 4; i++) st128_rlx(&G->cand[slot * DM + 64 * j + 16 * i + 4 * q], x[4*i], x[4*i+1], x[4*i+2], x[4*i+3]);
    }
    __syncwarp();
    if (wg == 0) { TSW(27); }
    {
      bar_sync(NB_WG01, 256);
      const float a0 = 1.f + rstd[0], b0 = bm[0], a1 = 1.f + rstd[1], b1 = bm[1];
      #pragma unroll
      for (int k = 0; k < 8; k++)
        stsm4(((sb + R5 + wg * 8192 + sa) ^ ((k & 3) << 5)) + (k >> 2) * 16384,
              pack_bf16(fmaf(h[8*k], a0, b0), fmaf(h[8*k+1], a0, b0)),     pack_bf16(fmaf(h[8*k+2], a1, b1), fmaf(h[8*k+3], a1, b1)),
              pack_bf16(fmaf(h[8*k+4], a0, b0), fmaf(h[8*k+5], a0, b0)),   pack_bf16(fmaf(h[8*k+6], a1, b1), fmaf(h[8*k+7], a1, b1)));
      sts32(sb + OFF_EXC + 4 * warp, 16 * warp + win);
      __syncwarp();
      if (lane == 0) mbar_arrive(sb + B_OUT + 8 * (warp >> 1));
      if (lane < 16) {
        const uint4 v = lds128(sb + R5 + (lane >> 3) * 16384 + (16 * warp + win) * 128 + (((lane & 7) ^ (win & 7)) << 4));
        st128_rlx(&G->cand[slot * DM + 512 + 64 * j + 4 * lane], v.x, v.y, v.z, v.w);
      }
    }
    if (wg == 0) { TSW(28); }
    {
      uint32_t wa[8][4][4];
      const uint32_t wb = sb + 16384 * ((0x7654cadb >> (4 * warp)) & 15) + ((lane & 7) + ((lane >> 4) << 3)) * 64 + ((((lane >> 3) & 1) ^ ((lane >> 1) & 3)) << 4);
      auto getw = [&](int ks) {
        #pragma unroll
        for (int m = 0; m < 4; m++) ldsm4t((wb ^ ((m & 1) << 5)) + (m >> 1) * 8192 + ks * 1024, wa[ks][m][0], wa[ks][m][1], wa[ks][m][2], wa[ks][m][3]);
      };
      if (f < NFFN_L) mbar_wait(sb + B_F + 8 * warp, 0);
      if (warp == 7) { TK(60); }
      #pragma unroll
      for (int ks = 0; ks < GRES; ks++) getw(ks);
      if (wg == 0) { TSW(15); }
      bar_sync(NB_XS, 384);
      if (wg == 0) { TSW(19); }
      uint4 xs[4];
      #pragma unroll
      for (int i = 0; i < 4; i++) xs[i] = lds128(sb + OFF_XSEL + 256 * warp + 64 * i + 16 * q);
      float d[4][4];
      #pragma unroll
      for (int ks = 0; ks < 8; ks++) {
        if (ks >= 1 && GRES + ks - 1 < 8) getw(GRES + ks - 1);
        #pragma unroll
        for (int m = 0; m < 4; m++) {
          if (ks == 0) { d[m][0] = 0.f; d[m][1] = 0.f; d[m][2] = 0.f; d[m][3] = 0.f; }
          mma16816(d[m][0], d[m][1], d[m][2], d[m][3], wa[ks][m][0], wa[ks][m][1], wa[ks][m][2], wa[ks][m][3],
                   (ks & 1) ? xs[ks >> 1].z : xs[ks >> 1].x, (ks & 1) ? xs[ks >> 1].w : xs[ks >> 1].y);
        }
      }
      if (q == 0) {
        #pragma unroll
        for (int m = 0; m < 8; m++) stsf(sb + OFF_GU + (8 * m + g) * 48 + 4 * warp, d[m >> 1][2 * (m & 1)]);
      }
      bar_arrive(NB_ACT, 384);
    }
    {
      float y0 = 0.f, y1 = 0.f, y2 = 0.f, y3 = 0.f;
      const uint32_t ky = __float_as_uint(ldsf(sb + OFF_KEY));
      const int kidx = 2047 - (ky & 2047);
      const float kr = __uint_as_float((ky & ~2047u) ^ ((ky >> 31) ? 0x80000000u : 0xfffff800u));
      const int col = 128 * (c >> 4) + 64 * (c & 1) + 32 * ((tid >> 2) & 1) + 16 * (tid & 1) + 8 * ((tid >> 1) & 1) + ((c >> 1) & 7);
      uint32_t it = 0, base = 0;
      if (tid < 8) {
        do { base = ld32_rlx(&G->cand[(kidx >> 4) * DM + 512 + (col >> 1)]); } while (base == ~0u && ++it < POLL_LIMIT);
      }
      if (tid < 2 * NFFN) {
        uint4 v;
        do { v = ld128_rlx(&G->ypart[(tid >> 1) * DM + 8 * c + 4 * (tid & 1)]); } while (v.w == ~0u && ++it < POLL_LIMIT);
        y0 = __uint_as_float(v.x); y1 = __uint_as_float(v.y); y2 = __uint_as_float(v.z); y3 = __uint_as_float(v.w);
      }
      __syncwarp();
      const bool b4 = lane & 16, b3 = lane & 8;
      const float u0 = (b4 ? y1 : y0) + __shfl_xor_sync(~0u, b4 ? y0 : y1, 16), u1 = (b4 ? y3 : y2) + __shfl_xor_sync(~0u, b4 ? y2 : y3, 16);
      float ys = (b3 ? u1 : u0) + __shfl_xor_sync(~0u, b3 ? u0 : u1, 8);
      ys += __shfl_xor_sync(~0u, ys, 4); ys += __shfl_xor_sync(~0u, ys, 2);
      if (!(lane & 6)) stsf(sb + OFF_ACT + ((4 * (lane & 1) + ((lane >> 3) & 1) * 2 + (lane >> 4)) * 8 + warp) * 4, ys);
      const float sg = __fdividef(1.f, 1.f + __expf(-kr));
      bar_sync(NB_WG01, 256);
      if (tid < 8) {
        const uint4 v0 = lds128(sb + OFF_ACT + tid * 32), v1 = lds128(sb + OFF_ACT + tid * 32 + 16);
        const float t8 = ((__uint_as_float(v0.x) + __uint_as_float(v0.y)) + (__uint_as_float(v0.z) + __uint_as_float(v0.w))) +
                         ((__uint_as_float(v1.x) + __uint_as_float(v1.y)) + __uint_as_float(v1.z));
        P.out_p[(size_t)kidx * DM + col] = __float2bfloat16(fmaf(t8, sg, (col & 1) ? bf_hi(base) : bf_lo(base)));
      }
      if (c == 0 && tid == 0) st32_rlx(&G->epoch, __float_as_uint(ldsf(sb + OFF_EP)));
      if (wg == 0) { TSW(22); TDUMP(); }
    }
  }
  if (wg == 2) {
    uint32_t wf[16][2][4];
    {
      const uint32_t wb = sb + 16384 * ((0xcadc >> (4 * wp)) & 15) + ((lane & 7) + ((lane >> 4) << 3)) * 128 + ((((lane >> 3) & 1) ^ (lane & 7)) << 4);
      if (f < NFFN_L) mbar_wait(sb + B_WD + 8 * wp, 0);
      if (wp == 0) { TK(61); }
      #pragma unroll
      for (int i = 0; i < 32; i++) ldsm4t((wb ^ (((i >> 1) & 3) << 5)) + (i >> 3) * 4096 + (i & 1) * 2048, wf[i >> 1][i & 1][0], wf[i >> 1][i & 1][1], wf[i >> 1][i & 1][2], wf[i >> 1][i & 1][3]);
      fence_async_smem();
      __syncwarp();
      if (lane == 0) mbar_arrive(sb + B_WC + 8 * wp);
      if (wp == 0) { TK(62); }
    }
    bar_sync(NB_G2E, 384);
    {
      uint32_t cur = 0;
      uint4 v;
      #pragma unroll 1
      for (uint32_t it = 0; it < POLL_LIMIT; it++) {
        const uint4 kx = ld128_rlx(&G->key[(c & 31) * 128 + 4 * lane]);
        v = ld128_rlx(&G->cand[((~cur >> 4) & 127) * DM + 4 * t]);
        uint32_t best;
        asm volatile("redux.sync.max.u32 %0, %1, 0xffffffff;" : "=r"(best) : "r"(max(max(kx.x, kx.y), max(kx.z, kx.w))));
        if (!__any_sync(~0u, min(min(kx.x, kx.y), min(kx.z, kx.w)) == 0 || v.w == ~0u) && best == cur) break;
        cur = best;
      }
      sts128(sb + OFF_XSEL + 16 * t, v.x, v.y, v.z, v.w);
      sts32(sb + OFF_KEY, cur);
      bar_arrive(NB_XS, 384);
      if (t == 0) mbar_arrive(sb + B_XS);
      TSW(18);
      bar_sync(NB_ACT, 384);
    }
    float gu[2];
    #pragma unroll
    for (int i = 0; i < 2; i++) {
      const uint4 v0 = lds128(sb + OFF_GU + (32 * i + lane) * 48), v1 = lds128(sb + OFF_GU + (32 * i + lane) * 48 + 16);
      gu[i] = ((__uint_as_float(v0.x) + __uint_as_float(v0.y)) + (__uint_as_float(v0.z) + __uint_as_float(v0.w))) +
              ((__uint_as_float(v1.x) + __uint_as_float(v1.y)) + (__uint_as_float(v1.z) + __uint_as_float(v1.w)));
    }
    const float act = gu[0] * gu[1] * rcp(1.f + ex2(-LOG2E * gu[0]));
    const uint32_t ap = pack_bf16(act, __shfl_down_sync(~0u, act, 1));
    uint32_t bf[4];
    #pragma unroll
    for (int i = 0; i < 4; i++) bf[i] = __shfl_sync(~0u, ap, 2 * q + 8 * i);
    TSW(20);
    float d[16][4];
    #pragma unroll
    for (int k = 0; k < 2; k++)
      #pragma unroll
      for (int i = 0; i < 16; i++) {
        if (k == 0) { d[i][0] = 0.f; d[i][1] = 0.f; d[i][2] = 0.f; d[i][3] = 0.f; }
        mma16816(d[i][0], d[i][1], d[i][2], d[i][3], wf[i][k][0], wf[i][k][1], wf[i][k][2], wf[i][k][3], bf[2*k], bf[2*k+1]);
      }
    #pragma unroll
    for (int a = 0; a < 2; a++) {
      float y[4];
      #pragma unroll
      for (int e = 0; e < 4; e++) {
        const int n = 8 * a + (e & 1);
        const float lo = (q & 1) ? d[n + 2][e & 2] : d[n][e & 2], hi = (q & 1) ? d[n + 6][e & 2] : d[n + 4][e & 2];
        y[e] = (q & 2) ? hi : lo;
      }
      if (f < NFFN) st128_rlx(&G->ypart[f * DM + 256 * wp + 128 * a + 4 * lane], __float_as_uint(y[0]), __float_as_uint(y[1]), __float_as_uint(y[2]), min(__float_as_uint(y[3]), ~1u));
    }
    TSW(21);
  }
  }
  cluster_wait();
}

typedef CUresult (*EncodeFn)(CUtensorMap*, CUtensorMapDataType, cuuint32_t, void*, const cuuint64_t*, const cuuint64_t*,
                             const cuuint32_t*, const cuuint32_t*, CUtensorMapInterleave, CUtensorMapSwizzle,
                             CUtensorMapL2promotion, CUtensorMapFloatOOBfill);

void make_map(EncodeFn enc, CUtensorMap* m, const void* p, int n, const cuuint64_t* dims, const cuuint64_t* str, const cuuint32_t* box,
              CUtensorMapSwizzle sw, CUtensorMapL2promotion promo) {
  cuuint32_t es[5] = {1, 1, 1, 1, 1};
  enc(m, CU_TENSOR_MAP_DATA_TYPE_BFLOAT16, n, const_cast<void*>(p), dims, str, box, es, CU_TENSOR_MAP_INTERLEAVE_NONE, sw, promo,
      CU_TENSOR_MAP_FLOAT_OOB_FILL_NONE);
}
void map2(EncodeFn enc, CUtensorMap* m, const void* p, uint64_t cols, uint64_t rows, uint32_t bc, uint32_t br, CUtensorMapSwizzle sw,
          CUtensorMapL2promotion promo) {
  const cuuint64_t dims[2] = {cols, rows}, str[1] = {cols * 2};
  const cuuint32_t box[2] = {bc, br};
  make_map(enc, m, p, 2, dims, str, box, sw, promo);
}
void map3(EncodeFn enc, CUtensorMap* m, const void* p, uint64_t cols, uint64_t rows, uint32_t br, uint32_t nb) {
  const cuuint64_t dims[3] = {64, rows, cols / 64}, str[2] = {cols * 2, 128};
  const cuuint32_t box[3] = {64, br, nb};
  make_map(enc, m, p, 3, dims, str, box, CU_TENSOR_MAP_SWIZZLE_128B, CU_TENSOR_MAP_L2_PROMOTION_L2_128B);
}

}

extern "C" void kernel_launch(void* const* d_in, const int* in_sizes, int n_in, void* d_out, int out_size) {
  (void)in_sizes; (void)n_in; (void)out_size;
  static EncodeFn enc = nullptr;
  static void* o_ptr = nullptr;
  if (!enc) {
    void* f = nullptr; cudaDriverEntryPointQueryResult qr;
    cudaGetDriverEntryPoint("cuTensorMapEncodeTiled", &f, cudaEnableDefault, &qr);
    enc = (EncodeFn)f;
    cudaGetSymbolAddress(&o_ptr, g_scr);
    cudaFuncSetAttribute(fused_kernel, cudaFuncAttributeMaxDynamicSharedMemorySize, SMEM_BYTES);
  }
  const bf16* x = (const bf16*)d_in[0];
  const bf16* wqkv = (const bf16*)d_in[1];
  const bf16* wphi = (const bf16*)d_in[2];
  const bf16* wo = (const bf16*)d_in[3];
  const bf16* wr = (const bf16*)d_in[5];
  const bf16* wgate = (const bf16*)d_in[6];
  const bf16* wup = (const bf16*)d_in[7];
  const bf16* wdown = (const bf16*)d_in[8];
  Params P;
  const CUtensorMapSwizzle S128 = CU_TENSOR_MAP_SWIZZLE_128B, S64 = CU_TENSOR_MAP_SWIZZLE_64B;
  const CUtensorMapL2promotion L128 = CU_TENSOR_MAP_L2_PROMOTION_L2_128B, L256 = CU_TENSOR_MAP_L2_PROMOTION_L2_256B,
                               L64 = CU_TENSOR_MAP_L2_PROMOTION_L2_64B;
  map2(enc, &P.x128, x, DM, SEQ, 64, 128, S128, L256);
  map2(enc, &P.x64, x, DM, SEQ, 64, 64, S128, L128);
  {
    const cuuint64_t dims[4] = {64, DM, 16, 3}, str[3] = {6 * DM, 128, 2 * DM};
    const cuuint32_t box[4] = {64, 64, 1, 2};
    make_map(enc, &P.wkv, wqkv, 4, dims, str, box, S128, L128);
  }
  map3(enc, &P.wq, wqkv, 3 * DM, DM, 64, 2);
  {
    const cuuint64_t dims[5] = {DM, DM - 94, 4, 4, 2}, str[4] = {2 * DM, 16 * DM, 4 * DM, 128 * DM};
    const cuuint32_t box[5] = {64, 2, 4, 4, 2};
    make_map(enc, &P.wo, wo, 5, dims, str, box, S128, L128);
  }
  map3(enc, &P.wd, wdown, DM, FF, 32, 4);
  map2(enc, &P.wg, wgate, FF, DM, 32, 128, S64, L64);
  map2(enc, &P.wu, wup, FF, DM, 32, 128, S64, L64);
  map2(enc, &P.tg, wgate, FF, DM, 8, 16, CU_TENSOR_MAP_SWIZZLE_NONE, L128);
  map2(enc, &P.tu, wup, FF, DM, 8, 16, CU_TENSOR_MAP_SWIZZLE_NONE, L128);
  map2(enc, &P.td, wdown, 128, FF * 8, 8, 16, CU_TENSOR_MAP_SWIZZLE_NONE, L256);
  map2(enc, &P.phi, wphi, 32, 1024, 32, 32, S64, L64);
  P.x = x; P.wqkv = wqkv; P.wo_p = wo; P.wd_p = wdown; P.wg_p = wgate; P.wu_p = wup; P.wr = wr; P.out_p = (bf16*)d_out; P.g = (Scratch*)o_ptr;

  cudaLaunchConfig_t cfg = {};
  cfg.gridDim = dim3(128); cfg.blockDim = dim3(512); cfg.dynamicSmemBytes = SMEM_BYTES; cfg.stream = cudaStreamPerThread;
  cudaLaunchAttribute at[1];
  at[0].id = cudaLaunchAttributeClusterDimension; at[0].val.clusterDim.x = 2; at[0].val.clusterDim.y = 1; at[0].val.clusterDim.z = 1;
  cfg.attrs = at; cfg.numAttrs = 1;
  cudaLaunchKernelEx(&cfg, fused_kernel, P);
}
```

```cpp
#include <cuda_runtime.h>
#include <cuda.h>
#include <cuda_bf16.h>
#include <stdint.h>

namespace {

typedef __nv_bfloat16 bf16;

__device__ __forceinline__ uint32_t smem_u32(const void* p){ return (uint32_t)__cvta_generic_to_shared(p); }
__device__ __forceinline__ void mbar_init(uint32_t bar, uint32_t cnt){ asm volatile("mbarrier.init.shared::cta.b64 [%0], %1;"::"r"(bar),"r"(cnt):"memory"); }
__device__ __forceinline__ void mbar_expect_tx(uint32_t bar, uint32_t bytes){ asm volatile("mbarrier.arrive.expect_tx.shared::cta.b64 _, [%0], %1;"::"r"(bar),"r"(bytes):"memory"); }
__device__ __forceinline__ void mbar_arrive(uint32_t bar){ asm volatile("mbarrier.arrive.shared::cta.b64 _, [%0];"::"r"(bar):"memory"); }
__device__ __forceinline__ uint32_t mapa(uint32_t addr, uint32_t cta){ uint32_t r; asm volatile("mapa.shared::cluster.u32 %0, %1, %2;":"=r"(r):"r"(addr),"r"(cta)); return r; }
__device__ __forceinline__ void mbar_arrive_at(uint32_t bar, uint32_t cta, uint32_t cnt){
  asm volatile("{\n.reg .b32 ra;\nmapa.shared::cluster.u32 ra, %0, %1;\nmbarrier.arrive.shared::cluster.b64 _, [ra], %2;\n}\n"::"r"(bar),"r"(cta),"r"(cnt):"memory"); }
__device__ __forceinline__ void mbar_arrive_remote(uint32_t cluster_addr, uint32_t cnt){
  asm volatile("mbarrier.arrive.shared::cluster.b64 _, [%0], %1;"::"r"(cluster_addr),"r"(cnt):"memory"); }
__device__ __forceinline__ void mbar_wait(uint32_t bar, uint32_t parity){
  asm volatile("{\n.reg .pred p;\n.reg .u32 c;\nmov.u32 c, 0;\nLW:\nmbarrier.try_wait.parity.shared::cta.b64 p, [%0], %1;\n@p bra LD;\nadd.u32 c, c, 1;\nsetp.lt.u32 p, c, 2000000;\n@p bra LW;\ntrap;\nLD:\n}\n"::"r"(bar),"r"(parity):"memory"); }
__device__ __forceinline__ void mbar_wait2(uint32_t bar0, uint32_t par0, uint32_t bar1, uint32_t par1){
  asm volatile("{\n.reg .pred p, q;\n.reg .u32 c;\nmov.u32 c, 0;\nLW:\nmbarrier.try_wait.parity.shared::cta.b64 p, [%0], %1;\nmbarrier.try_wait.parity.shared::cta.b64 q, [%2], %3;\nand.pred p, p, q;\n@p bra LD;\nadd.u32 c, c, 1;\nsetp.lt.u32 p, c, 2000000;\n@p bra LW;\ntrap;\nLD:\n}\n"::"r"(bar0),"r"(par0),"r"(bar1),"r"(par1):"memory"); }
__device__ __forceinline__ bool mbar_test2(uint32_t bar0, uint32_t par0, uint32_t bar1, uint32_t par1){
  uint32_t r;
  asm volatile("{\n.reg .pred p, q;\nmbarrier.test_wait.parity.shared::cta.b64 p, [%1], %2;\nmbarrier.test_wait.parity.shared::cta.b64 q, [%3], %4;\nand.pred p, p, q;\nselp.u32 %0, 1, 0, p;\n}\n":"=r"(r):"r"(bar0),"r"(par0),"r"(bar1),"r"(par1):"memory");
  return r; }
__device__ __forceinline__ void tma_2d(uint32_t dst, const CUtensorMap* m, int c0, int c1, uint32_t bar){
  asm volatile("cp.async.bulk.tensor.2d.shared::cluster.global.mbarrier::complete_tx::bytes [%0], [%1, {%3, %4}], [%2];"::"r"(dst),"l"(m),"r"(bar),"r"(c0),"r"(c1):"memory"); }
__device__ __forceinline__ void tma_2d_mc(uint32_t dst, const CUtensorMap* m, int c0, int c1, uint32_t bar){
  asm volatile("cp.async.bulk.tensor.2d.shared::cluster.global.mbarrier::complete_tx::bytes.multicast::cluster [%0], [%1, {%3, %4}], [%2], %5;"::"r"(dst),"l"(m),"r"(bar),"r"(c0),"r"(c1),"h"((uint16_t)3):"memory"); }
__device__ __forceinline__ void tma_2d_mc_h(uint32_t dst, const CUtensorMap* m, int c0, int c1, uint32_t bar, uint64_t pol){
  asm volatile("cp.async.bulk.tensor.2d.shared::cluster.global.mbarrier::complete_tx::bytes.multicast::cluster.L2::cache_hint [%0], [%1, {%3, %4}], [%2], %5, %6;"::"r"(dst),"l"(m),"r"(bar),"r"(c0),"r"(c1),"h"((uint16_t)3),"l"(pol):"memory"); }
__device__ __forceinline__ void tma_4d(uint32_t dst, const CUtensorMap* m, int c0, int c1, int c2, int c3, uint32_t bar){
  asm volatile("cp.async.bulk.tensor.4d.shared::cluster.global.mbarrier::complete_tx::bytes [%0], [%1, {%3, %4, %5, %6}], [%2];"::"r"(dst),"l"(m),"r"(bar),"r"(c0),"r"(c1),"r"(c2),"r"(c3):"memory"); }
__device__ __forceinline__ uint64_t policy_evict_first(){ uint64_t p; asm volatile("createpolicy.fractional.L2::evict_first.b64 %0, 1.0;":"=l"(p)); return p; }
__device__ __forceinline__ uint64_t policy_evict_normal(){ uint64_t p; asm("createpolicy.fractional.L2::evict_normal.b64 %0, 1.0;":"=l"(p)); return p; }
__device__ __forceinline__ void tma_3d_h(uint32_t dst, const CUtensorMap* m, int c0, int c1, int c2, uint32_t bar, uint64_t pol){
  asm volatile("cp.async.bulk.tensor.3d.shared::cluster.global.mbarrier::complete_tx::bytes.L2::cache_hint [%0], [%1, {%3, %4, %5}], [%2], %6;"::"r"(dst),"l"(m),"r"(bar),"r"(c0),"r"(c1),"r"(c2),"l"(pol):"memory"); }
__device__ __forceinline__ void tma_4d_h(uint32_t dst, const CUtensorMap* m, int c0, int c1, int c2, int c3, uint32_t bar, uint64_t pol){
  asm volatile("cp.async.bulk.tensor.4d.shared::cluster.global.mbarrier::complete_tx::bytes.L2::cache_hint [%0], [%1, {%3, %4, %5, %6}], [%2], %7;"::"r"(dst),"l"(m),"r"(bar),"r"(c0),"r"(c1),"r"(c2),"r"(c3),"l"(pol):"memory"); }
__device__ __forceinline__ void red_add_f32x4(float4* p, float x, float y, float z, float w){ asm volatile("red.relaxed.gpu.global.add.v4.f32 [%0], {%1,%2,%3,%4};"::"l"(p),"f"(x),"f"(y),"f"(z),"f"(w):"memory"); }
__device__ __forceinline__ void tma_5d_h(uint32_t dst, const CUtensorMap* m, int c0, int c1, uint32_t bar, uint64_t pol){
  asm volatile("cp.async.bulk.tensor.5d.shared::cluster.global.mbarrier::complete_tx::bytes.L2::cache_hint [%0], [%1, {%3, %4, 0, 0, 0}], [%2], %5;"::"r"(dst),"l"(m),"r"(bar),"r"(c0),"r"(c1),"l"(pol):"memory"); }
__device__ __forceinline__ bool elect_one(){ uint32_t p; asm volatile("{\n.reg .pred P;\nelect.sync _|P, 0xffffffff;\nselp.b32 %0, 1, 0, P;\n}\n":"=r"(p)); return p; }
__device__ __forceinline__ void bulk_prefetch(const void* p, uint32_t bytes){
  asm volatile("cp.async.bulk.prefetch.L2.global [%0], %1;"::"l"(p),"r"(bytes):"memory"); }
__device__ __forceinline__ void bulk_s2peer(uint32_t dst_cluster, uint32_t src, uint32_t bytes, uint32_t bar_cluster){
  asm volatile("cp.async.bulk.shared::cluster.shared::cta.mbarrier::complete_tx::bytes [%0], [%1], %2, [%3];"::"r"(dst_cluster),"r"(src),"r"(bytes),"r"(bar_cluster):"memory"); }
__device__ __forceinline__ void bulk_g2s_mc(uint32_t dst, const void* src, uint32_t bytes, uint32_t bar, uint64_t pol){
  asm volatile("cp.async.bulk.shared::cluster.global.mbarrier::complete_tx::bytes.multicast::cluster.L2::cache_hint [%0], [%1], %2, [%3], %4, %5;"::"r"(dst),"l"(src),"r"(bytes),"r"(bar),"h"((uint16_t)3),"l"(pol):"memory"); }
__device__ __forceinline__ void prefetch_map(const CUtensorMap* m){ asm volatile("prefetch.tensormap [%0];"::"l"(m):"memory"); }
__device__ __forceinline__ void fence_async_smem(){ asm volatile("fence.proxy.async.shared::cta;":::"memory"); }
__device__ __forceinline__ void fence_acquire_gpu(){ asm volatile("fence.acquire.gpu;":::"memory"); }
__device__ __forceinline__ void fence_gpu(){ asm volatile("fence.acq_rel.gpu;":::"memory"); }
__device__ __forceinline__ void wg_fence(){ asm volatile("wgmma.fence.sync.aligned;":::"memory"); }
__device__ __forceinline__ void wg_commit(){ asm volatile("wgmma.commit_group.sync.aligned;":::"memory"); }
template<int N> __device__ __forceinline__ void wg_wait(){ asm volatile("wgmma.wait_group.sync.aligned %0;"::"n"(N):"memory"); }
template<int N> __device__ __forceinline__ void fence_regs(float (&d)[N]){
  #pragma unroll
  for(int i=0;i<N;i++) asm volatile("":"+f"(d[i])::"memory"); }
__device__ __forceinline__ void bar_sync(int id, int n){ asm volatile("bar.sync %0, %1;"::"r"(id),"r"(n):"memory"); }
__device__ __forceinline__ void bar_arrive(int id, int n){ asm volatile("bar.arrive %0, %1;"::"r"(id),"r"(n):"memory"); }
__device__ __forceinline__ void cluster_arrive(){ asm volatile("barrier.cluster.arrive.relaxed.aligned;":::"memory"); }
__device__ __forceinline__ void cluster_wait(){ asm volatile("barrier.cluster.wait.aligned;":::"memory"); }
__host__ __device__ constexpr uint32_t dlo(uint32_t addr, uint32_t lbo){ return (addr >> 4) | ((lbo >> 4) << 16); }
__host__ __device__ constexpr uint32_t dhi(uint32_t sbo, uint32_t sw){ return (sbo >> 4) | (sw << 30); }
constexpr uint32_t H128 = dhi(1024, 1), H64 = dhi(512, 2), H0 = dhi(128, 0);
__device__ __forceinline__ uint32_t pack_bf16(float lo, float hi){ uint32_t r; asm("cvt.rn.bf16x2.f32 %0, %1, %2;":"=r"(r):"f"(hi),"f"(lo)); return r; }
__device__ __forceinline__ float bf_lo(uint32_t v){ return __uint_as_float(v<<16); }
__device__ __forceinline__ float bf_hi(uint32_t v){ return __uint_as_float(v&0xffff0000u); }
__device__ __forceinline__ float ex2(float x){ float r; asm("ex2.approx.ftz.f32 %0, %1;":"=f"(r):"f"(x)); return r; }
__device__ __forceinline__ float rcp(float x){ float r; asm("rcp.approx.ftz.f32 %0, %1;":"=f"(r):"f"(x)); return r; }
__device__ __forceinline__ void stsm4(uint32_t addr, uint32_t a, uint32_t b, uint32_t c, uint32_t d){
  asm volatile("stmatrix.sync.aligned.m8n8.x4.shared.b16 [%0], {%1,%2,%3,%4};"::"r"(addr),"r"(a),"r"(b),"r"(c),"r"(d)); }
__device__ __forceinline__ void stsm2(uint32_t addr, uint32_t a, uint32_t b){
  asm volatile("stmatrix.sync.aligned.m8n8.x2.shared.b16 [%0], {%1,%2};"::"r"(addr),"r"(a),"r"(b)); }
__device__ __forceinline__ void mma16816(float& d0, float& d1, float& d2, float& d3, uint32_t a0, uint32_t a1, uint32_t a2, uint32_t a3, uint32_t b0, uint32_t b1){
  asm volatile("mma.sync.aligned.m16n8k16.row.col.f32.bf16.bf16.f32 {%0,%1,%2,%3}, {%4,%5,%6,%7}, {%8,%9}, {%0,%1,%2,%3};"
               : "+f"(d0), "+f"(d1), "+f"(d2), "+f"(d3) : "r"(a0), "r"(a1), "r"(a2), "r"(a3), "r"(b0), "r"(b1)); }
__device__ __forceinline__ void ldsm4(uint32_t addr, uint32_t& a, uint32_t& b, uint32_t& c, uint32_t& d){
  asm volatile("ldmatrix.sync.aligned.m8n8.x4.shared.b16 {%0,%1,%2,%3}, [%4];":"=r"(a),"=r"(b),"=r"(c),"=r"(d):"r"(addr):"memory"); }
__device__ __forceinline__ void ldsm4t(uint32_t addr, uint32_t& a, uint32_t& b, uint32_t& c, uint32_t& d){
  asm volatile("ldmatrix.sync.aligned.m8n8.x4.trans.shared.b16 {%0,%1,%2,%3}, [%4];":"=r"(a),"=r"(b),"=r"(c),"=r"(d):"r"(addr):"memory"); }
__device__ __forceinline__ void sts32(uint32_t a, uint32_t v){ asm volatile("st.shared.b32 [%0], %1;"::"r"(a),"r"(v):"memory"); }
__device__ __forceinline__ void stsf(uint32_t a, float v){ asm volatile("st.shared.f32 [%0], %1;"::"r"(a),"f"(v):"memory"); }
__device__ __forceinline__ void sts64(uint32_t a, uint32_t x, uint32_t y){ asm volatile("st.shared.v2.b32 [%0], {%1,%2};"::"r"(a),"r"(x),"r"(y):"memory"); }
__device__ __forceinline__ void sts128(uint32_t a, uint32_t x, uint32_t y, uint32_t z, uint32_t w){ asm volatile("st.shared.v4.b32 [%0], {%1,%2,%3,%4};"::"r"(a),"r"(x),"r"(y),"r"(z),"r"(w):"memory"); }
__device__ __forceinline__ float ldsf(uint32_t a){ float v; asm volatile("ld.shared.f32 %0, [%1];":"=f"(v):"r"(a):"memory"); return v; }
__device__ __forceinline__ float2 lds64f(uint32_t a){ float2 v; asm volatile("ld.shared.v2.f32 {%0,%1}, [%2];":"=f"(v.x),"=f"(v.y):"r"(a):"memory"); return v; }
__device__ __forceinline__ uint4 lds128(uint32_t a){ uint4 v; asm volatile("ld.shared.v4.u32 {%0,%1,%2,%3}, [%4];":"=r"(v.x),"=r"(v.y),"=r"(v.z),"=r"(v.w):"r"(a):"memory"); return v; }
__device__ __forceinline__ uint4 ld128_keep(const void* p){ uint4 v; asm volatile("ld.global.v4.u32 {%0,%1,%2,%3}, [%4];":"=r"(v.x),"=r"(v.y),"=r"(v.z),"=r"(v.w):"l"(p):"memory"); return v; }
__device__ __forceinline__ uint4 ld128_rlx(const void* p){ uint4 v; asm volatile("ld.relaxed.gpu.global.v4.u32 {%0,%1,%2,%3}, [%4];":"=r"(v.x),"=r"(v.y),"=r"(v.z),"=r"(v.w):"l"(p):"memory"); return v; }
__device__ __forceinline__ uint32_t ld32_rlx(const void* p){ uint32_t v; asm volatile("ld.relaxed.gpu.global.u32 %0, [%1];":"=r"(v):"l"(p):"memory"); return v; }
__device__ __forceinline__ void st128_rlx(void* p, uint32_t x, uint32_t y, uint32_t z, uint32_t w){ asm volatile("st.relaxed.gpu.global.v4.u32 [%0], {%1,%2,%3,%4};"::"l"(p),"r"(x),"r"(y),"r"(z),"r"(w):"memory"); }
__device__ __forceinline__ void st64_rlx(void* p, uint32_t x, uint32_t y){ asm volatile("st.relaxed.gpu.global.v2.u32 [%0], {%1,%2};"::"l"(p),"r"(x),"r"(y):"memory"); }
__device__ __forceinline__ void st32_rlx(void* p, uint32_t x){ asm volatile("st.relaxed.gpu.global.u32 [%0], %1;"::"l"(p),"r"(x):"memory"); }
__device__ __forceinline__ uint32_t tagw(float x, uint32_t t){ return (__float_as_uint(x) & ~3u) | t; }
__device__ __forceinline__ float untag(uint32_t w){ return __uint_as_float(w & ~3u); }

template<int TA, int TB, uint32_t HA, uint32_t HB> __device__ __forceinline__ void wgmma_ss_n128(float (&d)[64], uint32_t da, uint32_t db, int scale_d){
  asm volatile("{\n.reg .pred p;\n.reg .b64 a, b;\nsetp.ne.b32 p, %70, 0;\nmov.b64 a, {%64, %68};\nmov.b64 b, {%65, %69};\n"
  "wgmma.mma_async.sync.aligned.m64n128k16.f32.bf16.bf16 {%0, %1, %2, %3, %4, %5, %6, %7, %8, %9, %10, %11, %12, %13, %14, %15, %16, %17, %18, %19, %20, %21, %22, %23, %24, %25, %26, %27, %28, %29, %30, %31, %32, %33, %34, %35, %36, %37, %38, %39, %40, %41, %42, %43, %44, %45, %46, %47, %48, %49, %50, %51, %52, %53, %54, %55, %56, %57, %58, %59, %60, %61, %62, %63}, a, b, p, 1, 1, %66, %67;\n}\n"
  : "+f"(d[0]), "+f"(d[1]), "+f"(d[2]), "+f"(d[3]), "+f"(d[4]), "+f"(d[5]), "+f"(d[6]), "+f"(d[7]), "+f"(d[8]), "+f"(d[9]), "+f"(d[10]), "+f"(d[11]), "+f"(d[12]), "+f"(d[13]), "+f"(d[14]), "+f"(d[15]), "+f"(d[16]), "+f"(d[17]), "+f"(d[18]), "+f"(d[19]), "+f"(d[20]), "+f"(d[21]), "+f"(d[22]), "+f"(d[23]), "+f"(d[24]), "+f"(d[25]), "+f"(d[26]), "+f"(d[27]), "+f"(d[28]), "+f"(d[29]), "+f"(d[30]), "+f"(d[31]), "+f"(d[32]), "+f"(d[33]), "+f"(d[34]), "+f"(d[35]), "+f"(d[36]), "+f"(d[37]), "+f"(d[38]), "+f"(d[39]), "+f"(d[40]), "+f"(d[41]), "+f"(d[42]), "+f"(d[43]), "+f"(d[44]), "+f"(d[45]), "+f"(d[46]), "+f"(d[47]), "+f"(d[48]), "+f"(d[49]), "+f"(d[50]), "+f"(d[51]), "+f"(d[52]), "+f"(d[53]), "+f"(d[54]), "+f"(d[55]), "+f"(d[56]), "+f"(d[57]), "+f"(d[58]), "+f"(d[59]), "+f"(d[60]), "+f"(d[61]), "+f"(d[62]), "+f"(d[63])
  : "r"(da), "r"(db), "n"(TA), "n"(TB), "n"(HA), "n"(HB), "r"(scale_d));
}
template<int TA, int TB, uint32_t HA, uint32_t HB> __device__ __forceinline__ void wgmma_sa_n128(float (&d)[64], uint32_t da, uint32_t db){
  asm volatile("{\n.reg .pred p;\n.reg .b64 a, b;\nsetp.ne.b32 p, 1, 0;\nmov.b64 a, {%64, %68};\nmov.b64 b, {%65, %69};\n"
  "wgmma.mma_async.sync.aligned.m64n128k16.f32.bf16.bf16 {%0, %1, %2, %3, %4, %5, %6, %7, %8, %9, %10, %11, %12, %13, %14, %15, %16, %17, %18, %19, %20, %21, %22, %23, %24, %25, %26, %27, %28, %29, %30, %31, %32, %33, %34, %35, %36, %37, %38, %39, %40, %41, %42, %43, %44, %45, %46, %47, %48, %49, %50, %51, %52, %53, %54, %55, %56, %57, %58, %59, %60, %61, %62, %63}, a, b, p, 1, 1, %66, %67;\n}\n"
  : "+f"(d[0]), "+f"(d[1]), "+f"(d[2]), "+f"(d[3]), "+f"(d[4]), "+f"(d[5]), "+f"(d[6]), "+f"(d[7]), "+f"(d[8]), "+f"(d[9]), "+f"(d[10]), "+f"(d[11]), "+f"(d[12]), "+f"(d[13]), "+f"(d[14]), "+f"(d[15]), "+f"(d[16]), "+f"(d[17]), "+f"(d[18]), "+f"(d[19]), "+f"(d[20]), "+f"(d[21]), "+f"(d[22]), "+f"(d[23]), "+f"(d[24]), "+f"(d[25]), "+f"(d[26]), "+f"(d[27]), "+f"(d[28]), "+f"(d[29]), "+f"(d[30]), "+f"(d[31]), "+f"(d[32]), "+f"(d[33]), "+f"(d[34]), "+f"(d[35]), "+f"(d[36]), "+f"(d[37]), "+f"(d[38]), "+f"(d[39]), "+f"(d[40]), "+f"(d[41]), "+f"(d[42]), "+f"(d[43]), "+f"(d[44]), "+f"(d[45]), "+f"(d[46]), "+f"(d[47]), "+f"(d[48]), "+f"(d[49]), "+f"(d[50]), "+f"(d[51]), "+f"(d[52]), "+f"(d[53]), "+f"(d[54]), "+f"(d[55]), "+f"(d[56]), "+f"(d[57]), "+f"(d[58]), "+f"(d[59]), "+f"(d[60]), "+f"(d[61]), "+f"(d[62]), "+f"(d[63])
  : "r"(da), "r"(db), "n"(TA), "n"(TB), "n"(HA), "n"(HB));
}
template<int TA, int TB, uint32_t HA, uint32_t HB> __device__ __forceinline__ void wgmma_sa_n40(float (&d)[20], uint32_t da, uint32_t db){
  asm volatile("{\n.reg .pred p;\n.reg .b64 a, b;\nsetp.ne.b32 p, 1, 0;\nmov.b64 a, {%20, %24};\nmov.b64 b, {%21, %25};\n"
  "wgmma.mma_async.sync.aligned.m64n40k16.f32.bf16.bf16 {%0, %1, %2, %3, %4, %5, %6, %7, %8, %9, %10, %11, %12, %13, %14, %15, %16, %17, %18, %19}, a, b, p, 1, 1, %22, %23;\n}\n"
  : "+f"(d[0]), "+f"(d[1]), "+f"(d[2]), "+f"(d[3]), "+f"(d[4]), "+f"(d[5]), "+f"(d[6]), "+f"(d[7]), "+f"(d[8]), "+f"(d[9]), "+f"(d[10]), "+f"(d[11]), "+f"(d[12]), "+f"(d[13]), "+f"(d[14]), "+f"(d[15]), "+f"(d[16]), "+f"(d[17]), "+f"(d[18]), "+f"(d[19])
  : "r"(da), "r"(db), "n"(TA), "n"(TB), "n"(HA), "n"(HB));
}
template<int TA, int TB, uint32_t HA, uint32_t HB> __device__ __forceinline__ void wgmma_sz_n40(float (&d)[20], uint32_t da, uint32_t db){
  asm volatile("{\n.reg .pred p;\n.reg .b64 a, b;\nsetp.ne.b32 p, 0, 0;\nmov.b64 a, {%20, %24};\nmov.b64 b, {%21, %25};\n"
  "wgmma.mma_async.sync.aligned.m64n40k16.f32.bf16.bf16 {%0, %1, %2, %3, %4, %5, %6, %7, %8, %9, %10, %11, %12, %13, %14, %15, %16, %17, %18, %19}, a, b, p, 1, 1, %22, %23;\n}\n"
  : "=f"(d[0]), "=f"(d[1]), "=f"(d[2]), "=f"(d[3]), "=f"(d[4]), "=f"(d[5]), "=f"(d[6]), "=f"(d[7]), "=f"(d[8]), "=f"(d[9]), "=f"(d[10]), "=f"(d[11]), "=f"(d[12]), "=f"(d[13]), "=f"(d[14]), "=f"(d[15]), "=f"(d[16]), "=f"(d[17]), "=f"(d[18]), "=f"(d[19])
  : "r"(da), "r"(db), "n"(TA), "n"(TB), "n"(HA), "n"(HB));
}
template<int TA, int TB, uint32_t HA, uint32_t HB> __device__ __forceinline__ void wgmma_sa_n32(float (&d)[16], uint32_t da, uint32_t db){
  asm volatile("{\n.reg .pred p;\n.reg .b64 a, b;\nsetp.ne.b32 p, 1, 0;\nmov.b64 a, {%16, %20};\nmov.b64 b, {%17, %21};\n"
  "wgmma.mma_async.sync.aligned.m64n32k16.f32.bf16.bf16 {%0, %1, %2, %3, %4, %5, %6, %7, %8, %9, %10, %11, %12, %13, %14, %15}, a, b, p, 1, 1, %18, %19;\n}\n"
  : "+f"(d[0]), "+f"(d[1]), "+f"(d[2]), "+f"(d[3]), "+f"(d[4]), "+f"(d[5]), "+f"(d[6]), "+f"(d[7]), "+f"(d[8]), "+f"(d[9]), "+f"(d[10]), "+f"(d[11]), "+f"(d[12]), "+f"(d[13]), "+f"(d[14]), "+f"(d[15])
  : "r"(da), "r"(db), "n"(TA), "n"(TB), "n"(HA), "n"(HB));
}
template<int TA, int TB, uint32_t HA, uint32_t HB> __device__ __forceinline__ void wgmma_ss_n32(float (&d)[16], uint32_t da, uint32_t db, int scale_d){
  asm volatile("{\n.reg .pred p;\n.reg .b64 a, b;\nsetp.ne.b32 p, %22, 0;\nmov.b64 a, {%16, %20};\nmov.b64 b, {%17, %21};\n"
  "wgmma.mma_async.sync.aligned.m64n32k16.f32.bf16.bf16 {%0, %1, %2, %3, %4, %5, %6, %7, %8, %9, %10, %11, %12, %13, %14, %15}, a, b, p, 1, 1, %18, %19;\n}\n"
  : "+f"(d[0]), "+f"(d[1]), "+f"(d[2]), "+f"(d[3]), "+f"(d[4]), "+f"(d[5]), "+f"(d[6]), "+f"(d[7]), "+f"(d[8]), "+f"(d[9]), "+f"(d[10]), "+f"(d[11]), "+f"(d[12]), "+f"(d[13]), "+f"(d[14]), "+f"(d[15])
  : "r"(da), "r"(db), "n"(TA), "n"(TB), "n"(HA), "n"(HB), "r"(scale_d));
}
template<int TB, uint32_t HB> __device__ __forceinline__ void wgmma_ra_n32(float (&d)[16], uint32_t a0, uint32_t a1, uint32_t a2, uint32_t a3, uint32_t db){
  asm volatile("{\n.reg .pred p;\n.reg .b64 a, b;\nsetp.ne.b32 p, 1, 0;\nmov.b64 b, {%20, %22};\n"
  "wgmma.mma_async.sync.aligned.m64n32k16.f32.bf16.bf16 {%0, %1, %2, %3, %4, %5, %6, %7, %8, %9, %10, %11, %12, %13, %14, %15}, {%16,%17,%18,%19}, b, p, 1, 1, %21;\n}\n"
  : "+f"(d[0]), "+f"(d[1]), "+f"(d[2]), "+f"(d[3]), "+f"(d[4]), "+f"(d[5]), "+f"(d[6]), "+f"(d[7]), "+f"(d[8]), "+f"(d[9]), "+f"(d[10]), "+f"(d[11]), "+f"(d[12]), "+f"(d[13]), "+f"(d[14]), "+f"(d[15])
  : "r"(a0), "r"(a1), "r"(a2), "r"(a3), "r"(db), "n"(TB), "n"(HB));
}
template<int TB, uint32_t HB> __device__ __forceinline__ void wgmma_rs_n32(float (&d)[16], uint32_t a0, uint32_t a1, uint32_t a2, uint32_t a3, uint32_t db, int scale_d){
  asm volatile("{\n.reg .pred p;\n.reg .b64 a, b;\nsetp.ne.b32 p, %23, 0;\nmov.b64 b, {%20, %22};\n"
  "wgmma.mma_async.sync.aligned.m64n32k16.f32.bf16.bf16 {%0, %1, %2, %3, %4, %5, %6, %7, %8, %9, %10, %11, %12, %13, %14, %15}, {%16,%17,%18,%19}, b, p, 1, 1, %21;\n}\n"
  : "+f"(d[0]), "+f"(d[1]), "+f"(d[2]), "+f"(d[3]), "+f"(d[4]), "+f"(d[5]), "+f"(d[6]), "+f"(d[7]), "+f"(d[8]), "+f"(d[9]), "+f"(d[10]), "+f"(d[11]), "+f"(d[12]), "+f"(d[13]), "+f"(d[14]), "+f"(d[15])
  : "r"(a0), "r"(a1), "r"(a2), "r"(a3), "r"(db), "n"(TB), "n"(HB), "r"(scale_d));
}
template<int TB, uint32_t HB> __device__ __forceinline__ void wgmma_ra_n40(float (&d)[20], uint32_t a0, uint32_t a1, uint32_t a2, uint32_t a3, uint32_t db){
  asm volatile("{\n.reg .pred p;\n.reg .b64 a, b;\nsetp.ne.b32 p, 1, 0;\nmov.b64 b, {%24, %26};\n"
  "wgmma.mma_async.sync.aligned.m64n40k16.f32.bf16.bf16 {%0, %1, %2, %3, %4, %5, %6, %7, %8, %9, %10, %11, %12, %13, %14, %15, %16, %17, %18, %19}, {%20,%21,%22,%23}, b, p, 1, 1, %25;\n}\n"
  : "+f"(d[0]), "+f"(d[1]), "+f"(d[2]), "+f"(d[3]), "+f"(d[4]), "+f"(d[5]), "+f"(d[6]), "+f"(d[7]), "+f"(d[8]), "+f"(d[9]), "+f"(d[10]), "+f"(d[11]), "+f"(d[12]), "+f"(d[13]), "+f"(d[14]), "+f"(d[15]), "+f"(d[16]), "+f"(d[17]), "+f"(d[18]), "+f"(d[19])
  : "r"(a0), "r"(a1), "r"(a2), "r"(a3), "r"(db), "n"(TB), "n"(HB));
}
template<int TB, uint32_t HB> __device__ __forceinline__ void wgmma_rz_n40(float (&d)[20], uint32_t a0, uint32_t a1, uint32_t a2, uint32_t a3, uint32_t db){
  asm volatile("{\n.reg .pred p;\n.reg .b64 a, b;\nsetp.ne.b32 p, 0, 0;\nmov.b64 b, {%24, %26};\n"
  "wgmma.mma_async.sync.aligned.m64n40k16.f32.bf16.bf16 {%0, %1, %2, %3, %4, %5, %6, %7, %8, %9, %10, %11, %12, %13, %14, %15, %16, %17, %18, %19}, {%20,%21,%22,%23}, b, p, 1, 1, %25;\n}\n"
  : "=f"(d[0]), "=f"(d[1]), "=f"(d[2]), "=f"(d[3]), "=f"(d[4]), "=f"(d[5]), "=f"(d[6]), "=f"(d[7]), "=f"(d[8]), "=f"(d[9]), "=f"(d[10]), "=f"(d[11]), "=f"(d[12]), "=f"(d[13]), "=f"(d[14]), "=f"(d[15]), "=f"(d[16]), "=f"(d[17]), "=f"(d[18]), "=f"(d[19])
  : "r"(a0), "r"(a1), "r"(a2), "r"(a3), "r"(db), "n"(TB), "n"(HB));
}
template<int TB, uint32_t HB> __device__ __forceinline__ void wgmma_ra_n8(float (&d)[4], uint32_t a0, uint32_t a1, uint32_t a2, uint32_t a3, uint32_t db){
  asm volatile("{\n.reg .pred p;\n.reg .b64 a, b;\nsetp.ne.b32 p, 1, 0;\nmov.b64 b, {%8, %10};\n"
  "wgmma.mma_async.sync.aligned.m64n8k16.f32.bf16.bf16 {%0, %1, %2, %3}, {%4,%5,%6,%7}, b, p, 1, 1, %9;\n}\n"
  : "+f"(d[0]), "+f"(d[1]), "+f"(d[2]), "+f"(d[3])
  : "r"(a0), "r"(a1), "r"(a2), "r"(a3), "r"(db), "n"(TB), "n"(HB));
}
template<int TB, uint32_t HB> __device__ __forceinline__ void wgmma_rz_n8(float (&d)[4], uint32_t a0, uint32_t a1, uint32_t a2, uint32_t a3, uint32_t db){
  asm volatile("{\n.reg .pred p;\n.reg .b64 a, b;\nsetp.ne.b32 p, 0, 0;\nmov.b64 b, {%8, %10};\n"
  "wgmma.mma_async.sync.aligned.m64n8k16.f32.bf16.bf16 {%0, %1, %2, %3}, {%4,%5,%6,%7}, b, p, 1, 1, %9;\n}\n"
  : "=f"(d[0]), "=f"(d[1]), "=f"(d[2]), "=f"(d[3])
  : "r"(a0), "r"(a1), "r"(a2), "r"(a3), "r"(db), "n"(TB), "n"(HB));
}

constexpr int SEQ = 2048, DM = 1024, FF = 3584;
constexpr float LOG2E = 1.4426950408889634f;
constexpr uint32_t POLL_LIMIT = 1u << 22;
constexpr int NPRE = 2;
#define QW 14
#define RS_N 24
#define RS_D1 430
#define RS_D2 300
#define SKM 0x252
#define LAG 1
#define PF_T0 4000
#define PF_DT 900
#define Q0L 2
#define NFFN_L NFFN
#define FF_DT 700
#define OUT_U 1
#define GRES 8
#define OUT_L 0
#define TMASK 0xffffff
#define PMASK 0xffffff
#define FF_T0 1200
#define GPRE 0
#define REL 0x882
#define EFI 11
#define G2UN 16
#define TKW 8
#define OUT_NS 0
constexpr int G2U = G2UN;
constexpr int NFFN = 112;

constexpr uint32_t SB0 = 1024;
constexpr uint32_t KV_STAGE = 49152, R5 = 32768;
constexpr uint32_t OFF_X = 163840, OFF_S = 196608, OFF_WPHI = OFF_S + 20480, OFF_M = 229376, SMEM_BYTES = 232448;
constexpr uint32_t OFF_RS256 = 212992, OFF_ONES = OFF_RS256 + 1024, OFF_WPHIK1 = OFF_ONES + 1024, OFF_KVZ = OFF_S;
constexpr uint32_t OFF_WPHIK = OFF_S, OFF_BXK = OFF_S + 2048, OFF_AXK = OFF_S + 4096;
constexpr uint32_t OFF_AXQ = OFF_WPHI, OFF_BXQ = OFF_WPHI + 2048, OFF_WPHIQ = OFF_WPHI + 4096;
constexpr uint32_t B_FULLKV = OFF_M, B_EMPTYKV = OFF_M + 32, B_FULL5 = OFF_M + 64, B_EMPTY5 = OFF_M + 104;
constexpr uint32_t B_W = OFF_M + 144, B_OS = OFF_M + 152, B_R = OFF_M + 160, B_AUX = OFF_M + 168, B_AUXQ = OFF_M + 176, B_KD = OFF_M + 184, B_RC = OFF_M + 192  ;
constexpr uint32_t B_FULLA = OFF_M + 768, B_QL = B_FULLA + 80, B_UO = B_FULLA + 96  ;
constexpr uint32_t OFF_SUMWR = OFF_M + 896, OFF_EP = OFF_M + 208, OFF_KEY = OFF_M + 216, OFF_EXC = OFF_M + 224;
constexpr uint32_t OFF_RSQ = OFF_M + 256, OFF_WR = OFF_M + 2048, OFF_XSEL = 4 * R5;
constexpr uint32_t OFF_ACT = OFF_XSEL + 2048, OFF_GU = OFF_XSEL + 4096, OFF_SCR = OFF_M + 2432, B_F = OFF_M + 1536  , B_WD = B_F + 64  , B_WC = B_F + 96  , B_DR = B_F + 128  , B_RX = B_F + 144, B_XS = B_F + 152, B_T = B_F + 160, B_OUT = B_F + 168  , OFF_T = OFF_M + 1792;
constexpr int KVP = 6 * 128;

enum { NB_G2E = 1, NB_XS = 2, NB_WG01 = 3, NB_ACT = 4, NB_Q0 = 5  , NB_ST = 14, NB_DN = 9, NB_ZERO = 10, NB_PUB = 11, NB_TOK = 10  , NB_L0 = 12  , NB_WG2 = 7, NB_QGO = 15 };

struct Scratch {
  bf16     o[SEQ * DM];
  float4   rstat[SEQ];
  uint32_t key[32 * 128];
  uint32_t cand[128 * DM];
  uint32_t ypart[NFFN * DM];
  float4   kvacc[32 * KVP];
  uint2    stats[SEQ];
  uint32_t cskv[2 * DM];
  uint32_t csq[4 * DM];
  uint32_t oset[16 * 32];
  uint32_t epoch;
};
__device__ __align__(1024) Scratch g_scr;
#define TS(id)
#define TDUMP()
#define TS0_DECL()
#define TS0_READ()
#define TS0_WRITE()
#define TK(id)
#define TSW(id)

struct Params {
  CUtensorMap x128, x64, wkv, wq, wo[2], wd, wg, wu, phi, tg, tu, td;
  const bf16 *x, *wqkv, *wo_p, *wg_p, *wu_p, *wd_p, *wr;
  bf16* out_p;
  Scratch* g;
};

constexpr float EXP_LIM = 1.1529215e18f, ARG_LIM2 = 3600.f;
__device__ __forceinline__ void dual_exp2(const float (&p)[2][16], uint32_t (&ph)[4][8]) {
  #pragma unroll
  for (int h = 0; h < 2; h++)
    #pragma unroll
    for (int k = 0; k < 8; k++) { ph[2*h][k] = pack_bf16(ex2(p[h][2*k]), ex2(p[h][2*k+1])); ph[2*h+1][k] = pack_bf16(ex2(-p[h][2*k]), ex2(-p[h][2*k+1])); }
}
__device__ __forceinline__ void row_extremes(const float (&p)[16], const float (&c)[2], float (&m)[4]) {
  m[0] = m[2] = p[0]; m[1] = m[3] = p[2];
  #pragma unroll
  for (int i = 0; i < 16; i++) { m[(i >> 1) & 1] = fmaxf(m[(i >> 1) & 1], p[i]); m[2 + ((i >> 1) & 1)] = fminf(m[2 + ((i >> 1) & 1)], p[i]); }
  #pragma unroll
  for (int o = 1; o < 4; o <<= 1) {
    m[0] = fmaxf(m[0], __shfl_xor_sync(~0u, m[0], o)); m[1] = fmaxf(m[1], __shfl_xor_sync(~0u, m[1], o));
    m[2] = fminf(m[2], __shfl_xor_sync(~0u, m[2], o)); m[3] = fminf(m[3], __shfl_xor_sync(~0u, m[3], o));
  }
  m[0] *= -c[0]; m[1] *= -c[1]; m[2] *= c[0]; m[3] *= c[1];
}
__device__ __forceinline__ void dual_exp2_shifted(const float (&p)[2][16], uint32_t (&ph)[4][8]) {
  #pragma unroll
  for (int h = 0; h < 2; h++) {
    const float one[2] = {1.f, 1.f};
    float m[4];
    row_extremes(p[h], one, m);
    #pragma unroll
    for (int k = 0; k < 8; k++) {
      ph[2*h][k] = pack_bf16(ex2(p[h][2*k] + m[k & 1]), ex2(p[h][2*k+1] + m[k & 1]));
      ph[2*h+1][k] = pack_bf16(ex2(m[2 + (k & 1)] - p[h][2*k]), ex2(m[2 + (k & 1)] - p[h][2*k+1]));
    }
  }
}
__device__ __forceinline__ void row_sums(float (&s)[4][4], const uint32_t (&ph)[4][8], uint32_t ones) {
  #pragma unroll
  for (int i = 0; i < 4; i++) wgmma_rz_n8<0, H0>(s[i], ph[i][0], ph[i][1], ph[i][2], ph[i][3], ones);
  #pragma unroll
  for (int i = 0; i < 4; i++) wgmma_ra_n8<0, H0>(s[i], ph[i][4], ph[i][5], ph[i][6], ph[i][7], ones);
}
__device__ __forceinline__ uint32_t mul_bf16x2(uint32_t a, uint32_t b) { uint32_t r; asm("mul.rn.bf16x2 %0, %1, %2;" : "=r"(r) : "r"(a), "r"(b)); return r; }
__device__ __forceinline__ void normalize(uint32_t (&ph)[4][8], const float (&s)[4][4]) {
  #pragma unroll
  for (int i = 0; i < 4; i++) {
    const float i0 = rcp(s[i][0]), i1 = rcp(s[i][2]);
    const uint32_t n0 = pack_bf16(i0, i0), n1 = pack_bf16(i1, i1);
    #pragma unroll
    for (int k = 0; k < 4; k++) { ph[i][2*k] = mul_bf16x2(ph[i][2*k], n0); ph[i][2*k+1] = mul_bf16x2(ph[i][2*k+1], n1); }
  }
}
__device__ __forceinline__ void split_bf16(float a, float b, uint32_t& hi, uint32_t& lo) { hi = pack_bf16(a, b); lo = pack_bf16(a - bf_lo(hi), b - bf_hi(hi)); }
__device__ __forceinline__ void put_colsums(uint32_t base, int lane, float a, float b, float c, float d) {
  uint32_t h0, l0, h1, l1;
  split_bf16(a, b, h0, l0); split_bf16(c, d, h1, l1);
  const uint32_t ad = base + (lane >> 1) * 128 + (lane & 1) * 8;
  sts64(ad, h0, h1); sts64(ad + 16, l0, l1); sts64(ad + 32, h0, h1); sts64(ad + 48, l0, l1);
  sts128(base + (lane >> 1) * 128 + 64 + (lane & 1) * 32, 0, 0, 0, 0); sts128(base + (lane >> 1) * 128 + 80 + (lane & 1) * 32, 0, 0, 0, 0);
}
__device__ __forceinline__ float reduce8(const float (&v)[8], int lane) {
  const bool b4 = lane & 16, b3 = lane & 8, b2 = lane & 4;
  float a[4], b[2];
  #pragma unroll
  for (int i = 0; i < 4; i++) a[i] = (b4 ? v[4 + i] : v[i]) + __shfl_xor_sync(~0u, b4 ? v[i] : v[4 + i], 16);
  #pragma unroll
  for (int i = 0; i < 2; i++) b[i] = (b3 ? a[2 + i] : a[i]) + __shfl_xor_sync(~0u, b3 ? a[i] : a[2 + i], 8);
  return (b2 ? b[1] : b[0]) + __shfl_xor_sync(~0u, b2 ? b[0] : b[1], 4);
}
__device__ __forceinline__ bool tag_bad(uint4 v, uint32_t tg) { return (((v.x ^ tg) | (v.y ^ tg) | (v.z ^ tg) | (v.w ^ tg)) & 3) != 0; }

__device__ __forceinline__ void project_q(float (&p)[2][16], uint32_t off, int w0, int w1) {
  const uint32_t da = dlo(SB0, 16) + (off >> 4);
  wg_fence();
  #pragma unroll
  for (int h = 0; h < 2; h++) {
    const uint32_t db = dlo(SB0 + OFF_WPHIQ, 16) + (h ? w1 : w0) * 128;
    wgmma_ss_n32<0, 1, H128, H64>(p[h], da + 4 * h, db, 0);
    wgmma_sa_n32<0, 1, H128, H64>(p[h], da + 4 * h + 2, db + 64);
  }
  wg_commit();
}

__global__ void __launch_bounds__(512, 1) fused_kernel(const __grid_constant__ Params P) {
  extern __shared__ __align__(1024) uint8_t smem_raw[];
  const uint32_t sb = smem_u32(smem_raw);
  const int tid = threadIdx.x, lane = tid & 31;
  const int warp = __shfl_sync(~0u, tid >> 5, 0), wg = warp >> 2, wp = warp & 3;
  const int cp = blockIdx.x >> 1, cu = cp - 36, cd = (cu * 37) >> 8;
  const int gi = cp < 4 ? 0 : cu < 0 ? (cp - 4) & 7 : 1 + cu - 7 * cd, gx = cp < 4 ? 4 + cp : cu < 0 ? (cp - 4) >> 3 : 4 + cd;
  const int rank = blockIdx.x & 1, c = 64 * (gi & 1) + 8 * gx + (gi & 6) + rank;
  const int f = 16 * ((gi + 7) & 7) + 2 * gx + rank;
  const int m256 = c >> 4, nkv = c & 15, m128 = c >> 3, j = c & 7;
  const int ha = 4 * (nkv >> 1) + (nkv & 1);

  Scratch* const G = P.g;
  if ((sb & 0x3ffff) != SB0) asm volatile("trap;");

  TS0_DECL();
  if (warp == 12) {
    const bool el = elect_one();
    TS0_READ();
    if (el) {
      #pragma unroll
      for (int i = 0; i < 4; i++) mbar_init(sb + B_FULLKV + 8 * i, 1);
      asm volatile("fence.mbarrier_init.release.cluster;" ::: "memory");
      fence_async_smem();
      #pragma unroll
      for (int s = 0; s < NPRE; s++) {
        const uint32_t st = sb + s * KV_STAGE, fb = sb + B_FULLKV + 8 * s;
        mbar_expect_tx(fb, KV_STAGE);
        tma_4d(st + 32768, &P.wkv, 0, 64 * s, nkv, 1, fb);
        tma_2d(st, &P.x128, 64 * s, 256 * m256, fb);
        tma_2d(st + 16384, &P.x128, 64 * s, 256 * m256 + 128, fb);
      }
    }
  } else if (tid == 0) {
    #pragma unroll
    for (int i = 0; i < 22; i++) mbar_init(sb + B_EMPTYKV + 8 * i, i >= 20 ? 4 : i < 4 ? 12 : (i >= 9 && i < 14) ? 4 : i == 17 || i == 18 ? 2 : 1);
    #pragma unroll
    for (int i = 0; i < 25; i++) mbar_init(sb + B_F + 8 * i, i > 20 ? 2 : i != 18 ? 1 : 8);
    #pragma unroll
    for (int i = 0; i < 16; i++) mbar_init(sb + B_FULLA + 8 * i, i < 11 ? 1 : i == 11 ? 2 : 4);
    asm volatile("fence.mbarrier_init.release.cluster;" ::: "memory");
    fence_async_smem();
  }
  __syncthreads();
  cluster_arrive();

  if (wg == 3) {
    asm volatile("setmaxnreg.dec.sync.aligned.u32 32;");
    cluster_wait();
    const bool el = elect_one();
    const uint64_t ef = policy_evict_first(), en = policy_evict_normal();
    auto fetch_o = [&](const int odd, uint32_t so, uint32_t par) {
      uint32_t ready = 0;
      const bf16* base = G->o + (m128 * 16 + odd) * 8192 + rank * 4096;
      const bf16* hint = base + (lane & 3) * 1024 + 966 + (odd ? (((j >> 1) + (lane >> 3)) & 3) * 32768 + 8 * (~lane & 4) : (((j & 6) + (lane >> 2)) & 7) * 16384);
      #pragma unroll 1
      for (int i = odd ? 0 : 2; i < 8; i++) {
        uint32_t it = 0;
        if (odd && i == 4) { ready = 0; hint += 16384; }
        while ((~ready >> (odd ? 8 * (i & 3) : 4 * i) & (odd ? 255 : 15)) && ++it < POLL_LIMIT) ready = __ballot_sync(~0u, ld32_rlx(hint) != ~0u);
        if (odd && i == 0) bar_sync(NB_L0, 64);
        mbar_wait(sb + B_EMPTY5 + so, par);
        if (el) {
          bulk_g2s_mc(sb + so * 4096 + rank * 8192, base + (odd ? (((j >> 1) + i) & 3) * 32768 + (i >> 2) * 16384 : (((j & 6) + i) & 7) * 16384), 8192, sb + B_FULLA + 2 * so + 8 * rank, ef);
          if (i == 2 && !odd) TS(rank ? 4 : 12);
          if (odd && !(i & 3)) TS(i ? (rank ? 31 : 10) : (rank ? 9 : 13));
        }
        so += 8;
        if (so == 40) { so = 0; par ^= 1; }
      }
    };
    if (wp == 0) {
      {
        #pragma unroll 1
        for (int kb = NPRE; kb < 16; kb++) {
          const uint32_t st = sb + (kb & 3) * KV_STAGE, fb = sb + B_FULLKV + 8 * (kb & 3);
          mbar_wait(fb + (B_EMPTYKV - B_FULLKV), ~(kb >> 2) & 1);
          if (el) {
            mbar_expect_tx(fb, KV_STAGE);
            tma_2d_mc(st + rank * 16384, &P.x128, 64 * kb, 256 * m256 + 128 * rank, fb);
            tma_4d_h(st + 32768, &P.wkv, 0, 64 * kb, nkv, 1, fb, ef);
          }
        }
        TS0_WRITE();
        uint64_t ord = 0xf3120edcba987654ull;
        uint32_t so = 0, par = 1;
        #pragma unroll 1
        for (int i = 0; i < 16; i++) {
          const uint32_t st = sb + so * 4096, fb = sb + B_FULL5 + so;
          const int k0 = (64 * (uint32_t)ord + 128 * (j & 6)) & 960;
          mbar_wait(i < 5 ? sb + B_EMPTYKV + so - (i > 1 ? 8 : 0) : fb + (B_EMPTY5 - B_FULL5), par);
          if (el) {
            mbar_expect_tx(fb, R5);
            tma_2d_mc_h(st + rank * 8192, &P.x64, k0, 128 * m128 + 64 * rank, fb, i >= EFI ? ef : en);
            tma_3d_h(st + 16384, &P.wq, 0, k0, 2 * j, fb, ef);
          }
          ord >>= 4; so += 8;
          if (so == 40) { so = 0; par ^= 1; }
        }
        #pragma unroll 1
        for (int i = 0; i < 16; i++) {
          const uint32_t fb = sb + B_FULL5 + so, fa = sb + B_FULLA + 2 * so, na = i == rank ? 0 : 8192;
          if (i == 1) { if (el) mbar_arrive(sb + B_QL); mbar_wait2(sb + B_FULL5 + 16, 0, sb + B_FULL5 + 24, 0); mbar_wait(sb + B_FULL5 + 32, 0); if (el) mbar_arrive(sb + B_R); }
          mbar_wait(fb + (B_EMPTY5 - B_FULL5), par);
          if (el) {
            mbar_expect_tx(fb, 16384);
            const int row = i < 8 ? 128 * (((j & 6) + i) & 7) : 256 * (((j >> 1) + i) & 3) + 32 + 16 * (i & 4);
            tma_5d_h(sb + so * 4096 + 16384, &P.wo[i >> 3], 128 * j, row, fb, ef);
            tma_5d_h(sb + so * 4096 + 24576, &P.wo[i >> 3], 128 * j + 64, row, fb, ef);
            mbar_expect_tx(fa, na); mbar_expect_tx(fa + 8, na);
          }
          so += 8;
          if (so == 40) { so = 0; par ^= 1; }
        }
        mbar_wait(sb + B_EMPTY5 + 16, 1); if (el) mbar_arrive(sb + B_DR);
        mbar_wait(sb + B_EMPTY5 + 24, 1); if (el) mbar_arrive(sb + B_DR + 8);
      }
    } else if (wp == 3) {
      const uint32_t t_start = (uint32_t)clock();
      if (el) {
        mbar_expect_tx(sb + B_W, 12288);
        #pragma unroll 1
        for (int i = 0; i < 6; i++) tma_2d(sb + (i == 0 ? OFF_WPHIK : i == 1 ? OFF_WPHIK1 : OFF_WPHIQ + 2048 * (i - 2)), &P.phi, 0, 32 * (i < 2 ? 2 * nkv + i : 4 * j + 2 * (i & 1) + ((i - 2) >> 1)), sb + B_W);
        prefetch_map(&P.x64); prefetch_map(&P.wq); prefetch_map(&P.wo[0]); prefetch_map(&P.wo[1]);
        prefetch_map(&P.wd); prefetch_map(&P.wg); prefetch_map(&P.wu);
      }
      #pragma unroll 1
      for (int i = 0; i < 8; i++) {
        st128_rlx(&G->cand[(m128 * 8 + i) * DM + (lane >> 4) * 512 + 64 * j + 4 * (lane & 15)], ~0u, ~0u, ~0u, ~0u);
        if (f < NFFN) st128_rlx(&G->ypart[f * DM + 128 * i + 4 * lane], ~0u, ~0u, ~0u, ~0u);
      }
      if (lane < 16) st128_rlx(&G->rstat[16 * c + lane], 0, 0, 0, 0);
      if (lane < 8) st128_rlx(&G->key[(4 * j + (lane >> 1)) * 128 + m128 * 8 + 4 * (lane & 1)], 0, 0, 0, 0);
      if (c < 32) {
        #pragma unroll 1
        for (int i = lane; i < KVP; i += 32) st128_rlx(&G->kvacc[(ha + 2 * m256) * KVP + i], 0, 0, 0, 0);
      }
      fence_gpu();
      bar_arrive(NB_ZERO, 160);
      if (el) {
        #pragma unroll 1
        for (int i = 0; i < 30; i++) {
          while ((uint32_t)clock() - t_start < (uint32_t)(PF_T0 + PF_DT * i)) __nanosleep(64);
          if (i < 4) { bulk_prefetch(P.wqkv + (size_t)(256 * i + c) * (3 * DM), 2048); bulk_prefetch(P.wqkv + (size_t)(256 * i + 128 + c) * (3 * DM), 2048); }
          else if (i < 6) bulk_prefetch(P.wo_p + (size_t)c * 8192 + (i - 4) * 4096, 8192);
          else if ((TMASK >> (i - 6)) & 1) {
            const int k = i - 6;
            if (f < NFFN) {
              if (k < 16) {
                #pragma unroll 1
                for (int e = 0; e < 4; e++) tma_2d(sb + OFF_T, rank ? &P.tu : &P.tg, 32 * (f & ~1), 64 * k + 16 * e, sb + B_T);
              } else { tma_2d(sb + OFF_T, &P.td, 0, 256 * f + 32 * (k - 16), sb + B_T); tma_2d(sb + OFF_T, &P.td, 0, 256 * f + 32 * (k - 16) + 16, sb + B_T); }
            }
          }
          else if (!((PMASK >> (i - 6)) & 1)) {}
          else if (i < 22) bulk_prefetch(((i & 1) ? P.wu_p : P.wg_p) + (size_t)((i - 6) >> 1) * 458752 + c * 3584, 7168);
          else bulk_prefetch(P.wd_p + (size_t)(i - 22) * 458752 + c * 3584, 7168);
        }
      }
      __syncwarp();
      mbar_wait2(sb + B_OS, 0, sb + B_RX, 0);
      fetch_o(0, 24, 0);
      bar_arrive(NB_L0, 64);
    } else {
      const int half = wp - 1;
      const uint32_t ep1 = ld32_rlx(&G->epoch) + 1, tg = ep1 & 3;
      {
        uint32_t it = 0;
        sts128(sb + OFF_ONES + half * 512 + lane * 16, 0x3f803f80u, 0x3f803f80u, 0x3f803f80u, 0x3f803f80u);
        auto reset_o = [&](int i0, int i1, uint32_t dt) {
          uint32_t t0 = (uint32_t)clock();
          #pragma unroll 1
          for (int i = i0; i < i1; i++) {
            st128_rlx(G->o + (m128 * 16 + 2 * j + half) * 8192 + 256 * i + 8 * lane, ~0u, ~0u, ~0u, ~0u);
            while ((uint32_t)clock() - t0 < dt) __nanosleep(40);
            t0 += dt;
          }
        };
        mbar_wait(sb + B_W, 0);
        reset_o(0, RS_N, RS_D1);
        bar_sync(NB_PUB, 192);
        const uint4* src = reinterpret_cast<const uint4*>(&G->stats[256 * m256 + 128 * half]) + lane;
        const uint4* srk = reinterpret_cast<const uint4*>(&G->cskv[128 * nkv]) + lane;
        uint4 v0, v1, vk;
        it = 0;
        do { v0 = ld128_rlx(src); v1 = ld128_rlx(src + 32); vk = ld128_rlx(srk); }
        while ((tag_bad(v0, tg) || tag_bad(v1, tg) || tag_bad(vk, tg)) && ++it < POLL_LIMIT);
        fence_acquire_gpu();
        if (half) put_colsums(sb + OFF_BXK, lane, untag(vk.x), untag(vk.y), untag(vk.z), untag(vk.w));
        #pragma unroll
        for (int i = 0; i < 2; i++) {
          const uint4 v = i ? v1 : v0;
          uint32_t hi, lo;
          split_bf16(-0.5f * untag(v.x), -0.5f * untag(v.z), hi, lo);
          const uint32_t h0 = __byte_perm(hi, hi, 0x1010), h1 = __byte_perm(hi, hi, 0x3232), l0 = __byte_perm(lo, lo, 0x1010), l1 = __byte_perm(lo, lo, 0x3232);
          const uint32_t a = sb + OFF_AXK + half * 2048 + i * 1024 + lane * 32;
          sts128(a, h0, l0, 0, 0); sts128(a + 16, h1, l1, 0, 0);
          sts64(sb + OFF_RS256 + half * 512 + i * 256 + lane * 8, v.y & ~3u, v.w & ~3u);
          if (half == (m128 & 1)) {
            const uint32_t aq = sb + OFF_AXQ + i * 1024 + lane * 32;
            sts128(aq, h0, l0, 0, 0); sts128(aq + 16, h1, l1, 0, 0);
            sts64(sb + OFF_RSQ + i * 256 + lane * 8, v.y & ~3u, v.w & ~3u);
          }
        }
        fence_async_smem();
        __syncwarp();
        if (el) { sts32(sb + OFF_EP, ep1); mbar_arrive(sb + B_AUX); if (!half) TS(1); }
        reset_o(RS_N, 32, RS_D2);
        fence_gpu();
        __syncwarp();
        if (el) { st32_rlx(&G->oset[m128 * 32 + 2 * j + half], ep1); if (half) mbar_arrive(sb + B_AUXQ); }
        if (!half) {
          const uint4* src = reinterpret_cast<const uint4*>(&G->csq[128 * j]) + lane;
          uint4 v0, v1, v2, v3;
          do { v0 = ld128_rlx(src); v1 = ld128_rlx(src + DM / 4); v2 = ld128_rlx(src + DM / 2); v3 = ld128_rlx(src + 3 * DM / 4); }
          while ((tag_bad(v0, tg) || tag_bad(v1, tg) || tag_bad(v2, tg) || tag_bad(v3, tg)) && ++it < POLL_LIMIT);
          put_colsums(sb + OFF_BXQ, lane, (untag(v0.x) + untag(v1.x)) + (untag(v2.x) + untag(v3.x)), (untag(v0.y) + untag(v1.y)) + (untag(v2.y) + untag(v3.y)),
                      (untag(v0.z) + untag(v1.z)) + (untag(v2.z) + untag(v3.z)), (untag(v0.w) + untag(v1.w)) + (untag(v2.w) + untag(v3.w)));
          fence_async_smem();
          __syncwarp();
          if (el) mbar_arrive(sb + B_AUXQ);
        }
      }
      if (half == 0) {
        for (uint32_t it = 0; __any_sync(~0u, ld32_rlx(&G->oset[m128 * 32 + (lane & 15)]) != ep1) && it < POLL_LIMIT; it++) {}
        fence_acquire_gpu();
        if (el) mbar_arrive(sb + B_OS);
      }
      auto put_gu = [&](int e, uint32_t dst) { mbar_expect_tx(sb + B_F + 8 * e, 16384); tma_2d(dst, &P.wg, 32 * f, 128 * e, sb + B_F + 8 * e); tma_2d(dst + 8192, &P.wu, 32 * f, 128 * e, sb + B_F + 8 * e); };
      if (half && f < NFFN_L) {
        if (Q0L) mbar_wait(sb + B_UO + 8 * Q0L - 8, 0);
        mbar_wait2(sb + B_KD, 0, sb + B_QL, 0);
        if (el) put_gu(0, sb + OFF_X + 16384);
      }
      if (!half) {
        #pragma unroll 1
        for (int hh = 0; hh < 2; hh++) {
          const uint32_t src = sb + (1 + rank) * R5 + hh * 8192, fa = sb + B_FULLA + 16 + 16 * rank + 8 * hh;
          mbar_wait(fa, 0);
          mbar_wait(sb + B_UO + 8 * hh, 0);
          if (el) bulk_s2peer(mapa(src, rank ^ 1), src, 8192, mapa(fa, rank ^ 1));
        }
        fetch_o(1, 32, 1);
      }
      else if (f < NFFN_L) {
        mbar_wait2(sb + B_UO, 0, sb + B_UO + 8, 0);
        mbar_wait(sb + B_UO + 24, 0);
        uint32_t t0 = (uint32_t)clock();
        while ((uint32_t)clock() - t0 < (uint32_t)FF_T0) __nanosleep(32);
        t0 -= FF_DT;
        #pragma unroll 1
        for (int i = 0; i < 11; i++) {
          const uint32_t dst = sb + 16384 * ((0x7654cadcadcull >> (4 * i)) & 15);
          if (i >= 3) mbar_wait(sb + B_WC + 8 * (i < 7 ? i - 3 : (i + 1) >> 1), 0);
          while ((uint32_t)clock() - t0 < (uint32_t)FF_DT) __nanosleep(32);
          t0 = (uint32_t)clock();
          TK(48 + i);
          if (el) {
            if (i < 4) { mbar_expect_tx(sb + B_WD + 8 * i, 16384); tma_3d_h(dst, &P.wd, 0, 32 * f, 4 * i, sb + B_WD + 8 * i, ef); }
            else put_gu(i - 3, dst);
          }
        }
      }
      __syncwarp();
    }
    {
      const int ch = lane & 15, rb = 32 * wp + (lane >> 4);
      const uint32_t src = sb + R5 + (ch >> 3) * 16384;
      bf16* dst = P.out_p + (size_t)(128 * m128) * DM + 128 * j + 8 * ch;
      __syncwarp();
      mbar_wait(sb + B_OUT + 8 * wp, 0);
      const float2 ex = lds64f(sb + OFF_EXC + 8 * wp);
      if (OUT_L) mbar_wait(sb + B_XS, 0);
      #pragma unroll 1
      for (int i = 0; i < 32; i += 2 * OUT_U) {
        uint4 v[OUT_U];
        #pragma unroll
        for (int e = 0; e < OUT_U; e++) { const int r = rb + i + 2 * e; v[e] = lds128(src + r * 128 + (((ch ^ r) & 7) << 4)); }
        #pragma unroll
        for (int e = 0; e < OUT_U; e++) { const int r = rb + i + 2 * e; if (r != __float_as_int(i < 16 ? ex.x : ex.y)) *reinterpret_cast<uint4*>(dst + r * DM) = v[e]; }
        if (OUT_NS) __nanosleep(OUT_NS);
      }
      if (wp == 0) { TK(63); }
      mbar_wait(sb + B_XS, 0);
      const int row = 2047 - (__float_as_uint(ldsf(sb + OFF_KEY)) & 2047) - 128 * m128, r = __float_as_int(lane < 16 ? ex.x : ex.y);
      if (r != row) *reinterpret_cast<uint4*>(dst + r * DM) = lds128(src + r * 128 + (((ch ^ r) & 7) << 4));
    }
    __syncwarp();
    cluster_arrive(); cluster_wait();
    return;
  }

  asm volatile("setmaxnreg.inc.sync.aligned.u32 160;");
  cluster_wait();
  const int t = tid & 127, g = lane >> 2;
  const uint32_t sa = (16 * wp + (lane & 15)) * 128 + (((lane >> 4) ^ (lane & 7)) << 4);

  if (wg == 2) {
    float s[2] = {0.f, 0.f}, s2[2] = {0.f, 0.f}, ck[8] = {0.f, 0.f, 0.f, 0.f, 0.f, 0.f, 0.f, 0.f}, cs[8] = {0.f, 0.f, 0.f, 0.f, 0.f, 0.f, 0.f, 0.f};
    const uint32_t ebr = mapa(sb + B_EMPTYKV, lane & 1), tg = (ld32_rlx(&G->epoch) + 1) & 3;
    auto addx = [&](const uint4 v) {
      const uint32_t w[4] = {v.x, v.y, v.z, v.w};
      #pragma unroll
      for (int e = 0; e < 4; e++) { const float a = bf_lo(w[e]), d = bf_hi(w[e]); s[0] += a; s[1] += d; s2[0] = fmaf(a, a, s2[0]); s2[1] = fmaf(d, d, s2[1]); }
    };
    auto addc = [&](const uint4 v, float (&o)[8]) {
      o[0] += bf_lo(v.x); o[1] += bf_hi(v.x); o[2] += bf_lo(v.y); o[3] += bf_hi(v.y); o[4] += bf_lo(v.z); o[5] += bf_hi(v.z); o[6] += bf_lo(v.w); o[7] += bf_hi(v.w);
    };
    {
      const uint32_t ra = (16 * nkv + (t >> 3)) * 128 + (t & 7) * 16;
      const uint32_t ca = 32768 + (m256 >> 2) * 8192 + (t >> 1) * 128 + (((2 * (m256 & 3) + (t & 1)) ^ ((t >> 1) & 7)) << 4);
      const bf16* gx = P.x + (size_t)(256 * m256 + 16 * nkv + (t >> 3)) * DM + 640 + (t & 7) * 8;
      const bf16* gw = P.wqkv + (size_t)(640 + (t >> 1)) * (3 * DM) + (1 + (m256 >> 2)) * DM + 64 * nkv + 16 * (m256 & 3) + 8 * (t & 1);
      uint4 u[4];
      #pragma unroll
      for (int e = 0; e < 4; e++) u[e] = make_uint4(0, 0, 0, 0);
      #pragma unroll 1
      for (int kb = 0; kb < 10; kb++) {
        const uint32_t st = sb + (kb & 3) * KV_STAGE;
        mbar_wait(sb + B_FULLKV + 8 * (kb & 3), (kb >> 2) & 1);
        const uint4 x0 = lds128(st + ra), w0 = lds128(st + ca);
        addx(x0); addc(w0, ck);
        __syncwarp();
        if (lane < 2) mbar_arrive_remote(ebr + 8 * (kb & 3), 1);
        if ((SKM >> kb) & 1) {
          addx(u[0]); addx(u[1]); addc(u[2], ck); addc(u[3], ck);
          if (kb < 9) {
            u[0] = ld128_keep(gx); u[1] = ld128_keep(gx + 64); u[2] = ld128_keep(gw); u[3] = ld128_keep(gw + 64 * 3 * DM);
            gx += 128; gw += 128 * 3 * DM;
          }
        }
      }
    }
    TK(82);
    const uint32_t scr = sb + OFF_SCR + 128;
    float sx = s[0] + s[1], sq = s2[0] + s2[1];
    #pragma unroll
    for (int o = 1; o < 8; o <<= 1) { sx += __shfl_xor_sync(~0u, sx, o); sq += __shfl_xor_sync(~0u, sq, o); }
    float v = reduce8(ck, lane);
    v += __shfl_xor_sync(~0u, v, 2);
    if (!(lane & 2)) stsf(scr + (wp * 16 + 8 * (lane & 1) + (lane >> 2)) * 4, v);

    bar_sync(NB_ZERO, 160);
    if ((lane & 7) == 0) {
      const float mean = sx * (1.f / DM);
      st64_rlx(&G->stats[256 * m256 + 16 * nkv + (t >> 3)], tagw(mean, tg), tagw(rsqrtf(fmaxf(sq * (1.f / DM) - mean * mean, 0.f) + 1e-5f), tg));
    }
    if (wp == 1 && lane < 16) {
      const uint32_t a = scr + lane * 4;
      st32_rlx(&G->cskv[128 * nkv + 16 * m256 + lane], tagw((ldsf(a) + ldsf(a + 64)) + (ldsf(a + 128) + ldsf(a + 192)), tg));
    }
    __syncwarp();
    bar_arrive(NB_PUB, 192);
    TSW(23);
    const uint4 wv = ld128_keep(P.wr + t * 8);
    #pragma unroll 1
    for (int i = 0; i < 2; i++) {
      const bf16* gq = P.wqkv + (size_t)(256 * (c >> 5) + 128 * i + (t >> 2)) * (3 * DM) + 32 * (c & 31) + 8 * (t & 3);
      const uint4 u0 = ld128_keep(gq), u1 = ld128_keep(gq + 32 * 3 * DM), u2 = ld128_keep(gq + 64 * 3 * DM), u3 = ld128_keep(gq + 96 * 3 * DM);
      addc(u0, cs); addc(u1, cs); addc(u2, cs); addc(u3, cs);
    }
    float sw = (bf_lo(wv.x) + bf_hi(wv.x)) + (bf_lo(wv.y) + bf_hi(wv.y)) + (bf_lo(wv.z) + bf_hi(wv.z)) + (bf_lo(wv.w) + bf_hi(wv.w));
    #pragma unroll
    for (int o = 16; o; o >>= 1) sw += __shfl_xor_sync(~0u, sw, o);
    if (lane == 0) stsf(sb + OFF_SUMWR + wp * 4, sw);
    if ((t >> 4) == j) {
      const uint32_t a = sb + OFF_WR + (t & 15) * 32;
      sts128(a, wv.x << 16, wv.x & 0xffff0000u, wv.y << 16, wv.y & 0xffff0000u);
      sts128(a + 16, wv.z << 16, wv.z & 0xffff0000u, wv.w << 16, wv.w & 0xffff0000u);
    }
    v = reduce8(cs, lane);
    bar_sync(NB_WG2, 128);
    stsf(scr + (wp * 32 + 8 * (lane & 3) + (lane >> 2)) * 4, v);
    bar_sync(NB_WG2, 128);
    if (wp == 0) {
      const uint32_t a = scr + lane * 4;
      st32_rlx(&G->csq[(c >> 5) * DM + 32 * (c & 31) + lane], tagw((ldsf(a) + ldsf(a + 128)) + (ldsf(a + 256) + ldsf(a + 384)), tg));
    }
  }

  uint32_t xr[32];
  {
    const bool isq = wg == 2;
    float acc[2][64];
    {
      const uint32_t emptyb = mapa(sb + (isq ? B_EMPTY5 : B_EMPTYKV), t & 1);
      if (!isq) {
        mbar_wait(sb + B_FULLKV, 0);
        if (wg == 0) { TSW(2); }
        #pragma unroll 1
        for (int kb = 0; kb < 16; kb++) {
          if (wg == 0) { TK(kb); }
          const uint32_t da = dlo(SB0, 16) + wg * 1024 + (kb & 3) * (KV_STAGE >> 4), db = dlo(SB0 + 32768, 8192) + (kb & 3) * (KV_STAGE >> 4);
          wg_fence();
          #pragma unroll
          for (int k = 0; k < 4; k++) {
            wgmma_ss_n128<0, 1, H128, H128>(acc[0], da + 2 * k, db + 128 * k, k > 0 || kb != 0);
            wgmma_ss_n128<0, 1, H128, H128>(acc[1], da + 512 + 2 * k, db + 128 * k, k > 0 || kb != 0);
          }
          wg_commit();
          wg_wait<1>();
          if (kb > 0 && t < 2) mbar_arrive_remote(emptyb + 8 * ((kb - 1) & 3), kb > 10 ? 3 : 1);
          if (kb < 15) mbar_wait(sb + B_FULLKV + 8 * ((kb + 1) & 3), ((kb + 1) >> 2) & 1);
          if (kb == 15 - LAG && wg == 1) bar_sync(NB_WG01, 256);
        }
        bar_arrive(wg ? NB_QGO : NB_WG01, 256);
      } else {
        uint32_t so = 0, po = 0, par = 0;
        mbar_wait(sb + B_FULL5, 0);
        bar_sync(NB_QGO, 256);
        TSW(11);
        #pragma unroll 1
        for (int kb = 0; kb < 16; kb++) {
          TK(16 + kb);
          const uint32_t da = dlo(SB0, 16) + so * 256, db = dlo(SB0 + 16384, 8192) + so * 256;
          #pragma unroll
          for (int k = 0; k < 4; k++) {
            wg_fence();
            wgmma_ss_n128<0, 1, H128, H128>(acc[0], da + 2 * k, db + 128 * k, k > 0 || kb != 0);
            wgmma_ss_n128<0, 1, H128, H128>(acc[1], da + 512 + 2 * k, db + 128 * k, k > 0 || kb != 0);
            wg_commit();
            if (k == 1 && kb > 0 && t < 2) mbar_arrive_remote(emptyb + po, 2);
            if (k == 3) {
              po = so; so += 8;
              if (so == 40) { so = 0; par ^= 1; }
              if (kb < 15) mbar_wait(sb + B_FULL5 + so, par);
            }
            if ((QW >> k) & 1) wg_wait<2>(); else wg_wait<1>();
          }
        }
        mbar_wait(sb + B_AUXQ, 0);
      }
      mbar_wait(sb + B_AUX, 0);
      const uint32_t xa = dlo(SB0, 0) + (isq ? OFF_AXQ >> 4 : (OFF_AXK >> 4) + wg * 128), xb = dlo(SB0, 0) + (isq ? OFF_BXQ >> 4 : OFF_BXK >> 4);
      wg_fence();
      wgmma_sa_n128<0, 1, H0, H0>(acc[0], xa, xb);
      wgmma_sa_n128<0, 1, H0, H0>(acc[1], xa + 64, xb);
      wg_commit();
      if (isq) mbar_wait(sb + B_RC, 0);
      wg_wait<0>();
      if (t < 2) mbar_arrive_remote(emptyb + (isq ? 0 : 24), isq ? 2 : 3);
      if (wg != 1) { TSW(wg ? 8 : 3); }
      fence_regs(acc[0]); fence_regs(acc[1]);
    }
    if (isq) {
      #pragma unroll
      for (int i = 0; i < 4; i++) {
        const uint32_t ta = sb + (i < 2 ? (1 + rank) * R5 : OFF_X) + sa + (i & 1) * 8192;
        if (i == 1) mbar_wait(sb + B_RC + 8, 0);
        #pragma unroll
        for (int k = 0; k < 4; k++) {
          const float* a = i < 2 ? &acc[i][32 * (k >> 1) + 8 * (k & 1)] : &acc[k >> 1][16 + 32 * (i & 1) + 8 * (k & 1)];
          stsm4(ta ^ (k << 5), pack_bf16(a[0], a[1]), pack_bf16(a[2], a[3]), pack_bf16(a[4], a[5]), pack_bf16(a[6], a[7]));
        }
        if (i < 2) { fence_async_smem(); bar_arrive(NB_Q0 + i, 256); }
      }
      TSW(26);
    } else {
      const uint32_t stg = sb + OFF_X + (1 - wg) * 24576;
      const uint32_t va = stg + 16384 + (16 * wp + (lane & 15)) * 64 + (((lane >> 4) ^ ((lane >> 1) & 3)) << 4);
      const uint32_t ra = sb + OFF_RS256 + (128 * wg + 16 * wp + g) * 4;
      const float rs[4] = {ldsf(ra), ldsf(ra + 32), ldsf(ra + 256), ldsf(ra + 288)};
      float p[2][16];
      uint32_t vf[16], kf[2][16];
      auto project = [&](const uint32_t (&f)[16], uint32_t db) {
        wg_fence();
        #pragma unroll
        for (int i = 0; i < 2; i++) {
          wgmma_rs_n32<1, H64>(p[i], f[8*i], f[8*i+1], f[8*i+2], f[8*i+3], db, 0);
          wgmma_ra_n32<1, H64>(p[i], f[8*i+4], f[8*i+5], f[8*i+6], f[8*i+7], db + 64);
        }
        wg_commit();
      };
      auto fold = [&](uint32_t (&f)[16], int col, float sc) {
        #pragma unroll
        for (int i = 0; i < 16; i++) {
          const float r = rs[2 * (i >> 3) + (i & 1)] * sc;
          f[i] = pack_bf16(acc[i >> 3][col + 2 * (i & 7)] * r, acc[i >> 3][col + 2 * (i & 7) + 1] * r);
          asm volatile("" : "+r"(f[i]));
        }
      };
      auto put_v = [&](const uint32_t (&f)[16]) {
        #pragma unroll
        for (int k = 0; k < 4; k++) stsm4((va ^ ((k & 1) << 5)) + (k >> 1) * 4096, f[4*k], f[4*k+1], f[4*k+2], f[4*k+3]);
      };
      fold(vf, 48, 1.f);
      mbar_wait(sb + B_W, 0);
      fold(kf[0], 0, LOG2E);
      #pragma unroll
      for (int i = 0; i < 32; i++) p[i >> 4][i & 15] = acc[i >> 4][i & 15];
      project(kf[0], dlo(SB0 + OFF_WPHIK, 16));
      mbar_wait(sb + B_W, 0);
      {
        uint32_t v0[16];
        fold(kf[1], 16, LOG2E);
        fold(v0, 32, 1.f);
        if (wg == 1) bar_sync(NB_DN, 256);
        put_v(v0);
      }
      wg_wait<0>();
      fence_regs(p[0]); fence_regs(p[1]);
      if (wg == 1) bar_arrive(NB_WG01, 256);
      #pragma unroll 1
      for (int h = 0; h < 2; h++) {
        uint32_t ph[4][8];
        float rsum[4][4];
        dual_exp2(p, ph);
        wg_fence();
        row_sums(rsum, ph, dlo(SB0 + OFF_ONES, 128));
        wg_commit();
        if (wg == 0 && h == 0) { bar_arrive(NB_DN, 256); bar_sync(NB_WG01, 256); }
        if (h == 1) {
          if (wg == 1) bar_sync(NB_DN, 256);
          put_v(vf);
        }
        wg_wait<0>();
        #pragma unroll
        for (int i = 0; i < 4; i++) fence_regs(rsum[i]);
        if (__builtin_expect(__any_sync(~0u, !((rsum[0][0] + rsum[0][2]) + (rsum[1][0] + rsum[1][2]) + (rsum[2][0] + rsum[2][2]) + (rsum[3][0] + rsum[3][2]) < EXP_LIM)), 0)) {
          dual_exp2_shifted(p, ph);
          #pragma unroll
          for (int i = 0; i < 8; i++) {
            const uint32_t* f = &ph[i >> 1][i & 1];
            float a = (bf_lo(f[0]) + bf_hi(f[0])) + (bf_lo(f[2]) + bf_hi(f[2])) + (bf_lo(f[4]) + bf_hi(f[4])) + (bf_lo(f[6]) + bf_hi(f[6]));
            a += __shfl_xor_sync(~0u, a, 1);
            rsum[i >> 1][2 * (i & 1)] = a + __shfl_xor_sync(~0u, a, 2);
          }
        }
        if (h == 0) project(kf[1], dlo(SB0 + OFF_WPHIK1, 16));
        normalize(ph, rsum);
        #pragma unroll
        for (int i = 0; i < 8; i++) {
          const uint32_t* f = &ph[i >> 1][4 * (i & 1)];
          stsm4(((stg + sa) ^ ((i & 3) << 5)) + (i >> 2) * 8192, f[0], f[1], f[2], f[3]);
        }
        fence_async_smem();
        if (wg == h) {
          float kv[20];
          #pragma unroll
          for (int w = 0; w < 2; w++) {
            const uint32_t da = dlo(SB0 + OFF_X, 16) + (h ^ w ^ 1) * 1536, db = dlo(SB0 + OFF_X + 16384, OFF_ONES - OFF_X - 16384) - (h ^ w ^ 1) * (1536 * 65535);
            if (w) bar_sync(NB_ST, 256); else bar_sync(NB_L0 + h, 128);
            wg_fence();
            #pragma unroll
            for (int k = 0; k < 8; k++) {
              if (k == 0 && w == 0) wgmma_sz_n40<1, 1, H128, H64>(kv, da, db);
              else wgmma_sa_n40<1, 1, H128, H64>(kv, da + k * 128, db - k * (64 * 65535));
            }
            wg_commit();
          }
          float4* dst = &G->kvacc[(ha + 2 * h) * KVP + t];
          wg_wait<0>();
          fence_regs(kv);
          if (h == 0) bar_arrive(NB_DN, 256); else if (t == 0) mbar_arrive(sb + B_KD);
          kv[17] = kv[18];
          #pragma unroll
          for (int i = 0; i < 6; i++) red_add_f32x4(dst + 128 * i, kv[3*i], kv[3*i+1], kv[3*i+2], 1.f);
          TSW(29 + h);
        } else bar_arrive(NB_ST, 256);
        wg_wait<0>();
        fence_regs(p[0]); fence_regs(p[1]);
      }
    }
    auto capture = [&]() {
      mbar_wait(sb + B_R, 0);
      #pragma unroll
      for (int k = 0; k < 8; k++) ldsm4(((sb + (1 + rank) * R5 + wg * 8192 + sa) ^ ((k & 3) << 5)) + (k >> 2) * 2 * R5, xr[4*k], xr[4*k+1], xr[4*k+2], xr[4*k+3]);
      fence_async_smem();
      __syncwarp();
      if (lane == 0) { mbar_arrive(sb + B_RC + 8 * wg); mbar_arrive_at(sb + B_RX, wg, 1); }
    };
    #pragma unroll
    for (int i = 0; i < 32; i++) asm volatile("mov.b32 %0, 0;" : "=r"(xr[i]));
    if (wg == 1) capture();
    {
      const uint4* src = reinterpret_cast<const uint4*>(&G->kvacc[(4 * j + wg) * KVP + t]);
      uint4 v[12];
      uint32_t it = 0, bad;
      do {
        bad = 0;
        #pragma unroll
        for (int i = 0; i < 12; i++) {
          v[i] = make_uint4(0, 0, 0, 0x41000000u);
          if (i < 6 || isq) v[i] = ld128_rlx(src + 128 * i);
          bad |= v[i].w ^ 0x41000000u;
        }
      } while (__any_sync(~0u, bad != 0) && ++it < POLL_LIMIT);
      mbar_wait(sb + B_KD, 0);
      #pragma unroll
      for (int e = 0; e < 2; e++) {
        if (e == 0 || isq) {
          float f[18];
          #pragma unroll
          for (int i = 0; i < 6; i++) { f[3*i] = __uint_as_float(v[6*e+i].x); f[3*i+1] = __uint_as_float(v[6*e+i].y); f[3*i+2] = __uint_as_float(v[6*e+i].z); }
          const uint32_t ka = sb + OFF_KVZ + (wg + e) * 5120 + wp * 1280 + lane * 16;
          stsm4(ka, pack_bf16(f[0], f[1]), pack_bf16(f[2], f[3]), pack_bf16(f[4], f[5]), pack_bf16(f[6], f[7]));
          stsm4(ka + 512, pack_bf16(f[8], f[9]), pack_bf16(f[10], f[11]), pack_bf16(f[12], f[13]), pack_bf16(f[14], f[15]));
          stsm2(ka + 1024, pack_bf16(f[16], 1.f), pack_bf16(f[17], 1.f));
        }
      }
    }
    if (wg == 0) capture(); else fence_async_smem();
    if (wg == 1) bar_arrive(NB_DN, 256);
    if (isq) mbar_wait(sb + B_OS, 0);
    TSW(wg == 0 ? 5 : wg == 1 ? 25 : 6);
    float p[2][16];
    #pragma unroll
    for (int i = 0; i < 32; i++) asm volatile("mov.b32 %0, 0;" : "=f"(p[i >> 4][i & 15]));
    #pragma unroll 1
    for (int e = wg; e < wg + 1 + (wg >> 1); e++) {
      const int half = e >> 1, hh = e & 1, turn = e;
      const uint32_t ao = (half ? OFF_X : (1 + rank) * R5) + hh * 8192;
      const uint32_t ra = sb + OFF_RSQ + (16 * wp + g) * 4 + (e == 1 ? 256 : 0), rb = ra + 256 * half;
      const float cc[2][2] = {{ldsf(ra) * LOG2E, ldsf(ra + 32) * LOG2E}, {ldsf(rb) * LOG2E, ldsf(rb + 32) * LOG2E}};
      float m[2][4] = {{0.f, 0.f, 0.f, 0.f}, {0.f, 0.f, 0.f, 0.f}};
      uint32_t ph[2][8];
      auto exps = [&](int h) {
        #pragma unroll
        for (int k = 0; k < 8; k++) {
          const float c = cc[h][k & 1], mp = m[h][k & 1], mm = m[h][2 + (k & 1)];
          ph[0][k] = pack_bf16(ex2(fmaf(p[h][2*k], c, mp)), ex2(fmaf(p[h][2*k+1], c, mp)));
          ph[1][k] = pack_bf16(ex2(fmaf(p[h][2*k], -c, mm)), ex2(fmaf(p[h][2*k+1], -c, mm)));
        }
      };
      uint32_t shifted = 0;
      asm volatile("" : "+r"(shifted));
      #pragma unroll 1
      for (;;) {
        if (shifted) { row_extremes(p[0], cc[0], m[0]); row_extremes(p[1], cc[1], m[1]); }
        uint32_t first = (shifted ^ 1) & (e != 3);
        asm volatile("" : "+r"(first));
        if (first) {
          bar_sync(NB_Q0 + wg, isq ? 128 : 256);
          project_q(p, ao, 2 * half, 1 + half);
          if (e) bar_sync(NB_TOK + e - 1, 256);
          wg_wait<0>();
        }
        TK(64 + 4 * turn);
        fence_regs(p[0]); fence_regs(p[1]);
        exps(0);
        float s2[4] = {0.f, 0.f, 0.f, 0.f};
        #pragma unroll
        for (int i = 0; i < 32; i++) s2[((i >> 1) & 1) + 2 * (i >> 4)] = fmaf(p[i >> 4][i & 15], p[i >> 4][i & 15], s2[((i >> 1) & 1) + 2 * (i >> 4)]);
        if (!__any_sync(~0u, !shifted & !((s2[0] * cc[0][0] * cc[0][0] < ARG_LIM2) & (s2[1] * cc[0][1] * cc[0][1] < ARG_LIM2) &
                                          (s2[2] * cc[1][0] * cc[1][0] < ARG_LIM2) & (s2[3] * cc[1][1] * cc[1][1] < ARG_LIM2)))) break;
        shifted = 1;
      }
      float ac[4][20];
      auto numer = [&](int h, const uint32_t (&f)[2][8]) {
        const uint32_t db = dlo(SB0 + OFF_KVZ, 128) + (half ? e : h) * 320;
        wg_fence();
        #pragma unroll
        for (int i = 0; i < 2; i++) {
          wgmma_rz_n40<1, dhi(256, 0)>(ac[2*h+i], f[i][0], f[i][1], f[i][2], f[i][3], db + i * 160);
          wgmma_ra_n40<1, dhi(256, 0)>(ac[2*h+i], f[i][4], f[i][5], f[i][6], f[i][7], db + (i * 160 + 80));
        }
        wg_commit();
      };
      const uint32_t oa = (16 * wp + g) * 128 + (((lane & 3) ^ g) << 4);
      auto finish = [&](int h) {
        const float* ap = ac[2 * h]; const float* am = ac[2 * h + 1];
        const float ip0 = rcp(ap[17]), im0 = rcp(am[17]), ip1 = rcp(ap[19]), im1 = rcp(am[19]);
        const float d0 = rcp(fmaf(ap[16], ip0, fmaf(am[16], im0, 1e-6f))), d1 = rcp(fmaf(ap[18], ip1, fmaf(am[18], im1, 1e-6f)));
        const float a0 = ip0 * d0, b0 = im0 * d0, a1 = ip1 * d1, b1 = im1 * d1;
        #pragma unroll
        for (int r = 0; r < 2; r++) {
          const float a = r ? a1 : a0, b = r ? b1 : b0;
          uint32_t w[4];
          #pragma unroll
          for (int k = 0; k < 4; k++) w[k] = pack_bf16(fmaf(ap[4*k+2*r], a, am[4*k+2*r] * b), fmaf(ap[4*k+2*r+1], a, am[4*k+2*r+1] * b));
          const uint32_t off = (oa ^ ((half ? rank : h) << 6)) + r * 1024;
          st128_rlx(reinterpret_cast<uint8_t*>(G->o + (m128 * 16 + (half ? 2 * (j & 6) + 2 * hh + 1 : 2 * j)) * 8192 + (half ? h : hh) * 4096) + off, w[0], w[1], w[2], w[3]);
          if (!half) sts128(sb + ao + off, w[0], w[1], w[2], w[3]);
        }
      };
      numer(0, ph);
      exps(1);
      if (wg == 0) bar_sync(NB_DN, 256);
      numer(1, ph);
      if (turn < 2) bar_arrive(NB_TOK + turn, 256);
      wg_wait<1>();
      TK(65 + 4 * turn);
      fence_regs(ac[0]); fence_regs(ac[1]);
      finish(0);
      wg_wait<0>();
      fence_regs(ac[2]); fence_regs(ac[3]);
      #pragma unroll
      for (int i = 0; i < 32; i++) asm volatile("mov.b32 %0, 0;" : "=f"(p[i >> 4][i & 15]));
      if (e == 2) project_q(p, ao + 8192, 3, 3);
      finish(1);
      TK(66 + 4 * turn);
      if (!half) fence_async_smem();
      __syncwarp();
      if (lane == 0) mbar_arrive(sb + B_UO + 8 * e);
      wg_wait<0>();
      TK(67 + 4 * turn);
    }
    if (isq) cluster_arrive();
  }

  {
  int lane;
  asm volatile("mov.u32 %0, %%laneid;" : "=r"(lane));
  const int g = lane >> 2, q = lane & 3;
  if (wg < 2) {
    float h[64];
    {
      if (wg == 0) { TK(83); }
      #pragma unroll
      for (int i = 0; i < 32; i++) { h[2*i] = bf_lo(xr[i]); h[2*i+1] = bf_hi(xr[i]); }
      fence_regs(h);
      TK(80 + wg);
      const uint64_t seq = rank ? 0x1043210432104312ull : 0x1043210432104321ull;
      const uint32_t emptyb = mapa(sb + B_EMPTY5, t & 1);
      uint32_t s = 1 + rank, ps = 0;
      mbar_wait2(sb + B_FULL5 + 8 * s, 1, sb + B_UO + 8 * wg, 0);
      if (wg == 0) { TSW(14); }
      #pragma unroll G2U
      for (int i = 0; i < 16; i++) {
        if (wg == 1 && (i & 12) == TKW) { TK(84 + (i & 3)); }
        if (wg == 0) { TK(32 + i); }
        const uint32_t da = dlo(SB0, 16) + s * 2048 + wg * 512, db = dlo(SB0 + 16384, 8192) + s * 2048;
        wg_fence();
        #pragma unroll
        for (int k = 0; k < 4; k++) wgmma_sa_n128<0, 1, H128, H128>(h, da + k * 2, db + k * 128);
        wg_commit();
        const uint32_t ns = (uint32_t)((seq >> 4) >> (4 * i)) & 15;
        const uint32_t b0 = sb + B_FULL5 + 8 * ns, p0 = (0x1f07 >> i) & 1, b1 = sb + B_FULLA + 16 * ns + 8 * wg, p1 = (0x41f0 >> i) & 1;
        const bool here = mbar_test2(b0, p0, b1, p1);
        wg_wait<1>();
        if (!(((2 * REL + 1) >> i) & 1) && t < 2) mbar_arrive_remote(emptyb + 8 * ps, 1);
        if ((REL >> i) & 1) { wg_wait<0>(); if (t < 2) mbar_arrive_remote(emptyb + 8 * s, 1); }
        if (!here) mbar_wait2(b0, p0, b1, p1);
        ps = s; s = ns;
      }
    }
    cluster_arrive();
    float2 wr[16];
    #pragma unroll
    for (int i = 0; i < 16; i++) wr[i] = lds64f(sb + OFF_WR + 32 * i + 8 * q);
    const int r0 = 64 * wg + 16 * wp + g;
    float sum0, sum1, dot0, dot1, sq0, sq1;
    uint32_t redo = 0;
    asm volatile("" : "+r"(redo));
    #pragma unroll 1
    for (;;) {
    if (redo) {
      wg_wait<0>();
      const int r = r0;
      #pragma unroll 1
      for (int n = 0; n < 16; n++) {
        const uint32_t* xp = reinterpret_cast<const uint32_t*>(P.x + (size_t)(128 * m128 + r) * DM + 128 * j + 8 * n) + q;
        const uint32_t x0 = xp[0], x1 = xp[4 * DM];
        float d0 = bf_lo(x0), d1 = bf_hi(x0), d2 = bf_lo(x1), d3 = bf_hi(x1);
        #pragma unroll 1
        for (int ks = 0; ks < 64; ks++) {
          const int kb = ks >> 2, kk = 16 * (ks & 3);
          const bf16* op = G->o + (m128 * 16 + kb) * 8192 + r * 64 + 2 * q;
          const int o0 = ((kk >> 3) ^ g) << 3;
          const uint16_t* w = reinterpret_cast<const uint16_t*>(P.wo_p) + (size_t)(((kb & 1) ? 256 * (kb >> 2) + 32 * (kb & 2) + 32 + 4 * (kk & 32) : 64 * kb + 2 * (kk & 32)) + ((kk & 16) >> 2) + 8 * q) * DM + 128 * j + 8 * n + g;
          const uint32_t b0 = w[0] | (w[DM] << 16), b1 = w[2 * DM] | (w[3 * DM] << 16);
          uint32_t a0, a1, a2, a3, it = 0;
          do { a0 = ld32_rlx(op + o0); a1 = ld32_rlx(op + 512 + o0); a2 = ld32_rlx(op + (o0 ^ 8)); a3 = ld32_rlx(op + 512 + (o0 ^ 8)); }
          while (max(max(a0, a1), max(a2, a3)) == ~0u && ++it < POLL_LIMIT);
          __syncwarp();
          mma16816(d0, d1, d2, d3, a0, a1, a2, a3, b0, b1);
        }
        #pragma unroll
        for (int i = 0; i < 60; i++) h[i] = h[i + 4];
        h[60] = d0; h[61] = d1; h[62] = d2; h[63] = d3;
      }
    }
    wg_wait<0>();
    fence_regs(h);
    if (wg == 0) { TSW(16); }
    sum0 = 0.f, sum1 = 0.f, dot0 = 0.f, dot1 = 0.f, sq0 = 0.f, sq1 = 0.f;
    #pragma unroll
    for (int i = 0; i < 16; i++) {
      sum0 += h[4*i] + h[4*i+1]; sum1 += h[4*i+2] + h[4*i+3];
      sq0 = fmaf(h[4*i], h[4*i], fmaf(h[4*i+1], h[4*i+1], sq0)); sq1 = fmaf(h[4*i+2], h[4*i+2], fmaf(h[4*i+3], h[4*i+3], sq1));
      dot0 = fmaf(h[4*i], wr[i].x, fmaf(h[4*i+1], wr[i].y, dot0)); dot1 = fmaf(h[4*i+2], wr[i].x, fmaf(h[4*i+3], wr[i].y, dot1));
    }
    if (!__any_sync(~0u, !redo & (h[0] != h[0] | h[2] != h[2]))) break;
    redo = 1;
    }
    float4* const rs = &G->rstat[128 * m128 + r0];
    {
      const bool up = q & 2;
      float a = up ? sum1 : sum0, b = up ? sq1 : sq0, d = up ? dot1 : dot0;
      a += __shfl_xor_sync(~0u, up ? sum0 : sum1, 2); b += __shfl_xor_sync(~0u, up ? sq0 : sq1, 2); d += __shfl_xor_sync(~0u, up ? dot0 : dot1, 2);
      a += __shfl_xor_sync(~0u, a, 1); b += __shfl_xor_sync(~0u, b, 1); d += __shfl_xor_sync(~0u, d, 1);
      if ((q & 1) == 0) red_add_f32x4(rs + 4 * q, a, b, d, 1.f);
    }
    bar_arrive(NB_G2E, 384);
    if (wg == 0) { TSW(24); }
    bar_sync(NB_WG01, 256);
    uint32_t wa[8][4][4];
    const uint32_t wb = sb + 16384 * ((0x7654cadb >> (4 * warp)) & 15) + ((lane & 7) + ((lane >> 4) << 3)) * 64 + ((((lane >> 3) & 1) ^ ((lane >> 1) & 3)) << 4);
    auto getw = [&](int ks) {
      #pragma unroll
      for (int m = 0; m < 4; m++) ldsm4t((wb ^ ((m & 1) << 5)) + (m >> 1) * 8192 + ks * 1024, wa[ks][m][0], wa[ks][m][1], wa[ks][m][2], wa[ks][m][3]);
    };
    if (GPRE && f < NFFN_L) mbar_wait(sb + B_F + 8 * warp, 0);
    if (warp == 7) { TK(60); }
    #pragma unroll
    for (int ks = 0; ks < GPRE; ks++) getw(ks);
    float rstd[2], bm[2];
    uint32_t best;
    {
      const float2 swa = lds64f(sb + OFF_SUMWR), swb = lds64f(sb + OFF_SUMWR + 8);
      const float sw = (swa.x + swa.y) + (swb.x + swb.y);
      uint4 a[2]; uint32_t it = 0, key[2];
      do { a[0] = ld128_rlx(rs); a[1] = ld128_rlx(rs + 8); } while (__any_sync(~0u, (a[0].w & a[1].w) != 0x41000000u) && ++it < POLL_LIMIT);
      #pragma unroll
      for (int i = 0; i < 2; i++) {
        const float mean = __uint_as_float(a[i].x) * (1.f / DM);
        rstd[i] = rsqrtf(fmaxf(__uint_as_float(a[i].y) * (1.f / DM) - mean * mean, 0.f) + 1e-5f);
        bm[i] = -mean * rstd[i];
        const uint32_t rr = __float_as_uint(fmaf(__uint_as_float(a[i].z), rstd[i], sw * bm[i]));
        key[i] = ((rr ^ ((uint32_t)((int32_t)rr >> 31) | 0x80000000u)) & ~2047u) | (2047 - 128 * m128 - r0 - 8 * i);
      }
      asm volatile("redux.sync.max.u32 %0, %1, 0xffffffff;" : "=r"(best) : "r"(max(key[0], key[1])));
    }
    if (wg == 0) { TSW(17); }
    const int slot = m128 * 8 + warp, win = ~best & 15;
    if (lane < 4) st32_rlx(&G->key[(4 * j + lane) * 128 + slot], best);
    if ((win & 7) == g) {
      const bool up = win & 8;
      const float ra = up ? rstd[1] : rstd[0], rb = up ? bm[1] : bm[0];
      uint32_t x[16];
      #pragma unroll
      for (int i = 0; i < 16; i++) x[i] = pack_bf16(fmaf(up ? h[4*i+2] : h[4*i], ra, rb), fmaf(up ? h[4*i+3] : h[4*i+1], ra, rb));
      #pragma unroll
      for (int i = 0; i < 4; i++) st128_rlx(&G->cand[slot * DM + 64 * j + 16 * i + 4 * q], x[4*i], x[4*i+1], x[4*i+2], x[4*i+3]);
    }
    __syncwarp();
    if (wg == 0) { TSW(27); }
    {
      const float a0 = 1.f + rstd[0], b0 = bm[0], a1 = 1.f + rstd[1], b1 = bm[1];
      #pragma unroll
      for (int k = 0; k < 8; k++)
        stsm4(((sb + R5 + wg * 8192 + sa) ^ ((k & 3) << 5)) + (k >> 2) * 16384,
              pack_bf16(fmaf(h[8*k], a0, b0), fmaf(h[8*k+1], a0, b0)),     pack_bf16(fmaf(h[8*k+2], a1, b1), fmaf(h[8*k+3], a1, b1)),
              pack_bf16(fmaf(h[8*k+4], a0, b0), fmaf(h[8*k+5], a0, b0)),   pack_bf16(fmaf(h[8*k+6], a1, b1), fmaf(h[8*k+7], a1, b1)));
      sts32(sb + OFF_EXC + 4 * warp, 16 * warp + win);
      __syncwarp();
      if (lane == 0) mbar_arrive(sb + B_OUT + 8 * (warp >> 1));
      if (lane < 16) {
        const uint4 v = lds128(sb + R5 + (lane >> 3) * 16384 + (16 * warp + win) * 128 + (((lane & 7) ^ (win & 7)) << 4));
        st128_rlx(&G->cand[slot * DM + 512 + 64 * j + 4 * lane], v.x, v.y, v.z, v.w);
      }
    }
    if (wg == 0) { TSW(28); }
    {
      if (!GPRE && f < NFFN_L) mbar_wait(sb + B_F + 8 * warp, 0);
      #pragma unroll
      for (int ks = GPRE; ks < GRES; ks++) getw(ks);
      if (wg == 0) { TSW(15); }
      bar_sync(NB_XS, 384);
      if (wg == 0) { TSW(19); }
      uint4 xs[4];
      #pragma unroll
      for (int i = 0; i < 4; i++) xs[i] = lds128(sb + OFF_XSEL + 256 * warp + 64 * i + 16 * q);
      float d[4][4];
      #pragma unroll
      for (int ks = 0; ks < 8; ks++) {
        if (ks >= 1 && GRES + ks - 1 < 8) getw(GRES + ks - 1);
        #pragma unroll
        for (int m = 0; m < 4; m++) {
          if (ks == 0) { d[m][0] = 0.f; d[m][1] = 0.f; d[m][2] = 0.f; d[m][3] = 0.f; }
          mma16816(d[m][0], d[m][1], d[m][2], d[m][3], wa[ks][m][0], wa[ks][m][1], wa[ks][m][2], wa[ks][m][3],
                   (ks & 1) ? xs[ks >> 1].z : xs[ks >> 1].x, (ks & 1) ? xs[ks >> 1].w : xs[ks >> 1].y);
        }
      }
      if (q == 0) {
        #pragma unroll
        for (int m = 0; m < 8; m++) stsf(sb + OFF_GU + (8 * m + g) * 48 + 4 * warp, d[m >> 1][2 * (m & 1)]);
      }
      bar_arrive(NB_ACT, 384);
    }
    {
      float y0 = 0.f, y1 = 0.f, y2 = 0.f, y3 = 0.f;
      const uint32_t ky = __float_as_uint(ldsf(sb + OFF_KEY));
      const int kidx = 2047 - (ky & 2047);
      const float kr = __uint_as_float((ky & ~2047u) ^ ((ky >> 31) ? 0x80000000u : 0xfffff800u));
      const int col = 128 * (c >> 4) + 64 * (c & 1) + 32 * ((tid >> 2) & 1) + 16 * (tid & 1) + 8 * ((tid >> 1) & 1) + ((c >> 1) & 7);
      uint32_t it = 0, base = 0;
      if (tid < 8) {
        do { base = ld32_rlx(&G->cand[(kidx >> 4) * DM + 512 + (col >> 1)]); } while (base == ~0u && ++it < POLL_LIMIT);
      }
      if (tid < 2 * NFFN) {
        uint4 v;
        do { v = ld128_rlx(&G->ypart[(tid >> 1) * DM + 8 * c + 4 * (tid & 1)]); } while (v.w == ~0u && ++it < POLL_LIMIT);
        y0 = __uint_as_float(v.x); y1 = __uint_as_float(v.y); y2 = __uint_as_float(v.z); y3 = __uint_as_float(v.w);
      }
      __syncwarp();
      const bool b4 = lane & 16, b3 = lane & 8;
      const float u0 = (b4 ? y1 : y0) + __shfl_xor_sync(~0u, b4 ? y0 : y1, 16), u1 = (b4 ? y3 : y2) + __shfl_xor_sync(~0u, b4 ? y2 : y3, 16);
      float ys = (b3 ? u1 : u0) + __shfl_xor_sync(~0u, b3 ? u0 : u1, 8);
      ys += __shfl_xor_sync(~0u, ys, 4); ys += __shfl_xor_sync(~0u, ys, 2);
      if (!(lane & 6)) stsf(sb + OFF_ACT + ((4 * (lane & 1) + ((lane >> 3) & 1) * 2 + (lane >> 4)) * 8 + warp) * 4, ys);
      const float sg = __fdividef(1.f, 1.f + __expf(-kr));
      bar_sync(NB_WG01, 256);
      if (tid < 8) {
        const uint4 v0 = lds128(sb + OFF_ACT + tid * 32), v1 = lds128(sb + OFF_ACT + tid * 32 + 16);
        const float t8 = ((__uint_as_float(v0.x) + __uint_as_float(v0.y)) + (__uint_as_float(v0.z) + __uint_as_float(v0.w))) +
                         ((__uint_as_float(v1.x) + __uint_as_float(v1.y)) + __uint_as_float(v1.z));
        P.out_p[(size_t)kidx * DM + col] = __float2bfloat16(fmaf(t8, sg, (col & 1) ? bf_hi(base) : bf_lo(base)));
      }
      if (c == 0 && tid == 0) st32_rlx(&G->epoch, __float_as_uint(ldsf(sb + OFF_EP)));
      if (wg == 0) { TSW(22); TDUMP(); }
    }
  }
  if (wg == 2) {
    uint32_t wf[16][2][4];
    {
      const uint32_t wb = sb + 16384 * ((0xcadc >> (4 * wp)) & 15) + ((lane & 7) + ((lane >> 4) << 3)) * 128 + ((((lane >> 3) & 1) ^ (lane & 7)) << 4);
      if (f < NFFN_L) mbar_wait(sb + B_WD + 8 * wp, 0);
      if (wp == 0) { TK(61); }
      #pragma unroll
      for (int i = 0; i < 32; i++) ldsm4t((wb ^ (((i >> 1) & 3) << 5)) + (i >> 3) * 4096 + (i & 1) * 2048, wf[i >> 1][i & 1][0], wf[i >> 1][i & 1][1], wf[i >> 1][i & 1][2], wf[i >> 1][i & 1][3]);
      fence_async_smem();
      __syncwarp();
      if (lane == 0) mbar_arrive(sb + B_WC + 8 * wp);
      if (wp == 0) { TK(62); }
    }
    bar_sync(NB_G2E, 384);
    {
      uint32_t cur = 0;
      uint4 v;
      #pragma unroll 1
      for (uint32_t it = 0; it < POLL_LIMIT; it++) {
        const uint4 kx = ld128_rlx(&G->key[(c & 31) * 128 + 4 * lane]);
        v = ld128_rlx(&G->cand[((~cur >> 4) & 127) * DM + 4 * t]);
        uint32_t best;
        asm volatile("redux.sync.max.u32 %0, %1, 0xffffffff;" : "=r"(best) : "r"(max(max(kx.x, kx.y), max(kx.z, kx.w))));
        if (!__any_sync(~0u, min(min(kx.x, kx.y), min(kx.z, kx.w)) == 0 || v.w == ~0u) && best == cur) break;
        cur = best;
      }
      sts128(sb + OFF_XSEL + 16 * t, v.x, v.y, v.z, v.w);
      sts32(sb + OFF_KEY, cur);
      bar_arrive(NB_XS, 384);
      if (t == 0) mbar_arrive(sb + B_XS);
      TSW(18);
      bar_sync(NB_ACT, 384);
    }
    float gu[2];
    #pragma unroll
    for (int i = 0; i < 2; i++) {
      const uint4 v0 = lds128(sb + OFF_GU + (32 * i + lane) * 48), v1 = lds128(sb + OFF_GU + (32 * i + lane) * 48 + 16);
      gu[i] = ((__uint_as_float(v0.x) + __uint_as_float(v0.y)) + (__uint_as_float(v0.z) + __uint_as_float(v0.w))) +
              ((__uint_as_float(v1.x) + __uint_as_float(v1.y)) + (__uint_as_float(v1.z) + __uint_as_float(v1.w)));
    }
    const float act = gu[0] * gu[1] * rcp(1.f + ex2(-LOG2E * gu[0]));
    const uint32_t ap = pack_bf16(act, __shfl_down_sync(~0u, act, 1));
    uint32_t bf[4];
    #pragma unroll
    for (int i = 0; i < 4; i++) bf[i] = __shfl_sync(~0u, ap, 2 * q + 8 * i);
    TSW(20);
    float d[16][4];
    #pragma unroll
    for (int k = 0; k < 2; k++)
      #pragma unroll
      for (int i = 0; i < 16; i++) {
        if (k == 0) { d[i][0] = 0.f; d[i][1] = 0.f; d[i][2] = 0.f; d[i][3] = 0.f; }
        mma16816(d[i][0], d[i][1], d[i][2], d[i][3], wf[i][k][0], wf[i][k][1], wf[i][k][2], wf[i][k][3], bf[2*k], bf[2*k+1]);
      }
    #pragma unroll
    for (int a = 0; a < 2; a++) {
      float y[4];
      #pragma unroll
      for (int e = 0; e < 4; e++) {
        const int n = 8 * a + (e & 1);
        const float lo = (q & 1) ? d[n + 2][e & 2] : d[n][e & 2], hi = (q & 1) ? d[n + 6][e & 2] : d[n + 4][e & 2];
        y[e] = (q & 2) ? hi : lo;
      }
      if (f < NFFN) st128_rlx(&G->ypart[f * DM + 256 * wp + 128 * a + 4 * lane], __float_as_uint(y[0]), __float_as_uint(y[1]), __float_as_uint(y[2]), min(__float_as_uint(y[3]), ~1u));
    }
    TSW(21);
  }
  }
  cluster_wait();
}

typedef CUresult (*EncodeFn)(CUtensorMap*, CUtensorMapDataType, cuuint32_t, void*, const cuuint64_t*, const cuuint64_t*,
                             const cuuint32_t*, const cuuint32_t*, CUtensorMapInterleave, CUtensorMapSwizzle,
                             CUtensorMapL2promotion, CUtensorMapFloatOOBfill);

void make_map(EncodeFn enc, CUtensorMap* m, const void* p, int n, const cuuint64_t* dims, const cuuint64_t* str, const cuuint32_t* box,
              CUtensorMapSwizzle sw, CUtensorMapL2promotion promo) {
  cuuint32_t es[5] = {1, 1, 1, 1, 1};
  enc(m, CU_TENSOR_MAP_DATA_TYPE_BFLOAT16, n, const_cast<void*>(p), dims, str, box, es, CU_TENSOR_MAP_INTERLEAVE_NONE, sw, promo,
      CU_TENSOR_MAP_FLOAT_OOB_FILL_NONE);
}
void map2(EncodeFn enc, CUtensorMap* m, const void* p, uint64_t cols, uint64_t rows, uint32_t bc, uint32_t br, CUtensorMapSwizzle sw,
          CUtensorMapL2promotion promo) {
  const cuuint64_t dims[2] = {cols, rows}, str[1] = {cols * 2};
  const cuuint32_t box[2] = {bc, br};
  make_map(enc, m, p, 2, dims, str, box, sw, promo);
}
void map3(EncodeFn enc, CUtensorMap* m, const void* p, uint64_t cols, uint64_t rows, uint32_t br, uint32_t nb) {
  const cuuint64_t dims[3] = {64, rows, cols / 64}, str[2] = {cols * 2, 128};
  const cuuint32_t box[3] = {64, br, nb};
  make_map(enc, m, p, 3, dims, str, box, CU_TENSOR_MAP_SWIZZLE_128B, CU_TENSOR_MAP_L2_PROMOTION_L2_128B);
}

}

extern "C" void kernel_launch(void* const* d_in, const int* in_sizes, int n_in, void* d_out, int out_size) {
  (void)in_sizes; (void)n_in; (void)out_size;
  static EncodeFn enc = nullptr;
  static void* o_ptr = nullptr;
  if (!enc) {
    void* f = nullptr; cudaDriverEntryPointQueryResult qr;
    cudaGetDriverEntryPoint("cuTensorMapEncodeTiled", &f, cudaEnableDefault, &qr);
    enc = (EncodeFn)f;
    cudaGetSymbolAddress(&o_ptr, g_scr);
    cudaFuncSetAttribute(fused_kernel, cudaFuncAttributeMaxDynamicSharedMemorySize, SMEM_BYTES);
  }
  const bf16* x = (const bf16*)d_in[0];
  const bf16* wqkv = (const bf16*)d_in[1];
  const bf16* wphi = (const bf16*)d_in[2];
  const bf16* wo = (const bf16*)d_in[3];
  const bf16* wr = (const bf16*)d_in[5];
  const bf16* wgate = (const bf16*)d_in[6];
  const bf16* wup = (const bf16*)d_in[7];
  const bf16* wdown = (const bf16*)d_in[8];
  Params P;
  const CUtensorMapSwizzle S128 = CU_TENSOR_MAP_SWIZZLE_128B, S64 = CU_TENSOR_MAP_SWIZZLE_64B;
  const CUtensorMapL2promotion L128 = CU_TENSOR_MAP_L2_PROMOTION_L2_128B, L256 = CU_TENSOR_MAP_L2_PROMOTION_L2_256B,
                               L64 = CU_TENSOR_MAP_L2_PROMOTION_L2_64B;
  map2(enc, &P.x128, x, DM, SEQ, 64, 128, S128, L256);
  map2(enc, &P.x64, x, DM, SEQ, 64, 64, S128, L128);
  {
    const cuuint64_t dims[4] = {64, DM, 16, 3}, str[3] = {6 * DM, 128, 2 * DM};
    const cuuint32_t box[4] = {64, 64, 1, 2};
    make_map(enc, &P.wkv, wqkv, 4, dims, str, box, S128, L128);
  }
  map3(enc, &P.wq, wqkv, 3 * DM, DM, 64, 2);
  for (int i = 0; i < 2; i++) {
    const cuuint64_t dims[5] = {DM, (cuuint64_t)(DM - 94 - 64 * i), 4, 4, 2}, str[4] = {2 * DM, 16 * DM, 4 * DM, (cuuint64_t)(128 * DM) << i};
    const cuuint32_t box[5] = {64, 2, 4, 4, 2};
    make_map(enc, &P.wo[i], wo, 5, dims, str, box, S128, L128);
  }
  map3(enc, &P.wd, wdown, DM, FF, 32, 4);
  map2(enc, &P.wg, wgate, FF, DM, 32, 128, S64, L64);
  map2(enc, &P.wu, wup, FF, DM, 32, 128, S64, L64);
  map2(enc, &P.tg, wgate, FF, DM, 8, 16, CU_TENSOR_MAP_SWIZZLE_NONE, L128);
  map2(enc, &P.tu, wup, FF, DM, 8, 16, CU_TENSOR_MAP_SWIZZLE_NONE, L128);
  map2(enc, &P.td, wdown, 128, FF * 8, 8, 16, CU_TENSOR_MAP_SWIZZLE_NONE, L256);
  map2(enc, &P.phi, wphi, 32, 1024, 32, 32, S64, L64);
  P.x = x; P.wqkv = wqkv; P.wo_p = wo; P.wd_p = wdown; P.wg_p = wgate; P.wu_p = wup; P.wr = wr; P.out_p = (bf16*)d_out; P.g = (Scratch*)o_ptr;

  cudaLaunchConfig_t cfg = {};
  cfg.gridDim = dim3(128); cfg.blockDim = dim3(512); cfg.dynamicSmemBytes = SMEM_BYTES; cfg.stream = cudaStreamPerThread;
  cudaLaunchAttribute at[1];
  at[0].id = cudaLaunchAttributeClusterDimension; at[0].val.clusterDim.x = 2; at[0].val.clusterDim.y = 1; at[0].val.clusterDim.z = 1;
  cfg.attrs = at; cfg.numAttrs = 1;
  cudaLaunchKernelEx(&cfg, fused_kernel, P);
}
```

```cpp
#include <cuda_runtime.h>
#include <cuda.h>
#include <cuda_bf16.h>
#include <stdint.h>

namespace {

typedef __nv_bfloat16 bf16;

__device__ __forceinline__ uint32_t smem_u32(const void* p){ return (uint32_t)__cvta_generic_to_shared(p); }
__device__ __forceinline__ void mbar_init(uint32_t bar, uint32_t cnt){ asm volatile("mbarrier.init.shared::cta.b64 [%0], %1;"::"r"(bar),"r"(cnt):"memory"); }
__device__ __forceinline__ void mbar_expect_tx(uint32_t bar, uint32_t bytes){ asm volatile("mbarrier.arrive.expect_tx.shared::cta.b64 _, [%0], %1;"::"r"(bar),"r"(bytes):"memory"); }
__device__ __forceinline__ void mbar_arrive(uint32_t bar){ asm volatile("mbarrier.arrive.shared::cta.b64 _, [%0];"::"r"(bar):"memory"); }
__device__ __forceinline__ uint32_t mapa(uint32_t addr, uint32_t cta){ uint32_t r; asm volatile("mapa.shared::cluster.u32 %0, %1, %2;":"=r"(r):"r"(addr),"r"(cta)); return r; }
__device__ __forceinline__ void mbar_arrive_at(uint32_t bar, uint32_t cta, uint32_t cnt){
  asm volatile("{\n.reg .b32 ra;\nmapa.shared::cluster.u32 ra, %0, %1;\nmbarrier.arrive.shared::cluster.b64 _, [ra], %2;\n}\n"::"r"(bar),"r"(cta),"r"(cnt):"memory"); }
__device__ __forceinline__ void mbar_arrive_remote(uint32_t cluster_addr, uint32_t cnt){
  asm volatile("mbarrier.arrive.shared::cluster.b64 _, [%0], %1;"::"r"(cluster_addr),"r"(cnt):"memory"); }
__device__ __forceinline__ void mbar_wait(uint32_t bar, uint32_t parity){
  asm volatile("{\n.reg .pred p;\n.reg .u32 c;\nmov.u32 c, 0;\nLW:\nmbarrier.try_wait.parity.shared::cta.b64 p, [%0], %1;\n@p bra LD;\nadd.u32 c, c, 1;\nsetp.lt.u32 p, c, 2000000;\n@p bra LW;\ntrap;\nLD:\n}\n"::"r"(bar),"r"(parity):"memory"); }
__device__ __forceinline__ void mbar_wait2(uint32_t bar0, uint32_t par0, uint32_t bar1, uint32_t par1){
  asm volatile("{\n.reg .pred p, q;\n.reg .u32 c;\nmov.u32 c, 0;\nLW:\nmbarrier.try_wait.parity.shared::cta.b64 p, [%0], %1;\nmbarrier.try_wait.parity.shared::cta.b64 q, [%2], %3;\nand.pred p, p, q;\n@p bra LD;\nadd.u32 c, c, 1;\nsetp.lt.u32 p, c, 2000000;\n@p bra LW;\ntrap;\nLD:\n}\n"::"r"(bar0),"r"(par0),"r"(bar1),"r"(par1):"memory"); }
__device__ __forceinline__ bool mbar_test2(uint32_t bar0, uint32_t par0, uint32_t bar1, uint32_t par1){
  uint32_t r;
  asm volatile("{\n.reg .pred p, q;\nmbarrier.test_wait.parity.shared::cta.b64 p, [%1], %2;\nmbarrier.test_wait.parity.shared::cta.b64 q, [%3], %4;\nand.pred p, p, q;\nselp.u32 %0, 1, 0, p;\n}\n":"=r"(r):"r"(bar0),"r"(par0),"r"(bar1),"r"(par1):"memory");
  return r; }
__device__ __forceinline__ void tma_2d(uint32_t dst, const CUtensorMap* m, int c0, int c1, uint32_t bar){
  asm volatile("cp.async.bulk.tensor.2d.shared::cluster.global.mbarrier::complete_tx::bytes [%0], [%1, {%3, %4}], [%2];"::"r"(dst),"l"(m),"r"(bar),"r"(c0),"r"(c1):"memory"); }
__device__ __forceinline__ void tma_2d_mc(uint32_t dst, const CUtensorMap* m, int c0, int c1, uint32_t bar){
  asm volatile("cp.async.bulk.tensor.2d.shared::cluster.global.mbarrier::complete_tx::bytes.multicast::cluster [%0], [%1, {%3, %4}], [%2], %5;"::"r"(dst),"l"(m),"r"(bar),"r"(c0),"r"(c1),"h"((uint16_t)3):"memory"); }
__device__ __forceinline__ void tma_2d_mc_h(uint32_t dst, const CUtensorMap* m, int c0, int c1, uint32_t bar, uint64_t pol){
  asm volatile("cp.async.bulk.tensor.2d.shared::cluster.global.mbarrier::complete_tx::bytes.multicast::cluster.L2::cache_hint [%0], [%1, {%3, %4}], [%2], %5, %6;"::"r"(dst),"l"(m),"r"(bar),"r"(c0),"r"(c1),"h"((uint16_t)3),"l"(pol):"memory"); }
__device__ __forceinline__ void tma_4d(uint32_t dst, const CUtensorMap* m, int c0, int c1, int c2, int c3, uint32_t bar){
  asm volatile("cp.async.bulk.tensor.4d.shared::cluster.global.mbarrier::complete_tx::bytes [%0], [%1, {%3, %4, %5, %6}], [%2];"::"r"(dst),"l"(m),"r"(bar),"r"(c0),"r"(c1),"r"(c2),"r"(c3):"memory"); }
__device__ __forceinline__ uint64_t policy_evict_first(){ uint64_t p; asm volatile("createpolicy.fractional.L2::evict_first.b64 %0, 1.0;":"=l"(p)); return p; }
__device__ __forceinline__ uint64_t policy_evict_normal(){ uint64_t p; asm("createpolicy.fractional.L2::evict_normal.b64 %0, 1.0;":"=l"(p)); return p; }
__device__ __forceinline__ void tma_3d_h(uint32_t dst, const CUtensorMap* m, int c0, int c1, int c2, uint32_t bar, uint64_t pol){
  asm volatile("cp.async.bulk.tensor.3d.shared::cluster.global.mbarrier::complete_tx::bytes.L2::cache_hint [%0], [%1, {%3, %4, %5}], [%2], %6;"::"r"(dst),"l"(m),"r"(bar),"r"(c0),"r"(c1),"r"(c2),"l"(pol):"memory"); }
__device__ __forceinline__ void tma_4d_h(uint32_t dst, const CUtensorMap* m, int c0, int c1, int c2, int c3, uint32_t bar, uint64_t pol){
  asm volatile("cp.async.bulk.tensor.4d.shared::cluster.global.mbarrier::complete_tx::bytes.L2::cache_hint [%0], [%1, {%3, %4, %5, %6}], [%2], %7;"::"r"(dst),"l"(m),"r"(bar),"r"(c0),"r"(c1),"r"(c2),"r"(c3),"l"(pol):"memory"); }
__device__ __forceinline__ void red_add_f32x4(float4* p, float x, float y, float z, float w){ asm volatile("red.relaxed.gpu.global.add.v4.f32 [%0], {%1,%2,%3,%4};"::"l"(p),"f"(x),"f"(y),"f"(z),"f"(w):"memory"); }
__device__ __forceinline__ void tma_5d_h(uint32_t dst, const CUtensorMap* m, int c0, int c1, uint32_t bar, uint64_t pol){
  asm volatile("cp.async.bulk.tensor.5d.shared::cluster.global.mbarrier::complete_tx::bytes.L2::cache_hint [%0], [%1, {%3, %4, 0, 0, 0}], [%2], %5;"::"r"(dst),"l"(m),"r"(bar),"r"(c0),"r"(c1),"l"(pol):"memory"); }
__device__ __forceinline__ bool elect_one(){ uint32_t p; asm volatile("{\n.reg .pred P;\nelect.sync _|P, 0xffffffff;\nselp.b32 %0, 1, 0, P;\n}\n":"=r"(p)); return p; }
__device__ __forceinline__ void bulk_prefetch(const void* p, uint32_t bytes){
  asm volatile("cp.async.bulk.prefetch.L2.global [%0], %1;"::"l"(p),"r"(bytes):"memory"); }
__device__ __forceinline__ void bulk_s2peer(uint32_t dst_cluster, uint32_t src, uint32_t bytes, uint32_t bar_cluster){
  asm volatile("cp.async.bulk.shared::cluster.shared::cta.mbarrier::complete_tx::bytes [%0], [%1], %2, [%3];"::"r"(dst_cluster),"r"(src),"r"(bytes),"r"(bar_cluster):"memory"); }
__device__ __forceinline__ void bulk_g2s_mc(uint32_t dst, const void* src, uint32_t bytes, uint32_t bar, uint64_t pol){
  asm volatile("cp.async.bulk.shared::cluster.global.mbarrier::complete_tx::bytes.multicast::cluster.L2::cache_hint [%0], [%1], %2, [%3], %4, %5;"::"r"(dst),"l"(src),"r"(bytes),"r"(bar),"h"((uint16_t)3),"l"(pol):"memory"); }
__device__ __forceinline__ void prefetch_map(const CUtensorMap* m){ asm volatile("prefetch.tensormap [%0];"::"l"(m):"memory"); }
__device__ __forceinline__ void fence_async_smem(){ asm volatile("fence.proxy.async.shared::cta;":::"memory"); }
__device__ __forceinline__ void fence_acquire_gpu(){ asm volatile("fence.acquire.gpu;":::"memory"); }
__device__ __forceinline__ void fence_gpu(){ asm volatile("fence.acq_rel.gpu;":::"memory"); }
__device__ __forceinline__ void wg_fence(){ asm volatile("wgmma.fence.sync.aligned;":::"memory"); }
__device__ __forceinline__ void wg_commit(){ asm volatile("wgmma.commit_group.sync.aligned;":::"memory"); }
template<int N> __device__ __forceinline__ void wg_wait(){ asm volatile("wgmma.wait_group.sync.aligned %0;"::"n"(N):"memory"); }
template<int N> __device__ __forceinline__ void fence_regs(float (&d)[N]){
  #pragma unroll
  for(int i=0;i<N;i++) asm volatile("":"+f"(d[i])::"memory"); }
__device__ __forceinline__ void bar_sync(int id, int n){ asm volatile("bar.sync %0, %1;"::"r"(id),"r"(n):"memory"); }
__device__ __forceinline__ void bar_arrive(int id, int n){ asm volatile("bar.arrive %0, %1;"::"r"(id),"r"(n):"memory"); }
__device__ __forceinline__ void cluster_arrive(){ asm volatile("barrier.cluster.arrive.relaxed.aligned;":::"memory"); }
__device__ __forceinline__ void cluster_wait(){ asm volatile("barrier.cluster.wait.aligned;":::"memory"); }
__host__ __device__ constexpr uint32_t dlo(uint32_t addr, uint32_t lbo){ return (addr >> 4) | ((lbo >> 4) << 16); }
__host__ __device__ constexpr uint32_t dhi(uint32_t sbo, uint32_t sw){ return (sbo >> 4) | (sw << 30); }
constexpr uint32_t H128 = dhi(1024, 1), H64 = dhi(512, 2), H0 = dhi(128, 0);
__device__ __forceinline__ uint32_t pack_bf16(float lo, float hi){ uint32_t r; asm("cvt.rn.bf16x2.f32 %0, %1, %2;":"=r"(r):"f"(hi),"f"(lo)); return r; }
__device__ __forceinline__ float bf_lo(uint32_t v){ return __uint_as_float(v<<16); }
__device__ __forceinline__ float bf_hi(uint32_t v){ return __uint_as_float(v&0xffff0000u); }
__device__ __forceinline__ float ex2(float x){ float r; asm("ex2.approx.ftz.f32 %0, %1;":"=f"(r):"f"(x)); return r; }
__device__ __forceinline__ float rcp(float x){ float r; asm("rcp.approx.ftz.f32 %0, %1;":"=f"(r):"f"(x)); return r; }
__device__ __forceinline__ void stsm4(uint32_t addr, uint32_t a, uint32_t b, uint32_t c, uint32_t d){
  asm volatile("stmatrix.sync.aligned.m8n8.x4.shared.b16 [%0], {%1,%2,%3,%4};"::"r"(addr),"r"(a),"r"(b),"r"(c),"r"(d)); }
__device__ __forceinline__ void stsm2(uint32_t addr, uint32_t a, uint32_t b){
  asm volatile("stmatrix.sync.aligned.m8n8.x2.shared.b16 [%0], {%1,%2};"::"r"(addr),"r"(a),"r"(b)); }
__device__ __forceinline__ void mma16816(float& d0, float& d1, float& d2, float& d3, uint32_t a0, uint32_t a1, uint32_t a2, uint32_t a3, uint32_t b0, uint32_t b1){
  asm volatile("mma.sync.aligned.m16n8k16.row.col.f32.bf16.bf16.f32 {%0,%1,%2,%3}, {%4,%5,%6,%7}, {%8,%9}, {%0,%1,%2,%3};"
               : "+f"(d0), "+f"(d1), "+f"(d2), "+f"(d3) : "r"(a0), "r"(a1), "r"(a2), "r"(a3), "r"(b0), "r"(b1)); }
__device__ __forceinline__ void ldsm4(uint32_t addr, uint32_t& a, uint32_t& b, uint32_t& c, uint32_t& d){
  asm volatile("ldmatrix.sync.aligned.m8n8.x4.shared.b16 {%0,%1,%2,%3}, [%4];":"=r"(a),"=r"(b),"=r"(c),"=r"(d):"r"(addr):"memory"); }
__device__ __forceinline__ void ldsm4t(uint32_t addr, uint32_t& a, uint32_t& b, uint32_t& c, uint32_t& d){
  asm volatile("ldmatrix.sync.aligned.m8n8.x4.trans.shared.b16 {%0,%1,%2,%3}, [%4];":"=r"(a),"=r"(b),"=r"(c),"=r"(d):"r"(addr):"memory"); }
__device__ __forceinline__ void sts32(uint32_t a, uint32_t v){ asm volatile("st.shared.b32 [%0], %1;"::"r"(a),"r"(v):"memory"); }
__device__ __forceinline__ void stsf(uint32_t a, float v){ asm volatile("st.shared.f32 [%0], %1;"::"r"(a),"f"(v):"memory"); }
__device__ __forceinline__ void sts64(uint32_t a, uint32_t x, uint32_t y){ asm volatile("st.shared.v2.b32 [%0], {%1,%2};"::"r"(a),"r"(x),"r"(y):"memory"); }
__device__ __forceinline__ void sts128(uint32_t a, uint32_t x, uint32_t y, uint32_t z, uint32_t w){ asm volatile("st.shared.v4.b32 [%0], {%1,%2,%3,%4};"::"r"(a),"r"(x),"r"(y),"r"(z),"r"(w):"memory"); }
__device__ __forceinline__ float ldsf(uint32_t a){ float v; asm volatile("ld.shared.f32 %0, [%1];":"=f"(v):"r"(a):"memory"); return v; }
__device__ __forceinline__ float2 lds64f(uint32_t a){ float2 v; asm volatile("ld.shared.v2.f32 {%0,%1}, [%2];":"=f"(v.x),"=f"(v.y):"r"(a):"memory"); return v; }
__device__ __forceinline__ uint4 lds128(uint32_t a){ uint4 v; asm volatile("ld.shared.v4.u32 {%0,%1,%2,%3}, [%4];":"=r"(v.x),"=r"(v.y),"=r"(v.z),"=r"(v.w):"r"(a):"memory"); return v; }
__device__ __forceinline__ uint4 ld128_keep(const void* p){ uint4 v; asm volatile("ld.global.v4.u32 {%0,%1,%2,%3}, [%4];":"=r"(v.x),"=r"(v.y),"=r"(v.z),"=r"(v.w):"l"(p):"memory"); return v; }
__device__ __forceinline__ uint4 ld128_rlx(const void* p){ uint4 v; asm volatile("ld.relaxed.gpu.global.v4.u32 {%0,%1,%2,%3}, [%4];":"=r"(v.x),"=r"(v.y),"=r"(v.z),"=r"(v.w):"l"(p):"memory"); return v; }
__device__ __forceinline__ uint32_t ld32_rlx(const void* p){ uint32_t v; asm volatile("ld.relaxed.gpu.global.u32 %0, [%1];":"=r"(v):"l"(p):"memory"); return v; }
__device__ __forceinline__ void st128_rlx(void* p, uint32_t x, uint32_t y, uint32_t z, uint32_t w){ asm volatile("st.relaxed.gpu.global.v4.u32 [%0], {%1,%2,%3,%4};"::"l"(p),"r"(x),"r"(y),"r"(z),"r"(w):"memory"); }
__device__ __forceinline__ void st64_rlx(void* p, uint32_t x, uint32_t y){ asm volatile("st.relaxed.gpu.global.v2.u32 [%0], {%1,%2};"::"l"(p),"r"(x),"r"(y):"memory"); }
__device__ __forceinline__ void st32_rlx(void* p, uint32_t x){ asm volatile("st.relaxed.gpu.global.u32 [%0], %1;"::"l"(p),"r"(x):"memory"); }
__device__ __forceinline__ uint32_t tagw(float x, uint32_t t){ return (__float_as_uint(x) & ~3u) | t; }
__device__ __forceinline__ float untag(uint32_t w){ return __uint_as_float(w & ~3u); }

template<int TA, int TB, uint32_t HA, uint32_t HB> __device__ __forceinline__ void wgmma_ss_n128(float (&d)[64], uint32_t da, uint32_t db, int scale_d){
  asm volatile("{\n.reg .pred p;\n.reg .b64 a, b;\nsetp.ne.b32 p, %70, 0;\nmov.b64 a, {%64, %68};\nmov.b64 b, {%65, %69};\n"
  "wgmma.mma_async.sync.aligned.m64n128k16.f32.bf16.bf16 {%0, %1, %2, %3, %4, %5, %6, %7, %8, %9, %10, %11, %12, %13, %14, %15, %16, %17, %18, %19, %20, %21, %22, %23, %24, %25, %26, %27, %28, %29, %30, %31, %32, %33, %34, %35, %36, %37, %38, %39, %40, %41, %42, %43, %44, %45, %46, %47, %48, %49, %50, %51, %52, %53, %54, %55, %56, %57, %58, %59, %60, %61, %62, %63}, a, b, p, 1, 1, %66, %67;\n}\n"
  : "+f"(d[0]), "+f"(d[1]), "+f"(d[2]), "+f"(d[3]), "+f"(d[4]), "+f"(d[5]), "+f"(d[6]), "+f"(d[7]), "+f"(d[8]), "+f"(d[9]), "+f"(d[10]), "+f"(d[11]), "+f"(d[12]), "+f"(d[13]), "+f"(d[14]), "+f"(d[15]), "+f"(d[16]), "+f"(d[17]), "+f"(d[18]), "+f"(d[19]), "+f"(d[20]), "+f"(d[21]), "+f"(d[22]), "+f"(d[23]), "+f"(d[24]), "+f"(d[25]), "+f"(d[26]), "+f"(d[27]), "+f"(d[28]), "+f"(d[29]), "+f"(d[30]), "+f"(d[31]), "+f"(d[32]), "+f"(d[33]), "+f"(d[34]), "+f"(d[35]), "+f"(d[36]), "+f"(d[37]), "+f"(d[38]), "+f"(d[39]), "+f"(d[40]), "+f"(d[41]), "+f"(d[42]), "+f"(d[43]), "+f"(d[44]), "+f"(d[45]), "+f"(d[46]), "+f"(d[47]), "+f"(d[48]), "+f"(d[49]), "+f"(d[50]), "+f"(d[51]), "+f"(d[52]), "+f"(d[53]), "+f"(d[54]), "+f"(d[55]), "+f"(d[56]), "+f"(d[57]), "+f"(d[58]), "+f"(d[59]), "+f"(d[60]), "+f"(d[61]), "+f"(d[62]), "+f"(d[63])
  : "r"(da), "r"(db), "n"(TA), "n"(TB), "n"(HA), "n"(HB), "r"(scale_d));
}
template<int TA, int TB, uint32_t HA, uint32_t HB> __device__ __forceinline__ void wgmma_sa_n128(float (&d)[64], uint32_t da, uint32_t db){
  asm volatile("{\n.reg .pred p;\n.reg .b64 a, b;\nsetp.ne.b32 p, 1, 0;\nmov.b64 a, {%64, %68};\nmov.b64 b, {%65, %69};\n"
  "wgmma.mma_async.sync.aligned.m64n128k16.f32.bf16.bf16 {%0, %1, %2, %3, %4, %5, %6, %7, %8, %9, %10, %11, %12, %13, %14, %15, %16, %17, %18, %19, %20, %21, %22, %23, %24, %25, %26, %27, %28, %29, %30, %31, %32, %33, %34, %35, %36, %37, %38, %39, %40, %41, %42, %43, %44, %45, %46, %47, %48, %49, %50, %51, %52, %53, %54, %55, %56, %57, %58, %59, %60, %61, %62, %63}, a, b, p, 1, 1, %66, %67;\n}\n"
  : "+f"(d[0]), "+f"(d[1]), "+f"(d[2]), "+f"(d[3]), "+f"(d[4]), "+f"(d[5]), "+f"(d[6]), "+f"(d[7]), "+f"(d[8]), "+f"(d[9]), "+f"(d[10]), "+f"(d[11]), "+f"(d[12]), "+f"(d[13]), "+f"(d[14]), "+f"(d[15]), "+f"(d[16]), "+f"(d[17]), "+f"(d[18]), "+f"(d[19]), "+f"(d[20]), "+f"(d[21]), "+f"(d[22]), "+f"(d[23]), "+f"(d[24]), "+f"(d[25]), "+f"(d[26]), "+f"(d[27]), "+f"(d[28]), "+f"(d[29]), "+f"(d[30]), "+f"(d[31]), "+f"(d[32]), "+f"(d[33]), "+f"(d[34]), "+f"(d[35]), "+f"(d[36]), "+f"(d[37]), "+f"(d[38]), "+f"(d[39]), "+f"(d[40]), "+f"(d[41]), "+f"(d[42]), "+f"(d[43]), "+f"(d[44]), "+f"(d[45]), "+f"(d[46]), "+f"(d[47]), "+f"(d[48]), "+f"(d[49]), "+f"(d[50]), "+f"(d[51]), "+f"(d[52]), "+f"(d[53]), "+f"(d[54]), "+f"(d[55]), "+f"(d[56]), "+f"(d[57]), "+f"(d[58]), "+f"(d[59]), "+f"(d[60]), "+f"(d[61]), "+f"(d[62]), "+f"(d[63])
  : "r"(da), "r"(db), "n"(TA), "n"(TB), "n"(HA), "n"(HB));
}
template<int TA, int TB, uint32_t HA, uint32_t HB> __device__ __forceinline__ void wgmma_sa_n40(float (&d)[20], uint32_t da, uint32_t db){
  asm volatile("{\n.reg .pred p;\n.reg .b64 a, b;\nsetp.ne.b32 p, 1, 0;\nmov.b64 a, {%20, %24};\nmov.b64 b, {%21, %25};\n"
  "wgmma.mma_async.sync.aligned.m64n40k16.f32.bf16.bf16 {%0, %1, %2, %3, %4, %5, %6, %7, %8, %9, %10, %11, %12, %13, %14, %15, %16, %17, %18, %19}, a, b, p, 1, 1, %22, %23;\n}\n"
  : "+f"(d[0]), "+f"(d[1]), "+f"(d[2]), "+f"(d[3]), "+f"(d[4]), "+f"(d[5]), "+f"(d[6]), "+f"(d[7]), "+f"(d[8]), "+f"(d[9]), "+f"(d[10]), "+f"(d[11]), "+f"(d[12]), "+f"(d[13]), "+f"(d[14]), "+f"(d[15]), "+f"(d[16]), "+f"(d[17]), "+f"(d[18]), "+f"(d[19])
  : "r"(da), "r"(db), "n"(TA), "n"(TB), "n"(HA), "n"(HB));
}
template<int TA, int TB, uint32_t HA, uint32_t HB> __device__ __forceinline__ void wgmma_sz_n40(float (&d)[20], uint32_t da, uint32_t db){
  asm volatile("{\n.reg .pred p;\n.reg .b64 a, b;\nsetp.ne.b32 p, 0, 0;\nmov.b64 a, {%20, %24};\nmov.b64 b, {%21, %25};\n"
  "wgmma.mma_async.sync.aligned.m64n40k16.f32.bf16.bf16 {%0, %1, %2, %3, %4, %5, %6, %7, %8, %9, %10, %11, %12, %13, %14, %15, %16, %17, %18, %19}, a, b, p, 1, 1, %22, %23;\n}\n"
  : "=f"(d[0]), "=f"(d[1]), "=f"(d[2]), "=f"(d[3]), "=f"(d[4]), "=f"(d[5]), "=f"(d[6]), "=f"(d[7]), "=f"(d[8]), "=f"(d[9]), "=f"(d[10]), "=f"(d[11]), "=f"(d[12]), "=f"(d[13]), "=f"(d[14]), "=f"(d[15]), "=f"(d[16]), "=f"(d[17]), "=f"(d[18]), "=f"(d[19])
  : "r"(da), "r"(db), "n"(TA), "n"(TB), "n"(HA), "n"(HB));
}
template<int TA, int TB, uint32_t HA, uint32_t HB> __device__ __forceinline__ void wgmma_sa_n32(float (&d)[16], uint32_t da, uint32_t db){
  asm volatile("{\n.reg .pred p;\n.reg .b64 a, b;\nsetp.ne.b32 p, 1, 0;\nmov.b64 a, {%16, %20};\nmov.b64 b, {%17, %21};\n"
  "wgmma.mma_async.sync.aligned.m64n32k16.f32.bf16.bf16 {%0, %1, %2, %3, %4, %5, %6, %7, %8, %9, %10, %11, %12, %13, %14, %15}, a, b, p, 1, 1, %18, %19;\n}\n"
  : "+f"(d[0]), "+f"(d[1]), "+f"(d[2]), "+f"(d[3]), "+f"(d[4]), "+f"(d[5]), "+f"(d[6]), "+f"(d[7]), "+f"(d[8]), "+f"(d[9]), "+f"(d[10]), "+f"(d[11]), "+f"(d[12]), "+f"(d[13]), "+f"(d[14]), "+f"(d[15])
  : "r"(da), "r"(db), "n"(TA), "n"(TB), "n"(HA), "n"(HB));
}
template<int TA, int TB, uint32_t HA, uint32_t HB> __device__ __forceinline__ void wgmma_ss_n32(float (&d)[16], uint32_t da, uint32_t db, int scale_d){
  asm volatile("{\n.reg .pred p;\n.reg .b64 a, b;\nsetp.ne.b32 p, %22, 0;\nmov.b64 a, {%16, %20};\nmov.b64 b, {%17, %21};\n"
  "wgmma.mma_async.sync.aligned.m64n32k16.f32.bf16.bf16 {%0, %1, %2, %3, %4, %5, %6, %7, %8, %9, %10, %11, %12, %13, %14, %15}, a, b, p, 1, 1, %18, %19;\n}\n"
  : "+f"(d[0]), "+f"(d[1]), "+f"(d[2]), "+f"(d[3]), "+f"(d[4]), "+f"(d[5]), "+f"(d[6]), "+f"(d[7]), "+f"(d[8]), "+f"(d[9]), "+f"(d[10]), "+f"(d[11]), "+f"(d[12]), "+f"(d[13]), "+f"(d[14]), "+f"(d[15])
  : "r"(da), "r"(db), "n"(TA), "n"(TB), "n"(HA), "n"(HB), "r"(scale_d));
}
template<int TB, uint32_t HB> __device__ __forceinline__ void wgmma_ra_n32(float (&d)[16], uint32_t a0, uint32_t a1, uint32_t a2, uint32_t a3, uint32_t db){
  asm volatile("{\n.reg .pred p;\n.reg .b64 a, b;\nsetp.ne.b32 p, 1, 0;\nmov.b64 b, {%20, %22};\n"
  "wgmma.mma_async.sync.aligned.m64n32k16.f32.bf16.bf16 {%0, %1, %2, %3, %4, %5, %6, %7, %8, %9, %10, %11, %12, %13, %14, %15}, {%16,%17,%18,%19}, b, p, 1, 1, %21;\n}\n"
  : "+f"(d[0]), "+f"(d[1]), "+f"(d[2]), "+f"(d[3]), "+f"(d[4]), "+f"(d[5]), "+f"(d[6]), "+f"(d[7]), "+f"(d[8]), "+f"(d[9]), "+f"(d[10]), "+f"(d[11]), "+f"(d[12]), "+f"(d[13]), "+f"(d[14]), "+f"(d[15])
  : "r"(a0), "r"(a1), "r"(a2), "r"(a3), "r"(db), "n"(TB), "n"(HB));
}
template<int TB, uint32_t HB> __device__ __forceinline__ void wgmma_rs_n32(float (&d)[16], uint32_t a0, uint32_t a1, uint32_t a2, uint32_t a3, uint32_t db, int scale_d){
  asm volatile("{\n.reg .pred p;\n.reg .b64 a, b;\nsetp.ne.b32 p, %23, 0;\nmov.b64 b, {%20, %22};\n"
  "wgmma.mma_async.sync.aligned.m64n32k16.f32.bf16.bf16 {%0, %1, %2, %3, %4, %5, %6, %7, %8, %9, %10, %11, %12, %13, %14, %15}, {%16,%17,%18,%19}, b, p, 1, 1, %21;\n}\n"
  : "+f"(d[0]), "+f"(d[1]), "+f"(d[2]), "+f"(d[3]), "+f"(d[4]), "+f"(d[5]), "+f"(d[6]), "+f"(d[7]), "+f"(d[8]), "+f"(d[9]), "+f"(d[10]), "+f"(d[11]), "+f"(d[12]), "+f"(d[13]), "+f"(d[14]), "+f"(d[15])
  : "r"(a0), "r"(a1), "r"(a2), "r"(a3), "r"(db), "n"(TB), "n"(HB), "r"(scale_d));
}
template<int TB, uint32_t HB> __device__ __forceinline__ void wgmma_ra_n40(float (&d)[20], uint32_t a0, uint32_t a1, uint32_t a2, uint32_t a3, uint32_t db){
  asm volatile("{\n.reg .pred p;\n.reg .b64 a, b;\nsetp.ne.b32 p, 1, 0;\nmov.b64 b, {%24, %26};\n"
  "wgmma.mma_async.sync.aligned.m64n40k16.f32.bf16.bf16 {%0, %1, %2, %3, %4, %5, %6, %7, %8, %9, %10, %11, %12, %13, %14, %15, %16, %17, %18, %19}, {%20,%21,%22,%23}, b, p, 1, 1, %25;\n}\n"
  : "+f"(d[0]), "+f"(d[1]), "+f"(d[2]), "+f"(d[3]), "+f"(d[4]), "+f"(d[5]), "+f"(d[6]), "+f"(d[7]), "+f"(d[8]), "+f"(d[9]), "+f"(d[10]), "+f"(d[11]), "+f"(d[12]), "+f"(d[13]), "+f"(d[14]), "+f"(d[15]), "+f"(d[16]), "+f"(d[17]), "+f"(d[18]), "+f"(d[19])
  : "r"(a0), "r"(a1), "r"(a2), "r"(a3), "r"(db), "n"(TB), "n"(HB));
}
template<int TB, uint32_t HB> __device__ __forceinline__ void wgmma_rz_n40(float (&d)[20], uint32_t a0, uint32_t a1, uint32_t a2, uint32_t a3, uint32_t db){
  asm volatile("{\n.reg .pred p;\n.reg .b64 a, b;\nsetp.ne.b32 p, 0, 0;\nmov.b64 b, {%24, %26};\n"
  "wgmma.mma_async.sync.aligned.m64n40k16.f32.bf16.bf16 {%0, %1, %2, %3, %4, %5, %6, %7, %8, %9, %10, %11, %12, %13, %14, %15, %16, %17, %18, %19}, {%20,%21,%22,%23}, b, p, 1, 1, %25;\n}\n"
  : "=f"(d[0]), "=f"(d[1]), "=f"(d[2]), "=f"(d[3]), "=f"(d[4]), "=f"(d[5]), "=f"(d[6]), "=f"(d[7]), "=f"(d[8]), "=f"(d[9]), "=f"(d[10]), "=f"(d[11]), "=f"(d[12]), "=f"(d[13]), "=f"(d[14]), "=f"(d[15]), "=f"(d[16]), "=f"(d[17]), "=f"(d[18]), "=f"(d[19])
  : "r"(a0), "r"(a1), "r"(a2), "r"(a3), "r"(db), "n"(TB), "n"(HB));
}
template<int TB, uint32_t HB> __device__ __forceinline__ void wgmma_ra_n8(float (&d)[4], uint32_t a0, uint32_t a1, uint32_t a2, uint32_t a3, uint32_t db){
  asm volatile("{\n.reg .pred p;\n.reg .b64 a, b;\nsetp.ne.b32 p, 1, 0;\nmov.b64 b, {%8, %10};\n"
  "wgmma.mma_async.sync.aligned.m64n8k16.f32.bf16.bf16 {%0, %1, %2, %3}, {%4,%5,%6,%7}, b, p, 1, 1, %9;\n}\n"
  : "+f"(d[0]), "+f"(d[1]), "+f"(d[2]), "+f"(d[3])
  : "r"(a0), "r"(a1), "r"(a2), "r"(a3), "r"(db), "n"(TB), "n"(HB));
}
template<int TB, uint32_t HB> __device__ __forceinline__ void wgmma_rz_n8(float (&d)[4], uint32_t a0, uint32_t a1, uint32_t a2, uint32_t a3, uint32_t db){
  asm volatile("{\n.reg .pred p;\n.reg .b64 a, b;\nsetp.ne.b32 p, 0, 0;\nmov.b64 b, {%8, %10};\n"
  "wgmma.mma_async.sync.aligned.m64n8k16.f32.bf16.bf16 {%0, %1, %2, %3}, {%4,%5,%6,%7}, b, p, 1, 1, %9;\n}\n"
  : "=f"(d[0]), "=f"(d[1]), "=f"(d[2]), "=f"(d[3])
  : "r"(a0), "r"(a1), "r"(a2), "r"(a3), "r"(db), "n"(TB), "n"(HB));
}

constexpr int SEQ = 2048, DM = 1024, FF = 3584;
constexpr float LOG2E = 1.4426950408889634f;
constexpr uint32_t POLL_LIMIT = 1u << 22;
constexpr int NPRE = 2;
#define QW 14
#define RS_N 24
#define RS_D1 430
#define RS_D2 300
#define SKM 0x252
#define LAG 1
#define PF_T0 4000
#define PF_DT 900
#define Q0L 2
#define NFFN_L NFFN
#define FF_DT 350
#define OUT_U 1
#define GRES 8
#define OUT_L 0
#define TMASK 0xffffff
#define PMASK 0xffffff
#define FF_T0 2200
#define GPRE 0
#define REL 0x882
#define EFI 11
#define G2UN 16
#define TKW 8
#define SLOT 0
#define SLOTW 48
#define OUT_NS 0
constexpr int G2U = G2UN;
constexpr int NFFN = 112;

constexpr uint32_t SB0 = 1024;
constexpr uint32_t KV_STAGE = 49152, R5 = 32768;
constexpr uint32_t OFF_X = 163840, OFF_S = 196608, OFF_WPHI = OFF_S + 20480, OFF_M = 229376, SMEM_BYTES = 232448;
constexpr uint32_t OFF_RS256 = 212992, OFF_ONES = OFF_RS256 + 1024, OFF_WPHIK1 = OFF_ONES + 1024, OFF_KVZ = OFF_S;
constexpr uint32_t OFF_WPHIK = OFF_S, OFF_BXK = OFF_S + 2048, OFF_AXK = OFF_S + 4096;
constexpr uint32_t OFF_AXQ = OFF_WPHI, OFF_BXQ = OFF_WPHI + 2048, OFF_WPHIQ = OFF_WPHI + 4096;
constexpr uint32_t B_FULLKV = OFF_M, B_EMPTYKV = OFF_M + 32, B_FULL5 = OFF_M + 64, B_EMPTY5 = OFF_M + 104;
constexpr uint32_t B_W = OFF_M + 144, B_OS = OFF_M + 152, B_R = OFF_M + 160, B_AUX = OFF_M + 168, B_AUXQ = OFF_M + 176, B_KD = OFF_M + 184, B_RC = OFF_M + 192  ;
constexpr uint32_t B_FULLA = OFF_M + 768, B_QL = B_FULLA + 80, B_UO = B_FULLA + 96  ;
constexpr uint32_t OFF_SUMWR = OFF_M + 896, OFF_EP = OFF_M + 208, OFF_KEY = OFF_M + 216, OFF_EXC = OFF_M + 224;
constexpr uint32_t OFF_RSQ = OFF_M + 256, OFF_WR = OFF_M + 2048, OFF_XSEL = 4 * R5;
constexpr uint32_t OFF_ACT = OFF_XSEL + 2048, OFF_GU = OFF_XSEL + 4096, OFF_SCR = OFF_M + 2432, B_F = OFF_M + 1536  , B_WD = B_F + 64  , B_WC = B_F + 96  , B_DR = B_F + 128  , B_RX = B_F + 144, B_XS = B_F + 152, B_T = B_F + 160, B_OUT = B_F + 168  , OFF_T = OFF_M + 1792;
constexpr int KVP = 6 * 128;

enum { NB_G2E = 1, NB_XS = 2, NB_WG01 = 3, NB_ACT = 4, NB_Q0 = 5  , NB_ST = 14, NB_DN = 9, NB_ZERO = 10, NB_PUB = 11, NB_TOK = 10  , NB_L0 = 12  , NB_WG2 = 7, NB_QGO = 15 };

struct Scratch {
  bf16     o[SEQ * DM];
  float4   rstat[SEQ];
  uint32_t key[32 * 128];
  uint32_t cand[128 * DM];
  uint32_t ypart[NFFN * DM];
  float4   kvacc[32 * KVP];
  uint2    stats[SEQ];
  uint32_t cskv[2 * DM];
  uint32_t csq[4 * DM];
  uint32_t oset[16 * 32];
  uint32_t epoch;
};
__device__ __align__(1024) Scratch g_scr;
#define TS(id)
#define TDUMP()
#define TS0_DECL()
#define TS0_READ()
#define TS0_WRITE()
#define TK(id)
#define TSW(id)

struct Params {
  CUtensorMap x128, x64, wkv, wq, wo[2], wd, wg, wu, phi, tg, tu, td;
  const bf16 *x, *wqkv, *wo_p, *wg_p, *wu_p, *wd_p, *wr;
  bf16* out_p;
  Scratch* g;
};

constexpr float EXP_LIM = 1.1529215e18f, ARG_LIM2 = 3600.f;
__device__ __forceinline__ void dual_exp2(const float (&p)[2][16], uint32_t (&ph)[4][8]) {
  #pragma unroll
  for (int h = 0; h < 2; h++)
    #pragma unroll
    for (int k = 0; k < 8; k++) { ph[2*h][k] = pack_bf16(ex2(p[h][2*k]), ex2(p[h][2*k+1])); ph[2*h+1][k] = pack_bf16(ex2(-p[h][2*k]), ex2(-p[h][2*k+1])); }
}
__device__ __forceinline__ void row_extremes(const float (&p)[16], const float (&c)[2], float (&m)[4]) {
  m[0] = m[2] = p[0]; m[1] = m[3] = p[2];
  #pragma unroll
  for (int i = 0; i < 16; i++) { m[(i >> 1) & 1] = fmaxf(m[(i >> 1) & 1], p[i]); m[2 + ((i >> 1) & 1)] = fminf(m[2 + ((i >> 1) & 1)], p[i]); }
  #pragma unroll
  for (int o = 1; o < 4; o <<= 1) {
    m[0] = fmaxf(m[0], __shfl_xor_sync(~0u, m[0], o)); m[1] = fmaxf(m[1], __shfl_xor_sync(~0u, m[1], o));
    m[2] = fminf(m[2], __shfl_xor_sync(~0u, m[2], o)); m[3] = fminf(m[3], __shfl_xor_sync(~0u, m[3], o));
  }
  m[0] *= -c[0]; m[1] *= -c[1]; m[2] *= c[0]; m[3] *= c[1];
}
__device__ __forceinline__ void dual_exp2_shifted(const float (&p)[2][16], uint32_t (&ph)[4][8]) {
  #pragma unroll
  for (int h = 0; h < 2; h++) {
    const float one[2] = {1.f, 1.f};
    float m[4];
    row_extremes(p[h], one, m);
    #pragma unroll
    for (int k = 0; k < 8; k++) {
      ph[2*h][k] = pack_bf16(ex2(p[h][2*k] + m[k & 1]), ex2(p[h][2*k+1] + m[k & 1]));
      ph[2*h+1][k] = pack_bf16(ex2(m[2 + (k & 1)] - p[h][2*k]), ex2(m[2 + (k & 1)] - p[h][2*k+1]));
    }
  }
}
__device__ __forceinline__ void row_sums(float (&s)[4][4], const uint32_t (&ph)[4][8], uint32_t ones) {
  #pragma unroll
  for (int i = 0; i < 4; i++) wgmma_rz_n8<0, H0>(s[i], ph[i][0], ph[i][1], ph[i][2], ph[i][3], ones);
  #pragma unroll
  for (int i = 0; i < 4; i++) wgmma_ra_n8<0, H0>(s[i], ph[i][4], ph[i][5], ph[i][6], ph[i][7], ones);
}
__device__ __forceinline__ uint32_t mul_bf16x2(uint32_t a, uint32_t b) { uint32_t r; asm("mul.rn.bf16x2 %0, %1, %2;" : "=r"(r) : "r"(a), "r"(b)); return r; }
__device__ __forceinline__ void normalize(uint32_t (&ph)[4][8], const float (&s)[4][4]) {
  #pragma unroll
  for (int i = 0; i < 4; i++) {
    const float i0 = rcp(s[i][0]), i1 = rcp(s[i][2]);
    const uint32_t n0 = pack_bf16(i0, i0), n1 = pack_bf16(i1, i1);
    #pragma unroll
    for (int k = 0; k < 4; k++) { ph[i][2*k] = mul_bf16x2(ph[i][2*k], n0); ph[i][2*k+1] = mul_bf16x2(ph[i][2*k+1], n1); }
  }
}
__device__ __forceinline__ void split_bf16(float a, float b, uint32_t& hi, uint32_t& lo) { hi = pack_bf16(a, b); lo = pack_bf16(a - bf_lo(hi), b - bf_hi(hi)); }
__device__ __forceinline__ void put_colsums(uint32_t base, int lane, float a, float b, float c, float d) {
  uint32_t h0, l0, h1, l1;
  split_bf16(a, b, h0, l0); split_bf16(c, d, h1, l1);
  const uint32_t ad = base + (lane >> 1) * 128 + (lane & 1) * 8;
  sts64(ad, h0, h1); sts64(ad + 16, l0, l1); sts64(ad + 32, h0, h1); sts64(ad + 48, l0, l1);
  sts128(base + (lane >> 1) * 128 + 64 + (lane & 1) * 32, 0, 0, 0, 0); sts128(base + (lane >> 1) * 128 + 80 + (lane & 1) * 32, 0, 0, 0, 0);
}
__device__ __forceinline__ float reduce8(const float (&v)[8], int lane) {
  const bool b4 = lane & 16, b3 = lane & 8, b2 = lane & 4;
  float a[4], b[2];
  #pragma unroll
  for (int i = 0; i < 4; i++) a[i] = (b4 ? v[4 + i] : v[i]) + __shfl_xor_sync(~0u, b4 ? v[i] : v[4 + i], 16);
  #pragma unroll
  for (int i = 0; i < 2; i++) b[i] = (b3 ? a[2 + i] : a[i]) + __shfl_xor_sync(~0u, b3 ? a[i] : a[2 + i], 8);
  return (b2 ? b[1] : b[0]) + __shfl_xor_sync(~0u, b2 ? b[0] : b[1], 4);
}
__device__ __forceinline__ bool tag_bad(uint4 v, uint32_t tg) { return (((v.x ^ tg) | (v.y ^ tg) | (v.z ^ tg) | (v.w ^ tg)) & 3) != 0; }

__device__ __forceinline__ void project_q(float (&p)[2][16], uint32_t off, int w0, int w1) {
  const uint32_t da = dlo(SB0, 16) + (off >> 4);
  wg_fence();
  #pragma unroll
  for (int h = 0; h < 2; h++) {
    const uint32_t db = dlo(SB0 + OFF_WPHIQ, 16) + (h ? w1 : w0) * 128;
    wgmma_ss_n32<0, 1, H128, H64>(p[h], da + 4 * h, db, 0);
    wgmma_sa_n32<0, 1, H128, H64>(p[h], da + 4 * h + 2, db + 64);
  }
  wg_commit();
}

__global__ void __launch_bounds__(512, 1) fused_kernel(const __grid_constant__ Params P) {
  extern __shared__ __align__(1024) uint8_t smem_raw[];
  const uint32_t sb = smem_u32(smem_raw);
  const int tid = threadIdx.x, lane = tid & 31;
  const int warp = __shfl_sync(~0u, tid >> 5, 0), wg = warp >> 2, wp = warp & 3;
  const int cp = blockIdx.x >> 1, cu = cp - 36, cd = (cu * 37) >> 8;
  const int gi = cp < 4 ? 0 : cu < 0 ? (cp - 4) & 7 : 1 + cu - 7 * cd, gx = cp < 4 ? 4 + cp : cu < 0 ? (cp - 4) >> 3 : 4 + cd;
  const int rank = blockIdx.x & 1, c = 64 * (gi & 1) + 8 * gx + (gi & 6) + rank;
  const int f = 16 * ((gi + 7) & 7) + 2 * gx + rank;
  const int m256 = c >> 4, nkv = c & 15, m128 = c >> 3, j = c & 7;
  const int ha = 4 * (nkv >> 1) + (nkv & 1);

  Scratch* const G = P.g;
  if ((sb & 0x3ffff) != SB0) asm volatile("trap;");

  TS0_DECL();
  if (warp == 12) {
    const bool el = elect_one();
    TS0_READ();
    if (el) {
      #pragma unroll
      for (int i = 0; i < 4; i++) mbar_init(sb + B_FULLKV + 8 * i, 1);
      asm volatile("fence.mbarrier_init.release.cluster;" ::: "memory");
      fence_async_smem();
      #pragma unroll
      for (int s = 0; s < NPRE; s++) {
        const uint32_t st = sb + s * KV_STAGE, fb = sb + B_FULLKV + 8 * s;
        mbar_expect_tx(fb, KV_STAGE);
        tma_4d(st + 32768, &P.wkv, 0, 64 * s, nkv, 1, fb);
        tma_2d(st, &P.x128, 64 * s, 256 * m256, fb);
        tma_2d(st + 16384, &P.x128, 64 * s, 256 * m256 + 128, fb);
      }
    }
  } else if (tid == 0) {
    #pragma unroll
    for (int i = 0; i < 22; i++) mbar_init(sb + B_EMPTYKV + 8 * i, i >= 20 ? 4 : i < 4 ? 12 : (i >= 9 && i < 14) ? 4 : i == 17 || i == 18 ? 2 : 1);
    #pragma unroll
    for (int i = 0; i < 25; i++) mbar_init(sb + B_F + 8 * i, i > 20 ? 2 : i != 18 ? 1 : 8);
    #pragma unroll
    for (int i = 0; i < 16; i++) mbar_init(sb + B_FULLA + 8 * i, i < 11 ? 1 : i == 11 ? 2 : 4);
    asm volatile("fence.mbarrier_init.release.cluster;" ::: "memory");
    fence_async_smem();
  }
  __syncthreads();
  cluster_arrive();

  if (wg == 3) {
    asm volatile("setmaxnreg.dec.sync.aligned.u32 32;");
    cluster_wait();
    const bool el = elect_one();
    const uint64_t ef = policy_evict_first(), en = policy_evict_normal();
    auto fetch_o = [&](const int t0, uint32_t so, uint32_t par) {
      const int sh = t0 & 1;
      uint32_t ready = 0;
      const bf16* base = G->o + (m128 * 16 + t0) * 8192 + rank * 4096;
      const bf16* hint = base + (lane & 3) * 1024 + 966 + (((j & 6) + ((lane >> 2) & ~sh)) & 7) * 16384 + 8 * sh * (~lane & 4);
      #pragma unroll 1
      for (int i = 2 - 2 * sh; i < 8; i += 1 + sh) {
        uint32_t it = 0;
        while ((~ready >> (4 * i) & (15 + 240 * sh)) && ++it < POLL_LIMIT) ready = __ballot_sync(~0u, ld32_rlx(hint) != ~0u);
        mbar_wait(sb + B_EMPTY5 + so, par);
        if (el) {
          bulk_g2s_mc(sb + so * 4096 + rank * 8192, base + (((j & 6) + i) & 7) * 16384, 8192, sb + B_FULLA + 2 * so + 8 * rank, ef);
          if (i == 2 - 2 * sh) TS(t0 == 0 ? (rank ? 4 : 12) : t0 == 3 ? (rank ? 31 : 10) : (rank ? 9 : 13));
        }
        so += 8;
        if (so == 40) { so = 0; par ^= 1; }
      }
    };
    if (wp == 0) {
      {
        #pragma unroll 1
        for (int kb = NPRE; kb < 16; kb++) {
          const uint32_t st = sb + (kb & 3) * KV_STAGE, fb = sb + B_FULLKV + 8 * (kb & 3);
          mbar_wait(fb + (B_EMPTYKV - B_FULLKV), ~(kb >> 2) & 1);
          if (el) {
            mbar_expect_tx(fb, KV_STAGE);
            tma_2d_mc(st + rank * 16384, &P.x128, 64 * kb, 256 * m256 + 128 * rank, fb);
            tma_4d_h(st + 32768, &P.wkv, 0, 64 * kb, nkv, 1, fb, ef);
          }
        }
        TS0_WRITE();
        uint64_t ord = 0xf3120edcba987654ull;
        uint32_t so = 0, par = 1;
        #pragma unroll 1
        for (int i = 0; i < 16; i++) {
          const uint32_t st = sb + so * 4096, fb = sb + B_FULL5 + so;
          const int k0 = (64 * (uint32_t)ord + 128 * (j & 6)) & 960;
          mbar_wait(i < 5 ? sb + B_EMPTYKV + so - (i > 1 ? 8 : 0) : fb + (B_EMPTY5 - B_FULL5), par);
          if (el) {
            mbar_expect_tx(fb, R5);
            tma_2d_mc_h(st + rank * 8192, &P.x64, k0, 128 * m128 + 64 * rank, fb, i >= EFI ? ef : en);
            tma_3d_h(st + 16384, &P.wq, 0, k0, 2 * j, fb, ef);
          }
          ord >>= 4; so += 8;
          if (so == 40) { so = 0; par ^= 1; }
        }
        #pragma unroll 1
        for (int i = 0; i < 16; i++) {
          const uint32_t fb = sb + B_FULL5 + so, fa = sb + B_FULLA + 2 * so, na = i == rank ? 0 : 8192;
          if (i == 1) { if (el) mbar_arrive(sb + B_QL); mbar_wait2(sb + B_FULL5 + 16, 0, sb + B_FULL5 + 24, 0); mbar_wait(sb + B_FULL5 + 32, 0); if (el) mbar_arrive(sb + B_R); }
          mbar_wait(fb + (B_EMPTY5 - B_FULL5), par);
          if (SLOT) { while (((uint32_t)clock() & (uint32_t)(SLOT - 1)) >= SLOTW) {} }
          if (el) {
            mbar_expect_tx(fb, 16384);
            const int row = i < 8 ? 128 * (((j & 6) + i) & 7) : 256 * (((j >> 1) + i) & 3) + 32 + 16 * (i & 4);
            tma_5d_h(sb + so * 4096 + 16384, &P.wo[i >> 3], 128 * j, row, fb, ef);
            tma_5d_h(sb + so * 4096 + 24576, &P.wo[i >> 3], 128 * j + 64, row, fb, ef);
            mbar_expect_tx(fa, na); mbar_expect_tx(fa + 8, na);
          }
          so += 8;
          if (so == 40) { so = 0; par ^= 1; }
        }
        mbar_wait(sb + B_EMPTY5 + 16, 1); if (el) mbar_arrive(sb + B_DR);
        mbar_wait(sb + B_EMPTY5 + 24, 1); if (el) mbar_arrive(sb + B_DR + 8);
      }
    } else if (wp == 3) {
      const uint32_t t_start = (uint32_t)clock();
      if (el) {
        mbar_expect_tx(sb + B_W, 12288);
        #pragma unroll 1
        for (int i = 0; i < 6; i++) tma_2d(sb + (i == 0 ? OFF_WPHIK : i == 1 ? OFF_WPHIK1 : OFF_WPHIQ + 2048 * (i - 2)), &P.phi, 0, 32 * (i < 2 ? 2 * nkv + i : 4 * j + 2 * (i & 1) + ((i - 2) >> 1)), sb + B_W);
        prefetch_map(&P.x64); prefetch_map(&P.wq); prefetch_map(&P.wo[0]); prefetch_map(&P.wo[1]);
        prefetch_map(&P.wd); prefetch_map(&P.wg); prefetch_map(&P.wu);
      }
      #pragma unroll 1
      for (int i = 0; i < 8; i++) {
        st128_rlx(&G->cand[(m128 * 8 + i) * DM + (lane >> 4) * 512 + 64 * j + 4 * (lane & 15)], ~0u, ~0u, ~0u, ~0u);
        if (f < NFFN) st128_rlx(&G->ypart[f * DM + 128 * i + 4 * lane], ~0u, ~0u, ~0u, ~0u);
      }
      if (lane < 16) st128_rlx(&G->rstat[16 * c + lane], 0, 0, 0, 0);
      if (lane < 8) st128_rlx(&G->key[(4 * j + (lane >> 1)) * 128 + m128 * 8 + 4 * (lane & 1)], 0, 0, 0, 0);
      if (c < 32) {
        #pragma unroll 1
        for (int i = lane; i < KVP; i += 32) st128_rlx(&G->kvacc[(ha + 2 * m256) * KVP + i], 0, 0, 0, 0);
      }
      fence_gpu();
      bar_arrive(NB_ZERO, 160);
      if (el) {
        #pragma unroll 1
        for (int i = 0; i < 30; i++) {
          while ((uint32_t)clock() - t_start < (uint32_t)(PF_T0 + PF_DT * i)) __nanosleep(64);
          if (i < 4) { bulk_prefetch(P.wqkv + (size_t)(256 * i + c) * (3 * DM), 2048); bulk_prefetch(P.wqkv + (size_t)(256 * i + 128 + c) * (3 * DM), 2048); }
          else if (i < 6) bulk_prefetch(P.wo_p + (size_t)c * 8192 + (i - 4) * 4096, 8192);
          else if ((TMASK >> (i - 6)) & 1) {
            const int k = i - 6;
            if (f < NFFN) {
              if (k < 16) {
                #pragma unroll 1
                for (int e = 0; e < 4; e++) tma_2d(sb + OFF_T, rank ? &P.tu : &P.tg, 32 * (f & ~1), 64 * k + 16 * e, sb + B_T);
              } else { tma_2d(sb + OFF_T, &P.td, 0, 256 * f + 32 * (k - 16), sb + B_T); tma_2d(sb + OFF_T, &P.td, 0, 256 * f + 32 * (k - 16) + 16, sb + B_T); }
            }
          }
          else if (!((PMASK >> (i - 6)) & 1)) {}
          else if (i < 22) bulk_prefetch(((i & 1) ? P.wu_p : P.wg_p) + (size_t)((i - 6) >> 1) * 458752 + c * 3584, 7168);
          else bulk_prefetch(P.wd_p + (size_t)(i - 22) * 458752 + c * 3584, 7168);
        }
      }
      __syncwarp();
      mbar_wait2(sb + B_OS, 0, sb + B_RX, 0);
      #pragma unroll 1
      for (int t0 = 0; t0 < 4; t0 += 3) fetch_o(t0, 24, 0);
    } else {
      const int half = wp - 1;
      const uint32_t ep1 = ld32_rlx(&G->epoch) + 1, tg = ep1 & 3;
      {
        uint32_t it = 0;
        sts128(sb + OFF_ONES + half * 512 + lane * 16, 0x3f803f80u, 0x3f803f80u, 0x3f803f80u, 0x3f803f80u);
        auto reset_o = [&](int i0, int i1, uint32_t dt) {
          uint32_t t0 = (uint32_t)clock();
          #pragma unroll 1
          for (int i = i0; i < i1; i++) {
            st128_rlx(G->o + (m128 * 16 + 2 * j + half) * 8192 + 256 * i + 8 * lane, ~0u, ~0u, ~0u, ~0u);
            while ((uint32_t)clock() - t0 < dt) __nanosleep(40);
            t0 += dt;
          }
        };
        mbar_wait(sb + B_W, 0);
        reset_o(0, RS_N, RS_D1);
        bar_sync(NB_PUB, 192);
        const uint4* src = reinterpret_cast<const uint4*>(&G->stats[256 * m256 + 128 * half]) + lane;
        const uint4* srk = reinterpret_cast<const uint4*>(&G->cskv[128 * nkv]) + lane;
        uint4 v0, v1, vk;
        it = 0;
        do { v0 = ld128_rlx(src); v1 = ld128_rlx(src + 32); vk = ld128_rlx(srk); }
        while ((tag_bad(v0, tg) || tag_bad(v1, tg) || tag_bad(vk, tg)) && ++it < POLL_LIMIT);
        fence_acquire_gpu();
        if (half) put_colsums(sb + OFF_BXK, lane, untag(vk.x), untag(vk.y), untag(vk.z), untag(vk.w));
        #pragma unroll
        for (int i = 0; i < 2; i++) {
          const uint4 v = i ? v1 : v0;
          uint32_t hi, lo;
          split_bf16(-0.5f * untag(v.x), -0.5f * untag(v.z), hi, lo);
          const uint32_t h0 = __byte_perm(hi, hi, 0x1010), h1 = __byte_perm(hi, hi, 0x3232), l0 = __byte_perm(lo, lo, 0x1010), l1 = __byte_perm(lo, lo, 0x3232);
          const uint32_t a = sb + OFF_AXK + half * 2048 + i * 1024 + lane * 32;
          sts128(a, h0, l0, 0, 0); sts128(a + 16, h1, l1, 0, 0);
          sts64(sb + OFF_RS256 + half * 512 + i * 256 + lane * 8, v.y & ~3u, v.w & ~3u);
          if (half == (m128 & 1)) {
            const uint32_t aq = sb + OFF_AXQ + i * 1024 + lane * 32;
            sts128(aq, h0, l0, 0, 0); sts128(aq + 16, h1, l1, 0, 0);
            sts64(sb + OFF_RSQ + i * 256 + lane * 8, v.y & ~3u, v.w & ~3u);
          }
        }
        fence_async_smem();
        __syncwarp();
        if (el) { sts32(sb + OFF_EP, ep1); mbar_arrive(sb + B_AUX); if (!half) TS(1); }
        reset_o(RS_N, 32, RS_D2);
        fence_gpu();
        __syncwarp();
        if (el) { st32_rlx(&G->oset[m128 * 32 + 2 * j + half], ep1); if (half) mbar_arrive(sb + B_AUXQ); }
        if (!half) {
          const uint4* src = reinterpret_cast<const uint4*>(&G->csq[128 * j]) + lane;
          uint4 v0, v1, v2, v3;
          do { v0 = ld128_rlx(src); v1 = ld128_rlx(src + DM / 4); v2 = ld128_rlx(src + DM / 2); v3 = ld128_rlx(src + 3 * DM / 4); }
          while ((tag_bad(v0, tg) || tag_bad(v1, tg) || tag_bad(v2, tg) || tag_bad(v3, tg)) && ++it < POLL_LIMIT);
          put_colsums(sb + OFF_BXQ, lane, (untag(v0.x) + untag(v1.x)) + (untag(v2.x) + untag(v3.x)), (untag(v0.y) + untag(v1.y)) + (untag(v2.y) + untag(v3.y)),
                      (untag(v0.z) + untag(v1.z)) + (untag(v2.z) + untag(v3.z)), (untag(v0.w) + untag(v1.w)) + (untag(v2.w) + untag(v3.w)));
          fence_async_smem();
          __syncwarp();
          if (el) mbar_arrive(sb + B_AUXQ);
        }
      }
      if (half == 0) {
        for (uint32_t it = 0; __any_sync(~0u, ld32_rlx(&G->oset[m128 * 32 + (lane & 15)]) != ep1) && it < POLL_LIMIT; it++) {}
        fence_acquire_gpu();
        if (el) mbar_arrive(sb + B_OS);
      }
      auto put_gu = [&](int e, uint32_t dst) { mbar_expect_tx(sb + B_F + 8 * e, 16384); tma_2d(dst, &P.wg, 32 * f, 128 * e, sb + B_F + 8 * e); tma_2d(dst + 8192, &P.wu, 32 * f, 128 * e, sb + B_F + 8 * e); };
      if (half && f < NFFN_L) {
        if (Q0L) mbar_wait(sb + B_UO + 8 * Q0L - 8, 0);
        mbar_wait2(sb + B_KD, 0, sb + B_QL, 0);
        if (el) put_gu(0, sb + OFF_X + 16384);
      }
      if (!half) {
        #pragma unroll 1
        for (int hh = 0; hh < 2; hh++) {
          const uint32_t src = sb + (1 + rank) * R5 + hh * 8192, fa = sb + B_FULLA + 16 + 16 * rank + 8 * hh;
          mbar_wait(fa, 0);
          mbar_wait(sb + B_UO + 8 * hh, 0);
          if (el) bulk_s2peer(mapa(src, rank ^ 1), src, 8192, mapa(fa, rank ^ 1));
        }
        fetch_o(1, 32, 1);
      }
      else if (f < NFFN_L) {
        mbar_wait2(sb + B_UO, 0, sb + B_UO + 8, 0);
        mbar_wait(sb + B_UO + 24, 0);
        uint32_t t0 = (uint32_t)clock();
        while ((uint32_t)clock() - t0 < (uint32_t)FF_T0) __nanosleep(32);
        t0 -= FF_DT;
        #pragma unroll 1
        for (int i = 0; i < 11; i++) {
          const uint32_t dst = sb + 16384 * ((0x7654cadcadcull >> (4 * i)) & 15);
          if (i >= 3) mbar_wait(sb + B_WC + 8 * (i < 7 ? i - 3 : (i + 1) >> 1), 0);
          while ((uint32_t)clock() - t0 < (uint32_t)FF_DT) __nanosleep(32);
          t0 = (uint32_t)clock();
          TK(48 + i);
          if (el) {
            if (i < 4) { mbar_expect_tx(sb + B_WD + 8 * i, 16384); tma_3d_h(dst, &P.wd, 0, 32 * f, 4 * i, sb + B_WD + 8 * i, ef); }
            else put_gu(i - 3, dst);
          }
        }
      }
      __syncwarp();
    }
    {
      const int ch = lane & 15, rb = 32 * wp + (lane >> 4);
      const uint32_t src = sb + R5 + (ch >> 3) * 16384;
      bf16* dst = P.out_p + (size_t)(128 * m128) * DM + 128 * j + 8 * ch;
      __syncwarp();
      mbar_wait(sb + B_OUT + 8 * wp, 0);
      const float2 ex = lds64f(sb + OFF_EXC + 8 * wp);
      if (OUT_L) mbar_wait(sb + B_XS, 0);
      #pragma unroll 1
      for (int i = 0; i < 32; i += 2 * OUT_U) {
        uint4 v[OUT_U];
        #pragma unroll
        for (int e = 0; e < OUT_U; e++) { const int r = rb + i + 2 * e; v[e] = lds128(src + r * 128 + (((ch ^ r) & 7) << 4)); }
        #pragma unroll
        for (int e = 0; e < OUT_U; e++) { const int r = rb + i + 2 * e; if (r != __float_as_int(i < 16 ? ex.x : ex.y)) *reinterpret_cast<uint4*>(dst + r * DM) = v[e]; }
        if (OUT_NS) __nanosleep(OUT_NS);
      }
      if (wp == 0) { TK(63); }
      mbar_wait(sb + B_XS, 0);
      const int row = 2047 - (__float_as_uint(ldsf(sb + OFF_KEY)) & 2047) - 128 * m128, r = __float_as_int(lane < 16 ? ex.x : ex.y);
      if (r != row) *reinterpret_cast<uint4*>(dst + r * DM) = lds128(src + r * 128 + (((ch ^ r) & 7) << 4));
    }
    __syncwarp();
    cluster_arrive(); cluster_wait();
    return;
  }

  asm volatile("setmaxnreg.inc.sync.aligned.u32 160;");
  cluster_wait();
  const int t = tid & 127, g = lane >> 2;
  const uint32_t sa = (16 * wp + (lane & 15)) * 128 + (((lane >> 4) ^ (lane & 7)) << 4);

  if (wg == 2) {
    float s[2] = {0.f, 0.f}, s2[2] = {0.f, 0.f}, ck[8] = {0.f, 0.f, 0.f, 0.f, 0.f, 0.f, 0.f, 0.f}, cs[8] = {0.f, 0.f, 0.f, 0.f, 0.f, 0.f, 0.f, 0.f};
    const uint32_t ebr = mapa(sb + B_EMPTYKV, lane & 1), tg = (ld32_rlx(&G->epoch) + 1) & 3;
    auto addx = [&](const uint4 v) {
      const uint32_t w[4] = {v.x, v.y, v.z, v.w};
      #pragma unroll
      for (int e = 0; e < 4; e++) { const float a = bf_lo(w[e]), d = bf_hi(w[e]); s[0] += a; s[1] += d; s2[0] = fmaf(a, a, s2[0]); s2[1] = fmaf(d, d, s2[1]); }
    };
    auto addc = [&](const uint4 v, float (&o)[8]) {
      o[0] += bf_lo(v.x); o[1] += bf_hi(v.x); o[2] += bf_lo(v.y); o[3] += bf_hi(v.y); o[4] += bf_lo(v.z); o[5] += bf_hi(v.z); o[6] += bf_lo(v.w); o[7] += bf_hi(v.w);
    };
    {
      const uint32_t ra = (16 * nkv + (t >> 3)) * 128 + (t & 7) * 16;
      const uint32_t ca = 32768 + (m256 >> 2) * 8192 + (t >> 1) * 128 + (((2 * (m256 & 3) + (t & 1)) ^ ((t >> 1) & 7)) << 4);
      const bf16* gx = P.x + (size_t)(256 * m256 + 16 * nkv + (t >> 3)) * DM + 640 + (t & 7) * 8;
      const bf16* gw = P.wqkv + (size_t)(640 + (t >> 1)) * (3 * DM) + (1 + (m256 >> 2)) * DM + 64 * nkv + 16 * (m256 & 3) + 8 * (t & 1);
      uint4 u[4];
      #pragma unroll
      for (int e = 0; e < 4; e++) u[e] = make_uint4(0, 0, 0, 0);
      #pragma unroll 1
      for (int kb = 0; kb < 10; kb++) {
        const uint32_t st = sb + (kb & 3) * KV_STAGE;
        mbar_wait(sb + B_FULLKV + 8 * (kb & 3), (kb >> 2) & 1);
        const uint4 x0 = lds128(st + ra), w0 = lds128(st + ca);
        addx(x0); addc(w0, ck);
        __syncwarp();
        if (lane < 2) mbar_arrive_remote(ebr + 8 * (kb & 3), 1);
        if ((SKM >> kb) & 1) {
          addx(u[0]); addx(u[1]); addc(u[2], ck); addc(u[3], ck);
          if (kb < 9) {
            u[0] = ld128_keep(gx); u[1] = ld128_keep(gx + 64); u[2] = ld128_keep(gw); u[3] = ld128_keep(gw + 64 * 3 * DM);
            gx += 128; gw += 128 * 3 * DM;
          }
        }
      }
    }
    TK(82);
    const uint32_t scr = sb + OFF_SCR + 128;
    float sx = s[0] + s[1], sq = s2[0] + s2[1];
    #pragma unroll
    for (int o = 1; o < 8; o <<= 1) { sx += __shfl_xor_sync(~0u, sx, o); sq += __shfl_xor_sync(~0u, sq, o); }
    float v = reduce8(ck, lane);
    v += __shfl_xor_sync(~0u, v, 2);
    if (!(lane & 2)) stsf(scr + (wp * 16 + 8 * (lane & 1) + (lane >> 2)) * 4, v);

    bar_sync(NB_ZERO, 160);
    if ((lane & 7) == 0) {
      const float mean = sx * (1.f / DM);
      st64_rlx(&G->stats[256 * m256 + 16 * nkv + (t >> 3)], tagw(mean, tg), tagw(rsqrtf(fmaxf(sq * (1.f / DM) - mean * mean, 0.f) + 1e-5f), tg));
    }
    if (wp == 1 && lane < 16) {
      const uint32_t a = scr + lane * 4;
      st32_rlx(&G->cskv[128 * nkv + 16 * m256 + lane], tagw((ldsf(a) + ldsf(a + 64)) + (ldsf(a + 128) + ldsf(a + 192)), tg));
    }
    __syncwarp();
    bar_arrive(NB_PUB, 192);
    TSW(23);
    const uint4 wv = ld128_keep(P.wr + t * 8);
    #pragma unroll 1
    for (int i = 0; i < 2; i++) {
      const bf16* gq = P.wqkv + (size_t)(256 * (c >> 5) + 128 * i + (t >> 2)) * (3 * DM) + 32 * (c & 31) + 8 * (t & 3);
      const uint4 u0 = ld128_keep(gq), u1 = ld128_keep(gq + 32 * 3 * DM), u2 = ld128_keep(gq + 64 * 3 * DM), u3 = ld128_keep(gq + 96 * 3 * DM);
      addc(u0, cs); addc(u1, cs); addc(u2, cs); addc(u3, cs);
    }
    float sw = (bf_lo(wv.x) + bf_hi(wv.x)) + (bf_lo(wv.y) + bf_hi(wv.y)) + (bf_lo(wv.z) + bf_hi(wv.z)) + (bf_lo(wv.w) + bf_hi(wv.w));
    #pragma unroll
    for (int o = 16; o; o >>= 1) sw += __shfl_xor_sync(~0u, sw, o);
    if (lane == 0) stsf(sb + OFF_SUMWR + wp * 4, sw);
    if ((t >> 4) == j) {
      const uint32_t a = sb + OFF_WR + (t & 15) * 32;
      sts128(a, wv.x << 16, wv.x & 0xffff0000u, wv.y << 16, wv.y & 0xffff0000u);
      sts128(a + 16, wv.z << 16, wv.z & 0xffff0000u, wv.w << 16, wv.w & 0xffff0000u);
    }
    v = reduce8(cs, lane);
    bar_sync(NB_WG2, 128);
    stsf(scr + (wp * 32 + 8 * (lane & 3) + (lane >> 2)) * 4, v);
    bar_sync(NB_WG2, 128);
    if (wp == 0) {
      const uint32_t a = scr + lane * 4;
      st32_rlx(&G->csq[(c >> 5) * DM + 32 * (c & 31) + lane], tagw((ldsf(a) + ldsf(a + 128)) + (ldsf(a + 256) + ldsf(a + 384)), tg));
    }
  }

  uint32_t xr[32];
  {
    const bool isq = wg == 2;
    float acc[2][64];
    {
      const uint32_t emptyb = mapa(sb + (isq ? B_EMPTY5 : B_EMPTYKV), t & 1);
      if (!isq) {
        mbar_wait(sb + B_FULLKV, 0);
        if (wg == 0) { TSW(2); }
        #pragma unroll 1
        for (int kb = 0; kb < 16; kb++) {
          if (wg == 0) { TK(kb); }
          const uint32_t da = dlo(SB0, 16) + wg * 1024 + (kb & 3) * (KV_STAGE >> 4), db = dlo(SB0 + 32768, 8192) + (kb & 3) * (KV_STAGE >> 4);
          wg_fence();
          #pragma unroll
          for (int k = 0; k < 4; k++) {
            wgmma_ss_n128<0, 1, H128, H128>(acc[0], da + 2 * k, db + 128 * k, k > 0 || kb != 0);
            wgmma_ss_n128<0, 1, H128, H128>(acc[1], da + 512 + 2 * k, db + 128 * k, k > 0 || kb != 0);
          }
          wg_commit();
          wg_wait<1>();
          if (kb > 0 && t < 2) mbar_arrive_remote(emptyb + 8 * ((kb - 1) & 3), kb > 10 ? 3 : 1);
          if (kb < 15) mbar_wait(sb + B_FULLKV + 8 * ((kb + 1) & 3), ((kb + 1) >> 2) & 1);
          if (kb == 15 - LAG && wg == 1) bar_sync(NB_WG01, 256);
        }
        bar_arrive(wg ? NB_QGO : NB_WG01, 256);
      } else {
        uint32_t so = 0, po = 0, par = 0;
        mbar_wait(sb + B_FULL5, 0);
        bar_sync(NB_QGO, 256);
        TSW(11);
        #pragma unroll 1
        for (int kb = 0; kb < 16; kb++) {
          TK(16 + kb);
          const uint32_t da = dlo(SB0, 16) + so * 256, db = dlo(SB0 + 16384, 8192) + so * 256;
          #pragma unroll
          for (int k = 0; k < 4; k++) {
            wg_fence();
            wgmma_ss_n128<0, 1, H128, H128>(acc[0], da + 2 * k, db + 128 * k, k > 0 || kb != 0);
            wgmma_ss_n128<0, 1, H128, H128>(acc[1], da + 512 + 2 * k, db + 128 * k, k > 0 || kb != 0);
            wg_commit();
            if (k == 1 && kb > 0 && t < 2) mbar_arrive_remote(emptyb + po, 2);
            if (k == 3) {
              po = so; so += 8;
              if (so == 40) { so = 0; par ^= 1; }
              if (kb < 15) mbar_wait(sb + B_FULL5 + so, par);
            }
            if ((QW >> k) & 1) wg_wait<2>(); else wg_wait<1>();
          }
        }
        mbar_wait(sb + B_AUXQ, 0);
      }
      mbar_wait(sb + B_AUX, 0);
      const uint32_t xa = dlo(SB0, 0) + (isq ? OFF_AXQ >> 4 : (OFF_AXK >> 4) + wg * 128), xb = dlo(SB0, 0) + (isq ? OFF_BXQ >> 4 : OFF_BXK >> 4);
      wg_fence();
      wgmma_sa_n128<0, 1, H0, H0>(acc[0], xa, xb);
      wgmma_sa_n128<0, 1, H0, H0>(acc[1], xa + 64, xb);
      wg_commit();
      if (isq) mbar_wait(sb + B_RC, 0);
      wg_wait<0>();
      if (t < 2) mbar_arrive_remote(emptyb + (isq ? 0 : 24), isq ? 2 : 3);
      if (wg != 1) { TSW(wg ? 8 : 3); }
      fence_regs(acc[0]); fence_regs(acc[1]);
    }
    if (isq) {
      #pragma unroll
      for (int i = 0; i < 4; i++) {
        const uint32_t ta = sb + (i < 2 ? (1 + rank) * R5 : OFF_X) + sa + (i & 1) * 8192;
        if (i == 1) mbar_wait(sb + B_RC + 8, 0);
        #pragma unroll
        for (int k = 0; k < 4; k++) {
          const float* a = i < 2 ? &acc[i][32 * (k >> 1) + 8 * (k & 1)] : &acc[k >> 1][16 + 32 * (i & 1) + 8 * (k & 1)];
          stsm4(ta ^ (k << 5), pack_bf16(a[0], a[1]), pack_bf16(a[2], a[3]), pack_bf16(a[4], a[5]), pack_bf16(a[6], a[7]));
        }
        if (i < 2) { fence_async_smem(); bar_arrive(NB_Q0 + i, 256); }
      }
      TSW(26);
    } else {
      const uint32_t stg = sb + OFF_X + (1 - wg) * 24576;
      const uint32_t va = stg + 16384 + (16 * wp + (lane & 15)) * 64 + (((lane >> 4) ^ ((lane >> 1) & 3)) << 4);
      const uint32_t ra = sb + OFF_RS256 + (128 * wg + 16 * wp + g) * 4;
      const float rs[4] = {ldsf(ra), ldsf(ra + 32), ldsf(ra + 256), ldsf(ra + 288)};
      float p[2][16];
      uint32_t vf[16], kf[2][16];
      auto project = [&](const uint32_t (&f)[16], uint32_t db) {
        wg_fence();
        #pragma unroll
        for (int i = 0; i < 2; i++) {
          wgmma_rs_n32<1, H64>(p[i], f[8*i], f[8*i+1], f[8*i+2], f[8*i+3], db, 0);
          wgmma_ra_n32<1, H64>(p[i], f[8*i+4], f[8*i+5], f[8*i+6], f[8*i+7], db + 64);
        }
        wg_commit();
      };
      auto fold = [&](uint32_t (&f)[16], int col, float sc) {
        #pragma unroll
        for (int i = 0; i < 16; i++) {
          const float r = rs[2 * (i >> 3) + (i & 1)] * sc;
          f[i] = pack_bf16(acc[i >> 3][col + 2 * (i & 7)] * r, acc[i >> 3][col + 2 * (i & 7) + 1] * r);
          asm volatile("" : "+r"(f[i]));
        }
      };
      auto put_v = [&](const uint32_t (&f)[16]) {
        #pragma unroll
        for (int k = 0; k < 4; k++) stsm4((va ^ ((k & 1) << 5)) + (k >> 1) * 4096, f[4*k], f[4*k+1], f[4*k+2], f[4*k+3]);
      };
      fold(vf, 48, 1.f);
      mbar_wait(sb + B_W, 0);
      fold(kf[0], 0, LOG2E);
      #pragma unroll
      for (int i = 0; i < 32; i++) p[i >> 4][i & 15] = acc[i >> 4][i & 15];
      project(kf[0], dlo(SB0 + OFF_WPHIK, 16));
      mbar_wait(sb + B_W, 0);
      {
        uint32_t v0[16];
        fold(kf[1], 16, LOG2E);
        fold(v0, 32, 1.f);
        if (wg == 1) bar_sync(NB_DN, 256);
        put_v(v0);
      }
      wg_wait<0>();
      fence_regs(p[0]); fence_regs(p[1]);
      if (wg == 1) bar_arrive(NB_WG01, 256);
      #pragma unroll 1
      for (int h = 0; h < 2; h++) {
        uint32_t ph[4][8];
        float rsum[4][4];
        dual_exp2(p, ph);
        wg_fence();
        row_sums(rsum, ph, dlo(SB0 + OFF_ONES, 128));
        wg_commit();
        if (wg == 0 && h == 0) { bar_arrive(NB_DN, 256); bar_sync(NB_WG01, 256); }
        if (h == 1) {
          if (wg == 1) bar_sync(NB_DN, 256);
          put_v(vf);
        }
        wg_wait<0>();
        #pragma unroll
        for (int i = 0; i < 4; i++) fence_regs(rsum[i]);
        if (__builtin_expect(__any_sync(~0u, !((rsum[0][0] + rsum[0][2]) + (rsum[1][0] + rsum[1][2]) + (rsum[2][0] + rsum[2][2]) + (rsum[3][0] + rsum[3][2]) < EXP_LIM)), 0)) {
          dual_exp2_shifted(p, ph);
          #pragma unroll
          for (int i = 0; i < 8; i++) {
            const uint32_t* f = &ph[i >> 1][i & 1];
            float a = (bf_lo(f[0]) + bf_hi(f[0])) + (bf_lo(f[2]) + bf_hi(f[2])) + (bf_lo(f[4]) + bf_hi(f[4])) + (bf_lo(f[6]) + bf_hi(f[6]));
            a += __shfl_xor_sync(~0u, a, 1);
            rsum[i >> 1][2 * (i & 1)] = a + __shfl_xor_sync(~0u, a, 2);
          }
        }
        if (h == 0) project(kf[1], dlo(SB0 + OFF_WPHIK1, 16));
        normalize(ph, rsum);
        #pragma unroll
        for (int i = 0; i < 8; i++) {
          const uint32_t* f = &ph[i >> 1][4 * (i & 1)];
          stsm4(((stg + sa) ^ ((i & 3) << 5)) + (i >> 2) * 8192, f[0], f[1], f[2], f[3]);
        }
        fence_async_smem();
        if (wg == h) {
          float kv[20];
          #pragma unroll
          for (int w = 0; w < 2; w++) {
            const uint32_t da = dlo(SB0 + OFF_X, 16) + (h ^ w ^ 1) * 1536, db = dlo(SB0 + OFF_X + 16384, OFF_ONES - OFF_X - 16384) - (h ^ w ^ 1) * (1536 * 65535);
            if (w) bar_sync(NB_ST, 256); else bar_sync(NB_L0 + h, 128);
            wg_fence();
            #pragma unroll
            for (int k = 0; k < 8; k++) {
              if (k == 0 && w == 0) wgmma_sz_n40<1, 1, H128, H64>(kv, da, db);
              else wgmma_sa_n40<1, 1, H128, H64>(kv, da + k * 128, db - k * (64 * 65535));
            }
            wg_commit();
          }
          float4* dst = &G->kvacc[(ha + 2 * h) * KVP + t];
          wg_wait<0>();
          fence_regs(kv);
          if (h == 0) bar_arrive(NB_DN, 256); else if (t == 0) mbar_arrive(sb + B_KD);
          kv[17] = kv[18];
          #pragma unroll
          for (int i = 0; i < 6; i++) red_add_f32x4(dst + 128 * i, kv[3*i], kv[3*i+1], kv[3*i+2], 1.f);
          TSW(29 + h);
        } else bar_arrive(NB_ST, 256);
        wg_wait<0>();
        fence_regs(p[0]); fence_regs(p[1]);
      }
    }
    auto capture = [&]() {
      mbar_wait(sb + B_R, 0);
      #pragma unroll
      for (int k = 0; k < 8; k++) ldsm4(((sb + (1 + rank) * R5 + wg * 8192 + sa) ^ ((k & 3) << 5)) + (k >> 2) * 2 * R5, xr[4*k], xr[4*k+1], xr[4*k+2], xr[4*k+3]);
      fence_async_smem();
      __syncwarp();
      if (lane == 0) { mbar_arrive(sb + B_RC + 8 * wg); mbar_arrive_at(sb + B_RX, wg, 1); }
    };
    #pragma unroll
    for (int i = 0; i < 32; i++) asm volatile("mov.b32 %0, 0;" : "=r"(xr[i]));
    if (wg == 1) capture();
    {
      const uint4* src = reinterpret_cast<const uint4*>(&G->kvacc[(4 * j + wg) * KVP + t]);
      uint4 v[12];
      uint32_t it = 0, bad;
      do {
        bad = 0;
        #pragma unroll
        for (int i = 0; i < 12; i++) {
          v[i] = make_uint4(0, 0, 0, 0x41000000u);
          if (i < 6 || isq) v[i] = ld128_rlx(src + 128 * i);
          bad |= v[i].w ^ 0x41000000u;
        }
      } while (__any_sync(~0u, bad != 0) && ++it < POLL_LIMIT);
      mbar_wait(sb + B_KD, 0);
      #pragma unroll
      for (int e = 0; e < 2; e++) {
        if (e == 0 || isq) {
          float f[18];
          #pragma unroll
          for (int i = 0; i < 6; i++) { f[3*i] = __uint_as_float(v[6*e+i].x); f[3*i+1] = __uint_as_float(v[6*e+i].y); f[3*i+2] = __uint_as_float(v[6*e+i].z); }
          const uint32_t ka = sb + OFF_KVZ + (wg + e) * 5120 + wp * 1280 + lane * 16;
          stsm4(ka, pack_bf16(f[0], f[1]), pack_bf16(f[2], f[3]), pack_bf16(f[4], f[5]), pack_bf16(f[6], f[7]));
          stsm4(ka + 512, pack_bf16(f[8], f[9]), pack_bf16(f[10], f[11]), pack_bf16(f[12], f[13]), pack_bf16(f[14], f[15]));
          stsm2(ka + 1024, pack_bf16(f[16], 1.f), pack_bf16(f[17], 1.f));
        }
      }
    }
    if (wg == 0) capture(); else fence_async_smem();
    if (wg == 1) bar_arrive(NB_DN, 256);
    if (isq) mbar_wait(sb + B_OS, 0);
    TSW(wg == 0 ? 5 : wg == 1 ? 25 : 6);
    float p[2][16];
    #pragma unroll
    for (int i = 0; i < 32; i++) asm volatile("mov.b32 %0, 0;" : "=f"(p[i >> 4][i & 15]));
    #pragma unroll 1
    for (int e = wg; e < wg + 1 + (wg >> 1); e++) {
      const int half = e >> 1, hh = e & 1, turn = e;
      const uint32_t ao = (half ? OFF_X : (1 + rank) * R5) + hh * 8192;
      const uint32_t ra = sb + OFF_RSQ + (16 * wp + g) * 4 + (e == 1 ? 256 : 0), rb = ra + 256 * half;
      const float cc[2][2] = {{ldsf(ra) * LOG2E, ldsf(ra + 32) * LOG2E}, {ldsf(rb) * LOG2E, ldsf(rb + 32) * LOG2E}};
      float m[2][4] = {{0.f, 0.f, 0.f, 0.f}, {0.f, 0.f, 0.f, 0.f}};
      uint32_t ph[2][8];
      auto exps = [&](int h) {
        #pragma unroll
        for (int k = 0; k < 8; k++) {
          const float c = cc[h][k & 1], mp = m[h][k & 1], mm = m[h][2 + (k & 1)];
          ph[0][k] = pack_bf16(ex2(fmaf(p[h][2*k], c, mp)), ex2(fmaf(p[h][2*k+1], c, mp)));
          ph[1][k] = pack_bf16(ex2(fmaf(p[h][2*k], -c, mm)), ex2(fmaf(p[h][2*k+1], -c, mm)));
        }
      };
      uint32_t shifted = 0;
      asm volatile("" : "+r"(shifted));
      #pragma unroll 1
      for (;;) {
        if (shifted) { row_extremes(p[0], cc[0], m[0]); row_extremes(p[1], cc[1], m[1]); }
        uint32_t first = (shifted ^ 1) & (e != 3);
        asm volatile("" : "+r"(first));
        if (first) {
          bar_sync(NB_Q0 + wg, isq ? 128 : 256);
          project_q(p, ao, 2 * half, 1 + half);
          if (e) bar_sync(NB_TOK + e - 1, 256);
          wg_wait<0>();
        }
        TK(64 + 4 * turn);
        fence_regs(p[0]); fence_regs(p[1]);
        exps(0);
        float s2[4] = {0.f, 0.f, 0.f, 0.f};
        #pragma unroll
        for (int i = 0; i < 32; i++) s2[((i >> 1) & 1) + 2 * (i >> 4)] = fmaf(p[i >> 4][i & 15], p[i >> 4][i & 15], s2[((i >> 1) & 1) + 2 * (i >> 4)]);
        if (!__any_sync(~0u, !shifted & !((s2[0] * cc[0][0] * cc[0][0] < ARG_LIM2) & (s2[1] * cc[0][1] * cc[0][1] < ARG_LIM2) &
                                          (s2[2] * cc[1][0] * cc[1][0] < ARG_LIM2) & (s2[3] * cc[1][1] * cc[1][1] < ARG_LIM2)))) break;
        shifted = 1;
      }
      float ac[4][20];
      auto numer = [&](int h, const uint32_t (&f)[2][8]) {
        const uint32_t db = dlo(SB0 + OFF_KVZ, 128) + (half ? e : h) * 320;
        wg_fence();
        #pragma unroll
        for (int i = 0; i < 2; i++) {
          wgmma_rz_n40<1, dhi(256, 0)>(ac[2*h+i], f[i][0], f[i][1], f[i][2], f[i][3], db + i * 160);
          wgmma_ra_n40<1, dhi(256, 0)>(ac[2*h+i], f[i][4], f[i][5], f[i][6], f[i][7], db + (i * 160 + 80));
        }
        wg_commit();
      };
      const uint32_t oa = (16 * wp + g) * 128 + (((lane & 3) ^ g) << 4);
      auto finish = [&](int h) {
        const float* ap = ac[2 * h]; const float* am = ac[2 * h + 1];
        const float ip0 = rcp(ap[17]), im0 = rcp(am[17]), ip1 = rcp(ap[19]), im1 = rcp(am[19]);
        const float d0 = rcp(fmaf(ap[16], ip0, fmaf(am[16], im0, 1e-6f))), d1 = rcp(fmaf(ap[18], ip1, fmaf(am[18], im1, 1e-6f)));
        const float a0 = ip0 * d0, b0 = im0 * d0, a1 = ip1 * d1, b1 = im1 * d1;
        #pragma unroll
        for (int r = 0; r < 2; r++) {
          const float a = r ? a1 : a0, b = r ? b1 : b0;
          uint32_t w[4];
          #pragma unroll
          for (int k = 0; k < 4; k++) w[k] = pack_bf16(fmaf(ap[4*k+2*r], a, am[4*k+2*r] * b), fmaf(ap[4*k+2*r+1], a, am[4*k+2*r+1] * b));
          const uint32_t off = (oa ^ ((half ? rank : h) << 6)) + r * 1024;
          st128_rlx(reinterpret_cast<uint8_t*>(G->o + (m128 * 16 + (half ? 2 * (j & 6) + 2 * hh + 1 : 2 * j)) * 8192 + (half ? h : hh) * 4096) + off, w[0], w[1], w[2], w[3]);
          if (!half) sts128(sb + ao + off, w[0], w[1], w[2], w[3]);
        }
      };
      numer(0, ph);
      exps(1);
      if (wg == 0) bar_sync(NB_DN, 256);
      numer(1, ph);
      if (turn < 2) bar_arrive(NB_TOK + turn, 256);
      wg_wait<1>();
      TK(65 + 4 * turn);
      fence_regs(ac[0]); fence_regs(ac[1]);
      finish(0);
      wg_wait<0>();
      fence_regs(ac[2]); fence_regs(ac[3]);
      #pragma unroll
      for (int i = 0; i < 32; i++) asm volatile("mov.b32 %0, 0;" : "=f"(p[i >> 4][i & 15]));
      if (e == 2) project_q(p, ao + 8192, 3, 3);
      finish(1);
      TK(66 + 4 * turn);
      if (!half) fence_async_smem();
      __syncwarp();
      if (lane == 0) mbar_arrive(sb + B_UO + 8 * e);
      wg_wait<0>();
      TK(67 + 4 * turn);
    }
    if (isq) cluster_arrive();
  }

  {
  int lane;
  asm volatile("mov.u32 %0, %%laneid;" : "=r"(lane));
  const int g = lane >> 2, q = lane & 3;
  if (wg < 2) {
    float h[64];
    {
      if (wg == 0) { TK(83); }
      #pragma unroll
      for (int i = 0; i < 32; i++) { h[2*i] = bf_lo(xr[i]); h[2*i+1] = bf_hi(xr[i]); }
      fence_regs(h);
      TK(80 + wg);
      const uint64_t seq = rank ? 0x1043210432104312ull : 0x1043210432104321ull;
      const uint32_t emptyb = mapa(sb + B_EMPTY5, t & 1);
      uint32_t s = 1 + rank, ps = 0;
      mbar_wait2(sb + B_FULL5 + 8 * s, 1, sb + B_UO + 8 * wg, 0);
      if (wg == 0) { TSW(14); }
      #pragma unroll G2U
      for (int i = 0; i < 16; i++) {
        if (wg == 1 && (i & 12) == TKW) { TK(84 + (i & 3)); }
        if (wg == 0) { TK(32 + i); }
        const uint32_t da = dlo(SB0, 16) + s * 2048 + wg * 512, db = dlo(SB0 + 16384, 8192) + s * 2048;
        wg_fence();
        #pragma unroll
        for (int k = 0; k < 4; k++) wgmma_sa_n128<0, 1, H128, H128>(h, da + k * 2, db + k * 128);
        wg_commit();
        const uint32_t ns = (uint32_t)((seq >> 4) >> (4 * i)) & 15;
        const uint32_t b0 = sb + B_FULL5 + 8 * ns, p0 = (0x1f07 >> i) & 1, b1 = sb + B_FULLA + 16 * ns + 8 * wg, p1 = (0x41f0 >> i) & 1;
        const bool here = mbar_test2(b0, p0, b1, p1);
        wg_wait<1>();
        if (!(((2 * REL + 1) >> i) & 1) && t < 2) mbar_arrive_remote(emptyb + 8 * ps, 1);
        if ((REL >> i) & 1) { wg_wait<0>(); if (t < 2) mbar_arrive_remote(emptyb + 8 * s, 1); }
        if (!here) mbar_wait2(b0, p0, b1, p1);
        ps = s; s = ns;
      }
    }
    cluster_arrive();
    float2 wr[16];
    #pragma unroll
    for (int i = 0; i < 16; i++) wr[i] = lds64f(sb + OFF_WR + 32 * i + 8 * q);
    const int r0 = 64 * wg + 16 * wp + g;
    float sum0, sum1, dot0, dot1, sq0, sq1;
    uint32_t redo = 0;
    asm volatile("" : "+r"(redo));
    #pragma unroll 1
    for (;;) {
    if (redo) {
      wg_wait<0>();
      const int r = r0;
      #pragma unroll 1
      for (int n = 0; n < 16; n++) {
        const uint32_t* xp = reinterpret_cast<const uint32_t*>(P.x + (size_t)(128 * m128 + r) * DM + 128 * j + 8 * n) + q;
        const uint32_t x0 = xp[0], x1 = xp[4 * DM];
        float d0 = bf_lo(x0), d1 = bf_hi(x0), d2 = bf_lo(x1), d3 = bf_hi(x1);
        #pragma unroll 1
        for (int ks = 0; ks < 64; ks++) {
          const int kb = ks >> 2, kk = 16 * (ks & 3);
          const bf16* op = G->o + (m128 * 16 + kb) * 8192 + r * 64 + 2 * q;
          const int o0 = ((kk >> 3) ^ g) << 3;
          const uint16_t* w = reinterpret_cast<const uint16_t*>(P.wo_p) + (size_t)(((kb & 1) ? 256 * (kb >> 2) + 32 * (kb & 2) + 32 + 4 * (kk & 32) : 64 * kb + 2 * (kk & 32)) + ((kk & 16) >> 2) + 8 * q) * DM + 128 * j + 8 * n + g;
          const uint32_t b0 = w[0] | (w[DM] << 16), b1 = w[2 * DM] | (w[3 * DM] << 16);
          uint32_t a0, a1, a2, a3, it = 0;
          do { a0 = ld32_rlx(op + o0); a1 = ld32_rlx(op + 512 + o0); a2 = ld32_rlx(op + (o0 ^ 8)); a3 = ld32_rlx(op + 512 + (o0 ^ 8)); }
          while (max(max(a0, a1), max(a2, a3)) == ~0u && ++it < POLL_LIMIT);
          __syncwarp();
          mma16816(d0, d1, d2, d3, a0, a1, a2, a3, b0, b1);
        }
        #pragma unroll
        for (int i = 0; i < 60; i++) h[i] = h[i + 4];
        h[60] = d0; h[61] = d1; h[62] = d2; h[63] = d3;
      }
    }
    wg_wait<0>();
    fence_regs(h);
    if (wg == 0) { TSW(16); }
    sum0 = 0.f, sum1 = 0.f, dot0 = 0.f, dot1 = 0.f, sq0 = 0.f, sq1 = 0.f;
    #pragma unroll
    for (int i = 0; i < 16; i++) {
      sum0 += h[4*i] + h[4*i+1]; sum1 += h[4*i+2] + h[4*i+3];
      sq0 = fmaf(h[4*i], h[4*i], fmaf(h[4*i+1], h[4*i+1], sq0)); sq1 = fmaf(h[4*i+2], h[4*i+2], fmaf(h[4*i+3], h[4*i+3], sq1));
      dot0 = fmaf(h[4*i], wr[i].x, fmaf(h[4*i+1], wr[i].y, dot0)); dot1 = fmaf(h[4*i+2], wr[i].x, fmaf(h[4*i+3], wr[i].y, dot1));
    }
    if (!__any_sync(~0u, !redo & (h[0] != h[0] | h[2] != h[2]))) break;
    redo = 1;
    }
    float4* const rs = &G->rstat[128 * m128 + r0];
    {
      const bool up = q & 2;
      float a = up ? sum1 : sum0, b = up ? sq1 : sq0, d = up ? dot1 : dot0;
      a += __shfl_xor_sync(~0u, up ? sum0 : sum1, 2); b += __shfl_xor_sync(~0u, up ? sq0 : sq1, 2); d += __shfl_xor_sync(~0u, up ? dot0 : dot1, 2);
      a += __shfl_xor_sync(~0u, a, 1); b += __shfl_xor_sync(~0u, b, 1); d += __shfl_xor_sync(~0u, d, 1);
      if ((q & 1) == 0) red_add_f32x4(rs + 4 * q, a, b, d, 1.f);
    }
    bar_arrive(NB_G2E, 384);
    if (wg == 0) { TSW(24); }
    bar_sync(NB_WG01, 256);
    uint32_t wa[8][4][4];
    const uint32_t wb = sb + 16384 * ((0x7654cadb >> (4 * warp)) & 15) + ((lane & 7) + ((lane >> 4) << 3)) * 64 + ((((lane >> 3) & 1) ^ ((lane >> 1) & 3)) << 4);
    auto getw = [&](int ks) {
      #pragma unroll
      for (int m = 0; m < 4; m++) ldsm4t((wb ^ ((m & 1) << 5)) + (m >> 1) * 8192 + ks * 1024, wa[ks][m][0], wa[ks][m][1], wa[ks][m][2], wa[ks][m][3]);
    };
    if (GPRE && f < NFFN_L) mbar_wait(sb + B_F + 8 * warp, 0);
    if (warp == 7) { TK(60); }
    #pragma unroll
    for (int ks = 0; ks < GPRE; ks++) getw(ks);
    float rstd[2], bm[2];
    uint32_t best;
    {
      const float2 swa = lds64f(sb + OFF_SUMWR), swb = lds64f(sb + OFF_SUMWR + 8);
      const float sw = (swa.x + swa.y) + (swb.x + swb.y);
      uint4 a[2]; uint32_t it = 0, key[2];
      do { a[0] = ld128_rlx(rs); a[1] = ld128_rlx(rs + 8); } while (__any_sync(~0u, (a[0].w & a[1].w) != 0x41000000u) && ++it < POLL_LIMIT);
      #pragma unroll
      for (int i = 0; i < 2; i++) {
        const float mean = __uint_as_float(a[i].x) * (1.f / DM);
        rstd[i] = rsqrtf(fmaxf(__uint_as_float(a[i].y) * (1.f / DM) - mean * mean, 0.f) + 1e-5f);
        bm[i] = -mean * rstd[i];
        const uint32_t rr = __float_as_uint(fmaf(__uint_as_float(a[i].z), rstd[i], sw * bm[i]));
        key[i] = ((rr ^ ((uint32_t)((int32_t)rr >> 31) | 0x80000000u)) & ~2047u) | (2047 - 128 * m128 - r0 - 8 * i);
      }
      asm volatile("redux.sync.max.u32 %0, %1, 0xffffffff;" : "=r"(best) : "r"(max(key[0], key[1])));
    }
    if (wg == 0) { TSW(17); }
    const int slot = m128 * 8 + warp, win = ~best & 15;
    if (lane < 4) st32_rlx(&G->key[(4 * j + lane) * 128 + slot], best);
    if ((win & 7) == g) {
      const bool up = win & 8;
      const float ra = up ? rstd[1] : rstd[0], rb = up ? bm[1] : bm[0];
      uint32_t x[16];
      #pragma unroll
      for (int i = 0; i < 16; i++) x[i] = pack_bf16(fmaf(up ? h[4*i+2] : h[4*i], ra, rb), fmaf(up ? h[4*i+3] : h[4*i+1], ra, rb));
      #pragma unroll
      for (int i = 0; i < 4; i++) st128_rlx(&G->cand[slot * DM + 64 * j + 16 * i + 4 * q], x[4*i], x[4*i+1], x[4*i+2], x[4*i+3]);
    }
    __syncwarp();
    if (wg == 0) { TSW(27); }
    {
      const float a0 = 1.f + rstd[0], b0 = bm[0], a1 = 1.f + rstd[1], b1 = bm[1];
      #pragma unroll
      for (int k = 0; k < 8; k++)
        stsm4(((sb + R5 + wg * 8192 + sa) ^ ((k & 3) << 5)) + (k >> 2) * 16384,
              pack_bf16(fmaf(h[8*k], a0, b0), fmaf(h[8*k+1], a0, b0)),     pack_bf16(fmaf(h[8*k+2], a1, b1), fmaf(h[8*k+3], a1, b1)),
              pack_bf16(fmaf(h[8*k+4], a0, b0), fmaf(h[8*k+5], a0, b0)),   pack_bf16(fmaf(h[8*k+6], a1, b1), fmaf(h[8*k+7], a1, b1)));
      sts32(sb + OFF_EXC + 4 * warp, 16 * warp + win);
      __syncwarp();
      if (lane == 0) mbar_arrive(sb + B_OUT + 8 * (warp >> 1));
      if (lane < 16) {
        const uint4 v = lds128(sb + R5 + (lane >> 3) * 16384 + (16 * warp + win) * 128 + (((lane & 7) ^ (win & 7)) << 4));
        st128_rlx(&G->cand[slot * DM + 512 + 64 * j + 4 * lane], v.x, v.y, v.z, v.w);
      }
    }
    if (wg == 0) { TSW(28); }
    {
      if (!GPRE && f < NFFN_L) mbar_wait(sb + B_F + 8 * warp, 0);
      #pragma unroll
      for (int ks = GPRE; ks < GRES; ks++) getw(ks);
      if (wg == 0) { TSW(15); }
      bar_sync(NB_XS, 384);
      if (wg == 0) { TSW(19); }
      uint4 xs[4];
      #pragma unroll
      for (int i = 0; i < 4; i++) xs[i] = lds128(sb + OFF_XSEL + 256 * warp + 64 * i + 16 * q);
      float d[4][4];
      #pragma unroll
      for (int ks = 0; ks < 8; ks++) {
        if (ks >= 1 && GRES + ks - 1 < 8) getw(GRES + ks - 1);
        #pragma unroll
        for (int m = 0; m < 4; m++) {
          if (ks == 0) { d[m][0] = 0.f; d[m][1] = 0.f; d[m][2] = 0.f; d[m][3] = 0.f; }
          mma16816(d[m][0], d[m][1], d[m][2], d[m][3], wa[ks][m][0], wa[ks][m][1], wa[ks][m][2], wa[ks][m][3],
                   (ks & 1) ? xs[ks >> 1].z : xs[ks >> 1].x, (ks & 1) ? xs[ks >> 1].w : xs[ks >> 1].y);
        }
      }
      if (q == 0) {
        #pragma unroll
        for (int m = 0; m < 8; m++) stsf(sb + OFF_GU + (8 * m + g) * 48 + 4 * warp, d[m >> 1][2 * (m & 1)]);
      }
      bar_arrive(NB_ACT, 384);
    }
    {
      float y0 = 0.f, y1 = 0.f, y2 = 0.f, y3 = 0.f;
      const uint32_t ky = __float_as_uint(ldsf(sb + OFF_KEY));
      const int kidx = 2047 - (ky & 2047);
      const float kr = __uint_as_float((ky & ~2047u) ^ ((ky >> 31) ? 0x80000000u : 0xfffff800u));
      const int col = 128 * (c >> 4) + 64 * (c & 1) + 32 * ((tid >> 2) & 1) + 16 * (tid & 1) + 8 * ((tid >> 1) & 1) + ((c >> 1) & 7);
      uint32_t it = 0, base = 0;
      if (tid < 8) {
        do { base = ld32_rlx(&G->cand[(kidx >> 4) * DM + 512 + (col >> 1)]); } while (base == ~0u && ++it < POLL_LIMIT);
      }
      if (tid < 2 * NFFN) {
        uint4 v;
        do { v = ld128_rlx(&G->ypart[(tid >> 1) * DM + 8 * c + 4 * (tid & 1)]); } while (v.w == ~0u && ++it < POLL_LIMIT);
        y0 = __uint_as_float(v.x); y1 = __uint_as_float(v.y); y2 = __uint_as_float(v.z); y3 = __uint_as_float(v.w);
      }
      __syncwarp();
      const bool b4 = lane & 16, b3 = lane & 8;
      const float u0 = (b4 ? y1 : y0) + __shfl_xor_sync(~0u, b4 ? y0 : y1, 16), u1 = (b4 ? y3 : y2) + __shfl_xor_sync(~0u, b4 ? y2 : y3, 16);
      float ys = (b3 ? u1 : u0) + __shfl_xor_sync(~0u, b3 ? u0 : u1, 8);
      ys += __shfl_xor_sync(~0u, ys, 4); ys += __shfl_xor_sync(~0u, ys, 2);
      if (!(lane & 6)) stsf(sb + OFF_ACT + ((4 * (lane & 1) + ((lane >> 3) & 1) * 2 + (lane >> 4)) * 8 + warp) * 4, ys);
      const float sg = __fdividef(1.f, 1.f + __expf(-kr));
      bar_sync(NB_WG01, 256);
      if (tid < 8) {
        const uint4 v0 = lds128(sb + OFF_ACT + tid * 32), v1 = lds128(sb + OFF_ACT + tid * 32 + 16);
        const float t8 = ((__uint_as_float(v0.x) + __uint_as_float(v0.y)) + (__uint_as_float(v0.z) + __uint_as_float(v0.w))) +
                         ((__uint_as_float(v1.x) + __uint_as_float(v1.y)) + __uint_as_float(v1.z));
        P.out_p[(size_t)kidx * DM + col] = __float2bfloat16(fmaf(t8, sg, (col & 1) ? bf_hi(base) : bf_lo(base)));
      }
      if (c == 0 && tid == 0) st32_rlx(&G->epoch, __float_as_uint(ldsf(sb + OFF_EP)));
      if (wg == 0) { TSW(22); TDUMP(); }
    }
  }
  if (wg == 2) {
    uint32_t wf[16][2][4];
    {
      const uint32_t wb = sb + 16384 * ((0xcadc >> (4 * wp)) & 15) + ((lane & 7) + ((lane >> 4) << 3)) * 128 + ((((lane >> 3) & 1) ^ (lane & 7)) << 4);
      if (f < NFFN_L) mbar_wait(sb + B_WD + 8 * wp, 0);
      if (wp == 0) { TK(61); }
      #pragma unroll
      for (int i = 0; i < 32; i++) ldsm4t((wb ^ (((i >> 1) & 3) << 5)) + (i >> 3) * 4096 + (i & 1) * 2048, wf[i >> 1][i & 1][0], wf[i >> 1][i & 1][1], wf[i >> 1][i & 1][2], wf[i >> 1][i & 1][3]);
      fence_async_smem();
      __syncwarp();
      if (lane == 0) mbar_arrive(sb + B_WC + 8 * wp);
      if (wp == 0) { TK(62); }
    }
    bar_sync(NB_G2E, 384);
    {
      uint32_t cur = 0;
      uint4 v;
      #pragma unroll 1
      for (uint32_t it = 0; it < POLL_LIMIT; it++) {
        const uint4 kx = ld128_rlx(&G->key[(c & 31) * 128 + 4 * lane]);
        v = ld128_rlx(&G->cand[((~cur >> 4) & 127) * DM + 4 * t]);
        uint32_t best;
        asm volatile("redux.sync.max.u32 %0, %1, 0xffffffff;" : "=r"(best) : "r"(max(max(kx.x, kx.y), max(kx.z, kx.w))));
        if (!__any_sync(~0u, min(min(kx.x, kx.y), min(kx.z, kx.w)) == 0 || v.w == ~0u) && best == cur) break;
        cur = best;
      }
      sts128(sb + OFF_XSEL + 16 * t, v.x, v.y, v.z, v.w);
      sts32(sb + OFF_KEY, cur);
      bar_arrive(NB_XS, 384);
      if (t == 0) mbar_arrive(sb + B_XS);
      TSW(18);
      bar_sync(NB_ACT, 384);
    }
    float gu[2];
    #pragma unroll
    for (int i = 0; i < 2; i++) {
      const uint4 v0 = lds128(sb + OFF_GU + (32 * i + lane) * 48), v1 = lds128(sb + OFF_GU + (32 * i + lane) * 48 + 16);
      gu[i] = ((__uint_as_float(v0.x) + __uint_as_float(v0.y)) + (__uint_as_float(v0.z) + __uint_as_float(v0.w))) +
              ((__uint_as_float(v1.x) + __uint_as_float(v1.y)) + (__uint_as_float(v1.z) + __uint_as_float(v1.w)));
    }
    const float act = gu[0] * gu[1] * rcp(1.f + ex2(-LOG2E * gu[0]));
    const uint32_t ap = pack_bf16(act, __shfl_down_sync(~0u, act, 1));
    uint32_t bf[4];
    #pragma unroll
    for (int i = 0; i < 4; i++) bf[i] = __shfl_sync(~0u, ap, 2 * q + 8 * i);
    TSW(20);
    float d[16][4];
    #pragma unroll
    for (int k = 0; k < 2; k++)
      #pragma unroll
      for (int i = 0; i < 16; i++) {
        if (k == 0) { d[i][0] = 0.f; d[i][1] = 0.f; d[i][2] = 0.f; d[i][3] = 0.f; }
        mma16816(d[i][0], d[i][1], d[i][2], d[i][3], wf[i][k][0], wf[i][k][1], wf[i][k][2], wf[i][k][3], bf[2*k], bf[2*k+1]);
      }
    #pragma unroll
    for (int a = 0; a < 2; a++) {
      float y[4];
      #pragma unroll
      for (int e = 0; e < 4; e++) {
        const int n = 8 * a + (e & 1);
        const float lo = (q & 1) ? d[n + 2][e & 2] : d[n][e & 2], hi = (q & 1) ? d[n + 6][e & 2] : d[n + 4][e & 2];
        y[e] = (q & 2) ? hi : lo;
      }
      if (f < NFFN) st128_rlx(&G->ypart[f * DM + 256 * wp + 128 * a + 4 * lane], __float_as_uint(y[0]), __float_as_uint(y[1]), __float_as_uint(y[2]), min(__float_as_uint(y[3]), ~1u));
    }
    TSW(21);
  }
  }
  cluster_wait();
}

typedef CUresult (*EncodeFn)(CUtensorMap*, CUtensorMapDataType, cuuint32_t, void*, const cuuint64_t*, const cuuint64_t*,
                             const cuuint32_t*, const cuuint32_t*, CUtensorMapInterleave, CUtensorMapSwizzle,
                             CUtensorMapL2promotion, CUtensorMapFloatOOBfill);

void make_map(EncodeFn enc, CUtensorMap* m, const void* p, int n, const cuuint64_t* dims, const cuuint64_t* str, const cuuint32_t* box,
              CUtensorMapSwizzle sw, CUtensorMapL2promotion promo) {
  cuuint32_t es[5] = {1, 1, 1, 1, 1};
  enc(m, CU_TENSOR_MAP_DATA_TYPE_BFLOAT16, n, const_cast<void*>(p), dims, str, box, es, CU_TENSOR_MAP_INTERLEAVE_NONE, sw, promo,
      CU_TENSOR_MAP_FLOAT_OOB_FILL_NONE);
}
void map2(EncodeFn enc, CUtensorMap* m, const void* p, uint64_t cols, uint64_t rows, uint32_t bc, uint32_t br, CUtensorMapSwizzle sw,
          CUtensorMapL2promotion promo) {
  const cuuint64_t dims[2] = {cols, rows}, str[1] = {cols * 2};
  const cuuint32_t box[2] = {bc, br};
  make_map(enc, m, p, 2, dims, str, box, sw, promo);
}
void map3(EncodeFn enc, CUtensorMap* m, const void* p, uint64_t cols, uint64_t rows, uint32_t br, uint32_t nb) {
  const cuuint64_t dims[3] = {64, rows, cols / 64}, str[2] = {cols * 2, 128};
  const cuuint32_t box[3] = {64, br, nb};
  make_map(enc, m, p, 3, dims, str, box, CU_TENSOR_MAP_SWIZZLE_128B, CU_TENSOR_MAP_L2_PROMOTION_L2_128B);
}

}

extern "C" void kernel_launch(void* const* d_in, const int* in_sizes, int n_in, void* d_out, int out_size) {
  (void)in_sizes; (void)n_in; (void)out_size;
  static EncodeFn enc = nullptr;
  static void* o_ptr = nullptr;
  if (!enc) {
    void* f = nullptr; cudaDriverEntryPointQueryResult qr;
    cudaGetDriverEntryPoint("cuTensorMapEncodeTiled", &f, cudaEnableDefault, &qr);
    enc = (EncodeFn)f;
    cudaGetSymbolAddress(&o_ptr, g_scr);
    cudaFuncSetAttribute(fused_kernel, cudaFuncAttributeMaxDynamicSharedMemorySize, SMEM_BYTES);
  }
  const bf16* x = (const bf16*)d_in[0];
  const bf16* wqkv = (const bf16*)d_in[1];
  const bf16* wphi = (const bf16*)d_in[2];
  const bf16* wo = (const bf16*)d_in[3];
  const bf16* wr = (const bf16*)d_in[5];
  const bf16* wgate = (const bf16*)d_in[6];
  const bf16* wup = (const bf16*)d_in[7];
  const bf16* wdown = (const bf16*)d_in[8];
  Params P;
  const CUtensorMapSwizzle S128 = CU_TENSOR_MAP_SWIZZLE_128B, S64 = CU_TENSOR_MAP_SWIZZLE_64B;
  const CUtensorMapL2promotion L128 = CU_TENSOR_MAP_L2_PROMOTION_L2_128B, L256 = CU_TENSOR_MAP_L2_PROMOTION_L2_256B,
                               L64 = CU_TENSOR_MAP_L2_PROMOTION_L2_64B;
  map2(enc, &P.x128, x, DM, SEQ, 64, 128, S128, L256);
  map2(enc, &P.x64, x, DM, SEQ, 64, 64, S128, L128);
  {
    const cuuint64_t dims[4] = {64, DM, 16, 3}, str[3] = {6 * DM, 128, 2 * DM};
    const cuuint32_t box[4] = {64, 64, 1, 2};
    make_map(enc, &P.wkv, wqkv, 4, dims, str, box, S128, L128);
  }
  map3(enc, &P.wq, wqkv, 3 * DM, DM, 64, 2);
  for (int i = 0; i < 2; i++) {
    const cuuint64_t dims[5] = {DM, (cuuint64_t)(DM - 94 - 64 * i), 4, 4, 2}, str[4] = {2 * DM, 16 * DM, 4 * DM, (cuuint64_t)(128 * DM) << i};
    const cuuint32_t box[5] = {64, 2, 4, 4, 2};
    make_map(enc, &P.wo[i], wo, 5, dims, str, box, S128, L128);
  }
  map3(enc, &P.wd, wdown, DM, FF, 32, 4);
  map2(enc, &P.wg, wgate, FF, DM, 32, 128, S64, L64);
  map2(enc, &P.wu, wup, FF, DM, 32, 128, S64, L64);
  map2(enc, &P.tg, wgate, FF, DM, 8, 16, CU_TENSOR_MAP_SWIZZLE_NONE, L128);
  map2(enc, &P.tu, wup, FF, DM, 8, 16, CU_TENSOR_MAP_SWIZZLE_NONE, L128);
  map2(enc, &P.td, wdown, 128, FF * 8, 8, 16, CU_TENSOR_MAP_SWIZZLE_NONE, L256);
  map2(enc, &P.phi, wphi, 32, 1024, 32, 32, S64, L64);
  P.x = x; P.wqkv = wqkv; P.wo_p = wo; P.wd_p = wdown; P.wg_p = wgate; P.wu_p = wup; P.wr = wr; P.out_p = (bf16*)d_out; P.g = (Scratch*)o_ptr;

  cudaLaunchConfig_t cfg = {};
  cfg.gridDim = dim3(128); cfg.blockDim = dim3(512); cfg.dynamicSmemBytes = SMEM_BYTES; cfg.stream = cudaStreamPerThread;
  cudaLaunchAttribute at[1];
  at[0].id = cudaLaunchAttributeClusterDimension; at[0].val.clusterDim.x = 2; at[0].val.clusterDim.y = 1; at[0].val.clusterDim.z = 1;
  cfg.attrs = at; cfg.numAttrs = 1;
  cudaLaunchKernelEx(&cfg, fused_kernel, P);
}
```

```cpp
#include <cuda_runtime.h>
#include <cuda.h>
#include <cuda_bf16.h>
#include <stdint.h>

namespace {

typedef __nv_bfloat16 bf16;

__device__ __forceinline__ uint32_t smem_u32(const void* p){ return (uint32_t)__cvta_generic_to_shared(p); }
__device__ __forceinline__ void mbar_init(uint32_t bar, uint32_t cnt){ asm volatile("mbarrier.init.shared::cta.b64 [%0], %1;"::"r"(bar),"r"(cnt):"memory"); }
__device__ __forceinline__ void mbar_expect_tx(uint32_t bar, uint32_t bytes){ asm volatile("mbarrier.arrive.expect_tx.shared::cta.b64 _, [%0], %1;"::"r"(bar),"r"(bytes):"memory"); }
__device__ __forceinline__ void mbar_arrive(uint32_t bar){ asm volatile("mbarrier.arrive.shared::cta.b64 _, [%0];"::"r"(bar):"memory"); }
__device__ __forceinline__ uint32_t mapa(uint32_t addr, uint32_t cta){ uint32_t r; asm volatile("mapa.shared::cluster.u32 %0, %1, %2;":"=r"(r):"r"(addr),"r"(cta)); return r; }
__device__ __forceinline__ void mbar_arrive_at(uint32_t bar, uint32_t cta, uint32_t cnt){
  asm volatile("{\n.reg .b32 ra;\nmapa.shared::cluster.u32 ra, %0, %1;\nmbarrier.arrive.shared::cluster.b64 _, [ra], %2;\n}\n"::"r"(bar),"r"(cta),"r"(cnt):"memory"); }
__device__ __forceinline__ void mbar_arrive_remote(uint32_t cluster_addr, uint32_t cnt){
  asm volatile("mbarrier.arrive.shared::cluster.b64 _, [%0], %1;"::"r"(cluster_addr),"r"(cnt):"memory"); }
__device__ __forceinline__ void mbar_wait(uint32_t bar, uint32_t parity){
  asm volatile("{\n.reg .pred p;\n.reg .u32 c;\nmov.u32 c, 0;\nLW:\nmbarrier.try_wait.parity.shared::cta.b64 p, [%0], %1;\n@p bra LD;\nadd.u32 c, c, 1;\nsetp.lt.u32 p, c, 2000000;\n@p bra LW;\ntrap;\nLD:\n}\n"::"r"(bar),"r"(parity):"memory"); }
__device__ __forceinline__ void mbar_wait2(uint32_t bar0, uint32_t par0, uint32_t bar1, uint32_t par1){
  asm volatile("{\n.reg .pred p, q;\n.reg .u32 c;\nmov.u32 c, 0;\nLW:\nmbarrier.try_wait.parity.shared::cta.b64 p, [%0], %1;\nmbarrier.try_wait.parity.shared::cta.b64 q, [%2], %3;\nand.pred p, p, q;\n@p bra LD;\nadd.u32 c, c, 1;\nsetp.lt.u32 p, c, 2000000;\n@p bra LW;\ntrap;\nLD:\n}\n"::"r"(bar0),"r"(par0),"r"(bar1),"r"(par1):"memory"); }
__device__ __forceinline__ bool mbar_test2(uint32_t bar0, uint32_t par0, uint32_t bar1, uint32_t par1){
  uint32_t r;
  asm volatile("{\n.reg .pred p, q;\nmbarrier.test_wait.parity.shared::cta.b64 p, [%1], %2;\nmbarrier.test_wait.parity.shared::cta.b64 q, [%3], %4;\nand.pred p, p, q;\nselp.u32 %0, 1, 0, p;\n}\n":"=r"(r):"r"(bar0),"r"(par0),"r"(bar1),"r"(par1):"memory");
  return r; }
__device__ __forceinline__ void tma_2d(uint32_t dst, const CUtensorMap* m, int c0, int c1, uint32_t bar){
  asm volatile("cp.async.bulk.tensor.2d.shared::cluster.global.mbarrier::complete_tx::bytes [%0], [%1, {%3, %4}], [%2];"::"r"(dst),"l"(m),"r"(bar),"r"(c0),"r"(c1):"memory"); }
__device__ __forceinline__ void tma_2d_mc(uint32_t dst, const CUtensorMap* m, int c0, int c1, uint32_t bar){
  asm volatile("cp.async.bulk.tensor.2d.shared::cluster.global.mbarrier::complete_tx::bytes.multicast::cluster [%0], [%1, {%3, %4}], [%2], %5;"::"r"(dst),"l"(m),"r"(bar),"r"(c0),"r"(c1),"h"((uint16_t)3):"memory"); }
__device__ __forceinline__ void tma_2d_mc_h(uint32_t dst, const CUtensorMap* m, int c0, int c1, uint32_t bar, uint64_t pol){
  asm volatile("cp.async.bulk.tensor.2d.shared::cluster.global.mbarrier::complete_tx::bytes.multicast::cluster.L2::cache_hint [%0], [%1, {%3, %4}], [%2], %5, %6;"::"r"(dst),"l"(m),"r"(bar),"r"(c0),"r"(c1),"h"((uint16_t)3),"l"(pol):"memory"); }
__device__ __forceinline__ void tma_4d(uint32_t dst, const CUtensorMap* m, int c0, int c1, int c2, int c3, uint32_t bar){
  asm volatile("cp.async.bulk.tensor.4d.shared::cluster.global.mbarrier::complete_tx::bytes [%0], [%1, {%3, %4, %5, %6}], [%2];"::"r"(dst),"l"(m),"r"(bar),"r"(c0),"r"(c1),"r"(c2),"r"(c3):"memory"); }
__device__ __forceinline__ uint64_t policy_evict_first(){ uint64_t p; asm volatile("createpolicy.fractional.L2::evict_first.b64 %0, 1.0;":"=l"(p)); return p; }
__device__ __forceinline__ uint64_t policy_evict_normal(){ uint64_t p; asm("createpolicy.fractional.L2::evict_normal.b64 %0, 1.0;":"=l"(p)); return p; }
__device__ __forceinline__ void tma_3d_h(uint32_t dst, const CUtensorMap* m, int c0, int c1, int c2, uint32_t bar, uint64_t pol){
  asm volatile("cp.async.bulk.tensor.3d.shared::cluster.global.mbarrier::complete_tx::bytes.L2::cache_hint [%0], [%1, {%3, %4, %5}], [%2], %6;"::"r"(dst),"l"(m),"r"(bar),"r"(c0),"r"(c1),"r"(c2),"l"(pol):"memory"); }
__device__ __forceinline__ void tma_4d_h(uint32_t dst, const CUtensorMap* m, int c0, int c1, int c2, int c3, uint32_t bar, uint64_t pol){
  asm volatile("cp.async.bulk.tensor.4d.shared::cluster.global.mbarrier::complete_tx::bytes.L2::cache_hint [%0], [%1, {%3, %4, %5, %6}], [%2], %7;"::"r"(dst),"l"(m),"r"(bar),"r"(c0),"r"(c1),"r"(c2),"r"(c3),"l"(pol):"memory"); }
__device__ __forceinline__ void red_add_f32x4(float4* p, float x, float y, float z, float w){ asm volatile("red.relaxed.gpu.global.add.v4.f32 [%0], {%1,%2,%3,%4};"::"l"(p),"f"(x),"f"(y),"f"(z),"f"(w):"memory"); }
__device__ __forceinline__ void tma_5d_h(uint32_t dst, const CUtensorMap* m, int c0, int c1, uint32_t bar, uint64_t pol){
  asm volatile("cp.async.bulk.tensor.5d.shared::cluster.global.mbarrier::complete_tx::bytes.L2::cache_hint [%0], [%1, {%3, %4, 0, 0, 0}], [%2], %5;"::"r"(dst),"l"(m),"r"(bar),"r"(c0),"r"(c1),"l"(pol):"memory"); }
__device__ __forceinline__ bool elect_one(){ uint32_t p; asm volatile("{\n.reg .pred P;\nelect.sync _|P, 0xffffffff;\nselp.b32 %0, 1, 0, P;\n}\n":"=r"(p)); return p; }
__device__ __forceinline__ void bulk_prefetch(const void* p, uint32_t bytes){
  asm volatile("cp.async.bulk.prefetch.L2.global [%0], %1;"::"l"(p),"r"(bytes):"memory"); }
__device__ __forceinline__ void bulk_s2peer(uint32_t dst_cluster, uint32_t src, uint32_t bytes, uint32_t bar_cluster){
  asm volatile("cp.async.bulk.shared::cluster.shared::cta.mbarrier::complete_tx::bytes [%0], [%1], %2, [%3];"::"r"(dst_cluster),"r"(src),"r"(bytes),"r"(bar_cluster):"memory"); }
__device__ __forceinline__ void bulk_g2s_mc(uint32_t dst, const void* src, uint32_t bytes, uint32_t bar, uint64_t pol){
  asm volatile("cp.async.bulk.shared::cluster.global.mbarrier::complete_tx::bytes.multicast::cluster.L2::cache_hint [%0], [%1], %2, [%3], %4, %5;"::"r"(dst),"l"(src),"r"(bytes),"r"(bar),"h"((uint16_t)3),"l"(pol):"memory"); }
__device__ __forceinline__ void prefetch_map(const CUtensorMap* m){ asm volatile("prefetch.tensormap [%0];"::"l"(m):"memory"); }
__device__ __forceinline__ void fence_async_smem(){ asm volatile("fence.proxy.async.shared::cta;":::"memory"); }
__device__ __forceinline__ void fence_acquire_gpu(){ asm volatile("fence.acquire.gpu;":::"memory"); }
__device__ __forceinline__ void fence_gpu(){ asm volatile("fence.acq_rel.gpu;":::"memory"); }
__device__ __forceinline__ void wg_fence(){ asm volatile("wgmma.fence.sync.aligned;":::"memory"); }
__device__ __forceinline__ void wg_commit(){ asm volatile("wgmma.commit_group.sync.aligned;":::"memory"); }
template<int N> __device__ __forceinline__ void wg_wait(){ asm volatile("wgmma.wait_group.sync.aligned %0;"::"n"(N):"memory"); }
template<int N> __device__ __forceinline__ void fence_regs(float (&d)[N]){
  #pragma unroll
  for(int i=0;i<N;i++) asm volatile("":"+f"(d[i])::"memory"); }
__device__ __forceinline__ void bar_sync(int id, int n){ asm volatile("bar.sync %0, %1;"::"r"(id),"r"(n):"memory"); }
__device__ __forceinline__ void bar_arrive(int id, int n){ asm volatile("bar.arrive %0, %1;"::"r"(id),"r"(n):"memory"); }
__device__ __forceinline__ void cluster_arrive(){ asm volatile("barrier.cluster.arrive.relaxed.aligned;":::"memory"); }
__device__ __forceinline__ void cluster_wait(){ asm volatile("barrier.cluster.wait.aligned;":::"memory"); }
__host__ __device__ constexpr uint32_t dlo(uint32_t addr, uint32_t lbo){ return (addr >> 4) | ((lbo >> 4) << 16); }
__host__ __device__ constexpr uint32_t dhi(uint32_t sbo, uint32_t sw){ return (sbo >> 4) | (sw << 30); }
constexpr uint32_t H128 = dhi(1024, 1), H64 = dhi(512, 2), H0 = dhi(128, 0);
__device__ __forceinline__ uint32_t pack_bf16(float lo, float hi){ uint32_t r; asm("cvt.rn.bf16x2.f32 %0, %1, %2;":"=r"(r):"f"(hi),"f"(lo)); return r; }
__device__ __forceinline__ float bf_lo(uint32_t v){ return __uint_as_float(v<<16); }
__device__ __forceinline__ float bf_hi(uint32_t v){ return __uint_as_float(v&0xffff0000u); }
__device__ __forceinline__ float ex2(float x){ float r; asm("ex2.approx.ftz.f32 %0, %1;":"=f"(r):"f"(x)); return r; }
__device__ __forceinline__ float rcp(float x){ float r; asm("rcp.approx.ftz.f32 %0, %1;":"=f"(r):"f"(x)); return r; }
__device__ __forceinline__ void stsm4(uint32_t addr, uint32_t a, uint32_t b, uint32_t c, uint32_t d){
  asm volatile("stmatrix.sync.aligned.m8n8.x4.shared.b16 [%0], {%1,%2,%3,%4};"::"r"(addr),"r"(a),"r"(b),"r"(c),"r"(d)); }
__device__ __forceinline__ void stsm2(uint32_t addr, uint32_t a, uint32_t b){
  asm volatile("stmatrix.sync.aligned.m8n8.x2.shared.b16 [%0], {%1,%2};"::"r"(addr),"r"(a),"r"(b)); }
__device__ __forceinline__ void mma16816(float& d0, float& d1, float& d2, float& d3, uint32_t a0, uint32_t a1, uint32_t a2, uint32_t a3, uint32_t b0, uint32_t b1){
  asm volatile("mma.sync.aligned.m16n8k16.row.col.f32.bf16.bf16.f32 {%0,%1,%2,%3}, {%4,%5,%6,%7}, {%8,%9}, {%0,%1,%2,%3};"
               : "+f"(d0), "+f"(d1), "+f"(d2), "+f"(d3) : "r"(a0), "r"(a1), "r"(a2), "r"(a3), "r"(b0), "r"(b1)); }
__device__ __forceinline__ void ldsm4(uint32_t addr, uint32_t& a, uint32_t& b, uint32_t& c, uint32_t& d){
  asm volatile("ldmatrix.sync.aligned.m8n8.x4.shared.b16 {%0,%1,%2,%3}, [%4];":"=r"(a),"=r"(b),"=r"(c),"=r"(d):"r"(addr):"memory"); }
__device__ __forceinline__ void ldsm4t(uint32_t addr, uint32_t& a, uint32_t& b, uint32_t& c, uint32_t& d){
  asm volatile("ldmatrix.sync.aligned.m8n8.x4.trans.shared.b16 {%0,%1,%2,%3}, [%4];":"=r"(a),"=r"(b),"=r"(c),"=r"(d):"r"(addr):"memory"); }
__device__ __forceinline__ void sts32(uint32_t a, uint32_t v){ asm volatile("st.shared.b32 [%0], %1;"::"r"(a),"r"(v):"memory"); }
__device__ __forceinline__ void stsf(uint32_t a, float v){ asm volatile("st.shared.f32 [%0], %1;"::"r"(a),"f"(v):"memory"); }
__device__ __forceinline__ void sts64(uint32_t a, uint32_t x, uint32_t y){ asm volatile("st.shared.v2.b32 [%0], {%1,%2};"::"r"(a),"r"(x),"r"(y):"memory"); }
__device__ __forceinline__ void sts128(uint32_t a, uint32_t x, uint32_t y, uint32_t z, uint32_t w){ asm volatile("st.shared.v4.b32 [%0], {%1,%2,%3,%4};"::"r"(a),"r"(x),"r"(y),"r"(z),"r"(w):"memory"); }
__device__ __forceinline__ float ldsf(uint32_t a){ float v; asm volatile("ld.shared.f32 %0, [%1];":"=f"(v):"r"(a):"memory"); return v; }
__device__ __forceinline__ float2 lds64f(uint32_t a){ float2 v; asm volatile("ld.shared.v2.f32 {%0,%1}, [%2];":"=f"(v.x),"=f"(v.y):"r"(a):"memory"); return v; }
__device__ __forceinline__ uint4 lds128(uint32_t a){ uint4 v; asm volatile("ld.shared.v4.u32 {%0,%1,%2,%3}, [%4];":"=r"(v.x),"=r"(v.y),"=r"(v.z),"=r"(v.w):"r"(a):"memory"); return v; }
__device__ __forceinline__ uint4 ld128_keep(const void* p){ uint4 v; asm volatile("ld.global.v4.u32 {%0,%1,%2,%3}, [%4];":"=r"(v.x),"=r"(v.y),"=r"(v.z),"=r"(v.w):"l"(p):"memory"); return v; }
__device__ __forceinline__ uint4 ld128_rlx(const void* p){ uint4 v; asm volatile("ld.relaxed.gpu.global.v4.u32 {%0,%1,%2,%3}, [%4];":"=r"(v.x),"=r"(v.y),"=r"(v.z),"=r"(v.w):"l"(p):"memory"); return v; }
__device__ __forceinline__ uint32_t ld32_rlx(const void* p){ uint32_t v; asm volatile("ld.relaxed.gpu.global.u32 %0, [%1];":"=r"(v):"l"(p):"memory"); return v; }
__device__ __forceinline__ void st128_rlx(void* p, uint32_t x, uint32_t y, uint32_t z, uint32_t w){ asm volatile("st.relaxed.gpu.global.v4.u32 [%0], {%1,%2,%3,%4};"::"l"(p),"r"(x),"r"(y),"r"(z),"r"(w):"memory"); }
__device__ __forceinline__ void st64_rlx(void* p, uint32_t x, uint32_t y){ asm volatile("st.relaxed.gpu.global.v2.u32 [%0], {%1,%2};"::"l"(p),"r"(x),"r"(y):"memory"); }
__device__ __forceinline__ void st32_rlx(void* p, uint32_t x){ asm volatile("st.relaxed.gpu.global.u32 [%0], %1;"::"l"(p),"r"(x):"memory"); }
__device__ __forceinline__ uint32_t tagw(float x, uint32_t t){ return (__float_as_uint(x) & ~3u) | t; }
__device__ __forceinline__ float untag(uint32_t w){ return __uint_as_float(w & ~3u); }

template<int TA, int TB, uint32_t HA, uint32_t HB> __device__ __forceinline__ void wgmma_ss_n128(float (&d)[64], uint32_t da, uint32_t db, int scale_d){
  asm volatile("{\n.reg .pred p;\n.reg .b64 a, b;\nsetp.ne.b32 p, %70, 0;\nmov.b64 a, {%64, %68};\nmov.b64 b, {%65, %69};\n"
  "wgmma.mma_async.sync.aligned.m64n128k16.f32.bf16.bf16 {%0, %1, %2, %3, %4, %5, %6, %7, %8, %9, %10, %11, %12, %13, %14, %15, %16, %17, %18, %19, %20, %21, %22, %23, %24, %25, %26, %27, %28, %29, %30, %31, %32, %33, %34, %35, %36, %37, %38, %39, %40, %41, %42, %43, %44, %45, %46, %47, %48, %49, %50, %51, %52, %53, %54, %55, %56, %57, %58, %59, %60, %61, %62, %63}, a, b, p, 1, 1, %66, %67;\n}\n"
  : "+f"(d[0]), "+f"(d[1]), "+f"(d[2]), "+f"(d[3]), "+f"(d[4]), "+f"(d[5]), "+f"(d[6]), "+f"(d[7]), "+f"(d[8]), "+f"(d[9]), "+f"(d[10]), "+f"(d[11]), "+f"(d[12]), "+f"(d[13]), "+f"(d[14]), "+f"(d[15]), "+f"(d[16]), "+f"(d[17]), "+f"(d[18]), "+f"(d[19]), "+f"(d[20]), "+f"(d[21]), "+f"(d[22]), "+f"(d[23]), "+f"(d[24]), "+f"(d[25]), "+f"(d[26]), "+f"(d[27]), "+f"(d[28]), "+f"(d[29]), "+f"(d[30]), "+f"(d[31]), "+f"(d[32]), "+f"(d[33]), "+f"(d[34]), "+f"(d[35]), "+f"(d[36]), "+f"(d[37]), "+f"(d[38]), "+f"(d[39]), "+f"(d[40]), "+f"(d[41]), "+f"(d[42]), "+f"(d[43]), "+f"(d[44]), "+f"(d[45]), "+f"(d[46]), "+f"(d[47]), "+f"(d[48]), "+f"(d[49]), "+f"(d[50]), "+f"(d[51]), "+f"(d[52]), "+f"(d[53]), "+f"(d[54]), "+f"(d[55]), "+f"(d[56]), "+f"(d[57]), "+f"(d[58]), "+f"(d[59]), "+f"(d[60]), "+f"(d[61]), "+f"(d[62]), "+f"(d[63])
  : "r"(da), "r"(db), "n"(TA), "n"(TB), "n"(HA), "n"(HB), "r"(scale_d));
}
template<int TA, int TB, uint32_t HA, uint32_t HB> __device__ __forceinline__ void wgmma_sa_n128(float (&d)[64], uint32_t da, uint32_t db){
  asm volatile("{\n.reg .pred p;\n.reg .b64 a, b;\nsetp.ne.b32 p, 1, 0;\nmov.b64 a, {%64, %68};\nmov.b64 b, {%65, %69};\n"
  "wgmma.mma_async.sync.aligned.m64n128k16.f32.bf16.bf16 {%0, %1, %2, %3, %4, %5, %6, %7, %8, %9, %10, %11, %12, %13, %14, %15, %16, %17, %18, %19, %20, %21, %22, %23, %24, %25, %26, %27, %28, %29, %30, %31, %32, %33, %34, %35, %36, %37, %38, %39, %40, %41, %42, %43, %44, %45, %46, %47, %48, %49, %50, %51, %52, %53, %54, %55, %56, %57, %58, %59, %60, %61, %62, %63}, a, b, p, 1, 1, %66, %67;\n}\n"
  : "+f"(d[0]), "+f"(d[1]), "+f"(d[2]), "+f"(d[3]), "+f"(d[4]), "+f"(d[5]), "+f"(d[6]), "+f"(d[7]), "+f"(d[8]), "+f"(d[9]), "+f"(d[10]), "+f"(d[11]), "+f"(d[12]), "+f"(d[13]), "+f"(d[14]), "+f"(d[15]), "+f"(d[16]), "+f"(d[17]), "+f"(d[18]), "+f"(d[19]), "+f"(d[20]), "+f"(d[21]), "+f"(d[22]), "+f"(d[23]), "+f"(d[24]), "+f"(d[25]), "+f"(d[26]), "+f"(d[27]), "+f"(d[28]), "+f"(d[29]), "+f"(d[30]), "+f"(d[31]), "+f"(d[32]), "+f"(d[33]), "+f"(d[34]), "+f"(d[35]), "+f"(d[36]), "+f"(d[37]), "+f"(d[38]), "+f"(d[39]), "+f"(d[40]), "+f"(d[41]), "+f"(d[42]), "+f"(d[43]), "+f"(d[44]), "+f"(d[45]), "+f"(d[46]), "+f"(d[47]), "+f"(d[48]), "+f"(d[49]), "+f"(d[50]), "+f"(d[51]), "+f"(d[52]), "+f"(d[53]), "+f"(d[54]), "+f"(d[55]), "+f"(d[56]), "+f"(d[57]), "+f"(d[58]), "+f"(d[59]), "+f"(d[60]), "+f"(d[61]), "+f"(d[62]), "+f"(d[63])
  : "r"(da), "r"(db), "n"(TA), "n"(TB), "n"(HA), "n"(HB));
}
template<int TA, int TB, uint32_t HA, uint32_t HB> __device__ __forceinline__ void wgmma_sa_n40(float (&d)[20], uint32_t da, uint32_t db){
  asm volatile("{\n.reg .pred p;\n.reg .b64 a, b;\nsetp.ne.b32 p, 1, 0;\nmov.b64 a, {%20, %24};\nmov.b64 b, {%21, %25};\n"
  "wgmma.mma_async.sync.aligned.m64n40k16.f32.bf16.bf16 {%0, %1, %2, %3, %4, %5, %6, %7, %8, %9, %10, %11, %12, %13, %14, %15, %16, %17, %18, %19}, a, b, p, 1, 1, %22, %23;\n}\n"
  : "+f"(d[0]), "+f"(d[1]), "+f"(d[2]), "+f"(d[3]), "+f"(d[4]), "+f"(d[5]), "+f"(d[6]), "+f"(d[7]), "+f"(d[8]), "+f"(d[9]), "+f"(d[10]), "+f"(d[11]), "+f"(d[12]), "+f"(d[13]), "+f"(d[14]), "+f"(d[15]), "+f"(d[16]), "+f"(d[17]), "+f"(d[18]), "+f"(d[19])
  : "r"(da), "r"(db), "n"(TA), "n"(TB), "n"(HA), "n"(HB));
}
template<int TA, int TB, uint32_t HA, uint32_t HB> __device__ __forceinline__ void wgmma_sz_n40(float (&d)[20], uint32_t da, uint32_t db){
  asm volatile("{\n.reg .pred p;\n.reg .b64 a, b;\nsetp.ne.b32 p, 0, 0;\nmov.b64 a, {%20, %24};\nmov.b64 b, {%21, %25};\n"
  "wgmma.mma_async.sync.aligned.m64n40k16.f32.bf16.bf16 {%0, %1, %2, %3, %4, %5, %6, %7, %8, %9, %10, %11, %12, %13, %14, %15, %16, %17, %18, %19}, a, b, p, 1, 1, %22, %23;\n}\n"
  : "=f"(d[0]), "=f"(d[1]), "=f"(d[2]), "=f"(d[3]), "=f"(d[4]), "=f"(d[5]), "=f"(d[6]), "=f"(d[7]), "=f"(d[8]), "=f"(d[9]), "=f"(d[10]), "=f"(d[11]), "=f"(d[12]), "=f"(d[13]), "=f"(d[14]), "=f"(d[15]), "=f"(d[16]), "=f"(d[17]), "=f"(d[18]), "=f"(d[19])
  : "r"(da), "r"(db), "n"(TA), "n"(TB), "n"(HA), "n"(HB));
}
template<int TA, int TB, uint32_t HA, uint32_t HB> __device__ __forceinline__ void wgmma_sa_n32(float (&d)[16], uint32_t da, uint32_t db){
  asm volatile("{\n.reg .pred p;\n.reg .b64 a, b;\nsetp.ne.b32 p, 1, 0;\nmov.b64 a, {%16, %20};\nmov.b64 b, {%17, %21};\n"
  "wgmma.mma_async.sync.aligned.m64n32k16.f32.bf16.bf16 {%0, %1, %2, %3, %4, %5, %6, %7, %8, %9, %10, %11, %12, %13, %14, %15}, a, b, p, 1, 1, %18, %19;\n}\n"
  : "+f"(d[0]), "+f"(d[1]), "+f"(d[2]), "+f"(d[3]), "+f"(d[4]), "+f"(d[5]), "+f"(d[6]), "+f"(d[7]), "+f"(d[8]), "+f"(d[9]), "+f"(d[10]), "+f"(d[11]), "+f"(d[12]), "+f"(d[13]), "+f"(d[14]), "+f"(d[15])
  : "r"(da), "r"(db), "n"(TA), "n"(TB), "n"(HA), "n"(HB));
}
template<int TA, int TB, uint32_t HA, uint32_t HB> __device__ __forceinline__ void wgmma_ss_n32(float (&d)[16], uint32_t da, uint32_t db, int scale_d){
  asm volatile("{\n.reg .pred p;\n.reg .b64 a, b;\nsetp.ne.b32 p, %22, 0;\nmov.b64 a, {%16, %20};\nmov.b64 b, {%17, %21};\n"
  "wgmma.mma_async.sync.aligned.m64n32k16.f32.bf16.bf16 {%0, %1, %2, %3, %4, %5, %6, %7, %8, %9, %10, %11, %12, %13, %14, %15}, a, b, p, 1, 1, %18, %19;\n}\n"
  : "+f"(d[0]), "+f"(d[1]), "+f"(d[2]), "+f"(d[3]), "+f"(d[4]), "+f"(d[5]), "+f"(d[6]), "+f"(d[7]), "+f"(d[8]), "+f"(d[9]), "+f"(d[10]), "+f"(d[11]), "+f"(d[12]), "+f"(d[13]), "+f"(d[14]), "+f"(d[15])
  : "r"(da), "r"(db), "n"(TA), "n"(TB), "n"(HA), "n"(HB), "r"(scale_d));
}
template<int TB, uint32_t HB> __device__ __forceinline__ void wgmma_ra_n32(float (&d)[16], uint32_t a0, uint32_t a1, uint32_t a2, uint32_t a3, uint32_t db){
  asm volatile("{\n.reg .pred p;\n.reg .b64 a, b;\nsetp.ne.b32 p, 1, 0;\nmov.b64 b, {%20, %22};\n"
  "wgmma.mma_async.sync.aligned.m64n32k16.f32.bf16.bf16 {%0, %1, %2, %3, %4, %5, %6, %7, %8, %9, %10, %11, %12, %13, %14, %15}, {%16,%17,%18,%19}, b, p, 1, 1, %21;\n}\n"
  : "+f"(d[0]), "+f"(d[1]), "+f"(d[2]), "+f"(d[3]), "+f"(d[4]), "+f"(d[5]), "+f"(d[6]), "+f"(d[7]), "+f"(d[8]), "+f"(d[9]), "+f"(d[10]), "+f"(d[11]), "+f"(d[12]), "+f"(d[13]), "+f"(d[14]), "+f"(d[15])
  : "r"(a0), "r"(a1), "r"(a2), "r"(a3), "r"(db), "n"(TB), "n"(HB));
}
template<int TB, uint32_t HB> __device__ __forceinline__ void wgmma_rs_n32(float (&d)[16], uint32_t a0, uint32_t a1, uint32_t a2, uint32_t a3, uint32_t db, int scale_d){
  asm volatile("{\n.reg .pred p;\n.reg .b64 a, b;\nsetp.ne.b32 p, %23, 0;\nmov.b64 b, {%20, %22};\n"
  "wgmma.mma_async.sync.aligned.m64n32k16.f32.bf16.bf16 {%0, %1, %2, %3, %4, %5, %6, %7, %8, %9, %10, %11, %12, %13, %14, %15}, {%16,%17,%18,%19}, b, p, 1, 1, %21;\n}\n"
  : "+f"(d[0]), "+f"(d[1]), "+f"(d[2]), "+f"(d[3]), "+f"(d[4]), "+f"(d[5]), "+f"(d[6]), "+f"(d[7]), "+f"(d[8]), "+f"(d[9]), "+f"(d[10]), "+f"(d[11]), "+f"(d[12]), "+f"(d[13]), "+f"(d[14]), "+f"(d[15])
  : "r"(a0), "r"(a1), "r"(a2), "r"(a3), "r"(db), "n"(TB), "n"(HB), "r"(scale_d));
}
template<int TB, uint32_t HB> __device__ __forceinline__ void wgmma_ra_n40(float (&d)[20], uint32_t a0, uint32_t a1, uint32_t a2, uint32_t a3, uint32_t db){
  asm volatile("{\n.reg .pred p;\n.reg .b64 a, b;\nsetp.ne.b32 p, 1, 0;\nmov.b64 b, {%24, %26};\n"
  "wgmma.mma_async.sync.aligned.m64n40k16.f32.bf16.bf16 {%0, %1, %2, %3, %4, %5, %6, %7, %8, %9, %10, %11, %12, %13, %14, %15, %16, %17, %18, %19}, {%20,%21,%22,%23}, b, p, 1, 1, %25;\n}\n"
  : "+f"(d[0]), "+f"(d[1]), "+f"(d[2]), "+f"(d[3]), "+f"(d[4]), "+f"(d[5]), "+f"(d[6]), "+f"(d[7]), "+f"(d[8]), "+f"(d[9]), "+f"(d[10]), "+f"(d[11]), "+f"(d[12]), "+f"(d[13]), "+f"(d[14]), "+f"(d[15]), "+f"(d[16]), "+f"(d[17]), "+f"(d[18]), "+f"(d[19])
  : "r"(a0), "r"(a1), "r"(a2), "r"(a3), "r"(db), "n"(TB), "n"(HB));
}
template<int TB, uint32_t HB> __device__ __forceinline__ void wgmma_rz_n40(float (&d)[20], uint32_t a0, uint32_t a1, uint32_t a2, uint32_t a3, uint32_t db){
  asm volatile("{\n.reg .pred p;\n.reg .b64 a, b;\nsetp.ne.b32 p, 0, 0;\nmov.b64 b, {%24, %26};\n"
  "wgmma.mma_async.sync.aligned.m64n40k16.f32.bf16.bf16 {%0, %1, %2, %3, %4, %5, %6, %7, %8, %9, %10, %11, %12, %13, %14, %15, %16, %17, %18, %19}, {%20,%21,%22,%23}, b, p, 1, 1, %25;\n}\n"
  : "=f"(d[0]), "=f"(d[1]), "=f"(d[2]), "=f"(d[3]), "=f"(d[4]), "=f"(d[5]), "=f"(d[6]), "=f"(d[7]), "=f"(d[8]), "=f"(d[9]), "=f"(d[10]), "=f"(d[11]), "=f"(d[12]), "=f"(d[13]), "=f"(d[14]), "=f"(d[15]), "=f"(d[16]), "=f"(d[17]), "=f"(d[18]), "=f"(d[19])
  : "r"(a0), "r"(a1), "r"(a2), "r"(a3), "r"(db), "n"(TB), "n"(HB));
}
template<int TB, uint32_t HB> __device__ __forceinline__ void wgmma_ra_n8(float (&d)[4], uint32_t a0, uint32_t a1, uint32_t a2, uint32_t a3, uint32_t db){
  asm volatile("{\n.reg .pred p;\n.reg .b64 a, b;\nsetp.ne.b32 p, 1, 0;\nmov.b64 b, {%8, %10};\n"
  "wgmma.mma_async.sync.aligned.m64n8k16.f32.bf16.bf16 {%0, %1, %2, %3}, {%4,%5,%6,%7}, b, p, 1, 1, %9;\n}\n"
  : "+f"(d[0]), "+f"(d[1]), "+f"(d[2]), "+f"(d[3])
  : "r"(a0), "r"(a1), "r"(a2), "r"(a3), "r"(db), "n"(TB), "n"(HB));
}
template<int TB, uint32_t HB> __device__ __forceinline__ void wgmma_rz_n8(float (&d)[4], uint32_t a0, uint32_t a1, uint32_t a2, uint32_t a3, uint32_t db){
  asm volatile("{\n.reg .pred p;\n.reg .b64 a, b;\nsetp.ne.b32 p, 0, 0;\nmov.b64 b, {%8, %10};\n"
  "wgmma.mma_async.sync.aligned.m64n8k16.f32.bf16.bf16 {%0, %1, %2, %3}, {%4,%5,%6,%7}, b, p, 1, 1, %9;\n}\n"
  : "=f"(d[0]), "=f"(d[1]), "=f"(d[2]), "=f"(d[3])
  : "r"(a0), "r"(a1), "r"(a2), "r"(a3), "r"(db), "n"(TB), "n"(HB));
}

constexpr int SEQ = 2048, DM = 1024, FF = 3584;
constexpr float LOG2E = 1.4426950408889634f;
constexpr uint32_t POLL_LIMIT = 1u << 22;
constexpr int NPRE = 2;
#define QW 14
#define RS_N 24
#define RS_D1 430
#define RS_D2 300
#define SKM 0x252
#define LAG 1
#define PF_T0 4000
#define PF_DT 900
#define NFFN_L NFFN
#define FF_DT 350
#define OUT_U 1
#define GRES 8
#define OUT_L 0
#define TMASK 0xffffff
#define PMASK 0xffffff
#define FF_T0 2200
#define GPRE 0
#define REL 2
#define EFI 11
#define TKW 8
#define SLOT 0
#define SLOTW 48
#define FF_ORD 0x76543210ba98ull
#define OUT_NS 0
constexpr int NFFN = 112;

constexpr uint32_t SB0 = 1024;
constexpr uint32_t KV_STAGE = 49152, R5 = 32768;
constexpr uint32_t OFF_X = 163840, OFF_S = 196608, OFF_WPHI = OFF_S + 20480, OFF_M = 229376, SMEM_BYTES = 232448;
constexpr uint32_t OFF_RS256 = 212992, OFF_ONES = OFF_RS256 + 1024, OFF_WPHIK1 = OFF_ONES + 1024, OFF_KVZ = OFF_S;
constexpr uint32_t OFF_WPHIK = OFF_S, OFF_BXK = OFF_S + 2048, OFF_AXK = OFF_S + 4096;
constexpr uint32_t OFF_AXQ = OFF_WPHI, OFF_BXQ = OFF_WPHI + 2048, OFF_WPHIQ = OFF_WPHI + 4096;
constexpr uint32_t B_FULLKV = OFF_M  , B_EMPTYKV = OFF_M + 32  ;
constexpr uint32_t B_EMPTY5 = OFF_M + 64  , B_UO = B_EMPTY5 + 48  , B_RC = B_UO + 32  ;
constexpr uint32_t B_OUT = B_RC + 16  , B_AUX = B_OUT + 32, B_AUXQ = B_AUX + 8, B_RX = B_AUXQ + 8;
constexpr uint32_t B_FULL5 = B_RX + 8  , B_FULLA = B_FULL5 + 48  , B_F = B_FULLA + 96  , B_WD = B_F + 64  ;
constexpr uint32_t B_WC = B_WD + 32  , B_DR = B_WC + 32  , B_W = B_DR + 24, B_OS = B_W + 8, B_R = B_W + 16, B_KD = B_W + 24, B_XS = B_W + 32, B_T = B_W + 40, B_END = B_W + 48;
static_assert(B_END <= OFF_M + 576, "barriers");
constexpr uint32_t OFF_EXC = OFF_M + 576, OFF_SUMWR = OFF_M + 608, OFF_EP = OFF_M + 624, OFF_KEY = OFF_M + 628;
constexpr uint32_t OFF_RSQ = OFF_M + 640, OFF_TL = OFF_M + 1152, OFF_T = OFF_M + 1792, OFF_WR = OFF_M + 2048, OFF_SCR = OFF_M + 2432;
constexpr uint32_t OFF_XSEL = 2 * R5, OFF_ACT = OFF_XSEL + 2048, OFF_GU = OFF_XSEL + 4096, OFF_OUT = 3 * R5;
constexpr uint64_t FF_SLOT = 0xdcdc3210dcbaull;
constexpr int KVP = 6 * 128;

enum { NB_G2E = 1, NB_XS = 2, NB_WG01 = 3, NB_ACT = 4, NB_Q0 = 5  , NB_ST = 14, NB_DN = 9, NB_ZERO = 10, NB_PUB = 11, NB_TOK = 10  , NB_L0 = 12  , NB_WG2 = 7, NB_QGO = 15 };

struct Scratch {
  bf16     o[SEQ * DM];
  float4   rstat[SEQ];
  uint32_t key[32 * 128];
  uint32_t cand[128 * DM];
  uint32_t ypart[NFFN * DM];
  float4   kvacc[32 * KVP];
  uint2    stats[SEQ];
  uint32_t cskv[2 * DM];
  uint32_t csq[4 * DM];
  uint32_t oset[16 * 32];
  uint32_t epoch;
};
__device__ __align__(1024) Scratch g_scr;
#define TS(id)
#define TDUMP()
#define TS0_DECL()
#define TS0_READ()
#define TS0_WRITE()
#define TK(id)
#define TSW(id)

struct Params {
  CUtensorMap x128, x64, wkv, wq, wo[2], wd, wg, wu, phi, tg, tu, td;
  const bf16 *x, *wqkv, *wo_p, *wg_p, *wu_p, *wd_p, *wr;
  bf16* out_p;
  Scratch* g;
};

constexpr float EXP_LIM = 1.1529215e18f, ARG_LIM2 = 3600.f;
__device__ __forceinline__ void dual_exp2(const float (&p)[2][16], uint32_t (&ph)[4][8]) {
  #pragma unroll
  for (int h = 0; h < 2; h++)
    #pragma unroll
    for (int k = 0; k < 8; k++) { ph[2*h][k] = pack_bf16(ex2(p[h][2*k]), ex2(p[h][2*k+1])); ph[2*h+1][k] = pack_bf16(ex2(-p[h][2*k]), ex2(-p[h][2*k+1])); }
}
__device__ __forceinline__ void row_extremes(const float (&p)[16], const float (&c)[2], float (&m)[4]) {
  m[0] = m[2] = p[0]; m[1] = m[3] = p[2];
  #pragma unroll
  for (int i = 0; i < 16; i++) { m[(i >> 1) & 1] = fmaxf(m[(i >> 1) & 1], p[i]); m[2 + ((i >> 1) & 1)] = fminf(m[2 + ((i >> 1) & 1)], p[i]); }
  #pragma unroll
  for (int o = 1; o < 4; o <<= 1) {
    m[0] = fmaxf(m[0], __shfl_xor_sync(~0u, m[0], o)); m[1] = fmaxf(m[1], __shfl_xor_sync(~0u, m[1], o));
    m[2] = fminf(m[2], __shfl_xor_sync(~0u, m[2], o)); m[3] = fminf(m[3], __shfl_xor_sync(~0u, m[3], o));
  }
  m[0] *= -c[0]; m[1] *= -c[1]; m[2] *= c[0]; m[3] *= c[1];
}
__device__ __forceinline__ void dual_exp2_shifted(const float (&p)[2][16], uint32_t (&ph)[4][8]) {
  #pragma unroll
  for (int h = 0; h < 2; h++) {
    const float one[2] = {1.f, 1.f};
    float m[4];
    row_extremes(p[h], one, m);
    #pragma unroll
    for (int k = 0; k < 8; k++) {
      ph[2*h][k] = pack_bf16(ex2(p[h][2*k] + m[k & 1]), ex2(p[h][2*k+1] + m[k & 1]));
      ph[2*h+1][k] = pack_bf16(ex2(m[2 + (k & 1)] - p[h][2*k]), ex2(m[2 + (k & 1)] - p[h][2*k+1]));
    }
  }
}
__device__ __forceinline__ void row_sums(float (&s)[4][4], const uint32_t (&ph)[4][8], uint32_t ones) {
  #pragma unroll
  for (int i = 0; i < 4; i++) wgmma_rz_n8<0, H0>(s[i], ph[i][0], ph[i][1], ph[i][2], ph[i][3], ones);
  #pragma unroll
  for (int i = 0; i < 4; i++) wgmma_ra_n8<0, H0>(s[i], ph[i][4], ph[i][5], ph[i][6], ph[i][7], ones);
}
__device__ __forceinline__ uint32_t mul_bf16x2(uint32_t a, uint32_t b) { uint32_t r; asm("mul.rn.bf16x2 %0, %1, %2;" : "=r"(r) : "r"(a), "r"(b)); return r; }
__device__ __forceinline__ void normalize(uint32_t (&ph)[4][8], const float (&s)[4][4]) {
  #pragma unroll
  for (int i = 0; i < 4; i++) {
    const float i0 = rcp(s[i][0]), i1 = rcp(s[i][2]);
    const uint32_t n0 = pack_bf16(i0, i0), n1 = pack_bf16(i1, i1);
    #pragma unroll
    for (int k = 0; k < 4; k++) { ph[i][2*k] = mul_bf16x2(ph[i][2*k], n0); ph[i][2*k+1] = mul_bf16x2(ph[i][2*k+1], n1); }
  }
}
__device__ __forceinline__ void split_bf16(float a, float b, uint32_t& hi, uint32_t& lo) { hi = pack_bf16(a, b); lo = pack_bf16(a - bf_lo(hi), b - bf_hi(hi)); }
__device__ __forceinline__ void put_colsums(uint32_t base, int lane, float a, float b, float c, float d) {
  uint32_t h0, l0, h1, l1;
  split_bf16(a, b, h0, l0); split_bf16(c, d, h1, l1);
  const uint32_t ad = base + (lane >> 1) * 128 + (lane & 1) * 8;
  sts64(ad, h0, h1); sts64(ad + 16, l0, l1); sts64(ad + 32, h0, h1); sts64(ad + 48, l0, l1);
  sts128(base + (lane >> 1) * 128 + 64 + (lane & 1) * 32, 0, 0, 0, 0); sts128(base + (lane >> 1) * 128 + 80 + (lane & 1) * 32, 0, 0, 0, 0);
}
__device__ __forceinline__ float reduce8(const float (&v)[8], int lane) {
  const bool b4 = lane & 16, b3 = lane & 8, b2 = lane & 4;
  float a[4], b[2];
  #pragma unroll
  for (int i = 0; i < 4; i++) a[i] = (b4 ? v[4 + i] : v[i]) + __shfl_xor_sync(~0u, b4 ? v[i] : v[4 + i], 16);
  #pragma unroll
  for (int i = 0; i < 2; i++) b[i] = (b3 ? a[2 + i] : a[i]) + __shfl_xor_sync(~0u, b3 ? a[i] : a[2 + i], 8);
  return (b2 ? b[1] : b[0]) + __shfl_xor_sync(~0u, b2 ? b[0] : b[1], 4);
}
__device__ __forceinline__ bool tag_bad(uint4 v, uint32_t tg) { return (((v.x ^ tg) | (v.y ^ tg) | (v.z ^ tg) | (v.w ^ tg)) & 3) != 0; }

__global__ void __launch_bounds__(512, 1) fused_kernel(const __grid_constant__ Params P) {
  extern __shared__ __align__(1024) uint8_t smem_raw[];
  const uint32_t sb = smem_u32(smem_raw);
  const int tid = threadIdx.x, lane = tid & 31;
  const int warp = __shfl_sync(~0u, tid >> 5, 0), wg = warp >> 2, wp = warp & 3;
  const int cp = blockIdx.x >> 1, cu = cp - 36, cd = (cu * 37) >> 8;
  const int gi = cp < 4 ? 0 : cu < 0 ? (cp - 4) & 7 : 1 + cu - 7 * cd, gx = cp < 4 ? 4 + cp : cu < 0 ? (cp - 4) >> 3 : 4 + cd;
  const int rank = blockIdx.x & 1, c = 64 * (gi & 1) + 8 * gx + (gi & 6) + rank;
  const int f = 16 * ((gi + 7) & 7) + 2 * gx + rank;
  const int m256 = c >> 4, nkv = c & 15, m128 = c >> 3, j = c & 7;
  const int ha = 4 * (nkv >> 1) + (nkv & 1);

  Scratch* const G = P.g;
  if ((sb & 0x3ffff) != SB0) asm volatile("trap;");

  TS0_DECL();
  if (warp == 12) {
    const bool el = elect_one();
    TS0_READ();
    if (el) {
      #pragma unroll
      for (int i = 0; i < 4; i++) mbar_init(sb + B_FULLKV + 8 * i, 1);
      asm volatile("fence.mbarrier_init.release.cluster;" ::: "memory");
      fence_async_smem();
      #pragma unroll
      for (int s = 0; s < NPRE; s++) {
        const uint32_t st = sb + s * KV_STAGE, fb = sb + B_FULLKV + 8 * s;
        mbar_expect_tx(fb, KV_STAGE);
        tma_4d(st + 32768, &P.wkv, 0, 64 * s, nkv, 1, fb);
        tma_2d(st, &P.x128, 64 * s, 256 * m256, fb);
        tma_2d(st + 16384, &P.x128, 64 * s, 256 * m256 + 128, fb);
      }
    }
  } else if (tid == 0) {
    #pragma unroll
    for (uint32_t b = B_EMPTYKV; b < B_END; b += 8) mbar_init(sb + b, b < B_EMPTY5 ? 12 : b < B_OUT ? 4 : b < B_RX ? 2 : b == B_RX ? 8 : 1);
    mbar_arrive(sb + B_FULL5 + 40);
    asm volatile("fence.mbarrier_init.release.cluster;" ::: "memory");
    fence_async_smem();
  }
  __syncthreads();
  cluster_arrive();

  if (wg == 3) {
    asm volatile("setmaxnreg.dec.sync.aligned.u32 32;");
    cluster_wait();
    const bool el = elect_one();
    const uint64_t ef = policy_evict_first(), en = policy_evict_normal();
    auto fetch_o = [&](const int t0, uint32_t so, uint32_t par) {
      const int sh = t0 & 1;
      uint32_t ready = 0;
      const bf16* base = G->o + (m128 * 16 + t0) * 8192 + rank * 4096;
      const bf16* hint = base + (lane & 3) * 1024 + 966 + (((j & 6) + ((lane >> 2) & ~sh)) & 7) * 16384 + 8 * sh * (~lane & 4);
      #pragma unroll 1
      for (int i = 2 - 2 * sh; i < 8; i += 1 + sh) {
        uint32_t it = 0;
        while ((~ready >> (4 * i) & (15 + 240 * sh)) && ++it < POLL_LIMIT) ready = __ballot_sync(~0u, ld32_rlx(hint) != ~0u);
        mbar_wait(sb + B_EMPTY5 + so, par);
        if (el) {
          bulk_g2s_mc(sb + so * 4096 + rank * 8192, base + (((j & 6) + i) & 7) * 16384, 8192, sb + B_FULLA + 2 * so + 8 * rank, ef);
          if (i == 2 - 2 * sh) TS(t0 == 0 ? (rank ? 4 : 12) : t0 == 3 ? (rank ? 31 : 10) : (rank ? 9 : 13));
        }
        so += 8;
        if (so == 48) { so = 0; par ^= 1; }
      }
    };
    if (wp == 0) {
      {
        #pragma unroll 1
        for (int kb = NPRE; kb < 16; kb++) {
          const uint32_t st = sb + (kb & 3) * KV_STAGE, fb = sb + B_FULLKV + 8 * (kb & 3);
          mbar_wait(fb + (B_EMPTYKV - B_FULLKV), ~(kb >> 2) & 1);
          if (el) {
            mbar_expect_tx(fb, KV_STAGE);
            tma_2d_mc(st + rank * 16384, &P.x128, 64 * kb, 256 * m256 + 128 * rank, fb);
            tma_4d_h(st + 32768, &P.wkv, 0, 64 * kb, nkv, 1, fb, ef);
          }
        }
        TS0_WRITE();
        uint64_t ord = 0xf3120edcba987654ull;
        uint32_t so = 0, par = 1;
        #pragma unroll 1
        for (int i = 0; i < 16; i++) {
          const uint32_t st = sb + so * 4096, fb = sb + B_FULL5 + so;
          const int k0 = (64 * (uint32_t)ord + 128 * (j & 6)) & 960;
          mbar_wait(i < 5 ? sb + B_EMPTYKV + so - (i > 1 ? 8 : 0) : fb + (B_EMPTY5 - B_FULL5), par);
          if (el) {
            mbar_expect_tx(fb, R5);
            tma_2d_mc_h(st + rank * 8192, &P.x64, k0, 128 * m128 + 64 * rank, fb, i >= EFI ? ef : en);
            tma_3d_h(st + 16384, &P.wq, 0, k0, 2 * j, fb, ef);
          }
          ord >>= 4; so += 8;
          if (so == 40) { so = 0; par ^= 1; }
        }
        #pragma unroll 1
        for (int i = 0; i < 19; i++) {
          const uint32_t fb = sb + B_FULL5 + so, fa = sb + B_FULLA + 2 * so, na = i == rank ? 0 : 8192;
          if (i == 1) { mbar_wait2(sb + B_FULL5 + 16, 0, sb + B_FULL5 + 24, 0); mbar_wait(sb + B_FULL5 + 32, 0); if (el) mbar_arrive(sb + B_R); }
          mbar_wait(fb + (B_EMPTY5 - B_FULL5), par);
          if (SLOT) { while (((uint32_t)clock() & (uint32_t)(SLOT - 1)) >= SLOTW) {} }
          if (el) {
            if (i < 16) {
              mbar_expect_tx(fb, 16384);
              const int row = i < 8 ? 128 * (((j & 6) + i) & 7) : 256 * (((j >> 1) + i) & 3) + 32 + 16 * (i & 4);
              tma_5d_h(sb + so * 4096 + 16384, &P.wo[i >> 3], 128 * j, row, fb, ef);
              tma_5d_h(sb + so * 4096 + 24576, &P.wo[i >> 3], 128 * j + 64, row, fb, ef);
              mbar_expect_tx(fa, na); mbar_expect_tx(fa + 8, na);
            } else mbar_arrive(sb + B_DR + 8 * (i - 16));
          }
          so += 8;
          if (so == 48) { so = 0; par ^= 1; }
        }
      }
    } else if (wp == 3) {
      const uint32_t t_start = (uint32_t)clock();
      if (el) {
        mbar_expect_tx(sb + B_W, 12288);
        #pragma unroll 1
        for (int i = 0; i < 6; i++) tma_2d(sb + (i == 0 ? OFF_WPHIK : i == 1 ? OFF_WPHIK1 : OFF_WPHIQ + 2048 * (i - 2)), &P.phi, 0, 32 * (i < 2 ? 2 * nkv + i : 4 * j + 2 * (i & 1) + ((i - 2) >> 1)), sb + B_W);
        prefetch_map(&P.x64); prefetch_map(&P.wq); prefetch_map(&P.wo[0]); prefetch_map(&P.wo[1]);
        prefetch_map(&P.wd); prefetch_map(&P.wg); prefetch_map(&P.wu);
      }
      #pragma unroll 1
      for (int i = 0; i < 8; i++) {
        st128_rlx(&G->cand[(m128 * 8 + i) * DM + (lane >> 4) * 512 + 64 * j + 4 * (lane & 15)], ~0u, ~0u, ~0u, ~0u);
        if (f < NFFN) st128_rlx(&G->ypart[f * DM + 128 * i + 4 * lane], ~0u, ~0u, ~0u, ~0u);
      }
      if (lane < 16) st128_rlx(&G->rstat[16 * c + lane], 0, 0, 0, 0);
      if (lane < 8) st128_rlx(&G->key[(4 * j + (lane >> 1)) * 128 + m128 * 8 + 4 * (lane & 1)], 0, 0, 0, 0);
      if (c < 32) {
        #pragma unroll 1
        for (int i = lane; i < KVP; i += 32) st128_rlx(&G->kvacc[(ha + 2 * m256) * KVP + i], 0, 0, 0, 0);
      }
      fence_gpu();
      bar_arrive(NB_ZERO, 160);
      if (el) {
        #pragma unroll 1
        for (int i = 0; i < 30; i++) {
          while ((uint32_t)clock() - t_start < (uint32_t)(PF_T0 + PF_DT * i)) __nanosleep(64);
          if (i < 4) { bulk_prefetch(P.wqkv + (size_t)(256 * i + c) * (3 * DM), 2048); bulk_prefetch(P.wqkv + (size_t)(256 * i + 128 + c) * (3 * DM), 2048); }
          else if (i < 6) bulk_prefetch(P.wo_p + (size_t)c * 8192 + (i - 4) * 4096, 8192);
          else if ((TMASK >> (i - 6)) & 1) {
            const int k = i - 6;
            if (f < NFFN) {
              if (k < 16) {
                #pragma unroll 1
                for (int e = 0; e < 4; e++) tma_2d(sb + OFF_T, rank ? &P.tu : &P.tg, 32 * (f & ~1), 64 * k + 16 * e, sb + B_T);
              } else { tma_2d(sb + OFF_T, &P.td, 0, 256 * f + 32 * (k - 16), sb + B_T); tma_2d(sb + OFF_T, &P.td, 0, 256 * f + 32 * (k - 16) + 16, sb + B_T); }
            }
          }
          else if (!((PMASK >> (i - 6)) & 1)) {}
          else if (i < 22) bulk_prefetch(((i & 1) ? P.wu_p : P.wg_p) + (size_t)((i - 6) >> 1) * 458752 + c * 3584, 7168);
          else bulk_prefetch(P.wd_p + (size_t)(i - 22) * 458752 + c * 3584, 7168);
        }
      }
      __syncwarp();
      mbar_wait2(sb + B_OS, 0, sb + B_RX, 0);
      #pragma unroll 1
      for (int t0 = 0; t0 < 4; t0 += 3) fetch_o(t0, t0 ? 8 : 24, 0);
    } else {
      const int half = wp - 1;
      const uint32_t ep1 = ld32_rlx(&G->epoch) + 1, tg = ep1 & 3;
      {
        uint32_t it = 0;
        sts128(sb + OFF_ONES + half * 512 + lane * 16, 0x3f803f80u, 0x3f803f80u, 0x3f803f80u, 0x3f803f80u);
        auto reset_o = [&](int i0, int i1, uint32_t dt) {
          uint32_t t0 = (uint32_t)clock();
          #pragma unroll 1
          for (int i = i0; i < i1; i++) {
            st128_rlx(G->o + (m128 * 16 + 2 * j + half) * 8192 + 256 * i + 8 * lane, ~0u, ~0u, ~0u, ~0u);
            while ((uint32_t)clock() - t0 < dt) __nanosleep(40);
            t0 += dt;
          }
        };
        mbar_wait(sb + B_W, 0);
        reset_o(0, RS_N, RS_D1);
        bar_sync(NB_PUB, 192);
        const uint4* src = reinterpret_cast<const uint4*>(&G->stats[256 * m256 + 128 * half]) + lane;
        const uint4* srk = reinterpret_cast<const uint4*>(&G->cskv[128 * nkv]) + lane;
        uint4 v0, v1, vk;
        it = 0;
        do { v0 = ld128_rlx(src); v1 = ld128_rlx(src + 32); vk = ld128_rlx(srk); }
        while ((tag_bad(v0, tg) || tag_bad(v1, tg) || tag_bad(vk, tg)) && ++it < POLL_LIMIT);
        fence_acquire_gpu();
        if (half) put_colsums(sb + OFF_BXK, lane, untag(vk.x), untag(vk.y), untag(vk.z), untag(vk.w));
        #pragma unroll
        for (int i = 0; i < 2; i++) {
          const uint4 v = i ? v1 : v0;
          uint32_t hi, lo;
          split_bf16(-0.5f * untag(v.x), -0.5f * untag(v.z), hi, lo);
          const uint32_t h0 = __byte_perm(hi, hi, 0x1010), h1 = __byte_perm(hi, hi, 0x3232), l0 = __byte_perm(lo, lo, 0x1010), l1 = __byte_perm(lo, lo, 0x3232);
          const uint32_t a = sb + OFF_AXK + half * 2048 + i * 1024 + lane * 32;
          sts128(a, h0, l0, 0, 0); sts128(a + 16, h1, l1, 0, 0);
          sts64(sb + OFF_RS256 + half * 512 + i * 256 + lane * 8, v.y & ~3u, v.w & ~3u);
          if (half == (m128 & 1)) {
            const uint32_t aq = sb + OFF_AXQ + i * 1024 + lane * 32;
            sts128(aq, h0, l0, 0, 0); sts128(aq + 16, h1, l1, 0, 0);
            sts64(sb + OFF_RSQ + i * 256 + lane * 8, v.y & ~3u, v.w & ~3u);
          }
        }
        fence_async_smem();
        __syncwarp();
        if (el) { sts32(sb + OFF_EP, ep1); mbar_arrive(sb + B_AUX); if (!half) TS(1); }
        reset_o(RS_N, 32, RS_D2);
        fence_gpu();
        __syncwarp();
        if (el) { st32_rlx(&G->oset[m128 * 32 + 2 * j + half], ep1); if (half) mbar_arrive(sb + B_AUXQ); }
        if (!half) {
          const uint4* src = reinterpret_cast<const uint4*>(&G->csq[128 * j]) + lane;
          uint4 v0, v1, v2, v3;
          do { v0 = ld128_rlx(src); v1 = ld128_rlx(src + DM / 4); v2 = ld128_rlx(src + DM / 2); v3 = ld128_rlx(src + 3 * DM / 4); }
          while ((tag_bad(v0, tg) || tag_bad(v1, tg) || tag_bad(v2, tg) || tag_bad(v3, tg)) && ++it < POLL_LIMIT);
          put_colsums(sb + OFF_BXQ, lane, (untag(v0.x) + untag(v1.x)) + (untag(v2.x) + untag(v3.x)), (untag(v0.y) + untag(v1.y)) + (untag(v2.y) + untag(v3.y)),
                      (untag(v0.z) + untag(v1.z)) + (untag(v2.z) + untag(v3.z)), (untag(v0.w) + untag(v1.w)) + (untag(v2.w) + untag(v3.w)));
          fence_async_smem();
          __syncwarp();
          if (el) mbar_arrive(sb + B_AUXQ);
        }
      }
      if (half == 0) {
        for (uint32_t it = 0; __any_sync(~0u, ld32_rlx(&G->oset[m128 * 32 + (lane & 15)]) != ep1) && it < POLL_LIMIT; it++) {}
        fence_acquire_gpu();
        if (el) mbar_arrive(sb + B_OS);
      }
      if (!half) {
        #pragma unroll 1
        for (int hh = 0; hh < 2; hh++) {
          const uint32_t src = sb + (1 + rank) * R5 + hh * 8192, fa = sb + B_FULLA + 16 + 16 * rank + 8 * hh;
          mbar_wait(fa, 0);
          mbar_wait(sb + B_UO + 8 * hh, 0);
          if (el) bulk_s2peer(mapa(src, rank ^ 1), src, 8192, mapa(fa, rank ^ 1));
        }
        fetch_o(1, 24, 1);
      }
      else if (f < NFFN_L) {
        mbar_wait2(sb + B_UO, 0, sb + B_UO + 8, 0);
        mbar_wait(sb + B_UO + 24, 0);
        uint32_t t0 = (uint32_t)clock();
        while ((uint32_t)clock() - t0 < (uint32_t)FF_T0) __nanosleep(32);
        t0 -= FF_DT;
        #pragma unroll 1
        for (int i = 0; i < 12; i++) {
          const int e = (FF_ORD >> (4 * i)) & 15;
          const uint32_t dst = sb + 16384 * ((FF_SLOT >> (4 * e)) & 15), fb = sb + B_F + 8 * e;
          if (i >= 2) mbar_wait(sb + B_WC + 8 * ((0x100066553244ull >> (4 * e)) & 15), 0);
          while ((uint32_t)clock() - t0 < (uint32_t)FF_DT) __nanosleep(32);
          t0 = (uint32_t)clock();
          TK(48 + i);
          if (el) {
            mbar_expect_tx(fb, 16384);
            if (e >= 8) tma_3d_h(dst, &P.wd, 0, 32 * f, 4 * e - 32, fb, ef);
            else { tma_2d(dst, &P.wg, 32 * f, 128 * e, fb); tma_2d(dst + 8192, &P.wu, 32 * f, 128 * e, fb); }
          }
        }
      }
      __syncwarp();
    }
    {
      const int ch = lane & 15, rb = 32 * wp + (lane >> 4);
      const uint32_t src = sb + OFF_OUT + (ch >> 3) * 16384;
      bf16* dst = P.out_p + (size_t)(128 * m128) * DM + 128 * j + 8 * ch;
      __syncwarp();
      mbar_wait(sb + B_OUT + 8 * wp, 0);
      const float2 ex = lds64f(sb + OFF_EXC + 8 * wp);
      if (OUT_L) mbar_wait(sb + B_XS, 0);
      #pragma unroll 1
      for (int i = 0; i < 32; i += 2 * OUT_U) {
        uint4 v[OUT_U];
        #pragma unroll
        for (int e = 0; e < OUT_U; e++) { const int r = rb + i + 2 * e; v[e] = lds128(src + r * 128 + (((ch ^ r) & 7) << 4)); }
        #pragma unroll
        for (int e = 0; e < OUT_U; e++) { const int r = rb + i + 2 * e; if (r != __float_as_int(i < 16 ? ex.x : ex.y)) *reinterpret_cast<uint4*>(dst + r * DM) = v[e]; }
        if (OUT_NS) __nanosleep(OUT_NS);
      }
      if (wp == 0) { TK(63); }
      mbar_wait(sb + B_XS, 0);
      const int row = 2047 - (__float_as_uint(ldsf(sb + OFF_KEY)) & 2047) - 128 * m128, r = __float_as_int(lane < 16 ? ex.x : ex.y);
      if (r != row) *reinterpret_cast<uint4*>(dst + r * DM) = lds128(src + r * 128 + (((ch ^ r) & 7) << 4));
    }
    __syncwarp();
    cluster_arrive(); cluster_wait();
    return;
  }

  asm volatile("setmaxnreg.inc.sync.aligned.u32 160;");
  cluster_wait();
  const int t = tid & 127, g = lane >> 2;
  const uint32_t sa = (16 * wp + (lane & 15)) * 128 + (((lane >> 4) ^ (lane & 7)) << 4);

  if (wg == 2) {
    float s[2] = {0.f, 0.f}, s2[2] = {0.f, 0.f}, ck[8] = {0.f, 0.f, 0.f, 0.f, 0.f, 0.f, 0.f, 0.f}, cs[8] = {0.f, 0.f, 0.f, 0.f, 0.f, 0.f, 0.f, 0.f};
    const uint32_t ebr = mapa(sb + B_EMPTYKV, lane & 1), tg = (ld32_rlx(&G->epoch) + 1) & 3;
    auto addx = [&](const uint4 v) {
      const uint32_t w[4] = {v.x, v.y, v.z, v.w};
      #pragma unroll
      for (int e = 0; e < 4; e++) { const float a = bf_lo(w[e]), d = bf_hi(w[e]); s[0] += a; s[1] += d; s2[0] = fmaf(a, a, s2[0]); s2[1] = fmaf(d, d, s2[1]); }
    };
    auto addc = [&](const uint4 v, float (&o)[8]) {
      o[0] += bf_lo(v.x); o[1] += bf_hi(v.x); o[2] += bf_lo(v.y); o[3] += bf_hi(v.y); o[4] += bf_lo(v.z); o[5] += bf_hi(v.z); o[6] += bf_lo(v.w); o[7] += bf_hi(v.w);
    };
    {
      const uint32_t ra = (16 * nkv + (t >> 3)) * 128 + (t & 7) * 16;
      const uint32_t ca = 32768 + (m256 >> 2) * 8192 + (t >> 1) * 128 + (((2 * (m256 & 3) + (t & 1)) ^ ((t >> 1) & 7)) << 4);
      const bf16* gx = P.x + (size_t)(256 * m256 + 16 * nkv + (t >> 3)) * DM + 640 + (t & 7) * 8;
      const bf16* gw = P.wqkv + (size_t)(640 + (t >> 1)) * (3 * DM) + (1 + (m256 >> 2)) * DM + 64 * nkv + 16 * (m256 & 3) + 8 * (t & 1);
      uint4 u[4];
      #pragma unroll
      for (int e = 0; e < 4; e++) u[e] = make_uint4(0, 0, 0, 0);
      #pragma unroll 1
      for (int kb = 0; kb < 10; kb++) {
        const uint32_t st = sb + (kb & 3) * KV_STAGE;
        mbar_wait(sb + B_FULLKV + 8 * (kb & 3), (kb >> 2) & 1);
        const uint4 x0 = lds128(st + ra), w0 = lds128(st + ca);
        addx(x0); addc(w0, ck);
        __syncwarp();
        if (lane < 2) mbar_arrive_remote(ebr + 8 * (kb & 3), 1);
        if ((SKM >> kb) & 1) {
          addx(u[0]); addx(u[1]); addc(u[2], ck); addc(u[3], ck);
          if (kb < 9) {
            u[0] = ld128_keep(gx); u[1] = ld128_keep(gx + 64); u[2] = ld128_keep(gw); u[3] = ld128_keep(gw + 64 * 3 * DM);
            gx += 128; gw += 128 * 3 * DM;
          }
        }
      }
    }
    TK(82);
    const uint32_t scr = sb + OFF_SCR + 128;
    float sx = s[0] + s[1], sq = s2[0] + s2[1];
    #pragma unroll
    for (int o = 1; o < 8; o <<= 1) { sx += __shfl_xor_sync(~0u, sx, o); sq += __shfl_xor_sync(~0u, sq, o); }
    float v = reduce8(ck, lane);
    v += __shfl_xor_sync(~0u, v, 2);
    if (!(lane & 2)) stsf(scr + (wp * 16 + 8 * (lane & 1) + (lane >> 2)) * 4, v);

    bar_sync(NB_ZERO, 160);
    if ((lane & 7) == 0) {
      const float mean = sx * (1.f / DM);
      st64_rlx(&G->stats[256 * m256 + 16 * nkv + (t >> 3)], tagw(mean, tg), tagw(rsqrtf(fmaxf(sq * (1.f / DM) - mean * mean, 0.f) + 1e-5f), tg));
    }
    if (wp == 1 && lane < 16) {
      const uint32_t a = scr + lane * 4;
      st32_rlx(&G->cskv[128 * nkv + 16 * m256 + lane], tagw((ldsf(a) + ldsf(a + 64)) + (ldsf(a + 128) + ldsf(a + 192)), tg));
    }
    __syncwarp();
    bar_arrive(NB_PUB, 192);
    TSW(23);
    const uint4 wv = ld128_keep(P.wr + t * 8);
    #pragma unroll 1
    for (int i = 0; i < 2; i++) {
      const bf16* gq = P.wqkv + (size_t)(256 * (c >> 5) + 128 * i + (t >> 2)) * (3 * DM) + 32 * (c & 31) + 8 * (t & 3);
      const uint4 u0 = ld128_keep(gq), u1 = ld128_keep(gq + 32 * 3 * DM), u2 = ld128_keep(gq + 64 * 3 * DM), u3 = ld128_keep(gq + 96 * 3 * DM);
      addc(u0, cs); addc(u1, cs); addc(u2, cs); addc(u3, cs);
    }
    float sw = (bf_lo(wv.x) + bf_hi(wv.x)) + (bf_lo(wv.y) + bf_hi(wv.y)) + (bf_lo(wv.z) + bf_hi(wv.z)) + (bf_lo(wv.w) + bf_hi(wv.w));
    #pragma unroll
    for (int o = 16; o; o >>= 1) sw += __shfl_xor_sync(~0u, sw, o);
    if (lane == 0) stsf(sb + OFF_SUMWR + wp * 4, sw);
    if ((t >> 4) == j) {
      const uint32_t a = sb + OFF_WR + (t & 15) * 32;
      sts128(a, wv.x << 16, wv.x & 0xffff0000u, wv.y << 16, wv.y & 0xffff0000u);
      sts128(a + 16, wv.z << 16, wv.z & 0xffff0000u, wv.w << 16, wv.w & 0xffff0000u);
    }
    v = reduce8(cs, lane);
    bar_sync(NB_WG2, 128);
    stsf(scr + (wp * 32 + 8 * (lane & 3) + (lane >> 2)) * 4, v);
    bar_sync(NB_WG2, 128);
    if (wp == 0) {
      const uint32_t a = scr + lane * 4;
      st32_rlx(&G->csq[(c >> 5) * DM + 32 * (c & 31) + lane], tagw((ldsf(a) + ldsf(a + 128)) + (ldsf(a + 256) + ldsf(a + 384)), tg));
    }
  }

  uint32_t xr[32];
  {
    const bool isq = wg == 2;
    float acc[2][64];
    {
      const uint32_t emptyb = mapa(sb + (isq ? B_EMPTY5 : B_EMPTYKV), t & 1);
      if (!isq) {
        mbar_wait(sb + B_FULLKV, 0);
        if (wg == 0) { TSW(2); }
        #pragma unroll 1
        for (int kb = 0; kb < 16; kb++) {
          if (wg == 0) { TK(kb); }
          const uint32_t da = dlo(SB0, 16) + wg * 1024 + (kb & 3) * (KV_STAGE >> 4), db = dlo(SB0 + 32768, 8192) + (kb & 3) * (KV_STAGE >> 4);
          wg_fence();
          #pragma unroll
          for (int k = 0; k < 4; k++) {
            wgmma_ss_n128<0, 1, H128, H128>(acc[0], da + 2 * k, db + 128 * k, k > 0 || kb != 0);
            wgmma_ss_n128<0, 1, H128, H128>(acc[1], da + 512 + 2 * k, db + 128 * k, k > 0 || kb != 0);
          }
          wg_commit();
          wg_wait<1>();
          if (kb > 0 && t < 2) mbar_arrive_remote(emptyb + 8 * ((kb - 1) & 3), kb > 10 ? 3 : 1);
          if (kb < 15) mbar_wait(sb + B_FULLKV + 8 * ((kb + 1) & 3), ((kb + 1) >> 2) & 1);
          if (kb == 15 - LAG && wg == 1) bar_sync(NB_WG01, 256);
        }
        bar_arrive(wg ? NB_QGO : NB_WG01, 256);
      } else {
        uint32_t so = 0, po = 0, par = 0;
        mbar_wait(sb + B_FULL5, 0);
        bar_sync(NB_QGO, 256);
        TSW(11);
        #pragma unroll 1
        for (int kb = 0; kb < 16; kb++) {
          TK(16 + kb);
          const uint32_t da = dlo(SB0, 16) + so * 256, db = dlo(SB0 + 16384, 8192) + so * 256;
          #pragma unroll
          for (int k = 0; k < 4; k++) {
            wg_fence();
            wgmma_ss_n128<0, 1, H128, H128>(acc[0], da + 2 * k, db + 128 * k, k > 0 || kb != 0);
            wgmma_ss_n128<0, 1, H128, H128>(acc[1], da + 512 + 2 * k, db + 128 * k, k > 0 || kb != 0);
            wg_commit();
            if (k == 1 && kb > 0 && t < 2) mbar_arrive_remote(emptyb + po, 2);
            if (k == 3) {
              po = so; so += 8;
              if (so == 40) { so = 0; par ^= 1; }
              if (kb < 15) mbar_wait(sb + B_FULL5 + so, par);
            }
            if ((QW >> k) & 1) wg_wait<2>(); else wg_wait<1>();
          }
        }
        mbar_wait(sb + B_AUXQ, 0);
      }
      mbar_wait(sb + B_AUX, 0);
      const uint32_t xa = dlo(SB0, 0) + (isq ? OFF_AXQ >> 4 : (OFF_AXK >> 4) + wg * 128), xb = dlo(SB0, 0) + (isq ? OFF_BXQ >> 4 : OFF_BXK >> 4);
      wg_fence();
      wgmma_sa_n128<0, 1, H0, H0>(acc[0], xa, xb);
      wgmma_sa_n128<0, 1, H0, H0>(acc[1], xa + 64, xb);
      wg_commit();
      if (isq) mbar_wait(sb + B_RC, 0);
      wg_wait<0>();
      if (t < 2) mbar_arrive_remote(emptyb + (isq ? 0 : 24), isq ? 2 : 3);
      if (wg != 1) { TSW(wg ? 8 : 3); }
      fence_regs(acc[0]); fence_regs(acc[1]);
    }
    if (isq) {
      #pragma unroll
      for (int i = 0; i < 2; i++) {
        const uint32_t ta = sb + (1 + rank) * R5 + sa + i * 8192;
        if (i == 1) mbar_wait(sb + B_RC + 8, 0);
        #pragma unroll
        for (int k = 0; k < 4; k++) {
          const float* a = &acc[i][32 * (k >> 1) + 8 * (k & 1)];
          stsm4(ta ^ (k << 5), pack_bf16(a[0], a[1]), pack_bf16(a[2], a[3]), pack_bf16(a[4], a[5]), pack_bf16(a[6], a[7]));
        }
        fence_async_smem();
        bar_arrive(NB_Q0 + i, 256);
      }
      #pragma unroll
      for (int i = 0; i < 32; i++) { const float* a = &acc[(i >> 3) & 1][16 + 32 * (i >> 4) + 2 * (i & 7)]; xr[i] = pack_bf16(a[0], a[1]); }
      TSW(26);
    } else {
      const uint32_t stg = sb + OFF_X + (1 - wg) * 24576;
      const uint32_t va = stg + 16384 + (16 * wp + (lane & 15)) * 64 + (((lane >> 4) ^ ((lane >> 1) & 3)) << 4);
      const uint32_t ra = sb + OFF_RS256 + (128 * wg + 16 * wp + g) * 4;
      const float rs[4] = {ldsf(ra), ldsf(ra + 32), ldsf(ra + 256), ldsf(ra + 288)};
      float p[2][16];
      uint32_t vf[16], kf[2][16];
      auto project = [&](const uint32_t (&f)[16], uint32_t db) {
        wg_fence();
        #pragma unroll
        for (int i = 0; i < 2; i++) {
          wgmma_rs_n32<1, H64>(p[i], f[8*i], f[8*i+1], f[8*i+2], f[8*i+3], db, 0);
          wgmma_ra_n32<1, H64>(p[i], f[8*i+4], f[8*i+5], f[8*i+6], f[8*i+7], db + 64);
        }
        wg_commit();
      };
      auto fold = [&](uint32_t (&f)[16], int col, float sc) {
        #pragma unroll
        for (int i = 0; i < 16; i++) {
          const float r = rs[2 * (i >> 3) + (i & 1)] * sc;
          f[i] = pack_bf16(acc[i >> 3][col + 2 * (i & 7)] * r, acc[i >> 3][col + 2 * (i & 7) + 1] * r);
          asm volatile("" : "+r"(f[i]));
        }
      };
      auto put_v = [&](const uint32_t (&f)[16]) {
        #pragma unroll
        for (int k = 0; k < 4; k++) stsm4((va ^ ((k & 1) << 5)) + (k >> 1) * 4096, f[4*k], f[4*k+1], f[4*k+2], f[4*k+3]);
      };
      fold(vf, 48, 1.f);
      mbar_wait(sb + B_W, 0);
      fold(kf[0], 0, LOG2E);
      #pragma unroll
      for (int i = 0; i < 32; i++) p[i >> 4][i & 15] = acc[i >> 4][i & 15];
      project(kf[0], dlo(SB0 + OFF_WPHIK, 16));
      mbar_wait(sb + B_W, 0);
      {
        uint32_t v0[16];
        fold(kf[1], 16, LOG2E);
        fold(v0, 32, 1.f);
        if (wg == 1) bar_sync(NB_DN, 256);
        put_v(v0);
      }
      wg_wait<0>();
      fence_regs(p[0]); fence_regs(p[1]);
      if (wg == 1) bar_arrive(NB_WG01, 256);
      #pragma unroll 1
      for (int h = 0; h < 2; h++) {
        uint32_t ph[4][8];
        float rsum[4][4];
        dual_exp2(p, ph);
        wg_fence();
        row_sums(rsum, ph, dlo(SB0 + OFF_ONES, 128));
        wg_commit();
        if (wg == 0 && h == 0) { bar_arrive(NB_DN, 256); bar_sync(NB_WG01, 256); }
        if (h == 1) {
          if (wg == 1) bar_sync(NB_DN, 256);
          put_v(vf);
        }
        wg_wait<0>();
        #pragma unroll
        for (int i = 0; i < 4; i++) fence_regs(rsum[i]);
        if (__builtin_expect(__any_sync(~0u, !((rsum[0][0] + rsum[0][2]) + (rsum[1][0] + rsum[1][2]) + (rsum[2][0] + rsum[2][2]) + (rsum[3][0] + rsum[3][2]) < EXP_LIM)), 0)) {
          dual_exp2_shifted(p, ph);
          #pragma unroll
          for (int i = 0; i < 8; i++) {
            const uint32_t* f = &ph[i >> 1][i & 1];
            float a = (bf_lo(f[0]) + bf_hi(f[0])) + (bf_lo(f[2]) + bf_hi(f[2])) + (bf_lo(f[4]) + bf_hi(f[4])) + (bf_lo(f[6]) + bf_hi(f[6]));
            a += __shfl_xor_sync(~0u, a, 1);
            rsum[i >> 1][2 * (i & 1)] = a + __shfl_xor_sync(~0u, a, 2);
          }
        }
        if (h == 0) project(kf[1], dlo(SB0 + OFF_WPHIK1, 16));
        normalize(ph, rsum);
        #pragma unroll
        for (int i = 0; i < 8; i++) {
          const uint32_t* f = &ph[i >> 1][4 * (i & 1)];
          stsm4(((stg + sa) ^ ((i & 3) << 5)) + (i >> 2) * 8192, f[0], f[1], f[2], f[3]);
        }
        fence_async_smem();
        if (wg == h) {
          float kv[20];
          #pragma unroll
          for (int w = 0; w < 2; w++) {
            const uint32_t da = dlo(SB0 + OFF_X, 16) + (h ^ w ^ 1) * 1536, db = dlo(SB0 + OFF_X + 16384, OFF_ONES - OFF_X - 16384) - (h ^ w ^ 1) * (1536 * 65535);
            if (w) bar_sync(NB_ST, 256); else bar_sync(NB_L0 + h, 128);
            wg_fence();
            #pragma unroll
            for (int k = 0; k < 8; k++) {
              if (k == 0 && w == 0) wgmma_sz_n40<1, 1, H128, H64>(kv, da, db);
              else wgmma_sa_n40<1, 1, H128, H64>(kv, da + k * 128, db - k * (64 * 65535));
            }
            wg_commit();
          }
          float4* dst = &G->kvacc[(ha + 2 * h) * KVP + t];
          wg_wait<0>();
          fence_regs(kv);
          if (h == 0) bar_arrive(NB_DN, 256); else if (t < 2) { mbar_arrive_at(sb + B_EMPTY5 + 40, t, 2); if (t == 0) mbar_arrive(sb + B_KD); }
          kv[17] = kv[18];
          #pragma unroll
          for (int i = 0; i < 6; i++) red_add_f32x4(dst + 128 * i, kv[3*i], kv[3*i+1], kv[3*i+2], 1.f);
          TSW(29 + h);
        } else bar_arrive(NB_ST, 256);
        wg_wait<0>();
        fence_regs(p[0]); fence_regs(p[1]);
      }
      #pragma unroll
      for (int i = 0; i < 32; i++) asm volatile("mov.b32 %0, 0;" : "=r"(xr[i]));
    }
    auto capture = [&]() {
      mbar_wait(sb + B_R, 0);
      #pragma unroll
      for (int k = 0; k < 8; k++) ldsm4(((sb + (1 + rank) * R5 + wg * 8192 + sa) ^ ((k & 3) << 5)) + (k >> 2) * 2 * R5, xr[4*k], xr[4*k+1], xr[4*k+2], xr[4*k+3]);
      fence_async_smem();
      __syncwarp();
      if (lane == 0) { mbar_arrive(sb + B_RC + 8 * wg); mbar_arrive_at(sb + B_RX, wg, 1); }
    };
    if (wg == 1) capture();
    {
      const uint4* src = reinterpret_cast<const uint4*>(&G->kvacc[(4 * j + wg) * KVP + t]);
      uint4 v[12];
      uint32_t it = 0, bad;
      do {
        bad = 0;
        #pragma unroll
        for (int i = 0; i < 12; i++) {
          v[i] = make_uint4(0, 0, 0, 0x41000000u);
          if (i < 6 || isq) v[i] = ld128_rlx(src + 128 * i);
          bad |= v[i].w ^ 0x41000000u;
        }
      } while (__any_sync(~0u, bad != 0) && ++it < POLL_LIMIT);
      mbar_wait(sb + B_KD, 0);
      #pragma unroll
      for (int e = 0; e < 2; e++) {
        if (e == 0 || isq) {
          float f[18];
          #pragma unroll
          for (int i = 0; i < 6; i++) { f[3*i] = __uint_as_float(v[6*e+i].x); f[3*i+1] = __uint_as_float(v[6*e+i].y); f[3*i+2] = __uint_as_float(v[6*e+i].z); }
          const uint32_t ka = sb + OFF_KVZ + (wg + e) * 5120 + wp * 1280 + lane * 16;
          stsm4(ka, pack_bf16(f[0], f[1]), pack_bf16(f[2], f[3]), pack_bf16(f[4], f[5]), pack_bf16(f[6], f[7]));
          stsm4(ka + 512, pack_bf16(f[8], f[9]), pack_bf16(f[10], f[11]), pack_bf16(f[12], f[13]), pack_bf16(f[14], f[15]));
          stsm2(ka + 1024, pack_bf16(f[16], 1.f), pack_bf16(f[17], 1.f));
        }
      }
    }
    if (wg == 0) capture(); else fence_async_smem();
    if (wg == 1) bar_arrive(NB_DN, 256);
    if (isq) mbar_wait(sb + B_OS, 0);
    TSW(wg == 0 ? 5 : wg == 1 ? 25 : 6);
    float p[2][16];
    #pragma unroll
    for (int i = 0; i < 32; i++) asm volatile("mov.b32 %0, 0;" : "=f"(p[i >> 4][i & 15]));
    auto project_r = [&](int w) {
      wg_fence();
      #pragma unroll
      for (int h = 0; h < 2; h++) {
        wgmma_rs_n32<1, H64>(p[h], xr[8*h], xr[8*h+1], xr[8*h+2], xr[8*h+3], dlo(SB0 + OFF_WPHIQ, 16) + 128 * w, 0);
        wgmma_ra_n32<1, H64>(p[h], xr[8*h+4], xr[8*h+5], xr[8*h+6], xr[8*h+7], dlo(SB0 + OFF_WPHIQ, 16) + 128 * w + 64);
      }
      wg_commit();
    };
    if (isq) {
      project_r(2);
      bar_sync(NB_TOK + 1, 256);
      wg_wait<0>();
      #pragma unroll
      for (int i = 0; i < 16; i++) xr[i] = xr[16 + i];
    }
    #pragma unroll 1
    for (int e = wg; e < wg + 1 + (wg >> 1); e++) {
      const int half = e >> 1, hh = e & 1, turn = e;
      const uint32_t ao = (1 + rank) * R5 + hh * 8192;
      const uint32_t ra = sb + OFF_RSQ + (16 * wp + g) * 4 + (e == 1 ? 256 : 0), rb = ra + 256 * half;
      const float cc[2][2] = {{ldsf(ra) * LOG2E, ldsf(ra + 32) * LOG2E}, {ldsf(rb) * LOG2E, ldsf(rb + 32) * LOG2E}};
      float m[2][4] = {{0.f, 0.f, 0.f, 0.f}, {0.f, 0.f, 0.f, 0.f}};
      uint32_t ph[2][8];
      auto exps = [&](int h) {
        #pragma unroll
        for (int k = 0; k < 8; k++) {
          const float c = cc[h][k & 1], mp = m[h][k & 1], mm = m[h][2 + (k & 1)];
          ph[0][k] = pack_bf16(ex2(fmaf(p[h][2*k], c, mp)), ex2(fmaf(p[h][2*k+1], c, mp)));
          ph[1][k] = pack_bf16(ex2(fmaf(p[h][2*k], -c, mm)), ex2(fmaf(p[h][2*k+1], -c, mm)));
        }
      };
      uint32_t shifted = 0;
      asm volatile("" : "+r"(shifted));
      #pragma unroll 1
      for (;;) {
        if (shifted) { row_extremes(p[0], cc[0], m[0]); row_extremes(p[1], cc[1], m[1]); }
        uint32_t first = (shifted ^ 1) & !isq;
        asm volatile("" : "+r"(first));
        if (first) {
          bar_sync(NB_Q0 + wg, 256);
          const uint32_t da = dlo(SB0, 16) + (ao >> 4), db = dlo(SB0 + OFF_WPHIQ, 16);
          wg_fence();
          #pragma unroll
          for (int h = 0; h < 2; h++) {
            wgmma_ss_n32<0, 1, H128, H64>(p[h], da + 4 * h, db + 128 * h, 0);
            wgmma_sa_n32<0, 1, H128, H64>(p[h], da + 4 * h + 2, db + 128 * h + 64);
          }
          wg_commit();
          if (e) bar_sync(NB_TOK, 256);
          wg_wait<0>();
        }
        TK(64 + 4 * turn);
        fence_regs(p[0]); fence_regs(p[1]);
        exps(0);
        float s2[4] = {0.f, 0.f, 0.f, 0.f};
        #pragma unroll
        for (int i = 0; i < 32; i++) s2[((i >> 1) & 1) + 2 * (i >> 4)] = fmaf(p[i >> 4][i & 15], p[i >> 4][i & 15], s2[((i >> 1) & 1) + 2 * (i >> 4)]);
        if (!__any_sync(~0u, !shifted & !((s2[0] * cc[0][0] * cc[0][0] < ARG_LIM2) & (s2[1] * cc[0][1] * cc[0][1] < ARG_LIM2) &
                                          (s2[2] * cc[1][0] * cc[1][0] < ARG_LIM2) & (s2[3] * cc[1][1] * cc[1][1] < ARG_LIM2)))) break;
        shifted = 1;
      }
      float ac[4][20];
      auto numer = [&](int h, const uint32_t (&f)[2][8]) {
        const uint32_t db = dlo(SB0 + OFF_KVZ, 128) + (half ? e : h) * 320;
        wg_fence();
        #pragma unroll
        for (int i = 0; i < 2; i++) {
          wgmma_rz_n40<1, dhi(256, 0)>(ac[2*h+i], f[i][0], f[i][1], f[i][2], f[i][3], db + i * 160);
          wgmma_ra_n40<1, dhi(256, 0)>(ac[2*h+i], f[i][4], f[i][5], f[i][6], f[i][7], db + (i * 160 + 80));
        }
        wg_commit();
      };
      const uint32_t oa = (16 * wp + g) * 128 + (((lane & 3) ^ g) << 4);
      auto finish = [&](int h) {
        const float* ap = ac[2 * h]; const float* am = ac[2 * h + 1];
        const float ip0 = rcp(ap[17]), im0 = rcp(am[17]), ip1 = rcp(ap[19]), im1 = rcp(am[19]);
        const float d0 = rcp(fmaf(ap[16], ip0, fmaf(am[16], im0, 1e-6f))), d1 = rcp(fmaf(ap[18], ip1, fmaf(am[18], im1, 1e-6f)));
        const float a0 = ip0 * d0, b0 = im0 * d0, a1 = ip1 * d1, b1 = im1 * d1;
        #pragma unroll
        for (int r = 0; r < 2; r++) {
          const float a = r ? a1 : a0, b = r ? b1 : b0;
          uint32_t w[4];
          #pragma unroll
          for (int k = 0; k < 4; k++) w[k] = pack_bf16(fmaf(ap[4*k+2*r], a, am[4*k+2*r] * b), fmaf(ap[4*k+2*r+1], a, am[4*k+2*r+1] * b));
          const uint32_t off = (oa ^ ((half ? rank : h) << 6)) + r * 1024;
          st128_rlx(reinterpret_cast<uint8_t*>(G->o + (m128 * 16 + (half ? 2 * (j & 6) + 2 * hh + 1 : 2 * j)) * 8192 + (half ? h : hh) * 4096) + off, w[0], w[1], w[2], w[3]);
          if (!half) sts128(sb + ao + off, w[0], w[1], w[2], w[3]);
        }
      };
      numer(0, ph);
      exps(1);
      if (wg == 0) bar_sync(NB_DN, 256);
      numer(1, ph);
      if (turn < 2) bar_arrive(NB_TOK + turn, 256);
      wg_wait<1>();
      TK(65 + 4 * turn);
      fence_regs(ac[0]); fence_regs(ac[1]);
      finish(0);
      wg_wait<0>();
      fence_regs(ac[2]); fence_regs(ac[3]);
      #pragma unroll
      for (int i = 0; i < 32; i++) asm volatile("mov.b32 %0, 0;" : "=f"(p[i >> 4][i & 15]));
      if (e == 2) project_r(3);
      finish(1);
      TK(66 + 4 * turn);
      if (!half) fence_async_smem();
      __syncwarp();
      if (lane == 0) mbar_arrive(sb + B_UO + 8 * e);
      wg_wait<0>();
      TK(67 + 4 * turn);
    }
    if (isq) cluster_arrive();
  }

  {
  int lane;
  asm volatile("mov.u32 %0, %%laneid;" : "=r"(lane));
  const int g = lane >> 2, q = lane & 3;
  if (wg < 2) {
    float h[64];
    {
      if (wg == 0) { TK(83); }
      #pragma unroll
      for (int i = 0; i < 32; i++) { h[2*i] = bf_lo(xr[i]); h[2*i+1] = bf_hi(xr[i]); }
      fence_regs(h);
      TK(80 + wg);
      const uint32_t emptyb = mapa(sb + B_EMPTY5, t & 1);
      uint32_t s = 1 + rank, ps = 0;
      mbar_wait2(sb + B_FULL5 + 8 * s, 1, sb + B_UO + 8 * wg, 0);
      if (wg == 0) { TSW(14); }
      #pragma unroll
      for (int i = 0; i < 16; i++) {
        if (wg == 1 && (i & 12) == TKW) { TK(84 + (i & 3)); }
        if (wg == 0) { TK(32 + i); }
        const uint32_t da = dlo(SB0, 16) + s * 2048 + wg * 512, db = dlo(SB0 + 16384, 8192) + s * 2048;
        wg_fence();
        #pragma unroll
        for (int k = 0; k < 4; k++) wgmma_sa_n128<0, 1, H128, H128>(h, da + k * 2, db + k * 128);
        wg_commit();
        const uint32_t ns = i ? (i + 2) % 6 : 2 - rank;
        const uint32_t b0 = sb + B_FULL5 + 8 * ns, p0 = (1 + (i + 2) / 6) & 1, b1 = sb + B_FULLA + 16 * ns + 8 * wg, p1 = ((i + 1) / 6) & 1;
        const bool here = i == 15 || mbar_test2(b0, p0, b1, p1);
        wg_wait<1>();
        if (!(((2 * REL + 1) >> i) & 1) && i < 14 && t < 2) mbar_arrive_remote(emptyb + 8 * ps, 1);
        if ((REL >> i) & 1) { wg_wait<0>(); if (t < 2) mbar_arrive_remote(emptyb + 8 * s, 1); }
        if (!here) mbar_wait2(b0, p0, b1, p1);
        ps = s; s = ns;
      }
    }
    cluster_arrive();
    float2 wr[16];
    #pragma unroll
    for (int i = 0; i < 16; i++) wr[i] = lds64f(sb + OFF_WR + 32 * i + 8 * q);
    const int r0 = 64 * wg + 16 * wp + g;
    float sum0, sum1, dot0, dot1, sq0, sq1;
    uint32_t redo = 0;
    asm volatile("" : "+r"(redo));
    #pragma unroll 1
    for (;;) {
    if (redo) {
      wg_wait<0>();
      const int r = r0;
      #pragma unroll 1
      for (int n = 0; n < 16; n++) {
        const uint32_t* xp = reinterpret_cast<const uint32_t*>(P.x + (size_t)(128 * m128 + r) * DM + 128 * j + 8 * n) + q;
        const uint32_t x0 = xp[0], x1 = xp[4 * DM];
        float d0 = bf_lo(x0), d1 = bf_hi(x0), d2 = bf_lo(x1), d3 = bf_hi(x1);
        #pragma unroll 1
        for (int ks = 0; ks < 64; ks++) {
          const int kb = ks >> 2, kk = 16 * (ks & 3);
          const bf16* op = G->o + (m128 * 16 + kb) * 8192 + r * 64 + 2 * q;
          const int o0 = ((kk >> 3) ^ g) << 3;
          const uint16_t* w = reinterpret_cast<const uint16_t*>(P.wo_p) + (size_t)(((kb & 1) ? 256 * (kb >> 2) + 32 * (kb & 2) + 32 + 4 * (kk & 32) : 64 * kb + 2 * (kk & 32)) + ((kk & 16) >> 2) + 8 * q) * DM + 128 * j + 8 * n + g;
          const uint32_t b0 = w[0] | (w[DM] << 16), b1 = w[2 * DM] | (w[3 * DM] << 16);
          uint32_t a0, a1, a2, a3, it = 0;
          do { a0 = ld32_rlx(op + o0); a1 = ld32_rlx(op + 512 + o0); a2 = ld32_rlx(op + (o0 ^ 8)); a3 = ld32_rlx(op + 512 + (o0 ^ 8)); }
          while (max(max(a0, a1), max(a2, a3)) == ~0u && ++it < POLL_LIMIT);
          __syncwarp();
          mma16816(d0, d1, d2, d3, a0, a1, a2, a3, b0, b1);
        }
        #pragma unroll
        for (int i = 0; i < 60; i++) h[i] = h[i + 4];
        h[60] = d0; h[61] = d1; h[62] = d2; h[63] = d3;
      }
    }
    wg_wait<0>();
    fence_regs(h);
    if (wg == 0) { TSW(16); }
    sum0 = 0.f, sum1 = 0.f, dot0 = 0.f, dot1 = 0.f, sq0 = 0.f, sq1 = 0.f;
    #pragma unroll
    for (int i = 0; i < 16; i++) {
      sum0 += h[4*i] + h[4*i+1]; sum1 += h[4*i+2] + h[4*i+3];
      sq0 = fmaf(h[4*i], h[4*i], fmaf(h[4*i+1], h[4*i+1], sq0)); sq1 = fmaf(h[4*i+2], h[4*i+2], fmaf(h[4*i+3], h[4*i+3], sq1));
      dot0 = fmaf(h[4*i], wr[i].x, fmaf(h[4*i+1], wr[i].y, dot0)); dot1 = fmaf(h[4*i+2], wr[i].x, fmaf(h[4*i+3], wr[i].y, dot1));
    }
    if (!__any_sync(~0u, !redo & (h[0] != h[0] | h[2] != h[2]))) break;
    redo = 1;
    }
    float4* const rs = &G->rstat[128 * m128 + r0];
    {
      const bool up = q & 2;
      float a = up ? sum1 : sum0, b = up ? sq1 : sq0, d = up ? dot1 : dot0;
      a += __shfl_xor_sync(~0u, up ? sum0 : sum1, 2); b += __shfl_xor_sync(~0u, up ? sq0 : sq1, 2); d += __shfl_xor_sync(~0u, up ? dot0 : dot1, 2);
      a += __shfl_xor_sync(~0u, a, 1); b += __shfl_xor_sync(~0u, b, 1); d += __shfl_xor_sync(~0u, d, 1);
      if ((q & 1) == 0) red_add_f32x4(rs + 4 * q, a, b, d, 1.f);
    }
    bar_arrive(NB_G2E, 384);
    if (wg == 0) { TSW(24); }
    bar_sync(NB_WG01, 256);
    uint32_t wa[8][4][4];
    const uint32_t wb = sb + 16384 * (((uint32_t)FF_SLOT >> (4 * warp)) & 15) + ((lane & 7) + ((lane >> 4) << 3)) * 64 + ((((lane >> 3) & 1) ^ ((lane >> 1) & 3)) << 4);
    auto getw = [&](int ks) {
      #pragma unroll
      for (int m = 0; m < 4; m++) ldsm4t((wb ^ ((m & 1) << 5)) + (m >> 1) * 8192 + ks * 1024, wa[ks][m][0], wa[ks][m][1], wa[ks][m][2], wa[ks][m][3]);
    };
    if (GPRE && f < NFFN_L) mbar_wait(sb + B_F + 8 * warp, 0);
    if (warp == 7) { TK(60); }
    #pragma unroll
    for (int ks = 0; ks < GPRE; ks++) getw(ks);
    float rstd[2], bm[2];
    uint32_t best;
    {
      const float2 swa = lds64f(sb + OFF_SUMWR), swb = lds64f(sb + OFF_SUMWR + 8);
      const float sw = (swa.x + swa.y) + (swb.x + swb.y);
      uint4 a[2]; uint32_t it = 0, key[2];
      do { a[0] = ld128_rlx(rs); a[1] = ld128_rlx(rs + 8); } while (__any_sync(~0u, (a[0].w & a[1].w) != 0x41000000u) && ++it < POLL_LIMIT);
      #pragma unroll
      for (int i = 0; i < 2; i++) {
        const float mean = __uint_as_float(a[i].x) * (1.f / DM);
        rstd[i] = rsqrtf(fmaxf(__uint_as_float(a[i].y) * (1.f / DM) - mean * mean, 0.f) + 1e-5f);
        bm[i] = -mean * rstd[i];
        const uint32_t rr = __float_as_uint(fmaf(__uint_as_float(a[i].z), rstd[i], sw * bm[i]));
        key[i] = ((rr ^ ((uint32_t)((int32_t)rr >> 31) | 0x80000000u)) & ~2047u) | (2047 - 128 * m128 - r0 - 8 * i);
      }
      asm volatile("redux.sync.max.u32 %0, %1, 0xffffffff;" : "=r"(best) : "r"(max(key[0], key[1])));
    }
    if (wg == 0) { TSW(17); }
    const int slot = m128 * 8 + warp, win = ~best & 15;
    if (lane < 4) st32_rlx(&G->key[(4 * j + lane) * 128 + slot], best);
    if ((win & 7) == g) {
      const bool up = win & 8;
      const float ra = up ? rstd[1] : rstd[0], rb = up ? bm[1] : bm[0];
      uint32_t x[16];
      #pragma unroll
      for (int i = 0; i < 16; i++) x[i] = pack_bf16(fmaf(up ? h[4*i+2] : h[4*i], ra, rb), fmaf(up ? h[4*i+3] : h[4*i+1], ra, rb));
      #pragma unroll
      for (int i = 0; i < 4; i++) st128_rlx(&G->cand[slot * DM + 64 * j + 16 * i + 4 * q], x[4*i], x[4*i+1], x[4*i+2], x[4*i+3]);
    }
    __syncwarp();
    if (wg == 0) { TSW(27); }
    {
      const float a0 = 1.f + rstd[0], b0 = bm[0], a1 = 1.f + rstd[1], b1 = bm[1];
      #pragma unroll
      for (int k = 0; k < 8; k++)
        stsm4(((sb + OFF_OUT + wg * 8192 + sa) ^ ((k & 3) << 5)) + (k >> 2) * 16384,
              pack_bf16(fmaf(h[8*k], a0, b0), fmaf(h[8*k+1], a0, b0)),     pack_bf16(fmaf(h[8*k+2], a1, b1), fmaf(h[8*k+3], a1, b1)),
              pack_bf16(fmaf(h[8*k+4], a0, b0), fmaf(h[8*k+5], a0, b0)),   pack_bf16(fmaf(h[8*k+6], a1, b1), fmaf(h[8*k+7], a1, b1)));
      sts32(sb + OFF_EXC + 4 * warp, 16 * warp + win);
      __syncwarp();
      if (lane == 0) mbar_arrive(sb + B_OUT + 8 * (warp >> 1));
      if (lane < 16) {
        const uint4 v = lds128(sb + OFF_OUT + (lane >> 3) * 16384 + (16 * warp + win) * 128 + (((lane & 7) ^ (win & 7)) << 4));
        st128_rlx(&G->cand[slot * DM + 512 + 64 * j + 4 * lane], v.x, v.y, v.z, v.w);
      }
    }
    if (wg == 0) { TSW(28); }
    {
      if (!GPRE && f < NFFN_L) mbar_wait(sb + B_F + 8 * warp, 0);
      #pragma unroll
      for (int ks = GPRE; ks < GRES; ks++) getw(ks);
      if (wg == 0) { TSW(15); }
      bar_sync(NB_XS, 384);
      if (wg == 0) { TSW(19); }
      uint4 xs[4];
      #pragma unroll
      for (int i = 0; i < 4; i++) xs[i] = lds128(sb + OFF_XSEL + 256 * warp + 64 * i + 16 * q);
      float d[4][4];
      #pragma unroll
      for (int ks = 0; ks < 8; ks++) {
        if (ks >= 1 && GRES + ks - 1 < 8) getw(GRES + ks - 1);
        #pragma unroll
        for (int m = 0; m < 4; m++) {
          if (ks == 0) { d[m][0] = 0.f; d[m][1] = 0.f; d[m][2] = 0.f; d[m][3] = 0.f; }
          mma16816(d[m][0], d[m][1], d[m][2], d[m][3], wa[ks][m][0], wa[ks][m][1], wa[ks][m][2], wa[ks][m][3],
                   (ks & 1) ? xs[ks >> 1].z : xs[ks >> 1].x, (ks & 1) ? xs[ks >> 1].w : xs[ks >> 1].y);
        }
      }
      if (q == 0) {
        #pragma unroll
        for (int m = 0; m < 8; m++) stsf(sb + OFF_GU + (8 * m + g) * 48 + 4 * warp, d[m >> 1][2 * (m & 1)]);
      }
      bar_arrive(NB_ACT, 384);
    }
    {
      float y0 = 0.f, y1 = 0.f, y2 = 0.f, y3 = 0.f;
      const uint32_t ky = __float_as_uint(ldsf(sb + OFF_KEY));
      const int kidx = 2047 - (ky & 2047);
      const float kr = __uint_as_float((ky & ~2047u) ^ ((ky >> 31) ? 0x80000000u : 0xfffff800u));
      const int col = 128 * (c >> 4) + 64 * (c & 1) + 32 * ((tid >> 2) & 1) + 16 * (tid & 1) + 8 * ((tid >> 1) & 1) + ((c >> 1) & 7);
      uint32_t it = 0, base = 0;
      if (tid < 8) {
        do { base = ld32_rlx(&G->cand[(kidx >> 4) * DM + 512 + (col >> 1)]); } while (base == ~0u && ++it < POLL_LIMIT);
      }
      if (tid < 2 * NFFN) {
        uint4 v;
        do { v = ld128_rlx(&G->ypart[(tid >> 1) * DM + 8 * c + 4 * (tid & 1)]); } while (v.w == ~0u && ++it < POLL_LIMIT);
        y0 = __uint_as_float(v.x); y1 = __uint_as_float(v.y); y2 = __uint_as_float(v.z); y3 = __uint_as_float(v.w);
      }
      __syncwarp();
      const bool b4 = lane & 16, b3 = lane & 8;
      const float u0 = (b4 ? y1 : y0) + __shfl_xor_sync(~0u, b4 ? y0 : y1, 16), u1 = (b4 ? y3 : y2) + __shfl_xor_sync(~0u, b4 ? y2 : y3, 16);
      float ys = (b3 ? u1 : u0) + __shfl_xor_sync(~0u, b3 ? u0 : u1, 8);
      ys += __shfl_xor_sync(~0u, ys, 4); ys += __shfl_xor_sync(~0u, ys, 2);
      if (!(lane & 6)) stsf(sb + OFF_ACT + ((4 * (lane & 1) + ((lane >> 3) & 1) * 2 + (lane >> 4)) * 8 + warp) * 4, ys);
      const float sg = __fdividef(1.f, 1.f + __expf(-kr));
      bar_sync(NB_WG01, 256);
      if (tid < 8) {
        const uint4 v0 = lds128(sb + OFF_ACT + tid * 32), v1 = lds128(sb + OFF_ACT + tid * 32 + 16);
        const float t8 = ((__uint_as_float(v0.x) + __uint_as_float(v0.y)) + (__uint_as_float(v0.z) + __uint_as_float(v0.w))) +
                         ((__uint_as_float(v1.x) + __uint_as_float(v1.y)) + __uint_as_float(v1.z));
        P.out_p[(size_t)kidx * DM + col] = __float2bfloat16(fmaf(t8, sg, (col & 1) ? bf_hi(base) : bf_lo(base)));
      }
      if (c == 0 && tid == 0) st32_rlx(&G->epoch, __float_as_uint(ldsf(sb + OFF_EP)));
      if (wg == 0) { TSW(22); TDUMP(); }
    }
  }
  if (wg == 2) {
    uint32_t wf[16][2][4];
    {
      const uint32_t wb = sb + OFF_S + 16384 * (wp & 1) + ((lane & 7) + ((lane >> 4) << 3)) * 128 + ((((lane >> 3) & 1) ^ (lane & 7)) << 4);
      if (f < NFFN_L) mbar_wait(sb + B_WD + 8 * wp, 0);
      if (wp == 0) { TK(61); }
      #pragma unroll
      for (int i = 0; i < 32; i++) ldsm4t((wb ^ (((i >> 1) & 3) << 5)) + (i >> 3) * 4096 + (i & 1) * 2048, wf[i >> 1][i & 1][0], wf[i >> 1][i & 1][1], wf[i >> 1][i & 1][2], wf[i >> 1][i & 1][3]);
      fence_async_smem();
      __syncwarp();
      if (lane == 0) mbar_arrive(sb + B_WC + 8 * wp);
      if (wp == 0) { TK(62); }
    }
    bar_sync(NB_G2E, 384);
    {
      uint32_t cur = 0;
      uint4 v;
      #pragma unroll 1
      for (uint32_t it = 0; it < POLL_LIMIT; it++) {
        const uint4 kx = ld128_rlx(&G->key[(c & 31) * 128 + 4 * lane]);
        v = ld128_rlx(&G->cand[((~cur >> 4) & 127) * DM + 4 * t]);
        uint32_t best;
        asm volatile("redux.sync.max.u32 %0, %1, 0xffffffff;" : "=r"(best) : "r"(max(max(kx.x, kx.y), max(kx.z, kx.w))));
        if (!__any_sync(~0u, min(min(kx.x, kx.y), min(kx.z, kx.w)) == 0 || v.w == ~0u) && best == cur) break;
        cur = best;
      }
      sts128(sb + OFF_XSEL + 16 * t, v.x, v.y, v.z, v.w);
      sts32(sb + OFF_KEY, cur);
      bar_arrive(NB_XS, 384);
      if (t == 0) mbar_arrive(sb + B_XS);
      TSW(18);
      bar_sync(NB_ACT, 384);
    }
    float gu[2];
    #pragma unroll
    for (int i = 0; i < 2; i++) {
      const uint4 v0 = lds128(sb + OFF_GU + (32 * i + lane) * 48), v1 = lds128(sb + OFF_GU + (32 * i + lane) * 48 + 16);
      gu[i] = ((__uint_as_float(v0.x) + __uint_as_float(v0.y)) + (__uint_as_float(v0.z) + __uint_as_float(v0.w))) +
              ((__uint_as_float(v1.x) + __uint_as_float(v1.y)) + (__uint_as_float(v1.z) + __uint_as_float(v1.w)));
    }
    const float act = gu[0] * gu[1] * rcp(1.f + ex2(-LOG2E * gu[0]));
    const uint32_t ap = pack_bf16(act, __shfl_down_sync(~0u, act, 1));
    uint32_t bf[4];
    #pragma unroll
    for (int i = 0; i < 4; i++) bf[i] = __shfl_sync(~0u, ap, 2 * q + 8 * i);
    TSW(20);
    float d[16][4];
    #pragma unroll
    for (int k = 0; k < 2; k++)
      #pragma unroll
      for (int i = 0; i < 16; i++) {
        if (k == 0) { d[i][0] = 0.f; d[i][1] = 0.f; d[i][2] = 0.f; d[i][3] = 0.f; }
        mma16816(d[i][0], d[i][1], d[i][2], d[i][3], wf[i][k][0], wf[i][k][1], wf[i][k][2], wf[i][k][3], bf[2*k], bf[2*k+1]);
      }
    #pragma unroll
    for (int a = 0; a < 2; a++) {
      float y[4];
      #pragma unroll
      for (int e = 0; e < 4; e++) {
        const int n = 8 * a + (e & 1);
        const float lo = (q & 1) ? d[n + 2][e & 2] : d[n][e & 2], hi = (q & 1) ? d[n + 6][e & 2] : d[n + 4][e & 2];
        y[e] = (q & 2) ? hi : lo;
      }
      if (f < NFFN) st128_rlx(&G->ypart[f * DM + 256 * wp + 128 * a + 4 * lane], __float_as_uint(y[0]), __float_as_uint(y[1]), __float_as_uint(y[2]), min(__float_as_uint(y[3]), ~1u));
    }
    TSW(21);
  }
  }
  cluster_wait();
}

typedef CUresult (*EncodeFn)(CUtensorMap*, CUtensorMapDataType, cuuint32_t, void*, const cuuint64_t*, const cuuint64_t*,
                             const cuuint32_t*, const cuuint32_t*, CUtensorMapInterleave, CUtensorMapSwizzle,
                             CUtensorMapL2promotion, CUtensorMapFloatOOBfill);

void make_map(EncodeFn enc, CUtensorMap* m, const void* p, int n, const cuuint64_t* dims, const cuuint64_t* str, const cuuint32_t* box,
              CUtensorMapSwizzle sw, CUtensorMapL2promotion promo) {
  cuuint32_t es[5] = {1, 1, 1, 1, 1};
  enc(m, CU_TENSOR_MAP_DATA_TYPE_BFLOAT16, n, const_cast<void*>(p), dims, str, box, es, CU_TENSOR_MAP_INTERLEAVE_NONE, sw, promo,
      CU_TENSOR_MAP_FLOAT_OOB_FILL_NONE);
}
void map2(EncodeFn enc, CUtensorMap* m, const void* p, uint64_t cols, uint64_t rows, uint32_t bc, uint32_t br, CUtensorMapSwizzle sw,
          CUtensorMapL2promotion promo) {
  const cuuint64_t dims[2] = {cols, rows}, str[1] = {cols * 2};
  const cuuint32_t box[2] = {bc, br};
  make_map(enc, m, p, 2, dims, str, box, sw, promo);
}
void map3(EncodeFn enc, CUtensorMap* m, const void* p, uint64_t cols, uint64_t rows, uint32_t br, uint32_t nb) {
  const cuuint64_t dims[3] = {64, rows, cols / 64}, str[2] = {cols * 2, 128};
  const cuuint32_t box[3] = {64, br, nb};
  make_map(enc, m, p, 3, dims, str, box, CU_TENSOR_MAP_SWIZZLE_128B, CU_TENSOR_MAP_L2_PROMOTION_L2_128B);
}

}

extern "C" void kernel_launch(void* const* d_in, const int* in_sizes, int n_in, void* d_out, int out_size) {
  (void)in_sizes; (void)n_in; (void)out_size;
  static EncodeFn enc = nullptr;
  static void* o_ptr = nullptr;
  if (!enc) {
    void* f = nullptr; cudaDriverEntryPointQueryResult qr;
    cudaGetDriverEntryPoint("cuTensorMapEncodeTiled", &f, cudaEnableDefault, &qr);
    enc = (EncodeFn)f;
    cudaGetSymbolAddress(&o_ptr, g_scr);
    cudaFuncSetAttribute(fused_kernel, cudaFuncAttributeMaxDynamicSharedMemorySize, SMEM_BYTES);
  }
  const bf16* x = (const bf16*)d_in[0];
  const bf16* wqkv = (const bf16*)d_in[1];
  const bf16* wphi = (const bf16*)d_in[2];
  const bf16* wo = (const bf16*)d_in[3];
  const bf16* wr = (const bf16*)d_in[5];
  const bf16* wgate = (const bf16*)d_in[6];
  const bf16* wup = (const bf16*)d_in[7];
  const bf16* wdown = (const bf16*)d_in[8];
  Params P;
  const CUtensorMapSwizzle S128 = CU_TENSOR_MAP_SWIZZLE_128B, S64 = CU_TENSOR_MAP_SWIZZLE_64B;
  const CUtensorMapL2promotion L128 = CU_TENSOR_MAP_L2_PROMOTION_L2_128B, L256 = CU_TENSOR_MAP_L2_PROMOTION_L2_256B,
                               L64 = CU_TENSOR_MAP_L2_PROMOTION_L2_64B;
  map2(enc, &P.x128, x, DM, SEQ, 64, 128, S128, L256);
  map2(enc, &P.x64, x, DM, SEQ, 64, 64, S128, L128);
  {
    const cuuint64_t dims[4] = {64, DM, 16, 3}, str[3] = {6 * DM, 128, 2 * DM};
    const cuuint32_t box[4] = {64, 64, 1, 2};
    make_map(enc, &P.wkv, wqkv, 4, dims, str, box, S128, L128);
  }
  map3(enc, &P.wq, wqkv, 3 * DM, DM, 64, 2);
  for (int i = 0; i < 2; i++) {
    const cuuint64_t dims[5] = {DM, (cuuint64_t)(DM - 94 - 64 * i), 4, 4, 2}, str[4] = {2 * DM, 16 * DM, 4 * DM, (cuuint64_t)(128 * DM) << i};
    const cuuint32_t box[5] = {64, 2, 4, 4, 2};
    make_map(enc, &P.wo[i], wo, 5, dims, str, box, S128, L128);
  }
  map3(enc, &P.wd, wdown, DM, FF, 32, 4);
  map2(enc, &P.wg, wgate, FF, DM, 32, 128, S64, L64);
  map2(enc, &P.wu, wup, FF, DM, 32, 128, S64, L64);
  map2(enc, &P.tg, wgate, FF, DM, 8, 16, CU_TENSOR_MAP_SWIZZLE_NONE, L128);
  map2(enc, &P.tu, wup, FF, DM, 8, 16, CU_TENSOR_MAP_SWIZZLE_NONE, L128);
  map2(enc, &P.td, wdown, 128, FF * 8, 8, 16, CU_TENSOR_MAP_SWIZZLE_NONE, L256);
  map2(enc, &P.phi, wphi, 32, 1024, 32, 32, S64, L64);
  P.x = x; P.wqkv = wqkv; P.wo_p = wo; P.wd_p = wdown; P.wg_p = wgate; P.wu_p = wup; P.wr = wr; P.out_p = (bf16*)d_out; P.g = (Scratch*)o_ptr;

  cudaLaunchConfig_t cfg = {};
  cfg.gridDim = dim3(128); cfg.blockDim = dim3(512); cfg.dynamicSmemBytes = SMEM_BYTES; cfg.stream = cudaStreamPerThread;
  cudaLaunchAttribute at[1];
  at[0].id = cudaLaunchAttributeClusterDimension; at[0].val.clusterDim.x = 2; at[0].val.clusterDim.y = 1; at[0].val.clusterDim.z = 1;
  cfg.attrs = at; cfg.numAttrs = 1;
  cudaLaunchKernelEx(&cfg, fused_kernel, P);
}
```

```cpp
#include <cuda_runtime.h>
#include <cuda.h>
#include <cuda_bf16.h>
#include <stdint.h>

namespace {

typedef __nv_bfloat16 bf16;

__device__ __forceinline__ uint32_t smem_u32(const void* p){ return (uint32_t)__cvta_generic_to_shared(p); }
__device__ __forceinline__ void mbar_init(uint32_t bar, uint32_t cnt){ asm volatile("mbarrier.init.shared::cta.b64 [%0], %1;"::"r"(bar),"r"(cnt):"memory"); }
__device__ __forceinline__ void mbar_expect_tx(uint32_t bar, uint32_t bytes){ asm volatile("mbarrier.arrive.expect_tx.shared::cta.b64 _, [%0], %1;"::"r"(bar),"r"(bytes):"memory"); }
__device__ __forceinline__ void mbar_arrive(uint32_t bar){ asm volatile("mbarrier.arrive.shared::cta.b64 _, [%0];"::"r"(bar):"memory"); }
__device__ __forceinline__ uint32_t mapa(uint32_t addr, uint32_t cta){ uint32_t r; asm volatile("mapa.shared::cluster.u32 %0, %1, %2;":"=r"(r):"r"(addr),"r"(cta)); return r; }
__device__ __forceinline__ void mbar_arrive_at(uint32_t bar, uint32_t cta, uint32_t cnt){
  asm volatile("{\n.reg .b32 ra;\nmapa.shared::cluster.u32 ra, %0, %1;\nmbarrier.arrive.shared::cluster.b64 _, [ra], %2;\n}\n"::"r"(bar),"r"(cta),"r"(cnt):"memory"); }
__device__ __forceinline__ void mbar_arrive_remote(uint32_t cluster_addr, uint32_t cnt){
  asm volatile("mbarrier.arrive.shared::cluster.b64 _, [%0], %1;"::"r"(cluster_addr),"r"(cnt):"memory"); }
__device__ __forceinline__ void mbar_wait(uint32_t bar, uint32_t parity){
  asm volatile("{\n.reg .pred p;\n.reg .u32 c;\nmov.u32 c, 0;\nLW:\nmbarrier.try_wait.parity.shared::cta.b64 p, [%0], %1;\n@p bra LD;\nadd.u32 c, c, 1;\nsetp.lt.u32 p, c, 2000000;\n@p bra LW;\ntrap;\nLD:\n}\n"::"r"(bar),"r"(parity):"memory"); }
__device__ __forceinline__ void mbar_wait2(uint32_t bar0, uint32_t par0, uint32_t bar1, uint32_t par1){
  asm volatile("{\n.reg .pred p, q;\n.reg .u32 c;\nmov.u32 c, 0;\nLW:\nmbarrier.try_wait.parity.shared::cta.b64 p, [%0], %1;\nmbarrier.try_wait.parity.shared::cta.b64 q, [%2], %3;\nand.pred p, p, q;\n@p bra LD;\nadd.u32 c, c, 1;\nsetp.lt.u32 p, c, 2000000;\n@p bra LW;\ntrap;\nLD:\n}\n"::"r"(bar0),"r"(par0),"r"(bar1),"r"(par1):"memory"); }
__device__ __forceinline__ bool mbar_test2(uint32_t bar0, uint32_t par0, uint32_t bar1, uint32_t par1){
  uint32_t r;
  asm volatile("{\n.reg .pred p, q;\nmbarrier.test_wait.parity.shared::cta.b64 p, [%1], %2;\nmbarrier.test_wait.parity.shared::cta.b64 q, [%3], %4;\nand.pred p, p, q;\nselp.u32 %0, 1, 0, p;\n}\n":"=r"(r):"r"(bar0),"r"(par0),"r"(bar1),"r"(par1):"memory");
  return r; }
__device__ __forceinline__ void tma_2d(uint32_t dst, const CUtensorMap* m, int c0, int c1, uint32_t bar){
  asm volatile("cp.async.bulk.tensor.2d.shared::cluster.global.mbarrier::complete_tx::bytes [%0], [%1, {%3, %4}], [%2];"::"r"(dst),"l"(m),"r"(bar),"r"(c0),"r"(c1):"memory"); }
__device__ __forceinline__ void tma_2d_mc(uint32_t dst, const CUtensorMap* m, int c0, int c1, uint32_t bar){
  asm volatile("cp.async.bulk.tensor.2d.shared::cluster.global.mbarrier::complete_tx::bytes.multicast::cluster [%0], [%1, {%3, %4}], [%2], %5;"::"r"(dst),"l"(m),"r"(bar),"r"(c0),"r"(c1),"h"((uint16_t)3):"memory"); }
__device__ __forceinline__ void tma_2d_mc_h(uint32_t dst, const CUtensorMap* m, int c0, int c1, uint32_t bar, uint64_t pol){
  asm volatile("cp.async.bulk.tensor.2d.shared::cluster.global.mbarrier::complete_tx::bytes.multicast::cluster.L2::cache_hint [%0], [%1, {%3, %4}], [%2], %5, %6;"::"r"(dst),"l"(m),"r"(bar),"r"(c0),"r"(c1),"h"((uint16_t)3),"l"(pol):"memory"); }
__device__ __forceinline__ void tma_4d(uint32_t dst, const CUtensorMap* m, int c0, int c1, int c2, int c3, uint32_t bar){
  asm volatile("cp.async.bulk.tensor.4d.shared::cluster.global.mbarrier::complete_tx::bytes [%0], [%1, {%3, %4, %5, %6}], [%2];"::"r"(dst),"l"(m),"r"(bar),"r"(c0),"r"(c1),"r"(c2),"r"(c3):"memory"); }
__device__ __forceinline__ uint64_t policy_evict_first(){ uint64_t p; asm volatile("createpolicy.fractional.L2::evict_first.b64 %0, 1.0;":"=l"(p)); return p; }
__device__ __forceinline__ uint64_t policy_evict_normal(){ uint64_t p; asm("createpolicy.fractional.L2::evict_normal.b64 %0, 1.0;":"=l"(p)); return p; }
__device__ __forceinline__ void tma_3d_h(uint32_t dst, const CUtensorMap* m, int c0, int c1, int c2, uint32_t bar, uint64_t pol){
  asm volatile("cp.async.bulk.tensor.3d.shared::cluster.global.mbarrier::complete_tx::bytes.L2::cache_hint [%0], [%1, {%3, %4, %5}], [%2], %6;"::"r"(dst),"l"(m),"r"(bar),"r"(c0),"r"(c1),"r"(c2),"l"(pol):"memory"); }
__device__ __forceinline__ void tma_4d_h(uint32_t dst, const CUtensorMap* m, int c0, int c1, int c2, int c3, uint32_t bar, uint64_t pol){
  asm volatile("cp.async.bulk.tensor.4d.shared::cluster.global.mbarrier::complete_tx::bytes.L2::cache_hint [%0], [%1, {%3, %4, %5, %6}], [%2], %7;"::"r"(dst),"l"(m),"r"(bar),"r"(c0),"r"(c1),"r"(c2),"r"(c3),"l"(pol):"memory"); }
__device__ __forceinline__ void red_add_f32x4(float4* p, float x, float y, float z, float w){ asm volatile("red.relaxed.gpu.global.add.v4.f32 [%0], {%1,%2,%3,%4};"::"l"(p),"f"(x),"f"(y),"f"(z),"f"(w):"memory"); }
__device__ __forceinline__ void tma_5d_h(uint32_t dst, const CUtensorMap* m, int c0, int c1, uint32_t bar, uint64_t pol){
  asm volatile("cp.async.bulk.tensor.5d.shared::cluster.global.mbarrier::complete_tx::bytes.L2::cache_hint [%0], [%1, {%3, %4, 0, 0, 0}], [%2], %5;"::"r"(dst),"l"(m),"r"(bar),"r"(c0),"r"(c1),"l"(pol):"memory"); }
__device__ __forceinline__ bool elect_one(){ uint32_t p; asm volatile("{\n.reg .pred P;\nelect.sync _|P, 0xffffffff;\nselp.b32 %0, 1, 0, P;\n}\n":"=r"(p)); return p; }
__device__ __forceinline__ void bulk_prefetch(const void* p, uint32_t bytes){
  asm volatile("cp.async.bulk.prefetch.L2.global [%0], %1;"::"l"(p),"r"(bytes):"memory"); }
__device__ __forceinline__ void bulk_s2peer(uint32_t dst_cluster, uint32_t src, uint32_t bytes, uint32_t bar_cluster){
  asm volatile("cp.async.bulk.shared::cluster.shared::cta.mbarrier::complete_tx::bytes [%0], [%1], %2, [%3];"::"r"(dst_cluster),"r"(src),"r"(bytes),"r"(bar_cluster):"memory"); }
__device__ __forceinline__ void bulk_g2s_mc(uint32_t dst, const void* src, uint32_t bytes, uint32_t bar, uint64_t pol){
  asm volatile("cp.async.bulk.shared::cluster.global.mbarrier::complete_tx::bytes.multicast::cluster.L2::cache_hint [%0], [%1], %2, [%3], %4, %5;"::"r"(dst),"l"(src),"r"(bytes),"r"(bar),"h"((uint16_t)3),"l"(pol):"memory"); }
__device__ __forceinline__ void prefetch_map(const CUtensorMap* m){ asm volatile("prefetch.tensormap [%0];"::"l"(m):"memory"); }
__device__ __forceinline__ void fence_async_smem(){ asm volatile("fence.proxy.async.shared::cta;":::"memory"); }
__device__ __forceinline__ void fence_acquire_gpu(){ asm volatile("fence.acquire.gpu;":::"memory"); }
__device__ __forceinline__ void fence_gpu(){ asm volatile("fence.acq_rel.gpu;":::"memory"); }
__device__ __forceinline__ void wg_fence(){ asm volatile("wgmma.fence.sync.aligned;":::"memory"); }
__device__ __forceinline__ void wg_commit(){ asm volatile("wgmma.commit_group.sync.aligned;":::"memory"); }
template<int N> __device__ __forceinline__ void wg_wait(){ asm volatile("wgmma.wait_group.sync.aligned %0;"::"n"(N):"memory"); }
template<int N> __device__ __forceinline__ void fence_regs(float (&d)[N]){
  #pragma unroll
  for(int i=0;i<N;i++) asm volatile("":"+f"(d[i])::"memory"); }
__device__ __forceinline__ void bar_sync(int id, int n){ asm volatile("bar.sync %0, %1;"::"r"(id),"r"(n):"memory"); }
__device__ __forceinline__ void bar_arrive(int id, int n){ asm volatile("bar.arrive %0, %1;"::"r"(id),"r"(n):"memory"); }
__device__ __forceinline__ void cluster_arrive(){ asm volatile("barrier.cluster.arrive.relaxed.aligned;":::"memory"); }
__device__ __forceinline__ void cluster_wait(){ asm volatile("barrier.cluster.wait.aligned;":::"memory"); }
__host__ __device__ constexpr uint32_t dlo(uint32_t addr, uint32_t lbo){ return (addr >> 4) | ((lbo >> 4) << 16); }
__host__ __device__ constexpr uint32_t dhi(uint32_t sbo, uint32_t sw){ return (sbo >> 4) | (sw << 30); }
constexpr uint32_t H128 = dhi(1024, 1), H64 = dhi(512, 2), H0 = dhi(128, 0);
__device__ __forceinline__ uint32_t pack_bf16(float lo, float hi){ uint32_t r; asm("cvt.rn.bf16x2.f32 %0, %1, %2;":"=r"(r):"f"(hi),"f"(lo)); return r; }
__device__ __forceinline__ float bf_lo(uint32_t v){ return __uint_as_float(v<<16); }
__device__ __forceinline__ float bf_hi(uint32_t v){ return __uint_as_float(v&0xffff0000u); }
__device__ __forceinline__ float ex2(float x){ float r; asm("ex2.approx.ftz.f32 %0, %1;":"=f"(r):"f"(x)); return r; }
__device__ __forceinline__ float rcp(float x){ float r; asm("rcp.approx.ftz.f32 %0, %1;":"=f"(r):"f"(x)); return r; }
__device__ __forceinline__ void stsm4(uint32_t addr, uint32_t a, uint32_t b, uint32_t c, uint32_t d){
  asm volatile("stmatrix.sync.aligned.m8n8.x4.shared.b16 [%0], {%1,%2,%3,%4};"::"r"(addr),"r"(a),"r"(b),"r"(c),"r"(d)); }
__device__ __forceinline__ void stsm2(uint32_t addr, uint32_t a, uint32_t b){
  asm volatile("stmatrix.sync.aligned.m8n8.x2.shared.b16 [%0], {%1,%2};"::"r"(addr),"r"(a),"r"(b)); }
__device__ __forceinline__ void mma16816(float& d0, float& d1, float& d2, float& d3, uint32_t a0, uint32_t a1, uint32_t a2, uint32_t a3, uint32_t b0, uint32_t b1){
  asm volatile("mma.sync.aligned.m16n8k16.row.col.f32.bf16.bf16.f32 {%0,%1,%2,%3}, {%4,%5,%6,%7}, {%8,%9}, {%0,%1,%2,%3};"
               : "+f"(d0), "+f"(d1), "+f"(d2), "+f"(d3) : "r"(a0), "r"(a1), "r"(a2), "r"(a3), "r"(b0), "r"(b1)); }
__device__ __forceinline__ void ldsm4(uint32_t addr, uint32_t& a, uint32_t& b, uint32_t& c, uint32_t& d){
  asm volatile("ldmatrix.sync.aligned.m8n8.x4.shared.b16 {%0,%1,%2,%3}, [%4];":"=r"(a),"=r"(b),"=r"(c),"=r"(d):"r"(addr):"memory"); }
__device__ __forceinline__ void ldsm4t(uint32_t addr, uint32_t& a, uint32_t& b, uint32_t& c, uint32_t& d){
  asm volatile("ldmatrix.sync.aligned.m8n8.x4.trans.shared.b16 {%0,%1,%2,%3}, [%4];":"=r"(a),"=r"(b),"=r"(c),"=r"(d):"r"(addr):"memory"); }
__device__ __forceinline__ void sts32(uint32_t a, uint32_t v){ asm volatile("st.shared.b32 [%0], %1;"::"r"(a),"r"(v):"memory"); }
__device__ __forceinline__ void stsf(uint32_t a, float v){ asm volatile("st.shared.f32 [%0], %1;"::"r"(a),"f"(v):"memory"); }
__device__ __forceinline__ void sts64(uint32_t a, uint32_t x, uint32_t y){ asm volatile("st.shared.v2.b32 [%0], {%1,%2};"::"r"(a),"r"(x),"r"(y):"memory"); }
__device__ __forceinline__ void sts128(uint32_t a, uint32_t x, uint32_t y, uint32_t z, uint32_t w){ asm volatile("st.shared.v4.b32 [%0], {%1,%2,%3,%4};"::"r"(a),"r"(x),"r"(y),"r"(z),"r"(w):"memory"); }
__device__ __forceinline__ float ldsf(uint32_t a){ float v; asm volatile("ld.shared.f32 %0, [%1];":"=f"(v):"r"(a):"memory"); return v; }
__device__ __forceinline__ float2 lds64f(uint32_t a){ float2 v; asm volatile("ld.shared.v2.f32 {%0,%1}, [%2];":"=f"(v.x),"=f"(v.y):"r"(a):"memory"); return v; }
__device__ __forceinline__ uint4 lds128(uint32_t a){ uint4 v; asm volatile("ld.shared.v4.u32 {%0,%1,%2,%3}, [%4];":"=r"(v.x),"=r"(v.y),"=r"(v.z),"=r"(v.w):"r"(a):"memory"); return v; }
__device__ __forceinline__ uint4 ld128_keep(const void* p){ uint4 v; asm volatile("ld.global.v4.u32 {%0,%1,%2,%3}, [%4];":"=r"(v.x),"=r"(v.y),"=r"(v.z),"=r"(v.w):"l"(p):"memory"); return v; }
__device__ __forceinline__ uint4 ld128_rlx(const void* p){ uint4 v; asm volatile("ld.relaxed.gpu.global.v4.u32 {%0,%1,%2,%3}, [%4];":"=r"(v.x),"=r"(v.y),"=r"(v.z),"=r"(v.w):"l"(p):"memory"); return v; }
__device__ __forceinline__ uint32_t ld32_rlx(const void* p){ uint32_t v; asm volatile("ld.relaxed.gpu.global.u32 %0, [%1];":"=r"(v):"l"(p):"memory"); return v; }
__device__ __forceinline__ void st128_rlx(void* p, uint32_t x, uint32_t y, uint32_t z, uint32_t w){ asm volatile("st.relaxed.gpu.global.v4.u32 [%0], {%1,%2,%3,%4};"::"l"(p),"r"(x),"r"(y),"r"(z),"r"(w):"memory"); }
__device__ __forceinline__ void st64_rlx(void* p, uint32_t x, uint32_t y){ asm volatile("st.relaxed.gpu.global.v2.u32 [%0], {%1,%2};"::"l"(p),"r"(x),"r"(y):"memory"); }
__device__ __forceinline__ void st32_rlx(void* p, uint32_t x){ asm volatile("st.relaxed.gpu.global.u32 [%0], %1;"::"l"(p),"r"(x):"memory"); }
__device__ __forceinline__ uint32_t tagw(float x, uint32_t t){ return (__float_as_uint(x) & ~3u) | t; }
__device__ __forceinline__ float untag(uint32_t w){ return __uint_as_float(w & ~3u); }

template<int TA, int TB, uint32_t HA, uint32_t HB> __device__ __forceinline__ void wgmma_ss_n128(float (&d)[64], uint32_t da, uint32_t db, int scale_d){
  asm volatile("{\n.reg .pred p;\n.reg .b64 a, b;\nsetp.ne.b32 p, %70, 0;\nmov.b64 a, {%64, %68};\nmov.b64 b, {%65, %69};\n"
  "wgmma.mma_async.sync.aligned.m64n128k16.f32.bf16.bf16 {%0, %1, %2, %3, %4, %5, %6, %7, %8, %9, %10, %11, %12, %13, %14, %15, %16, %17, %18, %19, %20, %21, %22, %23, %24, %25, %26, %27, %28, %29, %30, %31, %32, %33, %34, %35, %36, %37, %38, %39, %40, %41, %42, %43, %44, %45, %46, %47, %48, %49, %50, %51, %52, %53, %54, %55, %56, %57, %58, %59, %60, %61, %62, %63}, a, b, p, 1, 1, %66, %67;\n}\n"
  : "+f"(d[0]), "+f"(d[1]), "+f"(d[2]), "+f"(d[3]), "+f"(d[4]), "+f"(d[5]), "+f"(d[6]), "+f"(d[7]), "+f"(d[8]), "+f"(d[9]), "+f"(d[10]), "+f"(d[11]), "+f"(d[12]), "+f"(d[13]), "+f"(d[14]), "+f"(d[15]), "+f"(d[16]), "+f"(d[17]), "+f"(d[18]), "+f"(d[19]), "+f"(d[20]), "+f"(d[21]), "+f"(d[22]), "+f"(d[23]), "+f"(d[24]), "+f"(d[25]), "+f"(d[26]), "+f"(d[27]), "+f"(d[28]), "+f"(d[29]), "+f"(d[30]), "+f"(d[31]), "+f"(d[32]), "+f"(d[33]), "+f"(d[34]), "+f"(d[35]), "+f"(d[36]), "+f"(d[37]), "+f"(d[38]), "+f"(d[39]), "+f"(d[40]), "+f"(d[41]), "+f"(d[42]), "+f"(d[43]), "+f"(d[44]), "+f"(d[45]), "+f"(d[46]), "+f"(d[47]), "+f"(d[48]), "+f"(d[49]), "+f"(d[50]), "+f"(d[51]), "+f"(d[52]), "+f"(d[53]), "+f"(d[54]), "+f"(d[55]), "+f"(d[56]), "+f"(d[57]), "+f"(d[58]), "+f"(d[59]), "+f"(d[60]), "+f"(d[61]), "+f"(d[62]), "+f"(d[63])
  : "r"(da), "r"(db), "n"(TA), "n"(TB), "n"(HA), "n"(HB), "r"(scale_d));
}
template<int TA, int TB, uint32_t HA, uint32_t HB> __device__ __forceinline__ void wgmma_sa_n128(float (&d)[64], uint32_t da, uint32_t db){
  asm volatile("{\n.reg .pred p;\n.reg .b64 a, b;\nsetp.ne.b32 p, 1, 0;\nmov.b64 a, {%64, %68};\nmov.b64 b, {%65, %69};\n"
  "wgmma.mma_async.sync.aligned.m64n128k16.f32.bf16.bf16 {%0, %1, %2, %3, %4, %5, %6, %7, %8, %9, %10, %11, %12, %13, %14, %15, %16, %17, %18, %19, %20, %21, %22, %23, %24, %25, %26, %27, %28, %29, %30, %31, %32, %33, %34, %35, %36, %37, %38, %39, %40, %41, %42, %43, %44, %45, %46, %47, %48, %49, %50, %51, %52, %53, %54, %55, %56, %57, %58, %59, %60, %61, %62, %63}, a, b, p, 1, 1, %66, %67;\n}\n"
  : "+f"(d[0]), "+f"(d[1]), "+f"(d[2]), "+f"(d[3]), "+f"(d[4]), "+f"(d[5]), "+f"(d[6]), "+f"(d[7]), "+f"(d[8]), "+f"(d[9]), "+f"(d[10]), "+f"(d[11]), "+f"(d[12]), "+f"(d[13]), "+f"(d[14]), "+f"(d[15]), "+f"(d[16]), "+f"(d[17]), "+f"(d[18]), "+f"(d[19]), "+f"(d[20]), "+f"(d[21]), "+f"(d[22]), "+f"(d[23]), "+f"(d[24]), "+f"(d[25]), "+f"(d[26]), "+f"(d[27]), "+f"(d[28]), "+f"(d[29]), "+f"(d[30]), "+f"(d[31]), "+f"(d[32]), "+f"(d[33]), "+f"(d[34]), "+f"(d[35]), "+f"(d[36]), "+f"(d[37]), "+f"(d[38]), "+f"(d[39]), "+f"(d[40]), "+f"(d[41]), "+f"(d[42]), "+f"(d[43]), "+f"(d[44]), "+f"(d[45]), "+f"(d[46]), "+f"(d[47]), "+f"(d[48]), "+f"(d[49]), "+f"(d[50]), "+f"(d[51]), "+f"(d[52]), "+f"(d[53]), "+f"(d[54]), "+f"(d[55]), "+f"(d[56]), "+f"(d[57]), "+f"(d[58]), "+f"(d[59]), "+f"(d[60]), "+f"(d[61]), "+f"(d[62]), "+f"(d[63])
  : "r"(da), "r"(db), "n"(TA), "n"(TB), "n"(HA), "n"(HB));
}
template<int TA, int TB, uint32_t HA, uint32_t HB> __device__ __forceinline__ void wgmma_sa_n40(float (&d)[20], uint32_t da, uint32_t db){
  asm volatile("{\n.reg .pred p;\n.reg .b64 a, b;\nsetp.ne.b32 p, 1, 0;\nmov.b64 a, {%20, %24};\nmov.b64 b, {%21, %25};\n"
  "wgmma.mma_async.sync.aligned.m64n40k16.f32.bf16.bf16 {%0, %1, %2, %3, %4, %5, %6, %7, %8, %9, %10, %11, %12, %13, %14, %15, %16, %17, %18, %19}, a, b, p, 1, 1, %22, %23;\n}\n"
  : "+f"(d[0]), "+f"(d[1]), "+f"(d[2]), "+f"(d[3]), "+f"(d[4]), "+f"(d[5]), "+f"(d[6]), "+f"(d[7]), "+f"(d[8]), "+f"(d[9]), "+f"(d[10]), "+f"(d[11]), "+f"(d[12]), "+f"(d[13]), "+f"(d[14]), "+f"(d[15]), "+f"(d[16]), "+f"(d[17]), "+f"(d[18]), "+f"(d[19])
  : "r"(da), "r"(db), "n"(TA), "n"(TB), "n"(HA), "n"(HB));
}
template<int TA, int TB, uint32_t HA, uint32_t HB> __device__ __forceinline__ void wgmma_sz_n40(float (&d)[20], uint32_t da, uint32_t db){
  asm volatile("{\n.reg .pred p;\n.reg .b64 a, b;\nsetp.ne.b32 p, 0, 0;\nmov.b64 a, {%20, %24};\nmov.b64 b, {%21, %25};\n"
  "wgmma.mma_async.sync.aligned.m64n40k16.f32.bf16.bf16 {%0, %1, %2, %3, %4, %5, %6, %7, %8, %9, %10, %11, %12, %13, %14, %15, %16, %17, %18, %19}, a, b, p, 1, 1, %22, %23;\n}\n"
  : "=f"(d[0]), "=f"(d[1]), "=f"(d[2]), "=f"(d[3]), "=f"(d[4]), "=f"(d[5]), "=f"(d[6]), "=f"(d[7]), "=f"(d[8]), "=f"(d[9]), "=f"(d[10]), "=f"(d[11]), "=f"(d[12]), "=f"(d[13]), "=f"(d[14]), "=f"(d[15]), "=f"(d[16]), "=f"(d[17]), "=f"(d[18]), "=f"(d[19])
  : "r"(da), "r"(db), "n"(TA), "n"(TB), "n"(HA), "n"(HB));
}
template<int TA, int TB, uint32_t HA, uint32_t HB> __device__ __forceinline__ void wgmma_sa_n32(float (&d)[16], uint32_t da, uint32_t db){
  asm volatile("{\n.reg .pred p;\n.reg .b64 a, b;\nsetp.ne.b32 p, 1, 0;\nmov.b64 a, {%16, %20};\nmov.b64 b, {%17, %21};\n"
  "wgmma.mma_async.sync.aligned.m64n32k16.f32.bf16.bf16 {%0, %1, %2, %3, %4, %5, %6, %7, %8, %9, %10, %11, %12, %13, %14, %15}, a, b, p, 1, 1, %18, %19;\n}\n"
  : "+f"(d[0]), "+f"(d[1]), "+f"(d[2]), "+f"(d[3]), "+f"(d[4]), "+f"(d[5]), "+f"(d[6]), "+f"(d[7]), "+f"(d[8]), "+f"(d[9]), "+f"(d[10]), "+f"(d[11]), "+f"(d[12]), "+f"(d[13]), "+f"(d[14]), "+f"(d[15])
  : "r"(da), "r"(db), "n"(TA), "n"(TB), "n"(HA), "n"(HB));
}
template<int TA, int TB, uint32_t HA, uint32_t HB> __device__ __forceinline__ void wgmma_ss_n32(float (&d)[16], uint32_t da, uint32_t db, int scale_d){
  asm volatile("{\n.reg .pred p;\n.reg .b64 a, b;\nsetp.ne.b32 p, %22, 0;\nmov.b64 a, {%16, %20};\nmov.b64 b, {%17, %21};\n"
  "wgmma.mma_async.sync.aligned.m64n32k16.f32.bf16.bf16 {%0, %1, %2, %3, %4, %5, %6, %7, %8, %9, %10, %11, %12, %13, %14, %15}, a, b, p, 1, 1, %18, %19;\n}\n"
  : "+f"(d[0]), "+f"(d[1]), "+f"(d[2]), "+f"(d[3]), "+f"(d[4]), "+f"(d[5]), "+f"(d[6]), "+f"(d[7]), "+f"(d[8]), "+f"(d[9]), "+f"(d[10]), "+f"(d[11]), "+f"(d[12]), "+f"(d[13]), "+f"(d[14]), "+f"(d[15])
  : "r"(da), "r"(db), "n"(TA), "n"(TB), "n"(HA), "n"(HB), "r"(scale_d));
}
template<int TB, uint32_t HB> __device__ __forceinline__ void wgmma_ra_n32(float (&d)[16], uint32_t a0, uint32_t a1, uint32_t a2, uint32_t a3, uint32_t db){
  asm volatile("{\n.reg .pred p;\n.reg .b64 a, b;\nsetp.ne.b32 p, 1, 0;\nmov.b64 b, {%20, %22};\n"
  "wgmma.mma_async.sync.aligned.m64n32k16.f32.bf16.bf16 {%0, %1, %2, %3, %4, %5, %6, %7, %8, %9, %10, %11, %12, %13, %14, %15}, {%16,%17,%18,%19}, b, p, 1, 1, %21;\n}\n"
  : "+f"(d[0]), "+f"(d[1]), "+f"(d[2]), "+f"(d[3]), "+f"(d[4]), "+f"(d[5]), "+f"(d[6]), "+f"(d[7]), "+f"(d[8]), "+f"(d[9]), "+f"(d[10]), "+f"(d[11]), "+f"(d[12]), "+f"(d[13]), "+f"(d[14]), "+f"(d[15])
  : "r"(a0), "r"(a1), "r"(a2), "r"(a3), "r"(db), "n"(TB), "n"(HB));
}
template<int TB, uint32_t HB> __device__ __forceinline__ void wgmma_rs_n32(float (&d)[16], uint32_t a0, uint32_t a1, uint32_t a2, uint32_t a3, uint32_t db, int scale_d){
  asm volatile("{\n.reg .pred p;\n.reg .b64 a, b;\nsetp.ne.b32 p, %23, 0;\nmov.b64 b, {%20, %22};\n"
  "wgmma.mma_async.sync.aligned.m64n32k16.f32.bf16.bf16 {%0, %1, %2, %3, %4, %5, %6, %7, %8, %9, %10, %11, %12, %13, %14, %15}, {%16,%17,%18,%19}, b, p, 1, 1, %21;\n}\n"
  : "+f"(d[0]), "+f"(d[1]), "+f"(d[2]), "+f"(d[3]), "+f"(d[4]), "+f"(d[5]), "+f"(d[6]), "+f"(d[7]), "+f"(d[8]), "+f"(d[9]), "+f"(d[10]), "+f"(d[11]), "+f"(d[12]), "+f"(d[13]), "+f"(d[14]), "+f"(d[15])
  : "r"(a0), "r"(a1), "r"(a2), "r"(a3), "r"(db), "n"(TB), "n"(HB), "r"(scale_d));
}
template<int TB, uint32_t HB> __device__ __forceinline__ void wgmma_ra_n40(float (&d)[20], uint32_t a0, uint32_t a1, uint32_t a2, uint32_t a3, uint32_t db){
  asm volatile("{\n.reg .pred p;\n.reg .b64 a, b;\nsetp.ne.b32 p, 1, 0;\nmov.b64 b, {%24, %26};\n"
  "wgmma.mma_async.sync.aligned.m64n40k16.f32.bf16.bf16 {%0, %1, %2, %3, %4, %5, %6, %7, %8, %9, %10, %11, %12, %13, %14, %15, %16, %17, %18, %19}, {%20,%21,%22,%23}, b, p, 1, 1, %25;\n}\n"
  : "+f"(d[0]), "+f"(d[1]), "+f"(d[2]), "+f"(d[3]), "+f"(d[4]), "+f"(d[5]), "+f"(d[6]), "+f"(d[7]), "+f"(d[8]), "+f"(d[9]), "+f"(d[10]), "+f"(d[11]), "+f"(d[12]), "+f"(d[13]), "+f"(d[14]), "+f"(d[15]), "+f"(d[16]), "+f"(d[17]), "+f"(d[18]), "+f"(d[19])
  : "r"(a0), "r"(a1), "r"(a2), "r"(a3), "r"(db), "n"(TB), "n"(HB));
}
template<int TB, uint32_t HB> __device__ __forceinline__ void wgmma_rz_n40(float (&d)[20], uint32_t a0, uint32_t a1, uint32_t a2, uint32_t a3, uint32_t db){
  asm volatile("{\n.reg .pred p;\n.reg .b64 a, b;\nsetp.ne.b32 p, 0, 0;\nmov.b64 b, {%24, %26};\n"
  "wgmma.mma_async.sync.aligned.m64n40k16.f32.bf16.bf16 {%0, %1, %2, %3, %4, %5, %6, %7, %8, %9, %10, %11, %12, %13, %14, %15, %16, %17, %18, %19}, {%20,%21,%22,%23}, b, p, 1, 1, %25;\n}\n"
  : "=f"(d[0]), "=f"(d[1]), "=f"(d[2]), "=f"(d[3]), "=f"(d[4]), "=f"(d[5]), "=f"(d[6]), "=f"(d[7]), "=f"(d[8]), "=f"(d[9]), "=f"(d[10]), "=f"(d[11]), "=f"(d[12]), "=f"(d[13]), "=f"(d[14]), "=f"(d[15]), "=f"(d[16]), "=f"(d[17]), "=f"(d[18]), "=f"(d[19])
  : "r"(a0), "r"(a1), "r"(a2), "r"(a3), "r"(db), "n"(TB), "n"(HB));
}
template<int TB, uint32_t HB> __device__ __forceinline__ void wgmma_ra_n8(float (&d)[4], uint32_t a0, uint32_t a1, uint32_t a2, uint32_t a3, uint32_t db){
  asm volatile("{\n.reg .pred p;\n.reg .b64 a, b;\nsetp.ne.b32 p, 1, 0;\nmov.b64 b, {%8, %10};\n"
  "wgmma.mma_async.sync.aligned.m64n8k16.f32.bf16.bf16 {%0, %1, %2, %3}, {%4,%5,%6,%7}, b, p, 1, 1, %9;\n}\n"
  : "+f"(d[0]), "+f"(d[1]), "+f"(d[2]), "+f"(d[3])
  : "r"(a0), "r"(a1), "r"(a2), "r"(a3), "r"(db), "n"(TB), "n"(HB));
}
template<int TB, uint32_t HB> __device__ __forceinline__ void wgmma_rz_n8(float (&d)[4], uint32_t a0, uint32_t a1, uint32_t a2, uint32_t a3, uint32_t db){
  asm volatile("{\n.reg .pred p;\n.reg .b64 a, b;\nsetp.ne.b32 p, 0, 0;\nmov.b64 b, {%8, %10};\n"
  "wgmma.mma_async.sync.aligned.m64n8k16.f32.bf16.bf16 {%0, %1, %2, %3}, {%4,%5,%6,%7}, b, p, 1, 1, %9;\n}\n"
  : "=f"(d[0]), "=f"(d[1]), "=f"(d[2]), "=f"(d[3])
  : "r"(a0), "r"(a1), "r"(a2), "r"(a3), "r"(db), "n"(TB), "n"(HB));
}

constexpr int SEQ = 2048, DM = 1024, FF = 3584;
constexpr float LOG2E = 1.4426950408889634f;
constexpr uint32_t POLL_LIMIT = 1u << 22;
constexpr int NPRE = 2;
#define QW 0
#define RS_N 24
#define RS_D1 430
#define RS_D2 300
#define SKM 0x252
#define LAG 2
#define PF_T0 4000
#define PF_DT 900
#define NFFN_L NFFN
#define FF_DT 500
#define OUT_U 1
#define GRES 8
#define OUT_L 0
#define TMASK 0xffffff
#define PMASK 0xffffff
#define FF_T0 1
#define GPRE 0
#define REL 2
#define EFI 11
#define TKW 8
#define SLOT 0
#define SLOTW 48
#define FF_ORD 0x76543210ba98ull
#define KT 0
#define KK(id) do { if (KT) { TK(32 * wg + (id)); } } while (0)
#define OUT_NS 0
constexpr int NFFN = 112;

constexpr uint32_t SB0 = 1024;
constexpr uint32_t KV_STAGE = 49152, R5 = 32768;
constexpr uint32_t OFF_X = 163840, OFF_S = 196608, OFF_WPHI = OFF_S + 20480, OFF_M = 229376, SMEM_BYTES = 232448;
constexpr uint32_t OFF_RS256 = 212992, OFF_ONES = OFF_RS256 + 1024, OFF_WPHIK1 = OFF_ONES + 1024, OFF_KVZ = OFF_S;
constexpr uint32_t OFF_WPHIK = OFF_S, OFF_BXK = OFF_S + 2048, OFF_AXK = OFF_S + 4096;
constexpr uint32_t OFF_AXQ = OFF_WPHI, OFF_BXQ = OFF_WPHI + 2048, OFF_WPHIQ = OFF_WPHI + 4096;
constexpr uint32_t B_FULLKV = OFF_M  , B_EMPTYKV = OFF_M + 32  ;
constexpr uint32_t B_EMPTY5 = OFF_M + 64  , B_UO = B_EMPTY5 + 48  , B_RC = B_UO + 32  ;
constexpr uint32_t B_OUT = B_RC + 16  , B_AUX = B_OUT + 32, B_AUXQ = B_AUX + 8, B_RX = B_AUXQ + 8;
constexpr uint32_t B_FULL5 = B_RX + 8  , B_FULLA = B_FULL5 + 48  , B_F = B_FULLA + 96  , B_WD = B_F + 64  ;
constexpr uint32_t B_WC = B_WD + 32  , B_DR = B_WC + 32  , B_W = B_DR + 24, B_OS = B_W + 8, B_R = B_W + 16, B_KD = B_W + 24, B_XS = B_W + 32, B_T = B_W + 40, B_END = B_W + 48;
static_assert(B_END <= OFF_M + 576, "barriers");
constexpr uint32_t OFF_EXC = OFF_M + 576, OFF_SUMWR = OFF_M + 608, OFF_EP = OFF_M + 624, OFF_KEY = OFF_M + 628;
constexpr uint32_t OFF_RSQ = OFF_M + 640, OFF_TL = OFF_M + 1152, OFF_T = OFF_M + 1792, OFF_WR = OFF_M + 2048, OFF_SCR = OFF_M + 2432;
constexpr uint32_t OFF_XSEL = 2 * R5, OFF_ACT = OFF_XSEL + 2048, OFF_GU = OFF_XSEL + 4096, OFF_OUT = 3 * R5;
constexpr uint64_t FF_SLOT = 0xdcdc3210dcbaull;
constexpr int KVP = 6 * 128;

enum { NB_G2E = 1, NB_XS = 2, NB_WG01 = 3, NB_ACT = 4, NB_Q0 = 5  , NB_ST = 14, NB_DN = 9, NB_ZERO = 10, NB_PUB = 11, NB_TOK = 10  , NB_L0 = 12  , NB_WG2 = 7, NB_QGO = 15 };

struct Scratch {
  bf16     o[SEQ * DM];
  float4   rstat[SEQ];
  uint32_t key[32 * 128];
  uint32_t cand[128 * DM];
  uint32_t ypart[NFFN * DM];
  float4   kvacc[32 * KVP];
  uint2    stats[SEQ];
  uint32_t cskv[2 * DM];
  uint32_t csq[4 * DM];
  uint32_t oset[16 * 32];
  uint32_t epoch;
};
__device__ __align__(1024) Scratch g_scr;
#define TS(id)
#define TDUMP()
#define TS0_DECL()
#define TS0_READ()
#define TS0_WRITE()
#define TK(id)
#define TSW(id)

struct Params {
  CUtensorMap x128, x64, wkv, wq, wo[2], wd, wg, wu, phi, tg, tu, td;
  const bf16 *x, *wqkv, *wo_p, *wg_p, *wu_p, *wd_p, *wr;
  bf16* out_p;
  Scratch* g;
  uint32_t zero;
};

constexpr float EXP_LIM = 1.1529215e18f, ARG_LIM2 = 3600.f;
__device__ __forceinline__ void dual_exp2(const float (&p)[2][16], uint32_t (&ph)[4][8]) {
  #pragma unroll
  for (int h = 0; h < 2; h++)
    #pragma unroll
    for (int k = 0; k < 8; k++) { ph[2*h][k] = pack_bf16(ex2(p[h][2*k]), ex2(p[h][2*k+1])); ph[2*h+1][k] = pack_bf16(ex2(-p[h][2*k]), ex2(-p[h][2*k+1])); }
}
__device__ __forceinline__ void row_extremes(const float (&p)[16], const float (&c)[2], float (&m)[4]) {
  m[0] = m[2] = p[0]; m[1] = m[3] = p[2];
  #pragma unroll
  for (int i = 0; i < 16; i++) { m[(i >> 1) & 1] = fmaxf(m[(i >> 1) & 1], p[i]); m[2 + ((i >> 1) & 1)] = fminf(m[2 + ((i >> 1) & 1)], p[i]); }
  #pragma unroll
  for (int o = 1; o < 4; o <<= 1) {
    m[0] = fmaxf(m[0], __shfl_xor_sync(~0u, m[0], o)); m[1] = fmaxf(m[1], __shfl_xor_sync(~0u, m[1], o));
    m[2] = fminf(m[2], __shfl_xor_sync(~0u, m[2], o)); m[3] = fminf(m[3], __shfl_xor_sync(~0u, m[3], o));
  }
  m[0] *= -c[0]; m[1] *= -c[1]; m[2] *= c[0]; m[3] *= c[1];
}
__device__ __forceinline__ void dual_exp2_shifted(const float (&p)[2][16], uint32_t (&ph)[4][8]) {
  #pragma unroll
  for (int h = 0; h < 2; h++) {
    const float one[2] = {1.f, 1.f};
    float m[4];
    row_extremes(p[h], one, m);
    #pragma unroll
    for (int k = 0; k < 8; k++) {
      ph[2*h][k] = pack_bf16(ex2(p[h][2*k] + m[k & 1]), ex2(p[h][2*k+1] + m[k & 1]));
      ph[2*h+1][k] = pack_bf16(ex2(m[2 + (k & 1)] - p[h][2*k]), ex2(m[2 + (k & 1)] - p[h][2*k+1]));
    }
  }
}
__device__ __forceinline__ void row_sums(float (&s)[4][4], const uint32_t (&ph)[4][8], uint32_t ones) {
  #pragma unroll
  for (int i = 0; i < 4; i++) wgmma_rz_n8<0, H0>(s[i], ph[i][0], ph[i][1], ph[i][2], ph[i][3], ones);
  #pragma unroll
  for (int i = 0; i < 4; i++) wgmma_ra_n8<0, H0>(s[i], ph[i][4], ph[i][5], ph[i][6], ph[i][7], ones);
}
__device__ __forceinline__ uint32_t mul_bf16x2(uint32_t a, uint32_t b) { uint32_t r; asm("mul.rn.bf16x2 %0, %1, %2;" : "=r"(r) : "r"(a), "r"(b)); return r; }
__device__ __forceinline__ void normalize(uint32_t (&ph)[4][8], const float (&s)[4][4]) {
  #pragma unroll
  for (int i = 0; i < 4; i++) {
    const float i0 = rcp(s[i][0]), i1 = rcp(s[i][2]);
    const uint32_t n0 = pack_bf16(i0, i0), n1 = pack_bf16(i1, i1);
    #pragma unroll
    for (int k = 0; k < 4; k++) { ph[i][2*k] = mul_bf16x2(ph[i][2*k], n0); ph[i][2*k+1] = mul_bf16x2(ph[i][2*k+1], n1); }
  }
}
__device__ __forceinline__ void split_bf16(float a, float b, uint32_t& hi, uint32_t& lo) { hi = pack_bf16(a, b); lo = pack_bf16(a - bf_lo(hi), b - bf_hi(hi)); }
__device__ __forceinline__ void put_colsums(uint32_t base, int lane, float a, float b, float c, float d) {
  uint32_t h0, l0, h1, l1;
  split_bf16(a, b, h0, l0); split_bf16(c, d, h1, l1);
  const uint32_t ad = base + (lane >> 1) * 128 + (lane & 1) * 8;
  sts64(ad, h0, h1); sts64(ad + 16, l0, l1); sts64(ad + 32, h0, h1); sts64(ad + 48, l0, l1);
  sts128(base + (lane >> 1) * 128 + 64 + (lane & 1) * 32, 0, 0, 0, 0); sts128(base + (lane >> 1) * 128 + 80 + (lane & 1) * 32, 0, 0, 0, 0);
}
__device__ __forceinline__ float reduce8(const float (&v)[8], int lane) {
  const bool b4 = lane & 16, b3 = lane & 8, b2 = lane & 4;
  float a[4], b[2];
  #pragma unroll
  for (int i = 0; i < 4; i++) a[i] = (b4 ? v[4 + i] : v[i]) + __shfl_xor_sync(~0u, b4 ? v[i] : v[4 + i], 16);
  #pragma unroll
  for (int i = 0; i < 2; i++) b[i] = (b3 ? a[2 + i] : a[i]) + __shfl_xor_sync(~0u, b3 ? a[i] : a[2 + i], 8);
  return (b2 ? b[1] : b[0]) + __shfl_xor_sync(~0u, b2 ? b[0] : b[1], 4);
}
__device__ __forceinline__ bool tag_bad(uint4 v, uint32_t tg) { return (((v.x ^ tg) | (v.y ^ tg) | (v.z ^ tg) | (v.w ^ tg)) & 3) != 0; }

__global__ void __launch_bounds__(512, 1) fused_kernel(const __grid_constant__ Params P) {
  extern __shared__ __align__(1024) uint8_t smem_raw[];
  const uint32_t sb = smem_u32(smem_raw);
  const int tid = threadIdx.x, lane = tid & 31;
  const int warp = __shfl_sync(~0u, tid >> 5, 0), wg = warp >> 2, wp = warp & 3;
  const int cp = blockIdx.x >> 1, cu = cp - 36, cd = (cu * 37) >> 8;
  const int gi = cp < 4 ? 0 : cu < 0 ? (cp - 4) & 7 : 1 + cu - 7 * cd, gx = cp < 4 ? 4 + cp : cu < 0 ? (cp - 4) >> 3 : 4 + cd;
  const int rank = blockIdx.x & 1, c = 64 * (gi & 1) + 8 * gx + (gi & 6) + rank;
  const int f = 16 * ((gi + 7) & 7) + 2 * gx + rank;
  const int m256 = c >> 4, nkv = c & 15, m128 = c >> 3, j = c & 7;
  const int ha = 4 * (nkv >> 1) + (nkv & 1);

  Scratch* const G = P.g;
  if ((sb & 0x3ffff) != SB0) asm volatile("trap;");

  TS0_DECL();
  if (warp == 12) {
    const bool el = elect_one();
    TS0_READ();
    if (el) {
      #pragma unroll
      for (int i = 0; i < 4; i++) mbar_init(sb + B_FULLKV + 8 * i, 1);
      asm volatile("fence.mbarrier_init.release.cluster;" ::: "memory");
      fence_async_smem();
      #pragma unroll
      for (int s = 0; s < NPRE; s++) {
        const uint32_t st = sb + s * KV_STAGE, fb = sb + B_FULLKV + 8 * s;
        mbar_expect_tx(fb, KV_STAGE);
        tma_4d(st + 32768, &P.wkv, 0, 64 * s, nkv, 1, fb);
        tma_2d(st, &P.x128, 64 * s, 256 * m256, fb);
        tma_2d(st + 16384, &P.x128, 64 * s, 256 * m256 + 128, fb);
      }
    }
  } else if (tid == 0) {
    #pragma unroll
    for (uint32_t b = B_EMPTYKV; b < B_END; b += 8) mbar_init(sb + b, b < B_EMPTY5 ? 12 : b < B_OUT ? 4 : b < B_RX ? 2 : b == B_RX ? 8 : 1);
    mbar_arrive(sb + B_FULL5 + 40);
    asm volatile("fence.mbarrier_init.release.cluster;" ::: "memory");
    fence_async_smem();
  }
  __syncthreads();
  cluster_arrive();

  if (wg == 3) {
    asm volatile("setmaxnreg.dec.sync.aligned.u32 32;");
    cluster_wait();
    const bool el = elect_one();
    const uint64_t ef = policy_evict_first(), en = policy_evict_normal();
    auto fetch_o = [&](const int t0, uint32_t so, uint32_t par) {
      const int sh = t0 & 1;
      uint32_t ready = 0;
      const bf16* base = G->o + (m128 * 16 + t0) * 8192 + rank * 4096;
      const bf16* hint = base + (lane & 3) * 1024 + 966 + (((j & 6) + ((lane >> 2) & ~sh)) & 7) * 16384 + 8 * sh * (~lane & 4);
      #pragma unroll 1
      for (int i = 2 - 2 * sh; i < 8; i += 1 + sh) {
        uint32_t it = 0;
        while ((~ready >> (4 * i) & (15 + 240 * sh)) && ++it < POLL_LIMIT) ready = __ballot_sync(~0u, ld32_rlx(hint) != ~0u);
        mbar_wait(sb + B_EMPTY5 + so, par);
        if (el) {
          bulk_g2s_mc(sb + so * 4096 + rank * 8192, base + (((j & 6) + i) & 7) * 16384, 8192, sb + B_FULLA + 2 * so + 8 * rank, ef);
          if (i == 2 - 2 * sh) TS(t0 == 0 ? (rank ? 4 : 12) : t0 == 3 ? (rank ? 31 : 10) : (rank ? 9 : 13));
        }
        so += 8;
        if (so == 48) { so = 0; par ^= 1; }
      }
    };
    if (wp == 0) {
      {
        #pragma unroll 1
        for (int kb = NPRE; kb < 16; kb++) {
          const uint32_t st = sb + (kb & 3) * KV_STAGE, fb = sb + B_FULLKV + 8 * (kb & 3);
          mbar_wait(fb + (B_EMPTYKV - B_FULLKV), ~(kb >> 2) & 1);
          if (el) {
            mbar_expect_tx(fb, KV_STAGE);
            tma_2d_mc(st + rank * 16384, &P.x128, 64 * kb, 256 * m256 + 128 * rank, fb);
            tma_4d_h(st + 32768, &P.wkv, 0, 64 * kb, nkv, 1, fb, ef);
          }
        }
        TS0_WRITE();
        uint64_t ord = 0xf3120edcba987654ull;
        uint32_t so = 0, par = 1;
        #pragma unroll 1
        for (int i = 0; i < 16; i++) {
          const uint32_t st = sb + so * 4096, fb = sb + B_FULL5 + so;
          const int k0 = (64 * (uint32_t)ord + 128 * (j & 6)) & 960;
          mbar_wait(i < 5 ? sb + B_EMPTYKV + so - (i > 1 ? 8 : 0) : fb + (B_EMPTY5 - B_FULL5), par);
          if (el) {
            mbar_expect_tx(fb, R5);
            tma_2d_mc_h(st + rank * 8192, &P.x64, k0, 128 * m128 + 64 * rank, fb, i >= EFI ? ef : en);
            tma_3d_h(st + 16384, &P.wq, 0, k0, 2 * j, fb, ef);
          }
          ord >>= 4; so += 8;
          if (so == 40) { so = 0; par ^= 1; }
        }
        #pragma unroll 1
        for (int i = 0; i < 19; i++) {
          const uint32_t fb = sb + B_FULL5 + so, fa = sb + B_FULLA + 2 * so, na = i == rank ? 0 : 8192;
          if (i == 1) { mbar_wait2(sb + B_FULL5 + 16, 0, sb + B_FULL5 + 24, 0); mbar_wait(sb + B_FULL5 + 32, 0); if (el) mbar_arrive(sb + B_R); }
          mbar_wait(fb + (B_EMPTY5 - B_FULL5), par);
          if (SLOT) { while (((uint32_t)clock() & (uint32_t)(SLOT - 1)) >= SLOTW) {} }
          if (el) {
            if (i < 16) {
              mbar_expect_tx(fb, 16384);
              const int row = i < 8 ? 128 * (((j & 6) + i) & 7) : 256 * (((j >> 1) + i) & 3) + 32 + 16 * (i & 4);
              tma_5d_h(sb + so * 4096 + 16384, &P.wo[i >> 3], 128 * j, row, fb, ef);
              tma_5d_h(sb + so * 4096 + 24576, &P.wo[i >> 3], 128 * j + 64, row, fb, ef);
              mbar_expect_tx(fa, na); mbar_expect_tx(fa + 8, na);
            } else mbar_arrive(sb + B_DR + 8 * (i - 16));
          }
          so += 8;
          if (so == 48) { so = 0; par ^= 1; }
        }
      }
    } else if (wp == 3) {
      const uint32_t t_start = (uint32_t)clock();
      if (el) {
        mbar_expect_tx(sb + B_W, 12288);
        #pragma unroll 1
        for (int i = 0; i < 6; i++) tma_2d(sb + (i == 0 ? OFF_WPHIK : i == 1 ? OFF_WPHIK1 : OFF_WPHIQ + 2048 * (i - 2)), &P.phi, 0, 32 * (i < 2 ? 2 * nkv + i : 4 * j + 2 * (i & 1) + ((i - 2) >> 1)), sb + B_W);
        prefetch_map(&P.x64); prefetch_map(&P.wq); prefetch_map(&P.wo[0]); prefetch_map(&P.wo[1]);
        prefetch_map(&P.wd); prefetch_map(&P.wg); prefetch_map(&P.wu);
      }
      #pragma unroll 1
      for (int i = 0; i < 8; i++) {
        st128_rlx(&G->cand[(m128 * 8 + i) * DM + (lane >> 4) * 512 + 64 * j + 4 * (lane & 15)], ~0u, ~0u, ~0u, ~0u);
        if (f < NFFN) st128_rlx(&G->ypart[f * DM + 128 * i + 4 * lane], ~0u, ~0u, ~0u, ~0u);
      }
      if (lane < 16) st128_rlx(&G->rstat[16 * c + lane], 0, 0, 0, 0);
      if (lane < 8) st128_rlx(&G->key[(4 * j + (lane >> 1)) * 128 + m128 * 8 + 4 * (lane & 1)], 0, 0, 0, 0);
      if (c < 32) {
        #pragma unroll 1
        for (int i = lane; i < KVP; i += 32) st128_rlx(&G->kvacc[(ha + 2 * m256) * KVP + i], 0, 0, 0, 0);
      }
      fence_gpu();
      bar_arrive(NB_ZERO, 160);
      if (el) {
        #pragma unroll 1
        for (int i = 0; i < 30; i++) {
          while ((uint32_t)clock() - t_start < (uint32_t)(PF_T0 + PF_DT * i)) __nanosleep(64);
          if (i < 4) { bulk_prefetch(P.wqkv + (size_t)(256 * i + c) * (3 * DM), 2048); bulk_prefetch(P.wqkv + (size_t)(256 * i + 128 + c) * (3 * DM), 2048); }
          else if (i < 6) bulk_prefetch(P.wo_p + (size_t)c * 8192 + (i - 4) * 4096, 8192);
          else if ((TMASK >> (i - 6)) & 1) {
            const int k = i - 6;
            if (f < NFFN) {
              if (k < 16) {
                #pragma unroll 1
                for (int e = 0; e < 4; e++) tma_2d(sb + OFF_T, rank ? &P.tu : &P.tg, 32 * (f & ~1), 64 * k + 16 * e, sb + B_T);
              } else { tma_2d(sb + OFF_T, &P.td, 0, 256 * f + 32 * (k - 16), sb + B_T); tma_2d(sb + OFF_T, &P.td, 0, 256 * f + 32 * (k - 16) + 16, sb + B_T); }
            }
          }
          else if (!((PMASK >> (i - 6)) & 1)) {}
          else if (i < 22) bulk_prefetch(((i & 1) ? P.wu_p : P.wg_p) + (size_t)((i - 6) >> 1) * 458752 + c * 3584, 7168);
          else bulk_prefetch(P.wd_p + (size_t)(i - 22) * 458752 + c * 3584, 7168);
        }
      }
      __syncwarp();
      mbar_wait2(sb + B_OS, 0, sb + B_RX, 0);
      #pragma unroll 1
      for (int t0 = 0; t0 < 4; t0 += 3) fetch_o(t0, t0 ? 8 : 24, 0);
    } else {
      const int half = wp - 1;
      const uint32_t ep1 = ld32_rlx(&G->epoch) + 1, tg = ep1 & 3;
      {
        uint32_t it = 0;
        sts128(sb + OFF_ONES + half * 512 + lane * 16, 0x3f803f80u, 0x3f803f80u, 0x3f803f80u, 0x3f803f80u);
        auto reset_o = [&](int i0, int i1, uint32_t dt) {
          uint32_t t0 = (uint32_t)clock();
          #pragma unroll 1
          for (int i = i0; i < i1; i++) {
            st128_rlx(G->o + (m128 * 16 + 2 * j + half) * 8192 + 256 * i + 8 * lane, ~0u, ~0u, ~0u, ~0u);
            while ((uint32_t)clock() - t0 < dt) __nanosleep(40);
            t0 += dt;
          }
        };
        mbar_wait(sb + B_W, 0);
        reset_o(0, RS_N, RS_D1);
        bar_sync(NB_PUB, 192);
        const uint4* src = reinterpret_cast<const uint4*>(&G->stats[256 * m256 + 128 * half]) + lane;
        const uint4* srk = reinterpret_cast<const uint4*>(&G->cskv[128 * nkv]) + lane;
        uint4 v0, v1, vk;
        it = 0;
        do { v0 = ld128_rlx(src); v1 = ld128_rlx(src + 32); vk = ld128_rlx(srk); }
        while ((tag_bad(v0, tg) || tag_bad(v1, tg) || tag_bad(vk, tg)) && ++it < POLL_LIMIT);
        fence_acquire_gpu();
        if (half) put_colsums(sb + OFF_BXK, lane, untag(vk.x), untag(vk.y), untag(vk.z), untag(vk.w));
        #pragma unroll
        for (int i = 0; i < 2; i++) {
          const uint4 v = i ? v1 : v0;
          uint32_t hi, lo;
          split_bf16(-0.5f * untag(v.x), -0.5f * untag(v.z), hi, lo);
          const uint32_t h0 = __byte_perm(hi, hi, 0x1010), h1 = __byte_perm(hi, hi, 0x3232), l0 = __byte_perm(lo, lo, 0x1010), l1 = __byte_perm(lo, lo, 0x3232);
          const uint32_t a = sb + OFF_AXK + half * 2048 + i * 1024 + lane * 32;
          sts128(a, h0, l0, 0, 0); sts128(a + 16, h1, l1, 0, 0);
          sts64(sb + OFF_RS256 + half * 512 + i * 256 + lane * 8, v.y & ~3u, v.w & ~3u);
          if (half == (m128 & 1)) {
            const uint32_t aq = sb + OFF_AXQ + i * 1024 + lane * 32;
            sts128(aq, h0, l0, 0, 0); sts128(aq + 16, h1, l1, 0, 0);
            sts64(sb + OFF_RSQ + i * 256 + lane * 8, v.y & ~3u, v.w & ~3u);
          }
        }
        fence_async_smem();
        __syncwarp();
        if (el) { sts32(sb + OFF_EP, ep1); mbar_arrive(sb + B_AUX); if (!half) TS(1); }
        reset_o(RS_N, 32, RS_D2);
        fence_gpu();
        __syncwarp();
        if (el) { st32_rlx(&G->oset[m128 * 32 + 2 * j + half], ep1); if (half) mbar_arrive(sb + B_AUXQ); }
        if (!half) {
          const uint4* src = reinterpret_cast<const uint4*>(&G->csq[128 * j]) + lane;
          uint4 v0, v1, v2, v3;
          do { v0 = ld128_rlx(src); v1 = ld128_rlx(src + DM / 4); v2 = ld128_rlx(src + DM / 2); v3 = ld128_rlx(src + 3 * DM / 4); }
          while ((tag_bad(v0, tg) || tag_bad(v1, tg) || tag_bad(v2, tg) || tag_bad(v3, tg)) && ++it < POLL_LIMIT);
          put_colsums(sb + OFF_BXQ, lane, (untag(v0.x) + untag(v1.x)) + (untag(v2.x) + untag(v3.x)), (untag(v0.y) + untag(v1.y)) + (untag(v2.y) + untag(v3.y)),
                      (untag(v0.z) + untag(v1.z)) + (untag(v2.z) + untag(v3.z)), (untag(v0.w) + untag(v1.w)) + (untag(v2.w) + untag(v3.w)));
          fence_async_smem();
          __syncwarp();
          if (el) mbar_arrive(sb + B_AUXQ);
        }
      }
      if (half == 0) {
        for (uint32_t it = 0; __any_sync(~0u, ld32_rlx(&G->oset[m128 * 32 + (lane & 15)]) != ep1) && it < POLL_LIMIT; it++) {}
        fence_acquire_gpu();
        if (el) mbar_arrive(sb + B_OS);
      }
      if (!half) {
        #pragma unroll 1
        for (int hh = 0; hh < 2; hh++) {
          const uint32_t src = sb + (1 + rank) * R5 + hh * 8192, fa = sb + B_FULLA + 16 + 16 * rank + 8 * hh;
          mbar_wait(fa, 0);
          mbar_wait(sb + B_UO + 8 * hh, 0);
          if (el) bulk_s2peer(mapa(src, rank ^ 1), src, 8192, mapa(fa, rank ^ 1));
        }
        fetch_o(1, 24, 1);
      }
      else if (f < NFFN_L) {
        mbar_wait2(sb + B_UO, 0, sb + B_UO + 8, 0);
        mbar_wait(sb + B_UO + 24, 0);
        uint32_t t0 = (uint32_t)clock();
        while ((uint32_t)clock() - t0 < (uint32_t)FF_T0) __nanosleep(32);
        t0 -= FF_DT;
        #pragma unroll 1
        for (int i = 0; i < 12; i++) {
          const int e = (FF_ORD >> (4 * i)) & 15;
          const uint32_t dst = sb + 16384 * ((FF_SLOT >> (4 * e)) & 15), fb = sb + B_F + 8 * e;
          if (i >= 2) mbar_wait(sb + B_WC + 8 * ((0x100066553244ull >> (4 * e)) & 15), 0);
          while ((uint32_t)clock() - t0 < (uint32_t)FF_DT) __nanosleep(32);
          t0 = (uint32_t)clock();
          TK(48 + i);
          if (el) {
            mbar_expect_tx(fb, 16384);
            if (e >= 8) tma_3d_h(dst, &P.wd, 0, 32 * f, 4 * e - 32, fb, ef);
            else { tma_2d(dst, &P.wg, 32 * f, 128 * e, fb); tma_2d(dst + 8192, &P.wu, 32 * f, 128 * e, fb); }
          }
        }
      }
      __syncwarp();
    }
    {
      const int ch = lane & 15, rb = 32 * wp + (lane >> 4);
      const uint32_t src = sb + OFF_OUT + (ch >> 3) * 16384;
      bf16* dst = P.out_p + (size_t)(128 * m128) * DM + 128 * j + 8 * ch;
      __syncwarp();
      mbar_wait(sb + B_OUT + 8 * wp, 0);
      const float2 ex = lds64f(sb + OFF_EXC + 8 * wp);
      if (OUT_L) mbar_wait(sb + B_XS, 0);
      #pragma unroll 1
      for (int i = 0; i < 32; i += 2 * OUT_U) {
        uint4 v[OUT_U];
        #pragma unroll
        for (int e = 0; e < OUT_U; e++) { const int r = rb + i + 2 * e; v[e] = lds128(src + r * 128 + (((ch ^ r) & 7) << 4)); }
        #pragma unroll
        for (int e = 0; e < OUT_U; e++) { const int r = rb + i + 2 * e; if (r != __float_as_int(i < 16 ? ex.x : ex.y)) *reinterpret_cast<uint4*>(dst + r * DM) = v[e]; }
        if (OUT_NS) __nanosleep(OUT_NS);
      }
      if (wp == 0) { TK(63); }
      mbar_wait(sb + B_XS, 0);
      const int row = 2047 - (__float_as_uint(ldsf(sb + OFF_KEY)) & 2047) - 128 * m128, r = __float_as_int(lane < 16 ? ex.x : ex.y);
      if (r != row) *reinterpret_cast<uint4*>(dst + r * DM) = lds128(src + r * 128 + (((ch ^ r) & 7) << 4));
    }
    __syncwarp();
    cluster_arrive(); cluster_wait();
    return;
  }

  asm volatile("setmaxnreg.inc.sync.aligned.u32 160;");
  cluster_wait();
  const int t = tid & 127, g = lane >> 2;
  const uint32_t sa = (16 * wp + (lane & 15)) * 128 + (((lane >> 4) ^ (lane & 7)) << 4);

  if (wg == 2) {
    float s[2] = {0.f, 0.f}, s2[2] = {0.f, 0.f}, ck[8] = {0.f, 0.f, 0.f, 0.f, 0.f, 0.f, 0.f, 0.f}, cs[8] = {0.f, 0.f, 0.f, 0.f, 0.f, 0.f, 0.f, 0.f};
    const uint32_t ebr = mapa(sb + B_EMPTYKV, lane & 1), tg = (ld32_rlx(&G->epoch) + 1) & 3;
    auto addx = [&](const uint4 v) {
      const uint32_t w[4] = {v.x, v.y, v.z, v.w};
      #pragma unroll
      for (int e = 0; e < 4; e++) { const float a = bf_lo(w[e]), d = bf_hi(w[e]); s[0] += a; s[1] += d; s2[0] = fmaf(a, a, s2[0]); s2[1] = fmaf(d, d, s2[1]); }
    };
    auto addc = [&](const uint4 v, float (&o)[8]) {
      o[0] += bf_lo(v.x); o[1] += bf_hi(v.x); o[2] += bf_lo(v.y); o[3] += bf_hi(v.y); o[4] += bf_lo(v.z); o[5] += bf_hi(v.z); o[6] += bf_lo(v.w); o[7] += bf_hi(v.w);
    };
    {
      const uint32_t ra = (16 * nkv + (t >> 3)) * 128 + (t & 7) * 16;
      const uint32_t ca = 32768 + (m256 >> 2) * 8192 + (t >> 1) * 128 + (((2 * (m256 & 3) + (t & 1)) ^ ((t >> 1) & 7)) << 4);
      const bf16* gx = P.x + (size_t)(256 * m256 + 16 * nkv + (t >> 3)) * DM + 640 + (t & 7) * 8;
      const bf16* gw = P.wqkv + (size_t)(640 + (t >> 1)) * (3 * DM) + (1 + (m256 >> 2)) * DM + 64 * nkv + 16 * (m256 & 3) + 8 * (t & 1);
      uint4 u[4];
      #pragma unroll
      for (int e = 0; e < 4; e++) u[e] = make_uint4(0, 0, 0, 0);
      #pragma unroll 1
      for (int kb = 0; kb < 10; kb++) {
        const uint32_t st = sb + (kb & 3) * KV_STAGE;
        mbar_wait(sb + B_FULLKV + 8 * (kb & 3), (kb >> 2) & 1);
        const uint4 x0 = lds128(st + ra), w0 = lds128(st + ca);
        addx(x0); addc(w0, ck);
        __syncwarp();
        if (lane < 2) mbar_arrive_remote(ebr + 8 * (kb & 3), 1);
        if ((SKM >> kb) & 1) {
          addx(u[0]); addx(u[1]); addc(u[2], ck); addc(u[3], ck);
          if (kb < 9) {
            u[0] = ld128_keep(gx); u[1] = ld128_keep(gx + 64); u[2] = ld128_keep(gw); u[3] = ld128_keep(gw + 64 * 3 * DM);
            gx += 128; gw += 128 * 3 * DM;
          }
        }
      }
    }
    TK(82);
    const uint32_t scr = sb + OFF_SCR + 128;
    float sx = s[0] + s[1], sq = s2[0] + s2[1];
    #pragma unroll
    for (int o = 1; o < 8; o <<= 1) { sx += __shfl_xor_sync(~0u, sx, o); sq += __shfl_xor_sync(~0u, sq, o); }
    float v = reduce8(ck, lane);
    v += __shfl_xor_sync(~0u, v, 2);
    if (!(lane & 2)) stsf(scr + (wp * 16 + 8 * (lane & 1) + (lane >> 2)) * 4, v);

    bar_sync(NB_ZERO, 160);
    if ((lane & 7) == 0) {
      const float mean = sx * (1.f / DM);
      st64_rlx(&G->stats[256 * m256 + 16 * nkv + (t >> 3)], tagw(mean, tg), tagw(rsqrtf(fmaxf(sq * (1.f / DM) - mean * mean, 0.f) + 1e-5f), tg));
    }
    if (wp == 1 && lane < 16) {
      const uint32_t a = scr + lane * 4;
      st32_rlx(&G->cskv[128 * nkv + 16 * m256 + lane], tagw((ldsf(a) + ldsf(a + 64)) + (ldsf(a + 128) + ldsf(a + 192)), tg));
    }
    __syncwarp();
    bar_arrive(NB_PUB, 192);
    TSW(23);
    const uint4 wv = ld128_keep(P.wr + t * 8);
    #pragma unroll 1
    for (int i = 0; i < 2; i++) {
      const bf16* gq = P.wqkv + (size_t)(256 * (c >> 5) + 128 * i + (t >> 2)) * (3 * DM) + 32 * (c & 31) + 8 * (t & 3);
      const uint4 u0 = ld128_keep(gq), u1 = ld128_keep(gq + 32 * 3 * DM), u2 = ld128_keep(gq + 64 * 3 * DM), u3 = ld128_keep(gq + 96 * 3 * DM);
      addc(u0, cs); addc(u1, cs); addc(u2, cs); addc(u3, cs);
    }
    float sw = (bf_lo(wv.x) + bf_hi(wv.x)) + (bf_lo(wv.y) + bf_hi(wv.y)) + (bf_lo(wv.z) + bf_hi(wv.z)) + (bf_lo(wv.w) + bf_hi(wv.w));
    #pragma unroll
    for (int o = 16; o; o >>= 1) sw += __shfl_xor_sync(~0u, sw, o);
    if (lane == 0) stsf(sb + OFF_SUMWR + wp * 4, sw);
    if ((t >> 4) == j) {
      const uint32_t a = sb + OFF_WR + (t & 15) * 32;
      sts128(a, wv.x << 16, wv.x & 0xffff0000u, wv.y << 16, wv.y & 0xffff0000u);
      sts128(a + 16, wv.z << 16, wv.z & 0xffff0000u, wv.w << 16, wv.w & 0xffff0000u);
    }
    v = reduce8(cs, lane);
    bar_sync(NB_WG2, 128);
    stsf(scr + (wp * 32 + 8 * (lane & 3) + (lane >> 2)) * 4, v);
    bar_sync(NB_WG2, 128);
    if (wp == 0) {
      const uint32_t a = scr + lane * 4;
      st32_rlx(&G->csq[(c >> 5) * DM + 32 * (c & 31) + lane], tagw((ldsf(a) + ldsf(a + 128)) + (ldsf(a + 256) + ldsf(a + 384)), tg));
    }
  }

  uint32_t xr[32];
  {
    const bool isq = wg == 2;
    float acc[2][64];
    {
      const uint32_t emptyb = mapa(sb + (isq ? B_EMPTY5 : B_EMPTYKV), t & 1);
      if (!isq) {
        mbar_wait(sb + B_FULLKV, 0);
        if (wg == 0) { TSW(2); }
        #pragma unroll 1
        for (int kb = 0; kb < 16; kb++) {
          if (!KT && wg == 0) { TK(kb); }
          const uint32_t da = dlo(SB0, 16) + wg * 1024 + (kb & 3) * (KV_STAGE >> 4), db = dlo(SB0 + 32768, 8192) + (kb & 3) * (KV_STAGE >> 4);
          wg_fence();
          #pragma unroll
          for (int k = 0; k < 4; k++) {
            wgmma_ss_n128<0, 1, H128, H128>(acc[0], da + 2 * k, db + 128 * k, k > 0 || kb != 0);
            wgmma_ss_n128<0, 1, H128, H128>(acc[1], da + 512 + 2 * k, db + 128 * k, k > 0 || kb != 0);
          }
          wg_commit();
          wg_wait<1>();
          if (kb > 0 && t < 2) mbar_arrive_remote(emptyb + 8 * ((kb - 1) & 3), kb > 10 ? 3 : 1);
          if (kb < 15) mbar_wait(sb + B_FULLKV + 8 * ((kb + 1) & 3), ((kb + 1) >> 2) & 1);
          if (kb == 15 - LAG && wg == 1) bar_sync(NB_WG01, 256);
        }
        bar_arrive(wg ? NB_QGO : NB_WG01, 256);
      } else {
        uint32_t so = 0, po = 0, par = 0;
        mbar_wait(sb + B_FULL5, 0);
        bar_sync(NB_QGO, 256);
        TSW(11);
        #pragma unroll 1
        for (int kb = 0; kb < 16; kb++) {
          TK(16 + kb);
          const uint32_t da = dlo(SB0, 16) + so * 256, db = dlo(SB0 + 16384, 8192) + so * 256;
          #pragma unroll
          for (int k = 0; k < 4; k++) {
            wg_fence();
            wgmma_ss_n128<0, 1, H128, H128>(acc[0], da + 2 * k, db + 128 * k, k > 0 || kb != 0);
            wgmma_ss_n128<0, 1, H128, H128>(acc[1], da + 512 + 2 * k, db + 128 * k, k > 0 || kb != 0);
            wg_commit();
            if (k == 1 && kb > 0 && t < 2) mbar_arrive_remote(emptyb + po, 2);
            if (k == 3) {
              po = so; so += 8;
              if (so == 40) { so = 0; par ^= 1; }
              if (kb < 15) mbar_wait(sb + B_FULL5 + so, par);
            }
            if ((QW >> k) & 1) wg_wait<2>(); else wg_wait<1>();
          }
        }
        mbar_wait(sb + B_AUXQ, 0);
      }
      mbar_wait(sb + B_AUX, 0);
      const uint32_t xa = dlo(SB0, 0) + (isq ? OFF_AXQ >> 4 : (OFF_AXK >> 4) + wg * 128), xb = dlo(SB0, 0) + (isq ? OFF_BXQ >> 4 : OFF_BXK >> 4);
      wg_fence();
      wgmma_sa_n128<0, 1, H0, H0>(acc[0], xa, xb);
      wgmma_sa_n128<0, 1, H0, H0>(acc[1], xa + 64, xb);
      wg_commit();
      if (isq) mbar_wait(sb + B_RC, 0);
      wg_wait<0>();
      if (t < 2) mbar_arrive_remote(emptyb + (isq ? 0 : 24), isq ? 2 : 3);
      if (wg != 1) { TSW(wg ? 8 : 3); }
      fence_regs(acc[0]); fence_regs(acc[1]);
    }
    if (isq) {
      #pragma unroll
      for (int i = 0; i < 2; i++) {
        const uint32_t ta = sb + (1 + rank) * R5 + sa + i * 8192;
        if (i == 1) mbar_wait(sb + B_RC + 8, 0);
        #pragma unroll
        for (int k = 0; k < 4; k++) {
          const float* a = &acc[i][32 * (k >> 1) + 8 * (k & 1)];
          stsm4(ta ^ (k << 5), pack_bf16(a[0], a[1]), pack_bf16(a[2], a[3]), pack_bf16(a[4], a[5]), pack_bf16(a[6], a[7]));
        }
        fence_async_smem();
        bar_arrive(NB_Q0 + i, 256);
      }
      #pragma unroll
      for (int i = 0; i < 32; i++) { const float* a = &acc[(i >> 3) & 1][16 + 32 * (i >> 4) + 2 * (i & 7)]; xr[i] = pack_bf16(a[0], a[1]); }
      TSW(26);
    } else {
      const uint32_t stg = sb + OFF_X + (1 - wg) * 24576;
      const uint32_t va = stg + 16384 + (16 * wp + (lane & 15)) * 64 + (((lane >> 4) ^ ((lane >> 1) & 3)) << 4);
      const uint32_t ra = sb + OFF_RS256 + (128 * wg + 16 * wp + g) * 4;
      const float rs[4] = {ldsf(ra), ldsf(ra + 32), ldsf(ra + 256), ldsf(ra + 288)};
      float p[2][16];
      uint32_t vf[16], kf[2][16];
      auto project = [&](const uint32_t (&f)[16], uint32_t db) {
        wg_fence();
        #pragma unroll
        for (int i = 0; i < 2; i++) {
          wgmma_rs_n32<1, H64>(p[i], f[8*i], f[8*i+1], f[8*i+2], f[8*i+3], db, 0);
          wgmma_ra_n32<1, H64>(p[i], f[8*i+4], f[8*i+5], f[8*i+6], f[8*i+7], db + 64);
        }
        wg_commit();
      };
      auto fold = [&](uint32_t (&f)[16], int col, float sc) {
        #pragma unroll
        for (int i = 0; i < 16; i++) {
          const float r = rs[2 * (i >> 3) + (i & 1)] * sc;
          f[i] = pack_bf16(acc[i >> 3][col + 2 * (i & 7)] * r, acc[i >> 3][col + 2 * (i & 7) + 1] * r);
          asm volatile("" : "+r"(f[i]));
        }
      };
      auto put_v = [&](const uint32_t (&f)[16]) {
        #pragma unroll
        for (int k = 0; k < 4; k++) stsm4((va ^ ((k & 1) << 5)) + (k >> 1) * 4096, f[4*k], f[4*k+1], f[4*k+2], f[4*k+3]);
      };
      KK(0);
      fold(vf, 48, 1.f);
      mbar_wait(sb + B_W, 0);
      fold(kf[0], 0, LOG2E);
      #pragma unroll
      for (int i = 0; i < 32; i++) p[i >> 4][i & 15] = acc[i >> 4][i & 15];
      project(kf[0], dlo(SB0 + OFF_WPHIK, 16));
      mbar_wait(sb + B_W, 0);
      KK(1);
      {
        uint32_t v0[16];
        fold(kf[1], 16, LOG2E);
        fold(v0, 32, 1.f);
        if (wg == 1) bar_sync(NB_DN, 256);
        put_v(v0);
      }
      wg_wait<0>();
      fence_regs(p[0]); fence_regs(p[1]);
      if (wg == 1) bar_arrive(NB_WG01, 256);
      KK(2);
      #pragma unroll 1
      for (int h = 0; h < 2; h++) {
        uint32_t ph[4][8];
        float rsum[4][4];
        dual_exp2(p, ph);
        wg_fence();
        row_sums(rsum, ph, dlo(SB0 + OFF_ONES, 128));
        wg_commit();
        KK(3 + 6 * h);
        if (wg == 0 && h == 0) { bar_arrive(NB_DN, 256); bar_sync(NB_WG01, 256); }
        if (h == 1) {
          if (wg == 1) bar_sync(NB_DN, 256);
          put_v(vf);
        }
        wg_wait<0>();
        KK(4 + 6 * h);
        #pragma unroll
        for (int i = 0; i < 4; i++) fence_regs(rsum[i]);
        if (__builtin_expect(__any_sync(~0u, !((rsum[0][0] + rsum[0][2]) + (rsum[1][0] + rsum[1][2]) + (rsum[2][0] + rsum[2][2]) + (rsum[3][0] + rsum[3][2]) < EXP_LIM)), 0)) {
          dual_exp2_shifted(p, ph);
          #pragma unroll
          for (int i = 0; i < 8; i++) {
            const uint32_t* f = &ph[i >> 1][i & 1];
            float a = (bf_lo(f[0]) + bf_hi(f[0])) + (bf_lo(f[2]) + bf_hi(f[2])) + (bf_lo(f[4]) + bf_hi(f[4])) + (bf_lo(f[6]) + bf_hi(f[6]));
            a += __shfl_xor_sync(~0u, a, 1);
            rsum[i >> 1][2 * (i & 1)] = a + __shfl_xor_sync(~0u, a, 2);
          }
        }
        if (h == 0) project(kf[1], dlo(SB0 + OFF_WPHIK1, 16));
        normalize(ph, rsum);
        #pragma unroll
        for (int i = 0; i < 8; i++) {
          const uint32_t* f = &ph[i >> 1][4 * (i & 1)];
          stsm4(((stg + sa) ^ ((i & 3) << 5)) + (i >> 2) * 8192, f[0], f[1], f[2], f[3]);
        }
        KK(5 + 6 * h);
        fence_async_smem();
        KK(6 + 6 * h);
        if (wg != h) { KK(7 + 6 * h); }
        if (wg == h) {
          float kv[20];
          #pragma unroll
          for (int w = 0; w < 2; w++) {
            const uint32_t da = dlo(SB0 + OFF_X, 16) + (h ^ w ^ 1) * 1536, db = dlo(SB0 + OFF_X + 16384, OFF_ONES - OFF_X - 16384) - (h ^ w ^ 1) * (1536 * 65535);
            if (w) bar_sync(NB_ST, 256); else bar_sync(NB_L0 + h, 128);
            wg_fence();
            #pragma unroll
            for (int k = 0; k < 8; k++) {
              if (k == 0 && w == 0) wgmma_sz_n40<1, 1, H128, H64>(kv, da, db);
              else wgmma_sa_n40<1, 1, H128, H64>(kv, da + k * 128, db - k * (64 * 65535));
            }
            wg_commit();
          }
          float4* dst = &G->kvacc[(ha + 2 * h) * KVP + t];
          wg_wait<0>();
          fence_regs(kv);
          KK(7 + 6 * h);
          if (h == 0) bar_arrive(NB_DN, 256); else if (t < 2) { mbar_arrive_at(sb + B_EMPTY5 + 40, t, 2); if (t == 0) mbar_arrive(sb + B_KD); }
          kv[17] = kv[18];
          #pragma unroll
          for (int i = 0; i < 6; i++) red_add_f32x4(dst + 128 * i, kv[3*i], kv[3*i+1], kv[3*i+2], 1.f);
          TSW(29 + h);
        } else bar_arrive(NB_ST, 256);
        wg_wait<0>();
        KK(8 + 6 * h);
        fence_regs(p[0]); fence_regs(p[1]);
      }
      #pragma unroll
      for (int i = 0; i < 32; i++) asm volatile("mov.b32 %0, 0;" : "=r"(xr[i]));
    }
    float p[2][16];
    #pragma unroll
    for (int i = 0; i < 32; i++) asm volatile("mov.b32 %0, 0;" : "=f"(p[i >> 4][i & 15]));
    auto project_r = [&](int w) {
      wg_fence();
      #pragma unroll
      for (int h = 0; h < 2; h++) {
        wgmma_rs_n32<1, H64>(p[h], xr[8*h], xr[8*h+1], xr[8*h+2], xr[8*h+3], dlo(SB0 + OFF_WPHIQ, 16) + 128 * w, 0);
        wgmma_ra_n32<1, H64>(p[h], xr[8*h+4], xr[8*h+5], xr[8*h+6], xr[8*h+7], dlo(SB0 + OFF_WPHIQ, 16) + 128 * w + 64);
      }
      wg_commit();
    };
    {
      const uint4* src = reinterpret_cast<const uint4*>(&G->kvacc[(4 * j + wg) * KVP + t]);
      uint4 v[12];
      #pragma unroll
      for (int i = 0; i < 12; i++) v[i] = i < 6 || isq ? ld128_rlx(src + 128 * i) : make_uint4(0, 0, 0, 0x41000000u);
      if (isq) {
        project_r(2);
        wg_wait<0>();
        #pragma unroll
        for (int i = 0; i < 16; i++) xr[i] = xr[16 + i];
      } else {
        mbar_wait(sb + B_R, 0);
        #pragma unroll
        for (int k = 0; k < 8; k++) ldsm4(((sb + (1 + rank) * R5 + wg * 8192 + sa) ^ ((k & 3) << 5)) + (k >> 2) * 2 * R5, xr[4*k], xr[4*k+1], xr[4*k+2], xr[4*k+3]);
        const uint32_t one = (((xr[0] | xr[4] | xr[8]) | (xr[12] | xr[16] | xr[20]) | (xr[24] | xr[28])) & P.zero) + 1;
        if (lane == 0) { mbar_arrive_at(sb + B_RC + 8 * wg, rank, one); mbar_arrive_at(sb + B_RX, wg, one); }
      }
      #pragma unroll 1
      for (uint32_t it = 0; it < POLL_LIMIT; it++) {
        uint32_t bad = 0;
        #pragma unroll
        for (int i = 0; i < 12; i++) bad |= v[i].w ^ 0x41000000u;
        if (!__any_sync(~0u, bad != 0)) break;
        #pragma unroll
        for (int i = 0; i < 12; i++) if (i < 6 || isq) v[i] = ld128_rlx(src + 128 * i);
      }
      mbar_wait(sb + B_KD, 0);
      #pragma unroll
      for (int e = 0; e < 2; e++) {
        if (e == 0 || isq) {
          float f[18];
          #pragma unroll
          for (int i = 0; i < 6; i++) { f[3*i] = __uint_as_float(v[6*e+i].x); f[3*i+1] = __uint_as_float(v[6*e+i].y); f[3*i+2] = __uint_as_float(v[6*e+i].z); }
          const uint32_t ka = sb + OFF_KVZ + (wg + e) * 5120 + wp * 1280 + lane * 16;
          stsm4(ka, pack_bf16(f[0], f[1]), pack_bf16(f[2], f[3]), pack_bf16(f[4], f[5]), pack_bf16(f[6], f[7]));
          stsm4(ka + 512, pack_bf16(f[8], f[9]), pack_bf16(f[10], f[11]), pack_bf16(f[12], f[13]), pack_bf16(f[14], f[15]));
          stsm2(ka + 1024, pack_bf16(f[16], 1.f), pack_bf16(f[17], 1.f));
        }
      }
    }
    fence_async_smem();
    if (wg == 1) bar_arrive(NB_DN, 256);
    if (isq) mbar_wait(sb + B_OS, 0);
    TSW(wg == 0 ? 5 : wg == 1 ? 25 : 6);
    #pragma unroll 1
    for (int e = wg; e < wg + 1 + (wg >> 1); e++) {
      const int half = e >> 1, hh = e & 1, turn = e;
      const uint32_t ao = (1 + rank) * R5 + hh * 8192;
      const uint32_t ra = sb + OFF_RSQ + (16 * wp + g) * 4 + (e == 1 ? 256 : 0), rb = ra + 256 * half;
      const float cc[2][2] = {{ldsf(ra) * LOG2E, ldsf(ra + 32) * LOG2E}, {ldsf(rb) * LOG2E, ldsf(rb + 32) * LOG2E}};
      float m[2][4] = {{0.f, 0.f, 0.f, 0.f}, {0.f, 0.f, 0.f, 0.f}};
      uint32_t ph[2][8];
      auto exps = [&](int h) {
        #pragma unroll
        for (int k = 0; k < 8; k++) {
          const float c = cc[h][k & 1], mp = m[h][k & 1], mm = m[h][2 + (k & 1)];
          ph[0][k] = pack_bf16(ex2(fmaf(p[h][2*k], c, mp)), ex2(fmaf(p[h][2*k+1], c, mp)));
          ph[1][k] = pack_bf16(ex2(fmaf(p[h][2*k], -c, mm)), ex2(fmaf(p[h][2*k+1], -c, mm)));
        }
      };
      uint32_t shifted = 0;
      asm volatile("" : "+r"(shifted));
      #pragma unroll 1
      for (;;) {
        if (shifted) { row_extremes(p[0], cc[0], m[0]); row_extremes(p[1], cc[1], m[1]); }
        uint32_t first = (shifted ^ 1) & !isq;
        asm volatile("" : "+r"(first));
        if (first) {
          bar_sync(NB_Q0 + wg, 256);
          const uint32_t da = dlo(SB0, 16) + (ao >> 4), db = dlo(SB0 + OFF_WPHIQ, 16);
          wg_fence();
          #pragma unroll
          for (int h = 0; h < 2; h++) {
            wgmma_ss_n32<0, 1, H128, H64>(p[h], da + 4 * h, db + 128 * h, 0);
            wgmma_sa_n32<0, 1, H128, H64>(p[h], da + 4 * h + 2, db + 128 * h + 64);
          }
          wg_commit();
          wg_wait<0>();
        }
        if (!shifted && (e == 1 || e == 2)) bar_sync(NB_TOK + e - 1, 256);
        TK(64 + 4 * turn);
        fence_regs(p[0]); fence_regs(p[1]);
        exps(0);
        float s2[4] = {0.f, 0.f, 0.f, 0.f};
        #pragma unroll
        for (int i = 0; i < 32; i++) s2[((i >> 1) & 1) + 2 * (i >> 4)] = fmaf(p[i >> 4][i & 15], p[i >> 4][i & 15], s2[((i >> 1) & 1) + 2 * (i >> 4)]);
        if (!__any_sync(~0u, !shifted & !((s2[0] * cc[0][0] * cc[0][0] < ARG_LIM2) & (s2[1] * cc[0][1] * cc[0][1] < ARG_LIM2) &
                                          (s2[2] * cc[1][0] * cc[1][0] < ARG_LIM2) & (s2[3] * cc[1][1] * cc[1][1] < ARG_LIM2)))) break;
        shifted = 1;
      }
      float ac[4][20];
      auto numer = [&](int h, const uint32_t (&f)[2][8]) {
        const uint32_t db = dlo(SB0 + OFF_KVZ, 128) + (half ? e : h) * 320;
        wg_fence();
        #pragma unroll
        for (int i = 0; i < 2; i++) {
          wgmma_rz_n40<1, dhi(256, 0)>(ac[2*h+i], f[i][0], f[i][1], f[i][2], f[i][3], db + i * 160);
          wgmma_ra_n40<1, dhi(256, 0)>(ac[2*h+i], f[i][4], f[i][5], f[i][6], f[i][7], db + (i * 160 + 80));
        }
        wg_commit();
      };
      const uint32_t oa = (16 * wp + g) * 128 + (((lane & 3) ^ g) << 4);
      auto finish = [&](int h) {
        const float* ap = ac[2 * h]; const float* am = ac[2 * h + 1];
        const float ip0 = rcp(ap[17]), im0 = rcp(am[17]), ip1 = rcp(ap[19]), im1 = rcp(am[19]);
        const float d0 = rcp(fmaf(ap[16], ip0, fmaf(am[16], im0, 1e-6f))), d1 = rcp(fmaf(ap[18], ip1, fmaf(am[18], im1, 1e-6f)));
        const float a0 = ip0 * d0, b0 = im0 * d0, a1 = ip1 * d1, b1 = im1 * d1;
        #pragma unroll
        for (int r = 0; r < 2; r++) {
          const float a = r ? a1 : a0, b = r ? b1 : b0;
          uint32_t w[4];
          #pragma unroll
          for (int k = 0; k < 4; k++) w[k] = pack_bf16(fmaf(ap[4*k+2*r], a, am[4*k+2*r] * b), fmaf(ap[4*k+2*r+1], a, am[4*k+2*r+1] * b));
          const uint32_t off = (oa ^ ((half ? rank : h) << 6)) + r * 1024;
          st128_rlx(reinterpret_cast<uint8_t*>(G->o + (m128 * 16 + (half ? 2 * (j & 6) + 2 * hh + 1 : 2 * j)) * 8192 + (half ? h : hh) * 4096) + off, w[0], w[1], w[2], w[3]);
          if (!half) sts128(sb + ao + off, w[0], w[1], w[2], w[3]);
        }
      };
      numer(0, ph);
      exps(1);
      if (wg == 0) bar_sync(NB_DN, 256);
      numer(1, ph);
      if (turn < 2) bar_arrive(NB_TOK + turn, 256);
      wg_wait<1>();
      TK(65 + 4 * turn);
      fence_regs(ac[0]); fence_regs(ac[1]);
      finish(0);
      wg_wait<0>();
      fence_regs(ac[2]); fence_regs(ac[3]);
      #pragma unroll
      for (int i = 0; i < 32; i++) asm volatile("mov.b32 %0, 0;" : "=f"(p[i >> 4][i & 15]));
      if (e == 2) project_r(3);
      finish(1);
      TK(66 + 4 * turn);
      if (!half) fence_async_smem();
      __syncwarp();
      if (lane == 0) mbar_arrive(sb + B_UO + 8 * e);
      wg_wait<0>();
      TK(67 + 4 * turn);
    }
    if (isq) cluster_arrive();
  }

  {
  int lane;
  asm volatile("mov.u32 %0, %%laneid;" : "=r"(lane));
  const int g = lane >> 2, q = lane & 3;
  if (wg < 2) {
    float h[64];
    {
      if (wg == 0) { TK(83); }
      #pragma unroll
      for (int i = 0; i < 32; i++) { h[2*i] = bf_lo(xr[i]); h[2*i+1] = bf_hi(xr[i]); }
      fence_regs(h);
      TK(80 + wg);
      const uint32_t emptyb = mapa(sb + B_EMPTY5, t & 1);
      uint32_t s = 1 + rank, ps = 0;
      mbar_wait2(sb + B_FULL5 + 8 * s, 1, sb + B_UO + 8 * wg, 0);
      if (wg == 0) { TSW(14); }
      #pragma unroll
      for (int i = 0; i < 16; i++) {
        if (wg == 1 && (i & 12) == TKW) { TK(84 + (i & 3)); }
        if (!KT && wg == 0) { TK(32 + i); }
        const uint32_t da = dlo(SB0, 16) + s * 2048 + wg * 512, db = dlo(SB0 + 16384, 8192) + s * 2048;
        wg_fence();
        #pragma unroll
        for (int k = 0; k < 4; k++) wgmma_sa_n128<0, 1, H128, H128>(h, da + k * 2, db + k * 128);
        wg_commit();
        const uint32_t ns = i ? (i + 2) % 6 : 2 - rank;
        const uint32_t b0 = sb + B_FULL5 + 8 * ns, p0 = (1 + (i + 2) / 6) & 1, b1 = sb + B_FULLA + 16 * ns + 8 * wg, p1 = ((i + 1) / 6) & 1;
        const bool here = i == 15 || mbar_test2(b0, p0, b1, p1);
        wg_wait<1>();
        if (!(((2 * REL + 1) >> i) & 1) && i < 14 && t < 2) mbar_arrive_remote(emptyb + 8 * ps, 1);
        if ((REL >> i) & 1) { wg_wait<0>(); if (t < 2) mbar_arrive_remote(emptyb + 8 * s, 1); }
        if (!here) mbar_wait2(b0, p0, b1, p1);
        ps = s; s = ns;
      }
    }
    cluster_arrive();
    float2 wr[16];
    #pragma unroll
    for (int i = 0; i < 16; i++) wr[i] = lds64f(sb + OFF_WR + 32 * i + 8 * q);
    const int r0 = 64 * wg + 16 * wp + g;
    float sum0, sum1, dot0, dot1, sq0, sq1;
    uint32_t redo = 0;
    asm volatile("" : "+r"(redo));
    #pragma unroll 1
    for (;;) {
    if (redo) {
      wg_wait<0>();
      const int r = r0;
      #pragma unroll 1
      for (int n = 0; n < 16; n++) {
        const uint32_t* xp = reinterpret_cast<const uint32_t*>(P.x + (size_t)(128 * m128 + r) * DM + 128 * j + 8 * n) + q;
        const uint32_t x0 = xp[0], x1 = xp[4 * DM];
        float d0 = bf_lo(x0), d1 = bf_hi(x0), d2 = bf_lo(x1), d3 = bf_hi(x1);
        #pragma unroll 1
        for (int ks = 0; ks < 64; ks++) {
          const int kb = ks >> 2, kk = 16 * (ks & 3);
          const bf16* op = G->o + (m128 * 16 + kb) * 8192 + r * 64 + 2 * q;
          const int o0 = ((kk >> 3) ^ g) << 3;
          const uint16_t* w = reinterpret_cast<const uint16_t*>(P.wo_p) + (size_t)(((kb & 1) ? 256 * (kb >> 2) + 32 * (kb & 2) + 32 + 4 * (kk & 32) : 64 * kb + 2 * (kk & 32)) + ((kk & 16) >> 2) + 8 * q) * DM + 128 * j + 8 * n + g;
          const uint32_t b0 = w[0] | (w[DM] << 16), b1 = w[2 * DM] | (w[3 * DM] << 16);
          uint32_t a0, a1, a2, a3, it = 0;
          do { a0 = ld32_rlx(op + o0); a1 = ld32_rlx(op + 512 + o0); a2 = ld32_rlx(op + (o0 ^ 8)); a3 = ld32_rlx(op + 512 + (o0 ^ 8)); }
          while (max(max(a0, a1), max(a2, a3)) == ~0u && ++it < POLL_LIMIT);
          __syncwarp();
          mma16816(d0, d1, d2, d3, a0, a1, a2, a3, b0, b1);
        }
        #pragma unroll
        for (int i = 0; i < 60; i++) h[i] = h[i + 4];
        h[60] = d0; h[61] = d1; h[62] = d2; h[63] = d3;
      }
    }
    wg_wait<0>();
    fence_regs(h);
    if (wg == 0) { TSW(16); }
    sum0 = 0.f, sum1 = 0.f, dot0 = 0.f, dot1 = 0.f, sq0 = 0.f, sq1 = 0.f;
    #pragma unroll
    for (int i = 0; i < 16; i++) {
      sum0 += h[4*i] + h[4*i+1]; sum1 += h[4*i+2] + h[4*i+3];
      sq0 = fmaf(h[4*i], h[4*i], fmaf(h[4*i+1], h[4*i+1], sq0)); sq1 = fmaf(h[4*i+2], h[4*i+2], fmaf(h[4*i+3], h[4*i+3], sq1));
      dot0 = fmaf(h[4*i], wr[i].x, fmaf(h[4*i+1], wr[i].y, dot0)); dot1 = fmaf(h[4*i+2], wr[i].x, fmaf(h[4*i+3], wr[i].y, dot1));
    }
    if (!__any_sync(~0u, !redo & (h[0] != h[0] | h[2] != h[2]))) break;
    redo = 1;
    }
    float4* const rs = &G->rstat[128 * m128 + r0];
    {
      const bool up = q & 2;
      float a = up ? sum1 : sum0, b = up ? sq1 : sq0, d = up ? dot1 : dot0;
      a += __shfl_xor_sync(~0u, up ? sum0 : sum1, 2); b += __shfl_xor_sync(~0u, up ? sq0 : sq1, 2); d += __shfl_xor_sync(~0u, up ? dot0 : dot1, 2);
      a += __shfl_xor_sync(~0u, a, 1); b += __shfl_xor_sync(~0u, b, 1); d += __shfl_xor_sync(~0u, d, 1);
      if ((q & 1) == 0) red_add_f32x4(rs + 4 * q, a, b, d, 1.f);
    }
    bar_arrive(NB_G2E, 384);
    if (wg == 0) { TSW(24); }
    bar_sync(NB_WG01, 256);
    uint32_t wa[8][4][4];
    const uint32_t wb = sb + 16384 * (((uint32_t)FF_SLOT >> (4 * warp)) & 15) + ((lane & 7) + ((lane >> 4) << 3)) * 64 + ((((lane >> 3) & 1) ^ ((lane >> 1) & 3)) << 4);
    auto getw = [&](int ks) {
      #pragma unroll
      for (int m = 0; m < 4; m++) ldsm4t((wb ^ ((m & 1) << 5)) + (m >> 1) * 8192 + ks * 1024, wa[ks][m][0], wa[ks][m][1], wa[ks][m][2], wa[ks][m][3]);
    };
    if (GPRE && f < NFFN_L) mbar_wait(sb + B_F + 8 * warp, 0);
    if (warp == 7) { TK(60); }
    #pragma unroll
    for (int ks = 0; ks < GPRE; ks++) getw(ks);
    float rstd[2], bm[2];
    uint32_t best;
    {
      const float2 swa = lds64f(sb + OFF_SUMWR), swb = lds64f(sb + OFF_SUMWR + 8);
      const float sw = (swa.x + swa.y) + (swb.x + swb.y);
      uint4 a[2]; uint32_t it = 0, key[2];
      do { a[0] = ld128_rlx(rs); a[1] = ld128_rlx(rs + 8); } while (__any_sync(~0u, (a[0].w & a[1].w) != 0x41000000u) && ++it < POLL_LIMIT);
      #pragma unroll
      for (int i = 0; i < 2; i++) {
        const float mean = __uint_as_float(a[i].x) * (1.f / DM);
        rstd[i] = rsqrtf(fmaxf(__uint_as_float(a[i].y) * (1.f / DM) - mean * mean, 0.f) + 1e-5f);
        bm[i] = -mean * rstd[i];
        const uint32_t rr = __float_as_uint(fmaf(__uint_as_float(a[i].z), rstd[i], sw * bm[i]));
        key[i] = ((rr ^ ((uint32_t)((int32_t)rr >> 31) | 0x80000000u)) & ~2047u) | (2047 - 128 * m128 - r0 - 8 * i);
      }
      asm volatile("redux.sync.max.u32 %0, %1, 0xffffffff;" : "=r"(best) : "r"(max(key[0], key[1])));
    }
    if (wg == 0) { TSW(17); }
    const int slot = m128 * 8 + warp, win = ~best & 15;
    if (lane < 4) st32_rlx(&G->key[(4 * j + lane) * 128 + slot], best);
    if ((win & 7) == g) {
      const bool up = win & 8;
      const float ra = up ? rstd[1] : rstd[0], rb = up ? bm[1] : bm[0];
      uint32_t x[16];
      #pragma unroll
      for (int i = 0; i < 16; i++) x[i] = pack_bf16(fmaf(up ? h[4*i+2] : h[4*i], ra, rb), fmaf(up ? h[4*i+3] : h[4*i+1], ra, rb));
      #pragma unroll
      for (int i = 0; i < 4; i++) st128_rlx(&G->cand[slot * DM + 64 * j + 16 * i + 4 * q], x[4*i], x[4*i+1], x[4*i+2], x[4*i+3]);
    }
    __syncwarp();
    if (wg == 0) { TSW(27); }
    {
      const float a0 = 1.f + rstd[0], b0 = bm[0], a1 = 1.f + rstd[1], b1 = bm[1];
      #pragma unroll
      for (int k = 0; k < 8; k++)
        stsm4(((sb + OFF_OUT + wg * 8192 + sa) ^ ((k & 3) << 5)) + (k >> 2) * 16384,
              pack_bf16(fmaf(h[8*k], a0, b0), fmaf(h[8*k+1], a0, b0)),     pack_bf16(fmaf(h[8*k+2], a1, b1), fmaf(h[8*k+3], a1, b1)),
              pack_bf16(fmaf(h[8*k+4], a0, b0), fmaf(h[8*k+5], a0, b0)),   pack_bf16(fmaf(h[8*k+6], a1, b1), fmaf(h[8*k+7], a1, b1)));
      sts32(sb + OFF_EXC + 4 * warp, 16 * warp + win);
      __syncwarp();
      if (lane == 0) mbar_arrive(sb + B_OUT + 8 * (warp >> 1));
      if (lane < 16) {
        const uint4 v = lds128(sb + OFF_OUT + (lane >> 3) * 16384 + (16 * warp + win) * 128 + (((lane & 7) ^ (win & 7)) << 4));
        st128_rlx(&G->cand[slot * DM + 512 + 64 * j + 4 * lane], v.x, v.y, v.z, v.w);
      }
    }
    if (wg == 0) { TSW(28); }
    {
      if (!GPRE && f < NFFN_L) mbar_wait(sb + B_F + 8 * warp, 0);
      #pragma unroll
      for (int ks = GPRE; ks < GRES; ks++) getw(ks);
      if (wg == 0) { TSW(15); }
      bar_sync(NB_XS, 384);
      if (wg == 0) { TSW(19); }
      uint4 xs[4];
      #pragma unroll
      for (int i = 0; i < 4; i++) xs[i] = lds128(sb + OFF_XSEL + 256 * warp + 64 * i + 16 * q);
      float d[4][4];
      #pragma unroll
      for (int ks = 0; ks < 8; ks++) {
        if (ks >= 1 && GRES + ks - 1 < 8) getw(GRES + ks - 1);
        #pragma unroll
        for (int m = 0; m < 4; m++) {
          if (ks == 0) { d[m][0] = 0.f; d[m][1] = 0.f; d[m][2] = 0.f; d[m][3] = 0.f; }
          mma16816(d[m][0], d[m][1], d[m][2], d[m][3], wa[ks][m][0], wa[ks][m][1], wa[ks][m][2], wa[ks][m][3],
                   (ks & 1) ? xs[ks >> 1].z : xs[ks >> 1].x, (ks & 1) ? xs[ks >> 1].w : xs[ks >> 1].y);
        }
      }
      if (q == 0) {
        #pragma unroll
        for (int m = 0; m < 8; m++) stsf(sb + OFF_GU + (8 * m + g) * 48 + 4 * warp, d[m >> 1][2 * (m & 1)]);
      }
      bar_arrive(NB_ACT, 384);
    }
    {
      float y0 = 0.f, y1 = 0.f, y2 = 0.f, y3 = 0.f;
      const uint32_t ky = __float_as_uint(ldsf(sb + OFF_KEY));
      const int kidx = 2047 - (ky & 2047);
      const float kr = __uint_as_float((ky & ~2047u) ^ ((ky >> 31) ? 0x80000000u : 0xfffff800u));
      const int col = 128 * (c >> 4) + 64 * (c & 1) + 32 * ((tid >> 2) & 1) + 16 * (tid & 1) + 8 * ((tid >> 1) & 1) + ((c >> 1) & 7);
      uint32_t it = 0, base = 0;
      if (tid < 8) {
        do { base = ld32_rlx(&G->cand[(kidx >> 4) * DM + 512 + (col >> 1)]); } while (base == ~0u && ++it < POLL_LIMIT);
      }
      if (tid < 2 * NFFN) {
        uint4 v;
        do { v = ld128_rlx(&G->ypart[(tid >> 1) * DM + 8 * c + 4 * (tid & 1)]); } while (v.w == ~0u && ++it < POLL_LIMIT);
        y0 = __uint_as_float(v.x); y1 = __uint_as_float(v.y); y2 = __uint_as_float(v.z); y3 = __uint_as_float(v.w);
      }
      __syncwarp();
      const bool b4 = lane & 16, b3 = lane & 8;
      const float u0 = (b4 ? y1 : y0) + __shfl_xor_sync(~0u, b4 ? y0 : y1, 16), u1 = (b4 ? y3 : y2) + __shfl_xor_sync(~0u, b4 ? y2 : y3, 16);
      float ys = (b3 ? u1 : u0) + __shfl_xor_sync(~0u, b3 ? u0 : u1, 8);
      ys += __shfl_xor_sync(~0u, ys, 4); ys += __shfl_xor_sync(~0u, ys, 2);
      if (!(lane & 6)) stsf(sb + OFF_ACT + ((4 * (lane & 1) + ((lane >> 3) & 1) * 2 + (lane >> 4)) * 8 + warp) * 4, ys);
      const float sg = __fdividef(1.f, 1.f + __expf(-kr));
      bar_sync(NB_WG01, 256);
      if (tid < 8) {
        const uint4 v0 = lds128(sb + OFF_ACT + tid * 32), v1 = lds128(sb + OFF_ACT + tid * 32 + 16);
        const float t8 = ((__uint_as_float(v0.x) + __uint_as_float(v0.y)) + (__uint_as_float(v0.z) + __uint_as_float(v0.w))) +
                         ((__uint_as_float(v1.x) + __uint_as_float(v1.y)) + __uint_as_float(v1.z));
        P.out_p[(size_t)kidx * DM + col] = __float2bfloat16(fmaf(t8, sg, (col & 1) ? bf_hi(base) : bf_lo(base)));
      }
      if (c == 0 && tid == 0) st32_rlx(&G->epoch, __float_as_uint(ldsf(sb + OFF_EP)));
      if (wg == 0) { TSW(22); TDUMP(); }
    }
  }
  if (wg == 2) {
    uint32_t wf[16][2][4];
    {
      const uint32_t wb = sb + OFF_S + 16384 * (wp & 1) + ((lane & 7) + ((lane >> 4) << 3)) * 128 + ((((lane >> 3) & 1) ^ (lane & 7)) << 4);
      if (f < NFFN_L) mbar_wait(sb + B_WD + 8 * wp, 0);
      if (wp == 0) { TK(61); }
      #pragma unroll
      for (int i = 0; i < 32; i++) ldsm4t((wb ^ (((i >> 1) & 3) << 5)) + (i >> 3) * 4096 + (i & 1) * 2048, wf[i >> 1][i & 1][0], wf[i >> 1][i & 1][1], wf[i >> 1][i & 1][2], wf[i >> 1][i & 1][3]);
      fence_async_smem();
      __syncwarp();
      if (lane == 0) mbar_arrive(sb + B_WC + 8 * wp);
      if (wp == 0) { TK(62); }
    }
    bar_sync(NB_G2E, 384);
    {
      uint32_t cur = 0;
      uint4 v;
      #pragma unroll 1
      for (uint32_t it = 0; it < POLL_LIMIT; it++) {
        const uint4 kx = ld128_rlx(&G->key[(c & 31) * 128 + 4 * lane]);
        v = ld128_rlx(&G->cand[((~cur >> 4) & 127) * DM + 4 * t]);
        uint32_t best;
        asm volatile("redux.sync.max.u32 %0, %1, 0xffffffff;" : "=r"(best) : "r"(max(max(kx.x, kx.y), max(kx.z, kx.w))));
        if (!__any_sync(~0u, min(min(kx.x, kx.y), min(kx.z, kx.w)) == 0 || v.w == ~0u) && best == cur) break;
        cur = best;
      }
      sts128(sb + OFF_XSEL + 16 * t, v.x, v.y, v.z, v.w);
      sts32(sb + OFF_KEY, cur);
      bar_arrive(NB_XS, 384);
      if (t == 0) mbar_arrive(sb + B_XS);
      TSW(18);
      bar_sync(NB_ACT, 384);
    }
    float gu[2];
    #pragma unroll
    for (int i = 0; i < 2; i++) {
      const uint4 v0 = lds128(sb + OFF_GU + (32 * i + lane) * 48), v1 = lds128(sb + OFF_GU + (32 * i + lane) * 48 + 16);
      gu[i] = ((__uint_as_float(v0.x) + __uint_as_float(v0.y)) + (__uint_as_float(v0.z) + __uint_as_float(v0.w))) +
              ((__uint_as_float(v1.x) + __uint_as_float(v1.y)) + (__uint_as_float(v1.z) + __uint_as_float(v1.w)));
    }
    const float act = gu[0] * gu[1] * rcp(1.f + ex2(-LOG2E * gu[0]));
    const uint32_t ap = pack_bf16(act, __shfl_down_sync(~0u, act, 1));
    uint32_t bf[4];
    #pragma unroll
    for (int i = 0; i < 4; i++) bf[i] = __shfl_sync(~0u, ap, 2 * q + 8 * i);
    TSW(20);
    float d[16][4];
    #pragma unroll
    for (int k = 0; k < 2; k++)
      #pragma unroll
      for (int i = 0; i < 16; i++) {
        if (k == 0) { d[i][0] = 0.f; d[i][1] = 0.f; d[i][2] = 0.f; d[i][3] = 0.f; }
        mma16816(d[i][0], d[i][1], d[i][2], d[i][3], wf[i][k][0], wf[i][k][1], wf[i][k][2], wf[i][k][3], bf[2*k], bf[2*k+1]);
      }
    #pragma unroll
    for (int a = 0; a < 2; a++) {
      float y[4];
      #pragma unroll
      for (int e = 0; e < 4; e++) {
        const int n = 8 * a + (e & 1);
        const float lo = (q & 1) ? d[n + 2][e & 2] : d[n][e & 2], hi = (q & 1) ? d[n + 6][e & 2] : d[n + 4][e & 2];
        y[e] = (q & 2) ? hi : lo;
      }
      if (f < NFFN) st128_rlx(&G->ypart[f * DM + 256 * wp + 128 * a + 4 * lane], __float_as_uint(y[0]), __float_as_uint(y[1]), __float_as_uint(y[2]), min(__float_as_uint(y[3]), ~1u));
    }
    TSW(21);
  }
  }
  cluster_wait();
}

typedef CUresult (*EncodeFn)(CUtensorMap*, CUtensorMapDataType, cuuint32_t, void*, const cuuint64_t*, const cuuint64_t*,
                             const cuuint32_t*, const cuuint32_t*, CUtensorMapInterleave, CUtensorMapSwizzle,
                             CUtensorMapL2promotion, CUtensorMapFloatOOBfill);

void make_map(EncodeFn enc, CUtensorMap* m, const void* p, int n, const cuuint64_t* dims, const cuuint64_t* str, const cuuint32_t* box,
              CUtensorMapSwizzle sw, CUtensorMapL2promotion promo) {
  cuuint32_t es[5] = {1, 1, 1, 1, 1};
  enc(m, CU_TENSOR_MAP_DATA_TYPE_BFLOAT16, n, const_cast<void*>(p), dims, str, box, es, CU_TENSOR_MAP_INTERLEAVE_NONE, sw, promo,
      CU_TENSOR_MAP_FLOAT_OOB_FILL_NONE);
}
void map2(EncodeFn enc, CUtensorMap* m, const void* p, uint64_t cols, uint64_t rows, uint32_t bc, uint32_t br, CUtensorMapSwizzle sw,
          CUtensorMapL2promotion promo) {
  const cuuint64_t dims[2] = {cols, rows}, str[1] = {cols * 2};
  const cuuint32_t box[2] = {bc, br};
  make_map(enc, m, p, 2, dims, str, box, sw, promo);
}
void map3(EncodeFn enc, CUtensorMap* m, const void* p, uint64_t cols, uint64_t rows, uint32_t br, uint32_t nb) {
  const cuuint64_t dims[3] = {64, rows, cols / 64}, str[2] = {cols * 2, 128};
  const cuuint32_t box[3] = {64, br, nb};
  make_map(enc, m, p, 3, dims, str, box, CU_TENSOR_MAP_SWIZZLE_128B, CU_TENSOR_MAP_L2_PROMOTION_L2_128B);
}

}

extern "C" void kernel_launch(void* const* d_in, const int* in_sizes, int n_in, void* d_out, int out_size) {
  (void)in_sizes; (void)n_in; (void)out_size;
  static EncodeFn enc = nullptr;
  static void* o_ptr = nullptr;
  if (!enc) {
    void* f = nullptr; cudaDriverEntryPointQueryResult qr;
    cudaGetDriverEntryPoint("cuTensorMapEncodeTiled", &f, cudaEnableDefault, &qr);
    enc = (EncodeFn)f;
    cudaGetSymbolAddress(&o_ptr, g_scr);
    cudaFuncSetAttribute(fused_kernel, cudaFuncAttributeMaxDynamicSharedMemorySize, SMEM_BYTES);
  }
  const bf16* x = (const bf16*)d_in[0];
  const bf16* wqkv = (const bf16*)d_in[1];
  const bf16* wphi = (const bf16*)d_in[2];
  const bf16* wo = (const bf16*)d_in[3];
  const bf16* wr = (const bf16*)d_in[5];
  const bf16* wgate = (const bf16*)d_in[6];
  const bf16* wup = (const bf16*)d_in[7];
  const bf16* wdown = (const bf16*)d_in[8];
  Params P;
  const CUtensorMapSwizzle S128 = CU_TENSOR_MAP_SWIZZLE_128B, S64 = CU_TENSOR_MAP_SWIZZLE_64B;
  const CUtensorMapL2promotion L128 = CU_TENSOR_MAP_L2_PROMOTION_L2_128B, L256 = CU_TENSOR_MAP_L2_PROMOTION_L2_256B,
                               L64 = CU_TENSOR_MAP_L2_PROMOTION_L2_64B;
  map2(enc, &P.x128, x, DM, SEQ, 64, 128, S128, L256);
  map2(enc, &P.x64, x, DM, SEQ, 64, 64, S128, L128);
  {
    const cuuint64_t dims[4] = {64, DM, 16, 3}, str[3] = {6 * DM, 128, 2 * DM};
    const cuuint32_t box[4] = {64, 64, 1, 2};
    make_map(enc, &P.wkv, wqkv, 4, dims, str, box, S128, L128);
  }
  map3(enc, &P.wq, wqkv, 3 * DM, DM, 64, 2);
  for (int i = 0; i < 2; i++) {
    const cuuint64_t dims[5] = {DM, (cuuint64_t)(DM - 94 - 64 * i), 4, 4, 2}, str[4] = {2 * DM, 16 * DM, 4 * DM, (cuuint64_t)(128 * DM) << i};
    const cuuint32_t box[5] = {64, 2, 4, 4, 2};
    make_map(enc, &P.wo[i], wo, 5, dims, str, box, S128, L128);
  }
  map3(enc, &P.wd, wdown, DM, FF, 32, 4);
  map2(enc, &P.wg, wgate, FF, DM, 32, 128, S64, L64);
  map2(enc, &P.wu, wup, FF, DM, 32, 128, S64, L64);
  map2(enc, &P.tg, wgate, FF, DM, 8, 16, CU_TENSOR_MAP_SWIZZLE_NONE, L128);
  map2(enc, &P.tu, wup, FF, DM, 8, 16, CU_TENSOR_MAP_SWIZZLE_NONE, L128);
  map2(enc, &P.td, wdown, 128, FF * 8, 8, 16, CU_TENSOR_MAP_SWIZZLE_NONE, L256);
  map2(enc, &P.phi, wphi, 32, 1024, 32, 32, S64, L64);
  P.x = x; P.wqkv = wqkv; P.wo_p = wo; P.wd_p = wdown; P.wg_p = wgate; P.wu_p = wup; P.wr = wr; P.out_p = (bf16*)d_out; P.g = (Scratch*)o_ptr; P.zero = 0;

  cudaLaunchConfig_t cfg = {};
  cfg.gridDim = dim3(128); cfg.blockDim = dim3(512); cfg.dynamicSmemBytes = SMEM_BYTES; cfg.stream = cudaStreamPerThread;
  cudaLaunchAttribute at[1];
  at[0].id = cudaLaunchAttributeClusterDimension; at[0].val.clusterDim.x = 2; at[0].val.clusterDim.y = 1; at[0].val.clusterDim.z = 1;
  cfg.attrs = at; cfg.numAttrs = 1;
  cudaLaunchKernelEx(&cfg, fused_kernel, P);
}
```

```cpp
#include <cuda_runtime.h>
#include <cuda.h>
#include <cuda_bf16.h>
#include <stdint.h>

namespace {

typedef __nv_bfloat16 bf16;

__device__ __forceinline__ uint32_t smem_u32(const void* p){ return (uint32_t)__cvta_generic_to_shared(p); }
__device__ __forceinline__ void mbar_init(uint32_t bar, uint32_t cnt){ asm volatile("mbarrier.init.shared::cta.b64 [%0], %1;"::"r"(bar),"r"(cnt):"memory"); }
__device__ __forceinline__ void mbar_expect_tx(uint32_t bar, uint32_t bytes){ asm volatile("mbarrier.arrive.expect_tx.shared::cta.b64 _, [%0], %1;"::"r"(bar),"r"(bytes):"memory"); }
__device__ __forceinline__ void mbar_arrive(uint32_t bar){ asm volatile("mbarrier.arrive.shared::cta.b64 _, [%0];"::"r"(bar):"memory"); }
__device__ __forceinline__ uint32_t mapa(uint32_t addr, uint32_t cta){ uint32_t r; asm volatile("mapa.shared::cluster.u32 %0, %1, %2;":"=r"(r):"r"(addr),"r"(cta)); return r; }
__device__ __forceinline__ void mbar_arrive_at(uint32_t bar, uint32_t cta, uint32_t cnt){
  asm volatile("{\n.reg .b32 ra;\nmapa.shared::cluster.u32 ra, %0, %1;\nmbarrier.arrive.shared::cluster.b64 _, [ra], %2;\n}\n"::"r"(bar),"r"(cta),"r"(cnt):"memory"); }
__device__ __forceinline__ void mbar_arrive_remote(uint32_t cluster_addr, uint32_t cnt){
  asm volatile("mbarrier.arrive.shared::cluster.b64 _, [%0], %1;"::"r"(cluster_addr),"r"(cnt):"memory"); }
__device__ __forceinline__ void mbar_wait(uint32_t bar, uint32_t parity){
  asm volatile("{\n.reg .pred p;\n.reg .u32 c;\nmov.u32 c, 0;\nLW:\nmbarrier.try_wait.parity.shared::cta.b64 p, [%0], %1;\n@p bra LD;\nadd.u32 c, c, 1;\nsetp.lt.u32 p, c, 2000000;\n@p bra LW;\ntrap;\nLD:\n}\n"::"r"(bar),"r"(parity):"memory"); }
__device__ __forceinline__ void mbar_wait2(uint32_t bar0, uint32_t par0, uint32_t bar1, uint32_t par1){
  asm volatile("{\n.reg .pred p, q;\n.reg .u32 c;\nmov.u32 c, 0;\nLW:\nmbarrier.try_wait.parity.shared::cta.b64 p, [%0], %1;\nmbarrier.try_wait.parity.shared::cta.b64 q, [%2], %3;\nand.pred p, p, q;\n@p bra LD;\nadd.u32 c, c, 1;\nsetp.lt.u32 p, c, 2000000;\n@p bra LW;\ntrap;\nLD:\n}\n"::"r"(bar0),"r"(par0),"r"(bar1),"r"(par1):"memory"); }
__device__ __forceinline__ bool mbar_test2(uint32_t bar0, uint32_t par0, uint32_t bar1, uint32_t par1){
  uint32_t r;
  asm volatile("{\n.reg .pred p, q;\nmbarrier.test_wait.parity.shared::cta.b64 p, [%1], %2;\nmbarrier.test_wait.parity.shared::cta.b64 q, [%3], %4;\nand.pred p, p, q;\nselp.u32 %0, 1, 0, p;\n}\n":"=r"(r):"r"(bar0),"r"(par0),"r"(bar1),"r"(par1):"memory");
  return r; }
__device__ __forceinline__ void tma_2d(uint32_t dst, const CUtensorMap* m, int c0, int c1, uint32_t bar){
  asm volatile("cp.async.bulk.tensor.2d.shared::cluster.global.mbarrier::complete_tx::bytes [%0], [%1, {%3, %4}], [%2];"::"r"(dst),"l"(m),"r"(bar),"r"(c0),"r"(c1):"memory"); }
__device__ __forceinline__ void tma_2d_mc(uint32_t dst, const CUtensorMap* m, int c0, int c1, uint32_t bar){
  asm volatile("cp.async.bulk.tensor.2d.shared::cluster.global.mbarrier::complete_tx::bytes.multicast::cluster [%0], [%1, {%3, %4}], [%2], %5;"::"r"(dst),"l"(m),"r"(bar),"r"(c0),"r"(c1),"h"((uint16_t)3):"memory"); }
__device__ __forceinline__ void tma_2d_mc_h(uint32_t dst, const CUtensorMap* m, int c0, int c1, uint32_t bar, uint64_t pol){
  asm volatile("cp.async.bulk.tensor.2d.shared::cluster.global.mbarrier::complete_tx::bytes.multicast::cluster.L2::cache_hint [%0], [%1, {%3, %4}], [%2], %5, %6;"::"r"(dst),"l"(m),"r"(bar),"r"(c0),"r"(c1),"h"((uint16_t)3),"l"(pol):"memory"); }
__device__ __forceinline__ void tma_4d(uint32_t dst, const CUtensorMap* m, int c0, int c1, int c2, int c3, uint32_t bar){
  asm volatile("cp.async.bulk.tensor.4d.shared::cluster.global.mbarrier::complete_tx::bytes [%0], [%1, {%3, %4, %5, %6}], [%2];"::"r"(dst),"l"(m),"r"(bar),"r"(c0),"r"(c1),"r"(c2),"r"(c3):"memory"); }
__device__ __forceinline__ uint64_t policy_evict_first(){ uint64_t p; asm volatile("createpolicy.fractional.L2::evict_first.b64 %0, 1.0;":"=l"(p)); return p; }
__device__ __forceinline__ uint64_t policy_evict_normal(){ uint64_t p; asm("createpolicy.fractional.L2::evict_normal.b64 %0, 1.0;":"=l"(p)); return p; }
__device__ __forceinline__ void tma_3d_h(uint32_t dst, const CUtensorMap* m, int c0, int c1, int c2, uint32_t bar, uint64_t pol){
  asm volatile("cp.async.bulk.tensor.3d.shared::cluster.global.mbarrier::complete_tx::bytes.L2::cache_hint [%0], [%1, {%3, %4, %5}], [%2], %6;"::"r"(dst),"l"(m),"r"(bar),"r"(c0),"r"(c1),"r"(c2),"l"(pol):"memory"); }
__device__ __forceinline__ void tma_4d_h(uint32_t dst, const CUtensorMap* m, int c0, int c1, int c2, int c3, uint32_t bar, uint64_t pol){
  asm volatile("cp.async.bulk.tensor.4d.shared::cluster.global.mbarrier::complete_tx::bytes.L2::cache_hint [%0], [%1, {%3, %4, %5, %6}], [%2], %7;"::"r"(dst),"l"(m),"r"(bar),"r"(c0),"r"(c1),"r"(c2),"r"(c3),"l"(pol):"memory"); }
__device__ __forceinline__ void red_add_f32x4(float4* p, float x, float y, float z, float w){ asm volatile("red.relaxed.gpu.global.add.v4.f32 [%0], {%1,%2,%3,%4};"::"l"(p),"f"(x),"f"(y),"f"(z),"f"(w):"memory"); }
__device__ __forceinline__ void tma_5d_h(uint32_t dst, const CUtensorMap* m, int c0, int c1, uint32_t bar, uint64_t pol){
  asm volatile("cp.async.bulk.tensor.5d.shared::cluster.global.mbarrier::complete_tx::bytes.L2::cache_hint [%0], [%1, {%3, %4, 0, 0, 0}], [%2], %5;"::"r"(dst),"l"(m),"r"(bar),"r"(c0),"r"(c1),"l"(pol):"memory"); }
__device__ __forceinline__ bool elect_one(){ uint32_t p; asm volatile("{\n.reg .pred P;\nelect.sync _|P, 0xffffffff;\nselp.b32 %0, 1, 0, P;\n}\n":"=r"(p)); return p; }
__device__ __forceinline__ void bulk_prefetch(const void* p, uint32_t bytes){
  asm volatile("cp.async.bulk.prefetch.L2.global [%0], %1;"::"l"(p),"r"(bytes):"memory"); }
__device__ __forceinline__ void bulk_s2peer(uint32_t dst_cluster, uint32_t src, uint32_t bytes, uint32_t bar_cluster){
  asm volatile("cp.async.bulk.shared::cluster.shared::cta.mbarrier::complete_tx::bytes [%0], [%1], %2, [%3];"::"r"(dst_cluster),"r"(src),"r"(bytes),"r"(bar_cluster):"memory"); }
__device__ __forceinline__ void bulk_g2s_mc(uint32_t dst, const void* src, uint32_t bytes, uint32_t bar, uint64_t pol){
  asm volatile("cp.async.bulk.shared::cluster.global.mbarrier::complete_tx::bytes.multicast::cluster.L2::cache_hint [%0], [%1], %2, [%3], %4, %5;"::"r"(dst),"l"(src),"r"(bytes),"r"(bar),"h"((uint16_t)3),"l"(pol):"memory"); }
__device__ __forceinline__ void prefetch_map(const CUtensorMap* m){ asm volatile("prefetch.tensormap [%0];"::"l"(m):"memory"); }
__device__ __forceinline__ void fence_async_smem(){ asm volatile("fence.proxy.async.shared::cta;":::"memory"); }
__device__ __forceinline__ void fence_acquire_gpu(){ asm volatile("fence.acquire.gpu;":::"memory"); }
__device__ __forceinline__ void fence_gpu(){ asm volatile("fence.acq_rel.gpu;":::"memory"); }
__device__ __forceinline__ void wg_fence(){ asm volatile("wgmma.fence.sync.aligned;":::"memory"); }
__device__ __forceinline__ void wg_commit(){ asm volatile("wgmma.commit_group.sync.aligned;":::"memory"); }
template<int N> __device__ __forceinline__ void wg_wait(){ asm volatile("wgmma.wait_group.sync.aligned %0;"::"n"(N):"memory"); }
template<int N> __device__ __forceinline__ void fence_regs(float (&d)[N]){
  #pragma unroll
  for(int i=0;i<N;i++) asm volatile("":"+f"(d[i])::"memory"); }
__device__ __forceinline__ void bar_sync(int id, int n){ asm volatile("bar.sync %0, %1;"::"r"(id),"r"(n):"memory"); }
__device__ __forceinline__ void bar_arrive(int id, int n){ asm volatile("bar.arrive %0, %1;"::"r"(id),"r"(n):"memory"); }
__device__ __forceinline__ void cluster_arrive(){ asm volatile("barrier.cluster.arrive.relaxed.aligned;":::"memory"); }
__device__ __forceinline__ void cluster_wait(){ asm volatile("barrier.cluster.wait.aligned;":::"memory"); }
__host__ __device__ constexpr uint32_t dlo(uint32_t addr, uint32_t lbo){ return (addr >> 4) | ((lbo >> 4) << 16); }
__host__ __device__ constexpr uint32_t dhi(uint32_t sbo, uint32_t sw){ return (sbo >> 4) | (sw << 30); }
constexpr uint32_t H128 = dhi(1024, 1), H64 = dhi(512, 2), H0 = dhi(128, 0);
__device__ __forceinline__ uint32_t pack_bf16(float lo, float hi){ uint32_t r; asm("cvt.rn.bf16x2.f32 %0, %1, %2;":"=r"(r):"f"(hi),"f"(lo)); return r; }
__device__ __forceinline__ float bf_lo(uint32_t v){ return __uint_as_float(v<<16); }
__device__ __forceinline__ float bf_hi(uint32_t v){ return __uint_as_float(v&0xffff0000u); }
__device__ __forceinline__ float ex2(float x){ float r; asm("ex2.approx.ftz.f32 %0, %1;":"=f"(r):"f"(x)); return r; }
__device__ __forceinline__ float rcp(float x){ float r; asm("rcp.approx.ftz.f32 %0, %1;":"=f"(r):"f"(x)); return r; }
__device__ __forceinline__ void stsm4(uint32_t addr, uint32_t a, uint32_t b, uint32_t c, uint32_t d){
  asm volatile("stmatrix.sync.aligned.m8n8.x4.shared.b16 [%0], {%1,%2,%3,%4};"::"r"(addr),"r"(a),"r"(b),"r"(c),"r"(d)); }
__device__ __forceinline__ void stsm2(uint32_t addr, uint32_t a, uint32_t b){
  asm volatile("stmatrix.sync.aligned.m8n8.x2.shared.b16 [%0], {%1,%2};"::"r"(addr),"r"(a),"r"(b)); }
__device__ __forceinline__ void mma16816(float& d0, float& d1, float& d2, float& d3, uint32_t a0, uint32_t a1, uint32_t a2, uint32_t a3, uint32_t b0, uint32_t b1){
  asm volatile("mma.sync.aligned.m16n8k16.row.col.f32.bf16.bf16.f32 {%0,%1,%2,%3}, {%4,%5,%6,%7}, {%8,%9}, {%0,%1,%2,%3};"
               : "+f"(d0), "+f"(d1), "+f"(d2), "+f"(d3) : "r"(a0), "r"(a1), "r"(a2), "r"(a3), "r"(b0), "r"(b1)); }
__device__ __forceinline__ void ldsm4(uint32_t addr, uint32_t& a, uint32_t& b, uint32_t& c, uint32_t& d){
  asm volatile("ldmatrix.sync.aligned.m8n8.x4.shared.b16 {%0,%1,%2,%3}, [%4];":"=r"(a),"=r"(b),"=r"(c),"=r"(d):"r"(addr):"memory"); }
__device__ __forceinline__ void ldsm4t(uint32_t addr, uint32_t& a, uint32_t& b, uint32_t& c, uint32_t& d){
  asm volatile("ldmatrix.sync.aligned.m8n8.x4.trans.shared.b16 {%0,%1,%2,%3}, [%4];":"=r"(a),"=r"(b),"=r"(c),"=r"(d):"r"(addr):"memory"); }
__device__ __forceinline__ void sts32(uint32_t a, uint32_t v){ asm volatile("st.shared.b32 [%0], %1;"::"r"(a),"r"(v):"memory"); }
__device__ __forceinline__ void stsf(uint32_t a, float v){ asm volatile("st.shared.f32 [%0], %1;"::"r"(a),"f"(v):"memory"); }
__device__ __forceinline__ void sts64(uint32_t a, uint32_t x, uint32_t y){ asm volatile("st.shared.v2.b32 [%0], {%1,%2};"::"r"(a),"r"(x),"r"(y):"memory"); }
__device__ __forceinline__ void sts128(uint32_t a, uint32_t x, uint32_t y, uint32_t z, uint32_t w){ asm volatile("st.shared.v4.b32 [%0], {%1,%2,%3,%4};"::"r"(a),"r"(x),"r"(y),"r"(z),"r"(w):"memory"); }
__device__ __forceinline__ float ldsf(uint32_t a){ float v; asm volatile("ld.shared.f32 %0, [%1];":"=f"(v):"r"(a):"memory"); return v; }
__device__ __forceinline__ float2 lds64f(uint32_t a){ float2 v; asm volatile("ld.shared.v2.f32 {%0,%1}, [%2];":"=f"(v.x),"=f"(v.y):"r"(a):"memory"); return v; }
__device__ __forceinline__ uint4 lds128(uint32_t a){ uint4 v; asm volatile("ld.shared.v4.u32 {%0,%1,%2,%3}, [%4];":"=r"(v.x),"=r"(v.y),"=r"(v.z),"=r"(v.w):"r"(a):"memory"); return v; }
__device__ __forceinline__ uint4 ld128_keep(const void* p){ uint4 v; asm volatile("ld.global.v4.u32 {%0,%1,%2,%3}, [%4];":"=r"(v.x),"=r"(v.y),"=r"(v.z),"=r"(v.w):"l"(p):"memory"); return v; }
__device__ __forceinline__ uint4 ld128_rlx(const void* p){ uint4 v; asm volatile("ld.relaxed.gpu.global.v4.u32 {%0,%1,%2,%3}, [%4];":"=r"(v.x),"=r"(v.y),"=r"(v.z),"=r"(v.w):"l"(p):"memory"); return v; }
__device__ __forceinline__ uint32_t ld32_rlx(const void* p){ uint32_t v; asm volatile("ld.relaxed.gpu.global.u32 %0, [%1];":"=r"(v):"l"(p):"memory"); return v; }
__device__ __forceinline__ void st128_rlx(void* p, uint32_t x, uint32_t y, uint32_t z, uint32_t w){ asm volatile("st.relaxed.gpu.global.v4.u32 [%0], {%1,%2,%3,%4};"::"l"(p),"r"(x),"r"(y),"r"(z),"r"(w):"memory"); }
__device__ __forceinline__ void st64_rlx(void* p, uint32_t x, uint32_t y){ asm volatile("st.relaxed.gpu.global.v2.u32 [%0], {%1,%2};"::"l"(p),"r"(x),"r"(y):"memory"); }
__device__ __forceinline__ void st32_rlx(void* p, uint32_t x){ asm volatile("st.relaxed.gpu.global.u32 [%0], %1;"::"l"(p),"r"(x):"memory"); }
__device__ __forceinline__ uint32_t tagw(float x, uint32_t t){ return (__float_as_uint(x) & ~3u) | t; }
__device__ __forceinline__ float untag(uint32_t w){ return __uint_as_float(w & ~3u); }

template<int TA, int TB, uint32_t HA, uint32_t HB> __device__ __forceinline__ void wgmma_ss_n128(float (&d)[64], uint32_t da, uint32_t db, int scale_d){
  asm volatile("{\n.reg .pred p;\n.reg .b64 a, b;\nsetp.ne.b32 p, %70, 0;\nmov.b64 a, {%64, %68};\nmov.b64 b, {%65, %69};\n"
  "wgmma.mma_async.sync.aligned.m64n128k16.f32.bf16.bf16 {%0, %1, %2, %3, %4, %5, %6, %7, %8, %9, %10, %11, %12, %13, %14, %15, %16, %17, %18, %19, %20, %21, %22, %23, %24, %25, %26, %27, %28, %29, %30, %31, %32, %33, %34, %35, %36, %37, %38, %39, %40, %41, %42, %43, %44, %45, %46, %47, %48, %49, %50, %51, %52, %53, %54, %55, %56, %57, %58, %59, %60, %61, %62, %63}, a, b, p, 1, 1, %66, %67;\n}\n"
  : "+f"(d[0]), "+f"(d[1]), "+f"(d[2]), "+f"(d[3]), "+f"(d[4]), "+f"(d[5]), "+f"(d[6]), "+f"(d[7]), "+f"(d[8]), "+f"(d[9]), "+f"(d[10]), "+f"(d[11]), "+f"(d[12]), "+f"(d[13]), "+f"(d[14]), "+f"(d[15]), "+f"(d[16]), "+f"(d[17]), "+f"(d[18]), "+f"(d[19]), "+f"(d[20]), "+f"(d[21]), "+f"(d[22]), "+f"(d[23]), "+f"(d[24]), "+f"(d[25]), "+f"(d[26]), "+f"(d[27]), "+f"(d[28]), "+f"(d[29]), "+f"(d[30]), "+f"(d[31]), "+f"(d[32]), "+f"(d[33]), "+f"(d[34]), "+f"(d[35]), "+f"(d[36]), "+f"(d[37]), "+f"(d[38]), "+f"(d[39]), "+f"(d[40]), "+f"(d[41]), "+f"(d[42]), "+f"(d[43]), "+f"(d[44]), "+f"(d[45]), "+f"(d[46]), "+f"(d[47]), "+f"(d[48]), "+f"(d[49]), "+f"(d[50]), "+f"(d[51]), "+f"(d[52]), "+f"(d[53]), "+f"(d[54]), "+f"(d[55]), "+f"(d[56]), "+f"(d[57]), "+f"(d[58]), "+f"(d[59]), "+f"(d[60]), "+f"(d[61]), "+f"(d[62]), "+f"(d[63])
  : "r"(da), "r"(db), "n"(TA), "n"(TB), "n"(HA), "n"(HB), "r"(scale_d));
}
template<int TA, int TB, uint32_t HA, uint32_t HB> __device__ __forceinline__ void wgmma_sa_n128(float (&d)[64], uint32_t da, uint32_t db){
  asm volatile("{\n.reg .pred p;\n.reg .b64 a, b;\nsetp.ne.b32 p, 1, 0;\nmov.b64 a, {%64, %68};\nmov.b64 b, {%65, %69};\n"
  "wgmma.mma_async.sync.aligned.m64n128k16.f32.bf16.bf16 {%0, %1, %2, %3, %4, %5, %6, %7, %8, %9, %10, %11, %12, %13, %14, %15, %16, %17, %18, %19, %20, %21, %22, %23, %24, %25, %26, %27, %28, %29, %30, %31, %32, %33, %34, %35, %36, %37, %38, %39, %40, %41, %42, %43, %44, %45, %46, %47, %48, %49, %50, %51, %52, %53, %54, %55, %56, %57, %58, %59, %60, %61, %62, %63}, a, b, p, 1, 1, %66, %67;\n}\n"
  : "+f"(d[0]), "+f"(d[1]), "+f"(d[2]), "+f"(d[3]), "+f"(d[4]), "+f"(d[5]), "+f"(d[6]), "+f"(d[7]), "+f"(d[8]), "+f"(d[9]), "+f"(d[10]), "+f"(d[11]), "+f"(d[12]), "+f"(d[13]), "+f"(d[14]), "+f"(d[15]), "+f"(d[16]), "+f"(d[17]), "+f"(d[18]), "+f"(d[19]), "+f"(d[20]), "+f"(d[21]), "+f"(d[22]), "+f"(d[23]), "+f"(d[24]), "+f"(d[25]), "+f"(d[26]), "+f"(d[27]), "+f"(d[28]), "+f"(d[29]), "+f"(d[30]), "+f"(d[31]), "+f"(d[32]), "+f"(d[33]), "+f"(d[34]), "+f"(d[35]), "+f"(d[36]), "+f"(d[37]), "+f"(d[38]), "+f"(d[39]), "+f"(d[40]), "+f"(d[41]), "+f"(d[42]), "+f"(d[43]), "+f"(d[44]), "+f"(d[45]), "+f"(d[46]), "+f"(d[47]), "+f"(d[48]), "+f"(d[49]), "+f"(d[50]), "+f"(d[51]), "+f"(d[52]), "+f"(d[53]), "+f"(d[54]), "+f"(d[55]), "+f"(d[56]), "+f"(d[57]), "+f"(d[58]), "+f"(d[59]), "+f"(d[60]), "+f"(d[61]), "+f"(d[62]), "+f"(d[63])
  : "r"(da), "r"(db), "n"(TA), "n"(TB), "n"(HA), "n"(HB));
}
template<int TA, int TB, uint32_t HA, uint32_t HB> __device__ __forceinline__ void wgmma_sa_n40(float (&d)[20], uint32_t da, uint32_t db){
  asm volatile("{\n.reg .pred p;\n.reg .b64 a, b;\nsetp.ne.b32 p, 1, 0;\nmov.b64 a, {%20, %24};\nmov.b64 b, {%21, %25};\n"
  "wgmma.mma_async.sync.aligned.m64n40k16.f32.bf16.bf16 {%0, %1, %2, %3, %4, %5, %6, %7, %8, %9, %10, %11, %12, %13, %14, %15, %16, %17, %18, %19}, a, b, p, 1, 1, %22, %23;\n}\n"
  : "+f"(d[0]), "+f"(d[1]), "+f"(d[2]), "+f"(d[3]), "+f"(d[4]), "+f"(d[5]), "+f"(d[6]), "+f"(d[7]), "+f"(d[8]), "+f"(d[9]), "+f"(d[10]), "+f"(d[11]), "+f"(d[12]), "+f"(d[13]), "+f"(d[14]), "+f"(d[15]), "+f"(d[16]), "+f"(d[17]), "+f"(d[18]), "+f"(d[19])
  : "r"(da), "r"(db), "n"(TA), "n"(TB), "n"(HA), "n"(HB));
}
template<int TA, int TB, uint32_t HA, uint32_t HB> __device__ __forceinline__ void wgmma_sz_n40(float (&d)[20], uint32_t da, uint32_t db){
  asm volatile("{\n.reg .pred p;\n.reg .b64 a, b;\nsetp.ne.b32 p, 0, 0;\nmov.b64 a, {%20, %24};\nmov.b64 b, {%21, %25};\n"
  "wgmma.mma_async.sync.aligned.m64n40k16.f32.bf16.bf16 {%0, %1, %2, %3, %4, %5, %6, %7, %8, %9, %10, %11, %12, %13, %14, %15, %16, %17, %18, %19}, a, b, p, 1, 1, %22, %23;\n}\n"
  : "=f"(d[0]), "=f"(d[1]), "=f"(d[2]), "=f"(d[3]), "=f"(d[4]), "=f"(d[5]), "=f"(d[6]), "=f"(d[7]), "=f"(d[8]), "=f"(d[9]), "=f"(d[10]), "=f"(d[11]), "=f"(d[12]), "=f"(d[13]), "=f"(d[14]), "=f"(d[15]), "=f"(d[16]), "=f"(d[17]), "=f"(d[18]), "=f"(d[19])
  : "r"(da), "r"(db), "n"(TA), "n"(TB), "n"(HA), "n"(HB));
}
template<int TA, int TB, uint32_t HA, uint32_t HB> __device__ __forceinline__ void wgmma_sa_n32(float (&d)[16], uint32_t da, uint32_t db){
  asm volatile("{\n.reg .pred p;\n.reg .b64 a, b;\nsetp.ne.b32 p, 1, 0;\nmov.b64 a, {%16, %20};\nmov.b64 b, {%17, %21};\n"
  "wgmma.mma_async.sync.aligned.m64n32k16.f32.bf16.bf16 {%0, %1, %2, %3, %4, %5, %6, %7, %8, %9, %10, %11, %12, %13, %14, %15}, a, b, p, 1, 1, %18, %19;\n}\n"
  : "+f"(d[0]), "+f"(d[1]), "+f"(d[2]), "+f"(d[3]), "+f"(d[4]), "+f"(d[5]), "+f"(d[6]), "+f"(d[7]), "+f"(d[8]), "+f"(d[9]), "+f"(d[10]), "+f"(d[11]), "+f"(d[12]), "+f"(d[13]), "+f"(d[14]), "+f"(d[15])
  : "r"(da), "r"(db), "n"(TA), "n"(TB), "n"(HA), "n"(HB));
}
template<int TA, int TB, uint32_t HA, uint32_t HB> __device__ __forceinline__ void wgmma_ss_n32(float (&d)[16], uint32_t da, uint32_t db, int scale_d){
  asm volatile("{\n.reg .pred p;\n.reg .b64 a, b;\nsetp.ne.b32 p, %22, 0;\nmov.b64 a, {%16, %20};\nmov.b64 b, {%17, %21};\n"
  "wgmma.mma_async.sync.aligned.m64n32k16.f32.bf16.bf16 {%0, %1, %2, %3, %4, %5, %6, %7, %8, %9, %10, %11, %12, %13, %14, %15}, a, b, p, 1, 1, %18, %19;\n}\n"
  : "+f"(d[0]), "+f"(d[1]), "+f"(d[2]), "+f"(d[3]), "+f"(d[4]), "+f"(d[5]), "+f"(d[6]), "+f"(d[7]), "+f"(d[8]), "+f"(d[9]), "+f"(d[10]), "+f"(d[11]), "+f"(d[12]), "+f"(d[13]), "+f"(d[14]), "+f"(d[15])
  : "r"(da), "r"(db), "n"(TA), "n"(TB), "n"(HA), "n"(HB), "r"(scale_d));
}
template<int TB, uint32_t HB> __device__ __forceinline__ void wgmma_ra_n32(float (&d)[16], uint32_t a0, uint32_t a1, uint32_t a2, uint32_t a3, uint32_t db){
  asm volatile("{\n.reg .pred p;\n.reg .b64 a, b;\nsetp.ne.b32 p, 1, 0;\nmov.b64 b, {%20, %22};\n"
  "wgmma.mma_async.sync.aligned.m64n32k16.f32.bf16.bf16 {%0, %1, %2, %3, %4, %5, %6, %7, %8, %9, %10, %11, %12, %13, %14, %15}, {%16,%17,%18,%19}, b, p, 1, 1, %21;\n}\n"
  : "+f"(d[0]), "+f"(d[1]), "+f"(d[2]), "+f"(d[3]), "+f"(d[4]), "+f"(d[5]), "+f"(d[6]), "+f"(d[7]), "+f"(d[8]), "+f"(d[9]), "+f"(d[10]), "+f"(d[11]), "+f"(d[12]), "+f"(d[13]), "+f"(d[14]), "+f"(d[15])
  : "r"(a0), "r"(a1), "r"(a2), "r"(a3), "r"(db), "n"(TB), "n"(HB));
}
template<int TB, uint32_t HB> __device__ __forceinline__ void wgmma_rs_n32(float (&d)[16], uint32_t a0, uint32_t a1, uint32_t a2, uint32_t a3, uint32_t db, int scale_d){
  asm volatile("{\n.reg .pred p;\n.reg .b64 a, b;\nsetp.ne.b32 p, %23, 0;\nmov.b64 b, {%20, %22};\n"
  "wgmma.mma_async.sync.aligned.m64n32k16.f32.bf16.bf16 {%0, %1, %2, %3, %4, %5, %6, %7, %8, %9, %10, %11, %12, %13, %14, %15}, {%16,%17,%18,%19}, b, p, 1, 1, %21;\n}\n"
  : "+f"(d[0]), "+f"(d[1]), "+f"(d[2]), "+f"(d[3]), "+f"(d[4]), "+f"(d[5]), "+f"(d[6]), "+f"(d[7]), "+f"(d[8]), "+f"(d[9]), "+f"(d[10]), "+f"(d[11]), "+f"(d[12]), "+f"(d[13]), "+f"(d[14]), "+f"(d[15])
  : "r"(a0), "r"(a1), "r"(a2), "r"(a3), "r"(db), "n"(TB), "n"(HB), "r"(scale_d));
}
template<int TB, uint32_t HB> __device__ __forceinline__ void wgmma_ra_n40(float (&d)[20], uint32_t a0, uint32_t a1, uint32_t a2, uint32_t a3, uint32_t db){
  asm volatile("{\n.reg .pred p;\n.reg .b64 a, b;\nsetp.ne.b32 p, 1, 0;\nmov.b64 b, {%24, %26};\n"
  "wgmma.mma_async.sync.aligned.m64n40k16.f32.bf16.bf16 {%0, %1, %2, %3, %4, %5, %6, %7, %8, %9, %10, %11, %12, %13, %14, %15, %16, %17, %18, %19}, {%20,%21,%22,%23}, b, p, 1, 1, %25;\n}\n"
  : "+f"(d[0]), "+f"(d[1]), "+f"(d[2]), "+f"(d[3]), "+f"(d[4]), "+f"(d[5]), "+f"(d[6]), "+f"(d[7]), "+f"(d[8]), "+f"(d[9]), "+f"(d[10]), "+f"(d[11]), "+f"(d[12]), "+f"(d[13]), "+f"(d[14]), "+f"(d[15]), "+f"(d[16]), "+f"(d[17]), "+f"(d[18]), "+f"(d[19])
  : "r"(a0), "r"(a1), "r"(a2), "r"(a3), "r"(db), "n"(TB), "n"(HB));
}
template<int TB, uint32_t HB> __device__ __forceinline__ void wgmma_rz_n40(float (&d)[20], uint32_t a0, uint32_t a1, uint32_t a2, uint32_t a3, uint32_t db){
  asm volatile("{\n.reg .pred p;\n.reg .b64 a, b;\nsetp.ne.b32 p, 0, 0;\nmov.b64 b, {%24, %26};\n"
  "wgmma.mma_async.sync.aligned.m64n40k16.f32.bf16.bf16 {%0, %1, %2, %3, %4, %5, %6, %7, %8, %9, %10, %11, %12, %13, %14, %15, %16, %17, %18, %19}, {%20,%21,%22,%23}, b, p, 1, 1, %25;\n}\n"
  : "=f"(d[0]), "=f"(d[1]), "=f"(d[2]), "=f"(d[3]), "=f"(d[4]), "=f"(d[5]), "=f"(d[6]), "=f"(d[7]), "=f"(d[8]), "=f"(d[9]), "=f"(d[10]), "=f"(d[11]), "=f"(d[12]), "=f"(d[13]), "=f"(d[14]), "=f"(d[15]), "=f"(d[16]), "=f"(d[17]), "=f"(d[18]), "=f"(d[19])
  : "r"(a0), "r"(a1), "r"(a2), "r"(a3), "r"(db), "n"(TB), "n"(HB));
}
template<int TB, uint32_t HB> __device__ __forceinline__ void wgmma_ra_n8(float (&d)[4], uint32_t a0, uint32_t a1, uint32_t a2, uint32_t a3, uint32_t db){
  asm volatile("{\n.reg .pred p;\n.reg .b64 a, b;\nsetp.ne.b32 p, 1, 0;\nmov.b64 b, {%8, %10};\n"
  "wgmma.mma_async.sync.aligned.m64n8k16.f32.bf16.bf16 {%0, %1, %2, %3}, {%4,%5,%6,%7}, b, p, 1, 1, %9;\n}\n"
  : "+f"(d[0]), "+f"(d[1]), "+f"(d[2]), "+f"(d[3])
  : "r"(a0), "r"(a1), "r"(a2), "r"(a3), "r"(db), "n"(TB), "n"(HB));
}
template<int TB, uint32_t HB> __device__ __forceinline__ void wgmma_rz_n8(float (&d)[4], uint32_t a0, uint32_t a1, uint32_t a2, uint32_t a3, uint32_t db){
  asm volatile("{\n.reg .pred p;\n.reg .b64 a, b;\nsetp.ne.b32 p, 0, 0;\nmov.b64 b, {%8, %10};\n"
  "wgmma.mma_async.sync.aligned.m64n8k16.f32.bf16.bf16 {%0, %1, %2, %3}, {%4,%5,%6,%7}, b, p, 1, 1, %9;\n}\n"
  : "=f"(d[0]), "=f"(d[1]), "=f"(d[2]), "=f"(d[3])
  : "r"(a0), "r"(a1), "r"(a2), "r"(a3), "r"(db), "n"(TB), "n"(HB));
}

constexpr int SEQ = 2048, DM = 1024, FF = 3584;
constexpr float LOG2E = 1.4426950408889634f;
constexpr uint32_t POLL_LIMIT = 1u << 22;
#define NPRE0 1
#define NPREN 2
constexpr int NPRE = NPREN;
#define QW 0
#define RS_N 22
#define RS_D1 430
#define RS_D2 300
#define SKM 0x154
#define LAG 2
#define PF_T0 5000
#define PF_DT 870
#define NFFN_L NFFN
#define FF_DT 500
#define OUT_U 1
#define GRES 8
#define OUT_L 0
#define TMASK 0xffffff
#define PMASK 0xffffff
#define FF_T0 1
#define GPRE 0
#define REL 2
#define EFI 11
#define TKW 8
#define SLOT 0
#define SLOTW 48
#define FF_ORD 0x76543210ba98ull
#define KT 0
#define KK(id) do { if (KT) { TK(32 * wg + (id)); } } while (0)
#define OUT_NS 60
constexpr int NFFN = 112;

constexpr uint32_t SB0 = 1024;
constexpr uint32_t KV_STAGE = 49152, R5 = 32768;
constexpr uint32_t OFF_X = 163840, OFF_S = 196608, OFF_WPHI = OFF_S + 20480, OFF_M = 229376, SMEM_BYTES = 232448;
constexpr uint32_t OFF_RS256 = 212992, OFF_ONES = OFF_RS256 + 1024, OFF_WPHIK1 = OFF_ONES + 1024, OFF_KVZ = OFF_S;
constexpr uint32_t OFF_WPHIK = OFF_S, OFF_BXK = OFF_S + 2048, OFF_AXK = OFF_S + 4096, OFF_G = OFF_S + 8192;
constexpr uint32_t OFF_AXQ = OFF_WPHI, OFF_BXQ = OFF_WPHI + 2048, OFF_WPHIQ = OFF_WPHI + 4096;
constexpr uint32_t B_FULLKV = OFF_M  , B_EMPTYKV = OFF_M + 32  ;
constexpr uint32_t B_EMPTY5 = OFF_M + 64  , B_UO = B_EMPTY5 + 48  , B_RC = B_UO + 32  ;
constexpr uint32_t B_OUT = B_RC + 16  , B_AUX = B_OUT + 32, B_AUXQ = B_AUX + 8, B_RX = B_AUXQ + 8;
constexpr uint32_t B_FULL5 = B_RX + 8  , B_FULLA = B_FULL5 + 48  , B_F = B_FULLA + 96  , B_WD = B_F + 64  ;
constexpr uint32_t B_WC = B_WD + 32  , B_DR = B_WC + 32  , B_W = B_DR + 24, B_OS = B_W + 8, B_R = B_W + 16, B_KD = B_W + 24, B_XS = B_W + 32, B_T = B_W + 40, B_G = B_W + 48, B_END = B_W + 56, B_S0 = B_END;
static_assert(B_S0 < OFF_M + 576 && B_END <= OFF_M + 568 && B_FULL5 + 40 >= OFF_M + 200 && B_FULL5 + 40 < OFF_M + 384, "barriers");
constexpr uint32_t OFF_EXC = OFF_M + 576, OFF_SUMWR = OFF_M + 608, OFF_EP = OFF_M + 624, OFF_KEY = OFF_M + 628;
constexpr uint32_t OFF_RSQ = OFF_M + 640, OFF_TL = OFF_M + 1152, OFF_T = OFF_M + 1792, OFF_WR = OFF_M + 2048, OFF_SCR = OFF_M + 2432;
constexpr uint32_t OFF_XSEL = 2 * R5, OFF_ACT = OFF_XSEL + 2048, OFF_GU = OFF_XSEL + 4096, OFF_OUT = 3 * R5;
constexpr uint64_t FF_SLOT = 0xdcdc3210dcbaull;
constexpr int KVP = 6 * 128;

enum { NB_G2E = 1, NB_XS = 2, NB_WG01 = 3, NB_ACT = 4, NB_Q0 = 5  , NB_ST = 14, NB_DN = 9, NB_ZERO = 10, NB_PUB = 11, NB_TOK = 10  , NB_L0 = 12  , NB_WG2 = 7, NB_QGO = 15 };

struct Scratch {
  bf16     o[SEQ * DM];
  float4   rstat[SEQ];
  uint32_t key[32 * 128];
  uint32_t cand[128 * DM];
  uint32_t ypart[NFFN * DM];
  float4   kvacc[32 * KVP];
  uint2    stats[SEQ];
  uint32_t cskv[2 * DM];
  uint32_t csq[4 * DM];
  uint32_t oset[128 * 16];
  uint32_t epoch;
};
__device__ __align__(1024) Scratch g_scr;
#define TS(id)
#define TDUMP()
#define TS0_DECL()
#define TS0_READ()
#define TS0_WRITE()
#define TK(id)
#define TSW(id)

struct Params {
  CUtensorMap x128, x64, wkv, wq, wo[2], wd, wg, wu, phi, tg, tu, td, xs, ws, qs;
  const bf16 *x, *wqkv, *wo_p, *wg_p, *wu_p, *wd_p, *wr;
  bf16* out_p;
  Scratch* g;
  uint32_t zero;
};

constexpr float EXP_LIM = 1.1529215e18f, ARG_LIM2 = 3600.f;
__device__ __forceinline__ void dual_exp2(const float (&p)[2][16], uint32_t (&ph)[4][8]) {
  #pragma unroll
  for (int h = 0; h < 2; h++)
    #pragma unroll
    for (int k = 0; k < 8; k++) { ph[2*h][k] = pack_bf16(ex2(p[h][2*k]), ex2(p[h][2*k+1])); ph[2*h+1][k] = pack_bf16(ex2(-p[h][2*k]), ex2(-p[h][2*k+1])); }
}
__device__ __forceinline__ void row_extremes(const float (&p)[16], const float (&c)[2], float (&m)[4]) {
  m[0] = m[2] = p[0]; m[1] = m[3] = p[2];
  #pragma unroll
  for (int i = 0; i < 16; i++) { m[(i >> 1) & 1] = fmaxf(m[(i >> 1) & 1], p[i]); m[2 + ((i >> 1) & 1)] = fminf(m[2 + ((i >> 1) & 1)], p[i]); }
  #pragma unroll
  for (int o = 1; o < 4; o <<= 1) {
    m[0] = fmaxf(m[0], __shfl_xor_sync(~0u, m[0], o)); m[1] = fmaxf(m[1], __shfl_xor_sync(~0u, m[1], o));
    m[2] = fminf(m[2], __shfl_xor_sync(~0u, m[2], o)); m[3] = fminf(m[3], __shfl_xor_sync(~0u, m[3], o));
  }
  m[0] *= -c[0]; m[1] *= -c[1]; m[2] *= c[0]; m[3] *= c[1];
}
__device__ __forceinline__ void dual_exp2_shifted(const float (&p)[2][16], uint32_t (&ph)[4][8]) {
  #pragma unroll
  for (int h = 0; h < 2; h++) {
    const float one[2] = {1.f, 1.f};
    float m[4];
    row_extremes(p[h], one, m);
    #pragma unroll
    for (int k = 0; k < 8; k++) {
      ph[2*h][k] = pack_bf16(ex2(p[h][2*k] + m[k & 1]), ex2(p[h][2*k+1] + m[k & 1]));
      ph[2*h+1][k] = pack_bf16(ex2(m[2 + (k & 1)] - p[h][2*k]), ex2(m[2 + (k & 1)] - p[h][2*k+1]));
    }
  }
}
__device__ __forceinline__ void row_sums(float (&s)[4][4], const uint32_t (&ph)[4][8], uint32_t ones) {
  #pragma unroll
  for (int i = 0; i < 4; i++) wgmma_rz_n8<0, H0>(s[i], ph[i][0], ph[i][1], ph[i][2], ph[i][3], ones);
  #pragma unroll
  for (int i = 0; i < 4; i++) wgmma_ra_n8<0, H0>(s[i], ph[i][4], ph[i][5], ph[i][6], ph[i][7], ones);
}
__device__ __forceinline__ uint32_t mul_bf16x2(uint32_t a, uint32_t b) { uint32_t r; asm("mul.rn.bf16x2 %0, %1, %2;" : "=r"(r) : "r"(a), "r"(b)); return r; }
__device__ __forceinline__ void normalize(uint32_t (&ph)[4][8], const float (&s)[4][4]) {
  #pragma unroll
  for (int i = 0; i < 4; i++) {
    const float i0 = rcp(s[i][0]), i1 = rcp(s[i][2]);
    const uint32_t n0 = pack_bf16(i0, i0), n1 = pack_bf16(i1, i1);
    #pragma unroll
    for (int k = 0; k < 4; k++) { ph[i][2*k] = mul_bf16x2(ph[i][2*k], n0); ph[i][2*k+1] = mul_bf16x2(ph[i][2*k+1], n1); }
  }
}
__device__ __forceinline__ void split_bf16(float a, float b, uint32_t& hi, uint32_t& lo) { hi = pack_bf16(a, b); lo = pack_bf16(a - bf_lo(hi), b - bf_hi(hi)); }
__device__ __forceinline__ void put_colsums(uint32_t base, int lane, float a, float b, float c, float d) {
  uint32_t h0, l0, h1, l1;
  split_bf16(a, b, h0, l0); split_bf16(c, d, h1, l1);
  const uint32_t ad = base + (lane >> 1) * 128 + (lane & 1) * 8;
  sts64(ad, h0, h1); sts64(ad + 16, l0, l1); sts64(ad + 32, h0, h1); sts64(ad + 48, l0, l1);
  sts128(base + (lane >> 1) * 128 + 64 + (lane & 1) * 32, 0, 0, 0, 0); sts128(base + (lane >> 1) * 128 + 80 + (lane & 1) * 32, 0, 0, 0, 0);
}
__device__ __forceinline__ float reduce8(const float (&v)[8], int lane) {
  const bool b4 = lane & 16, b3 = lane & 8, b2 = lane & 4;
  float a[4], b[2];
  #pragma unroll
  for (int i = 0; i < 4; i++) a[i] = (b4 ? v[4 + i] : v[i]) + __shfl_xor_sync(~0u, b4 ? v[i] : v[4 + i], 16);
  #pragma unroll
  for (int i = 0; i < 2; i++) b[i] = (b3 ? a[2 + i] : a[i]) + __shfl_xor_sync(~0u, b3 ? a[i] : a[2 + i], 8);
  return (b2 ? b[1] : b[0]) + __shfl_xor_sync(~0u, b2 ? b[0] : b[1], 4);
}
__device__ __forceinline__ bool tag_bad(uint4 v, uint32_t tg) { return (((v.x ^ tg) | (v.y ^ tg) | (v.z ^ tg) | (v.w ^ tg)) & 3) != 0; }

__global__ void __launch_bounds__(512, 1) fused_kernel(const __grid_constant__ Params P) {
  extern __shared__ __align__(1024) uint8_t smem_raw[];
  const uint32_t sb = smem_u32(smem_raw);
  const int tid = threadIdx.x, lane = tid & 31;
  TS0_DECL();
  TS0_READ();
  if (tid == 352) { prefetch_map(&P.wkv); prefetch_map(&P.x128); }
  const int cp = blockIdx.x >> 1, rank = blockIdx.x & 1;
  const int cr = cp < 4 ? 32 + 8 * cp : cp - 4 + max((cp * 37 - 1076) >> 8, 0);
  const int c = (cr & 62) + 64 * (cr & 1) + rank;
  const int m256 = c >> 4, nkv = c & 15, m128 = c >> 3, j = c & 7;
  if ((tid >> 5) == 12 && elect_one()) {
    mbar_init(sb + B_S0, 1); mbar_init(sb + B_FULLKV, 1); mbar_init(sb + B_FULLKV + 8, 1);
    fence_async_smem();
    mbar_expect_tx(sb + B_S0, 32768);
    tma_4d(sb + 32768, &P.wkv, 0, 0, nkv, 1, sb + B_S0);
    tma_2d(sb, &P.x128, 0, 256 * m256, sb + B_S0);
    mbar_expect_tx(sb + B_FULLKV, 16384);
    tma_2d(sb + 16384, &P.x128, 0, 256 * m256 + 128, sb + B_FULLKV);
    if (NPRE0 > 1) {
      mbar_expect_tx(sb + B_FULLKV + 8, KV_STAGE);
      tma_4d(sb + KV_STAGE + 32768, &P.wkv, 0, 64, nkv, 1, sb + B_FULLKV + 8);
      tma_2d(sb + KV_STAGE, &P.x128, 64, 256 * m256, sb + B_FULLKV + 8);
      tma_2d(sb + KV_STAGE + 16384, &P.x128, 64, 256 * m256 + 128, sb + B_FULLKV + 8);
    }
    asm volatile("fence.mbarrier_init.release.cluster;" ::: "memory");
  }
  #pragma unroll
  for (int w = 0; w < 3; w++)
    if (tid == 32 + 32 * w) {
      #pragma unroll
      for (uint32_t b = B_FULLKV + 16 + 184 * w; b < B_FULLKV + 200 + 184 * w && b < B_END; b += 8)
        mbar_init(sb + b, b < B_EMPTYKV ? 1 : b < B_EMPTY5 ? 12 : b < B_OUT ? 4 : b < B_RX || b == B_W ? 2 : b == B_RX ? 8 : 1);
      if (w == 1) mbar_arrive(sb + B_FULL5 + 40);
      asm volatile("fence.mbarrier_init.release.cluster;" ::: "memory");
      fence_async_smem();
    }
  const int warp = __shfl_sync(~0u, tid >> 5, 0), wg = warp >> 2, wp = warp & 3;
  const int f = 16 * ((cr + 7) & 7) + 2 * (cr >> 3) + rank;
  const int ha = 4 * (nkv >> 1) + (nkv & 1);
  Scratch* const G = P.g;
  if ((sb & 0x3ffff) != SB0) asm volatile("trap;");
  __syncthreads();
  cluster_arrive();
  if (warp == 12) {
    TK(88 - 32);
    if (elect_one()) {
      #pragma unroll
      for (int s = NPRE0; s < NPRE; s++) {
        const uint32_t st = sb + s * KV_STAGE, fb = sb + B_FULLKV + 8 * s;
        mbar_expect_tx(fb, KV_STAGE);
        tma_4d(st + 32768, &P.wkv, 0, 64 * s, nkv, 1, fb);
        tma_2d(st, &P.x128, 64 * s, 256 * m256, fb);
        tma_2d(st + 16384, &P.x128, 64 * s, 256 * m256 + 128, fb);
      }
    }
    __syncwarp();
  }

  if (wg == 3) {
    asm volatile("setmaxnreg.dec.sync.aligned.u32 32;");
    cluster_wait();
    if (wp == 0) { TK(89 - 32); }
    const bool el = elect_one();
    const uint64_t ef = policy_evict_first(), en = policy_evict_normal();
    auto fetch_o = [&](const int t0, uint32_t so, uint32_t par) {
      const int sh = t0 & 1;
      uint32_t ready = 0;
      const bf16* base = G->o + (m128 * 16 + t0) * 8192 + rank * 4096;
      const bf16* hint = base + (lane & 3) * 1024 + 966 + (((j & 6) + ((lane >> 2) & ~sh)) & 7) * 16384 + 8 * sh * (~lane & 4);
      #pragma unroll 1
      for (int i = 2 - 2 * sh; i < 8; i += 1 + sh) {
        uint32_t it = 0;
        while ((~ready >> (4 * i) & (15 + 240 * sh)) && ++it < POLL_LIMIT) ready = __ballot_sync(~0u, ld32_rlx(hint) != ~0u);
        mbar_wait(sb + B_EMPTY5 + so, par);
        if (el) {
          bulk_g2s_mc(sb + so * 4096 + rank * 8192, base + (((j & 6) + i) & 7) * 16384, 8192, sb + B_FULLA + 2 * so + 8 * rank, ef);
          if (i == 2 - 2 * sh) TS(t0 == 0 ? (rank ? 4 : 12) : t0 == 3 ? (rank ? 31 : 10) : (rank ? 9 : 13));
        }
        so += 8;
        if (so == 48) { so = 0; par ^= 1; }
      }
    };
    if (wp == 0) {
      {
        #pragma unroll 1
        for (int kb = NPRE; kb < 16; kb++) {
          const uint32_t st = sb + (kb & 3) * KV_STAGE, fb = sb + B_FULLKV + 8 * (kb & 3);
          mbar_wait(fb + (B_EMPTYKV - B_FULLKV), ~(kb >> 2) & 1);
          if (el) {
            mbar_expect_tx(fb, KV_STAGE);
            tma_2d_mc(st + rank * 16384, &P.x128, 64 * kb, 256 * m256 + 128 * rank, fb);
            tma_4d_h(st + 32768, &P.wkv, 0, 64 * kb, nkv, 1, fb, ef);
          }
        }
        TS0_WRITE();
        uint64_t ord = 0xf3120edcba987654ull;
        uint32_t so = 0, par = 1;
        #pragma unroll 1
        for (int i = 0; i < 16; i++) {
          const uint32_t st = sb + so * 4096, fb = sb + B_FULL5 + so;
          const int k0 = (64 * (uint32_t)ord + 128 * (j & 6)) & 960;
          mbar_wait(i < 5 ? sb + B_EMPTYKV + so - (i > 1 ? 8 : 0) : fb + (B_EMPTY5 - B_FULL5), par);
          if (el) {
            mbar_expect_tx(fb, R5);
            tma_2d_mc_h(st + rank * 8192, &P.x64, k0, 128 * m128 + 64 * rank, fb, i >= EFI ? ef : en);
            tma_3d_h(st + 16384, &P.wq, 0, k0, 2 * j, fb, ef);
          }
          ord >>= 4; so += 8;
          if (so == 40) { so = 0; par ^= 1; }
        }
        #pragma unroll 1
        for (int i = 0; i < 19; i++) {
          const uint32_t fb = sb + B_FULL5 + so, fa = sb + B_FULLA + 2 * so, na = i == rank ? 0 : 8192;
          if (i == 1) { mbar_wait2(sb + B_FULL5 + 16, 0, sb + B_FULL5 + 24, 0); mbar_wait(sb + B_FULL5 + 32, 0); if (el) mbar_arrive(sb + B_R); }
          mbar_wait(fb + (B_EMPTY5 - B_FULL5), par);
          if (SLOT) { while (((uint32_t)clock() & (uint32_t)(SLOT - 1)) >= SLOTW) {} }
          if (el) {
            if (i < 16) {
              mbar_expect_tx(fb, 16384);
              const int row = i < 8 ? 128 * (((j & 6) + i) & 7) : 256 * (((j >> 1) + i) & 3) + 32 + 16 * (i & 4);
              tma_5d_h(sb + so * 4096 + 16384, &P.wo[i >> 3], 128 * j, row, fb, ef);
              tma_5d_h(sb + so * 4096 + 24576, &P.wo[i >> 3], 128 * j + 64, row, fb, ef);
              mbar_expect_tx(fa, na); mbar_expect_tx(fa + 8, na);
            } else mbar_arrive(sb + B_DR + 8 * (i - 16));
          }
          so += 8;
          if (so == 48) { so = 0; par ^= 1; }
        }
      }
    } else if (wp == 3) {
      const uint32_t t_start = (uint32_t)clock();
      if (el) {
        mbar_expect_tx(sb + B_W, 12288);
        #pragma unroll 1
        for (int i = 0; i < 6; i++) tma_2d(sb + (i == 0 ? OFF_WPHIK : i == 1 ? OFF_WPHIK1 : OFF_WPHIQ + 2048 * (i - 2)), &P.phi, 0, 32 * (i < 2 ? 2 * nkv + i : 4 * j + 2 * (i & 1) + ((i - 2) >> 1)), sb + B_W);
        prefetch_map(&P.x64); prefetch_map(&P.wq); prefetch_map(&P.wo[0]); prefetch_map(&P.wo[1]);
        prefetch_map(&P.wd); prefetch_map(&P.wg); prefetch_map(&P.wu);
      }
      #pragma unroll 1
      for (int i = 0; i < 8; i++) {
        st128_rlx(&G->cand[(m128 * 8 + i) * DM + (lane >> 4) * 512 + 64 * j + 4 * (lane & 15)], ~0u, ~0u, ~0u, ~0u);
        if (f < NFFN) st128_rlx(&G->ypart[f * DM + 128 * i + 4 * lane], ~0u, ~0u, ~0u, ~0u);
      }
      if (lane < 16) st128_rlx(&G->rstat[16 * c + lane], 0, 0, 0, 0);
      {
        const uint32_t nt = ld32_rlx(&G->epoch);
        if (lane < 8) { st128_rlx(&G->stats[16 * c + 2 * lane], nt, nt, nt, nt); st128_rlx(&G->csq[32 * c + 4 * lane], nt, nt, nt, nt); }
        if (lane < 4) { st128_rlx(&G->cskv[128 * nkv + 16 * m256 + 4 * lane], nt, nt, nt, nt); st128_rlx(&G->oset[16 * c + 4 * lane], nt, nt, nt, nt); }
      }
      if (lane < 8) st128_rlx(&G->key[(4 * j + (lane >> 1)) * 128 + m128 * 8 + 4 * (lane & 1)], 0, 0, 0, 0);
      if (c < 32) {
        #pragma unroll 1
        for (int i = lane; i < KVP; i += 32) st128_rlx(&G->kvacc[(ha + 2 * m256) * KVP + i], 0, 0, 0, 0);
      }
      fence_gpu();
      bar_arrive(NB_ZERO, 160);
      if (el) {
        #pragma unroll 1
        for (int i = 0; i < 30; i++) {
          while ((uint32_t)clock() - t_start < (uint32_t)(PF_T0 + PF_DT * i)) __nanosleep(64);
          if (i < 4) { bulk_prefetch(P.wqkv + (size_t)(256 * i + c) * (3 * DM), 2048); bulk_prefetch(P.wqkv + (size_t)(256 * i + 128 + c) * (3 * DM), 2048); }
          else if (i < 6) bulk_prefetch(P.wo_p + (size_t)c * 8192 + (i - 4) * 4096, 8192);
          else if ((TMASK >> (i - 6)) & 1) {
            const int k = i - 6;
            if (f < NFFN) {
              if (k < 16) {
                #pragma unroll 1
                for (int e = 0; e < 4; e++) tma_2d(sb + OFF_T, rank ? &P.tu : &P.tg, 32 * (f & ~1), 64 * k + 16 * e, sb + B_T);
              } else { tma_2d(sb + OFF_T, &P.td, 0, 256 * f + 32 * (k - 16), sb + B_T); tma_2d(sb + OFF_T, &P.td, 0, 256 * f + 32 * (k - 16) + 16, sb + B_T); }
            }
          }
          else if (!((PMASK >> (i - 6)) & 1)) {}
          else if (i < 22) bulk_prefetch(((i & 1) ? P.wu_p : P.wg_p) + (size_t)((i - 6) >> 1) * 458752 + c * 3584, 7168);
          else bulk_prefetch(P.wd_p + (size_t)(i - 22) * 458752 + c * 3584, 7168);
        }
      }
      __syncwarp();
      mbar_wait2(sb + B_OS, 0, sb + B_RX, 0);
      #pragma unroll 1
      for (int t0 = 0; t0 < 4; t0 += 3) fetch_o(t0, t0 ? 8 : 24, 0);
    } else {
      const int half = wp - 1;
      const uint32_t ep1 = ld32_rlx(&G->epoch) + 1, tg = ep1 & 3;
      {
        uint32_t it = 0;
        sts128(sb + OFF_ONES + half * 512 + lane * 16, 0x3f803f80u, 0x3f803f80u, 0x3f803f80u, 0x3f803f80u);
        auto reset_o = [&](int i0, int i1, uint32_t dt) {
          uint32_t t0 = (uint32_t)clock();
          #pragma unroll 1
          for (int i = i0; i < i1; i++) {
            st128_rlx(G->o + (m128 * 16 + 2 * j + half) * 8192 + 256 * i + 8 * lane, ~0u, ~0u, ~0u, ~0u);
            while ((uint32_t)clock() - t0 < dt) __nanosleep(40);
            t0 += dt;
          }
        };
        mbar_wait(sb + B_S0, 0);
        reset_o(0, RS_N, RS_D1);
        bar_sync(NB_PUB, 192);
        const uint4* src = reinterpret_cast<const uint4*>(&G->stats[256 * m256 + 128 * half]) + lane;
        const uint4* srk = reinterpret_cast<const uint4*>(&G->cskv[128 * nkv]) + lane;
        uint4 v0, v1, vk;
        it = 0;
        do { v0 = ld128_rlx(src); v1 = ld128_rlx(src + 32); vk = ld128_rlx(srk); }
        while ((tag_bad(v0, tg) || tag_bad(v1, tg) || tag_bad(vk, tg)) && ++it < POLL_LIMIT);
        fence_acquire_gpu();
        if (half) put_colsums(sb + OFF_BXK, lane, untag(vk.x), untag(vk.y), untag(vk.z), untag(vk.w));
        #pragma unroll
        for (int i = 0; i < 2; i++) {
          const uint4 v = i ? v1 : v0;
          uint32_t hi, lo;
          split_bf16(-0.5f * untag(v.x), -0.5f * untag(v.z), hi, lo);
          const uint32_t h0 = __byte_perm(hi, hi, 0x1010), h1 = __byte_perm(hi, hi, 0x3232), l0 = __byte_perm(lo, lo, 0x1010), l1 = __byte_perm(lo, lo, 0x3232);
          const uint32_t a = sb + OFF_AXK + half * 2048 + i * 1024 + lane * 32;
          sts128(a, h0, l0, 0, 0); sts128(a + 16, h1, l1, 0, 0);
          sts64(sb + OFF_RS256 + half * 512 + i * 256 + lane * 8, v.y & ~3u, v.w & ~3u);
          if (half == (m128 & 1)) {
            const uint32_t aq = sb + OFF_AXQ + i * 1024 + lane * 32;
            sts128(aq, h0, l0, 0, 0); sts128(aq + 16, h1, l1, 0, 0);
            sts64(sb + OFF_RSQ + i * 256 + lane * 8, v.y & ~3u, v.w & ~3u);
          }
        }
        fence_async_smem();
        __syncwarp();
        if (el) { sts32(sb + OFF_EP, ep1); mbar_arrive(sb + B_AUX); if (!half) TS(1); }
        reset_o(RS_N, 32, RS_D2);
        fence_gpu();
        __syncwarp();
        if (el) { st32_rlx(&G->oset[16 * c + 8 * half], ep1); if (half) mbar_arrive(sb + B_AUXQ); }
        if (!half) {
          const uint4* src = reinterpret_cast<const uint4*>(&G->csq[128 * j]) + lane;
          uint4 v0, v1, v2, v3;
          do { v0 = ld128_rlx(src); v1 = ld128_rlx(src + DM / 4); v2 = ld128_rlx(src + DM / 2); v3 = ld128_rlx(src + 3 * DM / 4); }
          while ((tag_bad(v0, tg) || tag_bad(v1, tg) || tag_bad(v2, tg) || tag_bad(v3, tg)) && ++it < POLL_LIMIT);
          put_colsums(sb + OFF_BXQ, lane, (untag(v0.x) + untag(v1.x)) + (untag(v2.x) + untag(v3.x)), (untag(v0.y) + untag(v1.y)) + (untag(v2.y) + untag(v3.y)),
                      (untag(v0.z) + untag(v1.z)) + (untag(v2.z) + untag(v3.z)), (untag(v0.w) + untag(v1.w)) + (untag(v2.w) + untag(v3.w)));
          fence_async_smem();
          __syncwarp();
          if (el) mbar_arrive(sb + B_AUXQ);
        }
      }
      if (half == 0) {
        for (uint32_t it = 0; __any_sync(~0u, ld32_rlx(&G->oset[m128 * 128 + 8 * (lane & 15)]) != ep1) && it < POLL_LIMIT; it++) {}
        fence_acquire_gpu();
        if (el) mbar_arrive(sb + B_OS);
      }
      if (!half) {
        #pragma unroll 1
        for (int hh = 0; hh < 2; hh++) {
          const uint32_t src = sb + (1 + rank) * R5 + hh * 8192, fa = sb + B_FULLA + 16 + 16 * rank + 8 * hh;
          mbar_wait(fa, 0);
          mbar_wait(sb + B_UO + 8 * hh, 0);
          if (el) bulk_s2peer(mapa(src, rank ^ 1), src, 8192, mapa(fa, rank ^ 1));
        }
        fetch_o(1, 24, 1);
      }
      else if (f < NFFN_L) {
        mbar_wait2(sb + B_UO, 0, sb + B_UO + 8, 0);
        mbar_wait(sb + B_UO + 24, 0);
        uint32_t t0 = (uint32_t)clock();
        while ((uint32_t)clock() - t0 < (uint32_t)FF_T0) __nanosleep(32);
        t0 -= FF_DT;
        #pragma unroll 1
        for (int i = 0; i < 12; i++) {
          const int e = (FF_ORD >> (4 * i)) & 15;
          const uint32_t dst = sb + 16384 * ((FF_SLOT >> (4 * e)) & 15), fb = sb + B_F + 8 * e;
          if (i >= 2) mbar_wait(sb + B_WC + 8 * ((0x100066553244ull >> (4 * e)) & 15), 0);
          while ((uint32_t)clock() - t0 < (uint32_t)FF_DT) __nanosleep(32);
          t0 = (uint32_t)clock();
          if (i < 8) { TK(48 + i); }
          if (el) {
            mbar_expect_tx(fb, 16384);
            if (e >= 8) tma_3d_h(dst, &P.wd, 0, 32 * f, 4 * e - 32, fb, ef);
            else { tma_2d(dst, &P.wg, 32 * f, 128 * e, fb); tma_2d(dst + 8192, &P.wu, 32 * f, 128 * e, fb); }
          }
        }
      }
      __syncwarp();
    }
    {
      const int ch = lane & 15, rb = 32 * wp + (lane >> 4);
      const uint32_t src = sb + OFF_OUT + (ch >> 3) * 16384;
      bf16* dst = P.out_p + (size_t)(128 * m128) * DM + 128 * j + 8 * ch;
      __syncwarp();
      mbar_wait(sb + B_OUT + 8 * wp, 0);
      const float2 ex = lds64f(sb + OFF_EXC + 8 * wp);
      if (OUT_L) mbar_wait(sb + B_XS, 0);
      #pragma unroll 1
      for (int i = 0; i < 32; i += 2 * OUT_U) {
        uint4 v[OUT_U];
        #pragma unroll
        for (int e = 0; e < OUT_U; e++) { const int r = rb + i + 2 * e; v[e] = lds128(src + r * 128 + (((ch ^ r) & 7) << 4)); }
        #pragma unroll
        for (int e = 0; e < OUT_U; e++) { const int r = rb + i + 2 * e; if (r != __float_as_int(i < 16 ? ex.x : ex.y)) *reinterpret_cast<uint4*>(dst + r * DM) = v[e]; }
        if (OUT_NS) __nanosleep(OUT_NS);
      }
      if (wp == 0) { TK(63); }
      mbar_wait(sb + B_XS, 0);
      const int row = 2047 - (__float_as_uint(ldsf(sb + OFF_KEY)) & 2047) - 128 * m128, r = __float_as_int(lane < 16 ? ex.x : ex.y);
      if (r != row) *reinterpret_cast<uint4*>(dst + r * DM) = lds128(src + r * 128 + (((ch ^ r) & 7) << 4));
    }
    __syncwarp();
    cluster_arrive(); cluster_wait();
    return;
  }

  asm volatile("setmaxnreg.inc.sync.aligned.u32 160;");
  cluster_wait();
  const int t = tid & 127, g = lane >> 2;
  const uint32_t sa = (16 * wp + (lane & 15)) * 128 + (((lane >> 4) ^ (lane & 7)) << 4);

  if (wg == 2) {
    float s[2] = {0.f, 0.f}, s2[2] = {0.f, 0.f}, ck[8] = {0.f, 0.f, 0.f, 0.f, 0.f, 0.f, 0.f, 0.f}, cs[8] = {0.f, 0.f, 0.f, 0.f, 0.f, 0.f, 0.f, 0.f};
    const uint32_t ebr = mapa(sb + B_EMPTYKV, lane & 1), tg = (ld32_rlx(&G->epoch) + 1) & 3;
    auto addx = [&](const uint4 v) {
      const uint32_t w[4] = {v.x, v.y, v.z, v.w};
      #pragma unroll
      for (int e = 0; e < 4; e++) { const float a = bf_lo(w[e]), d = bf_hi(w[e]); s[0] += a; s[1] += d; s2[0] = fmaf(a, a, s2[0]); s2[1] = fmaf(d, d, s2[1]); }
    };
    auto addc = [&](const uint4 v, float (&o)[8]) {
      o[0] += bf_lo(v.x); o[1] += bf_hi(v.x); o[2] += bf_lo(v.y); o[3] += bf_hi(v.y); o[4] += bf_lo(v.z); o[5] += bf_hi(v.z); o[6] += bf_lo(v.w); o[7] += bf_hi(v.w);
    };
    {
      const uint32_t ra = (16 * nkv + (t >> 3)) * 128 + (t & 7) * 16;
      const uint32_t ca = 32768 + (m256 >> 2) * 8192 + (t >> 1) * 128 + (((2 * (m256 & 3) + (t & 1)) ^ ((t >> 1) & 7)) << 4);
      int rd = 0;
      mbar_wait(sb + B_S0, 0);
      #pragma unroll 1
      for (int kb = 0; kb < 10; kb++) {
        const uint32_t st = sb + (kb & 3) * KV_STAGE;
        mbar_wait(sb + B_FULLKV + 8 * (kb & 3), (kb >> 2) & 1);
        const uint4 x0 = lds128(st + ra), w0 = lds128(st + ca);
        addx(x0); addc(w0, ck);
        __syncwarp();
        if (lane < 2) mbar_arrive_remote(ebr + 8 * (kb & 3), 1);
        if ((SKM >> kb) & 1) {
          if (rd) {
            mbar_wait(sb + B_G, (rd - 1) & 1);
            const uint32_t a = sb + OFF_G + (t >> 3) * 256 + (t & 7) * 16;
            const uint4 x1 = lds128(a), x2 = lds128(a + 128), w1 = lds128(sb + OFF_G + 4096 + t * 16), w2 = lds128(sb + OFF_G + 6144 + t * 16);
            addx(x1); addx(x2); addc(w1, ck); addc(w2, ck);
            bar_sync(NB_WG2, 128);
          }
          if (wp == 0 && elect_one()) {
            mbar_expect_tx(sb + B_G, 8192);
            if (rd < 3) {
              tma_2d(sb + OFF_G, &P.xs, 640 + 128 * rd, 256 * m256 + 16 * nkv, sb + B_G);
              tma_2d(sb + OFF_G + 4096, &P.ws, (1 + (m256 >> 2)) * DM + 64 * nkv + 16 * (m256 & 3), 640 + 128 * rd, sb + B_G);
            } else tma_2d(sb + OFF_G, &P.qs, 32 * (c & 31), 256 * (c >> 5), sb + B_G);
          }
          rd++;
        }
      }
    }
    TK(82);
    const uint32_t scr = sb + OFF_SCR + 128;
    float sx = s[0] + s[1], sq = s2[0] + s2[1];
    #pragma unroll
    for (int o = 1; o < 8; o <<= 1) { sx += __shfl_xor_sync(~0u, sx, o); sq += __shfl_xor_sync(~0u, sq, o); }
    float v = reduce8(ck, lane);
    v += __shfl_xor_sync(~0u, v, 2);
    if (!(lane & 2)) stsf(scr + (wp * 16 + 8 * (lane & 1) + (lane >> 2)) * 4, v);

    bar_sync(NB_ZERO, 160);
    if ((lane & 7) == 0) {
      const float mean = sx * (1.f / DM);
      st64_rlx(&G->stats[256 * m256 + 16 * nkv + (t >> 3)], tagw(mean, tg), tagw(rsqrtf(fmaxf(sq * (1.f / DM) - mean * mean, 0.f) + 1e-5f), tg));
    }
    if (wp == 1 && lane < 16) {
      const uint32_t a = scr + lane * 4;
      st32_rlx(&G->cskv[128 * nkv + 16 * m256 + lane], tagw((ldsf(a) + ldsf(a + 64)) + (ldsf(a + 128) + ldsf(a + 192)), tg));
    }
    __syncwarp();
    bar_arrive(NB_PUB, 192);
    TSW(23);
    const uint4 wv = ld128_keep(P.wr + t * 8);
    #pragma unroll 1
    for (int i = 0; i < 2; i++) {
      mbar_wait(sb + B_G, i ^ 1);
      const uint32_t a = sb + OFF_G + t * 16;
      const uint4 u0 = lds128(a), u1 = lds128(a + 2048), u2 = lds128(a + 4096), u3 = lds128(a + 6144);
      addc(u0, cs); addc(u1, cs); addc(u2, cs); addc(u3, cs);
      bar_sync(NB_WG2, 128);
      if (i == 0 && wp == 0 && elect_one()) { mbar_expect_tx(sb + B_G, 8192); tma_2d(sb + OFF_G, &P.qs, 32 * (c & 31), 256 * (c >> 5) + 128, sb + B_G); }
    }
    if (t == 0) mbar_arrive(sb + B_W);
    float sw = (bf_lo(wv.x) + bf_hi(wv.x)) + (bf_lo(wv.y) + bf_hi(wv.y)) + (bf_lo(wv.z) + bf_hi(wv.z)) + (bf_lo(wv.w) + bf_hi(wv.w));
    #pragma unroll
    for (int o = 16; o; o >>= 1) sw += __shfl_xor_sync(~0u, sw, o);
    if (lane == 0) stsf(sb + OFF_SUMWR + wp * 4, sw);
    if ((t >> 4) == j) {
      const uint32_t a = sb + OFF_WR + (t & 15) * 32;
      sts128(a, wv.x << 16, wv.x & 0xffff0000u, wv.y << 16, wv.y & 0xffff0000u);
      sts128(a + 16, wv.z << 16, wv.z & 0xffff0000u, wv.w << 16, wv.w & 0xffff0000u);
    }
    v = reduce8(cs, lane);
    stsf(scr + (wp * 32 + 8 * (lane & 3) + (lane >> 2)) * 4, v);
    bar_sync(NB_WG2, 128);
    if (wp == 0) {
      const uint32_t a = scr + lane * 4;
      st32_rlx(&G->csq[(c >> 5) * DM + 32 * (c & 31) + lane], tagw((ldsf(a) + ldsf(a + 128)) + (ldsf(a + 256) + ldsf(a + 384)), tg));
    }
  }

  uint32_t xr[32];
  {
    const bool isq = wg == 2;
    float acc[2][64];
    {
      const uint32_t emptyb = mapa(sb + (isq ? B_EMPTY5 : B_EMPTYKV), t & 1);
      if (!isq) {
        mbar_wait(sb + B_S0, 0);
        if (wg) mbar_wait(sb + B_FULLKV, 0);
        if (wg == 0) { TSW(2); }
        #pragma unroll 1
        for (int kb = 0; kb < 16; kb++) {
          if (!KT && wg == 0) { TK(kb); }
          const uint32_t da = dlo(SB0, 16) + wg * 1024 + (kb & 3) * (KV_STAGE >> 4), db = dlo(SB0 + 32768, 8192) + (kb & 3) * (KV_STAGE >> 4);
          wg_fence();
          #pragma unroll
          for (int k = 0; k < 4; k++) {
            wgmma_ss_n128<0, 1, H128, H128>(acc[0], da + 2 * k, db + 128 * k, k > 0 || kb != 0);
            wgmma_ss_n128<0, 1, H128, H128>(acc[1], da + 512 + 2 * k, db + 128 * k, k > 0 || kb != 0);
          }
          wg_commit();
          wg_wait<1>();
          if (kb > 0 && t < 2) mbar_arrive_remote(emptyb + 8 * ((kb - 1) & 3), kb > 10 ? 3 : 1);
          if (kb < 15) mbar_wait(sb + B_FULLKV + 8 * ((kb + 1) & 3), ((kb + 1) >> 2) & 1);
          if (kb == 15 - LAG && wg == 1) bar_sync(NB_WG01, 256);
        }
        bar_arrive(wg ? NB_QGO : NB_WG01, 256);
      } else {
        uint32_t so = 0, po = 0, par = 0;
        mbar_wait(sb + B_FULL5, 0);
        bar_sync(NB_QGO, 256);
        TSW(11);
        #pragma unroll 1
        for (int kb = 0; kb < 16; kb++) {
          TK(16 + kb);
          const uint32_t da = dlo(SB0, 16) + so * 256, db = dlo(SB0 + 16384, 8192) + so * 256;
          #pragma unroll
          for (int k = 0; k < 4; k++) {
            wg_fence();
            wgmma_ss_n128<0, 1, H128, H128>(acc[0], da + 2 * k, db + 128 * k, k > 0 || kb != 0);
            wgmma_ss_n128<0, 1, H128, H128>(acc[1], da + 512 + 2 * k, db + 128 * k, k > 0 || kb != 0);
            wg_commit();
            if (k == 1 && kb > 0 && t < 2) mbar_arrive_remote(emptyb + po, 2);
            if (k == 3) {
              po = so; so += 8;
              if (so == 40) { so = 0; par ^= 1; }
              if (kb < 15) mbar_wait(sb + B_FULL5 + so, par);
            }
            if ((QW >> k) & 1) wg_wait<2>(); else wg_wait<1>();
          }
        }
        mbar_wait(sb + B_AUXQ, 0);
      }
      mbar_wait(sb + B_AUX, 0);
      const uint32_t xa = dlo(SB0, 0) + (isq ? OFF_AXQ >> 4 : (OFF_AXK >> 4) + wg * 128), xb = dlo(SB0, 0) + (isq ? OFF_BXQ >> 4 : OFF_BXK >> 4);
      wg_fence();
      wgmma_sa_n128<0, 1, H0, H0>(acc[0], xa, xb);
      wgmma_sa_n128<0, 1, H0, H0>(acc[1], xa + 64, xb);
      wg_commit();
      if (isq) mbar_wait(sb + B_RC, 0);
      wg_wait<0>();
      if (t < 2) mbar_arrive_remote(emptyb + (isq ? 0 : 24), isq ? 2 : 3);
      if (wg != 1) { TSW(wg ? 8 : 3); }
      fence_regs(acc[0]); fence_regs(acc[1]);
    }
    if (isq) {
      #pragma unroll
      for (int i = 0; i < 2; i++) {
        const uint32_t ta = sb + (1 + rank) * R5 + sa + i * 8192;
        if (i == 1) mbar_wait(sb + B_RC + 8, 0);
        #pragma unroll
        for (int k = 0; k < 4; k++) {
          const float* a = &acc[i][32 * (k >> 1) + 8 * (k & 1)];
          stsm4(ta ^ (k << 5), pack_bf16(a[0], a[1]), pack_bf16(a[2], a[3]), pack_bf16(a[4], a[5]), pack_bf16(a[6], a[7]));
        }
        fence_async_smem();
        bar_arrive(NB_Q0 + i, 256);
      }
      #pragma unroll
      for (int i = 0; i < 32; i++) { const float* a = &acc[(i >> 3) & 1][16 + 32 * (i >> 4) + 2 * (i & 7)]; xr[i] = pack_bf16(a[0], a[1]); }
      TSW(26);
    } else {
      const uint32_t stg = sb + OFF_X + (1 - wg) * 24576;
      const uint32_t va = stg + 16384 + (16 * wp + (lane & 15)) * 64 + (((lane >> 4) ^ ((lane >> 1) & 3)) << 4);
      const uint32_t ra = sb + OFF_RS256 + (128 * wg + 16 * wp + g) * 4;
      const float rs[4] = {ldsf(ra), ldsf(ra + 32), ldsf(ra + 256), ldsf(ra + 288)};
      float p[2][16];
      uint32_t vf[16], kf[2][16];
      auto project = [&](const uint32_t (&f)[16], uint32_t db) {
        wg_fence();
        #pragma unroll
        for (int i = 0; i < 2; i++) {
          wgmma_rs_n32<1, H64>(p[i], f[8*i], f[8*i+1], f[8*i+2], f[8*i+3], db, 0);
          wgmma_ra_n32<1, H64>(p[i], f[8*i+4], f[8*i+5], f[8*i+6], f[8*i+7], db + 64);
        }
        wg_commit();
      };
      auto fold = [&](uint32_t (&f)[16], int col, float sc) {
        #pragma unroll
        for (int i = 0; i < 16; i++) {
          const float r = rs[2 * (i >> 3) + (i & 1)] * sc;
          f[i] = pack_bf16(acc[i >> 3][col + 2 * (i & 7)] * r, acc[i >> 3][col + 2 * (i & 7) + 1] * r);
          asm volatile("" : "+r"(f[i]));
        }
      };
      auto put_v = [&](const uint32_t (&f)[16]) {
        #pragma unroll
        for (int k = 0; k < 4; k++) stsm4((va ^ ((k & 1) << 5)) + (k >> 1) * 4096, f[4*k], f[4*k+1], f[4*k+2], f[4*k+3]);
      };
      KK(0);
      fold(vf, 48, 1.f);
      mbar_wait(sb + B_W, 0);
      fold(kf[0], 0, LOG2E);
      #pragma unroll
      for (int i = 0; i < 32; i++) p[i >> 4][i & 15] = acc[i >> 4][i & 15];
      project(kf[0], dlo(SB0 + OFF_WPHIK, 16));
      mbar_wait(sb + B_W, 0);
      KK(1);
      {
        uint32_t v0[16];
        fold(kf[1], 16, LOG2E);
        fold(v0, 32, 1.f);
        if (wg == 1) bar_sync(NB_DN, 256);
        put_v(v0);
      }
      wg_wait<0>();
      fence_regs(p[0]); fence_regs(p[1]);
      if (wg == 1) bar_arrive(NB_WG01, 256);
      KK(2);
      #pragma unroll 1
      for (int h = 0; h < 2; h++) {
        uint32_t ph[4][8];
        float rsum[4][4];
        dual_exp2(p, ph);
        wg_fence();
        row_sums(rsum, ph, dlo(SB0 + OFF_ONES, 128));
        wg_commit();
        KK(3 + 6 * h);
        if (wg == 0 && h == 0) { bar_arrive(NB_DN, 256); bar_sync(NB_WG01, 256); }
        if (h == 1) {
          if (wg == 1) bar_sync(NB_DN, 256);
          put_v(vf);
        }
        wg_wait<0>();
        KK(4 + 6 * h);
        #pragma unroll
        for (int i = 0; i < 4; i++) fence_regs(rsum[i]);
        if (__builtin_expect(__any_sync(~0u, !((rsum[0][0] + rsum[0][2]) + (rsum[1][0] + rsum[1][2]) + (rsum[2][0] + rsum[2][2]) + (rsum[3][0] + rsum[3][2]) < EXP_LIM)), 0)) {
          dual_exp2_shifted(p, ph);
          #pragma unroll
          for (int i = 0; i < 8; i++) {
            const uint32_t* f = &ph[i >> 1][i & 1];
            float a = (bf_lo(f[0]) + bf_hi(f[0])) + (bf_lo(f[2]) + bf_hi(f[2])) + (bf_lo(f[4]) + bf_hi(f[4])) + (bf_lo(f[6]) + bf_hi(f[6]));
            a += __shfl_xor_sync(~0u, a, 1);
            rsum[i >> 1][2 * (i & 1)] = a + __shfl_xor_sync(~0u, a, 2);
          }
        }
        if (h == 0) project(kf[1], dlo(SB0 + OFF_WPHIK1, 16));
        normalize(ph, rsum);
        #pragma unroll
        for (int i = 0; i < 8; i++) {
          const uint32_t* f = &ph[i >> 1][4 * (i & 1)];
          stsm4(((stg + sa) ^ ((i & 3) << 5)) + (i >> 2) * 8192, f[0], f[1], f[2], f[3]);
        }
        KK(5 + 6 * h);
        fence_async_smem();
        KK(6 + 6 * h);
        if (wg != h) { KK(7 + 6 * h); }
        if (wg == h) {
          float kv[20];
          #pragma unroll
          for (int w = 0; w < 2; w++) {
            const uint32_t da = dlo(SB0 + OFF_X, 16) + (h ^ w ^ 1) * 1536, db = dlo(SB0 + OFF_X + 16384, OFF_ONES - OFF_X - 16384) - (h ^ w ^ 1) * (1536 * 65535);
            if (w) bar_sync(NB_ST, 256); else bar_sync(NB_L0 + h, 128);
            wg_fence();
            #pragma unroll
            for (int k = 0; k < 8; k++) {
              if (k == 0 && w == 0) wgmma_sz_n40<1, 1, H128, H64>(kv, da, db);
              else wgmma_sa_n40<1, 1, H128, H64>(kv, da + k * 128, db - k * (64 * 65535));
            }
            wg_commit();
          }
          float4* dst = &G->kvacc[(ha + 2 * h) * KVP + t];
          wg_wait<0>();
          fence_regs(kv);
          KK(7 + 6 * h);
          if (h == 0) bar_arrive(NB_DN, 256); else if (t < 2) { mbar_arrive_at(sb + B_EMPTY5 + 40, t, 2); if (t == 0) mbar_arrive(sb + B_KD); }
          kv[17] = kv[18];
          #pragma unroll
          for (int i = 0; i < 6; i++) red_add_f32x4(dst + 128 * i, kv[3*i], kv[3*i+1], kv[3*i+2], 1.f);
          TSW(29 + h);
        } else bar_arrive(NB_ST, 256);
        wg_wait<0>();
        KK(8 + 6 * h);
        fence_regs(p[0]); fence_regs(p[1]);
      }
      #pragma unroll
      for (int i = 0; i < 32; i++) asm volatile("mov.b32 %0, 0;" : "=r"(xr[i]));
    }
    float p[2][16];
    #pragma unroll
    for (int i = 0; i < 32; i++) asm volatile("mov.b32 %0, 0;" : "=f"(p[i >> 4][i & 15]));
    auto project_r = [&](int w) {
      wg_fence();
      #pragma unroll
      for (int h = 0; h < 2; h++) {
        wgmma_rs_n32<1, H64>(p[h], xr[8*h], xr[8*h+1], xr[8*h+2], xr[8*h+3], dlo(SB0 + OFF_WPHIQ, 16) + 128 * w, 0);
        wgmma_ra_n32<1, H64>(p[h], xr[8*h+4], xr[8*h+5], xr[8*h+6], xr[8*h+7], dlo(SB0 + OFF_WPHIQ, 16) + 128 * w + 64);
      }
      wg_commit();
    };
    {
      const uint4* src = reinterpret_cast<const uint4*>(&G->kvacc[(4 * j + wg) * KVP + t]);
      uint4 v[12];
      #pragma unroll
      for (int i = 0; i < 12; i++) v[i] = i < 6 || isq ? ld128_rlx(src + 128 * i) : make_uint4(0, 0, 0, 0x41000000u);
      if (isq) {
        project_r(2);
        wg_wait<0>();
        #pragma unroll
        for (int i = 0; i < 16; i++) xr[i] = xr[16 + i];
      } else {
        mbar_wait(sb + B_R, 0);
        #pragma unroll
        for (int k = 0; k < 8; k++) ldsm4(((sb + (1 + rank) * R5 + wg * 8192 + sa) ^ ((k & 3) << 5)) + (k >> 2) * 2 * R5, xr[4*k], xr[4*k+1], xr[4*k+2], xr[4*k+3]);
        const uint32_t one = (((xr[0] | xr[4] | xr[8]) | (xr[12] | xr[16] | xr[20]) | (xr[24] | xr[28])) & P.zero) + 1;
        if (lane == 0) { mbar_arrive_at(sb + B_RC + 8 * wg, rank, one); mbar_arrive_at(sb + B_RX, wg, one); }
      }
      #pragma unroll 1
      for (uint32_t it = 0; it < POLL_LIMIT; it++) {
        uint32_t bad = 0;
        #pragma unroll
        for (int i = 0; i < 12; i++) bad |= v[i].w ^ 0x41000000u;
        if (!__any_sync(~0u, bad != 0)) break;
        #pragma unroll
        for (int i = 0; i < 12; i++) if (i < 6 || isq) v[i] = ld128_rlx(src + 128 * i);
      }
      mbar_wait(sb + B_KD, 0);
      #pragma unroll
      for (int e = 0; e < 2; e++) {
        if (e == 0 || isq) {
          float f[18];
          #pragma unroll
          for (int i = 0; i < 6; i++) { f[3*i] = __uint_as_float(v[6*e+i].x); f[3*i+1] = __uint_as_float(v[6*e+i].y); f[3*i+2] = __uint_as_float(v[6*e+i].z); }
          const uint32_t ka = sb + OFF_KVZ + (wg + e) * 5120 + wp * 1280 + lane * 16;
          stsm4(ka, pack_bf16(f[0], f[1]), pack_bf16(f[2], f[3]), pack_bf16(f[4], f[5]), pack_bf16(f[6], f[7]));
          stsm4(ka + 512, pack_bf16(f[8], f[9]), pack_bf16(f[10], f[11]), pack_bf16(f[12], f[13]), pack_bf16(f[14], f[15]));
          stsm2(ka + 1024, pack_bf16(f[16], 1.f), pack_bf16(f[17], 1.f));
        }
      }
    }
    fence_async_smem();
    if (wg == 1) bar_arrive(NB_DN, 256);
    if (isq) mbar_wait(sb + B_OS, 0);
    TSW(wg == 0 ? 5 : wg == 1 ? 25 : 6);
    #pragma unroll 1
    for (int e = wg; e < wg + 1 + (wg >> 1); e++) {
      const int half = e >> 1, hh = e & 1, turn = e;
      const uint32_t ao = (1 + rank) * R5 + hh * 8192;
      const uint32_t ra = sb + OFF_RSQ + (16 * wp + g) * 4 + (e == 1 ? 256 : 0), rb = ra + 256 * half;
      const float cc[2][2] = {{ldsf(ra) * LOG2E, ldsf(ra + 32) * LOG2E}, {ldsf(rb) * LOG2E, ldsf(rb + 32) * LOG2E}};
      float m[2][4] = {{0.f, 0.f, 0.f, 0.f}, {0.f, 0.f, 0.f, 0.f}};
      uint32_t ph[2][8];
      auto exps = [&](int h) {
        #pragma unroll
        for (int k = 0; k < 8; k++) {
          const float c = cc[h][k & 1], mp = m[h][k & 1], mm = m[h][2 + (k & 1)];
          ph[0][k] = pack_bf16(ex2(fmaf(p[h][2*k], c, mp)), ex2(fmaf(p[h][2*k+1], c, mp)));
          ph[1][k] = pack_bf16(ex2(fmaf(p[h][2*k], -c, mm)), ex2(fmaf(p[h][2*k+1], -c, mm)));
        }
      };
      uint32_t shifted = 0;
      asm volatile("" : "+r"(shifted));
      #pragma unroll 1
      for (;;) {
        if (shifted) { row_extremes(p[0], cc[0], m[0]); row_extremes(p[1], cc[1], m[1]); }
        uint32_t first = (shifted ^ 1) & !isq;
        asm volatile("" : "+r"(first));
        if (first) {
          bar_sync(NB_Q0 + wg, 256);
          const uint32_t da = dlo(SB0, 16) + (ao >> 4), db = dlo(SB0 + OFF_WPHIQ, 16);
          wg_fence();
          #pragma unroll
          for (int h = 0; h < 2; h++) {
            wgmma_ss_n32<0, 1, H128, H64>(p[h], da + 4 * h, db + 128 * h, 0);
            wgmma_sa_n32<0, 1, H128, H64>(p[h], da + 4 * h + 2, db + 128 * h + 64);
          }
          wg_commit();
          wg_wait<0>();
        }
        if (!shifted && (e == 1 || e == 2)) bar_sync(NB_TOK + e - 1, 256);
        TK(64 + 4 * turn);
        fence_regs(p[0]); fence_regs(p[1]);
        exps(0);
        float s2[4] = {0.f, 0.f, 0.f, 0.f};
        #pragma unroll
        for (int i = 0; i < 32; i++) s2[((i >> 1) & 1) + 2 * (i >> 4)] = fmaf(p[i >> 4][i & 15], p[i >> 4][i & 15], s2[((i >> 1) & 1) + 2 * (i >> 4)]);
        if (!__any_sync(~0u, !shifted & !((s2[0] * cc[0][0] * cc[0][0] < ARG_LIM2) & (s2[1] * cc[0][1] * cc[0][1] < ARG_LIM2) &
                                          (s2[2] * cc[1][0] * cc[1][0] < ARG_LIM2) & (s2[3] * cc[1][1] * cc[1][1] < ARG_LIM2)))) break;
        shifted = 1;
      }
      float ac[4][20];
      auto numer = [&](int h, const uint32_t (&f)[2][8]) {
        const uint32_t db = dlo(SB0 + OFF_KVZ, 128) + (half ? e : h) * 320;
        wg_fence();
        #pragma unroll
        for (int i = 0; i < 2; i++) {
          wgmma_rz_n40<1, dhi(256, 0)>(ac[2*h+i], f[i][0], f[i][1], f[i][2], f[i][3], db + i * 160);
          wgmma_ra_n40<1, dhi(256, 0)>(ac[2*h+i], f[i][4], f[i][5], f[i][6], f[i][7], db + (i * 160 + 80));
        }
        wg_commit();
      };
      const uint32_t oa = (16 * wp + g) * 128 + (((lane & 3) ^ g) << 4);
      auto finish = [&](int h) {
        const float* ap = ac[2 * h]; const float* am = ac[2 * h + 1];
        const float ip0 = rcp(ap[17]), im0 = rcp(am[17]), ip1 = rcp(ap[19]), im1 = rcp(am[19]);
        const float d0 = rcp(fmaf(ap[16], ip0, fmaf(am[16], im0, 1e-6f))), d1 = rcp(fmaf(ap[18], ip1, fmaf(am[18], im1, 1e-6f)));
        const float a0 = ip0 * d0, b0 = im0 * d0, a1 = ip1 * d1, b1 = im1 * d1;
        #pragma unroll
        for (int r = 0; r < 2; r++) {
          const float a = r ? a1 : a0, b = r ? b1 : b0;
          uint32_t w[4];
          #pragma unroll
          for (int k = 0; k < 4; k++) w[k] = pack_bf16(fmaf(ap[4*k+2*r], a, am[4*k+2*r] * b), fmaf(ap[4*k+2*r+1], a, am[4*k+2*r+1] * b));
          const uint32_t off = (oa ^ ((half ? rank : h) << 6)) + r * 1024;
          st128_rlx(reinterpret_cast<uint8_t*>(G->o + (m128 * 16 + (half ? 2 * (j & 6) + 2 * hh + 1 : 2 * j)) * 8192 + (half ? h : hh) * 4096) + off, w[0], w[1], w[2], w[3]);
          if (!half) sts128(sb + ao + off, w[0], w[1], w[2], w[3]);
        }
      };
      numer(0, ph);
      exps(1);
      if (wg == 0) bar_sync(NB_DN, 256);
      numer(1, ph);
      if (turn < 2) bar_arrive(NB_TOK + turn, 256);
      wg_wait<1>();
      TK(65 + 4 * turn);
      fence_regs(ac[0]); fence_regs(ac[1]);
      finish(0);
      wg_wait<0>();
      fence_regs(ac[2]); fence_regs(ac[3]);
      #pragma unroll
      for (int i = 0; i < 32; i++) asm volatile("mov.b32 %0, 0;" : "=f"(p[i >> 4][i & 15]));
      if (e == 2) project_r(3);
      finish(1);
      TK(66 + 4 * turn);
      if (!half) fence_async_smem();
      __syncwarp();
      if (lane == 0) mbar_arrive(sb + B_UO + 8 * e);
      wg_wait<0>();
      TK(67 + 4 * turn);
    }
    if (isq) cluster_arrive();
  }

  {
  int lane;
  asm volatile("mov.u32 %0, %%laneid;" : "=r"(lane));
  const int g = lane >> 2, q = lane & 3;
  if (wg < 2) {
    float h[64];
    {
      if (wg == 0) { TK(83); }
      #pragma unroll
      for (int i = 0; i < 32; i++) { h[2*i] = bf_lo(xr[i]); h[2*i+1] = bf_hi(xr[i]); }
      fence_regs(h);
      TK(80 + wg);
      const uint32_t emptyb = mapa(sb + B_EMPTY5, t & 1);
      uint32_t s = 1 + rank, ps = 0;
      mbar_wait2(sb + B_FULL5 + 8 * s, 1, sb + B_UO + 8 * wg, 0);
      if (wg == 0) { TSW(14); }
      #pragma unroll
      for (int i = 0; i < 16; i++) {
        if (wg == 1 && (i & 12) == TKW) { TK(84 + (i & 3)); }
        if (!KT && wg == 0) { TK(32 + i); }
        const uint32_t da = dlo(SB0, 16) + s * 2048 + wg * 512, db = dlo(SB0 + 16384, 8192) + s * 2048;
        wg_fence();
        #pragma unroll
        for (int k = 0; k < 4; k++) wgmma_sa_n128<0, 1, H128, H128>(h, da + k * 2, db + k * 128);
        wg_commit();
        const uint32_t ns = i ? (i + 2) % 6 : 2 - rank;
        const uint32_t b0 = sb + B_FULL5 + 8 * ns, p0 = (1 + (i + 2) / 6) & 1, b1 = sb + B_FULLA + 16 * ns + 8 * wg, p1 = ((i + 1) / 6) & 1;
        const bool here = i == 15 || mbar_test2(b0, p0, b1, p1);
        wg_wait<1>();
        if (!(((2 * REL + 1) >> i) & 1) && i < 14 && t < 2) mbar_arrive_remote(emptyb + 8 * ps, 1);
        if ((REL >> i) & 1) { wg_wait<0>(); if (t < 2) mbar_arrive_remote(emptyb + 8 * s, 1); }
        if (!here) mbar_wait2(b0, p0, b1, p1);
        ps = s; s = ns;
      }
    }
    cluster_arrive();
    float2 wr[16];
    #pragma unroll
    for (int i = 0; i < 16; i++) wr[i] = lds64f(sb + OFF_WR + 32 * i + 8 * q);
    const int r0 = 64 * wg + 16 * wp + g;
    float sum0, sum1, dot0, dot1, sq0, sq1;
    uint32_t redo = 0;
    asm volatile("" : "+r"(redo));
    #pragma unroll 1
    for (;;) {
    if (redo) {
      wg_wait<0>();
      const int r = r0;
      #pragma unroll 1
      for (int n = 0; n < 16; n++) {
        const uint32_t* xp = reinterpret_cast<const uint32_t*>(P.x + (size_t)(128 * m128 + r) * DM + 128 * j + 8 * n) + q;
        const uint32_t x0 = xp[0], x1 = xp[4 * DM];
        float d0 = bf_lo(x0), d1 = bf_hi(x0), d2 = bf_lo(x1), d3 = bf_hi(x1);
        #pragma unroll 1
        for (int ks = 0; ks < 64; ks++) {
          const int kb = ks >> 2, kk = 16 * (ks & 3);
          const bf16* op = G->o + (m128 * 16 + kb) * 8192 + r * 64 + 2 * q;
          const int o0 = ((kk >> 3) ^ g) << 3;
          const uint16_t* w = reinterpret_cast<const uint16_t*>(P.wo_p) + (size_t)(((kb & 1) ? 256 * (kb >> 2) + 32 * (kb & 2) + 32 + 4 * (kk & 32) : 64 * kb + 2 * (kk & 32)) + ((kk & 16) >> 2) + 8 * q) * DM + 128 * j + 8 * n + g;
          const uint32_t b0 = w[0] | (w[DM] << 16), b1 = w[2 * DM] | (w[3 * DM] << 16);
          uint32_t a0, a1, a2, a3, it = 0;
          do { a0 = ld32_rlx(op + o0); a1 = ld32_rlx(op + 512 + o0); a2 = ld32_rlx(op + (o0 ^ 8)); a3 = ld32_rlx(op + 512 + (o0 ^ 8)); }
          while (max(max(a0, a1), max(a2, a3)) == ~0u && ++it < POLL_LIMIT);
          __syncwarp();
          mma16816(d0, d1, d2, d3, a0, a1, a2, a3, b0, b1);
        }
        #pragma unroll
        for (int i = 0; i < 60; i++) h[i] = h[i + 4];
        h[60] = d0; h[61] = d1; h[62] = d2; h[63] = d3;
      }
    }
    wg_wait<0>();
    fence_regs(h);
    if (wg == 0) { TSW(16); }
    sum0 = 0.f, sum1 = 0.f, dot0 = 0.f, dot1 = 0.f, sq0 = 0.f, sq1 = 0.f;
    #pragma unroll
    for (int i = 0; i < 16; i++) {
      sum0 += h[4*i] + h[4*i+1]; sum1 += h[4*i+2] + h[4*i+3];
      sq0 = fmaf(h[4*i], h[4*i], fmaf(h[4*i+1], h[4*i+1], sq0)); sq1 = fmaf(h[4*i+2], h[4*i+2], fmaf(h[4*i+3], h[4*i+3], sq1));
      dot0 = fmaf(h[4*i], wr[i].x, fmaf(h[4*i+1], wr[i].y, dot0)); dot1 = fmaf(h[4*i+2], wr[i].x, fmaf(h[4*i+3], wr[i].y, dot1));
    }
    if (!__any_sync(~0u, !redo & (h[0] != h[0] | h[2] != h[2]))) break;
    redo = 1;
    }
    float4* const rs = &G->rstat[128 * m128 + r0];
    {
      const bool up = q & 2;
      float a = up ? sum1 : sum0, b = up ? sq1 : sq0, d = up ? dot1 : dot0;
      a += __shfl_xor_sync(~0u, up ? sum0 : sum1, 2); b += __shfl_xor_sync(~0u, up ? sq0 : sq1, 2); d += __shfl_xor_sync(~0u, up ? dot0 : dot1, 2);
      a += __shfl_xor_sync(~0u, a, 1); b += __shfl_xor_sync(~0u, b, 1); d += __shfl_xor_sync(~0u, d, 1);
      if ((q & 1) == 0) red_add_f32x4(rs + 4 * q, a, b, d, 1.f);
    }
    bar_arrive(NB_G2E, 384);
    if (wg == 0) { TSW(24); }
    bar_sync(NB_WG01, 256);
    uint32_t wa[8][4][4];
    const uint32_t wb = sb + 16384 * (((uint32_t)FF_SLOT >> (4 * warp)) & 15) + ((lane & 7) + ((lane >> 4) << 3)) * 64 + ((((lane >> 3) & 1) ^ ((lane >> 1) & 3)) << 4);
    auto getw = [&](int ks) {
      #pragma unroll
      for (int m = 0; m < 4; m++) ldsm4t((wb ^ ((m & 1) << 5)) + (m >> 1) * 8192 + ks * 1024, wa[ks][m][0], wa[ks][m][1], wa[ks][m][2], wa[ks][m][3]);
    };
    if (GPRE && f < NFFN_L) mbar_wait(sb + B_F + 8 * warp, 0);
    if (warp == 7) { TK(60); }
    #pragma unroll
    for (int ks = 0; ks < GPRE; ks++) getw(ks);
    float rstd[2], bm[2];
    uint32_t best;
    {
      const float2 swa = lds64f(sb + OFF_SUMWR), swb = lds64f(sb + OFF_SUMWR + 8);
      const float sw = (swa.x + swa.y) + (swb.x + swb.y);
      uint4 a[2]; uint32_t it = 0, key[2];
      do { a[0] = ld128_rlx(rs); a[1] = ld128_rlx(rs + 8); } while (__any_sync(~0u, (a[0].w & a[1].w) != 0x41000000u) && ++it < POLL_LIMIT);
      #pragma unroll
      for (int i = 0; i < 2; i++) {
        const float mean = __uint_as_float(a[i].x) * (1.f / DM);
        rstd[i] = rsqrtf(fmaxf(__uint_as_float(a[i].y) * (1.f / DM) - mean * mean, 0.f) + 1e-5f);
        bm[i] = -mean * rstd[i];
        const uint32_t rr = __float_as_uint(fmaf(__uint_as_float(a[i].z), rstd[i], sw * bm[i]));
        key[i] = ((rr ^ ((uint32_t)((int32_t)rr >> 31) | 0x80000000u)) & ~2047u) | (2047 - 128 * m128 - r0 - 8 * i);
      }
      asm volatile("redux.sync.max.u32 %0, %1, 0xffffffff;" : "=r"(best) : "r"(max(key[0], key[1])));
    }
    if (wg == 0) { TSW(17); }
    const int slot = m128 * 8 + warp, win = ~best & 15;
    if (lane < 4) st32_rlx(&G->key[(4 * j + lane) * 128 + slot], best);
    if ((win & 7) == g) {
      const bool up = win & 8;
      const float ra = up ? rstd[1] : rstd[0], rb = up ? bm[1] : bm[0];
      uint32_t x[16];
      #pragma unroll
      for (int i = 0; i < 16; i++) x[i] = pack_bf16(fmaf(up ? h[4*i+2] : h[4*i], ra, rb), fmaf(up ? h[4*i+3] : h[4*i+1], ra, rb));
      #pragma unroll
      for (int i = 0; i < 4; i++) st128_rlx(&G->cand[slot * DM + 64 * j + 16 * i + 4 * q], x[4*i], x[4*i+1], x[4*i+2], x[4*i+3]);
    }
    __syncwarp();
    if (wg == 0) { TSW(27); }
    {
      const float a0 = 1.f + rstd[0], b0 = bm[0], a1 = 1.f + rstd[1], b1 = bm[1];
      #pragma unroll
      for (int k = 0; k < 8; k++)
        stsm4(((sb + OFF_OUT + wg * 8192 + sa) ^ ((k & 3) << 5)) + (k >> 2) * 16384,
              pack_bf16(fmaf(h[8*k], a0, b0), fmaf(h[8*k+1], a0, b0)),     pack_bf16(fmaf(h[8*k+2], a1, b1), fmaf(h[8*k+3], a1, b1)),
              pack_bf16(fmaf(h[8*k+4], a0, b0), fmaf(h[8*k+5], a0, b0)),   pack_bf16(fmaf(h[8*k+6], a1, b1), fmaf(h[8*k+7], a1, b1)));
      sts32(sb + OFF_EXC + 4 * warp, 16 * warp + win);
      __syncwarp();
      if (lane == 0) mbar_arrive(sb + B_OUT + 8 * (warp >> 1));
      if (lane < 16) {
        const uint4 v = lds128(sb + OFF_OUT + (lane >> 3) * 16384 + (16 * warp + win) * 128 + (((lane & 7) ^ (win & 7)) << 4));
        st128_rlx(&G->cand[slot * DM + 512 + 64 * j + 4 * lane], v.x, v.y, v.z, v.w);
      }
    }
    if (wg == 0) { TSW(28); }
    {
      if (!GPRE && f < NFFN_L) mbar_wait(sb + B_F + 8 * warp, 0);
      #pragma unroll
      for (int ks = GPRE; ks < GRES; ks++) getw(ks);
      if (wg == 0) { TSW(15); }
      bar_sync(NB_XS, 384);
      if (wg == 0) { TSW(19); }
      uint4 xs[4];
      #pragma unroll
      for (int i = 0; i < 4; i++) xs[i] = lds128(sb + OFF_XSEL + 256 * warp + 64 * i + 16 * q);
      float d[4][4];
      #pragma unroll
      for (int ks = 0; ks < 8; ks++) {
        if (ks >= 1 && GRES + ks - 1 < 8) getw(GRES + ks - 1);
        #pragma unroll
        for (int m = 0; m < 4; m++) {
          if (ks == 0) { d[m][0] = 0.f; d[m][1] = 0.f; d[m][2] = 0.f; d[m][3] = 0.f; }
          mma16816(d[m][0], d[m][1], d[m][2], d[m][3], wa[ks][m][0], wa[ks][m][1], wa[ks][m][2], wa[ks][m][3],
                   (ks & 1) ? xs[ks >> 1].z : xs[ks >> 1].x, (ks & 1) ? xs[ks >> 1].w : xs[ks >> 1].y);
        }
      }
      if (q == 0) {
        #pragma unroll
        for (int m = 0; m < 8; m++) stsf(sb + OFF_GU + (8 * m + g) * 48 + 4 * warp, d[m >> 1][2 * (m & 1)]);
      }
      bar_arrive(NB_ACT, 384);
    }
    {
      float y0 = 0.f, y1 = 0.f, y2 = 0.f, y3 = 0.f;
      const uint32_t ky = __float_as_uint(ldsf(sb + OFF_KEY));
      const int kidx = 2047 - (ky & 2047);
      const float kr = __uint_as_float((ky & ~2047u) ^ ((ky >> 31) ? 0x80000000u : 0xfffff800u));
      const int col = 128 * (c >> 4) + 64 * (c & 1) + 32 * ((tid >> 2) & 1) + 16 * (tid & 1) + 8 * ((tid >> 1) & 1) + ((c >> 1) & 7);
      uint32_t it = 0, base = 0;
      if (tid < 8) {
        do { base = ld32_rlx(&G->cand[(kidx >> 4) * DM + 512 + (col >> 1)]); } while (base == ~0u && ++it < POLL_LIMIT);
      }
      if (tid < 2 * NFFN) {
        uint4 v;
        do { v = ld128_rlx(&G->ypart[(tid >> 1) * DM + 8 * c + 4 * (tid & 1)]); } while (v.w == ~0u && ++it < POLL_LIMIT);
        y0 = __uint_as_float(v.x); y1 = __uint_as_float(v.y); y2 = __uint_as_float(v.z); y3 = __uint_as_float(v.w);
      }
      __syncwarp();
      const bool b4 = lane & 16, b3 = lane & 8;
      const float u0 = (b4 ? y1 : y0) + __shfl_xor_sync(~0u, b4 ? y0 : y1, 16), u1 = (b4 ? y3 : y2) + __shfl_xor_sync(~0u, b4 ? y2 : y3, 16);
      float ys = (b3 ? u1 : u0) + __shfl_xor_sync(~0u, b3 ? u0 : u1, 8);
      ys += __shfl_xor_sync(~0u, ys, 4); ys += __shfl_xor_sync(~0u, ys, 2);
      if (!(lane & 6)) stsf(sb + OFF_ACT + ((4 * (lane & 1) + ((lane >> 3) & 1) * 2 + (lane >> 4)) * 8 + warp) * 4, ys);
      const float sg = __fdividef(1.f, 1.f + __expf(-kr));
      bar_sync(NB_WG01, 256);
      if (tid < 8) {
        const uint4 v0 = lds128(sb + OFF_ACT + tid * 32), v1 = lds128(sb + OFF_ACT + tid * 32 + 16);
        const float t8 = ((__uint_as_float(v0.x) + __uint_as_float(v0.y)) + (__uint_as_float(v0.z) + __uint_as_float(v0.w))) +
                         ((__uint_as_float(v1.x) + __uint_as_float(v1.y)) + __uint_as_float(v1.z));
        P.out_p[(size_t)kidx * DM + col] = __float2bfloat16(fmaf(t8, sg, (col & 1) ? bf_hi(base) : bf_lo(base)));
      }
      if (c == 0 && tid == 0) st32_rlx(&G->epoch, __float_as_uint(ldsf(sb + OFF_EP)));
      if (wg == 0) { TSW(22); TDUMP(); }
    }
  }
  if (wg == 2) {
    uint32_t wf[16][2][4];
    {
      const uint32_t wb = sb + OFF_S + 16384 * (wp & 1) + ((lane & 7) + ((lane >> 4) << 3)) * 128 + ((((lane >> 3) & 1) ^ (lane & 7)) << 4);
      if (f < NFFN_L) mbar_wait(sb + B_WD + 8 * wp, 0);
      if (wp == 0) { TK(61); }
      #pragma unroll
      for (int i = 0; i < 32; i++) ldsm4t((wb ^ (((i >> 1) & 3) << 5)) + (i >> 3) * 4096 + (i & 1) * 2048, wf[i >> 1][i & 1][0], wf[i >> 1][i & 1][1], wf[i >> 1][i & 1][2], wf[i >> 1][i & 1][3]);
      fence_async_smem();
      __syncwarp();
      if (lane == 0) mbar_arrive(sb + B_WC + 8 * wp);
      if (wp == 0) { TK(62); }
    }
    bar_sync(NB_G2E, 384);
    {
      uint32_t cur = 0;
      uint4 v;
      #pragma unroll 1
      for (uint32_t it = 0; it < POLL_LIMIT; it++) {
        const uint4 kx = ld128_rlx(&G->key[(c & 31) * 128 + 4 * lane]);
        v = ld128_rlx(&G->cand[((~cur >> 4) & 127) * DM + 4 * t]);
        uint32_t best;
        asm volatile("redux.sync.max.u32 %0, %1, 0xffffffff;" : "=r"(best) : "r"(max(max(kx.x, kx.y), max(kx.z, kx.w))));
        if (!__any_sync(~0u, min(min(kx.x, kx.y), min(kx.z, kx.w)) == 0 || v.w == ~0u) && best == cur) break;
        cur = best;
      }
      sts128(sb + OFF_XSEL + 16 * t, v.x, v.y, v.z, v.w);
      sts32(sb + OFF_KEY, cur);
      bar_arrive(NB_XS, 384);
      if (t == 0) mbar_arrive(sb + B_XS);
      TSW(18);
      bar_sync(NB_ACT, 384);
    }
    float gu[2];
    #pragma unroll
    for (int i = 0; i < 2; i++) {
      const uint4 v0 = lds128(sb + OFF_GU + (32 * i + lane) * 48), v1 = lds128(sb + OFF_GU + (32 * i + lane) * 48 + 16);
      gu[i] = ((__uint_as_float(v0.x) + __uint_as_float(v0.y)) + (__uint_as_float(v0.z) + __uint_as_float(v0.w))) +
              ((__uint_as_float(v1.x) + __uint_as_float(v1.y)) + (__uint_as_float(v1.z) + __uint_as_float(v1.w)));
    }
    const float act = gu[0] * gu[1] * rcp(1.f + ex2(-LOG2E * gu[0]));
    const uint32_t ap = pack_bf16(act, __shfl_down_sync(~0u, act, 1));
    uint32_t bf[4];
    #pragma unroll
    for (int i = 0; i < 4; i++) bf[i] = __shfl_sync(~0u, ap, 2 * q + 8 * i);
    TSW(20);
    float d[16][4];
    #pragma unroll
    for (int k = 0; k < 2; k++)
      #pragma unroll
      for (int i = 0; i < 16; i++) {
        if (k == 0) { d[i][0] = 0.f; d[i][1] = 0.f; d[i][2] = 0.f; d[i][3] = 0.f; }
        mma16816(d[i][0], d[i][1], d[i][2], d[i][3], wf[i][k][0], wf[i][k][1], wf[i][k][2], wf[i][k][3], bf[2*k], bf[2*k+1]);
      }
    #pragma unroll
    for (int a = 0; a < 2; a++) {
      float y[4];
      #pragma unroll
      for (int e = 0; e < 4; e++) {
        const int n = 8 * a + (e & 1);
        const float lo = (q & 1) ? d[n + 2][e & 2] : d[n][e & 2], hi = (q & 1) ? d[n + 6][e & 2] : d[n + 4][e & 2];
        y[e] = (q & 2) ? hi : lo;
      }
      if (f < NFFN) st128_rlx(&G->ypart[f * DM + 256 * wp + 128 * a + 4 * lane], __float_as_uint(y[0]), __float_as_uint(y[1]), __float_as_uint(y[2]), min(__float_as_uint(y[3]), ~1u));
    }
    TSW(21);
  }
  }
  cluster_wait();
}

typedef CUresult (*EncodeFn)(CUtensorMap*, CUtensorMapDataType, cuuint32_t, void*, const cuuint64_t*, const cuuint64_t*,
                             const cuuint32_t*, const cuuint32_t*, CUtensorMapInterleave, CUtensorMapSwizzle,
                             CUtensorMapL2promotion, CUtensorMapFloatOOBfill);

void make_map(EncodeFn enc, CUtensorMap* m, const void* p, int n, const cuuint64_t* dims, const cuuint64_t* str, const cuuint32_t* box,
              CUtensorMapSwizzle sw, CUtensorMapL2promotion promo) {
  cuuint32_t es[5] = {1, 1, 1, 1, 1};
  enc(m, CU_TENSOR_MAP_DATA_TYPE_BFLOAT16, n, const_cast<void*>(p), dims, str, box, es, CU_TENSOR_MAP_INTERLEAVE_NONE, sw, promo,
      CU_TENSOR_MAP_FLOAT_OOB_FILL_NONE);
}
void map2(EncodeFn enc, CUtensorMap* m, const void* p, uint64_t cols, uint64_t rows, uint32_t bc, uint32_t br, CUtensorMapSwizzle sw,
          CUtensorMapL2promotion promo) {
  const cuuint64_t dims[2] = {cols, rows}, str[1] = {cols * 2};
  const cuuint32_t box[2] = {bc, br};
  make_map(enc, m, p, 2, dims, str, box, sw, promo);
}
void map3(EncodeFn enc, CUtensorMap* m, const void* p, uint64_t cols, uint64_t rows, uint32_t br, uint32_t nb) {
  const cuuint64_t dims[3] = {64, rows, cols / 64}, str[2] = {cols * 2, 128};
  const cuuint32_t box[3] = {64, br, nb};
  make_map(enc, m, p, 3, dims, str, box, CU_TENSOR_MAP_SWIZZLE_128B, CU_TENSOR_MAP_L2_PROMOTION_L2_128B);
}

}

extern "C" void kernel_launch(void* const* d_in, const int* in_sizes, int n_in, void* d_out, int out_size) {
  (void)in_sizes; (void)n_in; (void)out_size;
  static EncodeFn enc = nullptr;
  static void* o_ptr = nullptr;
  if (!enc) {
    void* f = nullptr; cudaDriverEntryPointQueryResult qr;
    cudaGetDriverEntryPoint("cuTensorMapEncodeTiled", &f, cudaEnableDefault, &qr);
    enc = (EncodeFn)f;
    cudaGetSymbolAddress(&o_ptr, g_scr);
    cudaFuncSetAttribute(fused_kernel, cudaFuncAttributeMaxDynamicSharedMemorySize, SMEM_BYTES);
  }
  const bf16* x = (const bf16*)d_in[0];
  const bf16* wqkv = (const bf16*)d_in[1];
  const bf16* wphi = (const bf16*)d_in[2];
  const bf16* wo = (const bf16*)d_in[3];
  const bf16* wr = (const bf16*)d_in[5];
  const bf16* wgate = (const bf16*)d_in[6];
  const bf16* wup = (const bf16*)d_in[7];
  const bf16* wdown = (const bf16*)d_in[8];
  Params P;
  const CUtensorMapSwizzle S128 = CU_TENSOR_MAP_SWIZZLE_128B, S64 = CU_TENSOR_MAP_SWIZZLE_64B;
  const CUtensorMapL2promotion L128 = CU_TENSOR_MAP_L2_PROMOTION_L2_128B, L256 = CU_TENSOR_MAP_L2_PROMOTION_L2_256B,
                               L64 = CU_TENSOR_MAP_L2_PROMOTION_L2_64B;
  map2(enc, &P.x128, x, DM, SEQ, 64, 128, S128, L256);
  map2(enc, &P.x64, x, DM, SEQ, 64, 64, S128, L128);
  {
    const cuuint64_t dims[4] = {64, DM, 16, 3}, str[3] = {6 * DM, 128, 2 * DM};
    const cuuint32_t box[4] = {64, 64, 1, 2};
    make_map(enc, &P.wkv, wqkv, 4, dims, str, box, S128, L128);
  }
  map3(enc, &P.wq, wqkv, 3 * DM, DM, 64, 2);
  for (int i = 0; i < 2; i++) {
    const cuuint64_t dims[5] = {DM, (cuuint64_t)(DM - 94 - 64 * i), 4, 4, 2}, str[4] = {2 * DM, 16 * DM, 4 * DM, (cuuint64_t)(128 * DM) << i};
    const cuuint32_t box[5] = {64, 2, 4, 4, 2};
    make_map(enc, &P.wo[i], wo, 5, dims, str, box, S128, L128);
  }
  map3(enc, &P.wd, wdown, DM, FF, 32, 4);
  map2(enc, &P.wg, wgate, FF, DM, 32, 128, S64, L64);
  map2(enc, &P.wu, wup, FF, DM, 32, 128, S64, L64);
  map2(enc, &P.tg, wgate, FF, DM, 8, 16, CU_TENSOR_MAP_SWIZZLE_NONE, L128);
  map2(enc, &P.tu, wup, FF, DM, 8, 16, CU_TENSOR_MAP_SWIZZLE_NONE, L128);
  map2(enc, &P.td, wdown, 128, FF * 8, 8, 16, CU_TENSOR_MAP_SWIZZLE_NONE, L256);
  map2(enc, &P.xs, x, DM, SEQ, 128, 16, CU_TENSOR_MAP_SWIZZLE_NONE, L256);
  map2(enc, &P.ws, wqkv, 3 * DM, DM, 16, 128, CU_TENSOR_MAP_SWIZZLE_NONE, L128);
  map2(enc, &P.qs, wqkv, 3 * DM, DM, 32, 128, CU_TENSOR_MAP_SWIZZLE_NONE, L64);
  map2(enc, &P.phi, wphi, 32, 1024, 32, 32, S64, L64);
  P.x = x; P.wqkv = wqkv; P.wo_p = wo; P.wd_p = wdown; P.wg_p = wgate; P.wu_p = wup; P.wr = wr; P.out_p = (bf16*)d_out; P.g = (Scratch*)o_ptr; P.zero = 0;

  cudaLaunchConfig_t cfg = {};
  cfg.gridDim = dim3(128); cfg.blockDim = dim3(512); cfg.dynamicSmemBytes = SMEM_BYTES; cfg.stream = cudaStreamPerThread;
  cudaLaunchAttribute at[1];
  at[0].id = cudaLaunchAttributeClusterDimension; at[0].val.clusterDim.x = 2; at[0].val.clusterDim.y = 1; at[0].val.clusterDim.z = 1;
  cfg.attrs = at; cfg.numAttrs = 1;
  cudaLaunchKernelEx(&cfg, fused_kernel, P);
}
```

```cpp
#include <cuda_runtime.h>
#include <cuda.h>
#include <cuda_bf16.h>
#include <stdint.h>

namespace {

typedef __nv_bfloat16 bf16;

__device__ __forceinline__ uint32_t smem_u32(const void* p){ return (uint32_t)__cvta_generic_to_shared(p); }
__device__ __forceinline__ void mbar_init(uint32_t bar, uint32_t cnt){ asm volatile("mbarrier.init.shared::cta.b64 [%0], %1;"::"r"(bar),"r"(cnt):"memory"); }
__device__ __forceinline__ void mbar_expect_tx(uint32_t bar, uint32_t bytes){ asm volatile("mbarrier.arrive.expect_tx.shared::cta.b64 _, [%0], %1;"::"r"(bar),"r"(bytes):"memory"); }
__device__ __forceinline__ void mbar_arrive(uint32_t bar){ asm volatile("mbarrier.arrive.shared::cta.b64 _, [%0];"::"r"(bar):"memory"); }
__device__ __forceinline__ uint32_t mapa(uint32_t addr, uint32_t cta){ uint32_t r; asm volatile("mapa.shared::cluster.u32 %0, %1, %2;":"=r"(r):"r"(addr),"r"(cta)); return r; }
__device__ __forceinline__ void mbar_arrive_at(uint32_t bar, uint32_t cta, uint32_t cnt){
  asm volatile("{\n.reg .b32 ra;\nmapa.shared::cluster.u32 ra, %0, %1;\nmbarrier.arrive.shared::cluster.b64 _, [ra], %2;\n}\n"::"r"(bar),"r"(cta),"r"(cnt):"memory"); }
__device__ __forceinline__ void mbar_arrive_remote(uint32_t cluster_addr, uint32_t cnt){
  asm volatile("mbarrier.arrive.shared::cluster.b64 _, [%0], %1;"::"r"(cluster_addr),"r"(cnt):"memory"); }
__device__ __forceinline__ void mbar_wait(uint32_t bar, uint32_t parity){
  asm volatile("{\n.reg .pred p;\n.reg .u32 c;\nmov.u32 c, 0;\nLW:\nmbarrier.try_wait.parity.shared::cta.b64 p, [%0], %1;\n@p bra LD;\nadd.u32 c, c, 1;\nsetp.lt.u32 p, c, 2000000;\n@p bra LW;\ntrap;\nLD:\n}\n"::"r"(bar),"r"(parity):"memory"); }
__device__ __forceinline__ void mbar_wait2(uint32_t bar0, uint32_t par0, uint32_t bar1, uint32_t par1){
  asm volatile("{\n.reg .pred p, q;\n.reg .u32 c;\nmov.u32 c, 0;\nLW:\nmbarrier.try_wait.parity.shared::cta.b64 p, [%0], %1;\nmbarrier.try_wait.parity.shared::cta.b64 q, [%2], %3;\nand.pred p, p, q;\n@p bra LD;\nadd.u32 c, c, 1;\nsetp.lt.u32 p, c, 2000000;\n@p bra LW;\ntrap;\nLD:\n}\n"::"r"(bar0),"r"(par0),"r"(bar1),"r"(par1):"memory"); }
__device__ __forceinline__ bool mbar_test2(uint32_t bar0, uint32_t par0, uint32_t bar1, uint32_t par1){
  uint32_t r;
  asm volatile("{\n.reg .pred p, q;\nmbarrier.test_wait.parity.shared::cta.b64 p, [%1], %2;\nmbarrier.test_wait.parity.shared::cta.b64 q, [%3], %4;\nand.pred p, p, q;\nselp.u32 %0, 1, 0, p;\n}\n":"=r"(r):"r"(bar0),"r"(par0),"r"(bar1),"r"(par1):"memory");
  return r; }
__device__ __forceinline__ void tma_2d(uint32_t dst, const CUtensorMap* m, int c0, int c1, uint32_t bar){
  asm volatile("cp.async.bulk.tensor.2d.shared::cluster.global.mbarrier::complete_tx::bytes [%0], [%1, {%3, %4}], [%2];"::"r"(dst),"l"(m),"r"(bar),"r"(c0),"r"(c1):"memory"); }
__device__ __forceinline__ void tma_2d_mc(uint32_t dst, const CUtensorMap* m, int c0, int c1, uint32_t bar){
  asm volatile("cp.async.bulk.tensor.2d.shared::cluster.global.mbarrier::complete_tx::bytes.multicast::cluster [%0], [%1, {%3, %4}], [%2], %5;"::"r"(dst),"l"(m),"r"(bar),"r"(c0),"r"(c1),"h"((uint16_t)3):"memory"); }
__device__ __forceinline__ void tma_2d_mc_h(uint32_t dst, const CUtensorMap* m, int c0, int c1, uint32_t bar, uint64_t pol){
  asm volatile("cp.async.bulk.tensor.2d.shared::cluster.global.mbarrier::complete_tx::bytes.multicast::cluster.L2::cache_hint [%0], [%1, {%3, %4}], [%2], %5, %6;"::"r"(dst),"l"(m),"r"(bar),"r"(c0),"r"(c1),"h"((uint16_t)3),"l"(pol):"memory"); }
__device__ __forceinline__ void tma_4d(uint32_t dst, const CUtensorMap* m, int c0, int c1, int c2, int c3, uint32_t bar){
  asm volatile("cp.async.bulk.tensor.4d.shared::cluster.global.mbarrier::complete_tx::bytes [%0], [%1, {%3, %4, %5, %6}], [%2];"::"r"(dst),"l"(m),"r"(bar),"r"(c0),"r"(c1),"r"(c2),"r"(c3):"memory"); }
__device__ __forceinline__ uint64_t policy_evict_first(){ uint64_t p; asm volatile("createpolicy.fractional.L2::evict_first.b64 %0, 1.0;":"=l"(p)); return p; }
__device__ __forceinline__ uint64_t policy_evict_normal(){ uint64_t p; asm("createpolicy.fractional.L2::evict_normal.b64 %0, 1.0;":"=l"(p)); return p; }
__device__ __forceinline__ void tma_3d_h(uint32_t dst, const CUtensorMap* m, int c0, int c1, int c2, uint32_t bar, uint64_t pol){
  asm volatile("cp.async.bulk.tensor.3d.shared::cluster.global.mbarrier::complete_tx::bytes.L2::cache_hint [%0], [%1, {%3, %4, %5}], [%2], %6;"::"r"(dst),"l"(m),"r"(bar),"r"(c0),"r"(c1),"r"(c2),"l"(pol):"memory"); }
__device__ __forceinline__ void tma_4d_h(uint32_t dst, const CUtensorMap* m, int c0, int c1, int c2, int c3, uint32_t bar, uint64_t pol){
  asm volatile("cp.async.bulk.tensor.4d.shared::cluster.global.mbarrier::complete_tx::bytes.L2::cache_hint [%0], [%1, {%3, %4, %5, %6}], [%2], %7;"::"r"(dst),"l"(m),"r"(bar),"r"(c0),"r"(c1),"r"(c2),"r"(c3),"l"(pol):"memory"); }
__device__ __forceinline__ void red_add_f32x4(float4* p, float x, float y, float z, float w){ asm volatile("red.relaxed.gpu.global.add.v4.f32 [%0], {%1,%2,%3,%4};"::"l"(p),"f"(x),"f"(y),"f"(z),"f"(w):"memory"); }
__device__ __forceinline__ void tma_5d_h(uint32_t dst, const CUtensorMap* m, int c0, int c1, uint32_t bar, uint64_t pol){
  asm volatile("cp.async.bulk.tensor.5d.shared::cluster.global.mbarrier::complete_tx::bytes.L2::cache_hint [%0], [%1, {%3, %4, 0, 0, 0}], [%2], %5;"::"r"(dst),"l"(m),"r"(bar),"r"(c0),"r"(c1),"l"(pol):"memory"); }
__device__ __forceinline__ bool elect_one(){ uint32_t p; asm volatile("{\n.reg .pred P;\nelect.sync _|P, 0xffffffff;\nselp.b32 %0, 1, 0, P;\n}\n":"=r"(p)); return p; }
__device__ __forceinline__ void bulk_prefetch(const void* p, uint32_t bytes){
  asm volatile("cp.async.bulk.prefetch.L2.global [%0], %1;"::"l"(p),"r"(bytes):"memory"); }
__device__ __forceinline__ void bulk_s2peer(uint32_t dst_cluster, uint32_t src, uint32_t bytes, uint32_t bar_cluster){
  asm volatile("cp.async.bulk.shared::cluster.shared::cta.mbarrier::complete_tx::bytes [%0], [%1], %2, [%3];"::"r"(dst_cluster),"r"(src),"r"(bytes),"r"(bar_cluster):"memory"); }
__device__ __forceinline__ void bulk_g2s_mc(uint32_t dst, const void* src, uint32_t bytes, uint32_t bar, uint64_t pol){
  asm volatile("cp.async.bulk.shared::cluster.global.mbarrier::complete_tx::bytes.multicast::cluster.L2::cache_hint [%0], [%1], %2, [%3], %4, %5;"::"r"(dst),"l"(src),"r"(bytes),"r"(bar),"h"((uint16_t)3),"l"(pol):"memory"); }
__device__ __forceinline__ void prefetch_map(const CUtensorMap* m){ asm volatile("prefetch.tensormap [%0];"::"l"(m):"memory"); }
__device__ __forceinline__ void fence_async_smem(){ asm volatile("fence.proxy.async.shared::cta;":::"memory"); }
__device__ __forceinline__ void fence_acquire_gpu(){ asm volatile("fence.acquire.gpu;":::"memory"); }
__device__ __forceinline__ void fence_gpu(){ asm volatile("fence.acq_rel.gpu;":::"memory"); }
__device__ __forceinline__ void wg_fence(){ asm volatile("wgmma.fence.sync.aligned;":::"memory"); }
__device__ __forceinline__ void wg_commit(){ asm volatile("wgmma.commit_group.sync.aligned;":::"memory"); }
template<int N> __device__ __forceinline__ void wg_wait(){ asm volatile("wgmma.wait_group.sync.aligned %0;"::"n"(N):"memory"); }
template<int N> __device__ __forceinline__ void fence_regs(float (&d)[N]){
  #pragma unroll
  for(int i=0;i<N;i++) asm volatile("":"+f"(d[i])::"memory"); }
__device__ __forceinline__ void bar_sync(int id, int n){ asm volatile("bar.sync %0, %1;"::"r"(id),"r"(n):"memory"); }
__device__ __forceinline__ void bar_arrive(int id, int n){ asm volatile("bar.arrive %0, %1;"::"r"(id),"r"(n):"memory"); }
__device__ __forceinline__ void cluster_arrive(){ asm volatile("barrier.cluster.arrive.relaxed.aligned;":::"memory"); }
__device__ __forceinline__ void cluster_wait(){ asm volatile("barrier.cluster.wait.aligned;":::"memory"); }
__host__ __device__ constexpr uint32_t dlo(uint32_t addr, uint32_t lbo){ return (addr >> 4) | ((lbo >> 4) << 16); }
__host__ __device__ constexpr uint32_t dhi(uint32_t sbo, uint32_t sw){ return (sbo >> 4) | (sw << 30); }
constexpr uint32_t H128 = dhi(1024, 1), H64 = dhi(512, 2), H0 = dhi(128, 0);
__device__ __forceinline__ uint32_t pack_bf16(float lo, float hi){ uint32_t r; asm("cvt.rn.bf16x2.f32 %0, %1, %2;":"=r"(r):"f"(hi),"f"(lo)); return r; }
__device__ __forceinline__ float bf_lo(uint32_t v){ return __uint_as_float(v<<16); }
__device__ __forceinline__ float bf_hi(uint32_t v){ return __uint_as_float(v&0xffff0000u); }
__device__ __forceinline__ float ex2(float x){ float r; asm("ex2.approx.ftz.f32 %0, %1;":"=f"(r):"f"(x)); return r; }
__device__ __forceinline__ float rcp(float x){ float r; asm("rcp.approx.ftz.f32 %0, %1;":"=f"(r):"f"(x)); return r; }
__device__ __forceinline__ void stsm4(uint32_t addr, uint32_t a, uint32_t b, uint32_t c, uint32_t d){
  asm volatile("stmatrix.sync.aligned.m8n8.x4.shared.b16 [%0], {%1,%2,%3,%4};"::"r"(addr),"r"(a),"r"(b),"r"(c),"r"(d)); }
__device__ __forceinline__ void stsm2(uint32_t addr, uint32_t a, uint32_t b){
  asm volatile("stmatrix.sync.aligned.m8n8.x2.shared.b16 [%0], {%1,%2};"::"r"(addr),"r"(a),"r"(b)); }
__device__ __forceinline__ void mma16816(float& d0, float& d1, float& d2, float& d3, uint32_t a0, uint32_t a1, uint32_t a2, uint32_t a3, uint32_t b0, uint32_t b1){
  asm volatile("mma.sync.aligned.m16n8k16.row.col.f32.bf16.bf16.f32 {%0,%1,%2,%3}, {%4,%5,%6,%7}, {%8,%9}, {%0,%1,%2,%3};"
               : "+f"(d0), "+f"(d1), "+f"(d2), "+f"(d3) : "r"(a0), "r"(a1), "r"(a2), "r"(a3), "r"(b0), "r"(b1)); }
__device__ __forceinline__ void ldsm4(uint32_t addr, uint32_t& a, uint32_t& b, uint32_t& c, uint32_t& d){
  asm volatile("ldmatrix.sync.aligned.m8n8.x4.shared.b16 {%0,%1,%2,%3}, [%4];":"=r"(a),"=r"(b),"=r"(c),"=r"(d):"r"(addr):"memory"); }
__device__ __forceinline__ void ldsm4t(uint32_t addr, uint32_t& a, uint32_t& b, uint32_t& c, uint32_t& d){
  asm volatile("ldmatrix.sync.aligned.m8n8.x4.trans.shared.b16 {%0,%1,%2,%3}, [%4];":"=r"(a),"=r"(b),"=r"(c),"=r"(d):"r"(addr):"memory"); }
__device__ __forceinline__ void sts32(uint32_t a, uint32_t v){ asm volatile("st.shared.b32 [%0], %1;"::"r"(a),"r"(v):"memory"); }
__device__ __forceinline__ void stsf(uint32_t a, float v){ asm volatile("st.shared.f32 [%0], %1;"::"r"(a),"f"(v):"memory"); }
__device__ __forceinline__ void sts64(uint32_t a, uint32_t x, uint32_t y){ asm volatile("st.shared.v2.b32 [%0], {%1,%2};"::"r"(a),"r"(x),"r"(y):"memory"); }
__device__ __forceinline__ void sts128(uint32_t a, uint32_t x, uint32_t y, uint32_t z, uint32_t w){ asm volatile("st.shared.v4.b32 [%0], {%1,%2,%3,%4};"::"r"(a),"r"(x),"r"(y),"r"(z),"r"(w):"memory"); }
__device__ __forceinline__ float ldsf(uint32_t a){ float v; asm volatile("ld.shared.f32 %0, [%1];":"=f"(v):"r"(a):"memory"); return v; }
__device__ __forceinline__ float2 lds64f(uint32_t a){ float2 v; asm volatile("ld.shared.v2.f32 {%0,%1}, [%2];":"=f"(v.x),"=f"(v.y):"r"(a):"memory"); return v; }
__device__ __forceinline__ uint4 lds128(uint32_t a){ uint4 v; asm volatile("ld.shared.v4.u32 {%0,%1,%2,%3}, [%4];":"=r"(v.x),"=r"(v.y),"=r"(v.z),"=r"(v.w):"r"(a):"memory"); return v; }
__device__ __forceinline__ uint4 ld128_keep(const void* p){ uint4 v; asm volatile("ld.global.v4.u32 {%0,%1,%2,%3}, [%4];":"=r"(v.x),"=r"(v.y),"=r"(v.z),"=r"(v.w):"l"(p):"memory"); return v; }
__device__ __forceinline__ uint4 ld128_rlx(const void* p){ uint4 v; asm volatile("ld.relaxed.gpu.global.v4.u32 {%0,%1,%2,%3}, [%4];":"=r"(v.x),"=r"(v.y),"=r"(v.z),"=r"(v.w):"l"(p):"memory"); return v; }
__device__ __forceinline__ uint32_t ld32_rlx(const void* p){ uint32_t v; asm volatile("ld.relaxed.gpu.global.u32 %0, [%1];":"=r"(v):"l"(p):"memory"); return v; }
__device__ __forceinline__ void st128_rlx(void* p, uint32_t x, uint32_t y, uint32_t z, uint32_t w){ asm volatile("st.relaxed.gpu.global.v4.u32 [%0], {%1,%2,%3,%4};"::"l"(p),"r"(x),"r"(y),"r"(z),"r"(w):"memory"); }
__device__ __forceinline__ void st64_rlx(void* p, uint32_t x, uint32_t y){ asm volatile("st.relaxed.gpu.global.v2.u32 [%0], {%1,%2};"::"l"(p),"r"(x),"r"(y):"memory"); }
__device__ __forceinline__ void st32_rlx(void* p, uint32_t x){ asm volatile("st.relaxed.gpu.global.u32 [%0], %1;"::"l"(p),"r"(x):"memory"); }
__device__ __forceinline__ uint32_t tagw(float x, uint32_t t){ return (__float_as_uint(x) & ~3u) | t; }
__device__ __forceinline__ float untag(uint32_t w){ return __uint_as_float(w & ~3u); }

template<int TA, int TB, uint32_t HA, uint32_t HB> __device__ __forceinline__ void wgmma_ss_n128(float (&d)[64], uint32_t da, uint32_t db, int scale_d){
  asm volatile("{\n.reg .pred p;\n.reg .b64 a, b;\nsetp.ne.b32 p, %70, 0;\nmov.b64 a, {%64, %68};\nmov.b64 b, {%65, %69};\n"
  "wgmma.mma_async.sync.aligned.m64n128k16.f32.bf16.bf16 {%0, %1, %2, %3, %4, %5, %6, %7, %8, %9, %10, %11, %12, %13, %14, %15, %16, %17, %18, %19, %20, %21, %22, %23, %24, %25, %26, %27, %28, %29, %30, %31, %32, %33, %34, %35, %36, %37, %38, %39, %40, %41, %42, %43, %44, %45, %46, %47, %48, %49, %50, %51, %52, %53, %54, %55, %56, %57, %58, %59, %60, %61, %62, %63}, a, b, p, 1, 1, %66, %67;\n}\n"
  : "+f"(d[0]), "+f"(d[1]), "+f"(d[2]), "+f"(d[3]), "+f"(d[4]), "+f"(d[5]), "+f"(d[6]), "+f"(d[7]), "+f"(d[8]), "+f"(d[9]), "+f"(d[10]), "+f"(d[11]), "+f"(d[12]), "+f"(d[13]), "+f"(d[14]), "+f"(d[15]), "+f"(d[16]), "+f"(d[17]), "+f"(d[18]), "+f"(d[19]), "+f"(d[20]), "+f"(d[21]), "+f"(d[22]), "+f"(d[23]), "+f"(d[24]), "+f"(d[25]), "+f"(d[26]), "+f"(d[27]), "+f"(d[28]), "+f"(d[29]), "+f"(d[30]), "+f"(d[31]), "+f"(d[32]), "+f"(d[33]), "+f"(d[34]), "+f"(d[35]), "+f"(d[36]), "+f"(d[37]), "+f"(d[38]), "+f"(d[39]), "+f"(d[40]), "+f"(d[41]), "+f"(d[42]), "+f"(d[43]), "+f"(d[44]), "+f"(d[45]), "+f"(d[46]), "+f"(d[47]), "+f"(d[48]), "+f"(d[49]), "+f"(d[50]), "+f"(d[51]), "+f"(d[52]), "+f"(d[53]), "+f"(d[54]), "+f"(d[55]), "+f"(d[56]), "+f"(d[57]), "+f"(d[58]), "+f"(d[59]), "+f"(d[60]), "+f"(d[61]), "+f"(d[62]), "+f"(d[63])
  : "r"(da), "r"(db), "n"(TA), "n"(TB), "n"(HA), "n"(HB), "r"(scale_d));
}
template<int TA, int TB, uint32_t HA, uint32_t HB> __device__ __forceinline__ void wgmma_sa_n128(float (&d)[64], uint32_t da, uint32_t db){
  asm volatile("{\n.reg .pred p;\n.reg .b64 a, b;\nsetp.ne.b32 p, 1, 0;\nmov.b64 a, {%64, %68};\nmov.b64 b, {%65, %69};\n"
  "wgmma.mma_async.sync.aligned.m64n128k16.f32.bf16.bf16 {%0, %1, %2, %3, %4, %5, %6, %7, %8, %9, %10, %11, %12, %13, %14, %15, %16, %17, %18, %19, %20, %21, %22, %23, %24, %25, %26, %27, %28, %29, %30, %31, %32, %33, %34, %35, %36, %37, %38, %39, %40, %41, %42, %43, %44, %45, %46, %47, %48, %49, %50, %51, %52, %53, %54, %55, %56, %57, %58, %59, %60, %61, %62, %63}, a, b, p, 1, 1, %66, %67;\n}\n"
  : "+f"(d[0]), "+f"(d[1]), "+f"(d[2]), "+f"(d[3]), "+f"(d[4]), "+f"(d[5]), "+f"(d[6]), "+f"(d[7]), "+f"(d[8]), "+f"(d[9]), "+f"(d[10]), "+f"(d[11]), "+f"(d[12]), "+f"(d[13]), "+f"(d[14]), "+f"(d[15]), "+f"(d[16]), "+f"(d[17]), "+f"(d[18]), "+f"(d[19]), "+f"(d[20]), "+f"(d[21]), "+f"(d[22]), "+f"(d[23]), "+f"(d[24]), "+f"(d[25]), "+f"(d[26]), "+f"(d[27]), "+f"(d[28]), "+f"(d[29]), "+f"(d[30]), "+f"(d[31]), "+f"(d[32]), "+f"(d[33]), "+f"(d[34]), "+f"(d[35]), "+f"(d[36]), "+f"(d[37]), "+f"(d[38]), "+f"(d[39]), "+f"(d[40]), "+f"(d[41]), "+f"(d[42]), "+f"(d[43]), "+f"(d[44]), "+f"(d[45]), "+f"(d[46]), "+f"(d[47]), "+f"(d[48]), "+f"(d[49]), "+f"(d[50]), "+f"(d[51]), "+f"(d[52]), "+f"(d[53]), "+f"(d[54]), "+f"(d[55]), "+f"(d[56]), "+f"(d[57]), "+f"(d[58]), "+f"(d[59]), "+f"(d[60]), "+f"(d[61]), "+f"(d[62]), "+f"(d[63])
  : "r"(da), "r"(db), "n"(TA), "n"(TB), "n"(HA), "n"(HB));
}
template<int TA, int TB, uint32_t HA, uint32_t HB> __device__ __forceinline__ void wgmma_sa_n40(float (&d)[20], uint32_t da, uint32_t db){
  asm volatile("{\n.reg .pred p;\n.reg .b64 a, b;\nsetp.ne.b32 p, 1, 0;\nmov.b64 a, {%20, %24};\nmov.b64 b, {%21, %25};\n"
  "wgmma.mma_async.sync.aligned.m64n40k16.f32.bf16.bf16 {%0, %1, %2, %3, %4, %5, %6, %7, %8, %9, %10, %11, %12, %13, %14, %15, %16, %17, %18, %19}, a, b, p, 1, 1, %22, %23;\n}\n"
  : "+f"(d[0]), "+f"(d[1]), "+f"(d[2]), "+f"(d[3]), "+f"(d[4]), "+f"(d[5]), "+f"(d[6]), "+f"(d[7]), "+f"(d[8]), "+f"(d[9]), "+f"(d[10]), "+f"(d[11]), "+f"(d[12]), "+f"(d[13]), "+f"(d[14]), "+f"(d[15]), "+f"(d[16]), "+f"(d[17]), "+f"(d[18]), "+f"(d[19])
  : "r"(da), "r"(db), "n"(TA), "n"(TB), "n"(HA), "n"(HB));
}
template<int TA, int TB, uint32_t HA, uint32_t HB> __device__ __forceinline__ void wgmma_sz_n40(float (&d)[20], uint32_t da, uint32_t db){
  asm volatile("{\n.reg .pred p;\n.reg .b64 a, b;\nsetp.ne.b32 p, 0, 0;\nmov.b64 a, {%20, %24};\nmov.b64 b, {%21, %25};\n"
  "wgmma.mma_async.sync.aligned.m64n40k16.f32.bf16.bf16 {%0, %1, %2, %3, %4, %5, %6, %7, %8, %9, %10, %11, %12, %13, %14, %15, %16, %17, %18, %19}, a, b, p, 1, 1, %22, %23;\n}\n"
  : "=f"(d[0]), "=f"(d[1]), "=f"(d[2]), "=f"(d[3]), "=f"(d[4]), "=f"(d[5]), "=f"(d[6]), "=f"(d[7]), "=f"(d[8]), "=f"(d[9]), "=f"(d[10]), "=f"(d[11]), "=f"(d[12]), "=f"(d[13]), "=f"(d[14]), "=f"(d[15]), "=f"(d[16]), "=f"(d[17]), "=f"(d[18]), "=f"(d[19])
  : "r"(da), "r"(db), "n"(TA), "n"(TB), "n"(HA), "n"(HB));
}
template<int TA, int TB, uint32_t HA, uint32_t HB> __device__ __forceinline__ void wgmma_sa_n32(float (&d)[16], uint32_t da, uint32_t db){
  asm volatile("{\n.reg .pred p;\n.reg .b64 a, b;\nsetp.ne.b32 p, 1, 0;\nmov.b64 a, {%16, %20};\nmov.b64 b, {%17, %21};\n"
  "wgmma.mma_async.sync.aligned.m64n32k16.f32.bf16.bf16 {%0, %1, %2, %3, %4, %5, %6, %7, %8, %9, %10, %11, %12, %13, %14, %15}, a, b, p, 1, 1, %18, %19;\n}\n"
  : "+f"(d[0]), "+f"(d[1]), "+f"(d[2]), "+f"(d[3]), "+f"(d[4]), "+f"(d[5]), "+f"(d[6]), "+f"(d[7]), "+f"(d[8]), "+f"(d[9]), "+f"(d[10]), "+f"(d[11]), "+f"(d[12]), "+f"(d[13]), "+f"(d[14]), "+f"(d[15])
  : "r"(da), "r"(db), "n"(TA), "n"(TB), "n"(HA), "n"(HB));
}
template<int TA, int TB, uint32_t HA, uint32_t HB> __device__ __forceinline__ void wgmma_ss_n32(float (&d)[16], uint32_t da, uint32_t db, int scale_d){
  asm volatile("{\n.reg .pred p;\n.reg .b64 a, b;\nsetp.ne.b32 p, %22, 0;\nmov.b64 a, {%16, %20};\nmov.b64 b, {%17, %21};\n"
  "wgmma.mma_async.sync.aligned.m64n32k16.f32.bf16.bf16 {%0, %1, %2, %3, %4, %5, %6, %7, %8, %9, %10, %11, %12, %13, %14, %15}, a, b, p, 1, 1, %18, %19;\n}\n"
  : "+f"(d[0]), "+f"(d[1]), "+f"(d[2]), "+f"(d[3]), "+f"(d[4]), "+f"(d[5]), "+f"(d[6]), "+f"(d[7]), "+f"(d[8]), "+f"(d[9]), "+f"(d[10]), "+f"(d[11]), "+f"(d[12]), "+f"(d[13]), "+f"(d[14]), "+f"(d[15])
  : "r"(da), "r"(db), "n"(TA), "n"(TB), "n"(HA), "n"(HB), "r"(scale_d));
}
template<int TB, uint32_t HB> __device__ __forceinline__ void wgmma_ra_n32(float (&d)[16], uint32_t a0, uint32_t a1, uint32_t a2, uint32_t a3, uint32_t db){
  asm volatile("{\n.reg .pred p;\n.reg .b64 a, b;\nsetp.ne.b32 p, 1, 0;\nmov.b64 b, {%20, %22};\n"
  "wgmma.mma_async.sync.aligned.m64n32k16.f32.bf16.bf16 {%0, %1, %2, %3, %4, %5, %6, %7, %8, %9, %10, %11, %12, %13, %14, %15}, {%16,%17,%18,%19}, b, p, 1, 1, %21;\n}\n"
  : "+f"(d[0]), "+f"(d[1]), "+f"(d[2]), "+f"(d[3]), "+f"(d[4]), "+f"(d[5]), "+f"(d[6]), "+f"(d[7]), "+f"(d[8]), "+f"(d[9]), "+f"(d[10]), "+f"(d[11]), "+f"(d[12]), "+f"(d[13]), "+f"(d[14]), "+f"(d[15])
  : "r"(a0), "r"(a1), "r"(a2), "r"(a3), "r"(db), "n"(TB), "n"(HB));
}
template<int TB, uint32_t HB> __device__ __forceinline__ void wgmma_rs_n32(float (&d)[16], uint32_t a0, uint32_t a1, uint32_t a2, uint32_t a3, uint32_t db, int scale_d){
  asm volatile("{\n.reg .pred p;\n.reg .b64 a, b;\nsetp.ne.b32 p, %23, 0;\nmov.b64 b, {%20, %22};\n"
  "wgmma.mma_async.sync.aligned.m64n32k16.f32.bf16.bf16 {%0, %1, %2, %3, %4, %5, %6, %7, %8, %9, %10, %11, %12, %13, %14, %15}, {%16,%17,%18,%19}, b, p, 1, 1, %21;\n}\n"
  : "+f"(d[0]), "+f"(d[1]), "+f"(d[2]), "+f"(d[3]), "+f"(d[4]), "+f"(d[5]), "+f"(d[6]), "+f"(d[7]), "+f"(d[8]), "+f"(d[9]), "+f"(d[10]), "+f"(d[11]), "+f"(d[12]), "+f"(d[13]), "+f"(d[14]), "+f"(d[15])
  : "r"(a0), "r"(a1), "r"(a2), "r"(a3), "r"(db), "n"(TB), "n"(HB), "r"(scale_d));
}
template<int TB, uint32_t HB> __device__ __forceinline__ void wgmma_ra_n40(float (&d)[20], uint32_t a0, uint32_t a1, uint32_t a2, uint32_t a3, uint32_t db){
  asm volatile("{\n.reg .pred p;\n.reg .b64 a, b;\nsetp.ne.b32 p, 1, 0;\nmov.b64 b, {%24, %26};\n"
  "wgmma.mma_async.sync.aligned.m64n40k16.f32.bf16.bf16 {%0, %1, %2, %3, %4, %5, %6, %7, %8, %9, %10, %11, %12, %13, %14, %15, %16, %17, %18, %19}, {%20,%21,%22,%23}, b, p, 1, 1, %25;\n}\n"
  : "+f"(d[0]), "+f"(d[1]), "+f"(d[2]), "+f"(d[3]), "+f"(d[4]), "+f"(d[5]), "+f"(d[6]), "+f"(d[7]), "+f"(d[8]), "+f"(d[9]), "+f"(d[10]), "+f"(d[11]), "+f"(d[12]), "+f"(d[13]), "+f"(d[14]), "+f"(d[15]), "+f"(d[16]), "+f"(d[17]), "+f"(d[18]), "+f"(d[19])
  : "r"(a0), "r"(a1), "r"(a2), "r"(a3), "r"(db), "n"(TB), "n"(HB));
}
template<int TB, uint32_t HB> __device__ __forceinline__ void wgmma_rz_n40(float (&d)[20], uint32_t a0, uint32_t a1, uint32_t a2, uint32_t a3, uint32_t db){
  asm volatile("{\n.reg .pred p;\n.reg .b64 a, b;\nsetp.ne.b32 p, 0, 0;\nmov.b64 b, {%24, %26};\n"
  "wgmma.mma_async.sync.aligned.m64n40k16.f32.bf16.bf16 {%0, %1, %2, %3, %4, %5, %6, %7, %8, %9, %10, %11, %12, %13, %14, %15, %16, %17, %18, %19}, {%20,%21,%22,%23}, b, p, 1, 1, %25;\n}\n"
  : "=f"(d[0]), "=f"(d[1]), "=f"(d[2]), "=f"(d[3]), "=f"(d[4]), "=f"(d[5]), "=f"(d[6]), "=f"(d[7]), "=f"(d[8]), "=f"(d[9]), "=f"(d[10]), "=f"(d[11]), "=f"(d[12]), "=f"(d[13]), "=f"(d[14]), "=f"(d[15]), "=f"(d[16]), "=f"(d[17]), "=f"(d[18]), "=f"(d[19])
  : "r"(a0), "r"(a1), "r"(a2), "r"(a3), "r"(db), "n"(TB), "n"(HB));
}
template<int TB, uint32_t HB> __device__ __forceinline__ void wgmma_ra_n8(float (&d)[4], uint32_t a0, uint32_t a1, uint32_t a2, uint32_t a3, uint32_t db){
  asm volatile("{\n.reg .pred p;\n.reg .b64 a, b;\nsetp.ne.b32 p, 1, 0;\nmov.b64 b, {%8, %10};\n"
  "wgmma.mma_async.sync.aligned.m64n8k16.f32.bf16.bf16 {%0, %1, %2, %3}, {%4,%5,%6,%7}, b, p, 1, 1, %9;\n}\n"
  : "+f"(d[0]), "+f"(d[1]), "+f"(d[2]), "+f"(d[3])
  : "r"(a0), "r"(a1), "r"(a2), "r"(a3), "r"(db), "n"(TB), "n"(HB));
}
template<int TB, uint32_t HB> __device__ __forceinline__ void wgmma_rz_n8(float (&d)[4], uint32_t a0, uint32_t a1, uint32_t a2, uint32_t a3, uint32_t db){
  asm volatile("{\n.reg .pred p;\n.reg .b64 a, b;\nsetp.ne.b32 p, 0, 0;\nmov.b64 b, {%8, %10};\n"
  "wgmma.mma_async.sync.aligned.m64n8k16.f32.bf16.bf16 {%0, %1, %2, %3}, {%4,%5,%6,%7}, b, p, 1, 1, %9;\n}\n"
  : "=f"(d[0]), "=f"(d[1]), "=f"(d[2]), "=f"(d[3])
  : "r"(a0), "r"(a1), "r"(a2), "r"(a3), "r"(db), "n"(TB), "n"(HB));
}

constexpr int SEQ = 2048, DM = 1024, FF = 3584;
constexpr float LOG2E = 1.4426950408889634f;
constexpr uint32_t POLL_LIMIT = 1u << 22;
#define NPRE0 1
#define NPREN 2
constexpr int NPRE = NPREN;
#define QW 0
#define RS_N 22
#define RS_D1 430
#define RS_D2 300
#define SKM 0x154
#define LAG 2
#define PF_T0 5000
#define PF_DT 800
#define NFFN_L NFFN
#define FF_DT 500
#define OUT_U 1
#define GRES 8
#define OUT_L 0
#define TMASK 0xffffff
#define PMASK 0xffffff
#define FF_T0 400
#define GPRE 0
#define REL 6
#define EFI 11
#define TKW 8
#define SLOT 0
#define SLOTW 48
#define FF_ORD 0x76543210ba98ull
#define KT 0
#define KK(id) do { if (KT) { TK(32 * wg + (id)); } } while (0)
#define PF_I0 0
#define PF_ST 7
#define OUT_NS 60
constexpr int NFFN = 112;

constexpr uint32_t SB0 = 1024;
constexpr uint32_t KV_STAGE = 49152, R5 = 32768;
constexpr uint32_t OFF_X = 163840, OFF_S = 196608, OFF_WPHI = OFF_S + 20480, OFF_M = 229376, SMEM_BYTES = 232448;
constexpr uint32_t OFF_RS256 = 212992, OFF_ONES = OFF_RS256 + 1024, OFF_WPHIK1 = OFF_ONES + 1024, OFF_KVZ = OFF_S;
constexpr uint32_t OFF_WPHIK = OFF_S, OFF_BXK = OFF_S + 2048, OFF_AXK = OFF_S + 4096, OFF_G = OFF_S + 8192;
constexpr uint32_t OFF_AXQ = OFF_WPHI, OFF_BXQ = OFF_WPHI + 2048, OFF_WPHIQ = OFF_WPHI + 4096;
constexpr uint32_t B_FULLKV = OFF_M  , B_EMPTYKV = OFF_M + 32  ;
constexpr uint32_t B_EMPTY5 = OFF_M + 64  , B_UO = B_EMPTY5 + 48  , B_RC = B_UO + 32  ;
constexpr uint32_t B_OUT = B_RC + 16  , B_AUX = B_OUT + 32, B_AUXQ = B_AUX + 8, B_RX = B_AUXQ + 8;
constexpr uint32_t B_FULL5 = B_RX + 8  , B_FULLA = B_FULL5 + 48  , B_F = B_FULLA + 96  , B_WD = B_F + 64  ;
constexpr uint32_t B_WC = B_WD + 32  , B_DR = B_WC + 32  , B_W = B_DR + 24, B_OS = B_W + 8, B_R = B_W + 16, B_KD = B_W + 24, B_XS = B_W + 32, B_T = B_W + 40, B_G = B_W + 48, B_END = B_W + 56, B_S0 = B_END;
static_assert(B_S0 < OFF_M + 576 && B_END <= OFF_M + 568 && B_FULL5 + 40 >= OFF_M + 200 && B_FULL5 + 40 < OFF_M + 384, "barriers");
constexpr uint32_t OFF_EXC = OFF_M + 576, OFF_SUMWR = OFF_M + 608, OFF_EP = OFF_M + 624, OFF_KEY = OFF_M + 628;
constexpr uint32_t OFF_RSQ = OFF_M + 640, OFF_TL = OFF_M + 1152, OFF_T = OFF_M + 1792, OFF_WR = OFF_M + 2048, OFF_SCR = OFF_M + 2432;
constexpr uint32_t OFF_XSEL = 2 * R5, OFF_ACT = OFF_XSEL + 2048, OFF_GU = OFF_XSEL + 4096, OFF_OUT = 3 * R5;
constexpr uint64_t FF_SLOT = 0xdcdc3210dcbaull;
constexpr int KVP = 6 * 128;

enum { NB_G2E = 1, NB_XS = 2, NB_WG01 = 3, NB_ACT = 4, NB_Q0 = 5  , NB_ST = 14, NB_DN = 9, NB_ZERO = 10, NB_PUB = 11, NB_TOK = 10  , NB_L0 = 12  , NB_WG2 = 7, NB_QGO = 15 };

struct Scratch {
  bf16     o[SEQ * DM];
  float4   rstat[SEQ];
  uint32_t key[32 * 128];
  uint32_t cand[128 * DM];
  uint32_t ypart[NFFN * DM];
  float4   kvacc[32 * KVP];
  uint2    stats[SEQ];
  uint32_t cskv[2 * DM];
  uint32_t csq[4 * DM];
  uint32_t oset[128 * 16];
  uint32_t epoch;
};
__device__ __align__(1024) Scratch g_scr;
#define TS(id)
#define TDUMP()
#define TS0_DECL()
#define TS0_READ()
#define TS0_WRITE()
#define TK(id)
#define TSW(id)

struct Params {
  CUtensorMap x128, x64, wkv, wq, wo[2], wd, wg, wu, phi, tg, tu, td, xs, ws, qs;
  const bf16 *x, *wqkv, *wo_p, *wg_p, *wu_p, *wd_p, *wr;
  bf16* out_p;
  Scratch* g;
  uint32_t zero;
};

constexpr float EXP_LIM = 1.1529215e18f, ARG_LIM2 = 3600.f;
__device__ __forceinline__ void dual_exp2(const float (&p)[2][16], uint32_t (&ph)[4][8]) {
  #pragma unroll
  for (int h = 0; h < 2; h++)
    #pragma unroll
    for (int k = 0; k < 8; k++) { ph[2*h][k] = pack_bf16(ex2(p[h][2*k]), ex2(p[h][2*k+1])); ph[2*h+1][k] = pack_bf16(ex2(-p[h][2*k]), ex2(-p[h][2*k+1])); }
}
__device__ __forceinline__ void row_extremes(const float (&p)[16], const float (&c)[2], float (&m)[4]) {
  m[0] = m[2] = p[0]; m[1] = m[3] = p[2];
  #pragma unroll
  for (int i = 0; i < 16; i++) { m[(i >> 1) & 1] = fmaxf(m[(i >> 1) & 1], p[i]); m[2 + ((i >> 1) & 1)] = fminf(m[2 + ((i >> 1) & 1)], p[i]); }
  #pragma unroll
  for (int o = 1; o < 4; o <<= 1) {
    m[0] = fmaxf(m[0], __shfl_xor_sync(~0u, m[0], o)); m[1] = fmaxf(m[1], __shfl_xor_sync(~0u, m[1], o));
    m[2] = fminf(m[2], __shfl_xor_sync(~0u, m[2], o)); m[3] = fminf(m[3], __shfl_xor_sync(~0u, m[3], o));
  }
  m[0] *= -c[0]; m[1] *= -c[1]; m[2] *= c[0]; m[3] *= c[1];
}
__device__ __forceinline__ void dual_exp2_shifted(const float (&p)[2][16], uint32_t (&ph)[4][8]) {
  #pragma unroll
  for (int h = 0; h < 2; h++) {
    const float one[2] = {1.f, 1.f};
    float m[4];
    row_extremes(p[h], one, m);
    #pragma unroll
    for (int k = 0; k < 8; k++) {
      ph[2*h][k] = pack_bf16(ex2(p[h][2*k] + m[k & 1]), ex2(p[h][2*k+1] + m[k & 1]));
      ph[2*h+1][k] = pack_bf16(ex2(m[2 + (k & 1)] - p[h][2*k]), ex2(m[2 + (k & 1)] - p[h][2*k+1]));
    }
  }
}
__device__ __forceinline__ void row_sums(float (&s)[4][4], const uint32_t (&ph)[4][8], uint32_t ones) {
  #pragma unroll
  for (int i = 0; i < 4; i++) wgmma_rz_n8<0, H0>(s[i], ph[i][0], ph[i][1], ph[i][2], ph[i][3], ones);
  #pragma unroll
  for (int i = 0; i < 4; i++) wgmma_ra_n8<0, H0>(s[i], ph[i][4], ph[i][5], ph[i][6], ph[i][7], ones);
}
__device__ __forceinline__ uint32_t mul_bf16x2(uint32_t a, uint32_t b) { uint32_t r; asm("mul.rn.bf16x2 %0, %1, %2;" : "=r"(r) : "r"(a), "r"(b)); return r; }
__device__ __forceinline__ void normalize(uint32_t (&ph)[4][8], const float (&s)[4][4]) {
  #pragma unroll
  for (int i = 0; i < 4; i++) {
    const float i0 = rcp(s[i][0]), i1 = rcp(s[i][2]);
    const uint32_t n0 = pack_bf16(i0, i0), n1 = pack_bf16(i1, i1);
    #pragma unroll
    for (int k = 0; k < 4; k++) { ph[i][2*k] = mul_bf16x2(ph[i][2*k], n0); ph[i][2*k+1] = mul_bf16x2(ph[i][2*k+1], n1); }
  }
}
__device__ __forceinline__ void split_bf16(float a, float b, uint32_t& hi, uint32_t& lo) { hi = pack_bf16(a, b); lo = pack_bf16(a - bf_lo(hi), b - bf_hi(hi)); }
__device__ __forceinline__ void put_colsums(uint32_t base, int lane, float a, float b, float c, float d) {
  uint32_t h0, l0, h1, l1;
  split_bf16(a, b, h0, l0); split_bf16(c, d, h1, l1);
  const uint32_t ad = base + (lane >> 1) * 128 + (lane & 1) * 8;
  sts64(ad, h0, h1); sts64(ad + 16, l0, l1); sts64(ad + 32, h0, h1); sts64(ad + 48, l0, l1);
  sts128(base + (lane >> 1) * 128 + 64 + (lane & 1) * 32, 0, 0, 0, 0); sts128(base + (lane >> 1) * 128 + 80 + (lane & 1) * 32, 0, 0, 0, 0);
}
__device__ __forceinline__ float reduce8(const float (&v)[8], int lane) {
  const bool b4 = lane & 16, b3 = lane & 8, b2 = lane & 4;
  float a[4], b[2];
  #pragma unroll
  for (int i = 0; i < 4; i++) a[i] = (b4 ? v[4 + i] : v[i]) + __shfl_xor_sync(~0u, b4 ? v[i] : v[4 + i], 16);
  #pragma unroll
  for (int i = 0; i < 2; i++) b[i] = (b3 ? a[2 + i] : a[i]) + __shfl_xor_sync(~0u, b3 ? a[i] : a[2 + i], 8);
  return (b2 ? b[1] : b[0]) + __shfl_xor_sync(~0u, b2 ? b[0] : b[1], 4);
}
__device__ __forceinline__ bool tag_bad(uint4 v, uint32_t tg) { return (((v.x ^ tg) | (v.y ^ tg) | (v.z ^ tg) | (v.w ^ tg)) & 3) != 0; }

__global__ void __launch_bounds__(512, 1) fused_kernel(const __grid_constant__ Params P) {
  extern __shared__ __align__(1024) uint8_t smem_raw[];
  const uint32_t sb = smem_u32(smem_raw);
  const int tid = threadIdx.x, lane = tid & 31;
  TS0_DECL();
  TS0_READ();
  if (tid == 352) { prefetch_map(&P.wkv); prefetch_map(&P.x128); }
  const int cp = blockIdx.x >> 1, rank = blockIdx.x & 1;
  const int cr = cp < 4 ? 32 + 8 * cp : cp - 4 + max((cp * 37 - 1076) >> 8, 0);
  const int c = (cr & 62) + 64 * (cr & 1) + rank;
  const int m256 = c >> 4, nkv = c & 15, m128 = c >> 3, j = c & 7;
  if ((tid >> 5) == 12 && elect_one()) {
    mbar_init(sb + B_S0, 1); mbar_init(sb + B_FULLKV, 1); mbar_init(sb + B_FULLKV + 8, 1);
    fence_async_smem();
    mbar_expect_tx(sb + B_S0, 32768);
    tma_4d(sb + 32768, &P.wkv, 0, 0, nkv, 1, sb + B_S0);
    tma_2d(sb, &P.x128, 0, 256 * m256, sb + B_S0);
    mbar_expect_tx(sb + B_FULLKV, 16384);
    tma_2d(sb + 16384, &P.x128, 0, 256 * m256 + 128, sb + B_FULLKV);
    if (NPRE0 > 1) {
      mbar_expect_tx(sb + B_FULLKV + 8, KV_STAGE);
      tma_4d(sb + KV_STAGE + 32768, &P.wkv, 0, 64, nkv, 1, sb + B_FULLKV + 8);
      tma_2d(sb + KV_STAGE, &P.x128, 64, 256 * m256, sb + B_FULLKV + 8);
      tma_2d(sb + KV_STAGE + 16384, &P.x128, 64, 256 * m256 + 128, sb + B_FULLKV + 8);
    }
    asm volatile("fence.mbarrier_init.release.cluster;" ::: "memory");
  }
  #pragma unroll
  for (int w = 0; w < 3; w++)
    if (tid == 32 + 32 * w) {
      #pragma unroll
      for (uint32_t b = B_FULLKV + 16 + 184 * w; b < B_FULLKV + 200 + 184 * w && b < B_END; b += 8)
        mbar_init(sb + b, b < B_EMPTYKV ? 1 : b < B_EMPTY5 ? 12 : b < B_OUT ? 4 : b < B_RX || b == B_W ? 2 : b == B_RX ? 8 : 1);
      if (w == 1) mbar_arrive(sb + B_FULL5 + 40);
      asm volatile("fence.mbarrier_init.release.cluster;" ::: "memory");
      fence_async_smem();
    }
  const int warp = __shfl_sync(~0u, tid >> 5, 0), wg = warp >> 2, wp = warp & 3;
  const int f = 16 * ((cr + 7) & 7) + 2 * (cr >> 3) + rank;
  const int ha = 4 * (nkv >> 1) + (nkv & 1);
  Scratch* const G = P.g;
  if ((sb & 0x3ffff) != SB0) asm volatile("trap;");
  __syncthreads();
  cluster_arrive();
  if (warp == 12) {
    TK(88 - 32);
    if (elect_one()) {
      #pragma unroll
      for (int s = NPRE0; s < NPRE; s++) {
        const uint32_t st = sb + s * KV_STAGE, fb = sb + B_FULLKV + 8 * s;
        mbar_expect_tx(fb, KV_STAGE);
        tma_4d(st + 32768, &P.wkv, 0, 64 * s, nkv, 1, fb);
        tma_2d(st, &P.x128, 64 * s, 256 * m256, fb);
        tma_2d(st + 16384, &P.x128, 64 * s, 256 * m256 + 128, fb);
      }
    }
    __syncwarp();
  }

  if (wg == 3) {
    asm volatile("setmaxnreg.dec.sync.aligned.u32 32;");
    cluster_wait();
    if (wp == 0) { TK(89 - 32); }
    const bool el = elect_one();
    const uint64_t ef = policy_evict_first(), en = policy_evict_normal();
    auto fetch_o = [&](const int t0, uint32_t so, uint32_t par) {
      const int sh = t0 & 1;
      uint32_t ready = 0;
      const bf16* base = G->o + (m128 * 16 + t0) * 8192 + rank * 4096;
      const bf16* hint = base + (lane & 3) * 1024 + 966 + (((j & 6) + ((lane >> 2) & ~sh)) & 7) * 16384 + 8 * sh * (~lane & 4);
      #pragma unroll 1
      for (int i = 2 - 2 * sh; i < 8; i += 1 + sh) {
        uint32_t it = 0;
        while ((~ready >> (4 * i) & (15 + 240 * sh)) && ++it < POLL_LIMIT) ready = __ballot_sync(~0u, ld32_rlx(hint) != ~0u);
        mbar_wait(sb + B_EMPTY5 + so, par);
        if (el) {
          bulk_g2s_mc(sb + so * 4096 + rank * 8192, base + (((j & 6) + i) & 7) * 16384, 8192, sb + B_FULLA + 2 * so + 8 * rank, ef);
          if (i == 2 - 2 * sh) TS(t0 == 0 ? (rank ? 4 : 12) : t0 == 3 ? (rank ? 31 : 10) : (rank ? 9 : 13));
        }
        so += 8;
        if (so == 48) { so = 0; par ^= 1; }
      }
    };
    if (wp == 0) {
      {
        #pragma unroll 1
        for (int kb = NPRE; kb < 16; kb++) {
          const uint32_t st = sb + (kb & 3) * KV_STAGE, fb = sb + B_FULLKV + 8 * (kb & 3);
          mbar_wait(fb + (B_EMPTYKV - B_FULLKV), ~(kb >> 2) & 1);
          if (el) {
            mbar_expect_tx(fb, KV_STAGE);
            tma_2d_mc(st + rank * 16384, &P.x128, 64 * kb, 256 * m256 + 128 * rank, fb);
            tma_4d_h(st + 32768, &P.wkv, 0, 64 * kb, nkv, 1, fb, ef);
          }
        }
        TS0_WRITE();
        uint64_t ord = 0xf3120edcba987654ull;
        uint32_t so = 0, par = 1;
        #pragma unroll 1
        for (int i = 0; i < 16; i++) {
          const uint32_t st = sb + so * 4096, fb = sb + B_FULL5 + so;
          const int k0 = (64 * (uint32_t)ord + 128 * (j & 6)) & 960;
          mbar_wait(i < 5 ? sb + B_EMPTYKV + so - (i > 1 ? 8 : 0) : fb + (B_EMPTY5 - B_FULL5), par);
          if (el) {
            mbar_expect_tx(fb, R5);
            tma_2d_mc_h(st + rank * 8192, &P.x64, k0, 128 * m128 + 64 * rank, fb, i >= EFI ? ef : en);
            tma_3d_h(st + 16384, &P.wq, 0, k0, 2 * j, fb, ef);
          }
          ord >>= 4; so += 8;
          if (so == 40) { so = 0; par ^= 1; }
        }
        #pragma unroll 1
        for (int i = 0; i < 19; i++) {
          const uint32_t fb = sb + B_FULL5 + so, fa = sb + B_FULLA + 2 * so, na = i == rank ? 0 : 8192;
          if (i == 1) { mbar_wait2(sb + B_FULL5 + 16, 0, sb + B_FULL5 + 24, 0); mbar_wait(sb + B_FULL5 + 32, 0); if (el) mbar_arrive(sb + B_R); }
          mbar_wait(fb + (B_EMPTY5 - B_FULL5), par);
          if (SLOT) { while (((uint32_t)clock() & (uint32_t)(SLOT - 1)) >= SLOTW) {} }
          if (el) {
            if (i < 16) {
              mbar_expect_tx(fb, 16384);
              const int row = i < 8 ? 128 * (((j & 6) + i) & 7) : 256 * (((j >> 1) + i) & 3) + 32 + 16 * (i & 4);
              tma_5d_h(sb + so * 4096 + 16384, &P.wo[i >> 3], 128 * j, row, fb, ef);
              tma_5d_h(sb + so * 4096 + 24576, &P.wo[i >> 3], 128 * j + 64, row, fb, ef);
              mbar_expect_tx(fa, na); mbar_expect_tx(fa + 8, na);
            } else mbar_arrive(sb + B_DR + 8 * (i - 16));
          }
          so += 8;
          if (so == 48) { so = 0; par ^= 1; }
        }
      }
    } else if (wp == 3) {
      const uint32_t t_start = (uint32_t)clock();
      if (el) {
        mbar_expect_tx(sb + B_W, 12288);
        #pragma unroll 1
        for (int i = 0; i < 6; i++) tma_2d(sb + (i == 0 ? OFF_WPHIK : i == 1 ? OFF_WPHIK1 : OFF_WPHIQ + 2048 * (i - 2)), &P.phi, 0, 32 * (i < 2 ? 2 * nkv + i : 4 * j + 2 * (i & 1) + ((i - 2) >> 1)), sb + B_W);
        prefetch_map(&P.x64); prefetch_map(&P.wq); prefetch_map(&P.wo[0]); prefetch_map(&P.wo[1]);
        prefetch_map(&P.wd); prefetch_map(&P.wg); prefetch_map(&P.wu);
      }
      #pragma unroll 1
      for (int i = 0; i < 8; i++) {
        st128_rlx(&G->cand[(m128 * 8 + i) * DM + (lane >> 4) * 512 + 64 * j + 4 * (lane & 15)], ~0u, ~0u, ~0u, ~0u);
        if (f < NFFN) st128_rlx(&G->ypart[f * DM + 128 * i + 4 * lane], ~0u, ~0u, ~0u, ~0u);
      }
      if (lane < 16) st128_rlx(&G->rstat[16 * c + lane], 0, 0, 0, 0);
      {
        const uint32_t nt = ld32_rlx(&G->epoch);
        if (lane < 8) { st128_rlx(&G->stats[16 * c + 2 * lane], nt, nt, nt, nt); st128_rlx(&G->csq[32 * c + 4 * lane], nt, nt, nt, nt); }
        if (lane < 4) { st128_rlx(&G->cskv[128 * nkv + 16 * m256 + 4 * lane], nt, nt, nt, nt); st128_rlx(&G->oset[16 * c + 4 * lane], nt, nt, nt, nt); }
      }
      if (lane < 8) st128_rlx(&G->key[(4 * j + (lane >> 1)) * 128 + m128 * 8 + 4 * (lane & 1)], 0, 0, 0, 0);
      if (c < 32) {
        #pragma unroll 1
        for (int i = lane; i < KVP; i += 32) st128_rlx(&G->kvacc[(ha + 2 * m256) * KVP + i], 0, 0, 0, 0);
      }
      fence_gpu();
      bar_arrive(NB_ZERO, 160);
      if (el) {
        #pragma unroll 1
        for (int i = PF_I0; i < 30; i++) {
          while ((uint32_t)clock() - t_start < (uint32_t)(PF_T0 + PF_DT * (i - PF_I0) + PF_ST * f)) __nanosleep(64);
          if (i < 4) { bulk_prefetch(P.wqkv + (size_t)(256 * i + c) * (3 * DM), 2048); bulk_prefetch(P.wqkv + (size_t)(256 * i + 128 + c) * (3 * DM), 2048); }
          else if (i < 6) bulk_prefetch(P.wo_p + (size_t)c * 8192 + (i - 4) * 4096, 8192);
          else if ((TMASK >> (i - 6)) & 1) {
            const int k = i - 6;
            if (f < NFFN) {
              if (k < 16) {
                #pragma unroll 1
                for (int e = 0; e < 4; e++) tma_2d(sb + OFF_T, rank ? &P.tu : &P.tg, 32 * (f & ~1), 64 * k + 16 * e, sb + B_T);
              } else { tma_2d(sb + OFF_T, &P.td, 0, 256 * f + 32 * (k - 16), sb + B_T); tma_2d(sb + OFF_T, &P.td, 0, 256 * f + 32 * (k - 16) + 16, sb + B_T); }
            }
          }
          else if (!((PMASK >> (i - 6)) & 1)) {}
          else if (i < 22) bulk_prefetch(((i & 1) ? P.wu_p : P.wg_p) + (size_t)((i - 6) >> 1) * 458752 + c * 3584, 7168);
          else bulk_prefetch(P.wd_p + (size_t)(i - 22) * 458752 + c * 3584, 7168);
        }
      }
      __syncwarp();
      mbar_wait2(sb + B_OS, 0, sb + B_RX, 0);
      #pragma unroll 1
      for (int t0 = 0; t0 < 4; t0 += 3) fetch_o(t0, t0 ? 8 : 24, 0);
    } else {
      const int half = wp - 1;
      const uint32_t ep1 = ld32_rlx(&G->epoch) + 1, tg = ep1 & 3;
      {
        uint32_t it = 0;
        sts128(sb + OFF_ONES + half * 512 + lane * 16, 0x3f803f80u, 0x3f803f80u, 0x3f803f80u, 0x3f803f80u);
        auto reset_o = [&](int i0, int i1, uint32_t dt) {
          uint32_t t0 = (uint32_t)clock();
          #pragma unroll 1
          for (int i = i0; i < i1; i++) {
            st128_rlx(G->o + (m128 * 16 + 2 * j + half) * 8192 + 256 * i + 8 * lane, ~0u, ~0u, ~0u, ~0u);
            while ((uint32_t)clock() - t0 < dt) __nanosleep(40);
            t0 += dt;
          }
        };
        mbar_wait(sb + B_S0, 0);
        reset_o(0, RS_N, RS_D1);
        bar_sync(NB_PUB, 192);
        const uint4* src = reinterpret_cast<const uint4*>(&G->stats[256 * m256 + 128 * half]) + lane;
        const uint4* srk = reinterpret_cast<const uint4*>(&G->cskv[128 * nkv]) + lane;
        uint4 v0, v1, vk;
        it = 0;
        do { v0 = ld128_rlx(src); v1 = ld128_rlx(src + 32); vk = ld128_rlx(srk); }
        while ((tag_bad(v0, tg) || tag_bad(v1, tg) || tag_bad(vk, tg)) && ++it < POLL_LIMIT);
        fence_acquire_gpu();
        if (half) put_colsums(sb + OFF_BXK, lane, untag(vk.x), untag(vk.y), untag(vk.z), untag(vk.w));
        #pragma unroll
        for (int i = 0; i < 2; i++) {
          const uint4 v = i ? v1 : v0;
          uint32_t hi, lo;
          split_bf16(-0.5f * untag(v.x), -0.5f * untag(v.z), hi, lo);
          const uint32_t h0 = __byte_perm(hi, hi, 0x1010), h1 = __byte_perm(hi, hi, 0x3232), l0 = __byte_perm(lo, lo, 0x1010), l1 = __byte_perm(lo, lo, 0x3232);
          const uint32_t a = sb + OFF_AXK + half * 2048 + i * 1024 + lane * 32;
          sts128(a, h0, l0, 0, 0); sts128(a + 16, h1, l1, 0, 0);
          sts64(sb + OFF_RS256 + half * 512 + i * 256 + lane * 8, v.y & ~3u, v.w & ~3u);
          if (half == (m128 & 1)) {
            const uint32_t aq = sb + OFF_AXQ + i * 1024 + lane * 32;
            sts128(aq, h0, l0, 0, 0); sts128(aq + 16, h1, l1, 0, 0);
            sts64(sb + OFF_RSQ + i * 256 + lane * 8, v.y & ~3u, v.w & ~3u);
          }
        }
        fence_async_smem();
        __syncwarp();
        if (el) { sts32(sb + OFF_EP, ep1); mbar_arrive(sb + B_AUX); if (!half) TS(1); }
        reset_o(RS_N, 32, RS_D2);
        fence_gpu();
        __syncwarp();
        if (el) { st32_rlx(&G->oset[16 * c + 8 * half], ep1); if (half) mbar_arrive(sb + B_AUXQ); }
        if (!half) {
          const uint4* src = reinterpret_cast<const uint4*>(&G->csq[128 * j]) + lane;
          uint4 v0, v1, v2, v3;
          do { v0 = ld128_rlx(src); v1 = ld128_rlx(src + DM / 4); v2 = ld128_rlx(src + DM / 2); v3 = ld128_rlx(src + 3 * DM / 4); }
          while ((tag_bad(v0, tg) || tag_bad(v1, tg) || tag_bad(v2, tg) || tag_bad(v3, tg)) && ++it < POLL_LIMIT);
          put_colsums(sb + OFF_BXQ, lane, (untag(v0.x) + untag(v1.x)) + (untag(v2.x) + untag(v3.x)), (untag(v0.y) + untag(v1.y)) + (untag(v2.y) + untag(v3.y)),
                      (untag(v0.z) + untag(v1.z)) + (untag(v2.z) + untag(v3.z)), (untag(v0.w) + untag(v1.w)) + (untag(v2.w) + untag(v3.w)));
          fence_async_smem();
          __syncwarp();
          if (el) mbar_arrive(sb + B_AUXQ);
        }
      }
      if (half == 0) {
        for (uint32_t it = 0; __any_sync(~0u, ld32_rlx(&G->oset[m128 * 128 + 8 * (lane & 15)]) != ep1) && it < POLL_LIMIT; it++) {}
        fence_acquire_gpu();
        if (el) mbar_arrive(sb + B_OS);
      }
      if (!half) {
        #pragma unroll 1
        for (int hh = 0; hh < 2; hh++) {
          const uint32_t src = sb + (1 + rank) * R5 + hh * 8192, fa = sb + B_FULLA + 16 + 16 * rank + 8 * hh;
          mbar_wait(fa, 0);
          mbar_wait(sb + B_UO + 8 * hh, 0);
          if (el) bulk_s2peer(mapa(src, rank ^ 1), src, 8192, mapa(fa, rank ^ 1));
        }
        fetch_o(1, 24, 1);
      }
      else if (f < NFFN_L) {
        mbar_wait2(sb + B_UO, 0, sb + B_UO + 8, 0);
        mbar_wait(sb + B_UO + 24, 0);
        uint32_t t0 = (uint32_t)clock();
        while ((uint32_t)clock() - t0 < (uint32_t)FF_T0) __nanosleep(32);
        t0 -= FF_DT;
        #pragma unroll 1
        for (int i = 0; i < 12; i++) {
          const int e = (FF_ORD >> (4 * i)) & 15;
          const uint32_t dst = sb + 16384 * ((FF_SLOT >> (4 * e)) & 15), fb = sb + B_F + 8 * e;
          if (i >= 2) mbar_wait(sb + B_WC + 8 * ((0x100066553244ull >> (4 * e)) & 15), 0);
          while ((uint32_t)clock() - t0 < (uint32_t)FF_DT) __nanosleep(32);
          t0 = (uint32_t)clock();
          if (i < 8) { TK(48 + i); }
          if (el) {
            mbar_expect_tx(fb, 16384);
            if (e >= 8) tma_3d_h(dst, &P.wd, 0, 32 * f, 4 * e - 32, fb, ef);
            else { tma_2d(dst, &P.wg, 32 * f, 128 * e, fb); tma_2d(dst + 8192, &P.wu, 32 * f, 128 * e, fb); }
          }
        }
      }
      __syncwarp();
    }
    {
      const int ch = lane & 15, rb = 32 * wp + (lane >> 4);
      const uint32_t src = sb + OFF_OUT + (ch >> 3) * 16384;
      bf16* dst = P.out_p + (size_t)(128 * m128) * DM + 128 * j + 8 * ch;
      __syncwarp();
      mbar_wait(sb + B_OUT + 8 * wp, 0);
      const float2 ex = lds64f(sb + OFF_EXC + 8 * wp);
      if (OUT_L) mbar_wait(sb + B_XS, 0);
      #pragma unroll 1
      for (int i = 0; i < 32; i += 2 * OUT_U) {
        uint4 v[OUT_U];
        #pragma unroll
        for (int e = 0; e < OUT_U; e++) { const int r = rb + i + 2 * e; v[e] = lds128(src + r * 128 + (((ch ^ r) & 7) << 4)); }
        #pragma unroll
        for (int e = 0; e < OUT_U; e++) { const int r = rb + i + 2 * e; if (r != __float_as_int(i < 16 ? ex.x : ex.y)) *reinterpret_cast<uint4*>(dst + r * DM) = v[e]; }
        if (OUT_NS) __nanosleep(OUT_NS);
      }
      if (wp == 0) { TK(63); }
      mbar_wait(sb + B_XS, 0);
      const int row = 2047 - (__float_as_uint(ldsf(sb + OFF_KEY)) & 2047) - 128 * m128, r = __float_as_int(lane < 16 ? ex.x : ex.y);
      if (r != row) *reinterpret_cast<uint4*>(dst + r * DM) = lds128(src + r * 128 + (((ch ^ r) & 7) << 4));
    }
    __syncwarp();
    cluster_arrive(); cluster_wait();
    return;
  }

  asm volatile("setmaxnreg.inc.sync.aligned.u32 160;");
  cluster_wait();
  const int t = tid & 127, g = lane >> 2;
  const uint32_t sa = (16 * wp + (lane & 15)) * 128 + (((lane >> 4) ^ (lane & 7)) << 4);

  if (wg == 2) {
    float s[2] = {0.f, 0.f}, s2[2] = {0.f, 0.f}, ck[8] = {0.f, 0.f, 0.f, 0.f, 0.f, 0.f, 0.f, 0.f}, cs[8] = {0.f, 0.f, 0.f, 0.f, 0.f, 0.f, 0.f, 0.f};
    const uint32_t ebr = mapa(sb + B_EMPTYKV, lane & 1), tg = (ld32_rlx(&G->epoch) + 1) & 3;
    auto addx = [&](const uint4 v) {
      const uint32_t w[4] = {v.x, v.y, v.z, v.w};
      #pragma unroll
      for (int e = 0; e < 4; e++) { const float a = bf_lo(w[e]), d = bf_hi(w[e]); s[0] += a; s[1] += d; s2[0] = fmaf(a, a, s2[0]); s2[1] = fmaf(d, d, s2[1]); }
    };
    auto addc = [&](const uint4 v, float (&o)[8]) {
      o[0] += bf_lo(v.x); o[1] += bf_hi(v.x); o[2] += bf_lo(v.y); o[3] += bf_hi(v.y); o[4] += bf_lo(v.z); o[5] += bf_hi(v.z); o[6] += bf_lo(v.w); o[7] += bf_hi(v.w);
    };
    {
      const uint32_t ra = (16 * nkv + (t >> 3)) * 128 + (t & 7) * 16;
      const uint32_t ca = 32768 + (m256 >> 2) * 8192 + (t >> 1) * 128 + (((2 * (m256 & 3) + (t & 1)) ^ ((t >> 1) & 7)) << 4);
      int rd = 0;
      mbar_wait(sb + B_S0, 0);
      #pragma unroll 1
      for (int kb = 0; kb < 10; kb++) {
        const uint32_t st = sb + (kb & 3) * KV_STAGE;
        mbar_wait(sb + B_FULLKV + 8 * (kb & 3), (kb >> 2) & 1);
        const uint4 x0 = lds128(st + ra), w0 = lds128(st + ca);
        addx(x0); addc(w0, ck);
        __syncwarp();
        if (lane < 2) mbar_arrive_remote(ebr + 8 * (kb & 3), 1);
        if ((SKM >> kb) & 1) {
          if (rd) {
            mbar_wait(sb + B_G, (rd - 1) & 1);
            const uint32_t a = sb + OFF_G + (t >> 3) * 256 + (t & 7) * 16;
            const uint4 x1 = lds128(a), x2 = lds128(a + 128), w1 = lds128(sb + OFF_G + 4096 + t * 16), w2 = lds128(sb + OFF_G + 6144 + t * 16);
            addx(x1); addx(x2); addc(w1, ck); addc(w2, ck);
            bar_sync(NB_WG2, 128);
          }
          if (wp == 0 && elect_one()) {
            mbar_expect_tx(sb + B_G, 8192);
            if (rd < 3) {
              tma_2d(sb + OFF_G, &P.xs, 640 + 128 * rd, 256 * m256 + 16 * nkv, sb + B_G);
              tma_2d(sb + OFF_G + 4096, &P.ws, (1 + (m256 >> 2)) * DM + 64 * nkv + 16 * (m256 & 3), 640 + 128 * rd, sb + B_G);
            } else tma_2d(sb + OFF_G, &P.qs, 32 * (c & 31), 256 * (c >> 5), sb + B_G);
          }
          rd++;
        }
      }
    }
    TK(82);
    const uint32_t scr = sb + OFF_SCR + 128;
    float sx = s[0] + s[1], sq = s2[0] + s2[1];
    #pragma unroll
    for (int o = 1; o < 8; o <<= 1) { sx += __shfl_xor_sync(~0u, sx, o); sq += __shfl_xor_sync(~0u, sq, o); }
    float v = reduce8(ck, lane);
    v += __shfl_xor_sync(~0u, v, 2);
    if (!(lane & 2)) stsf(scr + (wp * 16 + 8 * (lane & 1) + (lane >> 2)) * 4, v);

    bar_sync(NB_ZERO, 160);
    if ((lane & 7) == 0) {
      const float mean = sx * (1.f / DM);
      st64_rlx(&G->stats[256 * m256 + 16 * nkv + (t >> 3)], tagw(mean, tg), tagw(rsqrtf(fmaxf(sq * (1.f / DM) - mean * mean, 0.f) + 1e-5f), tg));
    }
    if (wp == 1 && lane < 16) {
      const uint32_t a = scr + lane * 4;
      st32_rlx(&G->cskv[128 * nkv + 16 * m256 + lane], tagw((ldsf(a) + ldsf(a + 64)) + (ldsf(a + 128) + ldsf(a + 192)), tg));
    }
    __syncwarp();
    bar_arrive(NB_PUB, 192);
    TSW(23);
    const uint4 wv = ld128_keep(P.wr + t * 8);
    #pragma unroll 1
    for (int i = 0; i < 2; i++) {
      mbar_wait(sb + B_G, i ^ 1);
      const uint32_t a = sb + OFF_G + t * 16;
      const uint4 u0 = lds128(a), u1 = lds128(a + 2048), u2 = lds128(a + 4096), u3 = lds128(a + 6144);
      addc(u0, cs); addc(u1, cs); addc(u2, cs); addc(u3, cs);
      bar_sync(NB_WG2, 128);
      if (i == 0 && wp == 0 && elect_one()) { mbar_expect_tx(sb + B_G, 8192); tma_2d(sb + OFF_G, &P.qs, 32 * (c & 31), 256 * (c >> 5) + 128, sb + B_G); }
    }
    if (t == 0) mbar_arrive(sb + B_W);
    float sw = (bf_lo(wv.x) + bf_hi(wv.x)) + (bf_lo(wv.y) + bf_hi(wv.y)) + (bf_lo(wv.z) + bf_hi(wv.z)) + (bf_lo(wv.w) + bf_hi(wv.w));
    #pragma unroll
    for (int o = 16; o; o >>= 1) sw += __shfl_xor_sync(~0u, sw, o);
    if (lane == 0) stsf(sb + OFF_SUMWR + wp * 4, sw);
    if ((t >> 4) == j) {
      const uint32_t a = sb + OFF_WR + (t & 15) * 32;
      sts128(a, wv.x << 16, wv.x & 0xffff0000u, wv.y << 16, wv.y & 0xffff0000u);
      sts128(a + 16, wv.z << 16, wv.z & 0xffff0000u, wv.w << 16, wv.w & 0xffff0000u);
    }
    v = reduce8(cs, lane);
    stsf(scr + (wp * 32 + 8 * (lane & 3) + (lane >> 2)) * 4, v);
    bar_sync(NB_WG2, 128);
    if (wp == 0) {
      const uint32_t a = scr + lane * 4;
      st32_rlx(&G->csq[(c >> 5) * DM + 32 * (c & 31) + lane], tagw((ldsf(a) + ldsf(a + 128)) + (ldsf(a + 256) + ldsf(a + 384)), tg));
    }
  }

  uint32_t xr[32];
  {
    const bool isq = wg == 2;
    float acc[2][64];
    {
      const uint32_t emptyb = mapa(sb + (isq ? B_EMPTY5 : B_EMPTYKV), t & 1);
      if (!isq) {
        mbar_wait(sb + B_S0, 0);
        if (wg) mbar_wait(sb + B_FULLKV, 0);
        if (wg == 0) { TSW(2); }
        #pragma unroll 1
        for (int kb = 0; kb < 16; kb++) {
          if (!KT && wg == 0) { TK(kb); }
          const uint32_t da = dlo(SB0, 16) + wg * 1024 + (kb & 3) * (KV_STAGE >> 4), db = dlo(SB0 + 32768, 8192) + (kb & 3) * (KV_STAGE >> 4);
          wg_fence();
          #pragma unroll
          for (int k = 0; k < 4; k++) {
            wgmma_ss_n128<0, 1, H128, H128>(acc[0], da + 2 * k, db + 128 * k, k > 0 || kb != 0);
            wgmma_ss_n128<0, 1, H128, H128>(acc[1], da + 512 + 2 * k, db + 128 * k, k > 0 || kb != 0);
          }
          wg_commit();
          wg_wait<1>();
          if (kb > 0 && t < 2) mbar_arrive_remote(emptyb + 8 * ((kb - 1) & 3), kb > 10 ? 3 : 1);
          if (kb < 15) mbar_wait(sb + B_FULLKV + 8 * ((kb + 1) & 3), ((kb + 1) >> 2) & 1);
          if (kb == 15 - LAG && wg == 1) bar_sync(NB_WG01, 256);
        }
        bar_arrive(wg ? NB_QGO : NB_WG01, 256);
      } else {
        uint32_t so = 0, po = 0, par = 0;
        mbar_wait(sb + B_FULL5, 0);
        bar_sync(NB_QGO, 256);
        TSW(11);
        #pragma unroll 1
        for (int kb = 0; kb < 16; kb++) {
          TK(16 + kb);
          const uint32_t da = dlo(SB0, 16) + so * 256, db = dlo(SB0 + 16384, 8192) + so * 256;
          #pragma unroll
          for (int k = 0; k < 4; k++) {
            wg_fence();
            wgmma_ss_n128<0, 1, H128, H128>(acc[0], da + 2 * k, db + 128 * k, k > 0 || kb != 0);
            wgmma_ss_n128<0, 1, H128, H128>(acc[1], da + 512 + 2 * k, db + 128 * k, k > 0 || kb != 0);
            wg_commit();
            if (k == 1 && kb > 0 && t < 2) mbar_arrive_remote(emptyb + po, 2);
            if (k == 3) {
              po = so; so += 8;
              if (so == 40) { so = 0; par ^= 1; }
              if (kb < 15) mbar_wait(sb + B_FULL5 + so, par);
            }
            if ((QW >> k) & 1) wg_wait<2>(); else wg_wait<1>();
          }
        }
        mbar_wait(sb + B_AUXQ, 0);
      }
      mbar_wait(sb + B_AUX, 0);
      const uint32_t xa = dlo(SB0, 0) + (isq ? OFF_AXQ >> 4 : (OFF_AXK >> 4) + wg * 128), xb = dlo(SB0, 0) + (isq ? OFF_BXQ >> 4 : OFF_BXK >> 4);
      wg_fence();
      wgmma_sa_n128<0, 1, H0, H0>(acc[0], xa, xb);
      wgmma_sa_n128<0, 1, H0, H0>(acc[1], xa + 64, xb);
      wg_commit();
      if (isq) mbar_wait(sb + B_RC, 0);
      wg_wait<0>();
      if (t < 2) mbar_arrive_remote(emptyb + (isq ? 0 : 24), isq ? 2 : 3);
      if (wg != 1) { TSW(wg ? 8 : 3); }
      fence_regs(acc[0]); fence_regs(acc[1]);
    }
    if (isq) {
      #pragma unroll
      for (int i = 0; i < 2; i++) {
        const uint32_t ta = sb + (1 + rank) * R5 + sa + i * 8192;
        if (i == 1) mbar_wait(sb + B_RC + 8, 0);
        #pragma unroll
        for (int k = 0; k < 4; k++) {
          const float* a = &acc[i][32 * (k >> 1) + 8 * (k & 1)];
          stsm4(ta ^ (k << 5), pack_bf16(a[0], a[1]), pack_bf16(a[2], a[3]), pack_bf16(a[4], a[5]), pack_bf16(a[6], a[7]));
        }
        fence_async_smem();
        bar_arrive(NB_Q0 + i, 256);
      }
      #pragma unroll
      for (int i = 0; i < 32; i++) { const float* a = &acc[(i >> 3) & 1][16 + 32 * (i >> 4) + 2 * (i & 7)]; xr[i] = pack_bf16(a[0], a[1]); }
      TSW(26);
    } else {
      const uint32_t stg = sb + OFF_X + (1 - wg) * 24576;
      const uint32_t va = stg + 16384 + (16 * wp + (lane & 15)) * 64 + (((lane >> 4) ^ ((lane >> 1) & 3)) << 4);
      const uint32_t ra = sb + OFF_RS256 + (128 * wg + 16 * wp + g) * 4;
      const float rs[4] = {ldsf(ra), ldsf(ra + 32), ldsf(ra + 256), ldsf(ra + 288)};
      float p[2][16];
      uint32_t vf[16], kf[2][16];
      auto project = [&](const uint32_t (&f)[16], uint32_t db) {
        wg_fence();
        #pragma unroll
        for (int i = 0; i < 2; i++) {
          wgmma_rs_n32<1, H64>(p[i], f[8*i], f[8*i+1], f[8*i+2], f[8*i+3], db, 0);
          wgmma_ra_n32<1, H64>(p[i], f[8*i+4], f[8*i+5], f[8*i+6], f[8*i+7], db + 64);
        }
        wg_commit();
      };
      auto fold = [&](uint32_t (&f)[16], int col, float sc) {
        #pragma unroll
        for (int i = 0; i < 16; i++) {
          const float r = rs[2 * (i >> 3) + (i & 1)] * sc;
          f[i] = pack_bf16(acc[i >> 3][col + 2 * (i & 7)] * r, acc[i >> 3][col + 2 * (i & 7) + 1] * r);
          asm volatile("" : "+r"(f[i]));
        }
      };
      auto put_v = [&](const uint32_t (&f)[16]) {
        #pragma unroll
        for (int k = 0; k < 4; k++) stsm4((va ^ ((k & 1) << 5)) + (k >> 1) * 4096, f[4*k], f[4*k+1], f[4*k+2], f[4*k+3]);
      };
      KK(0);
      fold(vf, 48, 1.f);
      mbar_wait(sb + B_W, 0);
      fold(kf[0], 0, LOG2E);
      #pragma unroll
      for (int i = 0; i < 32; i++) p[i >> 4][i & 15] = acc[i >> 4][i & 15];
      project(kf[0], dlo(SB0 + OFF_WPHIK, 16));
      mbar_wait(sb + B_W, 0);
      KK(1);
      {
        uint32_t v0[16];
        fold(kf[1], 16, LOG2E);
        fold(v0, 32, 1.f);
        if (wg == 1) bar_sync(NB_DN, 256);
        put_v(v0);
      }
      wg_wait<0>();
      fence_regs(p[0]); fence_regs(p[1]);
      if (wg == 1) bar_arrive(NB_WG01, 256);
      KK(2);
      #pragma unroll 1
      for (int h = 0; h < 2; h++) {
        uint32_t ph[4][8];
        float rsum[4][4];
        dual_exp2(p, ph);
        wg_fence();
        row_sums(rsum, ph, dlo(SB0 + OFF_ONES, 128));
        wg_commit();
        KK(3 + 6 * h);
        if (wg == 0 && h == 0) { bar_arrive(NB_DN, 256); bar_sync(NB_WG01, 256); }
        if (h == 1) {
          if (wg == 1) bar_sync(NB_DN, 256);
          put_v(vf);
        }
        wg_wait<0>();
        KK(4 + 6 * h);
        #pragma unroll
        for (int i = 0; i < 4; i++) fence_regs(rsum[i]);
        if (__builtin_expect(__any_sync(~0u, !((rsum[0][0] + rsum[0][2]) + (rsum[1][0] + rsum[1][2]) + (rsum[2][0] + rsum[2][2]) + (rsum[3][0] + rsum[3][2]) < EXP_LIM)), 0)) {
          dual_exp2_shifted(p, ph);
          #pragma unroll
          for (int i = 0; i < 8; i++) {
            const uint32_t* f = &ph[i >> 1][i & 1];
            float a = (bf_lo(f[0]) + bf_hi(f[0])) + (bf_lo(f[2]) + bf_hi(f[2])) + (bf_lo(f[4]) + bf_hi(f[4])) + (bf_lo(f[6]) + bf_hi(f[6]));
            a += __shfl_xor_sync(~0u, a, 1);
            rsum[i >> 1][2 * (i & 1)] = a + __shfl_xor_sync(~0u, a, 2);
          }
        }
        if (h == 0) project(kf[1], dlo(SB0 + OFF_WPHIK1, 16));
        normalize(ph, rsum);
        #pragma unroll
        for (int i = 0; i < 8; i++) {
          const uint32_t* f = &ph[i >> 1][4 * (i & 1)];
          stsm4(((stg + sa) ^ ((i & 3) << 5)) + (i >> 2) * 8192, f[0], f[1], f[2], f[3]);
        }
        KK(5 + 6 * h);
        fence_async_smem();
        KK(6 + 6 * h);
        if (wg != h) { KK(7 + 6 * h); }
        if (wg == h) {
          float kv[20];
          #pragma unroll
          for (int w = 0; w < 2; w++) {
            const uint32_t da = dlo(SB0 + OFF_X, 16) + (h ^ w ^ 1) * 1536, db = dlo(SB0 + OFF_X + 16384, OFF_ONES - OFF_X - 16384) - (h ^ w ^ 1) * (1536 * 65535);
            if (w) bar_sync(NB_ST, 256); else bar_sync(NB_L0 + h, 128);
            wg_fence();
            #pragma unroll
            for (int k = 0; k < 8; k++) {
              if (k == 0 && w == 0) wgmma_sz_n40<1, 1, H128, H64>(kv, da, db);
              else wgmma_sa_n40<1, 1, H128, H64>(kv, da + k * 128, db - k * (64 * 65535));
            }
            wg_commit();
          }
          float4* dst = &G->kvacc[(ha + 2 * h) * KVP + t];
          wg_wait<0>();
          fence_regs(kv);
          KK(7 + 6 * h);
          if (h == 0) bar_arrive(NB_DN, 256); else if (t < 2) { mbar_arrive_at(sb + B_EMPTY5 + 40, t, 2); if (t == 0) mbar_arrive(sb + B_KD); }
          kv[17] = kv[18];
          #pragma unroll
          for (int i = 0; i < 6; i++) red_add_f32x4(dst + 128 * i, kv[3*i], kv[3*i+1], kv[3*i+2], 1.f);
          TSW(29 + h);
        } else bar_arrive(NB_ST, 256);
        wg_wait<0>();
        KK(8 + 6 * h);
        fence_regs(p[0]); fence_regs(p[1]);
      }
      #pragma unroll
      for (int i = 0; i < 32; i++) asm volatile("mov.b32 %0, 0;" : "=r"(xr[i]));
    }
    float p[2][16];
    #pragma unroll
    for (int i = 0; i < 32; i++) asm volatile("mov.b32 %0, 0;" : "=f"(p[i >> 4][i & 15]));
    auto project_r = [&](int w) {
      wg_fence();
      #pragma unroll
      for (int h = 0; h < 2; h++) {
        wgmma_rs_n32<1, H64>(p[h], xr[8*h], xr[8*h+1], xr[8*h+2], xr[8*h+3], dlo(SB0 + OFF_WPHIQ, 16) + 128 * w, 0);
        wgmma_ra_n32<1, H64>(p[h], xr[8*h+4], xr[8*h+5], xr[8*h+6], xr[8*h+7], dlo(SB0 + OFF_WPHIQ, 16) + 128 * w + 64);
      }
      wg_commit();
    };
    {
      const uint4* src = reinterpret_cast<const uint4*>(&G->kvacc[(4 * j + wg) * KVP + t]);
      uint4 v[12];
      #pragma unroll
      for (int i = 0; i < 12; i++) v[i] = i < 6 || isq ? ld128_rlx(src + 128 * i) : make_uint4(0, 0, 0, 0x41000000u);
      if (isq) {
        project_r(2);
        wg_wait<0>();
        #pragma unroll
        for (int i = 0; i < 16; i++) xr[i] = xr[16 + i];
      } else {
        mbar_wait(sb + B_R, 0);
        #pragma unroll
        for (int k = 0; k < 8; k++) ldsm4(((sb + (1 + rank) * R5 + wg * 8192 + sa) ^ ((k & 3) << 5)) + (k >> 2) * 2 * R5, xr[4*k], xr[4*k+1], xr[4*k+2], xr[4*k+3]);
        const uint32_t one = (((xr[0] | xr[4] | xr[8]) | (xr[12] | xr[16] | xr[20]) | (xr[24] | xr[28])) & P.zero) + 1;
        if (lane == 0) { mbar_arrive_at(sb + B_RC + 8 * wg, rank, one); mbar_arrive_at(sb + B_RX, wg, one); }
      }
      #pragma unroll 1
      for (uint32_t it = 0; it < POLL_LIMIT; it++) {
        uint32_t bad = 0;
        #pragma unroll
        for (int i = 0; i < 12; i++) bad |= v[i].w ^ 0x41000000u;
        if (!__any_sync(~0u, bad != 0)) break;
        #pragma unroll
        for (int i = 0; i < 12; i++) if (i < 6 || isq) v[i] = ld128_rlx(src + 128 * i);
      }
      mbar_wait(sb + B_KD, 0);
      #pragma unroll
      for (int e = 0; e < 2; e++) {
        if (e == 0 || isq) {
          float f[18];
          #pragma unroll
          for (int i = 0; i < 6; i++) { f[3*i] = __uint_as_float(v[6*e+i].x); f[3*i+1] = __uint_as_float(v[6*e+i].y); f[3*i+2] = __uint_as_float(v[6*e+i].z); }
          const uint32_t ka = sb + OFF_KVZ + (wg + e) * 5120 + wp * 1280 + lane * 16;
          stsm4(ka, pack_bf16(f[0], f[1]), pack_bf16(f[2], f[3]), pack_bf16(f[4], f[5]), pack_bf16(f[6], f[7]));
          stsm4(ka + 512, pack_bf16(f[8], f[9]), pack_bf16(f[10], f[11]), pack_bf16(f[12], f[13]), pack_bf16(f[14], f[15]));
          stsm2(ka + 1024, pack_bf16(f[16], 1.f), pack_bf16(f[17], 1.f));
        }
      }
    }
    fence_async_smem();
    if (wg == 1) bar_arrive(NB_DN, 256);
    if (isq) mbar_wait(sb + B_OS, 0);
    TSW(wg == 0 ? 5 : wg == 1 ? 25 : 6);
    #pragma unroll 1
    for (int e = wg; e < wg + 1 + (wg >> 1); e++) {
      const int half = e >> 1, hh = e & 1, turn = e;
      const uint32_t ao = (1 + rank) * R5 + hh * 8192;
      const uint32_t ra = sb + OFF_RSQ + (16 * wp + g) * 4 + (e == 1 ? 256 : 0), rb = ra + 256 * half;
      const float cc[2][2] = {{ldsf(ra) * LOG2E, ldsf(ra + 32) * LOG2E}, {ldsf(rb) * LOG2E, ldsf(rb + 32) * LOG2E}};
      float m[2][4] = {{0.f, 0.f, 0.f, 0.f}, {0.f, 0.f, 0.f, 0.f}};
      uint32_t ph[2][8];
      auto exps = [&](int h) {
        #pragma unroll
        for (int k = 0; k < 8; k++) {
          const float c = cc[h][k & 1], mp = m[h][k & 1], mm = m[h][2 + (k & 1)];
          ph[0][k] = pack_bf16(ex2(fmaf(p[h][2*k], c, mp)), ex2(fmaf(p[h][2*k+1], c, mp)));
          ph[1][k] = pack_bf16(ex2(fmaf(p[h][2*k], -c, mm)), ex2(fmaf(p[h][2*k+1], -c, mm)));
        }
      };
      uint32_t shifted = 0;
      asm volatile("" : "+r"(shifted));
      #pragma unroll 1
      for (;;) {
        if (shifted) { row_extremes(p[0], cc[0], m[0]); row_extremes(p[1], cc[1], m[1]); }
        uint32_t first = (shifted ^ 1) & !isq;
        asm volatile("" : "+r"(first));
        if (first) {
          bar_sync(NB_Q0 + wg, 256);
          const uint32_t da = dlo(SB0, 16) + (ao >> 4), db = dlo(SB0 + OFF_WPHIQ, 16);
          wg_fence();
          #pragma unroll
          for (int h = 0; h < 2; h++) {
            wgmma_ss_n32<0, 1, H128, H64>(p[h], da + 4 * h, db + 128 * h, 0);
            wgmma_sa_n32<0, 1, H128, H64>(p[h], da + 4 * h + 2, db + 128 * h + 64);
          }
          wg_commit();
          wg_wait<0>();
        }
        if (!shifted && (e == 1 || e == 2)) bar_sync(NB_TOK + e - 1, 256);
        TK(64 + 4 * turn);
        fence_regs(p[0]); fence_regs(p[1]);
        exps(0);
        float s2[4] = {0.f, 0.f, 0.f, 0.f};
        #pragma unroll
        for (int i = 0; i < 32; i++) s2[((i >> 1) & 1) + 2 * (i >> 4)] = fmaf(p[i >> 4][i & 15], p[i >> 4][i & 15], s2[((i >> 1) & 1) + 2 * (i >> 4)]);
        if (!__any_sync(~0u, !shifted & !((s2[0] * cc[0][0] * cc[0][0] < ARG_LIM2) & (s2[1] * cc[0][1] * cc[0][1] < ARG_LIM2) &
                                          (s2[2] * cc[1][0] * cc[1][0] < ARG_LIM2) & (s2[3] * cc[1][1] * cc[1][1] < ARG_LIM2)))) break;
        shifted = 1;
      }
      float ac[4][20];
      auto numer = [&](int h, const uint32_t (&f)[2][8]) {
        const uint32_t db = dlo(SB0 + OFF_KVZ, 128) + (half ? e : h) * 320;
        wg_fence();
        #pragma unroll
        for (int i = 0; i < 2; i++) {
          wgmma_rz_n40<1, dhi(256, 0)>(ac[2*h+i], f[i][0], f[i][1], f[i][2], f[i][3], db + i * 160);
          wgmma_ra_n40<1, dhi(256, 0)>(ac[2*h+i], f[i][4], f[i][5], f[i][6], f[i][7], db + (i * 160 + 80));
        }
        wg_commit();
      };
      const uint32_t oa = (16 * wp + g) * 128 + (((lane & 3) ^ g) << 4);
      auto finish = [&](int h) {
        const float* ap = ac[2 * h]; const float* am = ac[2 * h + 1];
        const float ip0 = rcp(ap[17]), im0 = rcp(am[17]), ip1 = rcp(ap[19]), im1 = rcp(am[19]);
        const float d0 = rcp(fmaf(ap[16], ip0, fmaf(am[16], im0, 1e-6f))), d1 = rcp(fmaf(ap[18], ip1, fmaf(am[18], im1, 1e-6f)));
        const float a0 = ip0 * d0, b0 = im0 * d0, a1 = ip1 * d1, b1 = im1 * d1;
        #pragma unroll
        for (int r = 0; r < 2; r++) {
          const float a = r ? a1 : a0, b = r ? b1 : b0;
          uint32_t w[4];
          #pragma unroll
          for (int k = 0; k < 4; k++) w[k] = pack_bf16(fmaf(ap[4*k+2*r], a, am[4*k+2*r] * b), fmaf(ap[4*k+2*r+1], a, am[4*k+2*r+1] * b));
          const uint32_t off = (oa ^ ((half ? rank : h) << 6)) + r * 1024;
          st128_rlx(reinterpret_cast<uint8_t*>(G->o + (m128 * 16 + (half ? 2 * (j & 6) + 2 * hh + 1 : 2 * j)) * 8192 + (half ? h : hh) * 4096) + off, w[0], w[1], w[2], w[3]);
          if (!half) sts128(sb + ao + off, w[0], w[1], w[2], w[3]);
        }
      };
      numer(0, ph);
      exps(1);
      if (wg == 0) bar_sync(NB_DN, 256);
      numer(1, ph);
      if (turn < 2) bar_arrive(NB_TOK + turn, 256);
      wg_wait<1>();
      TK(65 + 4 * turn);
      fence_regs(ac[0]); fence_regs(ac[1]);
      finish(0);
      wg_wait<0>();
      fence_regs(ac[2]); fence_regs(ac[3]);
      #pragma unroll
      for (int i = 0; i < 32; i++) asm volatile("mov.b32 %0, 0;" : "=f"(p[i >> 4][i & 15]));
      if (e == 2) project_r(3);
      finish(1);
      TK(66 + 4 * turn);
      if (!half) fence_async_smem();
      __syncwarp();
      if (lane == 0) mbar_arrive(sb + B_UO + 8 * e);
      wg_wait<0>();
      TK(67 + 4 * turn);
    }
    if (isq) cluster_arrive();
  }

  {
  int lane;
  asm volatile("mov.u32 %0, %%laneid;" : "=r"(lane));
  const int g = lane >> 2, q = lane & 3;
  if (wg < 2) {
    float h[64];
    {
      if (wg == 0) { TK(83); }
      #pragma unroll
      for (int i = 0; i < 32; i++) { h[2*i] = bf_lo(xr[i]); h[2*i+1] = bf_hi(xr[i]); }
      fence_regs(h);
      TK(80 + wg);
      const uint32_t emptyb = mapa(sb + B_EMPTY5, t & 1);
      uint32_t s = 1 + rank, ps = 0;
      mbar_wait2(sb + B_FULL5 + 8 * s, 1, sb + B_UO + 8 * wg, 0);
      if (wg == 0) { TSW(14); }
      #pragma unroll
      for (int i = 0; i < 16; i++) {
        if (wg == 1 && (i & 12) == TKW) { TK(84 + (i & 3)); }
        if (!KT && wg == 0) { TK(32 + i); }
        const uint32_t da = dlo(SB0, 16) + s * 2048 + wg * 512, db = dlo(SB0 + 16384, 8192) + s * 2048;
        wg_fence();
        #pragma unroll
        for (int k = 0; k < 4; k++) wgmma_sa_n128<0, 1, H128, H128>(h, da + k * 2, db + k * 128);
        wg_commit();
        const uint32_t ns = i ? (i + 2) % 6 : 2 - rank;
        const uint32_t b0 = sb + B_FULL5 + 8 * ns, p0 = (1 + (i + 2) / 6) & 1, b1 = sb + B_FULLA + 16 * ns + 8 * wg, p1 = ((i + 1) / 6) & 1;
        const bool here = i == 15 || mbar_test2(b0, p0, b1, p1);
        wg_wait<1>();
        if (!(((2 * REL + 1) >> i) & 1) && i < 14 && t < 2) mbar_arrive_remote(emptyb + 8 * ps, 1);
        if ((REL >> i) & 1) { wg_wait<0>(); if (t < 2) mbar_arrive_remote(emptyb + 8 * s, 1); }
        if (!here) mbar_wait2(b0, p0, b1, p1);
        ps = s; s = ns;
      }
    }
    cluster_arrive();
    float2 wr[16];
    #pragma unroll
    for (int i = 0; i < 16; i++) wr[i] = lds64f(sb + OFF_WR + 32 * i + 8 * q);
    const int r0 = 64 * wg + 16 * wp + g;
    float sum0, sum1, dot0, dot1, sq0, sq1;
    uint32_t redo = 0;
    asm volatile("" : "+r"(redo));
    #pragma unroll 1
    for (;;) {
    if (redo) {
      wg_wait<0>();
      const int r = r0;
      #pragma unroll 1
      for (int n = 0; n < 16; n++) {
        const uint32_t* xp = reinterpret_cast<const uint32_t*>(P.x + (size_t)(128 * m128 + r) * DM + 128 * j + 8 * n) + q;
        const uint32_t x0 = xp[0], x1 = xp[4 * DM];
        float d0 = bf_lo(x0), d1 = bf_hi(x0), d2 = bf_lo(x1), d3 = bf_hi(x1);
        #pragma unroll 1
        for (int ks = 0; ks < 64; ks++) {
          const int kb = ks >> 2, kk = 16 * (ks & 3);
          const bf16* op = G->o + (m128 * 16 + kb) * 8192 + r * 64 + 2 * q;
          const int o0 = ((kk >> 3) ^ g) << 3;
          const uint16_t* w = reinterpret_cast<const uint16_t*>(P.wo_p) + (size_t)(((kb & 1) ? 256 * (kb >> 2) + 32 * (kb & 2) + 32 + 4 * (kk & 32) : 64 * kb + 2 * (kk & 32)) + ((kk & 16) >> 2) + 8 * q) * DM + 128 * j + 8 * n + g;
          const uint32_t b0 = w[0] | (w[DM] << 16), b1 = w[2 * DM] | (w[3 * DM] << 16);
          uint32_t a0, a1, a2, a3, it = 0;
          do { a0 = ld32_rlx(op + o0); a1 = ld32_rlx(op + 512 + o0); a2 = ld32_rlx(op + (o0 ^ 8)); a3 = ld32_rlx(op + 512 + (o0 ^ 8)); }
          while (max(max(a0, a1), max(a2, a3)) == ~0u && ++it < POLL_LIMIT);
          __syncwarp();
          mma16816(d0, d1, d2, d3, a0, a1, a2, a3, b0, b1);
        }
        #pragma unroll
        for (int i = 0; i < 60; i++) h[i] = h[i + 4];
        h[60] = d0; h[61] = d1; h[62] = d2; h[63] = d3;
      }
    }
    wg_wait<0>();
    fence_regs(h);
    if (wg == 0) { TSW(16); }
    sum0 = 0.f, sum1 = 0.f, dot0 = 0.f, dot1 = 0.f, sq0 = 0.f, sq1 = 0.f;
    #pragma unroll
    for (int i = 0; i < 16; i++) {
      sum0 += h[4*i] + h[4*i+1]; sum1 += h[4*i+2] + h[4*i+3];
      sq0 = fmaf(h[4*i], h[4*i], fmaf(h[4*i+1], h[4*i+1], sq0)); sq1 = fmaf(h[4*i+2], h[4*i+2], fmaf(h[4*i+3], h[4*i+3], sq1));
      dot0 = fmaf(h[4*i], wr[i].x, fmaf(h[4*i+1], wr[i].y, dot0)); dot1 = fmaf(h[4*i+2], wr[i].x, fmaf(h[4*i+3], wr[i].y, dot1));
    }
    if (!__any_sync(~0u, !redo & (h[0] != h[0] | h[2] != h[2]))) break;
    redo = 1;
    }
    float4* const rs = &G->rstat[128 * m128 + r0];
    {
      const bool up = q & 2;
      float a = up ? sum1 : sum0, b = up ? sq1 : sq0, d = up ? dot1 : dot0;
      a += __shfl_xor_sync(~0u, up ? sum0 : sum1, 2); b += __shfl_xor_sync(~0u, up ? sq0 : sq1, 2); d += __shfl_xor_sync(~0u, up ? dot0 : dot1, 2);
      a += __shfl_xor_sync(~0u, a, 1); b += __shfl_xor_sync(~0u, b, 1); d += __shfl_xor_sync(~0u, d, 1);
      if ((q & 1) == 0) red_add_f32x4(rs + 4 * q, a, b, d, 1.f);
    }
    bar_arrive(NB_G2E, 384);
    if (wg == 0) { TSW(24); }
    bar_sync(NB_WG01, 256);
    uint32_t wa[8][4][4];
    const uint32_t wb = sb + 16384 * (((uint32_t)FF_SLOT >> (4 * warp)) & 15) + ((lane & 7) + ((lane >> 4) << 3)) * 64 + ((((lane >> 3) & 1) ^ ((lane >> 1) & 3)) << 4);
    auto getw = [&](int ks) {
      #pragma unroll
      for (int m = 0; m < 4; m++) ldsm4t((wb ^ ((m & 1) << 5)) + (m >> 1) * 8192 + ks * 1024, wa[ks][m][0], wa[ks][m][1], wa[ks][m][2], wa[ks][m][3]);
    };
    if (GPRE && f < NFFN_L) mbar_wait(sb + B_F + 8 * warp, 0);
    if (warp == 7) { TK(60); }
    #pragma unroll
    for (int ks = 0; ks < GPRE; ks++) getw(ks);
    float rstd[2], bm[2];
    uint32_t best;
    {
      const float2 swa = lds64f(sb + OFF_SUMWR), swb = lds64f(sb + OFF_SUMWR + 8);
      const float sw = (swa.x + swa.y) + (swb.x + swb.y);
      uint4 a[2]; uint32_t it = 0, key[2];
      do { a[0] = ld128_rlx(rs); a[1] = ld128_rlx(rs + 8); } while (__any_sync(~0u, (a[0].w & a[1].w) != 0x41000000u) && ++it < POLL_LIMIT);
      #pragma unroll
      for (int i = 0; i < 2; i++) {
        const float mean = __uint_as_float(a[i].x) * (1.f / DM);
        rstd[i] = rsqrtf(fmaxf(__uint_as_float(a[i].y) * (1.f / DM) - mean * mean, 0.f) + 1e-5f);
        bm[i] = -mean * rstd[i];
        const uint32_t rr = __float_as_uint(fmaf(__uint_as_float(a[i].z), rstd[i], sw * bm[i]));
        key[i] = ((rr ^ ((uint32_t)((int32_t)rr >> 31) | 0x80000000u)) & ~2047u) | (2047 - 128 * m128 - r0 - 8 * i);
      }
      asm volatile("redux.sync.max.u32 %0, %1, 0xffffffff;" : "=r"(best) : "r"(max(key[0], key[1])));
    }
    if (wg == 0) { TSW(17); }
    const int slot = m128 * 8 + warp, win = ~best & 15;
    if (lane < 4) st32_rlx(&G->key[(4 * j + lane) * 128 + slot], best);
    if ((win & 7) == g) {
      const bool up = win & 8;
      const float ra = up ? rstd[1] : rstd[0], rb = up ? bm[1] : bm[0];
      uint32_t x[16];
      #pragma unroll
      for (int i = 0; i < 16; i++) x[i] = pack_bf16(fmaf(up ? h[4*i+2] : h[4*i], ra, rb), fmaf(up ? h[4*i+3] : h[4*i+1], ra, rb));
      #pragma unroll
      for (int i = 0; i < 4; i++) st128_rlx(&G->cand[slot * DM + 64 * j + 16 * i + 4 * q], x[4*i], x[4*i+1], x[4*i+2], x[4*i+3]);
    }
    __syncwarp();
    if (wg == 0) { TSW(27); }
    {
      const float a0 = 1.f + rstd[0], b0 = bm[0], a1 = 1.f + rstd[1], b1 = bm[1];
      #pragma unroll
      for (int k = 0; k < 8; k++)
        stsm4(((sb + OFF_OUT + wg * 8192 + sa) ^ ((k & 3) << 5)) + (k >> 2) * 16384,
              pack_bf16(fmaf(h[8*k], a0, b0), fmaf(h[8*k+1], a0, b0)),     pack_bf16(fmaf(h[8*k+2], a1, b1), fmaf(h[8*k+3], a1, b1)),
              pack_bf16(fmaf(h[8*k+4], a0, b0), fmaf(h[8*k+5], a0, b0)),   pack_bf16(fmaf(h[8*k+6], a1, b1), fmaf(h[8*k+7], a1, b1)));
      sts32(sb + OFF_EXC + 4 * warp, 16 * warp + win);
      __syncwarp();
      if (lane == 0) mbar_arrive(sb + B_OUT + 8 * (warp >> 1));
      if (lane < 16) {
        const uint4 v = lds128(sb + OFF_OUT + (lane >> 3) * 16384 + (16 * warp + win) * 128 + (((lane & 7) ^ (win & 7)) << 4));
        st128_rlx(&G->cand[slot * DM + 512 + 64 * j + 4 * lane], v.x, v.y, v.z, v.w);
      }
    }
    if (wg == 0) { TSW(28); }
    {
      if (!GPRE && f < NFFN_L) mbar_wait(sb + B_F + 8 * warp, 0);
      #pragma unroll
      for (int ks = GPRE; ks < GRES; ks++) getw(ks);
      if (wg == 0) { TSW(15); }
      bar_sync(NB_XS, 384);
      if (wg == 0) { TSW(19); }
      uint4 xs[4];
      #pragma unroll
      for (int i = 0; i < 4; i++) xs[i] = lds128(sb + OFF_XSEL + 256 * warp + 64 * i + 16 * q);
      float d[4][4];
      #pragma unroll
      for (int ks = 0; ks < 8; ks++) {
        if (ks >= 1 && GRES + ks - 1 < 8) getw(GRES + ks - 1);
        #pragma unroll
        for (int m = 0; m < 4; m++) {
          if (ks == 0) { d[m][0] = 0.f; d[m][1] = 0.f; d[m][2] = 0.f; d[m][3] = 0.f; }
          mma16816(d[m][0], d[m][1], d[m][2], d[m][3], wa[ks][m][0], wa[ks][m][1], wa[ks][m][2], wa[ks][m][3],
                   (ks & 1) ? xs[ks >> 1].z : xs[ks >> 1].x, (ks & 1) ? xs[ks >> 1].w : xs[ks >> 1].y);
        }
      }
      if (q == 0) {
        #pragma unroll
        for (int m = 0; m < 8; m++) stsf(sb + OFF_GU + (8 * m + g) * 48 + 4 * warp, d[m >> 1][2 * (m & 1)]);
      }
      bar_arrive(NB_ACT, 384);
    }
    {
      float y0 = 0.f, y1 = 0.f, y2 = 0.f, y3 = 0.f;
      const uint32_t ky = __float_as_uint(ldsf(sb + OFF_KEY));
      const int kidx = 2047 - (ky & 2047);
      const float kr = __uint_as_float((ky & ~2047u) ^ ((ky >> 31) ? 0x80000000u : 0xfffff800u));
      const int col = 128 * (c >> 4) + 64 * (c & 1) + 32 * ((tid >> 2) & 1) + 16 * (tid & 1) + 8 * ((tid >> 1) & 1) + ((c >> 1) & 7);
      uint32_t it = 0, base = 0;
      if (tid < 8) {
        do { base = ld32_rlx(&G->cand[(kidx >> 4) * DM + 512 + (col >> 1)]); } while (base == ~0u && ++it < POLL_LIMIT);
      }
      if (tid < 2 * NFFN) {
        uint4 v;
        do { v = ld128_rlx(&G->ypart[(tid >> 1) * DM + 8 * c + 4 * (tid & 1)]); } while (v.w == ~0u && ++it < POLL_LIMIT);
        y0 = __uint_as_float(v.x); y1 = __uint_as_float(v.y); y2 = __uint_as_float(v.z); y3 = __uint_as_float(v.w);
      }
      __syncwarp();
      const bool b4 = lane & 16, b3 = lane & 8;
      const float u0 = (b4 ? y1 : y0) + __shfl_xor_sync(~0u, b4 ? y0 : y1, 16), u1 = (b4 ? y3 : y2) + __shfl_xor_sync(~0u, b4 ? y2 : y3, 16);
      float ys = (b3 ? u1 : u0) + __shfl_xor_sync(~0u, b3 ? u0 : u1, 8);
      ys += __shfl_xor_sync(~0u, ys, 4); ys += __shfl_xor_sync(~0u, ys, 2);
      if (!(lane & 6)) stsf(sb + OFF_ACT + ((4 * (lane & 1) + ((lane >> 3) & 1) * 2 + (lane >> 4)) * 8 + warp) * 4, ys);
      const float sg = __fdividef(1.f, 1.f + __expf(-kr));
      bar_sync(NB_WG01, 256);
      if (tid < 8) {
        const uint4 v0 = lds128(sb + OFF_ACT + tid * 32), v1 = lds128(sb + OFF_ACT + tid * 32 + 16);
        const float t8 = ((__uint_as_float(v0.x) + __uint_as_float(v0.y)) + (__uint_as_float(v0.z) + __uint_as_float(v0.w))) +
                         ((__uint_as_float(v1.x) + __uint_as_float(v1.y)) + __uint_as_float(v1.z));
        P.out_p[(size_t)kidx * DM + col] = __float2bfloat16(fmaf(t8, sg, (col & 1) ? bf_hi(base) : bf_lo(base)));
      }
      if (c == 0 && tid == 0) st32_rlx(&G->epoch, __float_as_uint(ldsf(sb + OFF_EP)));
      if (wg == 0) { TSW(22); TDUMP(); }
    }
  }
  if (wg == 2) {
    uint32_t wf[16][2][4];
    {
      const uint32_t wb = sb + OFF_S + 16384 * (wp & 1) + ((lane & 7) + ((lane >> 4) << 3)) * 128 + ((((lane >> 3) & 1) ^ (lane & 7)) << 4);
      if (f < NFFN_L) mbar_wait(sb + B_WD + 8 * wp, 0);
      if (wp == 0) { TK(61); }
      #pragma unroll
      for (int i = 0; i < 32; i++) ldsm4t((wb ^ (((i >> 1) & 3) << 5)) + (i >> 3) * 4096 + (i & 1) * 2048, wf[i >> 1][i & 1][0], wf[i >> 1][i & 1][1], wf[i >> 1][i & 1][2], wf[i >> 1][i & 1][3]);
      fence_async_smem();
      __syncwarp();
      if (lane == 0) mbar_arrive(sb + B_WC + 8 * wp);
      if (wp == 0) { TK(62); }
    }
    bar_sync(NB_G2E, 384);
    {
      uint32_t cur = 0;
      uint4 v;
      #pragma unroll 1
      for (uint32_t it = 0; it < POLL_LIMIT; it++) {
        const uint4 kx = ld128_rlx(&G->key[(c & 31) * 128 + 4 * lane]);
        v = ld128_rlx(&G->cand[((~cur >> 4) & 127) * DM + 4 * t]);
        uint32_t best;
        asm volatile("redux.sync.max.u32 %0, %1, 0xffffffff;" : "=r"(best) : "r"(max(max(kx.x, kx.y), max(kx.z, kx.w))));
        if (!__any_sync(~0u, min(min(kx.x, kx.y), min(kx.z, kx.w)) == 0 || v.w == ~0u) && best == cur) break;
        cur = best;
      }
      sts128(sb + OFF_XSEL + 16 * t, v.x, v.y, v.z, v.w);
      sts32(sb + OFF_KEY, cur);
      bar_arrive(NB_XS, 384);
      if (t == 0) mbar_arrive(sb + B_XS);
      TSW(18);
      bar_sync(NB_ACT, 384);
    }
    float gu[2];
    #pragma unroll
    for (int i = 0; i < 2; i++) {
      const uint4 v0 = lds128(sb + OFF_GU + (32 * i + lane) * 48), v1 = lds128(sb + OFF_GU + (32 * i + lane) * 48 + 16);
      gu[i] = ((__uint_as_float(v0.x) + __uint_as_float(v0.y)) + (__uint_as_float(v0.z) + __uint_as_float(v0.w))) +
              ((__uint_as_float(v1.x) + __uint_as_float(v1.y)) + (__uint_as_float(v1.z) + __uint_as_float(v1.w)));
    }
    const float act = gu[0] * gu[1] * rcp(1.f + ex2(-LOG2E * gu[0]));
    const uint32_t ap = pack_bf16(act, __shfl_down_sync(~0u, act, 1));
    uint32_t bf[4];
    #pragma unroll
    for (int i = 0; i < 4; i++) bf[i] = __shfl_sync(~0u, ap, 2 * q + 8 * i);
    TSW(20);
    float d[16][4];
    #pragma unroll
    for (int k = 0; k < 2; k++)
      #pragma unroll
      for (int i = 0; i < 16; i++) {
        if (k == 0) { d[i][0] = 0.f; d[i][1] = 0.f; d[i][2] = 0.f; d[i][3] = 0.f; }
        mma16816(d[i][0], d[i][1], d[i][2], d[i][3], wf[i][k][0], wf[i][k][1], wf[i][k][2], wf[i][k][3], bf[2*k], bf[2*k+1]);
      }
    #pragma unroll
    for (int a = 0; a < 2; a++) {
      float y[4];
      #pragma unroll
      for (int e = 0; e < 4; e++) {
        const int n = 8 * a + (e & 1);
        const float lo = (q & 1) ? d[n + 2][e & 2] : d[n][e & 2], hi = (q & 1) ? d[n + 6][e & 2] : d[n + 4][e & 2];
        y[e] = (q & 2) ? hi : lo;
      }
      if (f < NFFN) st128_rlx(&G->ypart[f * DM + 256 * wp + 128 * a + 4 * lane], __float_as_uint(y[0]), __float_as_uint(y[1]), __float_as_uint(y[2]), min(__float_as_uint(y[3]), ~1u));
    }
    TSW(21);
  }
  }
  cluster_wait();
}

typedef CUresult (*EncodeFn)(CUtensorMap*, CUtensorMapDataType, cuuint32_t, void*, const cuuint64_t*, const cuuint64_t*,
                             const cuuint32_t*, const cuuint32_t*, CUtensorMapInterleave, CUtensorMapSwizzle,
                             CUtensorMapL2promotion, CUtensorMapFloatOOBfill);

void make_map(EncodeFn enc, CUtensorMap* m, const void* p, int n, const cuuint64_t* dims, const cuuint64_t* str, const cuuint32_t* box,
              CUtensorMapSwizzle sw, CUtensorMapL2promotion promo) {
  cuuint32_t es[5] = {1, 1, 1, 1, 1};
  enc(m, CU_TENSOR_MAP_DATA_TYPE_BFLOAT16, n, const_cast<void*>(p), dims, str, box, es, CU_TENSOR_MAP_INTERLEAVE_NONE, sw, promo,
      CU_TENSOR_MAP_FLOAT_OOB_FILL_NONE);
}
void map2(EncodeFn enc, CUtensorMap* m, const void* p, uint64_t cols, uint64_t rows, uint32_t bc, uint32_t br, CUtensorMapSwizzle sw,
          CUtensorMapL2promotion promo) {
  const cuuint64_t dims[2] = {cols, rows}, str[1] = {cols * 2};
  const cuuint32_t box[2] = {bc, br};
  make_map(enc, m, p, 2, dims, str, box, sw, promo);
}
void map3(EncodeFn enc, CUtensorMap* m, const void* p, uint64_t cols, uint64_t rows, uint32_t br, uint32_t nb) {
  const cuuint64_t dims[3] = {64, rows, cols / 64}, str[2] = {cols * 2, 128};
  const cuuint32_t box[3] = {64, br, nb};
  make_map(enc, m, p, 3, dims, str, box, CU_TENSOR_MAP_SWIZZLE_128B, CU_TENSOR_MAP_L2_PROMOTION_L2_128B);
}

}

extern "C" void kernel_launch(void* const* d_in, const int* in_sizes, int n_in, void* d_out, int out_size) {
  (void)in_sizes; (void)n_in; (void)out_size;
  static EncodeFn enc = nullptr;
  static void* o_ptr = nullptr;
  if (!enc) {
    void* f = nullptr; cudaDriverEntryPointQueryResult qr;
    cudaGetDriverEntryPoint("cuTensorMapEncodeTiled", &f, cudaEnableDefault, &qr);
    enc = (EncodeFn)f;
    cudaGetSymbolAddress(&o_ptr, g_scr);
    cudaFuncSetAttribute(fused_kernel, cudaFuncAttributeMaxDynamicSharedMemorySize, SMEM_BYTES);
  }
  const bf16* x = (const bf16*)d_in[0];
  const bf16* wqkv = (const bf16*)d_in[1];
  const bf16* wphi = (const bf16*)d_in[2];
  const bf16* wo = (const bf16*)d_in[3];
  const bf16* wr = (const bf16*)d_in[5];
  const bf16* wgate = (const bf16*)d_in[6];
  const bf16* wup = (const bf16*)d_in[7];
  const bf16* wdown = (const bf16*)d_in[8];
  Params P;
  const CUtensorMapSwizzle S128 = CU_TENSOR_MAP_SWIZZLE_128B, S64 = CU_TENSOR_MAP_SWIZZLE_64B;
  const CUtensorMapL2promotion L128 = CU_TENSOR_MAP_L2_PROMOTION_L2_128B, L256 = CU_TENSOR_MAP_L2_PROMOTION_L2_256B,
                               L64 = CU_TENSOR_MAP_L2_PROMOTION_L2_64B;
  map2(enc, &P.x128, x, DM, SEQ, 64, 128, S128, L256);
  map2(enc, &P.x64, x, DM, SEQ, 64, 64, S128, L128);
  {
    const cuuint64_t dims[4] = {64, DM, 16, 3}, str[3] = {6 * DM, 128, 2 * DM};
    const cuuint32_t box[4] = {64, 64, 1, 2};
    make_map(enc, &P.wkv, wqkv, 4, dims, str, box, S128, L128);
  }
  map3(enc, &P.wq, wqkv, 3 * DM, DM, 64, 2);
  for (int i = 0; i < 2; i++) {
    const cuuint64_t dims[5] = {DM, (cuuint64_t)(DM - 94 - 64 * i), 4, 4, 2}, str[4] = {2 * DM, 16 * DM, 4 * DM, (cuuint64_t)(128 * DM) << i};
    const cuuint32_t box[5] = {64, 2, 4, 4, 2};
    make_map(enc, &P.wo[i], wo, 5, dims, str, box, S128, L128);
  }
  map3(enc, &P.wd, wdown, DM, FF, 32, 4);
  map2(enc, &P.wg, wgate, FF, DM, 32, 128, S64, L64);
  map2(enc, &P.wu, wup, FF, DM, 32, 128, S64, L64);
  map2(enc, &P.tg, wgate, FF, DM, 8, 16, CU_TENSOR_MAP_SWIZZLE_NONE, L128);
  map2(enc, &P.tu, wup, FF, DM, 8, 16, CU_TENSOR_MAP_SWIZZLE_NONE, L128);
  map2(enc, &P.td, wdown, 128, FF * 8, 8, 16, CU_TENSOR_MAP_SWIZZLE_NONE, L256);
  map2(enc, &P.xs, x, DM, SEQ, 128, 16, CU_TENSOR_MAP_SWIZZLE_NONE, L256);
  map2(enc, &P.ws, wqkv, 3 * DM, DM, 16, 128, CU_TENSOR_MAP_SWIZZLE_NONE, L128);
  map2(enc, &P.qs, wqkv, 3 * DM, DM, 32, 128, CU_TENSOR_MAP_SWIZZLE_NONE, L64);
  map2(enc, &P.phi, wphi, 32, 1024, 32, 32, S64, L64);
  P.x = x; P.wqkv = wqkv; P.wo_p = wo; P.wd_p = wdown; P.wg_p = wgate; P.wu_p = wup; P.wr = wr; P.out_p = (bf16*)d_out; P.g = (Scratch*)o_ptr; P.zero = 0;

  cudaLaunchConfig_t cfg = {};
  cfg.gridDim = dim3(128); cfg.blockDim = dim3(512); cfg.dynamicSmemBytes = SMEM_BYTES; cfg.stream = cudaStreamPerThread;
  cudaLaunchAttribute at[1];
  at[0].id = cudaLaunchAttributeClusterDimension; at[0].val.clusterDim.x = 2; at[0].val.clusterDim.y = 1; at[0].val.clusterDim.z = 1;
  cfg.attrs = at; cfg.numAttrs = 1;
  cudaLaunchKernelEx(&cfg, fused_kernel, P);
}
```

```cpp
#include <cuda_runtime.h>
#include <cuda.h>
#include <cuda_bf16.h>
#include <stdint.h>

namespace {

typedef __nv_bfloat16 bf16;

__device__ __forceinline__ uint32_t smem_u32(const void* p){ return (uint32_t)__cvta_generic_to_shared(p); }
__device__ __forceinline__ void mbar_init(uint32_t bar, uint32_t cnt){ asm volatile("mbarrier.init.shared::cta.b64 [%0], %1;"::"r"(bar),"r"(cnt):"memory"); }
__device__ __forceinline__ void mbar_expect_tx(uint32_t bar, uint32_t bytes){ asm volatile("mbarrier.arrive.expect_tx.shared::cta.b64 _, [%0], %1;"::"r"(bar),"r"(bytes):"memory"); }
__device__ __forceinline__ void mbar_arrive(uint32_t bar){ asm volatile("mbarrier.arrive.shared::cta.b64 _, [%0];"::"r"(bar):"memory"); }
__device__ __forceinline__ uint32_t mapa(uint32_t addr, uint32_t cta){ uint32_t r; asm volatile("mapa.shared::cluster.u32 %0, %1, %2;":"=r"(r):"r"(addr),"r"(cta)); return r; }
__device__ __forceinline__ void mbar_arrive_at(uint32_t bar, uint32_t cta, uint32_t cnt){
  asm volatile("{\n.reg .b32 ra;\nmapa.shared::cluster.u32 ra, %0, %1;\nmbarrier.arrive.shared::cluster.b64 _, [ra], %2;\n}\n"::"r"(bar),"r"(cta),"r"(cnt):"memory"); }
__device__ __forceinline__ void mbar_arrive_remote(uint32_t cluster_addr, uint32_t cnt){
  asm volatile("mbarrier.arrive.shared::cluster.b64 _, [%0], %1;"::"r"(cluster_addr),"r"(cnt):"memory"); }
__device__ __forceinline__ void mbar_wait(uint32_t bar, uint32_t parity){
  asm volatile("{\n.reg .pred p;\n.reg .u32 c;\nmov.u32 c, 0;\nLW:\nmbarrier.try_wait.parity.shared::cta.b64 p, [%0], %1;\n@p bra LD;\nadd.u32 c, c, 1;\nsetp.lt.u32 p, c, 2000000;\n@p bra LW;\ntrap;\nLD:\n}\n"::"r"(bar),"r"(parity):"memory"); }
__device__ __forceinline__ void mbar_wait2(uint32_t bar0, uint32_t par0, uint32_t bar1, uint32_t par1){
  asm volatile("{\n.reg .pred p, q;\n.reg .u32 c;\nmov.u32 c, 0;\nLW:\nmbarrier.try_wait.parity.shared::cta.b64 p, [%0], %1;\nmbarrier.try_wait.parity.shared::cta.b64 q, [%2], %3;\nand.pred p, p, q;\n@p bra LD;\nadd.u32 c, c, 1;\nsetp.lt.u32 p, c, 2000000;\n@p bra LW;\ntrap;\nLD:\n}\n"::"r"(bar0),"r"(par0),"r"(bar1),"r"(par1):"memory"); }
__device__ __forceinline__ bool mbar_test2(uint32_t bar0, uint32_t par0, uint32_t bar1, uint32_t par1){
  uint32_t r;
  asm volatile("{\n.reg .pred p, q;\nmbarrier.test_wait.parity.shared::cta.b64 p, [%1], %2;\nmbarrier.test_wait.parity.shared::cta.b64 q, [%3], %4;\nand.pred p, p, q;\nselp.u32 %0, 1, 0, p;\n}\n":"=r"(r):"r"(bar0),"r"(par0),"r"(bar1),"r"(par1):"memory");
  return r; }
__device__ __forceinline__ void tma_2d(uint32_t dst, const CUtensorMap* m, int c0, int c1, uint32_t bar){
  asm volatile("cp.async.bulk.tensor.2d.shared::cluster.global.mbarrier::complete_tx::bytes [%0], [%1, {%3, %4}], [%2];"::"r"(dst),"l"(m),"r"(bar),"r"(c0),"r"(c1):"memory"); }
__device__ __forceinline__ void tma_2d_mc(uint32_t dst, const CUtensorMap* m, int c0, int c1, uint32_t bar){
  asm volatile("cp.async.bulk.tensor.2d.shared::cluster.global.mbarrier::complete_tx::bytes.multicast::cluster [%0], [%1, {%3, %4}], [%2], %5;"::"r"(dst),"l"(m),"r"(bar),"r"(c0),"r"(c1),"h"((uint16_t)3):"memory"); }
__device__ __forceinline__ void tma_2d_mc_h(uint32_t dst, const CUtensorMap* m, int c0, int c1, uint32_t bar, uint64_t pol){
  asm volatile("cp.async.bulk.tensor.2d.shared::cluster.global.mbarrier::complete_tx::bytes.multicast::cluster.L2::cache_hint [%0], [%1, {%3, %4}], [%2], %5, %6;"::"r"(dst),"l"(m),"r"(bar),"r"(c0),"r"(c1),"h"((uint16_t)3),"l"(pol):"memory"); }
__device__ __forceinline__ void tma_4d(uint32_t dst, const CUtensorMap* m, int c0, int c1, int c2, int c3, uint32_t bar){
  asm volatile("cp.async.bulk.tensor.4d.shared::cluster.global.mbarrier::complete_tx::bytes [%0], [%1, {%3, %4, %5, %6}], [%2];"::"r"(dst),"l"(m),"r"(bar),"r"(c0),"r"(c1),"r"(c2),"r"(c3):"memory"); }
__device__ __forceinline__ uint64_t policy_evict_first(){ uint64_t p; asm volatile("createpolicy.fractional.L2::evict_first.b64 %0, 1.0;":"=l"(p)); return p; }
__device__ __forceinline__ uint64_t policy_evict_normal(){ uint64_t p; asm("createpolicy.fractional.L2::evict_normal.b64 %0, 1.0;":"=l"(p)); return p; }
__device__ __forceinline__ void tma_3d_h(uint32_t dst, const CUtensorMap* m, int c0, int c1, int c2, uint32_t bar, uint64_t pol){
  asm volatile("cp.async.bulk.tensor.3d.shared::cluster.global.mbarrier::complete_tx::bytes.L2::cache_hint [%0], [%1, {%3, %4, %5}], [%2], %6;"::"r"(dst),"l"(m),"r"(bar),"r"(c0),"r"(c1),"r"(c2),"l"(pol):"memory"); }
__device__ __forceinline__ void tma_4d_h(uint32_t dst, const CUtensorMap* m, int c0, int c1, int c2, int c3, uint32_t bar, uint64_t pol){
  asm volatile("cp.async.bulk.tensor.4d.shared::cluster.global.mbarrier::complete_tx::bytes.L2::cache_hint [%0], [%1, {%3, %4, %5, %6}], [%2], %7;"::"r"(dst),"l"(m),"r"(bar),"r"(c0),"r"(c1),"r"(c2),"r"(c3),"l"(pol):"memory"); }
__device__ __forceinline__ void red_add_f32x4(float4* p, float x, float y, float z, float w){ asm volatile("red.relaxed.gpu.global.add.v4.f32 [%0], {%1,%2,%3,%4};"::"l"(p),"f"(x),"f"(y),"f"(z),"f"(w):"memory"); }
__device__ __forceinline__ void tma_5d_h(uint32_t dst, const CUtensorMap* m, int c0, int c1, uint32_t bar, uint64_t pol){
  asm volatile("cp.async.bulk.tensor.5d.shared::cluster.global.mbarrier::complete_tx::bytes.L2::cache_hint [%0], [%1, {%3, %4, 0, 0, 0}], [%2], %5;"::"r"(dst),"l"(m),"r"(bar),"r"(c0),"r"(c1),"l"(pol):"memory"); }
__device__ __forceinline__ bool elect_one(){ uint32_t p; asm volatile("{\n.reg .pred P;\nelect.sync _|P, 0xffffffff;\nselp.b32 %0, 1, 0, P;\n}\n":"=r"(p)); return p; }
__device__ __forceinline__ void bulk_prefetch(const void* p, uint32_t bytes){
  asm volatile("cp.async.bulk.prefetch.L2.global [%0], %1;"::"l"(p),"r"(bytes):"memory"); }
__device__ __forceinline__ void bulk_s2peer(uint32_t dst_cluster, uint32_t src, uint32_t bytes, uint32_t bar_cluster){
  asm volatile("cp.async.bulk.shared::cluster.shared::cta.mbarrier::complete_tx::bytes [%0], [%1], %2, [%3];"::"r"(dst_cluster),"r"(src),"r"(bytes),"r"(bar_cluster):"memory"); }
__device__ __forceinline__ void bulk_g2s_mc(uint32_t dst, const void* src, uint32_t bytes, uint32_t bar, uint64_t pol){
  asm volatile("cp.async.bulk.shared::cluster.global.mbarrier::complete_tx::bytes.multicast::cluster.L2::cache_hint [%0], [%1], %2, [%3], %4, %5;"::"r"(dst),"l"(src),"r"(bytes),"r"(bar),"h"((uint16_t)3),"l"(pol):"memory"); }
__device__ __forceinline__ void prefetch_map(const CUtensorMap* m){ asm volatile("prefetch.tensormap [%0];"::"l"(m):"memory"); }
__device__ __forceinline__ void fence_async_smem(){ asm volatile("fence.proxy.async.shared::cta;":::"memory"); }
__device__ __forceinline__ void fence_acquire_gpu(){ asm volatile("fence.acquire.gpu;":::"memory"); }
__device__ __forceinline__ void fence_gpu(){ asm volatile("fence.acq_rel.gpu;":::"memory"); }
__device__ __forceinline__ void wg_fence(){ asm volatile("wgmma.fence.sync.aligned;":::"memory"); }
__device__ __forceinline__ void wg_commit(){ asm volatile("wgmma.commit_group.sync.aligned;":::"memory"); }
template<int N> __device__ __forceinline__ void wg_wait(){ asm volatile("wgmma.wait_group.sync.aligned %0;"::"n"(N):"memory"); }
template<int N> __device__ __forceinline__ void fence_regs(float (&d)[N]){
  #pragma unroll
  for(int i=0;i<N;i++) asm volatile("":"+f"(d[i])::"memory"); }
__device__ __forceinline__ void bar_sync(int id, int n){ asm volatile("bar.sync %0, %1;"::"r"(id),"r"(n):"memory"); }
__device__ __forceinline__ void bar_arrive(int id, int n){ asm volatile("bar.arrive %0, %1;"::"r"(id),"r"(n):"memory"); }
__device__ __forceinline__ void cluster_arrive(){ asm volatile("barrier.cluster.arrive.relaxed.aligned;":::"memory"); }
__device__ __forceinline__ void cluster_wait(){ asm volatile("barrier.cluster.wait.aligned;":::"memory"); }
__host__ __device__ constexpr uint32_t dlo(uint32_t addr, uint32_t lbo){ return (addr >> 4) | ((lbo >> 4) << 16); }
__host__ __device__ constexpr uint32_t dhi(uint32_t sbo, uint32_t sw){ return (sbo >> 4) | (sw << 30); }
constexpr uint32_t H128 = dhi(1024, 1), H64 = dhi(512, 2), H0 = dhi(128, 0);
__device__ __forceinline__ uint32_t pack_bf16(float lo, float hi){ uint32_t r; asm("cvt.rn.bf16x2.f32 %0, %1, %2;":"=r"(r):"f"(hi),"f"(lo)); return r; }
__device__ __forceinline__ float bf_lo(uint32_t v){ return __uint_as_float(v<<16); }
__device__ __forceinline__ float bf_hi(uint32_t v){ return __uint_as_float(v&0xffff0000u); }
__device__ __forceinline__ float ex2(float x){ float r; asm("ex2.approx.ftz.f32 %0, %1;":"=f"(r):"f"(x)); return r; }
__device__ __forceinline__ float rcp(float x){ float r; asm("rcp.approx.ftz.f32 %0, %1;":"=f"(r):"f"(x)); return r; }
__device__ __forceinline__ void stsm4(uint32_t addr, uint32_t a, uint32_t b, uint32_t c, uint32_t d){
  asm volatile("stmatrix.sync.aligned.m8n8.x4.shared.b16 [%0], {%1,%2,%3,%4};"::"r"(addr),"r"(a),"r"(b),"r"(c),"r"(d)); }
__device__ __forceinline__ void stsm2(uint32_t addr, uint32_t a, uint32_t b){
  asm volatile("stmatrix.sync.aligned.m8n8.x2.shared.b16 [%0], {%1,%2};"::"r"(addr),"r"(a),"r"(b)); }
__device__ __forceinline__ void mma16816(float& d0, float& d1, float& d2, float& d3, uint32_t a0, uint32_t a1, uint32_t a2, uint32_t a3, uint32_t b0, uint32_t b1){
  asm volatile("mma.sync.aligned.m16n8k16.row.col.f32.bf16.bf16.f32 {%0,%1,%2,%3}, {%4,%5,%6,%7}, {%8,%9}, {%0,%1,%2,%3};"
               : "+f"(d0), "+f"(d1), "+f"(d2), "+f"(d3) : "r"(a0), "r"(a1), "r"(a2), "r"(a3), "r"(b0), "r"(b1)); }
__device__ __forceinline__ void ldsm4(uint32_t addr, uint32_t& a, uint32_t& b, uint32_t& c, uint32_t& d){
  asm volatile("ldmatrix.sync.aligned.m8n8.x4.shared.b16 {%0,%1,%2,%3}, [%4];":"=r"(a),"=r"(b),"=r"(c),"=r"(d):"r"(addr):"memory"); }
__device__ __forceinline__ void ldsm4t(uint32_t addr, uint32_t& a, uint32_t& b, uint32_t& c, uint32_t& d){
  asm volatile("ldmatrix.sync.aligned.m8n8.x4.trans.shared.b16 {%0,%1,%2,%3}, [%4];":"=r"(a),"=r"(b),"=r"(c),"=r"(d):"r"(addr):"memory"); }
__device__ __forceinline__ void sts32(uint32_t a, uint32_t v){ asm volatile("st.shared.b32 [%0], %1;"::"r"(a),"r"(v):"memory"); }
__device__ __forceinline__ void stsf(uint32_t a, float v){ asm volatile("st.shared.f32 [%0], %1;"::"r"(a),"f"(v):"memory"); }
__device__ __forceinline__ void sts64(uint32_t a, uint32_t x, uint32_t y){ asm volatile("st.shared.v2.b32 [%0], {%1,%2};"::"r"(a),"r"(x),"r"(y):"memory"); }
__device__ __forceinline__ void sts128(uint32_t a, uint32_t x, uint32_t y, uint32_t z, uint32_t w){ asm volatile("st.shared.v4.b32 [%0], {%1,%2,%3,%4};"::"r"(a),"r"(x),"r"(y),"r"(z),"r"(w):"memory"); }
__device__ __forceinline__ float ldsf(uint32_t a){ float v; asm volatile("ld.shared.f32 %0, [%1];":"=f"(v):"r"(a):"memory"); return v; }
__device__ __forceinline__ float2 lds64f(uint32_t a){ float2 v; asm volatile("ld.shared.v2.f32 {%0,%1}, [%2];":"=f"(v.x),"=f"(v.y):"r"(a):"memory"); return v; }
__device__ __forceinline__ uint4 lds128(uint32_t a){ uint4 v; asm volatile("ld.shared.v4.u32 {%0,%1,%2,%3}, [%4];":"=r"(v.x),"=r"(v.y),"=r"(v.z),"=r"(v.w):"r"(a):"memory"); return v; }
__device__ __forceinline__ uint4 ld128_keep(const void* p){ uint4 v; asm volatile("ld.global.v4.u32 {%0,%1,%2,%3}, [%4];":"=r"(v.x),"=r"(v.y),"=r"(v.z),"=r"(v.w):"l"(p):"memory"); return v; }
__device__ __forceinline__ uint4 ld128_rlx(const void* p){ uint4 v; asm volatile("ld.relaxed.gpu.global.v4.u32 {%0,%1,%2,%3}, [%4];":"=r"(v.x),"=r"(v.y),"=r"(v.z),"=r"(v.w):"l"(p):"memory"); return v; }
__device__ __forceinline__ uint32_t ld32_rlx(const void* p){ uint32_t v; asm volatile("ld.relaxed.gpu.global.u32 %0, [%1];":"=r"(v):"l"(p):"memory"); return v; }
__device__ __forceinline__ void st128_rlx(void* p, uint32_t x, uint32_t y, uint32_t z, uint32_t w){ asm volatile("st.relaxed.gpu.global.v4.u32 [%0], {%1,%2,%3,%4};"::"l"(p),"r"(x),"r"(y),"r"(z),"r"(w):"memory"); }
__device__ __forceinline__ void st64_rlx(void* p, uint32_t x, uint32_t y){ asm volatile("st.relaxed.gpu.global.v2.u32 [%0], {%1,%2};"::"l"(p),"r"(x),"r"(y):"memory"); }
__device__ __forceinline__ void st32_rlx(void* p, uint32_t x){ asm volatile("st.relaxed.gpu.global.u32 [%0], %1;"::"l"(p),"r"(x):"memory"); }
__device__ __forceinline__ uint32_t tagw(float x, uint32_t t){ return (__float_as_uint(x) & ~3u) | t; }
__device__ __forceinline__ float untag(uint32_t w){ return __uint_as_float(w & ~3u); }

template<int TA, int TB, uint32_t HA, uint32_t HB> __device__ __forceinline__ void wgmma_ss_n128(float (&d)[64], uint32_t da, uint32_t db, int scale_d){
  asm volatile("{\n.reg .pred p;\n.reg .b64 a, b;\nsetp.ne.b32 p, %70, 0;\nmov.b64 a, {%64, %68};\nmov.b64 b, {%65, %69};\n"
  "wgmma.mma_async.sync.aligned.m64n128k16.f32.bf16.bf16 {%0, %1, %2, %3, %4, %5, %6, %7, %8, %9, %10, %11, %12, %13, %14, %15, %16, %17, %18, %19, %20, %21, %22, %23, %24, %25, %26, %27, %28, %29, %30, %31, %32, %33, %34, %35, %36, %37, %38, %39, %40, %41, %42, %43, %44, %45, %46, %47, %48, %49, %50, %51, %52, %53, %54, %55, %56, %57, %58, %59, %60, %61, %62, %63}, a, b, p, 1, 1, %66, %67;\n}\n"
  : "+f"(d[0]), "+f"(d[1]), "+f"(d[2]), "+f"(d[3]), "+f"(d[4]), "+f"(d[5]), "+f"(d[6]), "+f"(d[7]), "+f"(d[8]), "+f"(d[9]), "+f"(d[10]), "+f"(d[11]), "+f"(d[12]), "+f"(d[13]), "+f"(d[14]), "+f"(d[15]), "+f"(d[16]), "+f"(d[17]), "+f"(d[18]), "+f"(d[19]), "+f"(d[20]), "+f"(d[21]), "+f"(d[22]), "+f"(d[23]), "+f"(d[24]), "+f"(d[25]), "+f"(d[26]), "+f"(d[27]), "+f"(d[28]), "+f"(d[29]), "+f"(d[30]), "+f"(d[31]), "+f"(d[32]), "+f"(d[33]), "+f"(d[34]), "+f"(d[35]), "+f"(d[36]), "+f"(d[37]), "+f"(d[38]), "+f"(d[39]), "+f"(d[40]), "+f"(d[41]), "+f"(d[42]), "+f"(d[43]), "+f"(d[44]), "+f"(d[45]), "+f"(d[46]), "+f"(d[47]), "+f"(d[48]), "+f"(d[49]), "+f"(d[50]), "+f"(d[51]), "+f"(d[52]), "+f"(d[53]), "+f"(d[54]), "+f"(d[55]), "+f"(d[56]), "+f"(d[57]), "+f"(d[58]), "+f"(d[59]), "+f"(d[60]), "+f"(d[61]), "+f"(d[62]), "+f"(d[63])
  : "r"(da), "r"(db), "n"(TA), "n"(TB), "n"(HA), "n"(HB), "r"(scale_d));
}
template<int TA, int TB, uint32_t HA, uint32_t HB> __device__ __forceinline__ void wgmma_sa_n128(float (&d)[64], uint32_t da, uint32_t db){
  asm volatile("{\n.reg .pred p;\n.reg .b64 a, b;\nsetp.ne.b32 p, 1, 0;\nmov.b64 a, {%64, %68};\nmov.b64 b, {%65, %69};\n"
  "wgmma.mma_async.sync.aligned.m64n128k16.f32.bf16.bf16 {%0, %1, %2, %3, %4, %5, %6, %7, %8, %9, %10, %11, %12, %13, %14, %15, %16, %17, %18, %19, %20, %21, %22, %23, %24, %25, %26, %27, %28, %29, %30, %31, %32, %33, %34, %35, %36, %37, %38, %39, %40, %41, %42, %43, %44, %45, %46, %47, %48, %49, %50, %51, %52, %53, %54, %55, %56, %57, %58, %59, %60, %61, %62, %63}, a, b, p, 1, 1, %66, %67;\n}\n"
  : "+f"(d[0]), "+f"(d[1]), "+f"(d[2]), "+f"(d[3]), "+f"(d[4]), "+f"(d[5]), "+f"(d[6]), "+f"(d[7]), "+f"(d[8]), "+f"(d[9]), "+f"(d[10]), "+f"(d[11]), "+f"(d[12]), "+f"(d[13]), "+f"(d[14]), "+f"(d[15]), "+f"(d[16]), "+f"(d[17]), "+f"(d[18]), "+f"(d[19]), "+f"(d[20]), "+f"(d[21]), "+f"(d[22]), "+f"(d[23]), "+f"(d[24]), "+f"(d[25]), "+f"(d[26]), "+f"(d[27]), "+f"(d[28]), "+f"(d[29]), "+f"(d[30]), "+f"(d[31]), "+f"(d[32]), "+f"(d[33]), "+f"(d[34]), "+f"(d[35]), "+f"(d[36]), "+f"(d[37]), "+f"(d[38]), "+f"(d[39]), "+f"(d[40]), "+f"(d[41]), "+f"(d[42]), "+f"(d[43]), "+f"(d[44]), "+f"(d[45]), "+f"(d[46]), "+f"(d[47]), "+f"(d[48]), "+f"(d[49]), "+f"(d[50]), "+f"(d[51]), "+f"(d[52]), "+f"(d[53]), "+f"(d[54]), "+f"(d[55]), "+f"(d[56]), "+f"(d[57]), "+f"(d[58]), "+f"(d[59]), "+f"(d[60]), "+f"(d[61]), "+f"(d[62]), "+f"(d[63])
  : "r"(da), "r"(db), "n"(TA), "n"(TB), "n"(HA), "n"(HB));
}
template<int TA, int TB, uint32_t HA, uint32_t HB> __device__ __forceinline__ void wgmma_sa_n40(float (&d)[20], uint32_t da, uint32_t db){
  asm volatile("{\n.reg .pred p;\n.reg .b64 a, b;\nsetp.ne.b32 p, 1, 0;\nmov.b64 a, {%20, %24};\nmov.b64 b, {%21, %25};\n"
  "wgmma.mma_async.sync.aligned.m64n40k16.f32.bf16.bf16 {%0, %1, %2, %3, %4, %5, %6, %7, %8, %9, %10, %11, %12, %13, %14, %15, %16, %17, %18, %19}, a, b, p, 1, 1, %22, %23;\n}\n"
  : "+f"(d[0]), "+f"(d[1]), "+f"(d[2]), "+f"(d[3]), "+f"(d[4]), "+f"(d[5]), "+f"(d[6]), "+f"(d[7]), "+f"(d[8]), "+f"(d[9]), "+f"(d[10]), "+f"(d[11]), "+f"(d[12]), "+f"(d[13]), "+f"(d[14]), "+f"(d[15]), "+f"(d[16]), "+f"(d[17]), "+f"(d[18]), "+f"(d[19])
  : "r"(da), "r"(db), "n"(TA), "n"(TB), "n"(HA), "n"(HB));
}
template<int TA, int TB, uint32_t HA, uint32_t HB> __device__ __forceinline__ void wgmma_sz_n40(float (&d)[20], uint32_t da, uint32_t db){
  asm volatile("{\n.reg .pred p;\n.reg .b64 a, b;\nsetp.ne.b32 p, 0, 0;\nmov.b64 a, {%20, %24};\nmov.b64 b, {%21, %25};\n"
  "wgmma.mma_async.sync.aligned.m64n40k16.f32.bf16.bf16 {%0, %1, %2, %3, %4, %5, %6, %7, %8, %9, %10, %11, %12, %13, %14, %15, %16, %17, %18, %19}, a, b, p, 1, 1, %22, %23;\n}\n"
  : "=f"(d[0]), "=f"(d[1]), "=f"(d[2]), "=f"(d[3]), "=f"(d[4]), "=f"(d[5]), "=f"(d[6]), "=f"(d[7]), "=f"(d[8]), "=f"(d[9]), "=f"(d[10]), "=f"(d[11]), "=f"(d[12]), "=f"(d[13]), "=f"(d[14]), "=f"(d[15]), "=f"(d[16]), "=f"(d[17]), "=f"(d[18]), "=f"(d[19])
  : "r"(da), "r"(db), "n"(TA), "n"(TB), "n"(HA), "n"(HB));
}
template<int TA, int TB, uint32_t HA, uint32_t HB> __device__ __forceinline__ void wgmma_sa_n32(float (&d)[16], uint32_t da, uint32_t db){
  asm volatile("{\n.reg .pred p;\n.reg .b64 a, b;\nsetp.ne.b32 p, 1, 0;\nmov.b64 a, {%16, %20};\nmov.b64 b, {%17, %21};\n"
  "wgmma.mma_async.sync.aligned.m64n32k16.f32.bf16.bf16 {%0, %1, %2, %3, %4, %5, %6, %7, %8, %9, %10, %11, %12, %13, %14, %15}, a, b, p, 1, 1, %18, %19;\n}\n"
  : "+f"(d[0]), "+f"(d[1]), "+f"(d[2]), "+f"(d[3]), "+f"(d[4]), "+f"(d[5]), "+f"(d[6]), "+f"(d[7]), "+f"(d[8]), "+f"(d[9]), "+f"(d[10]), "+f"(d[11]), "+f"(d[12]), "+f"(d[13]), "+f"(d[14]), "+f"(d[15])
  : "r"(da), "r"(db), "n"(TA), "n"(TB), "n"(HA), "n"(HB));
}
template<int TA, int TB, uint32_t HA, uint32_t HB> __device__ __forceinline__ void wgmma_ss_n32(float (&d)[16], uint32_t da, uint32_t db, int scale_d){
  asm volatile("{\n.reg .pred p;\n.reg .b64 a, b;\nsetp.ne.b32 p, %22, 0;\nmov.b64 a, {%16, %20};\nmov.b64 b, {%17, %21};\n"
  "wgmma.mma_async.sync.aligned.m64n32k16.f32.bf16.bf16 {%0, %1, %2, %3, %4, %5, %6, %7, %8, %9, %10, %11, %12, %13, %14, %15}, a, b, p, 1, 1, %18, %19;\n}\n"
  : "+f"(d[0]), "+f"(d[1]), "+f"(d[2]), "+f"(d[3]), "+f"(d[4]), "+f"(d[5]), "+f"(d[6]), "+f"(d[7]), "+f"(d[8]), "+f"(d[9]), "+f"(d[10]), "+f"(d[11]), "+f"(d[12]), "+f"(d[13]), "+f"(d[14]), "+f"(d[15])
  : "r"(da), "r"(db), "n"(TA), "n"(TB), "n"(HA), "n"(HB), "r"(scale_d));
}
template<int TB, uint32_t HB> __device__ __forceinline__ void wgmma_ra_n32(float (&d)[16], uint32_t a0, uint32_t a1, uint32_t a2, uint32_t a3, uint32_t db){
  asm volatile("{\n.reg .pred p;\n.reg .b64 a, b;\nsetp.ne.b32 p, 1, 0;\nmov.b64 b, {%20, %22};\n"
  "wgmma.mma_async.sync.aligned.m64n32k16.f32.bf16.bf16 {%0, %1, %2, %3, %4, %5, %6, %7, %8, %9, %10, %11, %12, %13, %14, %15}, {%16,%17,%18,%19}, b, p, 1, 1, %21;\n}\n"
  : "+f"(d[0]), "+f"(d[1]), "+f"(d[2]), "+f"(d[3]), "+f"(d[4]), "+f"(d[5]), "+f"(d[6]), "+f"(d[7]), "+f"(d[8]), "+f"(d[9]), "+f"(d[10]), "+f"(d[11]), "+f"(d[12]), "+f"(d[13]), "+f"(d[14]), "+f"(d[15])
  : "r"(a0), "r"(a1), "r"(a2), "r"(a3), "r"(db), "n"(TB), "n"(HB));
}
template<int TB, uint32_t HB> __device__ __forceinline__ void wgmma_rs_n32(float (&d)[16], uint32_t a0, uint32_t a1, uint32_t a2, uint32_t a3, uint32_t db, int scale_d){
  asm volatile("{\n.reg .pred p;\n.reg .b64 a, b;\nsetp.ne.b32 p, %23, 0;\nmov.b64 b, {%20, %22};\n"
  "wgmma.mma_async.sync.aligned.m64n32k16.f32.bf16.bf16 {%0, %1, %2, %3, %4, %5, %6, %7, %8, %9, %10, %11, %12, %13, %14, %15}, {%16,%17,%18,%19}, b, p, 1, 1, %21;\n}\n"
  : "+f"(d[0]), "+f"(d[1]), "+f"(d[2]), "+f"(d[3]), "+f"(d[4]), "+f"(d[5]), "+f"(d[6]), "+f"(d[7]), "+f"(d[8]), "+f"(d[9]), "+f"(d[10]), "+f"(d[11]), "+f"(d[12]), "+f"(d[13]), "+f"(d[14]), "+f"(d[15])
  : "r"(a0), "r"(a1), "r"(a2), "r"(a3), "r"(db), "n"(TB), "n"(HB), "r"(scale_d));
}
template<int TB, uint32_t HB> __device__ __forceinline__ void wgmma_ra_n40(float (&d)[20], uint32_t a0, uint32_t a1, uint32_t a2, uint32_t a3, uint32_t db){
  asm volatile("{\n.reg .pred p;\n.reg .b64 a, b;\nsetp.ne.b32 p, 1, 0;\nmov.b64 b, {%24, %26};\n"
  "wgmma.mma_async.sync.aligned.m64n40k16.f32.bf16.bf16 {%0, %1, %2, %3, %4, %5, %6, %7, %8, %9, %10, %11, %12, %13, %14, %15, %16, %17, %18, %19}, {%20,%21,%22,%23}, b, p, 1, 1, %25;\n}\n"
  : "+f"(d[0]), "+f"(d[1]), "+f"(d[2]), "+f"(d[3]), "+f"(d[4]), "+f"(d[5]), "+f"(d[6]), "+f"(d[7]), "+f"(d[8]), "+f"(d[9]), "+f"(d[10]), "+f"(d[11]), "+f"(d[12]), "+f"(d[13]), "+f"(d[14]), "+f"(d[15]), "+f"(d[16]), "+f"(d[17]), "+f"(d[18]), "+f"(d[19])
  : "r"(a0), "r"(a1), "r"(a2), "r"(a3), "r"(db), "n"(TB), "n"(HB));
}
template<int TB, uint32_t HB> __device__ __forceinline__ void wgmma_rz_n40(float (&d)[20], uint32_t a0, uint32_t a1, uint32_t a2, uint32_t a3, uint32_t db){
  asm volatile("{\n.reg .pred p;\n.reg .b64 a, b;\nsetp.ne.b32 p, 0, 0;\nmov.b64 b, {%24, %26};\n"
  "wgmma.mma_async.sync.aligned.m64n40k16.f32.bf16.bf16 {%0, %1, %2, %3, %4, %5, %6, %7, %8, %9, %10, %11, %12, %13, %14, %15, %16, %17, %18, %19}, {%20,%21,%22,%23}, b, p, 1, 1, %25;\n}\n"
  : "=f"(d[0]), "=f"(d[1]), "=f"(d[2]), "=f"(d[3]), "=f"(d[4]), "=f"(d[5]), "=f"(d[6]), "=f"(d[7]), "=f"(d[8]), "=f"(d[9]), "=f"(d[10]), "=f"(d[11]), "=f"(d[12]), "=f"(d[13]), "=f"(d[14]), "=f"(d[15]), "=f"(d[16]), "=f"(d[17]), "=f"(d[18]), "=f"(d[19])
  : "r"(a0), "r"(a1), "r"(a2), "r"(a3), "r"(db), "n"(TB), "n"(HB));
}
template<int TB, uint32_t HB> __device__ __forceinline__ void wgmma_ra_n8(float (&d)[4], uint32_t a0, uint32_t a1, uint32_t a2, uint32_t a3, uint32_t db){
  asm volatile("{\n.reg .pred p;\n.reg .b64 a, b;\nsetp.ne.b32 p, 1, 0;\nmov.b64 b, {%8, %10};\n"
  "wgmma.mma_async.sync.aligned.m64n8k16.f32.bf16.bf16 {%0, %1, %2, %3}, {%4,%5,%6,%7}, b, p, 1, 1, %9;\n}\n"
  : "+f"(d[0]), "+f"(d[1]), "+f"(d[2]), "+f"(d[3])
  : "r"(a0), "r"(a1), "r"(a2), "r"(a3), "r"(db), "n"(TB), "n"(HB));
}
template<int TB, uint32_t HB> __device__ __forceinline__ void wgmma_rz_n8(float (&d)[4], uint32_t a0, uint32_t a1, uint32_t a2, uint32_t a3, uint32_t db){
  asm volatile("{\n.reg .pred p;\n.reg .b64 a, b;\nsetp.ne.b32 p, 0, 0;\nmov.b64 b, {%8, %10};\n"
  "wgmma.mma_async.sync.aligned.m64n8k16.f32.bf16.bf16 {%0, %1, %2, %3}, {%4,%5,%6,%7}, b, p, 1, 1, %9;\n}\n"
  : "=f"(d[0]), "=f"(d[1]), "=f"(d[2]), "=f"(d[3])
  : "r"(a0), "r"(a1), "r"(a2), "r"(a3), "r"(db), "n"(TB), "n"(HB));
}

constexpr int SEQ = 2048, DM = 1024, FF = 3584;
constexpr float LOG2E = 1.4426950408889634f;
constexpr uint32_t POLL_LIMIT = 1u << 22;
#define NPRE0 1
#define NPREN 2
constexpr int NPRE = NPREN;
#define QW 0
#define RS_N 22
#define RS_D1 430
#define RS_D2 300
#define SKM 0x154
#define LAG 2
#define PF_T0 5000
#define PF_DT 800
#define NFFN_L NFFN
#define FF_DT 500
#define OUT_U 1
#define GRES 8
#define OUT_L 0
#define TMASK 0xffffff
#define PMASK 0xffffff
#define FF_T0 400
#define GPRE 0
#define REL 6
#define EFI 11
#define TKW 8
#define SLOT 0
#define SLOTW 48
#define FF_ORD 0x76543210ba98ull
#define KT 0
#define KK(id) do { if (KT) { TK(32 * wg + (id)); } } while (0)
#define PF_I0 0
#define PF_ST 7
#define PRCP 1
#define OUT_NS 60
constexpr int NFFN = 112;

constexpr uint32_t SB0 = 1024;
constexpr uint32_t KV_STAGE = 49152, R5 = 32768;
constexpr uint32_t OFF_X = 163840, OFF_S = 196608, OFF_WPHI = OFF_S + 20480, OFF_M = 229376, SMEM_BYTES = 232448;
constexpr uint32_t OFF_RS256 = 212992, OFF_ONES = OFF_RS256 + 1024, OFF_WPHIK1 = OFF_ONES + 1024, OFF_KVZ = OFF_S;
constexpr uint32_t OFF_WPHIK = OFF_S, OFF_BXK = OFF_S + 2048, OFF_AXK = OFF_S + 4096, OFF_G = OFF_S + 8192;
constexpr uint32_t OFF_AXQ = OFF_WPHI, OFF_BXQ = OFF_WPHI + 2048, OFF_WPHIQ = OFF_WPHI + 4096;
constexpr uint32_t B_FULLKV = OFF_M  , B_EMPTYKV = OFF_M + 32  ;
constexpr uint32_t B_EMPTY5 = OFF_M + 64  , B_UO = B_EMPTY5 + 48  , B_RC = B_UO + 32  ;
constexpr uint32_t B_OUT = B_RC + 16  , B_AUX = B_OUT + 32, B_AUXQ = B_AUX + 8, B_RX = B_AUXQ + 8;
constexpr uint32_t B_FULL5 = B_RX + 8  , B_FULLA = B_FULL5 + 48  , B_F = B_FULLA + 96  , B_WD = B_F + 64  ;
constexpr uint32_t B_WC = B_WD + 32  , B_DR = B_WC + 32  , B_W = B_DR + 24, B_OS = B_W + 8, B_R = B_W + 16, B_KD = B_W + 24, B_XS = B_W + 32, B_T = B_W + 40, B_G = B_W + 48, B_END = B_W + 56, B_S0 = B_END;
static_assert(B_S0 < OFF_M + 576 && B_END <= OFF_M + 568 && B_FULL5 + 40 >= OFF_M + 200 && B_FULL5 + 40 < OFF_M + 384, "barriers");
constexpr uint32_t OFF_EXC = OFF_M + 576, OFF_SUMWR = OFF_M + 608, OFF_EP = OFF_M + 624, OFF_KEY = OFF_M + 628;
constexpr uint32_t OFF_RSQ = OFF_M + 640, OFF_TL = OFF_M + 1152, OFF_T = OFF_M + 1792, OFF_WR = OFF_M + 2048, OFF_SCR = OFF_M + 2432;
constexpr uint32_t OFF_XSEL = 2 * R5, OFF_ACT = OFF_XSEL + 2048, OFF_GU = OFF_XSEL + 4096, OFF_OUT = 3 * R5;
constexpr uint64_t FF_SLOT = 0xdcdc3210dcbaull;
constexpr int KVP = 6 * 128;

enum { NB_G2E = 1, NB_XS = 2, NB_WG01 = 3, NB_ACT = 4, NB_Q0 = 5  , NB_ST = 14, NB_DN = 9, NB_ZERO = 10, NB_PUB = 11, NB_TOK = 10  , NB_L0 = 12  , NB_WG2 = 7, NB_QGO = 15 };

struct Scratch {
  bf16     o[SEQ * DM];
  float4   rstat[SEQ];
  uint32_t key[32 * 128];
  uint32_t cand[128 * DM];
  uint32_t ypart[NFFN * DM];
  float4   kvacc[32 * KVP];
  uint2    stats[SEQ];
  uint32_t cskv[2 * DM];
  uint32_t csq[4 * DM];
  uint32_t oset[128 * 16];
  uint32_t epoch;
};
__device__ __align__(1024) Scratch g_scr;
#define TS(id)
#define TDUMP()
#define TS0_DECL()
#define TS0_READ()
#define TS0_WRITE()
#define TK(id)
#define TSW(id)

struct Params {
  CUtensorMap x128, x64, wkv, wq, wo[2], wd, wg, wu, phi, tg, tu, td, xs, ws, qs;
  const bf16 *x, *wqkv, *wo_p, *wg_p, *wu_p, *wd_p, *wr;
  bf16* out_p;
  Scratch* g;
  uint32_t zero;
};

constexpr float EXP_LIM = 1.1529215e18f, ARG_LIM2 = 3600.f;
__device__ __forceinline__ void dual_exp2(const float (&p)[2][16], uint32_t (&ph)[4][8]) {
  #pragma unroll
  for (int h = 0; h < 2; h++)
    #pragma unroll
    for (int k = 0; k < 8; k++) { ph[2*h][k] = pack_bf16(ex2(p[h][2*k]), ex2(p[h][2*k+1])); ph[2*h+1][k] = pack_bf16(ex2(-p[h][2*k]), ex2(-p[h][2*k+1])); }
}
__device__ __forceinline__ void dual_exp2_shifted(const float (&pp)[2][16], uint32_t (&ph)[4][8]) {
  #pragma unroll
  for (int h = 0; h < 2; h++) {
    const float* p = pp[h];
    float m[4] = {p[0], p[2], p[0], p[2]};
    #pragma unroll
    for (int i = 0; i < 16; i++) { m[(i >> 1) & 1] = fmaxf(m[(i >> 1) & 1], p[i]); m[2 + ((i >> 1) & 1)] = fminf(m[2 + ((i >> 1) & 1)], p[i]); }
    #pragma unroll
    for (int o = 1; o < 4; o <<= 1) {
      m[0] = fmaxf(m[0], __shfl_xor_sync(~0u, m[0], o)); m[1] = fmaxf(m[1], __shfl_xor_sync(~0u, m[1], o));
      m[2] = fminf(m[2], __shfl_xor_sync(~0u, m[2], o)); m[3] = fminf(m[3], __shfl_xor_sync(~0u, m[3], o));
    }
    #pragma unroll
    for (int k = 0; k < 8; k++) {
      ph[2*h][k] = pack_bf16(ex2(p[2*k] - m[k & 1]), ex2(p[2*k+1] - m[k & 1]));
      ph[2*h+1][k] = pack_bf16(ex2(m[2 + (k & 1)] - p[2*k]), ex2(m[2 + (k & 1)] - p[2*k+1]));
    }
  }
}
__device__ __forceinline__ void row_sums(float (&s)[4][4], const uint32_t (&ph)[4][8], uint32_t ones) {
  #pragma unroll
  for (int i = 0; i < 4; i++) wgmma_rz_n8<0, H0>(s[i], ph[i][0], ph[i][1], ph[i][2], ph[i][3], ones);
  #pragma unroll
  for (int i = 0; i < 4; i++) wgmma_ra_n8<0, H0>(s[i], ph[i][4], ph[i][5], ph[i][6], ph[i][7], ones);
}
__device__ __forceinline__ uint32_t mul_bf16x2(uint32_t a, uint32_t b) { uint32_t r; asm("mul.rn.bf16x2 %0, %1, %2;" : "=r"(r) : "r"(a), "r"(b)); return r; }
__device__ __forceinline__ void normalize(uint32_t (&ph)[4][8], const float (&s)[4][4]) {
  #pragma unroll
  for (int i = 0; i < 4; i++) {
    const float i0 = rcp(s[i][0]), i1 = rcp(s[i][2]);
    const uint32_t n0 = pack_bf16(i0, i0), n1 = pack_bf16(i1, i1);
    #pragma unroll
    for (int k = 0; k < 4; k++) { ph[i][2*k] = mul_bf16x2(ph[i][2*k], n0); ph[i][2*k+1] = mul_bf16x2(ph[i][2*k+1], n1); }
  }
}
__device__ __forceinline__ void split_bf16(float a, float b, uint32_t& hi, uint32_t& lo) { hi = pack_bf16(a, b); lo = pack_bf16(a - bf_lo(hi), b - bf_hi(hi)); }
__device__ __forceinline__ void put_colsums(uint32_t base, int lane, float a, float b, float c, float d) {
  uint32_t h0, l0, h1, l1;
  split_bf16(a, b, h0, l0); split_bf16(c, d, h1, l1);
  const uint32_t ad = base + (lane >> 1) * 128 + (lane & 1) * 8;
  sts64(ad, h0, h1); sts64(ad + 16, l0, l1); sts64(ad + 32, h0, h1); sts64(ad + 48, l0, l1);
  sts128(base + (lane >> 1) * 128 + 64 + (lane & 1) * 32, 0, 0, 0, 0); sts128(base + (lane >> 1) * 128 + 80 + (lane & 1) * 32, 0, 0, 0, 0);
}
__device__ __forceinline__ float reduce8(const float (&v)[8], int lane) {
  const bool b4 = lane & 16, b3 = lane & 8, b2 = lane & 4;
  float a[4], b[2];
  #pragma unroll
  for (int i = 0; i < 4; i++) a[i] = (b4 ? v[4 + i] : v[i]) + __shfl_xor_sync(~0u, b4 ? v[i] : v[4 + i], 16);
  #pragma unroll
  for (int i = 0; i < 2; i++) b[i] = (b3 ? a[2 + i] : a[i]) + __shfl_xor_sync(~0u, b3 ? a[i] : a[2 + i], 8);
  return (b2 ? b[1] : b[0]) + __shfl_xor_sync(~0u, b2 ? b[0] : b[1], 4);
}
__device__ __forceinline__ bool tag_bad(uint4 v, uint32_t tg) { return (((v.x ^ tg) | (v.y ^ tg) | (v.z ^ tg) | (v.w ^ tg)) & 3) != 0; }

__global__ void __launch_bounds__(512, 1) fused_kernel(const __grid_constant__ Params P) {
  extern __shared__ __align__(1024) uint8_t smem_raw[];
  const uint32_t sb = smem_u32(smem_raw);
  const int tid = threadIdx.x, lane = tid & 31;
  TS0_DECL();
  TS0_READ();
  if (tid == 352) { prefetch_map(&P.wkv); prefetch_map(&P.x128); }
  const int cp = blockIdx.x >> 1, rank = blockIdx.x & 1;
  const int cr = cp < 4 ? 32 + 8 * cp : cp - 4 + max((cp * 37 - 1076) >> 8, 0);
  const int c = (cr & 62) + 64 * (cr & 1) + rank;
  const int m256 = c >> 4, nkv = c & 15, m128 = c >> 3, j = c & 7;
  if ((tid >> 5) == 12 && elect_one()) {
    mbar_init(sb + B_S0, 1); mbar_init(sb + B_FULLKV, 1); mbar_init(sb + B_FULLKV + 8, 1);
    fence_async_smem();
    mbar_expect_tx(sb + B_S0, 32768);
    tma_4d(sb + 32768, &P.wkv, 0, 0, nkv, 1, sb + B_S0);
    tma_2d(sb, &P.x128, 0, 256 * m256, sb + B_S0);
    mbar_expect_tx(sb + B_FULLKV, 16384);
    tma_2d(sb + 16384, &P.x128, 0, 256 * m256 + 128, sb + B_FULLKV);
    if (NPRE0 > 1) {
      mbar_expect_tx(sb + B_FULLKV + 8, KV_STAGE);
      tma_4d(sb + KV_STAGE + 32768, &P.wkv, 0, 64, nkv, 1, sb + B_FULLKV + 8);
      tma_2d(sb + KV_STAGE, &P.x128, 64, 256 * m256, sb + B_FULLKV + 8);
      tma_2d(sb + KV_STAGE + 16384, &P.x128, 64, 256 * m256 + 128, sb + B_FULLKV + 8);
    }
    asm volatile("fence.mbarrier_init.release.cluster;" ::: "memory");
  }
  #pragma unroll
  for (int w = 0; w < 3; w++)
    if (tid == 32 + 32 * w) {
      #pragma unroll
      for (uint32_t b = B_FULLKV + 16 + 184 * w; b < B_FULLKV + 200 + 184 * w && b < B_END; b += 8)
        mbar_init(sb + b, b < B_EMPTYKV ? 1 : b < B_EMPTY5 ? 12 : b < B_OUT ? 4 : b < B_RX || b == B_W ? 2 : b == B_RX ? 8 : 1);
      if (w == 1) mbar_arrive(sb + B_FULL5 + 40);
      asm volatile("fence.mbarrier_init.release.cluster;" ::: "memory");
      fence_async_smem();
    }
  const int warp = __shfl_sync(~0u, tid >> 5, 0), wg = warp >> 2, wp = warp & 3;
  const int f = 16 * ((cr + 7) & 7) + 2 * (cr >> 3) + rank;
  const int ha = 4 * (nkv >> 1) + (nkv & 1);
  Scratch* const G = P.g;
  if ((sb & 0x3ffff) != SB0) asm volatile("trap;");
  __syncthreads();
  cluster_arrive();
  if (warp == 12) {
    TK(88 - 32);
    if (elect_one()) {
      #pragma unroll
      for (int s = NPRE0; s < NPRE; s++) {
        const uint32_t st = sb + s * KV_STAGE, fb = sb + B_FULLKV + 8 * s;
        mbar_expect_tx(fb, KV_STAGE);
        tma_4d(st + 32768, &P.wkv, 0, 64 * s, nkv, 1, fb);
        tma_2d(st, &P.x128, 64 * s, 256 * m256, fb);
        tma_2d(st + 16384, &P.x128, 64 * s, 256 * m256 + 128, fb);
      }
    }
    __syncwarp();
  }

  if (wg == 3) {
    asm volatile("setmaxnreg.dec.sync.aligned.u32 32;");
    cluster_wait();
    if (wp == 0) { TK(89 - 32); }
    const bool el = elect_one();
    const uint64_t ef = policy_evict_first(), en = policy_evict_normal();
    auto fetch_o = [&](const int t0, uint32_t so, uint32_t par) {
      const int sh = t0 & 1;
      uint32_t ready = 0;
      const bf16* base = G->o + (m128 * 16 + t0) * 8192 + rank * 4096;
      const bf16* hint = base + (lane & 3) * 1024 + 966 + (((j & 6) + ((lane >> 2) & ~sh)) & 7) * 16384 + 8 * sh * (~lane & 4);
      #pragma unroll 1
      for (int i = 2 - 2 * sh; i < 8; i += 1 + sh) {
        uint32_t it = 0;
        while ((~ready >> (4 * i) & (15 + 240 * sh)) && ++it < POLL_LIMIT) ready = __ballot_sync(~0u, ld32_rlx(hint) != ~0u);
        mbar_wait(sb + B_EMPTY5 + so, par);
        if (el) {
          bulk_g2s_mc(sb + so * 4096 + rank * 8192, base + (((j & 6) + i) & 7) * 16384, 8192, sb + B_FULLA + 2 * so + 8 * rank, ef);
          if (i == 2 - 2 * sh) TS(t0 == 0 ? (rank ? 4 : 12) : t0 == 3 ? (rank ? 31 : 10) : (rank ? 9 : 13));
        }
        so += 8;
        if (so == 48) { so = 0; par ^= 1; }
      }
    };
    if (wp == 0) {
      {
        #pragma unroll 1
        for (int kb = NPRE; kb < 16; kb++) {
          const uint32_t st = sb + (kb & 3) * KV_STAGE, fb = sb + B_FULLKV + 8 * (kb & 3);
          mbar_wait(fb + (B_EMPTYKV - B_FULLKV), ~(kb >> 2) & 1);
          if (el) {
            mbar_expect_tx(fb, KV_STAGE);
            tma_2d_mc(st + rank * 16384, &P.x128, 64 * kb, 256 * m256 + 128 * rank, fb);
            tma_4d_h(st + 32768, &P.wkv, 0, 64 * kb, nkv, 1, fb, ef);
          }
        }
        TS0_WRITE();
        uint64_t ord = 0xf3120edcba987654ull;
        uint32_t so = 0, par = 1;
        #pragma unroll 1
        for (int i = 0; i < 16; i++) {
          const uint32_t st = sb + so * 4096, fb = sb + B_FULL5 + so;
          const int k0 = (64 * (uint32_t)ord + 128 * (j & 6)) & 960;
          mbar_wait(i < 5 ? sb + B_EMPTYKV + so - (i > 1 ? 8 : 0) : fb + (B_EMPTY5 - B_FULL5), par);
          if (el) {
            mbar_expect_tx(fb, R5);
            tma_2d_mc_h(st + rank * 8192, &P.x64, k0, 128 * m128 + 64 * rank, fb, i >= EFI ? ef : en);
            tma_3d_h(st + 16384, &P.wq, 0, k0, 2 * j, fb, ef);
          }
          ord >>= 4; so += 8;
          if (so == 40) { so = 0; par ^= 1; }
        }
        #pragma unroll 1
        for (int i = 0; i < 19; i++) {
          const uint32_t fb = sb + B_FULL5 + so, fa = sb + B_FULLA + 2 * so, na = i == rank ? 0 : 8192;
          if (i == 1) { mbar_wait2(sb + B_FULL5 + 16, 0, sb + B_FULL5 + 24, 0); mbar_wait(sb + B_FULL5 + 32, 0); if (el) mbar_arrive(sb + B_R); }
          mbar_wait(fb + (B_EMPTY5 - B_FULL5), par);
          if (SLOT) { while (((uint32_t)clock() & (uint32_t)(SLOT - 1)) >= SLOTW) {} }
          if (el) {
            if (i < 16) {
              mbar_expect_tx(fb, 16384);
              const int row = i < 8 ? 128 * (((j & 6) + i) & 7) : 256 * (((j >> 1) + i) & 3) + 32 + 16 * (i & 4);
              tma_5d_h(sb + so * 4096 + 16384, &P.wo[i >> 3], 128 * j, row, fb, ef);
              tma_5d_h(sb + so * 4096 + 24576, &P.wo[i >> 3], 128 * j + 64, row, fb, ef);
              mbar_expect_tx(fa, na); mbar_expect_tx(fa + 8, na);
            } else mbar_arrive(sb + B_DR + 8 * (i - 16));
          }
          so += 8;
          if (so == 48) { so = 0; par ^= 1; }
        }
      }
    } else if (wp == 3) {
      const uint32_t t_start = (uint32_t)clock();
      if (el) {
        mbar_expect_tx(sb + B_W, 12288);
        #pragma unroll 1
        for (int i = 0; i < 6; i++) tma_2d(sb + (i == 0 ? OFF_WPHIK : i == 1 ? OFF_WPHIK1 : OFF_WPHIQ + 2048 * (i - 2)), &P.phi, 0, 32 * (i < 2 ? 2 * nkv + i : 4 * j + 2 * (i & 1) + ((i - 2) >> 1)), sb + B_W);
        prefetch_map(&P.x64); prefetch_map(&P.wq); prefetch_map(&P.wo[0]); prefetch_map(&P.wo[1]);
        prefetch_map(&P.wd); prefetch_map(&P.wg); prefetch_map(&P.wu);
      }
      #pragma unroll 1
      for (int i = 0; i < 8; i++) {
        st128_rlx(&G->cand[(m128 * 8 + i) * DM + (lane >> 4) * 512 + 64 * j + 4 * (lane & 15)], ~0u, ~0u, ~0u, ~0u);
        if (f < NFFN) st128_rlx(&G->ypart[f * DM + 128 * i + 4 * lane], ~0u, ~0u, ~0u, ~0u);
      }
      if (lane < 16) st128_rlx(&G->rstat[16 * c + lane], 0, 0, 0, 0);
      {
        const uint32_t nt = ld32_rlx(&G->epoch);
        if (lane < 8) { st128_rlx(&G->stats[16 * c + 2 * lane], nt, nt, nt, nt); st128_rlx(&G->csq[32 * c + 4 * lane], nt, nt, nt, nt); }
        if (lane < 4) { st128_rlx(&G->cskv[128 * nkv + 16 * m256 + 4 * lane], nt, nt, nt, nt); st128_rlx(&G->oset[16 * c + 4 * lane], nt, nt, nt, nt); }
      }
      if (lane < 8) st128_rlx(&G->key[(4 * j + (lane >> 1)) * 128 + m128 * 8 + 4 * (lane & 1)], 0, 0, 0, 0);
      if (c < 32) {
        #pragma unroll 1
        for (int i = lane; i < KVP; i += 32) st128_rlx(&G->kvacc[(ha + 2 * m256) * KVP + i], 0, 0, 0, 0);
      }
      fence_gpu();
      bar_arrive(NB_ZERO, 160);
      if (el) {
        #pragma unroll 1
        for (int i = PF_I0; i < 30; i++) {
          while ((uint32_t)clock() - t_start < (uint32_t)(PF_T0 + PF_DT * (i - PF_I0) + PF_ST * f)) __nanosleep(64);
          if (i < 4) { bulk_prefetch(P.wqkv + (size_t)(256 * i + c) * (3 * DM), 2048); bulk_prefetch(P.wqkv + (size_t)(256 * i + 128 + c) * (3 * DM), 2048); }
          else if (i < 6) bulk_prefetch(P.wo_p + (size_t)c * 8192 + (i - 4) * 4096, 8192);
          else if ((TMASK >> (i - 6)) & 1) {
            const int k = i - 6;
            if (f < NFFN) {
              if (k < 16) {
                #pragma unroll 1
                for (int e = 0; e < 4; e++) tma_2d(sb + OFF_T, rank ? &P.tu : &P.tg, 32 * (f & ~1), 64 * k + 16 * e, sb + B_T);
              } else { tma_2d(sb + OFF_T, &P.td, 0, 256 * f + 32 * (k - 16), sb + B_T); tma_2d(sb + OFF_T, &P.td, 0, 256 * f + 32 * (k - 16) + 16, sb + B_T); }
            }
          }
          else if (!((PMASK >> (i - 6)) & 1)) {}
          else if (i < 22) bulk_prefetch(((i & 1) ? P.wu_p : P.wg_p) + (size_t)((i - 6) >> 1) * 458752 + c * 3584, 7168);
          else bulk_prefetch(P.wd_p + (size_t)(i - 22) * 458752 + c * 3584, 7168);
        }
      }
      __syncwarp();
      mbar_wait2(sb + B_OS, 0, sb + B_RX, 0);
      #pragma unroll 1
      for (int t0 = 0; t0 < 4; t0 += 3) fetch_o(t0, t0 ? 8 : 24, 0);
    } else {
      const int half = wp - 1;
      const uint32_t ep1 = ld32_rlx(&G->epoch) + 1, tg = ep1 & 3;
      {
        uint32_t it = 0;
        sts128(sb + OFF_ONES + half * 512 + lane * 16, 0x3f803f80u, 0x3f803f80u, 0x3f803f80u, 0x3f803f80u);
        auto reset_o = [&](int i0, int i1, uint32_t dt) {
          uint32_t t0 = (uint32_t)clock();
          #pragma unroll 1
          for (int i = i0; i < i1; i++) {
            st128_rlx(G->o + (m128 * 16 + 2 * j + half) * 8192 + 256 * i + 8 * lane, ~0u, ~0u, ~0u, ~0u);
            while ((uint32_t)clock() - t0 < dt) __nanosleep(40);
            t0 += dt;
          }
        };
        mbar_wait(sb + B_S0, 0);
        reset_o(0, RS_N, RS_D1);
        bar_sync(NB_PUB, 192);
        const uint4* src = reinterpret_cast<const uint4*>(&G->stats[256 * m256 + 128 * half]) + lane;
        const uint4* srk = reinterpret_cast<const uint4*>(&G->cskv[128 * nkv]) + lane;
        uint4 v0, v1, vk;
        it = 0;
        do { v0 = ld128_rlx(src); v1 = ld128_rlx(src + 32); vk = ld128_rlx(srk); }
        while ((tag_bad(v0, tg) || tag_bad(v1, tg) || tag_bad(vk, tg)) && ++it < POLL_LIMIT);
        fence_acquire_gpu();
        if (half) put_colsums(sb + OFF_BXK, lane, untag(vk.x), untag(vk.y), untag(vk.z), untag(vk.w));
        #pragma unroll
        for (int i = 0; i < 2; i++) {
          const uint4 v = i ? v1 : v0;
          uint32_t hi, lo;
          split_bf16(-0.5f * untag(v.x), -0.5f * untag(v.z), hi, lo);
          const uint32_t h0 = __byte_perm(hi, hi, 0x1010), h1 = __byte_perm(hi, hi, 0x3232), l0 = __byte_perm(lo, lo, 0x1010), l1 = __byte_perm(lo, lo, 0x3232);
          const uint32_t a = sb + OFF_AXK + half * 2048 + i * 1024 + lane * 32;
          sts128(a, h0, l0, 0, 0); sts128(a + 16, h1, l1, 0, 0);
          sts64(sb + OFF_RS256 + half * 512 + i * 256 + lane * 8, v.y & ~3u, v.w & ~3u);
          if (half == (m128 & 1)) {
            const uint32_t aq = sb + OFF_AXQ + i * 1024 + lane * 32;
            sts128(aq, h0, l0, 0, 0); sts128(aq + 16, h1, l1, 0, 0);
            sts64(sb + OFF_RSQ + i * 256 + lane * 8, v.y & ~3u, v.w & ~3u);
          }
        }
        fence_async_smem();
        __syncwarp();
        if (el) { sts32(sb + OFF_EP, ep1); mbar_arrive(sb + B_AUX); if (!half) TS(1); }
        reset_o(RS_N, 32, RS_D2);
        fence_gpu();
        __syncwarp();
        if (el) { st32_rlx(&G->oset[16 * c + 8 * half], ep1); if (half) mbar_arrive(sb + B_AUXQ); }
        if (!half) {
          const uint4* src = reinterpret_cast<const uint4*>(&G->csq[128 * j]) + lane;
          uint4 v0, v1, v2, v3;
          do { v0 = ld128_rlx(src); v1 = ld128_rlx(src + DM / 4); v2 = ld128_rlx(src + DM / 2); v3 = ld128_rlx(src + 3 * DM / 4); }
          while ((tag_bad(v0, tg) || tag_bad(v1, tg) || tag_bad(v2, tg) || tag_bad(v3, tg)) && ++it < POLL_LIMIT);
          put_colsums(sb + OFF_BXQ, lane, (untag(v0.x) + untag(v1.x)) + (untag(v2.x) + untag(v3.x)), (untag(v0.y) + untag(v1.y)) + (untag(v2.y) + untag(v3.y)),
                      (untag(v0.z) + untag(v1.z)) + (untag(v2.z) + untag(v3.z)), (untag(v0.w) + untag(v1.w)) + (untag(v2.w) + untag(v3.w)));
          fence_async_smem();
          __syncwarp();
          if (el) mbar_arrive(sb + B_AUXQ);
        }
      }
      if (half == 0) {
        for (uint32_t it = 0; __any_sync(~0u, ld32_rlx(&G->oset[m128 * 128 + 8 * (lane & 15)]) != ep1) && it < POLL_LIMIT; it++) {}
        fence_acquire_gpu();
        if (el) mbar_arrive(sb + B_OS);
      }
      if (!half) {
        #pragma unroll 1
        for (int hh = 0; hh < 2; hh++) {
          const uint32_t src = sb + (1 + rank) * R5 + hh * 8192, fa = sb + B_FULLA + 16 + 16 * rank + 8 * hh;
          mbar_wait(fa, 0);
          mbar_wait(sb + B_UO + 8 * hh, 0);
          if (el) bulk_s2peer(mapa(src, rank ^ 1), src, 8192, mapa(fa, rank ^ 1));
        }
        fetch_o(1, 24, 1);
      }
      else if (f < NFFN_L) {
        mbar_wait2(sb + B_UO, 0, sb + B_UO + 8, 0);
        mbar_wait(sb + B_UO + 24, 0);
        uint32_t t0 = (uint32_t)clock();
        while ((uint32_t)clock() - t0 < (uint32_t)FF_T0) __nanosleep(32);
        t0 -= FF_DT;
        #pragma unroll 1
        for (int i = 0; i < 12; i++) {
          const int e = (FF_ORD >> (4 * i)) & 15;
          const uint32_t dst = sb + 16384 * ((FF_SLOT >> (4 * e)) & 15), fb = sb + B_F + 8 * e;
          if (i >= 2) mbar_wait(sb + B_WC + 8 * ((0x100066553244ull >> (4 * e)) & 15), 0);
          while ((uint32_t)clock() - t0 < (uint32_t)FF_DT) __nanosleep(32);
          t0 = (uint32_t)clock();
          if (i < 8) { TK(48 + i); }
          if (el) {
            mbar_expect_tx(fb, 16384);
            if (e >= 8) tma_3d_h(dst, &P.wd, 0, 32 * f, 4 * e - 32, fb, ef);
            else { tma_2d(dst, &P.wg, 32 * f, 128 * e, fb); tma_2d(dst + 8192, &P.wu, 32 * f, 128 * e, fb); }
          }
        }
      }
      __syncwarp();
    }
    {
      const int ch = lane & 15, rb = 32 * wp + (lane >> 4);
      const uint32_t src = sb + OFF_OUT + (ch >> 3) * 16384;
      bf16* dst = P.out_p + (size_t)(128 * m128) * DM + 128 * j + 8 * ch;
      __syncwarp();
      mbar_wait(sb + B_OUT + 8 * wp, 0);
      const float2 ex = lds64f(sb + OFF_EXC + 8 * wp);
      if (OUT_L) mbar_wait(sb + B_XS, 0);
      #pragma unroll 1
      for (int i = 0; i < 32; i += 2 * OUT_U) {
        uint4 v[OUT_U];
        #pragma unroll
        for (int e = 0; e < OUT_U; e++) { const int r = rb + i + 2 * e; v[e] = lds128(src + r * 128 + (((ch ^ r) & 7) << 4)); }
        #pragma unroll
        for (int e = 0; e < OUT_U; e++) { const int r = rb + i + 2 * e; if (r != __float_as_int(i < 16 ? ex.x : ex.y)) *reinterpret_cast<uint4*>(dst + r * DM) = v[e]; }
        if (OUT_NS) __nanosleep(OUT_NS);
      }
      if (wp == 0) { TK(63); }
      mbar_wait(sb + B_XS, 0);
      const int row = 2047 - (__float_as_uint(ldsf(sb + OFF_KEY)) & 2047) - 128 * m128, r = __float_as_int(lane < 16 ? ex.x : ex.y);
      if (r != row) *reinterpret_cast<uint4*>(dst + r * DM) = lds128(src + r * 128 + (((ch ^ r) & 7) << 4));
    }
    __syncwarp();
    cluster_arrive(); cluster_wait();
    return;
  }

  asm volatile("setmaxnreg.inc.sync.aligned.u32 160;");
  cluster_wait();
  const int t = tid & 127, g = lane >> 2;
  const uint32_t sa = (16 * wp + (lane & 15)) * 128 + (((lane >> 4) ^ (lane & 7)) << 4);

  if (wg == 2) {
    float s[2] = {0.f, 0.f}, s2[2] = {0.f, 0.f}, ck[8] = {0.f, 0.f, 0.f, 0.f, 0.f, 0.f, 0.f, 0.f}, cs[8] = {0.f, 0.f, 0.f, 0.f, 0.f, 0.f, 0.f, 0.f};
    const uint32_t ebr = mapa(sb + B_EMPTYKV, lane & 1), tg = (ld32_rlx(&G->epoch) + 1) & 3;
    auto addx = [&](const uint4 v) {
      const uint32_t w[4] = {v.x, v.y, v.z, v.w};
      #pragma unroll
      for (int e = 0; e < 4; e++) { const float a = bf_lo(w[e]), d = bf_hi(w[e]); s[0] += a; s[1] += d; s2[0] = fmaf(a, a, s2[0]); s2[1] = fmaf(d, d, s2[1]); }
    };
    auto addc = [&](const uint4 v, float (&o)[8]) {
      o[0] += bf_lo(v.x); o[1] += bf_hi(v.x); o[2] += bf_lo(v.y); o[3] += bf_hi(v.y); o[4] += bf_lo(v.z); o[5] += bf_hi(v.z); o[6] += bf_lo(v.w); o[7] += bf_hi(v.w);
    };
    {
      const uint32_t ra = (16 * nkv + (t >> 3)) * 128 + (t & 7) * 16;
      const uint32_t ca = 32768 + (m256 >> 2) * 8192 + (t >> 1) * 128 + (((2 * (m256 & 3) + (t & 1)) ^ ((t >> 1) & 7)) << 4);
      int rd = 0;
      mbar_wait(sb + B_S0, 0);
      #pragma unroll 1
      for (int kb = 0; kb < 10; kb++) {
        const uint32_t st = sb + (kb & 3) * KV_STAGE;
        mbar_wait(sb + B_FULLKV + 8 * (kb & 3), (kb >> 2) & 1);
        const uint4 x0 = lds128(st + ra), w0 = lds128(st + ca);
        addx(x0); addc(w0, ck);
        __syncwarp();
        if (lane < 2) mbar_arrive_remote(ebr + 8 * (kb & 3), 1);
        if ((SKM >> kb) & 1) {
          if (rd) {
            mbar_wait(sb + B_G, (rd - 1) & 1);
            const uint32_t a = sb + OFF_G + (t >> 3) * 256 + (t & 7) * 16;
            const uint4 x1 = lds128(a), x2 = lds128(a + 128), w1 = lds128(sb + OFF_G + 4096 + t * 16), w2 = lds128(sb + OFF_G + 6144 + t * 16);
            addx(x1); addx(x2); addc(w1, ck); addc(w2, ck);
            bar_sync(NB_WG2, 128);
          }
          if (wp == 0 && elect_one()) {
            mbar_expect_tx(sb + B_G, 8192);
            if (rd < 3) {
              tma_2d(sb + OFF_G, &P.xs, 640 + 128 * rd, 256 * m256 + 16 * nkv, sb + B_G);
              tma_2d(sb + OFF_G + 4096, &P.ws, (1 + (m256 >> 2)) * DM + 64 * nkv + 16 * (m256 & 3), 640 + 128 * rd, sb + B_G);
            } else tma_2d(sb + OFF_G, &P.qs, 32 * (c & 31), 256 * (c >> 5), sb + B_G);
          }
          rd++;
        }
      }
    }
    TK(82);
    const uint32_t scr = sb + OFF_SCR + 128;
    float sx = s[0] + s[1], sq = s2[0] + s2[1];
    #pragma unroll
    for (int o = 1; o < 8; o <<= 1) { sx += __shfl_xor_sync(~0u, sx, o); sq += __shfl_xor_sync(~0u, sq, o); }
    float v = reduce8(ck, lane);
    v += __shfl_xor_sync(~0u, v, 2);
    if (!(lane & 2)) stsf(scr + (wp * 16 + 8 * (lane & 1) + (lane >> 2)) * 4, v);

    bar_sync(NB_ZERO, 160);
    if ((lane & 7) == 0) {
      const float mean = sx * (1.f / DM);
      st64_rlx(&G->stats[256 * m256 + 16 * nkv + (t >> 3)], tagw(mean, tg), tagw(rsqrtf(fmaxf(sq * (1.f / DM) - mean * mean, 0.f) + 1e-5f), tg));
    }
    if (wp == 1 && lane < 16) {
      const uint32_t a = scr + lane * 4;
      st32_rlx(&G->cskv[128 * nkv + 16 * m256 + lane], tagw((ldsf(a) + ldsf(a + 64)) + (ldsf(a + 128) + ldsf(a + 192)), tg));
    }
    __syncwarp();
    bar_arrive(NB_PUB, 192);
    TSW(23);
    const uint4 wv = ld128_keep(P.wr + t * 8);
    #pragma unroll 1
    for (int i = 0; i < 2; i++) {
      mbar_wait(sb + B_G, i ^ 1);
      const uint32_t a = sb + OFF_G + t * 16;
      const uint4 u0 = lds128(a), u1 = lds128(a + 2048), u2 = lds128(a + 4096), u3 = lds128(a + 6144);
      addc(u0, cs); addc(u1, cs); addc(u2, cs); addc(u3, cs);
      bar_sync(NB_WG2, 128);
      if (i == 0 && wp == 0 && elect_one()) { mbar_expect_tx(sb + B_G, 8192); tma_2d(sb + OFF_G, &P.qs, 32 * (c & 31), 256 * (c >> 5) + 128, sb + B_G); }
    }
    if (t == 0) mbar_arrive(sb + B_W);
    float sw = (bf_lo(wv.x) + bf_hi(wv.x)) + (bf_lo(wv.y) + bf_hi(wv.y)) + (bf_lo(wv.z) + bf_hi(wv.z)) + (bf_lo(wv.w) + bf_hi(wv.w));
    #pragma unroll
    for (int o = 16; o; o >>= 1) sw += __shfl_xor_sync(~0u, sw, o);
    if (lane == 0) stsf(sb + OFF_SUMWR + wp * 4, sw);
    if ((t >> 4) == j) {
      const uint32_t a = sb + OFF_WR + (t & 15) * 32;
      sts128(a, wv.x << 16, wv.x & 0xffff0000u, wv.y << 16, wv.y & 0xffff0000u);
      sts128(a + 16, wv.z << 16, wv.z & 0xffff0000u, wv.w << 16, wv.w & 0xffff0000u);
    }
    v = reduce8(cs, lane);
    stsf(scr + (wp * 32 + 8 * (lane & 3) + (lane >> 2)) * 4, v);
    bar_sync(NB_WG2, 128);
    if (wp == 0) {
      const uint32_t a = scr + lane * 4;
      st32_rlx(&G->csq[(c >> 5) * DM + 32 * (c & 31) + lane], tagw((ldsf(a) + ldsf(a + 128)) + (ldsf(a + 256) + ldsf(a + 384)), tg));
    }
  }

  uint32_t xr[32];
  {
    const bool isq = wg == 2;
    float acc[2][64];
    {
      const uint32_t emptyb = mapa(sb + (isq ? B_EMPTY5 : B_EMPTYKV), t & 1);
      if (!isq) {
        mbar_wait(sb + B_S0, 0);
        if (wg) mbar_wait(sb + B_FULLKV, 0);
        if (wg == 0) { TSW(2); }
        #pragma unroll 1
        for (int kb = 0; kb < 16; kb++) {
          if (!KT && wg == 0) { TK(kb); }
          const uint32_t da = dlo(SB0, 16) + wg * 1024 + (kb & 3) * (KV_STAGE >> 4), db = dlo(SB0 + 32768, 8192) + (kb & 3) * (KV_STAGE >> 4);
          wg_fence();
          #pragma unroll
          for (int k = 0; k < 4; k++) {
            wgmma_ss_n128<0, 1, H128, H128>(acc[0], da + 2 * k, db + 128 * k, k > 0 || kb != 0);
            wgmma_ss_n128<0, 1, H128, H128>(acc[1], da + 512 + 2 * k, db + 128 * k, k > 0 || kb != 0);
          }
          wg_commit();
          wg_wait<1>();
          if (kb > 0 && t < 2) mbar_arrive_remote(emptyb + 8 * ((kb - 1) & 3), kb > 10 ? 3 : 1);
          if (kb < 15) mbar_wait(sb + B_FULLKV + 8 * ((kb + 1) & 3), ((kb + 1) >> 2) & 1);
          if (kb == 15 - LAG && wg == 1) bar_sync(NB_WG01, 256);
        }
        bar_arrive(wg ? NB_QGO : NB_WG01, 256);
      } else {
        uint32_t so = 0, po = 0, par = 0;
        mbar_wait(sb + B_FULL5, 0);
        bar_sync(NB_QGO, 256);
        TSW(11);
        #pragma unroll 1
        for (int kb = 0; kb < 16; kb++) {
          TK(16 + kb);
          const uint32_t da = dlo(SB0, 16) + so * 256, db = dlo(SB0 + 16384, 8192) + so * 256;
          #pragma unroll
          for (int k = 0; k < 4; k++) {
            wg_fence();
            wgmma_ss_n128<0, 1, H128, H128>(acc[0], da + 2 * k, db + 128 * k, k > 0 || kb != 0);
            wgmma_ss_n128<0, 1, H128, H128>(acc[1], da + 512 + 2 * k, db + 128 * k, k > 0 || kb != 0);
            wg_commit();
            if (k == 1 && kb > 0 && t < 2) mbar_arrive_remote(emptyb + po, 2);
            if (k == 3) {
              po = so; so += 8;
              if (so == 40) { so = 0; par ^= 1; }
              if (kb < 15) mbar_wait(sb + B_FULL5 + so, par);
            }
            if ((QW >> k) & 1) wg_wait<2>(); else wg_wait<1>();
          }
        }
        mbar_wait(sb + B_AUXQ, 0);
      }
      mbar_wait(sb + B_AUX, 0);
      const uint32_t xa = dlo(SB0, 0) + (isq ? OFF_AXQ >> 4 : (OFF_AXK >> 4) + wg * 128), xb = dlo(SB0, 0) + (isq ? OFF_BXQ >> 4 : OFF_BXK >> 4);
      wg_fence();
      wgmma_sa_n128<0, 1, H0, H0>(acc[0], xa, xb);
      wgmma_sa_n128<0, 1, H0, H0>(acc[1], xa + 64, xb);
      wg_commit();
      if (isq) mbar_wait(sb + B_RC, 0);
      wg_wait<0>();
      if (t < 2) mbar_arrive_remote(emptyb + (isq ? 0 : 24), isq ? 2 : 3);
      if (wg != 1) { TSW(wg ? 8 : 3); }
      fence_regs(acc[0]); fence_regs(acc[1]);
    }
    if (isq) {
      #pragma unroll
      for (int i = 0; i < 2; i++) {
        const uint32_t ta = sb + (1 + rank) * R5 + sa + i * 8192;
        if (i == 1) mbar_wait(sb + B_RC + 8, 0);
        #pragma unroll
        for (int k = 0; k < 4; k++) {
          const float* a = &acc[i][32 * (k >> 1) + 8 * (k & 1)];
          stsm4(ta ^ (k << 5), pack_bf16(a[0], a[1]), pack_bf16(a[2], a[3]), pack_bf16(a[4], a[5]), pack_bf16(a[6], a[7]));
        }
        fence_async_smem();
        bar_arrive(NB_Q0 + i, 256);
      }
      #pragma unroll
      for (int i = 0; i < 32; i++) { const float* a = &acc[(i >> 3) & 1][16 + 32 * (i >> 4) + 2 * (i & 7)]; xr[i] = pack_bf16(a[0], a[1]); }
      TSW(26);
    } else {
      const uint32_t stg = sb + OFF_X + (1 - wg) * 24576;
      const uint32_t va = stg + 16384 + (16 * wp + (lane & 15)) * 64 + (((lane >> 4) ^ ((lane >> 1) & 3)) << 4);
      const uint32_t ra = sb + OFF_RS256 + (128 * wg + 16 * wp + g) * 4;
      const float rs[4] = {ldsf(ra), ldsf(ra + 32), ldsf(ra + 256), ldsf(ra + 288)};
      float p[2][16];
      uint32_t vf[16], kf[2][16];
      auto project = [&](const uint32_t (&f)[16], uint32_t db) {
        wg_fence();
        #pragma unroll
        for (int i = 0; i < 2; i++) {
          wgmma_rs_n32<1, H64>(p[i], f[8*i], f[8*i+1], f[8*i+2], f[8*i+3], db, 0);
          wgmma_ra_n32<1, H64>(p[i], f[8*i+4], f[8*i+5], f[8*i+6], f[8*i+7], db + 64);
        }
        wg_commit();
      };
      auto fold = [&](uint32_t (&f)[16], int col, float sc) {
        #pragma unroll
        for (int i = 0; i < 16; i++) {
          const float r = rs[2 * (i >> 3) + (i & 1)] * sc;
          f[i] = pack_bf16(acc[i >> 3][col + 2 * (i & 7)] * r, acc[i >> 3][col + 2 * (i & 7) + 1] * r);
          asm volatile("" : "+r"(f[i]));
        }
      };
      auto put_v = [&](const uint32_t (&f)[16]) {
        #pragma unroll
        for (int k = 0; k < 4; k++) stsm4((va ^ ((k & 1) << 5)) + (k >> 1) * 4096, f[4*k], f[4*k+1], f[4*k+2], f[4*k+3]);
      };
      KK(0);
      fold(vf, 48, 1.f);
      mbar_wait(sb + B_W, 0);
      fold(kf[0], 0, LOG2E);
      #pragma unroll
      for (int i = 0; i < 32; i++) p[i >> 4][i & 15] = acc[i >> 4][i & 15];
      project(kf[0], dlo(SB0 + OFF_WPHIK, 16));
      mbar_wait(sb + B_W, 0);
      KK(1);
      {
        uint32_t v0[16];
        fold(kf[1], 16, LOG2E);
        fold(v0, 32, 1.f);
        if (wg == 1) bar_sync(NB_DN, 256);
        put_v(v0);
      }
      wg_wait<0>();
      fence_regs(p[0]); fence_regs(p[1]);
      if (wg == 1) bar_arrive(NB_WG01, 256);
      KK(2);
      #pragma unroll 1
      for (int h = 0; h < 2; h++) {
        uint32_t ph[4][8];
        float rsum[4][4];
        dual_exp2(p, ph);
        wg_fence();
        row_sums(rsum, ph, dlo(SB0 + OFF_ONES, 128));
        wg_commit();
        KK(3 + 6 * h);
        if (wg == 0 && h == 0) { bar_arrive(NB_DN, 256); bar_sync(NB_WG01, 256); }
        if (h == 1) {
          if (wg == 1) bar_sync(NB_DN, 256);
          put_v(vf);
        }
        wg_wait<0>();
        KK(4 + 6 * h);
        #pragma unroll
        for (int i = 0; i < 4; i++) fence_regs(rsum[i]);
        if (__builtin_expect(__any_sync(~0u, !((rsum[0][0] + rsum[0][2]) + (rsum[1][0] + rsum[1][2]) + (rsum[2][0] + rsum[2][2]) + (rsum[3][0] + rsum[3][2]) < EXP_LIM)), 0)) {
          dual_exp2_shifted(p, ph);
          #pragma unroll
          for (int i = 0; i < 8; i++) {
            const uint32_t* f = &ph[i >> 1][i & 1];
            float a = (bf_lo(f[0]) + bf_hi(f[0])) + (bf_lo(f[2]) + bf_hi(f[2])) + (bf_lo(f[4]) + bf_hi(f[4])) + (bf_lo(f[6]) + bf_hi(f[6]));
            a += __shfl_xor_sync(~0u, a, 1);
            rsum[i >> 1][2 * (i & 1)] = a + __shfl_xor_sync(~0u, a, 2);
          }
        }
        if (h == 0) project(kf[1], dlo(SB0 + OFF_WPHIK1, 16));
        normalize(ph, rsum);
        #pragma unroll
        for (int i = 0; i < 8; i++) {
          const uint32_t* f = &ph[i >> 1][4 * (i & 1)];
          stsm4(((stg + sa) ^ ((i & 3) << 5)) + (i >> 2) * 8192, f[0], f[1], f[2], f[3]);
        }
        KK(5 + 6 * h);
        fence_async_smem();
        KK(6 + 6 * h);
        if (wg != h) { KK(7 + 6 * h); }
        if (wg == h) {
          float kv[20];
          #pragma unroll
          for (int w = 0; w < 2; w++) {
            const uint32_t da = dlo(SB0 + OFF_X, 16) + (h ^ w ^ 1) * 1536, db = dlo(SB0 + OFF_X + 16384, OFF_ONES - OFF_X - 16384) - (h ^ w ^ 1) * (1536 * 65535);
            if (w) bar_sync(NB_ST, 256); else bar_sync(NB_L0 + h, 128);
            wg_fence();
            #pragma unroll
            for (int k = 0; k < 8; k++) {
              if (k == 0 && w == 0) wgmma_sz_n40<1, 1, H128, H64>(kv, da, db);
              else wgmma_sa_n40<1, 1, H128, H64>(kv, da + k * 128, db - k * (64 * 65535));
            }
            wg_commit();
          }
          float4* dst = &G->kvacc[(ha + 2 * h) * KVP + t];
          wg_wait<0>();
          fence_regs(kv);
          KK(7 + 6 * h);
          if (h == 0) bar_arrive(NB_DN, 256); else if (t < 2) { mbar_arrive_at(sb + B_EMPTY5 + 40, t, 2); if (t == 0) mbar_arrive(sb + B_KD); }
          kv[17] = kv[18];
          #pragma unroll
          for (int i = 0; i < 6; i++) red_add_f32x4(dst + 128 * i, kv[3*i], kv[3*i+1], kv[3*i+2], 1.f);
          TSW(29 + h);
        } else bar_arrive(NB_ST, 256);
        wg_wait<0>();
        KK(8 + 6 * h);
        fence_regs(p[0]); fence_regs(p[1]);
      }
      #pragma unroll
      for (int i = 0; i < 32; i++) asm volatile("mov.b32 %0, 0;" : "=r"(xr[i]));
    }
    float p[2][16];
    #pragma unroll
    for (int i = 0; i < 32; i++) asm volatile("mov.b32 %0, 0;" : "=f"(p[i >> 4][i & 15]));
    auto project_r = [&](int w) {
      wg_fence();
      #pragma unroll
      for (int h = 0; h < 2; h++) {
        wgmma_rs_n32<1, H64>(p[h], xr[8*h], xr[8*h+1], xr[8*h+2], xr[8*h+3], dlo(SB0 + OFF_WPHIQ, 16) + 128 * w, 0);
        wgmma_ra_n32<1, H64>(p[h], xr[8*h+4], xr[8*h+5], xr[8*h+6], xr[8*h+7], dlo(SB0 + OFF_WPHIQ, 16) + 128 * w + 64);
      }
      wg_commit();
    };
    {
      const uint4* src = reinterpret_cast<const uint4*>(&G->kvacc[(4 * j + wg) * KVP + t]);
      uint4 v[12];
      #pragma unroll
      for (int i = 0; i < 12; i++) v[i] = i < 6 || isq ? ld128_rlx(src + 128 * i) : make_uint4(0, 0, 0, 0x41000000u);
      if (isq) {
        project_r(2);
        wg_wait<0>();
        #pragma unroll
        for (int i = 0; i < 16; i++) xr[i] = xr[16 + i];
      } else {
        mbar_wait(sb + B_R, 0);
        #pragma unroll
        for (int k = 0; k < 8; k++) ldsm4(((sb + (1 + rank) * R5 + wg * 8192 + sa) ^ ((k & 3) << 5)) + (k >> 2) * 2 * R5, xr[4*k], xr[4*k+1], xr[4*k+2], xr[4*k+3]);
        const uint32_t one = (((xr[0] | xr[4] | xr[8]) | (xr[12] | xr[16] | xr[20]) | (xr[24] | xr[28])) & P.zero) + 1;
        if (lane == 0) { mbar_arrive_at(sb + B_RC + 8 * wg, rank, one); mbar_arrive_at(sb + B_RX, wg, one); }
      }
      #pragma unroll 1
      for (uint32_t it = 0; it < POLL_LIMIT; it++) {
        uint32_t bad = 0;
        #pragma unroll
        for (int i = 0; i < 12; i++) bad |= v[i].w ^ 0x41000000u;
        if (!__any_sync(~0u, bad != 0)) break;
        #pragma unroll
        for (int i = 0; i < 12; i++) if (i < 6 || isq) v[i] = ld128_rlx(src + 128 * i);
      }
      mbar_wait(sb + B_KD, 0);
      #pragma unroll
      for (int e = 0; e < 2; e++) {
        if (e == 0 || isq) {
          float f[18];
          #pragma unroll
          for (int i = 0; i < 6; i++) { f[3*i] = __uint_as_float(v[6*e+i].x); f[3*i+1] = __uint_as_float(v[6*e+i].y); f[3*i+2] = __uint_as_float(v[6*e+i].z); }
          const uint32_t ka = sb + OFF_KVZ + (wg + e) * 5120 + wp * 1280 + lane * 16;
          stsm4(ka, pack_bf16(f[0], f[1]), pack_bf16(f[2], f[3]), pack_bf16(f[4], f[5]), pack_bf16(f[6], f[7]));
          stsm4(ka + 512, pack_bf16(f[8], f[9]), pack_bf16(f[10], f[11]), pack_bf16(f[12], f[13]), pack_bf16(f[14], f[15]));
          stsm2(ka + 1024, pack_bf16(f[16], 1.f), pack_bf16(f[17], 1.f));
        }
      }
    }
    fence_async_smem();
    if (wg == 1) bar_arrive(NB_DN, 256);
    if (isq) mbar_wait(sb + B_OS, 0);
    TSW(wg == 0 ? 5 : wg == 1 ? 25 : 6);
    #pragma unroll 1
    for (int e = wg; e < wg + 1 + (wg >> 1); e++) {
      const int half = e >> 1, hh = e & 1, turn = e;
      const uint32_t ao = (1 + rank) * R5 + hh * 8192;
      const uint32_t ra = sb + OFF_RSQ + (16 * wp + g) * 4 + (e == 1 ? 256 : 0), rb = ra + 256 * half;
      const float cc[2][2] = {{ldsf(ra) * LOG2E, ldsf(ra + 32) * LOG2E}, {ldsf(rb) * LOG2E, ldsf(rb + 32) * LOG2E}};
      uint32_t ph[4][8];
      #pragma unroll
      for (int i = 0; i < 32; i++) asm volatile("mov.b32 %0, 0;" : "=r"(ph[i >> 3][i & 7]));
      auto exps = [&](int h) {
        #pragma unroll
        for (int k = 0; k < 8; k++) {
          const float a = ex2(p[h][2*k]), b = ex2(p[h][2*k+1]);
          ph[2*h][k] = pack_bf16(a, b);
          if (PRCP) { const float r = rcp(a * b); ph[2*h+1][k] = pack_bf16(r * b, r * a); }
          else ph[2*h+1][k] = pack_bf16(ex2(-p[h][2*k]), ex2(-p[h][2*k+1]));
        }
      };
      uint32_t shifted = 0;
      asm volatile("" : "+r"(shifted));
      #pragma unroll 1
      for (;;) {
        if (shifted) dual_exp2_shifted(p, ph);
        uint32_t first = (shifted ^ 1) & !isq;
        asm volatile("" : "+r"(first));
        if (first) {
          bar_sync(NB_Q0 + wg, 256);
          const uint32_t da = dlo(SB0, 16) + (ao >> 4), db = dlo(SB0 + OFF_WPHIQ, 16);
          wg_fence();
          #pragma unroll
          for (int h = 0; h < 2; h++) {
            wgmma_ss_n32<0, 1, H128, H64>(p[h], da + 4 * h, db + 128 * h, 0);
            wgmma_sa_n32<0, 1, H128, H64>(p[h], da + 4 * h + 2, db + 128 * h + 64);
          }
          wg_commit();
          wg_wait<0>();
        }
        fence_regs(p[0]); fence_regs(p[1]);
        uint32_t again = shifted;
        asm volatile("" : "+r"(again));
        if (again) break;
        float s2[4] = {0.f, 0.f, 0.f, 0.f};
        #pragma unroll
        for (int i = 0; i < 32; i++) { float& x = p[i >> 4][i & 15]; x *= cc[i >> 4][(i >> 1) & 1]; s2[i & 3] = fmaf(x, x, s2[i & 3]); }
        if (!__any_sync(~0u, !((s2[0] < ARG_LIM2) & (s2[1] < ARG_LIM2) & (s2[2] < ARG_LIM2) & (s2[3] < ARG_LIM2)))) break;
        shifted = 1;
      }
      if (e == 1 || e == 2) bar_sync(NB_TOK + e - 1, 256);
      TK(64 + 4 * turn);
      float ac[4][20];
      auto numer = [&](int h) {
        const uint32_t (*f)[8] = &ph[2 * h];
        const uint32_t db = dlo(SB0 + OFF_KVZ, 128) + (half ? e : h) * 320;
        wg_fence();
        #pragma unroll
        for (int i = 0; i < 2; i++) {
          wgmma_rz_n40<1, dhi(256, 0)>(ac[2*h+i], f[i][0], f[i][1], f[i][2], f[i][3], db + i * 160);
          wgmma_ra_n40<1, dhi(256, 0)>(ac[2*h+i], f[i][4], f[i][5], f[i][6], f[i][7], db + (i * 160 + 80));
        }
        wg_commit();
      };
      const uint32_t oa = (16 * wp + g) * 128 + (((lane & 3) ^ g) << 4);
      auto finish = [&](int h) {
        const float* ap = ac[2 * h]; const float* am = ac[2 * h + 1];
        const float ip0 = rcp(ap[17]), im0 = rcp(am[17]), ip1 = rcp(ap[19]), im1 = rcp(am[19]);
        const float d0 = rcp(fmaf(ap[16], ip0, fmaf(am[16], im0, 1e-6f))), d1 = rcp(fmaf(ap[18], ip1, fmaf(am[18], im1, 1e-6f)));
        const float a0 = ip0 * d0, b0 = im0 * d0, a1 = ip1 * d1, b1 = im1 * d1;
        #pragma unroll
        for (int r = 0; r < 2; r++) {
          const float a = r ? a1 : a0, b = r ? b1 : b0;
          uint32_t w[4];
          #pragma unroll
          for (int k = 0; k < 4; k++) w[k] = pack_bf16(fmaf(ap[4*k+2*r], a, am[4*k+2*r] * b), fmaf(ap[4*k+2*r+1], a, am[4*k+2*r+1] * b));
          const uint32_t off = (oa ^ ((half ? rank : h) << 6)) + r * 1024;
          st128_rlx(reinterpret_cast<uint8_t*>(G->o + (m128 * 16 + (half ? 2 * (j & 6) + 2 * hh + 1 : 2 * j)) * 8192 + (half ? h : hh) * 4096) + off, w[0], w[1], w[2], w[3]);
          if (!half) sts128(sb + ao + off, w[0], w[1], w[2], w[3]);
        }
      };
      if (!shifted) exps(0);
      numer(0);
      if (!shifted) exps(1);
      if (turn < 2) bar_arrive(NB_TOK + turn, 256);
      if (wg == 0) bar_sync(NB_DN, 256);
      numer(1);
      wg_wait<1>();
      TK(65 + 4 * turn);
      fence_regs(ac[0]); fence_regs(ac[1]);
      finish(0);
      wg_wait<0>();
      fence_regs(ac[2]); fence_regs(ac[3]);
      #pragma unroll
      for (int i = 0; i < 32; i++) asm volatile("mov.b32 %0, 0;" : "=f"(p[i >> 4][i & 15]));
      if (e == 2) project_r(3);
      finish(1);
      TK(66 + 4 * turn);
      if (!half) fence_async_smem();
      __syncwarp();
      if (lane == 0) mbar_arrive(sb + B_UO + 8 * e);
      wg_wait<0>();
      TK(67 + 4 * turn);
    }
    if (isq) cluster_arrive();
  }

  {
  int lane;
  asm volatile("mov.u32 %0, %%laneid;" : "=r"(lane));
  const int g = lane >> 2, q = lane & 3;
  if (wg < 2) {
    float h[64];
    {
      if (wg == 0) { TK(83); }
      #pragma unroll
      for (int i = 0; i < 32; i++) { h[2*i] = bf_lo(xr[i]); h[2*i+1] = bf_hi(xr[i]); }
      fence_regs(h);
      TK(80 + wg);
      const uint32_t emptyb = mapa(sb + B_EMPTY5, t & 1);
      uint32_t s = 1 + rank, ps = 0;
      mbar_wait2(sb + B_FULL5 + 8 * s, 1, sb + B_UO + 8 * wg, 0);
      if (wg == 0) { TSW(14); }
      #pragma unroll
      for (int i = 0; i < 16; i++) {
        if (wg == 1 && (i & 12) == TKW) { TK(84 + (i & 3)); }
        if (!KT && wg == 0) { TK(32 + i); }
        const uint32_t da = dlo(SB0, 16) + s * 2048 + wg * 512, db = dlo(SB0 + 16384, 8192) + s * 2048;
        wg_fence();
        #pragma unroll
        for (int k = 0; k < 4; k++) wgmma_sa_n128<0, 1, H128, H128>(h, da + k * 2, db + k * 128);
        wg_commit();
        const uint32_t ns = i ? (i + 2) % 6 : 2 - rank;
        const uint32_t b0 = sb + B_FULL5 + 8 * ns, p0 = (1 + (i + 2) / 6) & 1, b1 = sb + B_FULLA + 16 * ns + 8 * wg, p1 = ((i + 1) / 6) & 1;
        const bool here = i == 15 || mbar_test2(b0, p0, b1, p1);
        wg_wait<1>();
        if (!(((2 * REL + 1) >> i) & 1) && i < 14 && t < 2) mbar_arrive_remote(emptyb + 8 * ps, 1);
        if ((REL >> i) & 1) { wg_wait<0>(); if (t < 2) mbar_arrive_remote(emptyb + 8 * s, 1); }
        if (!here) mbar_wait2(b0, p0, b1, p1);
        ps = s; s = ns;
      }
    }
    cluster_arrive();
    float2 wr[16];
    #pragma unroll
    for (int i = 0; i < 16; i++) wr[i] = lds64f(sb + OFF_WR + 32 * i + 8 * q);
    const int r0 = 64 * wg + 16 * wp + g;
    float sum0, sum1, dot0, dot1, sq0, sq1;
    uint32_t redo = 0;
    asm volatile("" : "+r"(redo));
    #pragma unroll 1
    for (;;) {
    if (redo) {
      wg_wait<0>();
      const int r = r0;
      #pragma unroll 1
      for (int n = 0; n < 16; n++) {
        const uint32_t* xp = reinterpret_cast<const uint32_t*>(P.x + (size_t)(128 * m128 + r) * DM + 128 * j + 8 * n) + q;
        const uint32_t x0 = xp[0], x1 = xp[4 * DM];
        float d0 = bf_lo(x0), d1 = bf_hi(x0), d2 = bf_lo(x1), d3 = bf_hi(x1);
        #pragma unroll 1
        for (int ks = 0; ks < 64; ks++) {
          const int kb = ks >> 2, kk = 16 * (ks & 3);
          const bf16* op = G->o + (m128 * 16 + kb) * 8192 + r * 64 + 2 * q;
          const int o0 = ((kk >> 3) ^ g) << 3;
          const uint16_t* w = reinterpret_cast<const uint16_t*>(P.wo_p) + (size_t)(((kb & 1) ? 256 * (kb >> 2) + 32 * (kb & 2) + 32 + 4 * (kk & 32) : 64 * kb + 2 * (kk & 32)) + ((kk & 16) >> 2) + 8 * q) * DM + 128 * j + 8 * n + g;
          const uint32_t b0 = w[0] | (w[DM] << 16), b1 = w[2 * DM] | (w[3 * DM] << 16);
          uint32_t a0, a1, a2, a3, it = 0;
          do { a0 = ld32_rlx(op + o0); a1 = ld32_rlx(op + 512 + o0); a2 = ld32_rlx(op + (o0 ^ 8)); a3 = ld32_rlx(op + 512 + (o0 ^ 8)); }
          while (max(max(a0, a1), max(a2, a3)) == ~0u && ++it < POLL_LIMIT);
          __syncwarp();
          mma16816(d0, d1, d2, d3, a0, a1, a2, a3, b0, b1);
        }
        #pragma unroll
        for (int i = 0; i < 60; i++) h[i] = h[i + 4];
        h[60] = d0; h[61] = d1; h[62] = d2; h[63] = d3;
      }
    }
    wg_wait<0>();
    fence_regs(h);
    if (wg == 0) { TSW(16); }
    sum0 = 0.f, sum1 = 0.f, dot0 = 0.f, dot1 = 0.f, sq0 = 0.f, sq1 = 0.f;
    #pragma unroll
    for (int i = 0; i < 16; i++) {
      sum0 += h[4*i] + h[4*i+1]; sum1 += h[4*i+2] + h[4*i+3];
      sq0 = fmaf(h[4*i], h[4*i], fmaf(h[4*i+1], h[4*i+1], sq0)); sq1 = fmaf(h[4*i+2], h[4*i+2], fmaf(h[4*i+3], h[4*i+3], sq1));
      dot0 = fmaf(h[4*i], wr[i].x, fmaf(h[4*i+1], wr[i].y, dot0)); dot1 = fmaf(h[4*i+2], wr[i].x, fmaf(h[4*i+3], wr[i].y, dot1));
    }
    if (!__any_sync(~0u, !redo & (h[0] != h[0] | h[2] != h[2]))) break;
    redo = 1;
    }
    float4* const rs = &G->rstat[128 * m128 + r0];
    {
      const bool up = q & 2;
      float a = up ? sum1 : sum0, b = up ? sq1 : sq0, d = up ? dot1 : dot0;
      a += __shfl_xor_sync(~0u, up ? sum0 : sum1, 2); b += __shfl_xor_sync(~0u, up ? sq0 : sq1, 2); d += __shfl_xor_sync(~0u, up ? dot0 : dot1, 2);
      a += __shfl_xor_sync(~0u, a, 1); b += __shfl_xor_sync(~0u, b, 1); d += __shfl_xor_sync(~0u, d, 1);
      if ((q & 1) == 0) red_add_f32x4(rs + 4 * q, a, b, d, 1.f);
    }
    bar_arrive(NB_G2E, 384);
    if (wg == 0) { TSW(24); }
    bar_sync(NB_WG01, 256);
    uint32_t wa[8][4][4];
    const uint32_t wb = sb + 16384 * (((uint32_t)FF_SLOT >> (4 * warp)) & 15) + ((lane & 7) + ((lane >> 4) << 3)) * 64 + ((((lane >> 3) & 1) ^ ((lane >> 1) & 3)) << 4);
    auto getw = [&](int ks) {
      #pragma unroll
      for (int m = 0; m < 4; m++) ldsm4t((wb ^ ((m & 1) << 5)) + (m >> 1) * 8192 + ks * 1024, wa[ks][m][0], wa[ks][m][1], wa[ks][m][2], wa[ks][m][3]);
    };
    if (GPRE && f < NFFN_L) mbar_wait(sb + B_F + 8 * warp, 0);
    if (warp == 7) { TK(60); }
    #pragma unroll
    for (int ks = 0; ks < GPRE; ks++) getw(ks);
    float rstd[2], bm[2];
    uint32_t best;
    {
      const float2 swa = lds64f(sb + OFF_SUMWR), swb = lds64f(sb + OFF_SUMWR + 8);
      const float sw = (swa.x + swa.y) + (swb.x + swb.y);
      uint4 a[2]; uint32_t it = 0, key[2];
      do { a[0] = ld128_rlx(rs); a[1] = ld128_rlx(rs + 8); } while (__any_sync(~0u, (a[0].w & a[1].w) != 0x41000000u) && ++it < POLL_LIMIT);
      #pragma unroll
      for (int i = 0; i < 2; i++) {
        const float mean = __uint_as_float(a[i].x) * (1.f / DM);
        rstd[i] = rsqrtf(fmaxf(__uint_as_float(a[i].y) * (1.f / DM) - mean * mean, 0.f) + 1e-5f);
        bm[i] = -mean * rstd[i];
        const uint32_t rr = __float_as_uint(fmaf(__uint_as_float(a[i].z), rstd[i], sw * bm[i]));
        key[i] = ((rr ^ ((uint32_t)((int32_t)rr >> 31) | 0x80000000u)) & ~2047u) | (2047 - 128 * m128 - r0 - 8 * i);
      }
      asm volatile("redux.sync.max.u32 %0, %1, 0xffffffff;" : "=r"(best) : "r"(max(key[0], key[1])));
    }
    if (wg == 0) { TSW(17); }
    const int slot = m128 * 8 + warp, win = ~best & 15;
    if (lane < 4) st32_rlx(&G->key[(4 * j + lane) * 128 + slot], best);
    if ((win & 7) == g) {
      const bool up = win & 8;
      const float ra = up ? rstd[1] : rstd[0], rb = up ? bm[1] : bm[0];
      uint32_t x[16];
      #pragma unroll
      for (int i = 0; i < 16; i++) x[i] = pack_bf16(fmaf(up ? h[4*i+2] : h[4*i], ra, rb), fmaf(up ? h[4*i+3] : h[4*i+1], ra, rb));
      #pragma unroll
      for (int i = 0; i < 4; i++) st128_rlx(&G->cand[slot * DM + 64 * j + 16 * i + 4 * q], x[4*i], x[4*i+1], x[4*i+2], x[4*i+3]);
    }
    __syncwarp();
    if (wg == 0) { TSW(27); }
    {
      const float a0 = 1.f + rstd[0], b0 = bm[0], a1 = 1.f + rstd[1], b1 = bm[1];
      #pragma unroll
      for (int k = 0; k < 8; k++)
        stsm4(((sb + OFF_OUT + wg * 8192 + sa) ^ ((k & 3) << 5)) + (k >> 2) * 16384,
              pack_bf16(fmaf(h[8*k], a0, b0), fmaf(h[8*k+1], a0, b0)),     pack_bf16(fmaf(h[8*k+2], a1, b1), fmaf(h[8*k+3], a1, b1)),
              pack_bf16(fmaf(h[8*k+4], a0, b0), fmaf(h[8*k+5], a0, b0)),   pack_bf16(fmaf(h[8*k+6], a1, b1), fmaf(h[8*k+7], a1, b1)));
      sts32(sb + OFF_EXC + 4 * warp, 16 * warp + win);
      __syncwarp();
      if (lane == 0) mbar_arrive(sb + B_OUT + 8 * (warp >> 1));
      if (lane < 16) {
        const uint4 v = lds128(sb + OFF_OUT + (lane >> 3) * 16384 + (16 * warp + win) * 128 + (((lane & 7) ^ (win & 7)) << 4));
        st128_rlx(&G->cand[slot * DM + 512 + 64 * j + 4 * lane], v.x, v.y, v.z, v.w);
      }
    }
    if (wg == 0) { TSW(28); }
    {
      if (!GPRE && f < NFFN_L) mbar_wait(sb + B_F + 8 * warp, 0);
      #pragma unroll
      for (int ks = GPRE; ks < GRES; ks++) getw(ks);
      if (wg == 0) { TSW(15); }
      bar_sync(NB_XS, 384);
      if (wg == 0) { TSW(19); }
      uint4 xs[4];
      #pragma unroll
      for (int i = 0; i < 4; i++) xs[i] = lds128(sb + OFF_XSEL + 256 * warp + 64 * i + 16 * q);
      float d[4][4];
      #pragma unroll
      for (int ks = 0; ks < 8; ks++) {
        if (ks >= 1 && GRES + ks - 1 < 8) getw(GRES + ks - 1);
        #pragma unroll
        for (int m = 0; m < 4; m++) {
          if (ks == 0) { d[m][0] = 0.f; d[m][1] = 0.f; d[m][2] = 0.f; d[m][3] = 0.f; }
          mma16816(d[m][0], d[m][1], d[m][2], d[m][3], wa[ks][m][0], wa[ks][m][1], wa[ks][m][2], wa[ks][m][3],
                   (ks & 1) ? xs[ks >> 1].z : xs[ks >> 1].x, (ks & 1) ? xs[ks >> 1].w : xs[ks >> 1].y);
        }
      }
      if (q == 0) {
        #pragma unroll
        for (int m = 0; m < 8; m++) stsf(sb + OFF_GU + (8 * m + g) * 48 + 4 * warp, d[m >> 1][2 * (m & 1)]);
      }
      bar_arrive(NB_ACT, 384);
    }
    {
      float y0 = 0.f, y1 = 0.f, y2 = 0.f, y3 = 0.f;
      const uint32_t ky = __float_as_uint(ldsf(sb + OFF_KEY));
      const int kidx = 2047 - (ky & 2047);
      const float kr = __uint_as_float((ky & ~2047u) ^ ((ky >> 31) ? 0x80000000u : 0xfffff800u));
      const int col = 128 * (c >> 4) + 64 * (c & 1) + 32 * ((tid >> 2) & 1) + 16 * (tid & 1) + 8 * ((tid >> 1) & 1) + ((c >> 1) & 7);
      uint32_t it = 0, base = 0;
      if (tid < 8) {
        do { base = ld32_rlx(&G->cand[(kidx >> 4) * DM + 512 + (col >> 1)]); } while (base == ~0u && ++it < POLL_LIMIT);
      }
      if (tid < 2 * NFFN) {
        uint4 v;
        do { v = ld128_rlx(&G->ypart[(tid >> 1) * DM + 8 * c + 4 * (tid & 1)]); } while (v.w == ~0u && ++it < POLL_LIMIT);
        y0 = __uint_as_float(v.x); y1 = __uint_as_float(v.y); y2 = __uint_as_float(v.z); y3 = __uint_as_float(v.w);
      }
      __syncwarp();
      const bool b4 = lane & 16, b3 = lane & 8;
      const float u0 = (b4 ? y1 : y0) + __shfl_xor_sync(~0u, b4 ? y0 : y1, 16), u1 = (b4 ? y3 : y2) + __shfl_xor_sync(~0u, b4 ? y2 : y3, 16);
      float ys = (b3 ? u1 : u0) + __shfl_xor_sync(~0u, b3 ? u0 : u1, 8);
      ys += __shfl_xor_sync(~0u, ys, 4); ys += __shfl_xor_sync(~0u, ys, 2);
      if (!(lane & 6)) stsf(sb + OFF_ACT + ((4 * (lane & 1) + ((lane >> 3) & 1) * 2 + (lane >> 4)) * 8 + warp) * 4, ys);
      const float sg = __fdividef(1.f, 1.f + __expf(-kr));
      bar_sync(NB_WG01, 256);
      if (tid < 8) {
        const uint4 v0 = lds128(sb + OFF_ACT + tid * 32), v1 = lds128(sb + OFF_ACT + tid * 32 + 16);
        const float t8 = ((__uint_as_float(v0.x) + __uint_as_float(v0.y)) + (__uint_as_float(v0.z) + __uint_as_float(v0.w))) +
                         ((__uint_as_float(v1.x) + __uint_as_float(v1.y)) + __uint_as_float(v1.z));
        P.out_p[(size_t)kidx * DM + col] = __float2bfloat16(fmaf(t8, sg, (col & 1) ? bf_hi(base) : bf_lo(base)));
      }
      if (c == 0 && tid == 0) st32_rlx(&G->epoch, __float_as_uint(ldsf(sb + OFF_EP)));
      if (wg == 0) { TSW(22); TDUMP(); }
    }
  }
  if (wg == 2) {
    uint32_t wf[16][2][4];
    {
      const uint32_t wb = sb + OFF_S + 16384 * (wp & 1) + ((lane & 7) + ((lane >> 4) << 3)) * 128 + ((((lane >> 3) & 1) ^ (lane & 7)) << 4);
      if (f < NFFN_L) mbar_wait(sb + B_WD + 8 * wp, 0);
      if (wp == 0) { TK(61); }
      #pragma unroll
      for (int i = 0; i < 32; i++) ldsm4t((wb ^ (((i >> 1) & 3) << 5)) + (i >> 3) * 4096 + (i & 1) * 2048, wf[i >> 1][i & 1][0], wf[i >> 1][i & 1][1], wf[i >> 1][i & 1][2], wf[i >> 1][i & 1][3]);
      fence_async_smem();
      __syncwarp();
      if (lane == 0) mbar_arrive(sb + B_WC + 8 * wp);
      if (wp == 0) { TK(62); }
    }
    bar_sync(NB_G2E, 384);
    {
      uint32_t cur = 0;
      uint4 v;
      #pragma unroll 1
      for (uint32_t it = 0; it < POLL_LIMIT; it++) {
        const uint4 kx = ld128_rlx(&G->key[(c & 31) * 128 + 4 * lane]);
        v = ld128_rlx(&G->cand[((~cur >> 4) & 127) * DM + 4 * t]);
        uint32_t best;
        asm volatile("redux.sync.max.u32 %0, %1, 0xffffffff;" : "=r"(best) : "r"(max(max(kx.x, kx.y), max(kx.z, kx.w))));
        if (!__any_sync(~0u, min(min(kx.x, kx.y), min(kx.z, kx.w)) == 0 || v.w == ~0u) && best == cur) break;
        cur = best;
      }
      sts128(sb + OFF_XSEL + 16 * t, v.x, v.y, v.z, v.w);
      sts32(sb + OFF_KEY, cur);
      bar_arrive(NB_XS, 384);
      if (t == 0) mbar_arrive(sb + B_XS);
      TSW(18);
      bar_sync(NB_ACT, 384);
    }
    float gu[2];
    #pragma unroll
    for (int i = 0; i < 2; i++) {
      const uint4 v0 = lds128(sb + OFF_GU + (32 * i + lane) * 48), v1 = lds128(sb + OFF_GU + (32 * i + lane) * 48 + 16);
      gu[i] = ((__uint_as_float(v0.x) + __uint_as_float(v0.y)) + (__uint_as_float(v0.z) + __uint_as_float(v0.w))) +
              ((__uint_as_float(v1.x) + __uint_as_float(v1.y)) + (__uint_as_float(v1.z) + __uint_as_float(v1.w)));
    }
    const float act = gu[0] * gu[1] * rcp(1.f + ex2(-LOG2E * gu[0]));
    const uint32_t ap = pack_bf16(act, __shfl_down_sync(~0u, act, 1));
    uint32_t bf[4];
    #pragma unroll
    for (int i = 0; i < 4; i++) bf[i] = __shfl_sync(~0u, ap, 2 * q + 8 * i);
    TSW(20);
    float d[16][4];
    #pragma unroll
    for (int k = 0; k < 2; k++)
      #pragma unroll
      for (int i = 0; i < 16; i++) {
        if (k == 0) { d[i][0] = 0.f; d[i][1] = 0.f; d[i][2] = 0.f; d[i][3] = 0.f; }
        mma16816(d[i][0], d[i][1], d[i][2], d[i][3], wf[i][k][0], wf[i][k][1], wf[i][k][2], wf[i][k][3], bf[2*k], bf[2*k+1]);
      }
    #pragma unroll
    for (int a = 0; a < 2; a++) {
      float y[4];
      #pragma unroll
      for (int e = 0; e < 4; e++) {
        const int n = 8 * a + (e & 1);
        const float lo = (q & 1) ? d[n + 2][e & 2] : d[n][e & 2], hi = (q & 1) ? d[n + 6][e & 2] : d[n + 4][e & 2];
        y[e] = (q & 2) ? hi : lo;
      }
      if (f < NFFN) st128_rlx(&G->ypart[f * DM + 256 * wp + 128 * a + 4 * lane], __float_as_uint(y[0]), __float_as_uint(y[1]), __float_as_uint(y[2]), min(__float_as_uint(y[3]), ~1u));
    }
    TSW(21);
  }
  }
  cluster_wait();
}

typedef CUresult (*EncodeFn)(CUtensorMap*, CUtensorMapDataType, cuuint32_t, void*, const cuuint64_t*, const cuuint64_t*,
                             const cuuint32_t*, const cuuint32_t*, CUtensorMapInterleave, CUtensorMapSwizzle,
                             CUtensorMapL2promotion, CUtensorMapFloatOOBfill);

void make_map(EncodeFn enc, CUtensorMap* m, const void* p, int n, const cuuint64_t* dims, const cuuint64_t* str, const cuuint32_t* box,
              CUtensorMapSwizzle sw, CUtensorMapL2promotion promo) {
  cuuint32_t es[5] = {1, 1, 1, 1, 1};
  enc(m, CU_TENSOR_MAP_DATA_TYPE_BFLOAT16, n, const_cast<void*>(p), dims, str, box, es, CU_TENSOR_MAP_INTERLEAVE_NONE, sw, promo,
      CU_TENSOR_MAP_FLOAT_OOB_FILL_NONE);
}
void map2(EncodeFn enc, CUtensorMap* m, const void* p, uint64_t cols, uint64_t rows, uint32_t bc, uint32_t br, CUtensorMapSwizzle sw,
          CUtensorMapL2promotion promo) {
  const cuuint64_t dims[2] = {cols, rows}, str[1] = {cols * 2};
  const cuuint32_t box[2] = {bc, br};
  make_map(enc, m, p, 2, dims, str, box, sw, promo);
}
void map3(EncodeFn enc, CUtensorMap* m, const void* p, uint64_t cols, uint64_t rows, uint32_t br, uint32_t nb) {
  const cuuint64_t dims[3] = {64, rows, cols / 64}, str[2] = {cols * 2, 128};
  const cuuint32_t box[3] = {64, br, nb};
  make_map(enc, m, p, 3, dims, str, box, CU_TENSOR_MAP_SWIZZLE_128B, CU_TENSOR_MAP_L2_PROMOTION_L2_128B);
}

}

extern "C" void kernel_launch(void* const* d_in, const int* in_sizes, int n_in, void* d_out, int out_size) {
  (void)in_sizes; (void)n_in; (void)out_size;
  static EncodeFn enc = nullptr;
  static void* o_ptr = nullptr;
  if (!enc) {
    void* f = nullptr; cudaDriverEntryPointQueryResult qr;
    cudaGetDriverEntryPoint("cuTensorMapEncodeTiled", &f, cudaEnableDefault, &qr);
    enc = (EncodeFn)f;
    cudaGetSymbolAddress(&o_ptr, g_scr);
    cudaFuncSetAttribute(fused_kernel, cudaFuncAttributeMaxDynamicSharedMemorySize, SMEM_BYTES);
  }
  const bf16* x = (const bf16*)d_in[0];
  const bf16* wqkv = (const bf16*)d_in[1];
  const bf16* wphi = (const bf16*)d_in[2];
  const bf16* wo = (const bf16*)d_in[3];
  const bf16* wr = (const bf16*)d_in[5];
  const bf16* wgate = (const bf16*)d_in[6];
  const bf16* wup = (const bf16*)d_in[7];
  const bf16* wdown = (const bf16*)d_in[8];
  Params P;
  const CUtensorMapSwizzle S128 = CU_TENSOR_MAP_SWIZZLE_128B, S64 = CU_TENSOR_MAP_SWIZZLE_64B;
  const CUtensorMapL2promotion L128 = CU_TENSOR_MAP_L2_PROMOTION_L2_128B, L256 = CU_TENSOR_MAP_L2_PROMOTION_L2_256B,
                               L64 = CU_TENSOR_MAP_L2_PROMOTION_L2_64B;
  map2(enc, &P.x128, x, DM, SEQ, 64, 128, S128, L256);
  map2(enc, &P.x64, x, DM, SEQ, 64, 64, S128, L128);
  {
    const cuuint64_t dims[4] = {64, DM, 16, 3}, str[3] = {6 * DM, 128, 2 * DM};
    const cuuint32_t box[4] = {64, 64, 1, 2};
    make_map(enc, &P.wkv, wqkv, 4, dims, str, box, S128, L128);
  }
  map3(enc, &P.wq, wqkv, 3 * DM, DM, 64, 2);
  for (int i = 0; i < 2; i++) {
    const cuuint64_t dims[5] = {DM, (cuuint64_t)(DM - 94 - 64 * i), 4, 4, 2}, str[4] = {2 * DM, 16 * DM, 4 * DM, (cuuint64_t)(128 * DM) << i};
    const cuuint32_t box[5] = {64, 2, 4, 4, 2};
    make_map(enc, &P.wo[i], wo, 5, dims, str, box, S128, L128);
  }
  map3(enc, &P.wd, wdown, DM, FF, 32, 4);
  map2(enc, &P.wg, wgate, FF, DM, 32, 128, S64, L64);
  map2(enc, &P.wu, wup, FF, DM, 32, 128, S64, L64);
  map2(enc, &P.tg, wgate, FF, DM, 8, 16, CU_TENSOR_MAP_SWIZZLE_NONE, L128);
  map2(enc, &P.tu, wup, FF, DM, 8, 16, CU_TENSOR_MAP_SWIZZLE_NONE, L128);
  map2(enc, &P.td, wdown, 128, FF * 8, 8, 16, CU_TENSOR_MAP_SWIZZLE_NONE, L256);
  map2(enc, &P.xs, x, DM, SEQ, 128, 16, CU_TENSOR_MAP_SWIZZLE_NONE, L256);
  map2(enc, &P.ws, wqkv, 3 * DM, DM, 16, 128, CU_TENSOR_MAP_SWIZZLE_NONE, L128);
  map2(enc, &P.qs, wqkv, 3 * DM, DM, 32, 128, CU_TENSOR_MAP_SWIZZLE_NONE, L64);
  map2(enc, &P.phi, wphi, 32, 1024, 32, 32, S64, L64);
  P.x = x; P.wqkv = wqkv; P.wo_p = wo; P.wd_p = wdown; P.wg_p = wgate; P.wu_p = wup; P.wr = wr; P.out_p = (bf16*)d_out; P.g = (Scratch*)o_ptr; P.zero = 0;

  cudaLaunchConfig_t cfg = {};
  cfg.gridDim = dim3(128); cfg.blockDim = dim3(512); cfg.dynamicSmemBytes = SMEM_BYTES; cfg.stream = cudaStreamPerThread;
  cudaLaunchAttribute at[1];
  at[0].id = cudaLaunchAttributeClusterDimension; at[0].val.clusterDim.x = 2; at[0].val.clusterDim.y = 1; at[0].val.clusterDim.z = 1;
  cfg.attrs = at; cfg.numAttrs = 1;
  cudaLaunchKernelEx(&cfg, fused_kernel, P);
}
```

```cpp
#include <cuda_runtime.h>
#include <cuda.h>
#include <cuda_bf16.h>
#include <stdint.h>

namespace {

typedef __nv_bfloat16 bf16;

__device__ __forceinline__ uint32_t smem_u32(const void* p){ return (uint32_t)__cvta_generic_to_shared(p); }
__device__ __forceinline__ void mbar_init(uint32_t bar, uint32_t cnt){ asm volatile("mbarrier.init.shared::cta.b64 [%0], %1;"::"r"(bar),"r"(cnt):"memory"); }
__device__ __forceinline__ void mbar_expect_tx(uint32_t bar, uint32_t bytes){ asm volatile("mbarrier.arrive.expect_tx.shared::cta.b64 _, [%0], %1;"::"r"(bar),"r"(bytes):"memory"); }
__device__ __forceinline__ void mbar_arrive(uint32_t bar){ asm volatile("mbarrier.arrive.shared::cta.b64 _, [%0];"::"r"(bar):"memory"); }
__device__ __forceinline__ uint32_t mapa(uint32_t addr, uint32_t cta){ uint32_t r; asm volatile("mapa.shared::cluster.u32 %0, %1, %2;":"=r"(r):"r"(addr),"r"(cta)); return r; }
__device__ __forceinline__ void mbar_arrive_at(uint32_t bar, uint32_t cta, uint32_t cnt){
  asm volatile("{\n.reg .b32 ra;\nmapa.shared::cluster.u32 ra, %0, %1;\nmbarrier.arrive.shared::cluster.b64 _, [ra], %2;\n}\n"::"r"(bar),"r"(cta),"r"(cnt):"memory"); }
__device__ __forceinline__ void mbar_arrive_remote(uint32_t cluster_addr, uint32_t cnt){
  asm volatile("mbarrier.arrive.shared::cluster.b64 _, [%0], %1;"::"r"(cluster_addr),"r"(cnt):"memory"); }
__device__ __forceinline__ void mbar_wait(uint32_t bar, uint32_t parity){
  asm volatile("{\n.reg .pred p;\n.reg .u32 c;\nmov.u32 c, 0;\nLW:\nmbarrier.try_wait.parity.shared::cta.b64 p, [%0], %1;\n@p bra LD;\nadd.u32 c, c, 1;\nsetp.lt.u32 p, c, 2000000;\n@p bra LW;\ntrap;\nLD:\n}\n"::"r"(bar),"r"(parity):"memory"); }
__device__ __forceinline__ void mbar_wait2(uint32_t bar0, uint32_t par0, uint32_t bar1, uint32_t par1){
  asm volatile("{\n.reg .pred p, q;\n.reg .u32 c;\nmov.u32 c, 0;\nLW:\nmbarrier.try_wait.parity.shared::cta.b64 p, [%0], %1;\nmbarrier.try_wait.parity.shared::cta.b64 q, [%2], %3;\nand.pred p, p, q;\n@p bra LD;\nadd.u32 c, c, 1;\nsetp.lt.u32 p, c, 2000000;\n@p bra LW;\ntrap;\nLD:\n}\n"::"r"(bar0),"r"(par0),"r"(bar1),"r"(par1):"memory"); }
__device__ __forceinline__ bool mbar_test2(uint32_t bar0, uint32_t par0, uint32_t bar1, uint32_t par1){
  uint32_t r;
  asm volatile("{\n.reg .pred p, q;\nmbarrier.test_wait.parity.shared::cta.b64 p, [%1], %2;\nmbarrier.test_wait.parity.shared::cta.b64 q, [%3], %4;\nand.pred p, p, q;\nselp.u32 %0, 1, 0, p;\n}\n":"=r"(r):"r"(bar0),"r"(par0),"r"(bar1),"r"(par1):"memory");
  return r; }
__device__ __forceinline__ void tma_2d(uint32_t dst, const CUtensorMap* m, int c0, int c1, uint32_t bar){
  asm volatile("cp.async.bulk.tensor.2d.shared::cluster.global.mbarrier::complete_tx::bytes [%0], [%1, {%3, %4}], [%2];"::"r"(dst),"l"(m),"r"(bar),"r"(c0),"r"(c1):"memory"); }
__device__ __forceinline__ void tma_2d_mc(uint32_t dst, const CUtensorMap* m, int c0, int c1, uint32_t bar){
  asm volatile("cp.async.bulk.tensor.2d.shared::cluster.global.mbarrier::complete_tx::bytes.multicast::cluster [%0], [%1, {%3, %4}], [%2], %5;"::"r"(dst),"l"(m),"r"(bar),"r"(c0),"r"(c1),"h"((uint16_t)3):"memory"); }
__device__ __forceinline__ void tma_2d_mc_h(uint32_t dst, const CUtensorMap* m, int c0, int c1, uint32_t bar, uint64_t pol){
  asm volatile("cp.async.bulk.tensor.2d.shared::cluster.global.mbarrier::complete_tx::bytes.multicast::cluster.L2::cache_hint [%0], [%1, {%3, %4}], [%2], %5, %6;"::"r"(dst),"l"(m),"r"(bar),"r"(c0),"r"(c1),"h"((uint16_t)3),"l"(pol):"memory"); }
__device__ __forceinline__ void tma_4d(uint32_t dst, const CUtensorMap* m, int c0, int c1, int c2, int c3, uint32_t bar){
  asm volatile("cp.async.bulk.tensor.4d.shared::cluster.global.mbarrier::complete_tx::bytes [%0], [%1, {%3, %4, %5, %6}], [%2];"::"r"(dst),"l"(m),"r"(bar),"r"(c0),"r"(c1),"r"(c2),"r"(c3):"memory"); }
__device__ __forceinline__ uint64_t policy_evict_first(){ uint64_t p; asm volatile("createpolicy.fractional.L2::evict_first.b64 %0, 1.0;":"=l"(p)); return p; }
__device__ __forceinline__ uint64_t policy_evict_normal(){ uint64_t p; asm("createpolicy.fractional.L2::evict_normal.b64 %0, 1.0;":"=l"(p)); return p; }
__device__ __forceinline__ void tma_3d_h(uint32_t dst, const CUtensorMap* m, int c0, int c1, int c2, uint32_t bar, uint64_t pol){
  asm volatile("cp.async.bulk.tensor.3d.shared::cluster.global.mbarrier::complete_tx::bytes.L2::cache_hint [%0], [%1, {%3, %4, %5}], [%2], %6;"::"r"(dst),"l"(m),"r"(bar),"r"(c0),"r"(c1),"r"(c2),"l"(pol):"memory"); }
__device__ __forceinline__ void tma_4d_h(uint32_t dst, const CUtensorMap* m, int c0, int c1, int c2, int c3, uint32_t bar, uint64_t pol){
  asm volatile("cp.async.bulk.tensor.4d.shared::cluster.global.mbarrier::complete_tx::bytes.L2::cache_hint [%0], [%1, {%3, %4, %5, %6}], [%2], %7;"::"r"(dst),"l"(m),"r"(bar),"r"(c0),"r"(c1),"r"(c2),"r"(c3),"l"(pol):"memory"); }
__device__ __forceinline__ void red_add_f32x4(float4* p, float x, float y, float z, float w){ asm volatile("red.relaxed.gpu.global.add.v4.f32 [%0], {%1,%2,%3,%4};"::"l"(p),"f"(x),"f"(y),"f"(z),"f"(w):"memory"); }
__device__ __forceinline__ void tma_5d_h(uint32_t dst, const CUtensorMap* m, int c0, int c1, uint32_t bar, uint64_t pol){
  asm volatile("cp.async.bulk.tensor.5d.shared::cluster.global.mbarrier::complete_tx::bytes.L2::cache_hint [%0], [%1, {%3, %4, 0, 0, 0}], [%2], %5;"::"r"(dst),"l"(m),"r"(bar),"r"(c0),"r"(c1),"l"(pol):"memory"); }
__device__ __forceinline__ bool elect_one(){ uint32_t p; asm volatile("{\n.reg .pred P;\nelect.sync _|P, 0xffffffff;\nselp.b32 %0, 1, 0, P;\n}\n":"=r"(p)); return p; }
__device__ __forceinline__ void bulk_prefetch(const void* p, uint32_t bytes){
  asm volatile("cp.async.bulk.prefetch.L2.global [%0], %1;"::"l"(p),"r"(bytes):"memory"); }
__device__ __forceinline__ void bulk_s2peer(uint32_t dst_cluster, uint32_t src, uint32_t bytes, uint32_t bar_cluster){
  asm volatile("cp.async.bulk.shared::cluster.shared::cta.mbarrier::complete_tx::bytes [%0], [%1], %2, [%3];"::"r"(dst_cluster),"r"(src),"r"(bytes),"r"(bar_cluster):"memory"); }
__device__ __forceinline__ void bulk_g2s_mc(uint32_t dst, const void* src, uint32_t bytes, uint32_t bar, uint64_t pol){
  asm volatile("cp.async.bulk.shared::cluster.global.mbarrier::complete_tx::bytes.multicast::cluster.L2::cache_hint [%0], [%1], %2, [%3], %4, %5;"::"r"(dst),"l"(src),"r"(bytes),"r"(bar),"h"((uint16_t)3),"l"(pol):"memory"); }
__device__ __forceinline__ void prefetch_map(const CUtensorMap* m){ asm volatile("prefetch.tensormap [%0];"::"l"(m):"memory"); }
__device__ __forceinline__ void fence_async_smem(){ asm volatile("fence.proxy.async.shared::cta;":::"memory"); }
__device__ __forceinline__ void fence_acquire_gpu(){ asm volatile("fence.acquire.gpu;":::"memory"); }
__device__ __forceinline__ void fence_gpu(){ asm volatile("fence.acq_rel.gpu;":::"memory"); }
__device__ __forceinline__ void wg_fence(){ asm volatile("wgmma.fence.sync.aligned;":::"memory"); }
__device__ __forceinline__ void wg_commit(){ asm volatile("wgmma.commit_group.sync.aligned;":::"memory"); }
template<int N> __device__ __forceinline__ void wg_wait(){ asm volatile("wgmma.wait_group.sync.aligned %0;"::"n"(N):"memory"); }
template<int N> __device__ __forceinline__ void fence_regs(float (&d)[N]){
  #pragma unroll
  for(int i=0;i<N;i++) asm volatile("":"+f"(d[i])::"memory"); }
__device__ __forceinline__ void bar_sync(int id, int n){ asm volatile("bar.sync %0, %1;"::"r"(id),"r"(n):"memory"); }
__device__ __forceinline__ void bar_arrive(int id, int n){ asm volatile("bar.arrive %0, %1;"::"r"(id),"r"(n):"memory"); }
__device__ __forceinline__ void cluster_arrive(){ asm volatile("barrier.cluster.arrive.relaxed.aligned;":::"memory"); }
__device__ __forceinline__ void cluster_wait(){ asm volatile("barrier.cluster.wait.aligned;":::"memory"); }
__host__ __device__ constexpr uint32_t dlo(uint32_t addr, uint32_t lbo){ return (addr >> 4) | ((lbo >> 4) << 16); }
__host__ __device__ constexpr uint32_t dhi(uint32_t sbo, uint32_t sw){ return (sbo >> 4) | (sw << 30); }
constexpr uint32_t H128 = dhi(1024, 1), H64 = dhi(512, 2), H0 = dhi(128, 0);
__device__ __forceinline__ uint32_t pack_bf16(float lo, float hi){ uint32_t r; asm("cvt.rn.bf16x2.f32 %0, %1, %2;":"=r"(r):"f"(hi),"f"(lo)); return r; }
__device__ __forceinline__ float bf_lo(uint32_t v){ return __uint_as_float(v<<16); }
__device__ __forceinline__ float bf_hi(uint32_t v){ return __uint_as_float(v&0xffff0000u); }
__device__ __forceinline__ float ex2(float x){ float r; asm("ex2.approx.ftz.f32 %0, %1;":"=f"(r):"f"(x)); return r; }
__device__ __forceinline__ float rcp(float x){ float r; asm("rcp.approx.ftz.f32 %0, %1;":"=f"(r):"f"(x)); return r; }
__device__ __forceinline__ void stsm4(uint32_t addr, uint32_t a, uint32_t b, uint32_t c, uint32_t d){
  asm volatile("stmatrix.sync.aligned.m8n8.x4.shared.b16 [%0], {%1,%2,%3,%4};"::"r"(addr),"r"(a),"r"(b),"r"(c),"r"(d)); }
__device__ __forceinline__ void stsm2(uint32_t addr, uint32_t a, uint32_t b){
  asm volatile("stmatrix.sync.aligned.m8n8.x2.shared.b16 [%0], {%1,%2};"::"r"(addr),"r"(a),"r"(b)); }
__device__ __forceinline__ void mma16816(float& d0, float& d1, float& d2, float& d3, uint32_t a0, uint32_t a1, uint32_t a2, uint32_t a3, uint32_t b0, uint32_t b1){
  asm volatile("mma.sync.aligned.m16n8k16.row.col.f32.bf16.bf16.f32 {%0,%1,%2,%3}, {%4,%5,%6,%7}, {%8,%9}, {%0,%1,%2,%3};"
               : "+f"(d0), "+f"(d1), "+f"(d2), "+f"(d3) : "r"(a0), "r"(a1), "r"(a2), "r"(a3), "r"(b0), "r"(b1)); }
__device__ __forceinline__ void ldsm4(uint32_t addr, uint32_t& a, uint32_t& b, uint32_t& c, uint32_t& d){
  asm volatile("ldmatrix.sync.aligned.m8n8.x4.shared.b16 {%0,%1,%2,%3}, [%4];":"=r"(a),"=r"(b),"=r"(c),"=r"(d):"r"(addr):"memory"); }
__device__ __forceinline__ void ldsm4t(uint32_t addr, uint32_t& a, uint32_t& b, uint32_t& c, uint32_t& d){
  asm volatile("ldmatrix.sync.aligned.m8n8.x4.trans.shared.b16 {%0,%1,%2,%3}, [%4];":"=r"(a),"=r"(b),"=r"(c),"=r"(d):"r"(addr):"memory"); }
__device__ __forceinline__ void sts32(uint32_t a, uint32_t v){ asm volatile("st.shared.b32 [%0], %1;"::"r"(a),"r"(v):"memory"); }
__device__ __forceinline__ void stsf(uint32_t a, float v){ asm volatile("st.shared.f32 [%0], %1;"::"r"(a),"f"(v):"memory"); }
__device__ __forceinline__ void sts64(uint32_t a, uint32_t x, uint32_t y){ asm volatile("st.shared.v2.b32 [%0], {%1,%2};"::"r"(a),"r"(x),"r"(y):"memory"); }
__device__ __forceinline__ void sts128(uint32_t a, uint32_t x, uint32_t y, uint32_t z, uint32_t w){ asm volatile("st.shared.v4.b32 [%0], {%1,%2,%3,%4};"::"r"(a),"r"(x),"r"(y),"r"(z),"r"(w):"memory"); }
__device__ __forceinline__ float ldsf(uint32_t a){ float v; asm volatile("ld.shared.f32 %0, [%1];":"=f"(v):"r"(a):"memory"); return v; }
__device__ __forceinline__ float2 lds64f(uint32_t a){ float2 v; asm volatile("ld.shared.v2.f32 {%0,%1}, [%2];":"=f"(v.x),"=f"(v.y):"r"(a):"memory"); return v; }
__device__ __forceinline__ uint4 lds128(uint32_t a){ uint4 v; asm volatile("ld.shared.v4.u32 {%0,%1,%2,%3}, [%4];":"=r"(v.x),"=r"(v.y),"=r"(v.z),"=r"(v.w):"r"(a):"memory"); return v; }
__device__ __forceinline__ uint4 ld128_keep(const void* p){ uint4 v; asm volatile("ld.global.v4.u32 {%0,%1,%2,%3}, [%4];":"=r"(v.x),"=r"(v.y),"=r"(v.z),"=r"(v.w):"l"(p):"memory"); return v; }
__device__ __forceinline__ uint4 ld128_rlx(const void* p){ uint4 v; asm volatile("ld.relaxed.gpu.global.v4.u32 {%0,%1,%2,%3}, [%4];":"=r"(v.x),"=r"(v.y),"=r"(v.z),"=r"(v.w):"l"(p):"memory"); return v; }
__device__ __forceinline__ uint32_t ld32_rlx(const void* p){ uint32_t v; asm volatile("ld.relaxed.gpu.global.u32 %0, [%1];":"=r"(v):"l"(p):"memory"); return v; }
__device__ __forceinline__ void st128_rlx(void* p, uint32_t x, uint32_t y, uint32_t z, uint32_t w){ asm volatile("st.relaxed.gpu.global.v4.u32 [%0], {%1,%2,%3,%4};"::"l"(p),"r"(x),"r"(y),"r"(z),"r"(w):"memory"); }
__device__ __forceinline__ void st64_rlx(void* p, uint32_t x, uint32_t y){ asm volatile("st.relaxed.gpu.global.v2.u32 [%0], {%1,%2};"::"l"(p),"r"(x),"r"(y):"memory"); }
__device__ __forceinline__ void st32_rlx(void* p, uint32_t x){ asm volatile("st.relaxed.gpu.global.u32 [%0], %1;"::"l"(p),"r"(x):"memory"); }
__device__ __forceinline__ uint32_t tagw(float x, uint32_t t){ return (__float_as_uint(x) & ~3u) | t; }
__device__ __forceinline__ float untag(uint32_t w){ return __uint_as_float(w & ~3u); }

template<int TA, int TB, uint32_t HA, uint32_t HB> __device__ __forceinline__ void wgmma_ss_n128(float (&d)[64], uint32_t da, uint32_t db, int scale_d){
  asm volatile("{\n.reg .pred p;\n.reg .b64 a, b;\nsetp.ne.b32 p, %70, 0;\nmov.b64 a, {%64, %68};\nmov.b64 b, {%65, %69};\n"
  "wgmma.mma_async.sync.aligned.m64n128k16.f32.bf16.bf16 {%0, %1, %2, %3, %4, %5, %6, %7, %8, %9, %10, %11, %12, %13, %14, %15, %16, %17, %18, %19, %20, %21, %22, %23, %24, %25, %26, %27, %28, %29, %30, %31, %32, %33, %34, %35, %36, %37, %38, %39, %40, %41, %42, %43, %44, %45, %46, %47, %48, %49, %50, %51, %52, %53, %54, %55, %56, %57, %58, %59, %60, %61, %62, %63}, a, b, p, 1, 1, %66, %67;\n}\n"
  : "+f"(d[0]), "+f"(d[1]), "+f"(d[2]), "+f"(d[3]), "+f"(d[4]), "+f"(d[5]), "+f"(d[6]), "+f"(d[7]), "+f"(d[8]), "+f"(d[9]), "+f"(d[10]), "+f"(d[11]), "+f"(d[12]), "+f"(d[13]), "+f"(d[14]), "+f"(d[15]), "+f"(d[16]), "+f"(d[17]), "+f"(d[18]), "+f"(d[19]), "+f"(d[20]), "+f"(d[21]), "+f"(d[22]), "+f"(d[23]), "+f"(d[24]), "+f"(d[25]), "+f"(d[26]), "+f"(d[27]), "+f"(d[28]), "+f"(d[29]), "+f"(d[30]), "+f"(d[31]), "+f"(d[32]), "+f"(d[33]), "+f"(d[34]), "+f"(d[35]), "+f"(d[36]), "+f"(d[37]), "+f"(d[38]), "+f"(d[39]), "+f"(d[40]), "+f"(d[41]), "+f"(d[42]), "+f"(d[43]), "+f"(d[44]), "+f"(d[45]), "+f"(d[46]), "+f"(d[47]), "+f"(d[48]), "+f"(d[49]), "+f"(d[50]), "+f"(d[51]), "+f"(d[52]), "+f"(d[53]), "+f"(d[54]), "+f"(d[55]), "+f"(d[56]), "+f"(d[57]), "+f"(d[58]), "+f"(d[59]), "+f"(d[60]), "+f"(d[61]), "+f"(d[62]), "+f"(d[63])
  : "r"(da), "r"(db), "n"(TA), "n"(TB), "n"(HA), "n"(HB), "r"(scale_d));
}
template<int TA, int TB, uint32_t HA, uint32_t HB> __device__ __forceinline__ void wgmma_sa_n128(float (&d)[64], uint32_t da, uint32_t db){
  asm volatile("{\n.reg .pred p;\n.reg .b64 a, b;\nsetp.ne.b32 p, 1, 0;\nmov.b64 a, {%64, %68};\nmov.b64 b, {%65, %69};\n"
  "wgmma.mma_async.sync.aligned.m64n128k16.f32.bf16.bf16 {%0, %1, %2, %3, %4, %5, %6, %7, %8, %9, %10, %11, %12, %13, %14, %15, %16, %17, %18, %19, %20, %21, %22, %23, %24, %25, %26, %27, %28, %29, %30, %31, %32, %33, %34, %35, %36, %37, %38, %39, %40, %41, %42, %43, %44, %45, %46, %47, %48, %49, %50, %51, %52, %53, %54, %55, %56, %57, %58, %59, %60, %61, %62, %63}, a, b, p, 1, 1, %66, %67;\n}\n"
  : "+f"(d[0]), "+f"(d[1]), "+f"(d[2]), "+f"(d[3]), "+f"(d[4]), "+f"(d[5]), "+f"(d[6]), "+f"(d[7]), "+f"(d[8]), "+f"(d[9]), "+f"(d[10]), "+f"(d[11]), "+f"(d[12]), "+f"(d[13]), "+f"(d[14]), "+f"(d[15]), "+f"(d[16]), "+f"(d[17]), "+f"(d[18]), "+f"(d[19]), "+f"(d[20]), "+f"(d[21]), "+f"(d[22]), "+f"(d[23]), "+f"(d[24]), "+f"(d[25]), "+f"(d[26]), "+f"(d[27]), "+f"(d[28]), "+f"(d[29]), "+f"(d[30]), "+f"(d[31]), "+f"(d[32]), "+f"(d[33]), "+f"(d[34]), "+f"(d[35]), "+f"(d[36]), "+f"(d[37]), "+f"(d[38]), "+f"(d[39]), "+f"(d[40]), "+f"(d[41]), "+f"(d[42]), "+f"(d[43]), "+f"(d[44]), "+f"(d[45]), "+f"(d[46]), "+f"(d[47]), "+f"(d[48]), "+f"(d[49]), "+f"(d[50]), "+f"(d[51]), "+f"(d[52]), "+f"(d[53]), "+f"(d[54]), "+f"(d[55]), "+f"(d[56]), "+f"(d[57]), "+f"(d[58]), "+f"(d[59]), "+f"(d[60]), "+f"(d[61]), "+f"(d[62]), "+f"(d[63])
  : "r"(da), "r"(db), "n"(TA), "n"(TB), "n"(HA), "n"(HB));
}
template<int TA, int TB, uint32_t HA, uint32_t HB> __device__ __forceinline__ void wgmma_sa_n40(float (&d)[20], uint32_t da, uint32_t db){
  asm volatile("{\n.reg .pred p;\n.reg .b64 a, b;\nsetp.ne.b32 p, 1, 0;\nmov.b64 a, {%20, %24};\nmov.b64 b, {%21, %25};\n"
  "wgmma.mma_async.sync.aligned.m64n40k16.f32.bf16.bf16 {%0, %1, %2, %3, %4, %5, %6, %7, %8, %9, %10, %11, %12, %13, %14, %15, %16, %17, %18, %19}, a, b, p, 1, 1, %22, %23;\n}\n"
  : "+f"(d[0]), "+f"(d[1]), "+f"(d[2]), "+f"(d[3]), "+f"(d[4]), "+f"(d[5]), "+f"(d[6]), "+f"(d[7]), "+f"(d[8]), "+f"(d[9]), "+f"(d[10]), "+f"(d[11]), "+f"(d[12]), "+f"(d[13]), "+f"(d[14]), "+f"(d[15]), "+f"(d[16]), "+f"(d[17]), "+f"(d[18]), "+f"(d[19])
  : "r"(da), "r"(db), "n"(TA), "n"(TB), "n"(HA), "n"(HB));
}
template<int TA, int TB, uint32_t HA, uint32_t HB> __device__ __forceinline__ void wgmma_sz_n40(float (&d)[20], uint32_t da, uint32_t db){
  asm volatile("{\n.reg .pred p;\n.reg .b64 a, b;\nsetp.ne.b32 p, 0, 0;\nmov.b64 a, {%20, %24};\nmov.b64 b, {%21, %25};\n"
  "wgmma.mma_async.sync.aligned.m64n40k16.f32.bf16.bf16 {%0, %1, %2, %3, %4, %5, %6, %7, %8, %9, %10, %11, %12, %13, %14, %15, %16, %17, %18, %19}, a, b, p, 1, 1, %22, %23;\n}\n"
  : "=f"(d[0]), "=f"(d[1]), "=f"(d[2]), "=f"(d[3]), "=f"(d[4]), "=f"(d[5]), "=f"(d[6]), "=f"(d[7]), "=f"(d[8]), "=f"(d[9]), "=f"(d[10]), "=f"(d[11]), "=f"(d[12]), "=f"(d[13]), "=f"(d[14]), "=f"(d[15]), "=f"(d[16]), "=f"(d[17]), "=f"(d[18]), "=f"(d[19])
  : "r"(da), "r"(db), "n"(TA), "n"(TB), "n"(HA), "n"(HB));
}
template<int TA, int TB, uint32_t HA, uint32_t HB> __device__ __forceinline__ void wgmma_sa_n32(float (&d)[16], uint32_t da, uint32_t db){
  asm volatile("{\n.reg .pred p;\n.reg .b64 a, b;\nsetp.ne.b32 p, 1, 0;\nmov.b64 a, {%16, %20};\nmov.b64 b, {%17, %21};\n"
  "wgmma.mma_async.sync.aligned.m64n32k16.f32.bf16.bf16 {%0, %1, %2, %3, %4, %5, %6, %7, %8, %9, %10, %11, %12, %13, %14, %15}, a, b, p, 1, 1, %18, %19;\n}\n"
  : "+f"(d[0]), "+f"(d[1]), "+f"(d[2]), "+f"(d[3]), "+f"(d[4]), "+f"(d[5]), "+f"(d[6]), "+f"(d[7]), "+f"(d[8]), "+f"(d[9]), "+f"(d[10]), "+f"(d[11]), "+f"(d[12]), "+f"(d[13]), "+f"(d[14]), "+f"(d[15])
  : "r"(da), "r"(db), "n"(TA), "n"(TB), "n"(HA), "n"(HB));
}
template<int TA, int TB, uint32_t HA, uint32_t HB> __device__ __forceinline__ void wgmma_ss_n32(float (&d)[16], uint32_t da, uint32_t db, int scale_d){
  asm volatile("{\n.reg .pred p;\n.reg .b64 a, b;\nsetp.ne.b32 p, %22, 0;\nmov.b64 a, {%16, %20};\nmov.b64 b, {%17, %21};\n"
  "wgmma.mma_async.sync.aligned.m64n32k16.f32.bf16.bf16 {%0, %1, %2, %3, %4, %5, %6, %7, %8, %9, %10, %11, %12, %13, %14, %15}, a, b, p, 1, 1, %18, %19;\n}\n"
  : "+f"(d[0]), "+f"(d[1]), "+f"(d[2]), "+f"(d[3]), "+f"(d[4]), "+f"(d[5]), "+f"(d[6]), "+f"(d[7]), "+f"(d[8]), "+f"(d[9]), "+f"(d[10]), "+f"(d[11]), "+f"(d[12]), "+f"(d[13]), "+f"(d[14]), "+f"(d[15])
  : "r"(da), "r"(db), "n"(TA), "n"(TB), "n"(HA), "n"(HB), "r"(scale_d));
}
template<int TB, uint32_t HB> __device__ __forceinline__ void wgmma_ra_n32(float (&d)[16], uint32_t a0, uint32_t a1, uint32_t a2, uint32_t a3, uint32_t db){
  asm volatile("{\n.reg .pred p;\n.reg .b64 a, b;\nsetp.ne.b32 p, 1, 0;\nmov.b64 b, {%20, %22};\n"
  "wgmma.mma_async.sync.aligned.m64n32k16.f32.bf16.bf16 {%0, %1, %2, %3, %4, %5, %6, %7, %8, %9, %10, %11, %12, %13, %14, %15}, {%16,%17,%18,%19}, b, p, 1, 1, %21;\n}\n"
  : "+f"(d[0]), "+f"(d[1]), "+f"(d[2]), "+f"(d[3]), "+f"(d[4]), "+f"(d[5]), "+f"(d[6]), "+f"(d[7]), "+f"(d[8]), "+f"(d[9]), "+f"(d[10]), "+f"(d[11]), "+f"(d[12]), "+f"(d[13]), "+f"(d[14]), "+f"(d[15])
  : "r"(a0), "r"(a1), "r"(a2), "r"(a3), "r"(db), "n"(TB), "n"(HB));
}
template<int TB, uint32_t HB> __device__ __forceinline__ void wgmma_rs_n32(float (&d)[16], uint32_t a0, uint32_t a1, uint32_t a2, uint32_t a3, uint32_t db, int scale_d){
  asm volatile("{\n.reg .pred p;\n.reg .b64 a, b;\nsetp.ne.b32 p, %23, 0;\nmov.b64 b, {%20, %22};\n"
  "wgmma.mma_async.sync.aligned.m64n32k16.f32.bf16.bf16 {%0, %1, %2, %3, %4, %5, %6, %7, %8, %9, %10, %11, %12, %13, %14, %15}, {%16,%17,%18,%19}, b, p, 1, 1, %21;\n}\n"
  : "+f"(d[0]), "+f"(d[1]), "+f"(d[2]), "+f"(d[3]), "+f"(d[4]), "+f"(d[5]), "+f"(d[6]), "+f"(d[7]), "+f"(d[8]), "+f"(d[9]), "+f"(d[10]), "+f"(d[11]), "+f"(d[12]), "+f"(d[13]), "+f"(d[14]), "+f"(d[15])
  : "r"(a0), "r"(a1), "r"(a2), "r"(a3), "r"(db), "n"(TB), "n"(HB), "r"(scale_d));
}
template<int TB, uint32_t HB> __device__ __forceinline__ void wgmma_ra_n40(float (&d)[20], uint32_t a0, uint32_t a1, uint32_t a2, uint32_t a3, uint32_t db){
  asm volatile("{\n.reg .pred p;\n.reg .b64 a, b;\nsetp.ne.b32 p, 1, 0;\nmov.b64 b, {%24, %26};\n"
  "wgmma.mma_async.sync.aligned.m64n40k16.f32.bf16.bf16 {%0, %1, %2, %3, %4, %5, %6, %7, %8, %9, %10, %11, %12, %13, %14, %15, %16, %17, %18, %19}, {%20,%21,%22,%23}, b, p, 1, 1, %25;\n}\n"
  : "+f"(d[0]), "+f"(d[1]), "+f"(d[2]), "+f"(d[3]), "+f"(d[4]), "+f"(d[5]), "+f"(d[6]), "+f"(d[7]), "+f"(d[8]), "+f"(d[9]), "+f"(d[10]), "+f"(d[11]), "+f"(d[12]), "+f"(d[13]), "+f"(d[14]), "+f"(d[15]), "+f"(d[16]), "+f"(d[17]), "+f"(d[18]), "+f"(d[19])
  : "r"(a0), "r"(a1), "r"(a2), "r"(a3), "r"(db), "n"(TB), "n"(HB));
}
template<int TB, uint32_t HB> __device__ __forceinline__ void wgmma_rz_n40(float (&d)[20], uint32_t a0, uint32_t a1, uint32_t a2, uint32_t a3, uint32_t db){
  asm volatile("{\n.reg .pred p;\n.reg .b64 a, b;\nsetp.ne.b32 p, 0, 0;\nmov.b64 b, {%24, %26};\n"
  "wgmma.mma_async.sync.aligned.m64n40k16.f32.bf16.bf16 {%0, %1, %2, %3, %4, %5, %6, %7, %8, %9, %10, %11, %12, %13, %14, %15, %16, %17, %18, %19}, {%20,%21,%22,%23}, b, p, 1, 1, %25;\n}\n"
  : "=f"(d[0]), "=f"(d[1]), "=f"(d[2]), "=f"(d[3]), "=f"(d[4]), "=f"(d[5]), "=f"(d[6]), "=f"(d[7]), "=f"(d[8]), "=f"(d[9]), "=f"(d[10]), "=f"(d[11]), "=f"(d[12]), "=f"(d[13]), "=f"(d[14]), "=f"(d[15]), "=f"(d[16]), "=f"(d[17]), "=f"(d[18]), "=f"(d[19])
  : "r"(a0), "r"(a1), "r"(a2), "r"(a3), "r"(db), "n"(TB), "n"(HB));
}
template<int TB, uint32_t HB> __device__ __forceinline__ void wgmma_ra_n8(float (&d)[4], uint32_t a0, uint32_t a1, uint32_t a2, uint32_t a3, uint32_t db){
  asm volatile("{\n.reg .pred p;\n.reg .b64 a, b;\nsetp.ne.b32 p, 1, 0;\nmov.b64 b, {%8, %10};\n"
  "wgmma.mma_async.sync.aligned.m64n8k16.f32.bf16.bf16 {%0, %1, %2, %3}, {%4,%5,%6,%7}, b, p, 1, 1, %9;\n}\n"
  : "+f"(d[0]), "+f"(d[1]), "+f"(d[2]), "+f"(d[3])
  : "r"(a0), "r"(a1), "r"(a2), "r"(a3), "r"(db), "n"(TB), "n"(HB));
}
template<int TB, uint32_t HB> __device__ __forceinline__ void wgmma_rz_n8(float (&d)[4], uint32_t a0, uint32_t a1, uint32_t a2, uint32_t a3, uint32_t db){
  asm volatile("{\n.reg .pred p;\n.reg .b64 a, b;\nsetp.ne.b32 p, 0, 0;\nmov.b64 b, {%8, %10};\n"
  "wgmma.mma_async.sync.aligned.m64n8k16.f32.bf16.bf16 {%0, %1, %2, %3}, {%4,%5,%6,%7}, b, p, 1, 1, %9;\n}\n"
  : "=f"(d[0]), "=f"(d[1]), "=f"(d[2]), "=f"(d[3])
  : "r"(a0), "r"(a1), "r"(a2), "r"(a3), "r"(db), "n"(TB), "n"(HB));
}

constexpr int SEQ = 2048, DM = 1024, FF = 3584;
constexpr float LOG2E = 1.4426950408889634f;
constexpr uint32_t POLL_LIMIT = 1u << 22;
#define NPRE0 1
#define NPREN 2
constexpr int NPRE = NPREN;
#define QW 0
#define RS_N 22
#define RS_D1 430
#define RS_D2 300
#define SKM 0x154
#define LAG 2
#define PF_T0 5000
#define PF_DT 800
#define NFFN_L NFFN
#define FF_DT 500
#define OUT_U 1
#define GRES 8
#define OUT_L 0
#define TMASK 0xffffff
#define PMASK 0xffffff
#define FF_T0 400
#define GPRE 0
#define REL 6
#define EFI 11
#define TKW 8
#define SLOT 0
#define SLOTW 48
#define FF_ORD 0x76543210ba98ull
#define KT 0
#define KK(id) do { if (KT) { TK(32 * wg + (id)); } } while (0)
#define PF_I0 0
#define PF_ST 7
#define PRCP 1
#define TRKL 1
#define YR 4
#define OUT_NS 60
constexpr int NFFN = 112;

constexpr uint32_t SB0 = 1024;
constexpr uint32_t KV_STAGE = 49152, R5 = 32768;
constexpr uint32_t OFF_X = 163840, OFF_S = 196608, OFF_WPHI = OFF_S + 20480, OFF_M = 229376, SMEM_BYTES = 232448;
constexpr uint32_t OFF_RS256 = 212992, OFF_ONES = OFF_RS256 + 1024, OFF_WPHIK1 = OFF_ONES + 1024, OFF_KVZ = OFF_S;
constexpr uint32_t OFF_WPHIK = OFF_S, OFF_BXK = OFF_S + 2048, OFF_AXK = OFF_S + 4096, OFF_G = OFF_S + 8192;
constexpr uint32_t OFF_AXQ = OFF_WPHI, OFF_BXQ = OFF_WPHI + 2048, OFF_WPHIQ = OFF_WPHI + 4096;
constexpr uint32_t B_FULLKV = OFF_M  , B_EMPTYKV = OFF_M + 32  ;
constexpr uint32_t B_EMPTY5 = OFF_M + 64  , B_UO = B_EMPTY5 + 48  , B_RC = B_UO + 32  ;
constexpr uint32_t B_OUT = B_RC + 16  , B_AUX = B_OUT + 32, B_AUXQ = B_AUX + 8, B_RX = B_AUXQ + 8;
constexpr uint32_t B_FULL5 = B_RX + 8  , B_FULLA = B_FULL5 + 48  , B_F = B_FULLA + 96  , B_WD = B_F + 64  ;
constexpr uint32_t B_WC = B_WD + 32  , B_DR = B_WC + 32  , B_W = B_DR + 24, B_OS = B_W + 8, B_R = B_W + 16, B_KD = B_W + 24, B_XS = B_W + 32, B_T = B_W + 40, B_G = B_W + 48, B_END = B_W + 56, B_S0 = B_END;
static_assert(B_S0 < OFF_M + 576 && B_END <= OFF_M + 568 && B_FULL5 + 40 >= OFF_M + 200 && B_FULL5 + 40 < OFF_M + 384, "barriers");
constexpr uint32_t OFF_EXC = OFF_M + 576, OFF_SUMWR = OFF_M + 608, OFF_EP = OFF_M + 624, OFF_KEY = OFF_M + 628;
constexpr uint32_t OFF_RSQ = OFF_M + 640, OFF_TL = OFF_M + 1152, OFF_T = OFF_M + 1792, OFF_WR = OFF_M + 2048, OFF_SCR = OFF_M + 2432;
constexpr uint32_t OFF_XSEL = 2 * R5, OFF_GU = OFF_XSEL + 4096, OFF_OUT = 3 * R5;
constexpr uint64_t FF_SLOT = 0xdcdc3210dcbaull;
constexpr int KVP = 6 * 128;

enum { NB_G2E = 1, NB_XS = 2, NB_WG01 = 3, NB_ACT = 4, NB_Q0 = 5  , NB_ST = 14, NB_DN = 9, NB_ZERO = 10, NB_PUB = 11, NB_TOK = 10  , NB_L0 = 12  , NB_WG2 = 7, NB_QGO = 15 };

struct Scratch {
  bf16     o[SEQ * DM];
  float4   rstat[SEQ];
  uint32_t key[32 * 128];
  uint32_t cand[128 * DM];
  float4   yacc[YR * 3 * 128];
  float4   kvacc[32 * KVP];
  uint2    stats[SEQ];
  uint32_t cskv[2 * DM];
  uint32_t csq[4 * DM];
  uint32_t oset[128 * 16];
  uint32_t epoch;
};
__device__ __align__(1024) Scratch g_scr;
#define TS(id)
#define TDUMP()
#define TS0_DECL()
#define TS0_READ()
#define TS0_WRITE()
#define TK(id)
#define TSW(id)

struct Params {
  CUtensorMap x128, x64, wkv, wq, wo[2], wd, wg, wu, phi, tg, tu, td, xs, ws, qs;
  const bf16 *x, *wqkv, *wo_p, *wg_p, *wu_p, *wd_p, *wr;
  bf16* out_p;
  Scratch* g;
  uint32_t zero;
};

constexpr float EXP_LIM = 1.1529215e18f, ARG_LIM2 = 3600.f;
__device__ __forceinline__ void dual_exp2(const float (&p)[2][16], uint32_t (&ph)[4][8]) {
  #pragma unroll
  for (int h = 0; h < 2; h++)
    #pragma unroll
    for (int k = 0; k < 8; k++) { ph[2*h][k] = pack_bf16(ex2(p[h][2*k]), ex2(p[h][2*k+1])); ph[2*h+1][k] = pack_bf16(ex2(-p[h][2*k]), ex2(-p[h][2*k+1])); }
}
__device__ __forceinline__ void dual_exp2_shifted(const float (&pp)[2][16], uint32_t (&ph)[4][8]) {
  #pragma unroll
  for (int h = 0; h < 2; h++) {
    const float* p = pp[h];
    float m[4] = {p[0], p[2], p[0], p[2]};
    #pragma unroll
    for (int i = 0; i < 16; i++) { m[(i >> 1) & 1] = fmaxf(m[(i >> 1) & 1], p[i]); m[2 + ((i >> 1) & 1)] = fminf(m[2 + ((i >> 1) & 1)], p[i]); }
    #pragma unroll
    for (int o = 1; o < 4; o <<= 1) {
      m[0] = fmaxf(m[0], __shfl_xor_sync(~0u, m[0], o)); m[1] = fmaxf(m[1], __shfl_xor_sync(~0u, m[1], o));
      m[2] = fminf(m[2], __shfl_xor_sync(~0u, m[2], o)); m[3] = fminf(m[3], __shfl_xor_sync(~0u, m[3], o));
    }
    #pragma unroll
    for (int k = 0; k < 8; k++) {
      ph[2*h][k] = pack_bf16(ex2(p[2*k] - m[k & 1]), ex2(p[2*k+1] - m[k & 1]));
      ph[2*h+1][k] = pack_bf16(ex2(m[2 + (k & 1)] - p[2*k]), ex2(m[2 + (k & 1)] - p[2*k+1]));
    }
  }
}
__device__ __forceinline__ void row_sums(float (&s)[4][4], const uint32_t (&ph)[4][8], uint32_t ones) {
  #pragma unroll
  for (int i = 0; i < 4; i++) wgmma_rz_n8<0, H0>(s[i], ph[i][0], ph[i][1], ph[i][2], ph[i][3], ones);
  #pragma unroll
  for (int i = 0; i < 4; i++) wgmma_ra_n8<0, H0>(s[i], ph[i][4], ph[i][5], ph[i][6], ph[i][7], ones);
}
__device__ __forceinline__ uint32_t mul_bf16x2(uint32_t a, uint32_t b) { uint32_t r; asm("mul.rn.bf16x2 %0, %1, %2;" : "=r"(r) : "r"(a), "r"(b)); return r; }
__device__ __forceinline__ void normalize(uint32_t (&ph)[4][8], const float (&s)[4][4]) {
  #pragma unroll
  for (int i = 0; i < 4; i++) {
    const float i0 = rcp(s[i][0]), i1 = rcp(s[i][2]);
    const uint32_t n0 = pack_bf16(i0, i0), n1 = pack_bf16(i1, i1);
    #pragma unroll
    for (int k = 0; k < 4; k++) { ph[i][2*k] = mul_bf16x2(ph[i][2*k], n0); ph[i][2*k+1] = mul_bf16x2(ph[i][2*k+1], n1); }
  }
}
__device__ __forceinline__ void split_bf16(float a, float b, uint32_t& hi, uint32_t& lo) { hi = pack_bf16(a, b); lo = pack_bf16(a - bf_lo(hi), b - bf_hi(hi)); }
__device__ __forceinline__ void put_colsums(uint32_t base, int lane, float a, float b, float c, float d) {
  uint32_t h0, l0, h1, l1;
  split_bf16(a, b, h0, l0); split_bf16(c, d, h1, l1);
  const uint32_t ad = base + (lane >> 1) * 128 + (lane & 1) * 8;
  sts64(ad, h0, h1); sts64(ad + 16, l0, l1); sts64(ad + 32, h0, h1); sts64(ad + 48, l0, l1);
  sts128(base + (lane >> 1) * 128 + 64 + (lane & 1) * 32, 0, 0, 0, 0); sts128(base + (lane >> 1) * 128 + 80 + (lane & 1) * 32, 0, 0, 0, 0);
}
__device__ __forceinline__ float reduce8(const float (&v)[8], int lane) {
  const bool b4 = lane & 16, b3 = lane & 8, b2 = lane & 4;
  float a[4], b[2];
  #pragma unroll
  for (int i = 0; i < 4; i++) a[i] = (b4 ? v[4 + i] : v[i]) + __shfl_xor_sync(~0u, b4 ? v[i] : v[4 + i], 16);
  #pragma unroll
  for (int i = 0; i < 2; i++) b[i] = (b3 ? a[2 + i] : a[i]) + __shfl_xor_sync(~0u, b3 ? a[i] : a[2 + i], 8);
  return (b2 ? b[1] : b[0]) + __shfl_xor_sync(~0u, b2 ? b[0] : b[1], 4);
}
__device__ __forceinline__ bool tag_bad(uint4 v, uint32_t tg) { return (((v.x ^ tg) | (v.y ^ tg) | (v.z ^ tg) | (v.w ^ tg)) & 3) != 0; }

__global__ void __launch_bounds__(512, 1) fused_kernel(const __grid_constant__ Params P) {
  extern __shared__ __align__(1024) uint8_t smem_raw[];
  const uint32_t sb = smem_u32(smem_raw);
  const int tid = threadIdx.x, lane = tid & 31;
  TS0_DECL();
  TS0_READ();
  if (tid == 352) { prefetch_map(&P.wkv); prefetch_map(&P.x128); }
  const int cp = blockIdx.x >> 1, rank = blockIdx.x & 1;
  const int cr = cp < 4 ? 32 + 8 * cp : cp - 4 + max((cp * 37 - 1076) >> 8, 0);
  const int c = (cr & 62) + 64 * (cr & 1) + rank;
  const int m256 = c >> 4, nkv = c & 15, m128 = c >> 3, j = c & 7;
  if ((tid >> 5) == 12 && elect_one()) {
    mbar_init(sb + B_S0, 1); mbar_init(sb + B_FULLKV, 1); mbar_init(sb + B_FULLKV + 8, 1);
    fence_async_smem();
    mbar_expect_tx(sb + B_S0, 32768);
    tma_4d(sb + 32768, &P.wkv, 0, 0, nkv, 1, sb + B_S0);
    tma_2d(sb, &P.x128, 0, 256 * m256, sb + B_S0);
    mbar_expect_tx(sb + B_FULLKV, 16384);
    tma_2d(sb + 16384, &P.x128, 0, 256 * m256 + 128, sb + B_FULLKV);
    if (NPRE0 > 1) {
      mbar_expect_tx(sb + B_FULLKV + 8, KV_STAGE);
      tma_4d(sb + KV_STAGE + 32768, &P.wkv, 0, 64, nkv, 1, sb + B_FULLKV + 8);
      tma_2d(sb + KV_STAGE, &P.x128, 64, 256 * m256, sb + B_FULLKV + 8);
      tma_2d(sb + KV_STAGE + 16384, &P.x128, 64, 256 * m256 + 128, sb + B_FULLKV + 8);
    }
    asm volatile("fence.mbarrier_init.release.cluster;" ::: "memory");
  }
  #pragma unroll
  for (int w = 0; w < 3; w++)
    if (tid == 32 + 32 * w) {
      #pragma unroll
      for (uint32_t b = B_FULLKV + 16 + 184 * w; b < B_FULLKV + 200 + 184 * w && b < B_END; b += 8)
        mbar_init(sb + b, b < B_EMPTYKV ? 1 : b < B_EMPTY5 ? 12 : b < B_OUT ? 4 : b < B_RX || b == B_W ? 2 : b == B_RX ? 8 : 1);
      if (w == 1) mbar_arrive(sb + B_FULL5 + 40);
      asm volatile("fence.mbarrier_init.release.cluster;" ::: "memory");
      fence_async_smem();
    }
  const int warp = __shfl_sync(~0u, tid >> 5, 0), wg = warp >> 2, wp = warp & 3;
  const int f = 16 * ((cr + 7) & 7) + 2 * (cr >> 3) + rank;
  const int ha = 4 * (nkv >> 1) + (nkv & 1);
  Scratch* const G = P.g;
  if ((sb & 0x3ffff) != SB0) asm volatile("trap;");
  __syncthreads();
  cluster_arrive();
  if (warp == 12) {
    TK(88 - 32);
    if (elect_one()) {
      #pragma unroll
      for (int s = NPRE0; s < NPRE; s++) {
        const uint32_t st = sb + s * KV_STAGE, fb = sb + B_FULLKV + 8 * s;
        mbar_expect_tx(fb, KV_STAGE);
        tma_4d(st + 32768, &P.wkv, 0, 64 * s, nkv, 1, fb);
        tma_2d(st, &P.x128, 64 * s, 256 * m256, fb);
        tma_2d(st + 16384, &P.x128, 64 * s, 256 * m256 + 128, fb);
      }
    }
    __syncwarp();
  }

  if (wg == 3) {
    asm volatile("setmaxnreg.dec.sync.aligned.u32 32;");
    cluster_wait();
    if (wp == 0) { TK(89 - 32); }
    const bool el = elect_one();
    const uint64_t ef = policy_evict_first(), en = policy_evict_normal();
    auto fetch_o = [&](const int t0, uint32_t so, uint32_t par) {
      const int sh = t0 & 1;
      uint32_t ready = 0;
      const bf16* base = G->o + (m128 * 16 + t0) * 8192 + rank * 4096;
      const bf16* hint = base + (lane & 3) * 1024 + 966 + (((j & 6) + ((lane >> 2) & ~sh)) & 7) * 16384 + 8 * sh * (~lane & 4);
      #pragma unroll 1
      for (int i = 2 - 2 * sh; i < 8; i += 1 + sh) {
        uint32_t it = 0;
        while ((~ready >> (4 * i) & (15 + 240 * sh)) && ++it < POLL_LIMIT) ready = __ballot_sync(~0u, ld32_rlx(hint) != ~0u);
        mbar_wait(sb + B_EMPTY5 + so, par);
        if (el) {
          bulk_g2s_mc(sb + so * 4096 + rank * 8192, base + (((j & 6) + i) & 7) * 16384, 8192, sb + B_FULLA + 2 * so + 8 * rank, ef);
          if (i == 2 - 2 * sh) TS(t0 == 0 ? (rank ? 4 : 12) : t0 == 3 ? (rank ? 31 : 10) : (rank ? 9 : 13));
        }
        so += 8;
        if (so == 48) { so = 0; par ^= 1; }
      }
    };
    if (wp == 0) {
      {
        #pragma unroll 1
        for (int kb = NPRE; kb < 16; kb++) {
          const uint32_t st = sb + (kb & 3) * KV_STAGE, fb = sb + B_FULLKV + 8 * (kb & 3);
          mbar_wait(fb + (B_EMPTYKV - B_FULLKV), ~(kb >> 2) & 1);
          if (el) {
            mbar_expect_tx(fb, KV_STAGE);
            tma_2d_mc(st + rank * 16384, &P.x128, 64 * kb, 256 * m256 + 128 * rank, fb);
            tma_4d_h(st + 32768, &P.wkv, 0, 64 * kb, nkv, 1, fb, ef);
          }
        }
        TS0_WRITE();
        uint64_t ord = 0xf3120edcba987654ull;
        uint32_t so = 0, par = 1;
        #pragma unroll 1
        for (int i = 0; i < 16; i++) {
          const uint32_t st = sb + so * 4096, fb = sb + B_FULL5 + so;
          const int k0 = (64 * (uint32_t)ord + 128 * (j & 6)) & 960;
          mbar_wait(i < 5 ? sb + B_EMPTYKV + so - (i > 1 ? 8 : 0) : fb + (B_EMPTY5 - B_FULL5), par);
          if (el) {
            mbar_expect_tx(fb, R5);
            tma_2d_mc_h(st + rank * 8192, &P.x64, k0, 128 * m128 + 64 * rank, fb, i >= EFI ? ef : en);
            tma_3d_h(st + 16384, &P.wq, 0, k0, 2 * j, fb, ef);
          }
          ord >>= 4; so += 8;
          if (so == 40) { so = 0; par ^= 1; }
        }
        #pragma unroll 1
        for (int i = 0; i < 19; i++) {
          const uint32_t fb = sb + B_FULL5 + so, fa = sb + B_FULLA + 2 * so, na = i == rank ? 0 : 8192;
          if (i == 1) { mbar_wait2(sb + B_FULL5 + 16, 0, sb + B_FULL5 + 24, 0); mbar_wait(sb + B_FULL5 + 32, 0); if (el) mbar_arrive(sb + B_R); }
          mbar_wait(fb + (B_EMPTY5 - B_FULL5), par);
          if (SLOT) { while (((uint32_t)clock() & (uint32_t)(SLOT - 1)) >= SLOTW) {} }
          if (el) {
            if (i < 16) {
              mbar_expect_tx(fb, 16384);
              const int row = i < 8 ? 128 * (((j & 6) + i) & 7) : 256 * (((j >> 1) + i) & 3) + 32 + 16 * (i & 4);
              tma_5d_h(sb + so * 4096 + 16384, &P.wo[i >> 3], 128 * j, row, fb, ef);
              tma_5d_h(sb + so * 4096 + 24576, &P.wo[i >> 3], 128 * j + 64, row, fb, ef);
              mbar_expect_tx(fa, na); mbar_expect_tx(fa + 8, na);
            } else mbar_arrive(sb + B_DR + 8 * (i - 16));
          }
          so += 8;
          if (so == 48) { so = 0; par ^= 1; }
        }
      }
    } else if (wp == 3) {
      const uint32_t t_start = (uint32_t)clock();
      if (el) {
        mbar_expect_tx(sb + B_W, 12288);
        #pragma unroll 1
        for (int i = 0; i < 6; i++) tma_2d(sb + (i == 0 ? OFF_WPHIK : i == 1 ? OFF_WPHIK1 : OFF_WPHIQ + 2048 * (i - 2)), &P.phi, 0, 32 * (i < 2 ? 2 * nkv + i : 4 * j + 2 * (i & 1) + ((i - 2) >> 1)), sb + B_W);
        prefetch_map(&P.x64); prefetch_map(&P.wq); prefetch_map(&P.wo[0]); prefetch_map(&P.wo[1]);
        prefetch_map(&P.wd); prefetch_map(&P.wg); prefetch_map(&P.wu);
      }
      #pragma unroll 1
      for (int i = 0; i < 8; i++) {
        st128_rlx(&G->cand[(m128 * 8 + i) * DM + (lane >> 4) * 512 + 64 * j + 4 * (lane & 15)], ~0u, ~0u, ~0u, ~0u);
      }
      if (lane < 16) st128_rlx(&G->rstat[16 * c + lane], 0, 0, 0, 0);
      if (lane < 3 * YR) st128_rlx(&G->yacc[3 * YR * c + lane], 0, 0, 0, 0);
      {
        const uint32_t nt = ld32_rlx(&G->epoch);
        if (lane < 8) { st128_rlx(&G->stats[16 * c + 2 * lane], nt, nt, nt, nt); st128_rlx(&G->csq[32 * c + 4 * lane], nt, nt, nt, nt); }
        if (lane < 4) { st128_rlx(&G->cskv[128 * nkv + 16 * m256 + 4 * lane], nt, nt, nt, nt); st128_rlx(&G->oset[16 * c + 4 * lane], nt, nt, nt, nt); }
      }
      if (lane < 8) st128_rlx(&G->key[(4 * j + (lane >> 1)) * 128 + m128 * 8 + 4 * (lane & 1)], 0, 0, 0, 0);
      if (c < 32) {
        #pragma unroll 1
        for (int i = lane; i < KVP; i += 32) st128_rlx(&G->kvacc[(ha + 2 * m256) * KVP + i], 0, 0, 0, 0);
      }
      fence_gpu();
      bar_arrive(NB_ZERO, 160);
      if (el) {
        #pragma unroll 1
        for (int i = PF_I0; i < 30; i++) {
          while ((uint32_t)clock() - t_start < (uint32_t)(PF_T0 + PF_DT * (i - PF_I0) + PF_ST * f)) __nanosleep(64);
          if (i < 4) { bulk_prefetch(P.wqkv + (size_t)(256 * i + c) * (3 * DM), 2048); bulk_prefetch(P.wqkv + (size_t)(256 * i + 128 + c) * (3 * DM), 2048); }
          else if (i < 6) bulk_prefetch(P.wo_p + (size_t)c * 8192 + (i - 4) * 4096, 8192);
          else if ((TMASK >> (i - 6)) & 1) {
            const int k = i - 6;
            if (f < NFFN) {
              if (k < 16) {
                #pragma unroll 1
                for (int e = 0; e < 4; e++) tma_2d(sb + OFF_T, rank ? &P.tu : &P.tg, 32 * (f & ~1), 64 * k + 16 * e, sb + B_T);
              } else { tma_2d(sb + OFF_T, &P.td, 0, 256 * f + 32 * (k - 16), sb + B_T); tma_2d(sb + OFF_T, &P.td, 0, 256 * f + 32 * (k - 16) + 16, sb + B_T); }
            }
          }
          else if (!((PMASK >> (i - 6)) & 1)) {}
          else if (i < 22) bulk_prefetch(((i & 1) ? P.wu_p : P.wg_p) + (size_t)((i - 6) >> 1) * 458752 + c * 3584, 7168);
          else bulk_prefetch(P.wd_p + (size_t)(i - 22) * 458752 + c * 3584, 7168);
        }
      }
      __syncwarp();
      mbar_wait2(sb + B_OS, 0, sb + B_RX, 0);
      #pragma unroll 1
      for (int t0 = 0; t0 < 4; t0 += 3) fetch_o(t0, t0 ? 8 : 24, 0);
    } else {
      const int half = wp - 1;
      const uint32_t ep1 = ld32_rlx(&G->epoch) + 1, tg = ep1 & 3;
      {
        uint32_t it = 0;
        sts128(sb + OFF_ONES + half * 512 + lane * 16, 0x3f803f80u, 0x3f803f80u, 0x3f803f80u, 0x3f803f80u);
        auto reset_o = [&](int i0, int i1, uint32_t dt) {
          uint32_t t0 = (uint32_t)clock();
          #pragma unroll 1
          for (int i = i0; i < i1; i++) {
            st128_rlx(G->o + (m128 * 16 + 2 * j + half) * 8192 + 256 * i + 8 * lane, ~0u, ~0u, ~0u, ~0u);
            while ((uint32_t)clock() - t0 < dt) __nanosleep(40);
            t0 += dt;
          }
        };
        mbar_wait(sb + B_S0, 0);
        reset_o(0, RS_N, RS_D1);
        bar_sync(NB_PUB, 192);
        const uint4* src = reinterpret_cast<const uint4*>(&G->stats[256 * m256 + 128 * half]) + lane;
        const uint4* srk = reinterpret_cast<const uint4*>(&G->cskv[128 * nkv]) + lane;
        uint4 v0, v1, vk;
        it = 0;
        do { v0 = ld128_rlx(src); v1 = ld128_rlx(src + 32); vk = ld128_rlx(srk); }
        while ((tag_bad(v0, tg) || tag_bad(v1, tg) || tag_bad(vk, tg)) && ++it < POLL_LIMIT);
        fence_acquire_gpu();
        if (half) put_colsums(sb + OFF_BXK, lane, untag(vk.x), untag(vk.y), untag(vk.z), untag(vk.w));
        #pragma unroll
        for (int i = 0; i < 2; i++) {
          const uint4 v = i ? v1 : v0;
          uint32_t hi, lo;
          split_bf16(-0.5f * untag(v.x), -0.5f * untag(v.z), hi, lo);
          const uint32_t h0 = __byte_perm(hi, hi, 0x1010), h1 = __byte_perm(hi, hi, 0x3232), l0 = __byte_perm(lo, lo, 0x1010), l1 = __byte_perm(lo, lo, 0x3232);
          const uint32_t a = sb + OFF_AXK + half * 2048 + i * 1024 + lane * 32;
          sts128(a, h0, l0, 0, 0); sts128(a + 16, h1, l1, 0, 0);
          sts64(sb + OFF_RS256 + half * 512 + i * 256 + lane * 8, v.y & ~3u, v.w & ~3u);
          if (half == (m128 & 1)) {
            const uint32_t aq = sb + OFF_AXQ + i * 1024 + lane * 32;
            sts128(aq, h0, l0, 0, 0); sts128(aq + 16, h1, l1, 0, 0);
            sts64(sb + OFF_RSQ + i * 256 + lane * 8, v.y & ~3u, v.w & ~3u);
          }
        }
        fence_async_smem();
        __syncwarp();
        if (el) { sts32(sb + OFF_EP, ep1); mbar_arrive(sb + B_AUX); if (!half) TS(1); }
        reset_o(RS_N, 32, RS_D2);
        fence_gpu();
        __syncwarp();
        if (el) { st32_rlx(&G->oset[16 * c + 8 * half], ep1); if (half) mbar_arrive(sb + B_AUXQ); }
        if (!half) {
          const uint4* src = reinterpret_cast<const uint4*>(&G->csq[128 * j]) + lane;
          uint4 v0, v1, v2, v3;
          do { v0 = ld128_rlx(src); v1 = ld128_rlx(src + DM / 4); v2 = ld128_rlx(src + DM / 2); v3 = ld128_rlx(src + 3 * DM / 4); }
          while ((tag_bad(v0, tg) || tag_bad(v1, tg) || tag_bad(v2, tg) || tag_bad(v3, tg)) && ++it < POLL_LIMIT);
          put_colsums(sb + OFF_BXQ, lane, (untag(v0.x) + untag(v1.x)) + (untag(v2.x) + untag(v3.x)), (untag(v0.y) + untag(v1.y)) + (untag(v2.y) + untag(v3.y)),
                      (untag(v0.z) + untag(v1.z)) + (untag(v2.z) + untag(v3.z)), (untag(v0.w) + untag(v1.w)) + (untag(v2.w) + untag(v3.w)));
          fence_async_smem();
          __syncwarp();
          if (el) mbar_arrive(sb + B_AUXQ);
        }
      }
      if (half == 0) {
        for (uint32_t it = 0; __any_sync(~0u, ld32_rlx(&G->oset[m128 * 128 + 8 * (lane & 15)]) != ep1) && it < POLL_LIMIT; it++) {}
        fence_acquire_gpu();
        if (el) mbar_arrive(sb + B_OS);
      }
      if (!half) {
        #pragma unroll 1
        for (int hh = 0; hh < 2; hh++) {
          const uint32_t src = sb + (1 + rank) * R5 + hh * 8192, fa = sb + B_FULLA + 16 + 16 * rank + 8 * hh;
          mbar_wait(fa, 0);
          mbar_wait(sb + B_UO + 8 * hh, 0);
          if (el) bulk_s2peer(mapa(src, rank ^ 1), src, 8192, mapa(fa, rank ^ 1));
        }
        fetch_o(1, 24, 1);
      }
      else if (f < NFFN_L) {
        mbar_wait2(sb + B_UO, 0, sb + B_UO + 8, 0);
        mbar_wait(sb + B_UO + 24, 0);
        uint32_t t0 = (uint32_t)clock();
        while ((uint32_t)clock() - t0 < (uint32_t)FF_T0) __nanosleep(32);
        t0 -= FF_DT;
        #pragma unroll 1
        for (int i = 0; i < 12; i++) {
          const int e = (FF_ORD >> (4 * i)) & 15;
          const uint32_t dst = sb + 16384 * ((FF_SLOT >> (4 * e)) & 15), fb = sb + B_F + 8 * e;
          if (i >= 2) mbar_wait(sb + B_WC + 8 * ((0x100066553244ull >> (4 * e)) & 15), 0);
          while ((uint32_t)clock() - t0 < (uint32_t)FF_DT) __nanosleep(32);
          t0 = (uint32_t)clock();
          if (i < 8) { TK(48 + i); }
          if (el) {
            mbar_expect_tx(fb, 16384);
            if (e >= 8) tma_3d_h(dst, &P.wd, 0, 32 * f, 4 * e - 32, fb, ef);
            else { tma_2d(dst, &P.wg, 32 * f, 128 * e, fb); tma_2d(dst + 8192, &P.wu, 32 * f, 128 * e, fb); }
          }
        }
      }
      __syncwarp();
    }
    {
      const int ch = lane & 15, rb = 32 * wp + (lane >> 4);
      const uint32_t src = sb + OFF_OUT + (ch >> 3) * 16384;
      bf16* dst = P.out_p + (size_t)(128 * m128) * DM + 128 * j + 8 * ch;
      __syncwarp();
      mbar_wait(sb + B_OUT + 8 * wp, 0);
      const float2 ex = lds64f(sb + OFF_EXC + 8 * wp);
      if (OUT_L) mbar_wait(sb + B_XS, 0);
      #pragma unroll 1
      for (int i = 0; i < 32; i += 2 * OUT_U) {
        uint4 v[OUT_U];
        #pragma unroll
        for (int e = 0; e < OUT_U; e++) { const int r = rb + i + 2 * e; v[e] = lds128(src + r * 128 + (((ch ^ r) & 7) << 4)); }
        #pragma unroll
        for (int e = 0; e < OUT_U; e++) { const int r = rb + i + 2 * e; if (r != __float_as_int(i < 16 ? ex.x : ex.y)) *reinterpret_cast<uint4*>(dst + r * DM) = v[e]; }
        if (OUT_NS) __nanosleep(OUT_NS);
      }
      if (wp == 0) { TK(63); }
      mbar_wait(sb + B_XS, 0);
      const int row = 2047 - (__float_as_uint(ldsf(sb + OFF_KEY)) & 2047) - 128 * m128, r = __float_as_int(lane < 16 ? ex.x : ex.y);
      if (r != row) *reinterpret_cast<uint4*>(dst + r * DM) = lds128(src + r * 128 + (((ch ^ r) & 7) << 4));
    }
    __syncwarp();
    cluster_arrive(); cluster_wait();
    return;
  }

  asm volatile("setmaxnreg.inc.sync.aligned.u32 160;");
  cluster_wait();
  const int t = tid & 127, g = lane >> 2;
  const uint32_t sa = (16 * wp + (lane & 15)) * 128 + (((lane >> 4) ^ (lane & 7)) << 4);

  if (wg == 2) {
    float s[2] = {0.f, 0.f}, s2[2] = {0.f, 0.f}, ck[8] = {0.f, 0.f, 0.f, 0.f, 0.f, 0.f, 0.f, 0.f}, cs[8] = {0.f, 0.f, 0.f, 0.f, 0.f, 0.f, 0.f, 0.f};
    const uint32_t ebr = mapa(sb + B_EMPTYKV, lane & 1), tg = (ld32_rlx(&G->epoch) + 1) & 3;
    auto addx = [&](const uint4 v) {
      const uint32_t w[4] = {v.x, v.y, v.z, v.w};
      #pragma unroll
      for (int e = 0; e < 4; e++) { const float a = bf_lo(w[e]), d = bf_hi(w[e]); s[0] += a; s[1] += d; s2[0] = fmaf(a, a, s2[0]); s2[1] = fmaf(d, d, s2[1]); }
    };
    auto addc = [&](const uint4 v, float (&o)[8]) {
      o[0] += bf_lo(v.x); o[1] += bf_hi(v.x); o[2] += bf_lo(v.y); o[3] += bf_hi(v.y); o[4] += bf_lo(v.z); o[5] += bf_hi(v.z); o[6] += bf_lo(v.w); o[7] += bf_hi(v.w);
    };
    {
      const uint32_t ra = (16 * nkv + (t >> 3)) * 128 + (t & 7) * 16;
      const uint32_t ca = 32768 + (m256 >> 2) * 8192 + (t >> 1) * 128 + (((2 * (m256 & 3) + (t & 1)) ^ ((t >> 1) & 7)) << 4);
      int rd = 0;
      mbar_wait(sb + B_S0, 0);
      #pragma unroll 1
      for (int kb = 0; kb < 10; kb++) {
        const uint32_t st = sb + (kb & 3) * KV_STAGE;
        mbar_wait(sb + B_FULLKV + 8 * (kb & 3), (kb >> 2) & 1);
        const uint4 x0 = lds128(st + ra), w0 = lds128(st + ca);
        addx(x0); addc(w0, ck);
        __syncwarp();
        if (lane < 2) mbar_arrive_remote(ebr + 8 * (kb & 3), 1);
        if ((SKM >> kb) & 1) {
          if (rd) {
            mbar_wait(sb + B_G, (rd - 1) & 1);
            const uint32_t a = sb + OFF_G + (t >> 3) * 256 + (t & 7) * 16;
            const uint4 x1 = lds128(a), x2 = lds128(a + 128), w1 = lds128(sb + OFF_G + 4096 + t * 16), w2 = lds128(sb + OFF_G + 6144 + t * 16);
            addx(x1); addx(x2); addc(w1, ck); addc(w2, ck);
            bar_sync(NB_WG2, 128);
          }
          if (wp == 0 && elect_one()) {
            mbar_expect_tx(sb + B_G, 8192);
            if (rd < 3) {
              tma_2d(sb + OFF_G, &P.xs, 640 + 128 * rd, 256 * m256 + 16 * nkv, sb + B_G);
              tma_2d(sb + OFF_G + 4096, &P.ws, (1 + (m256 >> 2)) * DM + 64 * nkv + 16 * (m256 & 3), 640 + 128 * rd, sb + B_G);
            } else tma_2d(sb + OFF_G, &P.qs, 32 * (c & 31), 256 * (c >> 5), sb + B_G);
          }
          rd++;
        }
      }
    }
    TK(82);
    const uint32_t scr = sb + OFF_SCR + 128;
    float sx = s[0] + s[1], sq = s2[0] + s2[1];
    #pragma unroll
    for (int o = 1; o < 8; o <<= 1) { sx += __shfl_xor_sync(~0u, sx, o); sq += __shfl_xor_sync(~0u, sq, o); }
    float v = reduce8(ck, lane);
    v += __shfl_xor_sync(~0u, v, 2);
    if (!(lane & 2)) stsf(scr + (wp * 16 + 8 * (lane & 1) + (lane >> 2)) * 4, v);

    bar_sync(NB_ZERO, 160);
    if ((lane & 7) == 0) {
      const float mean = sx * (1.f / DM);
      st64_rlx(&G->stats[256 * m256 + 16 * nkv + (t >> 3)], tagw(mean, tg), tagw(rsqrtf(fmaxf(sq * (1.f / DM) - mean * mean, 0.f) + 1e-5f), tg));
    }
    if (wp == 1 && lane < 16) {
      const uint32_t a = scr + lane * 4;
      st32_rlx(&G->cskv[128 * nkv + 16 * m256 + lane], tagw((ldsf(a) + ldsf(a + 64)) + (ldsf(a + 128) + ldsf(a + 192)), tg));
    }
    __syncwarp();
    bar_arrive(NB_PUB, 192);
    TSW(23);
    const uint4 wv = ld128_keep(P.wr + t * 8);
    #pragma unroll 1
    for (int i = 0; i < 2; i++) {
      mbar_wait(sb + B_G, i ^ 1);
      const uint32_t a = sb + OFF_G + t * 16;
      const uint4 u0 = lds128(a), u1 = lds128(a + 2048), u2 = lds128(a + 4096), u3 = lds128(a + 6144);
      addc(u0, cs); addc(u1, cs); addc(u2, cs); addc(u3, cs);
      bar_sync(NB_WG2, 128);
      if (i == 0 && wp == 0 && elect_one()) { mbar_expect_tx(sb + B_G, 8192); tma_2d(sb + OFF_G, &P.qs, 32 * (c & 31), 256 * (c >> 5) + 128, sb + B_G); }
    }
    if (t == 0) mbar_arrive(sb + B_W);
    float sw = (bf_lo(wv.x) + bf_hi(wv.x)) + (bf_lo(wv.y) + bf_hi(wv.y)) + (bf_lo(wv.z) + bf_hi(wv.z)) + (bf_lo(wv.w) + bf_hi(wv.w));
    #pragma unroll
    for (int o = 16; o; o >>= 1) sw += __shfl_xor_sync(~0u, sw, o);
    if (lane == 0) stsf(sb + OFF_SUMWR + wp * 4, sw);
    if ((t >> 4) == j) {
      const uint32_t a = sb + OFF_WR + (t & 15) * 32;
      sts128(a, wv.x << 16, wv.x & 0xffff0000u, wv.y << 16, wv.y & 0xffff0000u);
      sts128(a + 16, wv.z << 16, wv.z & 0xffff0000u, wv.w << 16, wv.w & 0xffff0000u);
    }
    v = reduce8(cs, lane);
    stsf(scr + (wp * 32 + 8 * (lane & 3) + (lane >> 2)) * 4, v);
    bar_sync(NB_WG2, 128);
    if (wp == 0) {
      const uint32_t a = scr + lane * 4;
      st32_rlx(&G->csq[(c >> 5) * DM + 32 * (c & 31) + lane], tagw((ldsf(a) + ldsf(a + 128)) + (ldsf(a + 256) + ldsf(a + 384)), tg));
    }
  }

  uint32_t xr[32];
  {
    const bool isq = wg == 2;
    float acc[2][64];
    {
      const uint32_t emptyb = mapa(sb + (isq ? B_EMPTY5 : B_EMPTYKV), t & 1);
      if (!isq) {
        mbar_wait(sb + B_S0, 0);
        if (wg) mbar_wait(sb + B_FULLKV, 0);
        if (wg == 0) { TSW(2); }
        #pragma unroll 1
        for (int kb = 0; kb < 16; kb++) {
          if (!KT && wg == 0) { TK(kb); }
          const uint32_t da = dlo(SB0, 16) + wg * 1024 + (kb & 3) * (KV_STAGE >> 4), db = dlo(SB0 + 32768, 8192) + (kb & 3) * (KV_STAGE >> 4);
          wg_fence();
          #pragma unroll
          for (int k = 0; k < 4; k++) {
            wgmma_ss_n128<0, 1, H128, H128>(acc[0], da + 2 * k, db + 128 * k, k > 0 || kb != 0);
            wgmma_ss_n128<0, 1, H128, H128>(acc[1], da + 512 + 2 * k, db + 128 * k, k > 0 || kb != 0);
          }
          wg_commit();
          wg_wait<1>();
          if (kb > 0 && t < 2) mbar_arrive_remote(emptyb + 8 * ((kb - 1) & 3), kb > 10 ? 3 : 1);
          if (kb < 15) mbar_wait(sb + B_FULLKV + 8 * ((kb + 1) & 3), ((kb + 1) >> 2) & 1);
          if (kb == 15 - LAG && wg == 1) bar_sync(NB_WG01, 256);
        }
        bar_arrive(wg ? NB_QGO : NB_WG01, 256);
      } else {
        uint32_t so = 0, po = 0, par = 0;
        mbar_wait(sb + B_FULL5, 0);
        bar_sync(NB_QGO, 256);
        TSW(11);
        #pragma unroll 1
        for (int kb = 0; kb < 16; kb++) {
          TK(16 + kb);
          const uint32_t da = dlo(SB0, 16) + so * 256, db = dlo(SB0 + 16384, 8192) + so * 256;
          #pragma unroll
          for (int k = 0; k < 4; k++) {
            wg_fence();
            wgmma_ss_n128<0, 1, H128, H128>(acc[0], da + 2 * k, db + 128 * k, k > 0 || kb != 0);
            wgmma_ss_n128<0, 1, H128, H128>(acc[1], da + 512 + 2 * k, db + 128 * k, k > 0 || kb != 0);
            wg_commit();
            if (k == 1 && kb > 0 && t < 2) mbar_arrive_remote(emptyb + po, 2);
            if (k == 3) {
              po = so; so += 8;
              if (so == 40) { so = 0; par ^= 1; }
              if (kb < 15) mbar_wait(sb + B_FULL5 + so, par);
            }
            if ((QW >> k) & 1) wg_wait<2>(); else wg_wait<1>();
          }
        }
        mbar_wait(sb + B_AUXQ, 0);
      }
      mbar_wait(sb + B_AUX, 0);
      const uint32_t xa = dlo(SB0, 0) + (isq ? OFF_AXQ >> 4 : (OFF_AXK >> 4) + wg * 128), xb = dlo(SB0, 0) + (isq ? OFF_BXQ >> 4 : OFF_BXK >> 4);
      wg_fence();
      wgmma_sa_n128<0, 1, H0, H0>(acc[0], xa, xb);
      wgmma_sa_n128<0, 1, H0, H0>(acc[1], xa + 64, xb);
      wg_commit();
      if (isq) mbar_wait(sb + B_RC, 0);
      wg_wait<0>();
      if (t < 2) mbar_arrive_remote(emptyb + (isq ? 0 : 24), isq ? 2 : 3);
      if (wg != 1) { TSW(wg ? 8 : 3); }
      fence_regs(acc[0]); fence_regs(acc[1]);
    }
    if (isq) {
      #pragma unroll
      for (int i = 0; i < 2; i++) {
        const uint32_t ta = sb + (1 + rank) * R5 + sa + i * 8192;
        if (i == 1) mbar_wait(sb + B_RC + 8, 0);
        #pragma unroll
        for (int k = 0; k < 4; k++) {
          const float* a = &acc[i][32 * (k >> 1) + 8 * (k & 1)];
          stsm4(ta ^ (k << 5), pack_bf16(a[0], a[1]), pack_bf16(a[2], a[3]), pack_bf16(a[4], a[5]), pack_bf16(a[6], a[7]));
        }
        fence_async_smem();
        bar_arrive(NB_Q0 + i, 256);
      }
      #pragma unroll
      for (int i = 0; i < 32; i++) { const float* a = &acc[(i >> 3) & 1][16 + 32 * (i >> 4) + 2 * (i & 7)]; xr[i] = pack_bf16(a[0], a[1]); }
      TSW(26);
    } else {
      const uint32_t stg = sb + OFF_X + (1 - wg) * 24576;
      const uint32_t va = stg + 16384 + (16 * wp + (lane & 15)) * 64 + (((lane >> 4) ^ ((lane >> 1) & 3)) << 4);
      const uint32_t ra = sb + OFF_RS256 + (128 * wg + 16 * wp + g) * 4;
      const float rs[4] = {ldsf(ra), ldsf(ra + 32), ldsf(ra + 256), ldsf(ra + 288)};
      float p[2][16];
      uint32_t vf[16], kf[2][16];
      auto project = [&](const uint32_t (&f)[16], uint32_t db) {
        wg_fence();
        #pragma unroll
        for (int i = 0; i < 2; i++) {
          wgmma_rs_n32<1, H64>(p[i], f[8*i], f[8*i+1], f[8*i+2], f[8*i+3], db, 0);
          wgmma_ra_n32<1, H64>(p[i], f[8*i+4], f[8*i+5], f[8*i+6], f[8*i+7], db + 64);
        }
        wg_commit();
      };
      auto fold = [&](uint32_t (&f)[16], int col, float sc) {
        #pragma unroll
        for (int i = 0; i < 16; i++) {
          const float r = rs[2 * (i >> 3) + (i & 1)] * sc;
          f[i] = pack_bf16(acc[i >> 3][col + 2 * (i & 7)] * r, acc[i >> 3][col + 2 * (i & 7) + 1] * r);
          asm volatile("" : "+r"(f[i]));
        }
      };
      auto put_v = [&](const uint32_t (&f)[16]) {
        #pragma unroll
        for (int k = 0; k < 4; k++) stsm4((va ^ ((k & 1) << 5)) + (k >> 1) * 4096, f[4*k], f[4*k+1], f[4*k+2], f[4*k+3]);
      };
      KK(0);
      fold(vf, 48, 1.f);
      mbar_wait(sb + B_W, 0);
      fold(kf[0], 0, LOG2E);
      #pragma unroll
      for (int i = 0; i < 32; i++) p[i >> 4][i & 15] = acc[i >> 4][i & 15];
      project(kf[0], dlo(SB0 + OFF_WPHIK, 16));
      mbar_wait(sb + B_W, 0);
      KK(1);
      {
        uint32_t v0[16];
        fold(kf[1], 16, LOG2E);
        fold(v0, 32, 1.f);
        if (wg == 1) bar_sync(NB_DN, 256);
        put_v(v0);
      }
      wg_wait<0>();
      fence_regs(p[0]); fence_regs(p[1]);
      if (wg == 1) bar_arrive(NB_WG01, 256);
      KK(2);
      #pragma unroll 1
      for (int h = 0; h < 2; h++) {
        uint32_t ph[4][8];
        float rsum[4][4];
        dual_exp2(p, ph);
        wg_fence();
        row_sums(rsum, ph, dlo(SB0 + OFF_ONES, 128));
        wg_commit();
        KK(3 + 6 * h);
        if (wg == 0 && h == 0) { bar_arrive(NB_DN, 256); bar_sync(NB_WG01, 256); }
        if (h == 1) {
          if (wg == 1) bar_sync(NB_DN, 256);
          put_v(vf);
        }
        wg_wait<0>();
        KK(4 + 6 * h);
        #pragma unroll
        for (int i = 0; i < 4; i++) fence_regs(rsum[i]);
        if (__builtin_expect(__any_sync(~0u, !((rsum[0][0] + rsum[0][2]) + (rsum[1][0] + rsum[1][2]) + (rsum[2][0] + rsum[2][2]) + (rsum[3][0] + rsum[3][2]) < EXP_LIM)), 0)) {
          dual_exp2_shifted(p, ph);
          #pragma unroll
          for (int i = 0; i < 8; i++) {
            const uint32_t* f = &ph[i >> 1][i & 1];
            float a = (bf_lo(f[0]) + bf_hi(f[0])) + (bf_lo(f[2]) + bf_hi(f[2])) + (bf_lo(f[4]) + bf_hi(f[4])) + (bf_lo(f[6]) + bf_hi(f[6]));
            a += __shfl_xor_sync(~0u, a, 1);
            rsum[i >> 1][2 * (i & 1)] = a + __shfl_xor_sync(~0u, a, 2);
          }
        }
        if (h == 0) project(kf[1], dlo(SB0 + OFF_WPHIK1, 16));
        normalize(ph, rsum);
        #pragma unroll
        for (int i = 0; i < 8; i++) {
          const uint32_t* f = &ph[i >> 1][4 * (i & 1)];
          stsm4(((stg + sa) ^ ((i & 3) << 5)) + (i >> 2) * 8192, f[0], f[1], f[2], f[3]);
        }
        KK(5 + 6 * h);
        fence_async_smem();
        KK(6 + 6 * h);
        if (wg != h) { KK(7 + 6 * h); }
        if (wg == h) {
          float kv[20];
          #pragma unroll
          for (int w = 0; w < 2; w++) {
            const uint32_t da = dlo(SB0 + OFF_X, 16) + (h ^ w ^ 1) * 1536, db = dlo(SB0 + OFF_X + 16384, OFF_ONES - OFF_X - 16384) - (h ^ w ^ 1) * (1536 * 65535);
            if (w) bar_sync(NB_ST, 256); else bar_sync(NB_L0 + h, 128);
            wg_fence();
            #pragma unroll
            for (int k = 0; k < 8; k++) {
              if (k == 0 && w == 0) wgmma_sz_n40<1, 1, H128, H64>(kv, da, db);
              else wgmma_sa_n40<1, 1, H128, H64>(kv, da + k * 128, db - k * (64 * 65535));
            }
            wg_commit();
          }
          float4* dst = &G->kvacc[(ha + 2 * h) * KVP + t];
          wg_wait<0>();
          fence_regs(kv);
          KK(7 + 6 * h);
          if (h == 0) bar_arrive(NB_DN, 256); else if (t < 2) { mbar_arrive_at(sb + B_EMPTY5 + 40, t, 2); if (t == 0) mbar_arrive(sb + B_KD); }
          kv[17] = kv[18];
          #pragma unroll
          for (int i = 0; i < 6; i++) red_add_f32x4(dst + 128 * i, kv[3*i], kv[3*i+1], kv[3*i+2], 1.f);
          TSW(29 + h);
        } else bar_arrive(NB_ST, 256);
        wg_wait<0>();
        KK(8 + 6 * h);
        fence_regs(p[0]); fence_regs(p[1]);
      }
      #pragma unroll
      for (int i = 0; i < 32; i++) asm volatile("mov.b32 %0, 0;" : "=r"(xr[i]));
    }
    float p[2][16];
    #pragma unroll
    for (int i = 0; i < 32; i++) asm volatile("mov.b32 %0, 0;" : "=f"(p[i >> 4][i & 15]));
    auto project_r = [&](int w) {
      wg_fence();
      #pragma unroll
      for (int h = 0; h < 2; h++) {
        wgmma_rs_n32<1, H64>(p[h], xr[8*h], xr[8*h+1], xr[8*h+2], xr[8*h+3], dlo(SB0 + OFF_WPHIQ, 16) + 128 * w, 0);
        wgmma_ra_n32<1, H64>(p[h], xr[8*h+4], xr[8*h+5], xr[8*h+6], xr[8*h+7], dlo(SB0 + OFF_WPHIQ, 16) + 128 * w + 64);
      }
      wg_commit();
    };
    {
      const uint4* src = reinterpret_cast<const uint4*>(&G->kvacc[(4 * j + wg) * KVP + t]);
      uint4 v[12];
      #pragma unroll
      for (int i = 0; i < 12; i++) v[i] = i < 6 || isq ? ld128_rlx(src + 128 * i) : make_uint4(0, 0, 0, 0x41000000u);
      if (isq) {
        project_r(2);
        wg_wait<0>();
        #pragma unroll
        for (int i = 0; i < 16; i++) xr[i] = xr[16 + i];
      } else {
        mbar_wait(sb + B_R, 0);
        #pragma unroll
        for (int k = 0; k < 8; k++) ldsm4(((sb + (1 + rank) * R5 + wg * 8192 + sa) ^ ((k & 3) << 5)) + (k >> 2) * 2 * R5, xr[4*k], xr[4*k+1], xr[4*k+2], xr[4*k+3]);
        const uint32_t one = (((xr[0] | xr[4] | xr[8]) | (xr[12] | xr[16] | xr[20]) | (xr[24] | xr[28])) & P.zero) + 1;
        if (lane == 0) { mbar_arrive_at(sb + B_RC + 8 * wg, rank, one); mbar_arrive_at(sb + B_RX, wg, one); }
      }
      #pragma unroll 1
      for (uint32_t it = 0; it < POLL_LIMIT; it++) {
        uint32_t bad = 0;
        #pragma unroll
        for (int i = 0; i < 12; i++) bad |= v[i].w ^ 0x41000000u;
        if (!__any_sync(~0u, bad != 0)) break;
        #pragma unroll
        for (int i = 0; i < 12; i++) if (i < 6 || isq) v[i] = ld128_rlx(src + 128 * i);
      }
      mbar_wait(sb + B_KD, 0);
      #pragma unroll
      for (int e = 0; e < 2; e++) {
        if (e == 0 || isq) {
          float f[18];
          #pragma unroll
          for (int i = 0; i < 6; i++) { f[3*i] = __uint_as_float(v[6*e+i].x); f[3*i+1] = __uint_as_float(v[6*e+i].y); f[3*i+2] = __uint_as_float(v[6*e+i].z); }
          const uint32_t ka = sb + OFF_KVZ + (wg + e) * 5120 + wp * 1280 + lane * 16;
          stsm4(ka, pack_bf16(f[0], f[1]), pack_bf16(f[2], f[3]), pack_bf16(f[4], f[5]), pack_bf16(f[6], f[7]));
          stsm4(ka + 512, pack_bf16(f[8], f[9]), pack_bf16(f[10], f[11]), pack_bf16(f[12], f[13]), pack_bf16(f[14], f[15]));
          stsm2(ka + 1024, pack_bf16(f[16], 1.f), pack_bf16(f[17], 1.f));
        }
      }
    }
    fence_async_smem();
    if (wg == 1) bar_arrive(NB_DN, 256);
    if (isq) mbar_wait(sb + B_OS, 0);
    TSW(wg == 0 ? 5 : wg == 1 ? 25 : 6);
    #pragma unroll 1
    for (int e = wg; e < wg + 1 + (wg >> 1); e++) {
      const int half = e >> 1, hh = e & 1, turn = e;
      const uint32_t ao = (1 + rank) * R5 + hh * 8192;
      const uint32_t ra = sb + OFF_RSQ + (16 * wp + g) * 4 + (e == 1 ? 256 : 0), rb = ra + 256 * half;
      const float cc[2][2] = {{ldsf(ra) * LOG2E, ldsf(ra + 32) * LOG2E}, {ldsf(rb) * LOG2E, ldsf(rb + 32) * LOG2E}};
      uint32_t ph[4][8];
      #pragma unroll
      for (int i = 0; i < 32; i++) asm volatile("mov.b32 %0, 0;" : "=r"(ph[i >> 3][i & 7]));
      auto exps = [&](int h) {
        #pragma unroll
        for (int k = 0; k < 8; k++) {
          const float a = ex2(p[h][2*k]), b = ex2(p[h][2*k+1]);
          ph[2*h][k] = pack_bf16(a, b);
          if (PRCP) { const float r = rcp(a * b); ph[2*h+1][k] = pack_bf16(r * b, r * a); }
          else ph[2*h+1][k] = pack_bf16(ex2(-p[h][2*k]), ex2(-p[h][2*k+1]));
        }
      };
      uint32_t shifted = 0;
      asm volatile("" : "+r"(shifted));
      #pragma unroll 1
      for (;;) {
        if (shifted) dual_exp2_shifted(p, ph);
        uint32_t first = (shifted ^ 1) & !isq;
        asm volatile("" : "+r"(first));
        if (first) {
          bar_sync(NB_Q0 + wg, 256);
          const uint32_t da = dlo(SB0, 16) + (ao >> 4), db = dlo(SB0 + OFF_WPHIQ, 16);
          wg_fence();
          #pragma unroll
          for (int h = 0; h < 2; h++) {
            wgmma_ss_n32<0, 1, H128, H64>(p[h], da + 4 * h, db + 128 * h, 0);
            wgmma_sa_n32<0, 1, H128, H64>(p[h], da + 4 * h + 2, db + 128 * h + 64);
          }
          wg_commit();
          wg_wait<0>();
        }
        fence_regs(p[0]); fence_regs(p[1]);
        uint32_t again = shifted;
        asm volatile("" : "+r"(again));
        if (again) break;
        float s2[4] = {0.f, 0.f, 0.f, 0.f};
        #pragma unroll
        for (int i = 0; i < 32; i++) { float& x = p[i >> 4][i & 15]; x *= cc[i >> 4][(i >> 1) & 1]; s2[i & 3] = fmaf(x, x, s2[i & 3]); }
        if (!__any_sync(~0u, !((s2[0] < ARG_LIM2) & (s2[1] < ARG_LIM2) & (s2[2] < ARG_LIM2) & (s2[3] < ARG_LIM2)))) break;
        shifted = 1;
      }
      if (e == 1 || e == 2) bar_sync(NB_TOK + e - 1, 256);
      TK(64 + 4 * turn);
      float ac[4][20];
      auto numer = [&](int h) {
        const uint32_t (*f)[8] = &ph[2 * h];
        const uint32_t db = dlo(SB0 + OFF_KVZ, 128) + (half ? e : h) * 320;
        wg_fence();
        #pragma unroll
        for (int i = 0; i < 2; i++) {
          wgmma_rz_n40<1, dhi(256, 0)>(ac[2*h+i], f[i][0], f[i][1], f[i][2], f[i][3], db + i * 160);
          wgmma_ra_n40<1, dhi(256, 0)>(ac[2*h+i], f[i][4], f[i][5], f[i][6], f[i][7], db + (i * 160 + 80));
        }
        wg_commit();
      };
      const uint32_t oa = (16 * wp + g) * 128 + (((lane & 3) ^ g) << 4);
      auto finish = [&](int h) {
        const float* ap = ac[2 * h]; const float* am = ac[2 * h + 1];
        const float ip0 = rcp(ap[17]), im0 = rcp(am[17]), ip1 = rcp(ap[19]), im1 = rcp(am[19]);
        const float d0 = rcp(fmaf(ap[16], ip0, fmaf(am[16], im0, 1e-6f))), d1 = rcp(fmaf(ap[18], ip1, fmaf(am[18], im1, 1e-6f)));
        const float a0 = ip0 * d0, b0 = im0 * d0, a1 = ip1 * d1, b1 = im1 * d1;
        #pragma unroll
        for (int r = 0; r < 2; r++) {
          const float a = r ? a1 : a0, b = r ? b1 : b0;
          uint32_t w[4];
          #pragma unroll
          for (int k = 0; k < 4; k++) w[k] = pack_bf16(fmaf(ap[4*k+2*r], a, am[4*k+2*r] * b), fmaf(ap[4*k+2*r+1], a, am[4*k+2*r+1] * b));
          const uint32_t off = (oa ^ ((half ? rank : h) << 6)) + r * 1024;
          st128_rlx(reinterpret_cast<uint8_t*>(G->o + (m128 * 16 + (half ? 2 * (j & 6) + 2 * hh + 1 : 2 * j)) * 8192 + (half ? h : hh) * 4096) + off, w[0], w[1], w[2], w[3]);
          if (!half) sts128(sb + ao + off, w[0], w[1], w[2], w[3]);
        }
      };
      if (!shifted) exps(0);
      numer(0);
      if (!shifted) exps(1);
      if (turn < 2) bar_arrive(NB_TOK + turn, 256);
      if (wg == 0) bar_sync(NB_DN, 256);
      numer(1);
      wg_wait<1>();
      TK(65 + 4 * turn);
      fence_regs(ac[0]); fence_regs(ac[1]);
      finish(0);
      wg_wait<0>();
      fence_regs(ac[2]); fence_regs(ac[3]);
      #pragma unroll
      for (int i = 0; i < 32; i++) asm volatile("mov.b32 %0, 0;" : "=f"(p[i >> 4][i & 15]));
      if (e == 2) project_r(3);
      finish(1);
      TK(66 + 4 * turn);
      if (!half) fence_async_smem();
      __syncwarp();
      if (lane == 0) mbar_arrive(sb + B_UO + 8 * e);
      wg_wait<0>();
      TK(67 + 4 * turn);
    }
    if (isq) cluster_arrive();
  }

  {
  int lane;
  asm volatile("mov.u32 %0, %%laneid;" : "=r"(lane));
  const int g = lane >> 2, q = lane & 3;
  if (wg < 2) {
    float h[64];
    {
      if (wg == 0) { TK(83); }
      #pragma unroll
      for (int i = 0; i < 32; i++) { h[2*i] = bf_lo(xr[i]); h[2*i+1] = bf_hi(xr[i]); }
      fence_regs(h);
      TK(80 + wg);
      const uint32_t emptyb = mapa(sb + B_EMPTY5, t & 1);
      uint32_t s = 1 + rank, ps = 0;
      mbar_wait2(sb + B_FULL5 + 8 * s, 1, sb + B_UO + 8 * wg, 0);
      if (wg == 0) { TSW(14); }
      #pragma unroll
      for (int i = 0; i < 16; i++) {
        if (wg == 1 && (i & 12) == TKW) { TK(84 + (i & 3)); }
        if (!KT && wg == 0) { TK(32 + i); }
        const uint32_t da = dlo(SB0, 16) + s * 2048 + wg * 512, db = dlo(SB0 + 16384, 8192) + s * 2048;
        wg_fence();
        #pragma unroll
        for (int k = 0; k < 4; k++) wgmma_sa_n128<0, 1, H128, H128>(h, da + k * 2, db + k * 128);
        wg_commit();
        const uint32_t ns = i ? (i + 2) % 6 : 2 - rank;
        const uint32_t b0 = sb + B_FULL5 + 8 * ns, p0 = (1 + (i + 2) / 6) & 1, b1 = sb + B_FULLA + 16 * ns + 8 * wg, p1 = ((i + 1) / 6) & 1;
        const bool here = i == 15 || mbar_test2(b0, p0, b1, p1);
        wg_wait<1>();
        if (!(((2 * REL + 1) >> i) & 1) && i < 14 && t < 2) mbar_arrive_remote(emptyb + 8 * ps, 1);
        if ((REL >> i) & 1) { wg_wait<0>(); if (t < 2) mbar_arrive_remote(emptyb + 8 * s, 1); }
        if (!here) mbar_wait2(b0, p0, b1, p1);
        ps = s; s = ns;
      }
    }
    cluster_arrive();
    float2 wr[16];
    #pragma unroll
    for (int i = 0; i < 16; i++) wr[i] = lds64f(sb + OFF_WR + 32 * i + 8 * q);
    const int r0 = 64 * wg + 16 * wp + g;
    float sum0, sum1, dot0, dot1, sq0, sq1;
    uint32_t redo = 0;
    asm volatile("" : "+r"(redo));
    #pragma unroll 1
    for (;;) {
    if (redo) {
      wg_wait<0>();
      const int r = r0;
      #pragma unroll 1
      for (int n = 0; n < 16; n++) {
        const uint32_t* xp = reinterpret_cast<const uint32_t*>(P.x + (size_t)(128 * m128 + r) * DM + 128 * j + 8 * n) + q;
        const uint32_t x0 = xp[0], x1 = xp[4 * DM];
        float d0 = bf_lo(x0), d1 = bf_hi(x0), d2 = bf_lo(x1), d3 = bf_hi(x1);
        #pragma unroll 1
        for (int ks = 0; ks < 64; ks++) {
          const int kb = ks >> 2, kk = 16 * (ks & 3);
          const bf16* op = G->o + (m128 * 16 + kb) * 8192 + r * 64 + 2 * q;
          const int o0 = ((kk >> 3) ^ g) << 3;
          const uint16_t* w = reinterpret_cast<const uint16_t*>(P.wo_p) + (size_t)(((kb & 1) ? 256 * (kb >> 2) + 32 * (kb & 2) + 32 + 4 * (kk & 32) : 64 * kb + 2 * (kk & 32)) + ((kk & 16) >> 2) + 8 * q) * DM + 128 * j + 8 * n + g;
          const uint32_t b0 = w[0] | (w[DM] << 16), b1 = w[2 * DM] | (w[3 * DM] << 16);
          uint32_t a0, a1, a2, a3, it = 0;
          do { a0 = ld32_rlx(op + o0); a1 = ld32_rlx(op + 512 + o0); a2 = ld32_rlx(op + (o0 ^ 8)); a3 = ld32_rlx(op + 512 + (o0 ^ 8)); }
          while (max(max(a0, a1), max(a2, a3)) == ~0u && ++it < POLL_LIMIT);
          __syncwarp();
          mma16816(d0, d1, d2, d3, a0, a1, a2, a3, b0, b1);
        }
        #pragma unroll
        for (int i = 0; i < 60; i++) h[i] = h[i + 4];
        h[60] = d0; h[61] = d1; h[62] = d2; h[63] = d3;
      }
    }
    wg_wait<0>();
    fence_regs(h);
    if (wg == 0) { TSW(16); }
    sum0 = 0.f, sum1 = 0.f, dot0 = 0.f, dot1 = 0.f, sq0 = 0.f, sq1 = 0.f;
    #pragma unroll
    for (int i = 0; i < 16; i++) {
      sum0 += h[4*i] + h[4*i+1]; sum1 += h[4*i+2] + h[4*i+3];
      sq0 = fmaf(h[4*i], h[4*i], fmaf(h[4*i+1], h[4*i+1], sq0)); sq1 = fmaf(h[4*i+2], h[4*i+2], fmaf(h[4*i+3], h[4*i+3], sq1));
      dot0 = fmaf(h[4*i], wr[i].x, fmaf(h[4*i+1], wr[i].y, dot0)); dot1 = fmaf(h[4*i+2], wr[i].x, fmaf(h[4*i+3], wr[i].y, dot1));
    }
    if (!__any_sync(~0u, !redo & (h[0] != h[0] | h[2] != h[2]))) break;
    redo = 1;
    }
    float4* const rs = &G->rstat[128 * m128 + r0];
    {
      const bool up = q & 2;
      float a = up ? sum1 : sum0, b = up ? sq1 : sq0, d = up ? dot1 : dot0;
      a += __shfl_xor_sync(~0u, up ? sum0 : sum1, 2); b += __shfl_xor_sync(~0u, up ? sq0 : sq1, 2); d += __shfl_xor_sync(~0u, up ? dot0 : dot1, 2);
      a += __shfl_xor_sync(~0u, a, 1); b += __shfl_xor_sync(~0u, b, 1); d += __shfl_xor_sync(~0u, d, 1);
      if ((q & 1) == 0) red_add_f32x4(rs + 4 * q, a, b, d, 1.f);
    }
    if (TRKL == 0) bar_arrive(NB_G2E, 384);
    if (wg == 0) { TSW(24); }
    bar_sync(NB_WG01, 256);
    uint32_t wa[8][4][4];
    const uint32_t wb = sb + 16384 * (((uint32_t)FF_SLOT >> (4 * warp)) & 15) + ((lane & 7) + ((lane >> 4) << 3)) * 64 + ((((lane >> 3) & 1) ^ ((lane >> 1) & 3)) << 4);
    auto getw = [&](int ks) {
      #pragma unroll
      for (int m = 0; m < 4; m++) ldsm4t((wb ^ ((m & 1) << 5)) + (m >> 1) * 8192 + ks * 1024, wa[ks][m][0], wa[ks][m][1], wa[ks][m][2], wa[ks][m][3]);
    };
    if (GPRE && f < NFFN_L) mbar_wait(sb + B_F + 8 * warp, 0);
    if (warp == 7) { TK(60); }
    #pragma unroll
    for (int ks = 0; ks < GPRE; ks++) getw(ks);
    float rstd[2], bm[2];
    uint32_t best;
    {
      const float2 swa = lds64f(sb + OFF_SUMWR), swb = lds64f(sb + OFF_SUMWR + 8);
      const float sw = (swa.x + swa.y) + (swb.x + swb.y);
      uint4 a[2]; uint32_t it = 0, key[2];
      do { a[0] = ld128_rlx(rs); a[1] = ld128_rlx(rs + 8); } while (__any_sync(~0u, (a[0].w & a[1].w) != 0x41000000u) && ++it < POLL_LIMIT);
      #pragma unroll
      for (int i = 0; i < 2; i++) {
        const float mean = __uint_as_float(a[i].x) * (1.f / DM);
        rstd[i] = rsqrtf(fmaxf(__uint_as_float(a[i].y) * (1.f / DM) - mean * mean, 0.f) + 1e-5f);
        bm[i] = -mean * rstd[i];
        const uint32_t rr = __float_as_uint(fmaf(__uint_as_float(a[i].z), rstd[i], sw * bm[i]));
        key[i] = ((rr ^ ((uint32_t)((int32_t)rr >> 31) | 0x80000000u)) & ~2047u) | (2047 - 128 * m128 - r0 - 8 * i);
      }
      asm volatile("redux.sync.max.u32 %0, %1, 0xffffffff;" : "=r"(best) : "r"(max(key[0], key[1])));
    }
    if (TRKL == 2) bar_arrive(NB_G2E, 384);
    if (TRKL == 3 && wg == 0) bar_arrive(NB_G2E, 256);
    if (wg == 0) { TSW(17); }
    const int slot = m128 * 8 + warp, win = ~best & 15;
    if (lane < 4) st32_rlx(&G->key[(4 * j + lane) * 128 + slot], best);
    if ((win & 7) == g) {
      const bool up = win & 8;
      const float ra = up ? rstd[1] : rstd[0], rb = up ? bm[1] : bm[0];
      uint32_t x[16];
      #pragma unroll
      for (int i = 0; i < 16; i++) x[i] = pack_bf16(fmaf(up ? h[4*i+2] : h[4*i], ra, rb), fmaf(up ? h[4*i+3] : h[4*i+1], ra, rb));
      #pragma unroll
      for (int i = 0; i < 4; i++) st128_rlx(&G->cand[slot * DM + 64 * j + 16 * i + 4 * q], x[4*i], x[4*i+1], x[4*i+2], x[4*i+3]);
    }
    __syncwarp();
    if (TRKL == 1) bar_arrive(NB_G2E, 384);
    if (wg == 0) { TSW(27); }
    {
      const float a0 = 1.f + rstd[0], b0 = bm[0], a1 = 1.f + rstd[1], b1 = bm[1];
      #pragma unroll
      for (int k = 0; k < 8; k++)
        stsm4(((sb + OFF_OUT + wg * 8192 + sa) ^ ((k & 3) << 5)) + (k >> 2) * 16384,
              pack_bf16(fmaf(h[8*k], a0, b0), fmaf(h[8*k+1], a0, b0)),     pack_bf16(fmaf(h[8*k+2], a1, b1), fmaf(h[8*k+3], a1, b1)),
              pack_bf16(fmaf(h[8*k+4], a0, b0), fmaf(h[8*k+5], a0, b0)),   pack_bf16(fmaf(h[8*k+6], a1, b1), fmaf(h[8*k+7], a1, b1)));
      sts32(sb + OFF_EXC + 4 * warp, 16 * warp + win);
      __syncwarp();
      if (lane == 0) mbar_arrive(sb + B_OUT + 8 * (warp >> 1));
      if (lane < 16) {
        const uint4 v = lds128(sb + OFF_OUT + (lane >> 3) * 16384 + (16 * warp + win) * 128 + (((lane & 7) ^ (win & 7)) << 4));
        st128_rlx(&G->cand[slot * DM + 512 + 64 * j + 4 * lane], v.x, v.y, v.z, v.w);
      }
    }
    if (wg == 0) { TSW(28); }
    {
      if (!GPRE && f < NFFN_L) mbar_wait(sb + B_F + 8 * warp, 0);
      #pragma unroll
      for (int ks = GPRE; ks < GRES; ks++) getw(ks);
      if (wg == 0) { TSW(15); }
      bar_sync(NB_XS, 384);
      if (wg == 0) { TSW(19); }
      uint4 xs[4];
      #pragma unroll
      for (int i = 0; i < 4; i++) xs[i] = lds128(sb + OFF_XSEL + 256 * warp + 64 * i + 16 * q);
      float d[4][4];
      #pragma unroll
      for (int ks = 0; ks < 8; ks++) {
        if (ks >= 1 && GRES + ks - 1 < 8) getw(GRES + ks - 1);
        #pragma unroll
        for (int m = 0; m < 4; m++) {
          if (ks == 0) { d[m][0] = 0.f; d[m][1] = 0.f; d[m][2] = 0.f; d[m][3] = 0.f; }
          mma16816(d[m][0], d[m][1], d[m][2], d[m][3], wa[ks][m][0], wa[ks][m][1], wa[ks][m][2], wa[ks][m][3],
                   (ks & 1) ? xs[ks >> 1].z : xs[ks >> 1].x, (ks & 1) ? xs[ks >> 1].w : xs[ks >> 1].y);
        }
      }
      if (q == 0) {
        #pragma unroll
        for (int m = 0; m < 8; m++) stsf(sb + OFF_GU + (8 * m + g) * 48 + 4 * warp, d[m >> 1][2 * (m & 1)]);
      }
      bar_arrive(NB_ACT, 384);
    }
    {
      if (warp == 0) {
        const uint32_t ky = __float_as_uint(ldsf(sb + OFF_KEY));
        const int kidx = 2047 - (ky & 2047), r = lane & (YR - 1), e = 3 * (lane / YR) + r;
        const float kr = __uint_as_float((ky & ~2047u) ^ ((ky >> 31) ? 0x80000000u : 0xfffff800u));
        const int col = 256 * (c >> 5) + 32 * (e & 4) + 32 * (c & 3) + 16 * (e & 1) + 4 * (e & 2) + ((c >> 2) & 7);
        const float sg = rcp(1.f + ex2(-LOG2E * kr));
        const float4* yp = &G->yacc[(r * 3 + min(lane / YR, 2)) * 128 + c];
        const uint32_t* bp = &G->cand[(kidx >> 4) * DM + 512 + (col >> 1)];
        uint32_t it = 0, base;
        uint4 v;
        do { v = ld128_rlx(yp); base = ld32_rlx(bp); } while (__any_sync(~0u, __uint_as_float(v.w) != (float)(NFFN / YR) || base == ~0u) && ++it < POLL_LIMIT);
        float y0 = __uint_as_float(v.x), y1 = __uint_as_float(v.y), y2 = __uint_as_float(v.z);
        #pragma unroll
        for (int o = 1; o < YR; o <<= 1) { y0 += __shfl_xor_sync(~0u, y0, o); y1 += __shfl_xor_sync(~0u, y1, o); y2 += __shfl_xor_sync(~0u, y2, o); }
        if (r < 3 && e < 8) P.out_p[(size_t)kidx * DM + col] = __float2bfloat16(fmaf(r == 0 ? y0 : r == 1 ? y1 : y2, sg, (col & 1) ? bf_hi(base) : bf_lo(base)));
        if (c == 0 && lane == 0) st32_rlx(&G->epoch, __float_as_uint(ldsf(sb + OFF_EP)));
      }
      if (warp == 0) { TSW(22); }
      if (wg == 0) { TDUMP(); }
    }
  }
  if (wg == 2) {
    uint32_t wf[16][2][4];
    {
      const uint32_t wb = sb + OFF_S + 16384 * (wp & 1) + ((lane & 7) + ((lane >> 4) << 3)) * 128 + ((((lane >> 3) & 1) ^ (lane & 7)) << 4);
      if (f < NFFN_L) mbar_wait(sb + B_WD + 8 * wp, 0);
      if (wp == 0) { TK(61); }
      #pragma unroll
      for (int i = 0; i < 32; i++) ldsm4t((wb ^ (((i >> 1) & 3) << 5)) + (i >> 3) * 4096 + (i & 1) * 2048, wf[i >> 1][i & 1][0], wf[i >> 1][i & 1][1], wf[i >> 1][i & 1][2], wf[i >> 1][i & 1][3]);
      fence_async_smem();
      __syncwarp();
      if (lane == 0) mbar_arrive(sb + B_WC + 8 * wp);
      if (wp == 0) { TK(62); }
    }
    bar_sync(NB_G2E, TRKL == 3 ? 256 : 384);
    {
      uint32_t cur = 0;
      uint4 v;
      #pragma unroll 1
      for (uint32_t it = 0; it < POLL_LIMIT; it++) {
        const uint4 kx = ld128_rlx(&G->key[(c & 31) * 128 + 4 * lane]);
        v = ld128_rlx(&G->cand[((~cur >> 4) & 127) * DM + 4 * t]);
        uint32_t best;
        asm volatile("redux.sync.max.u32 %0, %1, 0xffffffff;" : "=r"(best) : "r"(max(max(kx.x, kx.y), max(kx.z, kx.w))));
        if (!__any_sync(~0u, min(min(kx.x, kx.y), min(kx.z, kx.w)) == 0 || v.w == ~0u) && best == cur) break;
        cur = best;
      }
      sts128(sb + OFF_XSEL + 16 * t, v.x, v.y, v.z, v.w);
      sts32(sb + OFF_KEY, cur);
      bar_arrive(NB_XS, 384);
      if (t == 0) mbar_arrive(sb + B_XS);
      TSW(18);
      bar_sync(NB_ACT, 384);
    }
    float gu[2];
    #pragma unroll
    for (int i = 0; i < 2; i++) {
      const uint4 v0 = lds128(sb + OFF_GU + (32 * i + lane) * 48), v1 = lds128(sb + OFF_GU + (32 * i + lane) * 48 + 16);
      gu[i] = ((__uint_as_float(v0.x) + __uint_as_float(v0.y)) + (__uint_as_float(v0.z) + __uint_as_float(v0.w))) +
              ((__uint_as_float(v1.x) + __uint_as_float(v1.y)) + (__uint_as_float(v1.z) + __uint_as_float(v1.w)));
    }
    const float act = gu[0] * gu[1] * rcp(1.f + ex2(-LOG2E * gu[0]));
    const uint32_t ap = pack_bf16(act, __shfl_down_sync(~0u, act, 1));
    uint32_t bf[4];
    #pragma unroll
    for (int i = 0; i < 4; i++) bf[i] = __shfl_sync(~0u, ap, 2 * q + 8 * i);
    TSW(20);
    float d[16][4];
    #pragma unroll
    for (int k = 0; k < 2; k++)
      #pragma unroll
      for (int i = 0; i < 16; i++) {
        if (k == 0) { d[i][0] = 0.f; d[i][1] = 0.f; d[i][2] = 0.f; d[i][3] = 0.f; }
        mma16816(d[i][0], d[i][1], d[i][2], d[i][3], wf[i][k][0], wf[i][k][1], wf[i][k][2], wf[i][k][3], bf[2*k], bf[2*k+1]);
      }
    float y[9];
    #pragma unroll
    for (int e = 0; e < 8; e++) {
      const int n = 2 * (e & 4) + (e & 1);
      const float lo = (q & 1) ? d[n + 2][e & 2] : d[n][e & 2], hi = (q & 1) ? d[n + 6][e & 2] : d[n + 4][e & 2];
      y[e] = (q & 2) ? hi : lo;
    }
    y[8] = 0.f;
    if (f < NFFN) {
      #pragma unroll
      for (int i = 0; i < 3; i++) red_add_f32x4(&G->yacc[((f & (YR - 1)) * 3 + i) * 128 + t], y[3*i], y[3*i+1], y[3*i+2], 1.f);
    }
    TSW(21);
  }
  }
  cluster_wait();
}

typedef CUresult (*EncodeFn)(CUtensorMap*, CUtensorMapDataType, cuuint32_t, void*, const cuuint64_t*, const cuuint64_t*,
                             const cuuint32_t*, const cuuint32_t*, CUtensorMapInterleave, CUtensorMapSwizzle,
                             CUtensorMapL2promotion, CUtensorMapFloatOOBfill);

void make_map(EncodeFn enc, CUtensorMap* m, const void* p, int n, const cuuint64_t* dims, const cuuint64_t* str, const cuuint32_t* box,
              CUtensorMapSwizzle sw, CUtensorMapL2promotion promo) {
  cuuint32_t es[5] = {1, 1, 1, 1, 1};
  enc(m, CU_TENSOR_MAP_DATA_TYPE_BFLOAT16, n, const_cast<void*>(p), dims, str, box, es, CU_TENSOR_MAP_INTERLEAVE_NONE, sw, promo,
      CU_TENSOR_MAP_FLOAT_OOB_FILL_NONE);
}
void map2(EncodeFn enc, CUtensorMap* m, const void* p, uint64_t cols, uint64_t rows, uint32_t bc, uint32_t br, CUtensorMapSwizzle sw,
          CUtensorMapL2promotion promo) {
  const cuuint64_t dims[2] = {cols, rows}, str[1] = {cols * 2};
  const cuuint32_t box[2] = {bc, br};
  make_map(enc, m, p, 2, dims, str, box, sw, promo);
}
void map3(EncodeFn enc, CUtensorMap* m, const void* p, uint64_t cols, uint64_t rows, uint32_t br, uint32_t nb) {
  const cuuint64_t dims[3] = {64, rows, cols / 64}, str[2] = {cols * 2, 128};
  const cuuint32_t box[3] = {64, br, nb};
  make_map(enc, m, p, 3, dims, str, box, CU_TENSOR_MAP_SWIZZLE_128B, CU_TENSOR_MAP_L2_PROMOTION_L2_128B);
}

}

extern "C" void kernel_launch(void* const* d_in, const int* in_sizes, int n_in, void* d_out, int out_size) {
  (void)in_sizes; (void)n_in; (void)out_size;
  static EncodeFn enc = nullptr;
  static void* o_ptr = nullptr;
  if (!enc) {
    void* f = nullptr; cudaDriverEntryPointQueryResult qr;
    cudaGetDriverEntryPoint("cuTensorMapEncodeTiled", &f, cudaEnableDefault, &qr);
    enc = (EncodeFn)f;
    cudaGetSymbolAddress(&o_ptr, g_scr);
    cudaFuncSetAttribute(fused_kernel, cudaFuncAttributeMaxDynamicSharedMemorySize, SMEM_BYTES);
  }
  const bf16* x = (const bf16*)d_in[0];
  const bf16* wqkv = (const bf16*)d_in[1];
  const bf16* wphi = (const bf16*)d_in[2];
  const bf16* wo = (const bf16*)d_in[3];
  const bf16* wr = (const bf16*)d_in[5];
  const bf16* wgate = (const bf16*)d_in[6];
  const bf16* wup = (const bf16*)d_in[7];
  const bf16* wdown = (const bf16*)d_in[8];
  Params P;
  const CUtensorMapSwizzle S128 = CU_TENSOR_MAP_SWIZZLE_128B, S64 = CU_TENSOR_MAP_SWIZZLE_64B;
  const CUtensorMapL2promotion L128 = CU_TENSOR_MAP_L2_PROMOTION_L2_128B, L256 = CU_TENSOR_MAP_L2_PROMOTION_L2_256B,
                               L64 = CU_TENSOR_MAP_L2_PROMOTION_L2_64B;
  map2(enc, &P.x128, x, DM, SEQ, 64, 128, S128, L256);
  map2(enc, &P.x64, x, DM, SEQ, 64, 64, S128, L128);
  {
    const cuuint64_t dims[4] = {64, DM, 16, 3}, str[3] = {6 * DM, 128, 2 * DM};
    const cuuint32_t box[4] = {64, 64, 1, 2};
    make_map(enc, &P.wkv, wqkv, 4, dims, str, box, S128, L128);
  }
  map3(enc, &P.wq, wqkv, 3 * DM, DM, 64, 2);
  for (int i = 0; i < 2; i++) {
    const cuuint64_t dims[5] = {DM, (cuuint64_t)(DM - 94 - 64 * i), 4, 4, 2}, str[4] = {2 * DM, 16 * DM, 4 * DM, (cuuint64_t)(128 * DM) << i};
    const cuuint32_t box[5] = {64, 2, 4, 4, 2};
    make_map(enc, &P.wo[i], wo, 5, dims, str, box, S128, L128);
  }
  map3(enc, &P.wd, wdown, DM, FF, 32, 4);
  map2(enc, &P.wg, wgate, FF, DM, 32, 128, S64, L64);
  map2(enc, &P.wu, wup, FF, DM, 32, 128, S64, L64);
  map2(enc, &P.tg, wgate, FF, DM, 8, 16, CU_TENSOR_MAP_SWIZZLE_NONE, L128);
  map2(enc, &P.tu, wup, FF, DM, 8, 16, CU_TENSOR_MAP_SWIZZLE_NONE, L128);
  map2(enc, &P.td, wdown, 128, FF * 8, 8, 16, CU_TENSOR_MAP_SWIZZLE_NONE, L256);
  map2(enc, &P.xs, x, DM, SEQ, 128, 16, CU_TENSOR_MAP_SWIZZLE_NONE, L256);
  map2(enc, &P.ws, wqkv, 3 * DM, DM, 16, 128, CU_TENSOR_MAP_SWIZZLE_NONE, L128);
  map2(enc, &P.qs, wqkv, 3 * DM, DM, 32, 128, CU_TENSOR_MAP_SWIZZLE_NONE, L64);
  map2(enc, &P.phi, wphi, 32, 1024, 32, 32, S64, L64);
  P.x = x; P.wqkv = wqkv; P.wo_p = wo; P.wd_p = wdown; P.wg_p = wgate; P.wu_p = wup; P.wr = wr; P.out_p = (bf16*)d_out; P.g = (Scratch*)o_ptr; P.zero = 0;

  cudaLaunchConfig_t cfg = {};
  cfg.gridDim = dim3(128); cfg.blockDim = dim3(512); cfg.dynamicSmemBytes = SMEM_BYTES; cfg.stream = cudaStreamPerThread;
  cudaLaunchAttribute at[1];
  at[0].id = cudaLaunchAttributeClusterDimension; at[0].val.clusterDim.x = 2; at[0].val.clusterDim.y = 1; at[0].val.clusterDim.z = 1;
  cfg.attrs = at; cfg.numAttrs = 1;
  cudaLaunchKernelEx(&cfg, fused_kernel, P);
}
```

```cpp
#include <cuda_runtime.h>
#include <cuda.h>
#include <cuda_bf16.h>
#include <stdint.h>

namespace {

typedef __nv_bfloat16 bf16;

__device__ __forceinline__ uint32_t smem_u32(const void* p){ return (uint32_t)__cvta_generic_to_shared(p); }
__device__ __forceinline__ void mbar_init(uint32_t bar, uint32_t cnt){ asm volatile("mbarrier.init.shared::cta.b64 [%0], %1;"::"r"(bar),"r"(cnt):"memory"); }
__device__ __forceinline__ void mbar_expect_tx(uint32_t bar, uint32_t bytes){ asm volatile("mbarrier.arrive.expect_tx.shared::cta.b64 _, [%0], %1;"::"r"(bar),"r"(bytes):"memory"); }
__device__ __forceinline__ void mbar_arrive(uint32_t bar){ asm volatile("mbarrier.arrive.shared::cta.b64 _, [%0];"::"r"(bar):"memory"); }
__device__ __forceinline__ uint32_t mapa(uint32_t addr, uint32_t cta){ uint32_t r; asm volatile("mapa.shared::cluster.u32 %0, %1, %2;":"=r"(r):"r"(addr),"r"(cta)); return r; }
__device__ __forceinline__ void mbar_arrive_at(uint32_t bar, uint32_t cta, uint32_t cnt){
  asm volatile("{\n.reg .b32 ra;\nmapa.shared::cluster.u32 ra, %0, %1;\nmbarrier.arrive.shared::cluster.b64 _, [ra], %2;\n}\n"::"r"(bar),"r"(cta),"r"(cnt):"memory"); }
__device__ __forceinline__ void mbar_arrive_remote(uint32_t cluster_addr, uint32_t cnt){
  asm volatile("mbarrier.arrive.shared::cluster.b64 _, [%0], %1;"::"r"(cluster_addr),"r"(cnt):"memory"); }
__device__ __forceinline__ void mbar_wait(uint32_t bar, uint32_t parity){
  asm volatile("{\n.reg .pred p;\n.reg .u32 c;\nmov.u32 c, 0;\nLW:\nmbarrier.try_wait.parity.shared::cta.b64 p, [%0], %1;\n@p bra LD;\nadd.u32 c, c, 1;\nsetp.lt.u32 p, c, 2000000;\n@p bra LW;\ntrap;\nLD:\n}\n"::"r"(bar),"r"(parity):"memory"); }
__device__ __forceinline__ void mbar_wait2(uint32_t bar0, uint32_t par0, uint32_t bar1, uint32_t par1){
  asm volatile("{\n.reg .pred p, q;\n.reg .u32 c;\nmov.u32 c, 0;\nLW:\nmbarrier.try_wait.parity.shared::cta.b64 p, [%0], %1;\nmbarrier.try_wait.parity.shared::cta.b64 q, [%2], %3;\nand.pred p, p, q;\n@p bra LD;\nadd.u32 c, c, 1;\nsetp.lt.u32 p, c, 2000000;\n@p bra LW;\ntrap;\nLD:\n}\n"::"r"(bar0),"r"(par0),"r"(bar1),"r"(par1):"memory"); }
__device__ __forceinline__ bool mbar_test2(uint32_t bar0, uint32_t par0, uint32_t bar1, uint32_t par1){
  uint32_t r;
  asm volatile("{\n.reg .pred p, q;\nmbarrier.test_wait.parity.shared::cta.b64 p, [%1], %2;\nmbarrier.test_wait.parity.shared::cta.b64 q, [%3], %4;\nand.pred p, p, q;\nselp.u32 %0, 1, 0, p;\n}\n":"=r"(r):"r"(bar0),"r"(par0),"r"(bar1),"r"(par1):"memory");
  return r; }
__device__ __forceinline__ void tma_2d(uint32_t dst, const CUtensorMap* m, int c0, int c1, uint32_t bar){
  asm volatile("cp.async.bulk.tensor.2d.shared::cluster.global.mbarrier::complete_tx::bytes [%0], [%1, {%3, %4}], [%2];"::"r"(dst),"l"(m),"r"(bar),"r"(c0),"r"(c1):"memory"); }
__device__ __forceinline__ void tma_2d_mc(uint32_t dst, const CUtensorMap* m, int c0, int c1, uint32_t bar){
  asm volatile("cp.async.bulk.tensor.2d.shared::cluster.global.mbarrier::complete_tx::bytes.multicast::cluster [%0], [%1, {%3, %4}], [%2], %5;"::"r"(dst),"l"(m),"r"(bar),"r"(c0),"r"(c1),"h"((uint16_t)3):"memory"); }
__device__ __forceinline__ void tma_2d_mc_h(uint32_t dst, const CUtensorMap* m, int c0, int c1, uint32_t bar, uint64_t pol){
  asm volatile("cp.async.bulk.tensor.2d.shared::cluster.global.mbarrier::complete_tx::bytes.multicast::cluster.L2::cache_hint [%0], [%1, {%3, %4}], [%2], %5, %6;"::"r"(dst),"l"(m),"r"(bar),"r"(c0),"r"(c1),"h"((uint16_t)3),"l"(pol):"memory"); }
__device__ __forceinline__ void tma_4d(uint32_t dst, const CUtensorMap* m, int c0, int c1, int c2, int c3, uint32_t bar){
  asm volatile("cp.async.bulk.tensor.4d.shared::cluster.global.mbarrier::complete_tx::bytes [%0], [%1, {%3, %4, %5, %6}], [%2];"::"r"(dst),"l"(m),"r"(bar),"r"(c0),"r"(c1),"r"(c2),"r"(c3):"memory"); }
__device__ __forceinline__ uint64_t policy_evict_first(){ uint64_t p; asm volatile("createpolicy.fractional.L2::evict_first.b64 %0, 1.0;":"=l"(p)); return p; }
__device__ __forceinline__ uint64_t policy_evict_normal(){ uint64_t p; asm("createpolicy.fractional.L2::evict_normal.b64 %0, 1.0;":"=l"(p)); return p; }
__device__ __forceinline__ void tma_3d_h(uint32_t dst, const CUtensorMap* m, int c0, int c1, int c2, uint32_t bar, uint64_t pol){
  asm volatile("cp.async.bulk.tensor.3d.shared::cluster.global.mbarrier::complete_tx::bytes.L2::cache_hint [%0], [%1, {%3, %4, %5}], [%2], %6;"::"r"(dst),"l"(m),"r"(bar),"r"(c0),"r"(c1),"r"(c2),"l"(pol):"memory"); }
__device__ __forceinline__ void tma_4d_h(uint32_t dst, const CUtensorMap* m, int c0, int c1, int c2, int c3, uint32_t bar, uint64_t pol){
  asm volatile("cp.async.bulk.tensor.4d.shared::cluster.global.mbarrier::complete_tx::bytes.L2::cache_hint [%0], [%1, {%3, %4, %5, %6}], [%2], %7;"::"r"(dst),"l"(m),"r"(bar),"r"(c0),"r"(c1),"r"(c2),"r"(c3),"l"(pol):"memory"); }
__device__ __forceinline__ void red_add_f32x4(float4* p, float x, float y, float z, float w){ asm volatile("red.relaxed.gpu.global.add.v4.f32 [%0], {%1,%2,%3,%4};"::"l"(p),"f"(x),"f"(y),"f"(z),"f"(w):"memory"); }
__device__ __forceinline__ void tma_5d_h(uint32_t dst, const CUtensorMap* m, int c0, int c1, uint32_t bar, uint64_t pol){
  asm volatile("cp.async.bulk.tensor.5d.shared::cluster.global.mbarrier::complete_tx::bytes.L2::cache_hint [%0], [%1, {%3, %4, 0, 0, 0}], [%2], %5;"::"r"(dst),"l"(m),"r"(bar),"r"(c0),"r"(c1),"l"(pol):"memory"); }
__device__ __forceinline__ void tma_store_2d(const CUtensorMap* m, int c0, int c1, uint32_t src){
  asm volatile("cp.async.bulk.tensor.2d.global.shared::cta.bulk_group [%0, {%2, %3}], [%1];"::"l"(m),"r"(src),"r"(c0),"r"(c1):"memory"); }
__device__ __forceinline__ void bulk_commit(){ asm volatile("cp.async.bulk.commit_group;":::"memory"); }
__device__ __forceinline__ void bulk_wait_all(){ asm volatile("cp.async.bulk.wait_group 0;":::"memory"); }
__device__ __forceinline__ void fence_async_global(){ asm volatile("fence.proxy.async.global;":::"memory"); }
__device__ __forceinline__ bool elect_one(){ uint32_t p; asm volatile("{\n.reg .pred P;\nelect.sync _|P, 0xffffffff;\nselp.b32 %0, 1, 0, P;\n}\n":"=r"(p)); return p; }
__device__ __forceinline__ void bulk_prefetch(const void* p, uint32_t bytes){
  asm volatile("cp.async.bulk.prefetch.L2.global [%0], %1;"::"l"(p),"r"(bytes):"memory"); }
__device__ __forceinline__ void bulk_s2peer(uint32_t dst_cluster, uint32_t src, uint32_t bytes, uint32_t bar_cluster){
  asm volatile("cp.async.bulk.shared::cluster.shared::cta.mbarrier::complete_tx::bytes [%0], [%1], %2, [%3];"::"r"(dst_cluster),"r"(src),"r"(bytes),"r"(bar_cluster):"memory"); }
__device__ __forceinline__ void bulk_g2s_mc(uint32_t dst, const void* src, uint32_t bytes, uint32_t bar, uint64_t pol){
  asm volatile("cp.async.bulk.shared::cluster.global.mbarrier::complete_tx::bytes.multicast::cluster.L2::cache_hint [%0], [%1], %2, [%3], %4, %5;"::"r"(dst),"l"(src),"r"(bytes),"r"(bar),"h"((uint16_t)3),"l"(pol):"memory"); }
__device__ __forceinline__ void prefetch_map(const CUtensorMap* m){ asm volatile("prefetch.tensormap [%0];"::"l"(m):"memory"); }
__device__ __forceinline__ void fence_async_smem(){ asm volatile("fence.proxy.async.shared::cta;":::"memory"); }
__device__ __forceinline__ void fence_acquire_gpu(){ asm volatile("fence.acquire.gpu;":::"memory"); }
__device__ __forceinline__ void fence_gpu(){ asm volatile("fence.acq_rel.gpu;":::"memory"); }
__device__ __forceinline__ void wg_fence(){ asm volatile("wgmma.fence.sync.aligned;":::"memory"); }
__device__ __forceinline__ void wg_commit(){ asm volatile("wgmma.commit_group.sync.aligned;":::"memory"); }
template<int N> __device__ __forceinline__ void wg_wait(){ asm volatile("wgmma.wait_group.sync.aligned %0;"::"n"(N):"memory"); }
template<int N> __device__ __forceinline__ void fence_regs(float (&d)[N]){
  #pragma unroll
  for(int i=0;i<N;i++) asm volatile("":"+f"(d[i])::"memory"); }
__device__ __forceinline__ void bar_sync(int id, int n){ asm volatile("bar.sync %0, %1;"::"r"(id),"r"(n):"memory"); }
__device__ __forceinline__ void bar_arrive(int id, int n){ asm volatile("bar.arrive %0, %1;"::"r"(id),"r"(n):"memory"); }
__device__ __forceinline__ void cluster_arrive(){ asm volatile("barrier.cluster.arrive.relaxed.aligned;":::"memory"); }
__device__ __forceinline__ void cluster_wait(){ asm volatile("barrier.cluster.wait.aligned;":::"memory"); }
__host__ __device__ constexpr uint32_t dlo(uint32_t addr, uint32_t lbo){ return (addr >> 4) | ((lbo >> 4) << 16); }
__host__ __device__ constexpr uint32_t dhi(uint32_t sbo, uint32_t sw){ return (sbo >> 4) | (sw << 30); }
constexpr uint32_t H128 = dhi(1024, 1), H64 = dhi(512, 2), H0 = dhi(128, 0);
__device__ __forceinline__ uint32_t pack_bf16(float lo, float hi){ uint32_t r; asm("cvt.rn.bf16x2.f32 %0, %1, %2;":"=r"(r):"f"(hi),"f"(lo)); return r; }
__device__ __forceinline__ float bf_lo(uint32_t v){ return __uint_as_float(v<<16); }
__device__ __forceinline__ float bf_hi(uint32_t v){ return __uint_as_float(v&0xffff0000u); }
__device__ __forceinline__ float ex2(float x){ float r; asm("ex2.approx.ftz.f32 %0, %1;":"=f"(r):"f"(x)); return r; }
__device__ __forceinline__ float rcp(float x){ float r; asm("rcp.approx.ftz.f32 %0, %1;":"=f"(r):"f"(x)); return r; }
__device__ __forceinline__ void stsm4(uint32_t addr, uint32_t a, uint32_t b, uint32_t c, uint32_t d){
  asm volatile("stmatrix.sync.aligned.m8n8.x4.shared.b16 [%0], {%1,%2,%3,%4};"::"r"(addr),"r"(a),"r"(b),"r"(c),"r"(d)); }
__device__ __forceinline__ void stsm2(uint32_t addr, uint32_t a, uint32_t b){
  asm volatile("stmatrix.sync.aligned.m8n8.x2.shared.b16 [%0], {%1,%2};"::"r"(addr),"r"(a),"r"(b)); }
__device__ __forceinline__ void mma16816(float& d0, float& d1, float& d2, float& d3, uint32_t a0, uint32_t a1, uint32_t a2, uint32_t a3, uint32_t b0, uint32_t b1){
  asm volatile("mma.sync.aligned.m16n8k16.row.col.f32.bf16.bf16.f32 {%0,%1,%2,%3}, {%4,%5,%6,%7}, {%8,%9}, {%0,%1,%2,%3};"
               : "+f"(d0), "+f"(d1), "+f"(d2), "+f"(d3) : "r"(a0), "r"(a1), "r"(a2), "r"(a3), "r"(b0), "r"(b1)); }
__device__ __forceinline__ void ldsm4(uint32_t addr, uint32_t& a, uint32_t& b, uint32_t& c, uint32_t& d){
  asm volatile("ldmatrix.sync.aligned.m8n8.x4.shared.b16 {%0,%1,%2,%3}, [%4];":"=r"(a),"=r"(b),"=r"(c),"=r"(d):"r"(addr):"memory"); }
__device__ __forceinline__ void ldsm4t(uint32_t addr, uint32_t& a, uint32_t& b, uint32_t& c, uint32_t& d){
  asm volatile("ldmatrix.sync.aligned.m8n8.x4.trans.shared.b16 {%0,%1,%2,%3}, [%4];":"=r"(a),"=r"(b),"=r"(c),"=r"(d):"r"(addr):"memory"); }
__device__ __forceinline__ void sts32(uint32_t a, uint32_t v){ asm volatile("st.shared.b32 [%0], %1;"::"r"(a),"r"(v):"memory"); }
__device__ __forceinline__ void stsf(uint32_t a, float v){ asm volatile("st.shared.f32 [%0], %1;"::"r"(a),"f"(v):"memory"); }
__device__ __forceinline__ void sts64(uint32_t a, uint32_t x, uint32_t y){ asm volatile("st.shared.v2.b32 [%0], {%1,%2};"::"r"(a),"r"(x),"r"(y):"memory"); }
__device__ __forceinline__ void sts128(uint32_t a, uint32_t x, uint32_t y, uint32_t z, uint32_t w){ asm volatile("st.shared.v4.b32 [%0], {%1,%2,%3,%4};"::"r"(a),"r"(x),"r"(y),"r"(z),"r"(w):"memory"); }
__device__ __forceinline__ float ldsf(uint32_t a){ float v; asm volatile("ld.shared.f32 %0, [%1];":"=f"(v):"r"(a):"memory"); return v; }
__device__ __forceinline__ float2 lds64f(uint32_t a){ float2 v; asm volatile("ld.shared.v2.f32 {%0,%1}, [%2];":"=f"(v.x),"=f"(v.y):"r"(a):"memory"); return v; }
__device__ __forceinline__ uint4 lds128(uint32_t a){ uint4 v; asm volatile("ld.shared.v4.u32 {%0,%1,%2,%3}, [%4];":"=r"(v.x),"=r"(v.y),"=r"(v.z),"=r"(v.w):"r"(a):"memory"); return v; }
__device__ __forceinline__ uint4 ld128_keep(const void* p){ uint4 v; asm volatile("ld.global.v4.u32 {%0,%1,%2,%3}, [%4];":"=r"(v.x),"=r"(v.y),"=r"(v.z),"=r"(v.w):"l"(p):"memory"); return v; }
__device__ __forceinline__ uint4 ld128_rlx(const void* p){ uint4 v; asm volatile("ld.relaxed.gpu.global.v4.u32 {%0,%1,%2,%3}, [%4];":"=r"(v.x),"=r"(v.y),"=r"(v.z),"=r"(v.w):"l"(p):"memory"); return v; }
__device__ __forceinline__ uint32_t ld32_rlx(const void* p){ uint32_t v; asm volatile("ld.relaxed.gpu.global.u32 %0, [%1];":"=r"(v):"l"(p):"memory"); return v; }
__device__ __forceinline__ void st128_rlx(void* p, uint32_t x, uint32_t y, uint32_t z, uint32_t w){ asm volatile("st.relaxed.gpu.global.v4.u32 [%0], {%1,%2,%3,%4};"::"l"(p),"r"(x),"r"(y),"r"(z),"r"(w):"memory"); }
__device__ __forceinline__ void st64_rlx(void* p, uint32_t x, uint32_t y){ asm volatile("st.relaxed.gpu.global.v2.u32 [%0], {%1,%2};"::"l"(p),"r"(x),"r"(y):"memory"); }
__device__ __forceinline__ void st32_rlx(void* p, uint32_t x){ asm volatile("st.relaxed.gpu.global.u32 [%0], %1;"::"l"(p),"r"(x):"memory"); }
__device__ __forceinline__ uint32_t tagw(float x, uint32_t t){ return (__float_as_uint(x) & ~3u) | t; }
__device__ __forceinline__ float untag(uint32_t w){ return __uint_as_float(w & ~3u); }

template<int TA, int TB, uint32_t HA, uint32_t HB> __device__ __forceinline__ void wgmma_ss_n128(float (&d)[64], uint32_t da, uint32_t db, int scale_d){
  asm volatile("{\n.reg .pred p;\n.reg .b64 a, b;\nsetp.ne.b32 p, %70, 0;\nmov.b64 a, {%64, %68};\nmov.b64 b, {%65, %69};\n"
  "wgmma.mma_async.sync.aligned.m64n128k16.f32.bf16.bf16 {%0, %1, %2, %3, %4, %5, %6, %7, %8, %9, %10, %11, %12, %13, %14, %15, %16, %17, %18, %19, %20, %21, %22, %23, %24, %25, %26, %27, %28, %29, %30, %31, %32, %33, %34, %35, %36, %37, %38, %39, %40, %41, %42, %43, %44, %45, %46, %47, %48, %49, %50, %51, %52, %53, %54, %55, %56, %57, %58, %59, %60, %61, %62, %63}, a, b, p, 1, 1, %66, %67;\n}\n"
  : "+f"(d[0]), "+f"(d[1]), "+f"(d[2]), "+f"(d[3]), "+f"(d[4]), "+f"(d[5]), "+f"(d[6]), "+f"(d[7]), "+f"(d[8]), "+f"(d[9]), "+f"(d[10]), "+f"(d[11]), "+f"(d[12]), "+f"(d[13]), "+f"(d[14]), "+f"(d[15]), "+f"(d[16]), "+f"(d[17]), "+f"(d[18]), "+f"(d[19]), "+f"(d[20]), "+f"(d[21]), "+f"(d[22]), "+f"(d[23]), "+f"(d[24]), "+f"(d[25]), "+f"(d[26]), "+f"(d[27]), "+f"(d[28]), "+f"(d[29]), "+f"(d[30]), "+f"(d[31]), "+f"(d[32]), "+f"(d[33]), "+f"(d[34]), "+f"(d[35]), "+f"(d[36]), "+f"(d[37]), "+f"(d[38]), "+f"(d[39]), "+f"(d[40]), "+f"(d[41]), "+f"(d[42]), "+f"(d[43]), "+f"(d[44]), "+f"(d[45]), "+f"(d[46]), "+f"(d[47]), "+f"(d[48]), "+f"(d[49]), "+f"(d[50]), "+f"(d[51]), "+f"(d[52]), "+f"(d[53]), "+f"(d[54]), "+f"(d[55]), "+f"(d[56]), "+f"(d[57]), "+f"(d[58]), "+f"(d[59]), "+f"(d[60]), "+f"(d[61]), "+f"(d[62]), "+f"(d[63])
  : "r"(da), "r"(db), "n"(TA), "n"(TB), "n"(HA), "n"(HB), "r"(scale_d));
}
template<int TA, int TB, uint32_t HA, uint32_t HB> __device__ __forceinline__ void wgmma_sa_n128(float (&d)[64], uint32_t da, uint32_t db){
  asm volatile("{\n.reg .pred p;\n.reg .b64 a, b;\nsetp.ne.b32 p, 1, 0;\nmov.b64 a, {%64, %68};\nmov.b64 b, {%65, %69};\n"
  "wgmma.mma_async.sync.aligned.m64n128k16.f32.bf16.bf16 {%0, %1, %2, %3, %4, %5, %6, %7, %8, %9, %10, %11, %12, %13, %14, %15, %16, %17, %18, %19, %20, %21, %22, %23, %24, %25, %26, %27, %28, %29, %30, %31, %32, %33, %34, %35, %36, %37, %38, %39, %40, %41, %42, %43, %44, %45, %46, %47, %48, %49, %50, %51, %52, %53, %54, %55, %56, %57, %58, %59, %60, %61, %62, %63}, a, b, p, 1, 1, %66, %67;\n}\n"
  : "+f"(d[0]), "+f"(d[1]), "+f"(d[2]), "+f"(d[3]), "+f"(d[4]), "+f"(d[5]), "+f"(d[6]), "+f"(d[7]), "+f"(d[8]), "+f"(d[9]), "+f"(d[10]), "+f"(d[11]), "+f"(d[12]), "+f"(d[13]), "+f"(d[14]), "+f"(d[15]), "+f"(d[16]), "+f"(d[17]), "+f"(d[18]), "+f"(d[19]), "+f"(d[20]), "+f"(d[21]), "+f"(d[22]), "+f"(d[23]), "+f"(d[24]), "+f"(d[25]), "+f"(d[26]), "+f"(d[27]), "+f"(d[28]), "+f"(d[29]), "+f"(d[30]), "+f"(d[31]), "+f"(d[32]), "+f"(d[33]), "+f"(d[34]), "+f"(d[35]), "+f"(d[36]), "+f"(d[37]), "+f"(d[38]), "+f"(d[39]), "+f"(d[40]), "+f"(d[41]), "+f"(d[42]), "+f"(d[43]), "+f"(d[44]), "+f"(d[45]), "+f"(d[46]), "+f"(d[47]), "+f"(d[48]), "+f"(d[49]), "+f"(d[50]), "+f"(d[51]), "+f"(d[52]), "+f"(d[53]), "+f"(d[54]), "+f"(d[55]), "+f"(d[56]), "+f"(d[57]), "+f"(d[58]), "+f"(d[59]), "+f"(d[60]), "+f"(d[61]), "+f"(d[62]), "+f"(d[63])
  : "r"(da), "r"(db), "n"(TA), "n"(TB), "n"(HA), "n"(HB));
}
template<int TA, int TB, uint32_t HA, uint32_t HB> __device__ __forceinline__ void wgmma_sa_n40(float (&d)[20], uint32_t da, uint32_t db){
  asm volatile("{\n.reg .pred p;\n.reg .b64 a, b;\nsetp.ne.b32 p, 1, 0;\nmov.b64 a, {%20, %24};\nmov.b64 b, {%21, %25};\n"
  "wgmma.mma_async.sync.aligned.m64n40k16.f32.bf16.bf16 {%0, %1, %2, %3, %4, %5, %6, %7, %8, %9, %10, %11, %12, %13, %14, %15, %16, %17, %18, %19}, a, b, p, 1, 1, %22, %23;\n}\n"
  : "+f"(d[0]), "+f"(d[1]), "+f"(d[2]), "+f"(d[3]), "+f"(d[4]), "+f"(d[5]), "+f"(d[6]), "+f"(d[7]), "+f"(d[8]), "+f"(d[9]), "+f"(d[10]), "+f"(d[11]), "+f"(d[12]), "+f"(d[13]), "+f"(d[14]), "+f"(d[15]), "+f"(d[16]), "+f"(d[17]), "+f"(d[18]), "+f"(d[19])
  : "r"(da), "r"(db), "n"(TA), "n"(TB), "n"(HA), "n"(HB));
}
template<int TA, int TB, uint32_t HA, uint32_t HB> __device__ __forceinline__ void wgmma_sz_n40(float (&d)[20], uint32_t da, uint32_t db){
  asm volatile("{\n.reg .pred p;\n.reg .b64 a, b;\nsetp.ne.b32 p, 0, 0;\nmov.b64 a, {%20, %24};\nmov.b64 b, {%21, %25};\n"
  "wgmma.mma_async.sync.aligned.m64n40k16.f32.bf16.bf16 {%0, %1, %2, %3, %4, %5, %6, %7, %8, %9, %10, %11, %12, %13, %14, %15, %16, %17, %18, %19}, a, b, p, 1, 1, %22, %23;\n}\n"
  : "=f"(d[0]), "=f"(d[1]), "=f"(d[2]), "=f"(d[3]), "=f"(d[4]), "=f"(d[5]), "=f"(d[6]), "=f"(d[7]), "=f"(d[8]), "=f"(d[9]), "=f"(d[10]), "=f"(d[11]), "=f"(d[12]), "=f"(d[13]), "=f"(d[14]), "=f"(d[15]), "=f"(d[16]), "=f"(d[17]), "=f"(d[18]), "=f"(d[19])
  : "r"(da), "r"(db), "n"(TA), "n"(TB), "n"(HA), "n"(HB));
}
template<int TA, int TB, uint32_t HA, uint32_t HB> __device__ __forceinline__ void wgmma_sa_n32(float (&d)[16], uint32_t da, uint32_t db){
  asm volatile("{\n.reg .pred p;\n.reg .b64 a, b;\nsetp.ne.b32 p, 1, 0;\nmov.b64 a, {%16, %20};\nmov.b64 b, {%17, %21};\n"
  "wgmma.mma_async.sync.aligned.m64n32k16.f32.bf16.bf16 {%0, %1, %2, %3, %4, %5, %6, %7, %8, %9, %10, %11, %12, %13, %14, %15}, a, b, p, 1, 1, %18, %19;\n}\n"
  : "+f"(d[0]), "+f"(d[1]), "+f"(d[2]), "+f"(d[3]), "+f"(d[4]), "+f"(d[5]), "+f"(d[6]), "+f"(d[7]), "+f"(d[8]), "+f"(d[9]), "+f"(d[10]), "+f"(d[11]), "+f"(d[12]), "+f"(d[13]), "+f"(d[14]), "+f"(d[15])
  : "r"(da), "r"(db), "n"(TA), "n"(TB), "n"(HA), "n"(HB));
}
template<int TA, int TB, uint32_t HA, uint32_t HB> __device__ __forceinline__ void wgmma_ss_n32(float (&d)[16], uint32_t da, uint32_t db, int scale_d){
  asm volatile("{\n.reg .pred p;\n.reg .b64 a, b;\nsetp.ne.b32 p, %22, 0;\nmov.b64 a, {%16, %20};\nmov.b64 b, {%17, %21};\n"
  "wgmma.mma_async.sync.aligned.m64n32k16.f32.bf16.bf16 {%0, %1, %2, %3, %4, %5, %6, %7, %8, %9, %10, %11, %12, %13, %14, %15}, a, b, p, 1, 1, %18, %19;\n}\n"
  : "+f"(d[0]), "+f"(d[1]), "+f"(d[2]), "+f"(d[3]), "+f"(d[4]), "+f"(d[5]), "+f"(d[6]), "+f"(d[7]), "+f"(d[8]), "+f"(d[9]), "+f"(d[10]), "+f"(d[11]), "+f"(d[12]), "+f"(d[13]), "+f"(d[14]), "+f"(d[15])
  : "r"(da), "r"(db), "n"(TA), "n"(TB), "n"(HA), "n"(HB), "r"(scale_d));
}
template<int TB, uint32_t HB> __device__ __forceinline__ void wgmma_ra_n32(float (&d)[16], uint32_t a0, uint32_t a1, uint32_t a2, uint32_t a3, uint32_t db){
  asm volatile("{\n.reg .pred p;\n.reg .b64 a, b;\nsetp.ne.b32 p, 1, 0;\nmov.b64 b, {%20, %22};\n"
  "wgmma.mma_async.sync.aligned.m64n32k16.f32.bf16.bf16 {%0, %1, %2, %3, %4, %5, %6, %7, %8, %9, %10, %11, %12, %13, %14, %15}, {%16,%17,%18,%19}, b, p, 1, 1, %21;\n}\n"
  : "+f"(d[0]), "+f"(d[1]), "+f"(d[2]), "+f"(d[3]), "+f"(d[4]), "+f"(d[5]), "+f"(d[6]), "+f"(d[7]), "+f"(d[8]), "+f"(d[9]), "+f"(d[10]), "+f"(d[11]), "+f"(d[12]), "+f"(d[13]), "+f"(d[14]), "+f"(d[15])
  : "r"(a0), "r"(a1), "r"(a2), "r"(a3), "r"(db), "n"(TB), "n"(HB));
}
template<int TB, uint32_t HB> __device__ __forceinline__ void wgmma_rs_n32(float (&d)[16], uint32_t a0, uint32_t a1, uint32_t a2, uint32_t a3, uint32_t db, int scale_d){
  asm volatile("{\n.reg .pred p;\n.reg .b64 a, b;\nsetp.ne.b32 p, %23, 0;\nmov.b64 b, {%20, %22};\n"
  "wgmma.mma_async.sync.aligned.m64n32k16.f32.bf16.bf16 {%0, %1, %2, %3, %4, %5, %6, %7, %8, %9, %10, %11, %12, %13, %14, %15}, {%16,%17,%18,%19}, b, p, 1, 1, %21;\n}\n"
  : "+f"(d[0]), "+f"(d[1]), "+f"(d[2]), "+f"(d[3]), "+f"(d[4]), "+f"(d[5]), "+f"(d[6]), "+f"(d[7]), "+f"(d[8]), "+f"(d[9]), "+f"(d[10]), "+f"(d[11]), "+f"(d[12]), "+f"(d[13]), "+f"(d[14]), "+f"(d[15])
  : "r"(a0), "r"(a1), "r"(a2), "r"(a3), "r"(db), "n"(TB), "n"(HB), "r"(scale_d));
}
template<int TB, uint32_t HB> __device__ __forceinline__ void wgmma_ra_n40(float (&d)[20], uint32_t a0, uint32_t a1, uint32_t a2, uint32_t a3, uint32_t db){
  asm volatile("{\n.reg .pred p;\n.reg .b64 a, b;\nsetp.ne.b32 p, 1, 0;\nmov.b64 b, {%24, %26};\n"
  "wgmma.mma_async.sync.aligned.m64n40k16.f32.bf16.bf16 {%0, %1, %2, %3, %4, %5, %6, %7, %8, %9, %10, %11, %12, %13, %14, %15, %16, %17, %18, %19}, {%20,%21,%22,%23}, b, p, 1, 1, %25;\n}\n"
  : "+f"(d[0]), "+f"(d[1]), "+f"(d[2]), "+f"(d[3]), "+f"(d[4]), "+f"(d[5]), "+f"(d[6]), "+f"(d[7]), "+f"(d[8]), "+f"(d[9]), "+f"(d[10]), "+f"(d[11]), "+f"(d[12]), "+f"(d[13]), "+f"(d[14]), "+f"(d[15]), "+f"(d[16]), "+f"(d[17]), "+f"(d[18]), "+f"(d[19])
  : "r"(a0), "r"(a1), "r"(a2), "r"(a3), "r"(db), "n"(TB), "n"(HB));
}
template<int TB, uint32_t HB> __device__ __forceinline__ void wgmma_rz_n40(float (&d)[20], uint32_t a0, uint32_t a1, uint32_t a2, uint32_t a3, uint32_t db){
  asm volatile("{\n.reg .pred p;\n.reg .b64 a, b;\nsetp.ne.b32 p, 0, 0;\nmov.b64 b, {%24, %26};\n"
  "wgmma.mma_async.sync.aligned.m64n40k16.f32.bf16.bf16 {%0, %1, %2, %3, %4, %5, %6, %7, %8, %9, %10, %11, %12, %13, %14, %15, %16, %17, %18, %19}, {%20,%21,%22,%23}, b, p, 1, 1, %25;\n}\n"
  : "=f"(d[0]), "=f"(d[1]), "=f"(d[2]), "=f"(d[3]), "=f"(d[4]), "=f"(d[5]), "=f"(d[6]), "=f"(d[7]), "=f"(d[8]), "=f"(d[9]), "=f"(d[10]), "=f"(d[11]), "=f"(d[12]), "=f"(d[13]), "=f"(d[14]), "=f"(d[15]), "=f"(d[16]), "=f"(d[17]), "=f"(d[18]), "=f"(d[19])
  : "r"(a0), "r"(a1), "r"(a2), "r"(a3), "r"(db), "n"(TB), "n"(HB));
}
template<int TB, uint32_t HB> __device__ __forceinline__ void wgmma_ra_n8(float (&d)[4], uint32_t a0, uint32_t a1, uint32_t a2, uint32_t a3, uint32_t db){
  asm volatile("{\n.reg .pred p;\n.reg .b64 a, b;\nsetp.ne.b32 p, 1, 0;\nmov.b64 b, {%8, %10};\n"
  "wgmma.mma_async.sync.aligned.m64n8k16.f32.bf16.bf16 {%0, %1, %2, %3}, {%4,%5,%6,%7}, b, p, 1, 1, %9;\n}\n"
  : "+f"(d[0]), "+f"(d[1]), "+f"(d[2]), "+f"(d[3])
  : "r"(a0), "r"(a1), "r"(a2), "r"(a3), "r"(db), "n"(TB), "n"(HB));
}
template<int TB, uint32_t HB> __device__ __forceinline__ void wgmma_rz_n8(float (&d)[4], uint32_t a0, uint32_t a1, uint32_t a2, uint32_t a3, uint32_t db){
  asm volatile("{\n.reg .pred p;\n.reg .b64 a, b;\nsetp.ne.b32 p, 0, 0;\nmov.b64 b, {%8, %10};\n"
  "wgmma.mma_async.sync.aligned.m64n8k16.f32.bf16.bf16 {%0, %1, %2, %3}, {%4,%5,%6,%7}, b, p, 1, 1, %9;\n}\n"
  : "=f"(d[0]), "=f"(d[1]), "=f"(d[2]), "=f"(d[3])
  : "r"(a0), "r"(a1), "r"(a2), "r"(a3), "r"(db), "n"(TB), "n"(HB));
}

constexpr int SEQ = 2048, DM = 1024, FF = 3584;
constexpr float LOG2E = 1.4426950408889634f;
constexpr uint32_t POLL_LIMIT = 1u << 22;
#define NPRE0 1
#define NPREN 2
constexpr int NPRE = NPREN;
#define QW 0
#define RS_N 22
#define RS_D1 430
#define RS_D2 300
#define SKM 0x154
#define LAG 2
#define PF_T0 5000
#define PF_DT 800
#define NFFN_L NFFN
#define FF_DT 500
#define GRES 8
#define TMASK 0xffffff
#define PMASK 0xffffff
#define FF_T0 400
#define GPRE 0
#define REL 6
#define EFI 11
#define TKW 8
#define SLOT 0
#define SLOTW 48
#define FF_ORD 0x76543210ba98ull
#define KT 0
#define KK(id) do { if (KT) { TK(32 * wg + (id)); } } while (0)
#define PF_I0 0
#define PF_ST 7
#define PRCP 1
#define TRKL 1
#define KR 4
#define KSEL c
#define XP 0
#define CAPL 0
#define OUT_D 400
#define OUT_0 0
constexpr int NFFN = 112;

constexpr uint32_t SB0 = 1024;
constexpr uint32_t KV_STAGE = 49152, R5 = 32768;
constexpr uint32_t OFF_X = 163840, OFF_S = 196608, OFF_WPHI = OFF_S + 20480, OFF_M = 229376, SMEM_BYTES = 232448;
constexpr uint32_t OFF_RS256 = 212992, OFF_ONES = OFF_RS256 + 1024, OFF_WPHIK1 = OFF_ONES + 1024, OFF_KVZ = OFF_S;
constexpr uint32_t OFF_WPHIK = OFF_S, OFF_BXK = OFF_S + 2048, OFF_AXK = OFF_S + 4096, OFF_G = OFF_S + 8192;
constexpr uint32_t OFF_AXQ = OFF_WPHI, OFF_BXQ = OFF_WPHI + 2048, OFF_WPHIQ = OFF_WPHI + 4096;
constexpr uint32_t B_FULLKV = OFF_M  , B_EMPTYKV = OFF_M + 32  ;
constexpr uint32_t B_EMPTY5 = OFF_M + 64  , B_UO = B_EMPTY5 + 48  , B_RC = B_UO + 32  ;
constexpr uint32_t B_OUT = B_RC + 16  , B_SD = B_OUT + 16, B_AUX = B_SD + 8, B_AUXQ = B_AUX + 8, B_RX = B_AUXQ + 8;
constexpr uint32_t B_FULL5 = B_RX + 8  , B_FULLA = B_FULL5 + 48  , B_F = B_FULLA + 96  , B_WD = B_F + 64  ;
constexpr uint32_t B_WC = B_WD + 32  , B_DR = B_WC + 32  , B_W = B_DR + 24, B_OS = B_W + 8, B_R = B_W + 16, B_KD = B_W + 24, B_R1 = B_W + 32, B_T = B_W + 40, B_G = B_W + 48, B_END = B_W + 56, B_S0 = B_END;
static_assert(B_S0 < OFF_M + 592 && B_END <= OFF_M + 592 && B_FULL5 + 40 >= OFF_M + 208 && B_FULL5 + 40 < OFF_M + 400, "barriers");
constexpr uint32_t OFF_SUMWR = OFF_M + 608, OFF_EP = OFF_M + 624, OFF_KEY = OFF_M + 628;
constexpr uint32_t OFF_RSQ = OFF_M + 640, OFF_TL = OFF_M + 1152, OFF_T = OFF_M + 1792, OFF_WR = OFF_M + 2048, OFF_SCR = OFF_M + 2432;
constexpr uint32_t OFF_XSEL = 2 * R5, OFF_GU = OFF_XSEL + 4096, OFF_OUT = 3 * R5;
constexpr uint64_t FF_SLOT = 0xdcdc3210dcbaull;
constexpr int KVP = 6 * 128;

enum { NB_G2E = 1, NB_XS = 2, NB_WG01 = 3, NB_ACT = 4, NB_Q0 = 5  , NB_ST = 14, NB_DN = 9, NB_ZERO = 10, NB_PUB = 11, NB_TOK = 10  , NB_L0 = 12  , NB_WG2 = 7, NB_QGO = 15 };

struct Scratch {
  bf16     o[SEQ * DM];
  float4   rstat[SEQ];
  uint32_t key[8 * KR * 128];
  uint32_t cand[128 * 512];
  float4   yacc[4 * 3 * 128];
  float4   kvacc[32 * KVP];
  uint2    stats[SEQ];
  uint32_t cskv[2 * DM];
  uint32_t csq[4 * DM];
  uint32_t oset[128 * 16];
  uint32_t epoch;
};
__device__ __align__(1024) Scratch g_scr;
#define TS(id)
#define TDUMP()
#define TS0_DECL()
#define TS0_READ()
#define TS0_WRITE()
#define TK(id)
#define TSW(id)

struct Params {
  CUtensorMap x128, x64, wkv, wq, wo[2], wd, wg, wu, phi, tg, tu, td, xs, ws, qs, out;
  const bf16 *x, *wqkv, *wo_p, *wg_p, *wu_p, *wd_p, *wr;
  bf16* out_p;
  Scratch* g;
  uint32_t zero;
};

constexpr float EXP_LIM = 1.1529215e18f, ARG_LIM2 = 3600.f;
__device__ __forceinline__ void dual_exp2(const float (&p)[2][16], uint32_t (&ph)[4][8]) {
  #pragma unroll
  for (int h = 0; h < 2; h++)
    #pragma unroll
    for (int k = 0; k < 8; k++) { ph[2*h][k] = pack_bf16(ex2(p[h][2*k]), ex2(p[h][2*k+1])); ph[2*h+1][k] = pack_bf16(ex2(-p[h][2*k]), ex2(-p[h][2*k+1])); }
}
__device__ __forceinline__ void dual_exp2_shifted(const float (&pp)[2][16], uint32_t (&ph)[4][8]) {
  #pragma unroll
  for (int h = 0; h < 2; h++) {
    const float* p = pp[h];
    float m[4] = {p[0], p[2], p[0], p[2]};
    #pragma unroll
    for (int i = 0; i < 16; i++) { m[(i >> 1) & 1] = fmaxf(m[(i >> 1) & 1], p[i]); m[2 + ((i >> 1) & 1)] = fminf(m[2 + ((i >> 1) & 1)], p[i]); }
    #pragma unroll
    for (int o = 1; o < 4; o <<= 1) {
      m[0] = fmaxf(m[0], __shfl_xor_sync(~0u, m[0], o)); m[1] = fmaxf(m[1], __shfl_xor_sync(~0u, m[1], o));
      m[2] = fminf(m[2], __shfl_xor_sync(~0u, m[2], o)); m[3] = fminf(m[3], __shfl_xor_sync(~0u, m[3], o));
    }
    #pragma unroll
    for (int k = 0; k < 8; k++) {
      ph[2*h][k] = pack_bf16(ex2(p[2*k] - m[k & 1]), ex2(p[2*k+1] - m[k & 1]));
      ph[2*h+1][k] = pack_bf16(ex2(m[2 + (k & 1)] - p[2*k]), ex2(m[2 + (k & 1)] - p[2*k+1]));
    }
  }
}
__device__ __forceinline__ void row_sums(float (&s)[4][4], const uint32_t (&ph)[4][8], uint32_t ones) {
  #pragma unroll
  for (int i = 0; i < 4; i++) wgmma_rz_n8<0, H0>(s[i], ph[i][0], ph[i][1], ph[i][2], ph[i][3], ones);
  #pragma unroll
  for (int i = 0; i < 4; i++) wgmma_ra_n8<0, H0>(s[i], ph[i][4], ph[i][5], ph[i][6], ph[i][7], ones);
}
__device__ __forceinline__ uint32_t mul_bf16x2(uint32_t a, uint32_t b) { uint32_t r; asm("mul.rn.bf16x2 %0, %1, %2;" : "=r"(r) : "r"(a), "r"(b)); return r; }
__device__ __forceinline__ void normalize(uint32_t (&ph)[4][8], const float (&s)[4][4]) {
  #pragma unroll
  for (int i = 0; i < 4; i++) {
    const float i0 = rcp(s[i][0]), i1 = rcp(s[i][2]);
    const uint32_t n0 = pack_bf16(i0, i0), n1 = pack_bf16(i1, i1);
    #pragma unroll
    for (int k = 0; k < 4; k++) { ph[i][2*k] = mul_bf16x2(ph[i][2*k], n0); ph[i][2*k+1] = mul_bf16x2(ph[i][2*k+1], n1); }
  }
}
__device__ __forceinline__ void split_bf16(float a, float b, uint32_t& hi, uint32_t& lo) { hi = pack_bf16(a, b); lo = pack_bf16(a - bf_lo(hi), b - bf_hi(hi)); }
__device__ __forceinline__ void put_colsums(uint32_t base, int lane, float a, float b, float c, float d) {
  uint32_t h0, l0, h1, l1;
  split_bf16(a, b, h0, l0); split_bf16(c, d, h1, l1);
  const uint32_t ad = base + (lane >> 1) * 128 + (lane & 1) * 8;
  sts64(ad, h0, h1); sts64(ad + 16, l0, l1); sts64(ad + 32, h0, h1); sts64(ad + 48, l0, l1);
  sts128(base + (lane >> 1) * 128 + 64 + (lane & 1) * 32, 0, 0, 0, 0); sts128(base + (lane >> 1) * 128 + 80 + (lane & 1) * 32, 0, 0, 0, 0);
}
__device__ __forceinline__ float reduce8(const float (&v)[8], int lane) {
  const bool b4 = lane & 16, b3 = lane & 8, b2 = lane & 4;
  float a[4], b[2];
  #pragma unroll
  for (int i = 0; i < 4; i++) a[i] = (b4 ? v[4 + i] : v[i]) + __shfl_xor_sync(~0u, b4 ? v[i] : v[4 + i], 16);
  #pragma unroll
  for (int i = 0; i < 2; i++) b[i] = (b3 ? a[2 + i] : a[i]) + __shfl_xor_sync(~0u, b3 ? a[i] : a[2 + i], 8);
  return (b2 ? b[1] : b[0]) + __shfl_xor_sync(~0u, b2 ? b[0] : b[1], 4);
}
__device__ __forceinline__ bool tag_bad(uint4 v, uint32_t tg) { return (((v.x ^ tg) | (v.y ^ tg) | (v.z ^ tg) | (v.w ^ tg)) & 3) != 0; }

__global__ void __launch_bounds__(512, 1) fused_kernel(const __grid_constant__ Params P) {
  extern __shared__ __align__(1024) uint8_t smem_raw[];
  const uint32_t sb = smem_u32(smem_raw);
  const int tid = threadIdx.x, lane = tid & 31;
  TS0_DECL();
  TS0_READ();
  if (tid == 352) { prefetch_map(&P.wkv); prefetch_map(&P.x128); }
  const int cp = blockIdx.x >> 1, rank = blockIdx.x & 1;
  const int cr = cp < 4 ? 32 + 8 * cp : cp - 4 + max((cp * 37 - 1076) >> 8, 0);
  const int c = (cr & 62) + 64 * (cr & 1) + rank;
  const int m256 = c >> 4, nkv = c & 15, m128 = c >> 3, j = c & 7;
  if ((tid >> 5) == 12 && elect_one()) {
    mbar_init(sb + B_S0, 1); mbar_init(sb + B_FULLKV, 1); mbar_init(sb + B_FULLKV + 8, 1);
    fence_async_smem();
    mbar_expect_tx(sb + B_S0, 32768);
    tma_4d(sb + 32768, &P.wkv, 0, 0, nkv, 1, sb + B_S0);
    tma_2d(sb, &P.x128, 0, 256 * m256, sb + B_S0);
    mbar_expect_tx(sb + B_FULLKV, 16384);
    tma_2d(sb + 16384, &P.x128, 0, 256 * m256 + 128, sb + B_FULLKV);
    if (NPRE0 > 1) {
      mbar_expect_tx(sb + B_FULLKV + 8, KV_STAGE);
      tma_4d(sb + KV_STAGE + 32768, &P.wkv, 0, 64, nkv, 1, sb + B_FULLKV + 8);
      tma_2d(sb + KV_STAGE, &P.x128, 64, 256 * m256, sb + B_FULLKV + 8);
      tma_2d(sb + KV_STAGE + 16384, &P.x128, 64, 256 * m256 + 128, sb + B_FULLKV + 8);
    }
    asm volatile("fence.mbarrier_init.release.cluster;" ::: "memory");
  }
  #pragma unroll
  for (int w = 0; w < 3; w++)
    if (tid == 32 + 32 * w) {
      #pragma unroll
      for (uint32_t b = B_FULLKV + 16 + 192 * w; b < B_FULLKV + 208 + 192 * w && b < B_END; b += 8)
        mbar_init(sb + b, b < B_EMPTYKV ? 1 : b < B_EMPTY5 ? 12 : b < B_SD ? 4 : b < B_RX || b == B_W ? 2 : b == B_RX ? 8 : 1);
      if (w == 1) mbar_arrive(sb + B_FULL5 + 40);
      asm volatile("fence.mbarrier_init.release.cluster;" ::: "memory");
      fence_async_smem();
    }
  const int warp = __shfl_sync(~0u, tid >> 5, 0), wg = warp >> 2, wp = warp & 3;
  const int f = 16 * ((cr + 7) & 7) + 2 * (cr >> 3) + rank;
  const int ha = 4 * (nkv >> 1) + (nkv & 1);
  Scratch* const G = P.g;
  if ((sb & 0x3ffff) != SB0) asm volatile("trap;");
  __syncthreads();
  cluster_arrive();
  if (warp == 12) {
    TK(88 - 32);
    if (elect_one()) {
      #pragma unroll
      for (int s = NPRE0; s < NPRE; s++) {
        const uint32_t st = sb + s * KV_STAGE, fb = sb + B_FULLKV + 8 * s;
        mbar_expect_tx(fb, KV_STAGE);
        tma_4d(st + 32768, &P.wkv, 0, 64 * s, nkv, 1, fb);
        tma_2d(st, &P.x128, 64 * s, 256 * m256, fb);
        tma_2d(st + 16384, &P.x128, 64 * s, 256 * m256 + 128, fb);
      }
    }
    __syncwarp();
  }

  if (wg == 3) {
    asm volatile("setmaxnreg.dec.sync.aligned.u32 32;");
    cluster_wait();
    if (wp == 0) { TK(89 - 32); }
    const bool el = elect_one();
    const uint64_t ef = policy_evict_first(), en = policy_evict_normal();
    auto fetch_o = [&](const int t0, uint32_t so, uint32_t par) {
      const int sh = t0 & 1;
      uint32_t ready = 0;
      const bf16* base = G->o + (m128 * 16 + t0) * 8192 + rank * 4096;
      const bf16* hint = base + (lane & 3) * 1024 + 966 + (((j & 6) + ((lane >> 2) & ~sh)) & 7) * 16384 + 8 * sh * (~lane & 4);
      #pragma unroll 1
      for (int i = 2 - 2 * sh; i < 8; i += 1 + sh) {
        uint32_t it = 0;
        while ((~ready >> (4 * i) & (15 + 240 * sh)) && ++it < POLL_LIMIT) ready = __ballot_sync(~0u, ld32_rlx(hint) != ~0u);
        mbar_wait(sb + B_EMPTY5 + so, par);
        if (el) {
          bulk_g2s_mc(sb + so * 4096 + rank * 8192, base + (((j & 6) + i) & 7) * 16384, 8192, sb + B_FULLA + 2 * so + 8 * rank, ef);
          if (i == 2 - 2 * sh) TS(t0 == 0 ? (rank ? 4 : 12) : t0 == 3 ? (rank ? 31 : 10) : (rank ? 9 : 13));
        }
        so += 8;
        if (so == 48) { so = 0; par ^= 1; }
      }
    };
    if (wp == 0) {
      {
        #pragma unroll 1
        for (int kb = NPRE; kb < 16; kb++) {
          const uint32_t st = sb + (kb & 3) * KV_STAGE, fb = sb + B_FULLKV + 8 * (kb & 3);
          mbar_wait(fb + (B_EMPTYKV - B_FULLKV), ~(kb >> 2) & 1);
          if (el) {
            mbar_expect_tx(fb, KV_STAGE);
            tma_2d_mc(st + rank * 16384, &P.x128, 64 * kb, 256 * m256 + 128 * rank, fb);
            tma_4d_h(st + 32768, &P.wkv, 0, 64 * kb, nkv, 1, fb, ef);
          }
        }
        uint64_t ord = 0xf3120edcba987654ull;
        uint32_t so = 0, par = 1;
        #pragma unroll 1
        for (int i = 0; i < 16; i++) {
          const uint32_t st = sb + so * 4096, fb = sb + B_FULL5 + so;
          const int k0 = (64 * (uint32_t)ord + 128 * (j & 6)) & 960;
          mbar_wait(i < 5 ? sb + B_EMPTYKV + so - (i > 1 ? 8 : 0) : fb + (B_EMPTY5 - B_FULL5), par);
          if (el) {
            mbar_expect_tx(fb, R5);
            tma_2d_mc_h(st + rank * 8192, &P.x64, k0, 128 * m128 + 64 * rank, fb, i >= EFI ? ef : en);
            tma_3d_h(st + 16384, &P.wq, 0, k0, 2 * j, fb, ef);
          }
          ord >>= 4; so += 8;
          if (so == 40) { so = 0; par ^= 1; }
        }
        mbar_wait(sb + B_FULL5 + 8 + 8 * rank, 0); if (el) mbar_arrive(sb + B_R);
        mbar_wait(sb + B_FULL5 + 24 + 8 * rank, 0); if (el) mbar_arrive(sb + B_R1);
        #pragma unroll 1
        for (int i = 0; i < 19; i++) {
          const uint32_t fb = sb + B_FULL5 + so, fa = sb + B_FULLA + 2 * so, na = i == rank ? 0 : 8192;
          mbar_wait(fb + (B_EMPTY5 - B_FULL5), par);
          if (SLOT) { while (((uint32_t)clock() & (uint32_t)(SLOT - 1)) >= SLOTW) {} }
          if (el) {
            if (i < 16) {
              mbar_expect_tx(fb, 16384);
              const int row = i < 8 ? 128 * (((j & 6) + i) & 7) : 256 * (((j >> 1) + i) & 3) + 32 + 16 * (i & 4);
              tma_5d_h(sb + so * 4096 + 16384, &P.wo[i >> 3], 128 * j, row, fb, ef);
              tma_5d_h(sb + so * 4096 + 24576, &P.wo[i >> 3], 128 * j + 64, row, fb, ef);
              mbar_expect_tx(fa, na); mbar_expect_tx(fa + 8, na);
            } else mbar_arrive(sb + B_DR + 8 * (i - 16));
          }
          so += 8;
          if (so == 48) { so = 0; par ^= 1; }
        }
      }
    } else if (wp == 3) {
      const uint32_t t_start = (uint32_t)clock();
      if (el) {
        mbar_expect_tx(sb + B_W, 12288);
        #pragma unroll 1
        for (int i = 0; i < 6; i++) tma_2d(sb + (i == 0 ? OFF_WPHIK : i == 1 ? OFF_WPHIK1 : OFF_WPHIQ + 2048 * (i - 2)), &P.phi, 0, 32 * (i < 2 ? 2 * nkv + i : 4 * j + 2 * (i & 1) + ((i - 2) >> 1)), sb + B_W);
        prefetch_map(&P.x64); prefetch_map(&P.wq); prefetch_map(&P.wo[0]); prefetch_map(&P.wo[1]);
        prefetch_map(&P.wd); prefetch_map(&P.out); prefetch_map(&P.wg); prefetch_map(&P.wu);
      }
      #pragma unroll 1
      for (int i = 0; i < 8; i++) {
        if (lane < 16) st128_rlx(&G->cand[(m128 * 8 + i) * 512 + 64 * j + 4 * lane], ~0u, ~0u, ~0u, ~0u);
      }
      if (lane < 16) st128_rlx(&G->rstat[16 * c + lane], 0, 0, 0, 0);
      if (lane < 12) st128_rlx(&G->yacc[12 * c + lane], 0, 0, 0, 0);
      {
        const uint32_t nt = ld32_rlx(&G->epoch);
        if (lane < 8) { st128_rlx(&G->stats[16 * c + 2 * lane], nt, nt, nt, nt); st128_rlx(&G->csq[32 * c + 4 * lane], nt, nt, nt, nt); }
        if (lane < 4) { st128_rlx(&G->cskv[128 * nkv + 16 * m256 + 4 * lane], nt, nt, nt, nt); st128_rlx(&G->oset[16 * c + 4 * lane], nt, nt, nt, nt); }
      }
      if (lane < 2 * KR) st128_rlx(&G->key[(KR * j + (lane >> 1)) * 128 + m128 * 8 + 4 * (lane & 1)], 0, 0, 0, 0);
      if (c < 32) {
        #pragma unroll 1
        for (int i = lane; i < KVP; i += 32) st128_rlx(&G->kvacc[(ha + 2 * m256) * KVP + i], 0, 0, 0, 0);
      }
      fence_gpu();
      bar_arrive(NB_ZERO, 160);
      TS0_WRITE();
      if (el) {
        #pragma unroll 1
        for (int i = PF_I0; i < ((XP & 4) ? 0 : 30); i++) {
          while ((uint32_t)clock() - t_start < (uint32_t)(PF_T0 + PF_DT * (i - PF_I0) + PF_ST * f)) __nanosleep(64);
          if (i < 4) { bulk_prefetch(P.wqkv + (size_t)(256 * i + c) * (3 * DM), 2048); bulk_prefetch(P.wqkv + (size_t)(256 * i + 128 + c) * (3 * DM), 2048); }
          else if (i < 6) bulk_prefetch(P.wo_p + (size_t)c * 8192 + (i - 4) * 4096, 8192);
          else if ((TMASK >> (i - 6)) & 1) {
            const int k = i - 6;
            if (f < NFFN) {
              if (k < 16) {
                #pragma unroll 1
                for (int e = 0; e < 4; e++) tma_2d(sb + OFF_T, rank ? &P.tu : &P.tg, 32 * (f & ~1), 64 * k + 16 * e, sb + B_T);
              } else { tma_2d(sb + OFF_T, &P.td, 0, 256 * f + 32 * (k - 16), sb + B_T); tma_2d(sb + OFF_T, &P.td, 0, 256 * f + 32 * (k - 16) + 16, sb + B_T); }
            }
          }
          else if (!((PMASK >> (i - 6)) & 1)) {}
          else if (i < 22) bulk_prefetch(((i & 1) ? P.wu_p : P.wg_p) + (size_t)((i - 6) >> 1) * 458752 + c * 3584, 7168);
          else bulk_prefetch(P.wd_p + (size_t)(i - 22) * 458752 + c * 3584, 7168);
        }
      }
      __syncwarp();
      mbar_wait2(sb + B_OS, 0, sb + B_RX, 0);
      #pragma unroll 1
      for (int t0 = 0; t0 < 4; t0 += 3) fetch_o(t0, t0 ? 8 : 24, 0);
    } else {
      const int half = wp - 1;
      const uint32_t ep1 = ld32_rlx(&G->epoch) + 1, tg = ep1 & 3;
      {
        uint32_t it = 0;
        sts128(sb + OFF_ONES + half * 512 + lane * 16, 0x3f803f80u, 0x3f803f80u, 0x3f803f80u, 0x3f803f80u);
        auto reset_o = [&](int i0, int i1, uint32_t dt) {
          uint32_t t0 = (uint32_t)clock();
          #pragma unroll 1
          for (int i = i0; i < i1; i++) {
            if (!(XP & 2)) st128_rlx(G->o + (m128 * 16 + 2 * j + half) * 8192 + 256 * i + 8 * lane, ~0u, ~0u, ~0u, ~0u);
            while ((uint32_t)clock() - t0 < dt) __nanosleep(40);
            t0 += dt;
          }
        };
        mbar_wait(sb + B_S0, 0);
        reset_o(0, RS_N, RS_D1);
        bar_sync(NB_PUB, 192);
        const uint4* src = reinterpret_cast<const uint4*>(&G->stats[256 * m256 + 128 * half]) + lane;
        const uint4* srk = reinterpret_cast<const uint4*>(&G->cskv[128 * nkv]) + lane;
        uint4 v0, v1, vk;
        it = 0;
        do { v0 = ld128_rlx(src); v1 = ld128_rlx(src + 32); vk = ld128_rlx(srk); }
        while ((tag_bad(v0, tg) || tag_bad(v1, tg) || tag_bad(vk, tg)) && ++it < POLL_LIMIT);
        fence_acquire_gpu();
        if (half) put_colsums(sb + OFF_BXK, lane, untag(vk.x), untag(vk.y), untag(vk.z), untag(vk.w));
        #pragma unroll
        for (int i = 0; i < 2; i++) {
          const uint4 v = i ? v1 : v0;
          uint32_t hi, lo;
          split_bf16(-0.5f * untag(v.x), -0.5f * untag(v.z), hi, lo);
          const uint32_t h0 = __byte_perm(hi, hi, 0x1010), h1 = __byte_perm(hi, hi, 0x3232), l0 = __byte_perm(lo, lo, 0x1010), l1 = __byte_perm(lo, lo, 0x3232);
          const uint32_t a = sb + OFF_AXK + half * 2048 + i * 1024 + lane * 32;
          sts128(a, h0, l0, 0, 0); sts128(a + 16, h1, l1, 0, 0);
          sts64(sb + OFF_RS256 + half * 512 + i * 256 + lane * 8, v.y & ~3u, v.w & ~3u);
          if (half == (m128 & 1)) {
            const uint32_t aq = sb + OFF_AXQ + i * 1024 + lane * 32;
            sts128(aq, h0, l0, 0, 0); sts128(aq + 16, h1, l1, 0, 0);
            sts64(sb + OFF_RSQ + i * 256 + lane * 8, v.y & ~3u, v.w & ~3u);
          }
        }
        fence_async_smem();
        __syncwarp();
        if (el) { sts32(sb + OFF_EP, ep1); mbar_arrive(sb + B_AUX); if (!half) TS(1); }
        reset_o(RS_N, 32, RS_D2);
        fence_gpu();
        __syncwarp();
        if (el) { st32_rlx(&G->oset[16 * c + 8 * half], ep1); if (half) mbar_arrive(sb + B_AUXQ); }
        if (!half) {
          const uint4* src = reinterpret_cast<const uint4*>(&G->csq[128 * j]) + lane;
          uint4 v0, v1, v2, v3;
          do { v0 = ld128_rlx(src); v1 = ld128_rlx(src + DM / 4); v2 = ld128_rlx(src + DM / 2); v3 = ld128_rlx(src + 3 * DM / 4); }
          while ((tag_bad(v0, tg) || tag_bad(v1, tg) || tag_bad(v2, tg) || tag_bad(v3, tg)) && ++it < POLL_LIMIT);
          put_colsums(sb + OFF_BXQ, lane, (untag(v0.x) + untag(v1.x)) + (untag(v2.x) + untag(v3.x)), (untag(v0.y) + untag(v1.y)) + (untag(v2.y) + untag(v3.y)),
                      (untag(v0.z) + untag(v1.z)) + (untag(v2.z) + untag(v3.z)), (untag(v0.w) + untag(v1.w)) + (untag(v2.w) + untag(v3.w)));
          fence_async_smem();
          __syncwarp();
          if (el) mbar_arrive(sb + B_AUXQ);
        }
      }
      if (half == 0) {
        for (uint32_t it = 0; __any_sync(~0u, ld32_rlx(&G->oset[m128 * 128 + 8 * (lane & 15)]) != ep1) && it < POLL_LIMIT; it++) {}
        fence_acquire_gpu();
        if (el) mbar_arrive(sb + B_OS);
      }
      if (!half) {
        #pragma unroll 1
        for (int hh = 0; hh < 2; hh++) {
          const uint32_t src = sb + (1 + rank) * R5 + hh * 8192, fa = sb + B_FULLA + 16 + 16 * rank + 8 * hh;
          mbar_wait(fa, 0);
          mbar_wait(sb + B_UO + 8 * hh, 0);
          if (el) bulk_s2peer(mapa(src, rank ^ 1), src, 8192, mapa(fa, rank ^ 1));
        }
        fetch_o(1, 24, 1);
      }
      else if (f < NFFN_L) {
        mbar_wait2(sb + B_UO, 0, sb + B_UO + 8, 0);
        mbar_wait(sb + B_UO + 24, 0);
        uint32_t t0 = (uint32_t)clock();
        while ((uint32_t)clock() - t0 < (uint32_t)FF_T0) __nanosleep(32);
        t0 -= FF_DT;
        #pragma unroll 1
        for (int i = 0; i < 12; i++) {
          const int e = (FF_ORD >> (4 * i)) & 15;
          const uint32_t dst = sb + 16384 * ((FF_SLOT >> (4 * e)) & 15), fb = sb + B_F + 8 * e;
          if (i >= 2) mbar_wait(sb + B_WC + 8 * ((0x100066553244ull >> (4 * e)) & 15), 0);
          while ((uint32_t)clock() - t0 < (uint32_t)FF_DT) __nanosleep(32);
          t0 = (uint32_t)clock();
          if (i < 8) { TK(48 + i); }
          if (el) {
            mbar_expect_tx(fb, 16384);
            if (e >= 8) tma_3d_h(dst, &P.wd, 0, 32 * f, 4 * e - 32, fb, ef);
            else { tma_2d(dst, &P.wg, 32 * f, 128 * e, fb); tma_2d(dst + 8192, &P.wu, 32 * f, 128 * e, fb); }
          }
        }
      }
      __syncwarp();
    }
    if (wp & 1) {
      __syncwarp();
      mbar_wait(sb + B_OUT + 8 * (wp >> 1), 0);
      uint32_t t0 = (uint32_t)clock() + OUT_0;
      #pragma unroll 1
      for (int i = 0; i < 8; i++) {
        while ((int32_t)((uint32_t)clock() - t0) < 0) __nanosleep(20);
        if (el) tma_store_2d(&P.out, 128 * j + 64 * (i & 1), 128 * m128 + 32 * (wp & 2) + 8 * (i & 6), sb + OFF_OUT + (i & 1) * 16384 + (wp & 2) * 4096 + (i & 6) * 1024);
        t0 += OUT_D;
      }
      if (el) { bulk_commit(); bulk_wait_all(); fence_async_global(); mbar_arrive(sb + B_SD); TS(19); }
    }
    __syncwarp();
    cluster_arrive(); cluster_wait();
    return;
  }

  asm volatile("setmaxnreg.inc.sync.aligned.u32 160;");
  cluster_wait();
  const int t = tid & 127, g = lane >> 2;
  const uint32_t sa = (16 * wp + (lane & 15)) * 128 + (((lane >> 4) ^ (lane & 7)) << 4);

  if (wg == 2) {
    float s[2] = {0.f, 0.f}, s2[2] = {0.f, 0.f}, ck[8] = {0.f, 0.f, 0.f, 0.f, 0.f, 0.f, 0.f, 0.f}, cs[8] = {0.f, 0.f, 0.f, 0.f, 0.f, 0.f, 0.f, 0.f};
    const uint32_t ebr = mapa(sb + B_EMPTYKV, lane & 1), tg = (ld32_rlx(&G->epoch) + 1) & 3;
    auto addx = [&](const uint4 v) {
      const uint32_t w[4] = {v.x, v.y, v.z, v.w};
      #pragma unroll
      for (int e = 0; e < 4; e++) { const float a = bf_lo(w[e]), d = bf_hi(w[e]); s[0] += a; s[1] += d; s2[0] = fmaf(a, a, s2[0]); s2[1] = fmaf(d, d, s2[1]); }
    };
    auto addc = [&](const uint4 v, float (&o)[8]) {
      o[0] += bf_lo(v.x); o[1] += bf_hi(v.x); o[2] += bf_lo(v.y); o[3] += bf_hi(v.y); o[4] += bf_lo(v.z); o[5] += bf_hi(v.z); o[6] += bf_lo(v.w); o[7] += bf_hi(v.w);
    };
    {
      const uint32_t ra = (16 * nkv + (t >> 3)) * 128 + (t & 7) * 16;
      const uint32_t ca = 32768 + (m256 >> 2) * 8192 + (t >> 1) * 128 + (((2 * (m256 & 3) + (t & 1)) ^ ((t >> 1) & 7)) << 4);
      int rd = 0;
      mbar_wait(sb + B_S0, 0);
      #pragma unroll 1
      for (int kb = 0; kb < 10; kb++) {
        const uint32_t st = sb + (kb & 3) * KV_STAGE;
        mbar_wait(sb + B_FULLKV + 8 * (kb & 3), (kb >> 2) & 1);
        const uint4 x0 = lds128(st + ra), w0 = lds128(st + ca);
        if (!(XP & 1)) { addx(x0); addc(w0, ck); } else s[0] += __uint_as_float(x0.x ^ w0.x);
        __syncwarp();
        if (lane < 2) mbar_arrive_remote(ebr + 8 * (kb & 3), 1);
        if ((SKM >> kb) & 1) {
          if (rd) {
            mbar_wait(sb + B_G, (rd - 1) & 1);
            const uint32_t a = sb + OFF_G + (t >> 3) * 256 + (t & 7) * 16;
            const uint4 x1 = lds128(a), x2 = lds128(a + 128), w1 = lds128(sb + OFF_G + 4096 + t * 16), w2 = lds128(sb + OFF_G + 6144 + t * 16);
            addx(x1); addx(x2); addc(w1, ck); addc(w2, ck);
            bar_sync(NB_WG2, 128);
          }
          if (wp == 0 && elect_one()) {
            mbar_expect_tx(sb + B_G, 8192);
            if (rd < 3) {
              tma_2d(sb + OFF_G, &P.xs, 640 + 128 * rd, 256 * m256 + 16 * nkv, sb + B_G);
              tma_2d(sb + OFF_G + 4096, &P.ws, (1 + (m256 >> 2)) * DM + 64 * nkv + 16 * (m256 & 3), 640 + 128 * rd, sb + B_G);
            } else tma_2d(sb + OFF_G, &P.qs, 32 * (c & 31), 256 * (c >> 5), sb + B_G);
          }
          rd++;
        }
      }
    }
    TK(82);
    const uint32_t scr = sb + OFF_SCR + 128;
    float sx = s[0] + s[1], sq = s2[0] + s2[1];
    #pragma unroll
    for (int o = 1; o < 8; o <<= 1) { sx += __shfl_xor_sync(~0u, sx, o); sq += __shfl_xor_sync(~0u, sq, o); }
    float v = reduce8(ck, lane);
    v += __shfl_xor_sync(~0u, v, 2);
    if (!(lane & 2)) stsf(scr + (wp * 16 + 8 * (lane & 1) + (lane >> 2)) * 4, v);

    bar_sync(NB_ZERO, 160);
    if ((lane & 7) == 0) {
      const float mean = sx * (1.f / DM);
      st64_rlx(&G->stats[256 * m256 + 16 * nkv + (t >> 3)], tagw(mean, tg), tagw(rsqrtf(fmaxf(sq * (1.f / DM) - mean * mean, 0.f) + 1e-5f), tg));
    }
    if (wp == 1 && lane < 16) {
      const uint32_t a = scr + lane * 4;
      st32_rlx(&G->cskv[128 * nkv + 16 * m256 + lane], tagw((ldsf(a) + ldsf(a + 64)) + (ldsf(a + 128) + ldsf(a + 192)), tg));
    }
    __syncwarp();
    bar_arrive(NB_PUB, 192);
    TSW(23);
    const uint4 wv = ld128_keep(P.wr + t * 8);
    #pragma unroll 1
    for (int i = 0; i < 2; i++) {
      mbar_wait(sb + B_G, i ^ 1);
      const uint32_t a = sb + OFF_G + t * 16;
      const uint4 u0 = lds128(a), u1 = lds128(a + 2048), u2 = lds128(a + 4096), u3 = lds128(a + 6144);
      addc(u0, cs); addc(u1, cs); addc(u2, cs); addc(u3, cs);
      bar_sync(NB_WG2, 128);
      if (i == 0 && wp == 0 && elect_one()) { mbar_expect_tx(sb + B_G, 8192); tma_2d(sb + OFF_G, &P.qs, 32 * (c & 31), 256 * (c >> 5) + 128, sb + B_G); }
    }
    if (t == 0) mbar_arrive(sb + B_W);
    float sw = (bf_lo(wv.x) + bf_hi(wv.x)) + (bf_lo(wv.y) + bf_hi(wv.y)) + (bf_lo(wv.z) + bf_hi(wv.z)) + (bf_lo(wv.w) + bf_hi(wv.w));
    #pragma unroll
    for (int o = 16; o; o >>= 1) sw += __shfl_xor_sync(~0u, sw, o);
    if (lane == 0) stsf(sb + OFF_SUMWR + wp * 4, sw);
    if ((t >> 4) == j) {
      const uint32_t a = sb + OFF_WR + (t & 15) * 32;
      sts128(a, wv.x << 16, wv.x & 0xffff0000u, wv.y << 16, wv.y & 0xffff0000u);
      sts128(a + 16, wv.z << 16, wv.z & 0xffff0000u, wv.w << 16, wv.w & 0xffff0000u);
    }
    v = reduce8(cs, lane);
    stsf(scr + (wp * 32 + 8 * (lane & 3) + (lane >> 2)) * 4, v);
    bar_sync(NB_WG2, 128);
    if (wp == 0) {
      const uint32_t a = scr + lane * 4;
      st32_rlx(&G->csq[(c >> 5) * DM + 32 * (c & 31) + lane], tagw((ldsf(a) + ldsf(a + 128)) + (ldsf(a + 256) + ldsf(a + 384)), tg));
    }
  }

  uint32_t xr[32];
  {
    const bool isq = wg == 2;
    float acc[2][64];
    {
      const uint32_t emptyb = mapa(sb + (isq ? B_EMPTY5 : B_EMPTYKV), t & 1);
      if (!isq) {
        mbar_wait(sb + B_S0, 0);
        if (wg) mbar_wait(sb + B_FULLKV, 0);
        if (wg == 0) { TSW(2); }
        #pragma unroll 1
        for (int kb = 0; kb < 16; kb++) {
          if (!KT && wg == 0) { TK(kb); }
          const uint32_t da = dlo(SB0, 16) + wg * 1024 + (kb & 3) * (KV_STAGE >> 4), db = dlo(SB0 + 32768, 8192) + (kb & 3) * (KV_STAGE >> 4);
          wg_fence();
          #pragma unroll
          for (int k = 0; k < 4; k++) {
            wgmma_ss_n128<0, 1, H128, H128>(acc[0], da + 2 * k, db + 128 * k, k > 0 || kb != 0);
            wgmma_ss_n128<0, 1, H128, H128>(acc[1], da + 512 + 2 * k, db + 128 * k, k > 0 || kb != 0);
          }
          wg_commit();
          wg_wait<1>();
          if (kb > 0 && t < 2) mbar_arrive_remote(emptyb + 8 * ((kb - 1) & 3), kb > 10 ? 3 : 1);
          if (kb < 15) mbar_wait(sb + B_FULLKV + 8 * ((kb + 1) & 3), ((kb + 1) >> 2) & 1);
          if (kb == 15 - LAG && wg == 1) bar_sync(NB_WG01, 256);
        }
        bar_arrive(wg ? NB_QGO : NB_WG01, 256);
      } else {
        uint32_t so = 0, po = 0, par = 0;
        mbar_wait(sb + B_FULL5, 0);
        bar_sync(NB_QGO, 256);
        TSW(11);
        #pragma unroll 1
        for (int kb = 0; kb < 16; kb++) {
          TK(16 + kb);
          const uint32_t da = dlo(SB0, 16) + so * 256, db = dlo(SB0 + 16384, 8192) + so * 256;
          #pragma unroll
          for (int k = 0; k < 4; k++) {
            wg_fence();
            wgmma_ss_n128<0, 1, H128, H128>(acc[0], da + 2 * k, db + 128 * k, k > 0 || kb != 0);
            wgmma_ss_n128<0, 1, H128, H128>(acc[1], da + 512 + 2 * k, db + 128 * k, k > 0 || kb != 0);
            wg_commit();
            if (k == 1 && kb > 0 && t < 2) mbar_arrive_remote(emptyb + po, 2);
            if (k == 3) {
              po = so; so += 8;
              if (so == 40) { so = 0; par ^= 1; }
              if (kb < 15) mbar_wait(sb + B_FULL5 + so, par);
            }
            if ((QW >> k) & 1) wg_wait<2>(); else wg_wait<1>();
          }
        }
        mbar_wait(sb + B_AUXQ, 0);
      }
      mbar_wait(sb + B_AUX, 0);
      const uint32_t xa = dlo(SB0, 0) + (isq ? OFF_AXQ >> 4 : (OFF_AXK >> 4) + wg * 128), xb = dlo(SB0, 0) + (isq ? OFF_BXQ >> 4 : OFF_BXK >> 4);
      wg_fence();
      wgmma_sa_n128<0, 1, H0, H0>(acc[0], xa, xb);
      wgmma_sa_n128<0, 1, H0, H0>(acc[1], xa + 64, xb);
      wg_commit();
      if (isq) mbar_wait(sb + B_RC, 0);
      wg_wait<0>();
      if (t < 2) mbar_arrive_remote(emptyb + (isq ? 0 : 24), isq ? 2 : 3);
      if (wg != 1) { TSW(wg ? 8 : 3); }
      fence_regs(acc[0]); fence_regs(acc[1]);
    }
    if (isq) {
      #pragma unroll
      for (int i = 0; i < 2; i++) {
        const uint32_t ta = sb + (1 + rank) * R5 + sa + i * 8192;
        if (i == 1) mbar_wait(sb + B_RC + 8, 0);
        #pragma unroll
        for (int k = 0; k < 4; k++) {
          const float* a = &acc[i][32 * (k >> 1) + 8 * (k & 1)];
          stsm4(ta ^ (k << 5), pack_bf16(a[0], a[1]), pack_bf16(a[2], a[3]), pack_bf16(a[4], a[5]), pack_bf16(a[6], a[7]));
        }
        fence_async_smem();
        bar_arrive(NB_Q0 + i, 256);
      }
      #pragma unroll
      for (int i = 0; i < 32; i++) { const float* a = &acc[(i >> 3) & 1][16 + 32 * (i >> 4) + 2 * (i & 7)]; xr[i] = pack_bf16(a[0], a[1]); }
      TSW(26);
    } else {
      const uint32_t stg = sb + OFF_X + (1 - wg) * 24576;
      const uint32_t va = stg + 16384 + (16 * wp + (lane & 15)) * 64 + (((lane >> 4) ^ ((lane >> 1) & 3)) << 4);
      const uint32_t ra = sb + OFF_RS256 + (128 * wg + 16 * wp + g) * 4;
      const float rs[4] = {ldsf(ra), ldsf(ra + 32), ldsf(ra + 256), ldsf(ra + 288)};
      float p[2][16];
      uint32_t vf[16], kf[2][16];
      auto project = [&](const uint32_t (&f)[16], uint32_t db) {
        wg_fence();
        #pragma unroll
        for (int i = 0; i < 2; i++) {
          wgmma_rs_n32<1, H64>(p[i], f[8*i], f[8*i+1], f[8*i+2], f[8*i+3], db, 0);
          wgmma_ra_n32<1, H64>(p[i], f[8*i+4], f[8*i+5], f[8*i+6], f[8*i+7], db + 64);
        }
        wg_commit();
      };
      auto fold = [&](uint32_t (&f)[16], int col, float sc) {
        #pragma unroll
        for (int i = 0; i < 16; i++) {
          const float r = rs[2 * (i >> 3) + (i & 1)] * sc;
          f[i] = pack_bf16(acc[i >> 3][col + 2 * (i & 7)] * r, acc[i >> 3][col + 2 * (i & 7) + 1] * r);
          asm volatile("" : "+r"(f[i]));
        }
      };
      auto put_v = [&](const uint32_t (&f)[16]) {
        #pragma unroll
        for (int k = 0; k < 4; k++) stsm4((va ^ ((k & 1) << 5)) + (k >> 1) * 4096, f[4*k], f[4*k+1], f[4*k+2], f[4*k+3]);
      };
      KK(0);
      fold(vf, 48, 1.f);
      mbar_wait(sb + B_W, 0);
      fold(kf[0], 0, LOG2E);
      #pragma unroll
      for (int i = 0; i < 32; i++) p[i >> 4][i & 15] = acc[i >> 4][i & 15];
      project(kf[0], dlo(SB0 + OFF_WPHIK, 16));
      mbar_wait(sb + B_W, 0);
      KK(1);
      {
        uint32_t v0[16];
        fold(kf[1], 16, LOG2E);
        fold(v0, 32, 1.f);
        if (wg == 1) bar_sync(NB_DN, 256);
        put_v(v0);
      }
      wg_wait<0>();
      fence_regs(p[0]); fence_regs(p[1]);
      if (wg == 1) bar_arrive(NB_WG01, 256);
      KK(2);
      #pragma unroll 1
      for (int h = 0; h < 2; h++) {
        uint32_t ph[4][8];
        float rsum[4][4];
        dual_exp2(p, ph);
        wg_fence();
        row_sums(rsum, ph, dlo(SB0 + OFF_ONES, 128));
        wg_commit();
        KK(3 + 6 * h);
        if (wg == 0 && h == 0) { bar_arrive(NB_DN, 256); bar_sync(NB_WG01, 256); }
        if (h == 1) {
          if (wg == 1) bar_sync(NB_DN, 256);
          put_v(vf);
        }
        wg_wait<0>();
        KK(4 + 6 * h);
        #pragma unroll
        for (int i = 0; i < 4; i++) fence_regs(rsum[i]);
        if (!(XP & 8) && __builtin_expect(__any_sync(~0u, !((rsum[0][0] + rsum[0][2]) + (rsum[1][0] + rsum[1][2]) + (rsum[2][0] + rsum[2][2]) + (rsum[3][0] + rsum[3][2]) < EXP_LIM)), 0)) {
          dual_exp2_shifted(p, ph);
          #pragma unroll
          for (int i = 0; i < 8; i++) {
            const uint32_t* f = &ph[i >> 1][i & 1];
            float a = (bf_lo(f[0]) + bf_hi(f[0])) + (bf_lo(f[2]) + bf_hi(f[2])) + (bf_lo(f[4]) + bf_hi(f[4])) + (bf_lo(f[6]) + bf_hi(f[6]));
            a += __shfl_xor_sync(~0u, a, 1);
            rsum[i >> 1][2 * (i & 1)] = a + __shfl_xor_sync(~0u, a, 2);
          }
        }
        if (h == 0) project(kf[1], dlo(SB0 + OFF_WPHIK1, 16));
        normalize(ph, rsum);
        #pragma unroll
        for (int i = 0; i < 8; i++) {
          const uint32_t* f = &ph[i >> 1][4 * (i & 1)];
          stsm4(((stg + sa) ^ ((i & 3) << 5)) + (i >> 2) * 8192, f[0], f[1], f[2], f[3]);
        }
        KK(5 + 6 * h);
        fence_async_smem();
        KK(6 + 6 * h);
        if (wg != h) { KK(7 + 6 * h); }
        if (wg == h) {
          float kv[20];
          #pragma unroll
          for (int w = 0; w < 2; w++) {
            const uint32_t da = dlo(SB0 + OFF_X, 16) + (h ^ w ^ 1) * 1536, db = dlo(SB0 + OFF_X + 16384, OFF_ONES - OFF_X - 16384) - (h ^ w ^ 1) * (1536 * 65535);
            if (w) bar_sync(NB_ST, 256); else bar_sync(NB_L0 + h, 128);
            wg_fence();
            #pragma unroll
            for (int k = 0; k < 8; k++) {
              if (k == 0 && w == 0) wgmma_sz_n40<1, 1, H128, H64>(kv, da, db);
              else wgmma_sa_n40<1, 1, H128, H64>(kv, da + k * 128, db - k * (64 * 65535));
            }
            wg_commit();
          }
          float4* dst = &G->kvacc[(ha + 2 * h) * KVP + t];
          wg_wait<0>();
          fence_regs(kv);
          KK(7 + 6 * h);
          if (h == 0) bar_arrive(NB_DN, 256); else if (t < 2) { mbar_arrive_at(sb + B_EMPTY5 + 40, t, 2); if (t == 0) mbar_arrive(sb + B_KD); }
          kv[17] = kv[18];
          #pragma unroll
          for (int i = 0; i < 6; i++) red_add_f32x4(dst + 128 * i, kv[3*i], kv[3*i+1], kv[3*i+2], 1.f);
          TSW(29 + h);
        } else bar_arrive(NB_ST, 256);
        wg_wait<0>();
        KK(8 + 6 * h);
        fence_regs(p[0]); fence_regs(p[1]);
      }
      #pragma unroll
      for (int i = 0; i < 32; i++) asm volatile("mov.b32 %0, 0;" : "=r"(xr[i]));
    }
    float p[2][16];
    #pragma unroll
    for (int i = 0; i < 32; i++) asm volatile("mov.b32 %0, 0;" : "=f"(p[i >> 4][i & 15]));
    auto project_r = [&](int w) {
      wg_fence();
      #pragma unroll
      for (int h = 0; h < 2; h++) {
        wgmma_rs_n32<1, H64>(p[h], xr[8*h], xr[8*h+1], xr[8*h+2], xr[8*h+3], dlo(SB0 + OFF_WPHIQ, 16) + 128 * w, 0);
        wgmma_ra_n32<1, H64>(p[h], xr[8*h+4], xr[8*h+5], xr[8*h+6], xr[8*h+7], dlo(SB0 + OFF_WPHIQ, 16) + 128 * w + 64);
      }
      wg_commit();
    };
    auto capture = [&](const int i) {
      if (!i || CAPL != 2) mbar_wait(sb + (i ? B_R1 : B_R), 0);
      #pragma unroll
      for (int k = 0; k < 4; k++) ldsm4(((sb + (1 + rank) * R5 + wg * 8192 + sa) ^ (k << 5)) + i * 2 * R5, xr[16*i+4*k], xr[16*i+4*k+1], xr[16*i+4*k+2], xr[16*i+4*k+3]);
      const uint32_t one = (((xr[16*i] | xr[16*i+4]) | (xr[16*i+8] | xr[16*i+12])) & P.zero) + 1;
      if (lane == 0) mbar_arrive_at(sb + (i ? B_RX : B_RC + 8 * wg), i ? wg : rank, one);
    };
    {
      const uint4* src = reinterpret_cast<const uint4*>(&G->kvacc[(4 * j + wg) * KVP + t]);
      uint4 v[12];
      #pragma unroll
      for (int i = 0; i < 12; i++) v[i] = i < 6 || isq ? ld128_rlx(src + 128 * i) : make_uint4(0, 0, 0, 0x41000000u);
      if (isq) {
        project_r(2);
        wg_wait<0>();
        #pragma unroll
        for (int i = 0; i < 16; i++) xr[i] = xr[16 + i];
      } else {
        capture(0);
        if (CAPL == 0) capture(1);
      }
      #pragma unroll 1
      for (uint32_t it = 0; it < POLL_LIMIT; it++) {
        uint32_t bad = 0;
        #pragma unroll
        for (int i = 0; i < 12; i++) bad |= v[i].w ^ 0x41000000u;
        if (!__any_sync(~0u, bad != 0)) break;
        #pragma unroll
        for (int i = 0; i < 12; i++) if (i < 6 || isq) v[i] = ld128_rlx(src + 128 * i);
      }
      mbar_wait(sb + B_KD, 0);
      #pragma unroll
      for (int e = 0; e < 2; e++) {
        if (e == 0 || isq) {
          float f[18];
          #pragma unroll
          for (int i = 0; i < 6; i++) { f[3*i] = __uint_as_float(v[6*e+i].x); f[3*i+1] = __uint_as_float(v[6*e+i].y); f[3*i+2] = __uint_as_float(v[6*e+i].z); }
          const uint32_t ka = sb + OFF_KVZ + (wg + e) * 5120 + wp * 1280 + lane * 16;
          stsm4(ka, pack_bf16(f[0], f[1]), pack_bf16(f[2], f[3]), pack_bf16(f[4], f[5]), pack_bf16(f[6], f[7]));
          stsm4(ka + 512, pack_bf16(f[8], f[9]), pack_bf16(f[10], f[11]), pack_bf16(f[12], f[13]), pack_bf16(f[14], f[15]));
          stsm2(ka + 1024, pack_bf16(f[16], 1.f), pack_bf16(f[17], 1.f));
        }
      }
    }
    fence_async_smem();
    if (wg == 1) bar_arrive(NB_DN, 256);
    if (CAPL == 1 && !isq) capture(1);
    if (isq) mbar_wait(sb + B_OS, 0);
    TSW(wg == 0 ? 5 : wg == 1 ? 25 : 6);
    #pragma unroll 1
    for (int e = wg; e < wg + 1 + (wg >> 1); e++) {
      const int half = e >> 1, hh = e & 1, turn = e;
      const uint32_t ao = (1 + rank) * R5 + hh * 8192;
      const uint32_t ra = sb + OFF_RSQ + (16 * wp + g) * 4 + (e == 1 ? 256 : 0), rb = ra + 256 * half;
      const float cc[2][2] = {{ldsf(ra) * LOG2E, ldsf(ra + 32) * LOG2E}, {ldsf(rb) * LOG2E, ldsf(rb + 32) * LOG2E}};
      uint32_t ph[4][8];
      #pragma unroll
      for (int i = 0; i < 32; i++) asm volatile("mov.b32 %0, 0;" : "=r"(ph[i >> 3][i & 7]));
      auto exps = [&](int h) {
        #pragma unroll
        for (int k = 0; k < 8; k++) {
          const float a = ex2(p[h][2*k]), b = ex2(p[h][2*k+1]);
          ph[2*h][k] = pack_bf16(a, b);
          if (PRCP) { const float r = rcp(a * b); ph[2*h+1][k] = pack_bf16(r * b, r * a); }
          else ph[2*h+1][k] = pack_bf16(ex2(-p[h][2*k]), ex2(-p[h][2*k+1]));
        }
      };
      uint32_t shifted = 0;
      asm volatile("" : "+r"(shifted));
      #pragma unroll 1
      for (;;) {
        if (!(XP & 16) && shifted) dual_exp2_shifted(p, ph);
        uint32_t first = (shifted ^ 1) & !isq;
        asm volatile("" : "+r"(first));
        if (first) {
          if (wg == 0) { TSW(7); }
          bar_sync(NB_Q0 + wg, 256);
          const uint32_t da = dlo(SB0, 16) + (ao >> 4), db = dlo(SB0 + OFF_WPHIQ, 16);
          wg_fence();
          #pragma unroll
          for (int h = 0; h < 2; h++) {
            wgmma_ss_n32<0, 1, H128, H64>(p[h], da + 4 * h, db + 128 * h, 0);
            wgmma_sa_n32<0, 1, H128, H64>(p[h], da + 4 * h + 2, db + 128 * h + 64);
          }
          wg_commit();
          if (CAPL == 2) capture(1);
          wg_wait<0>();
        }
        fence_regs(p[0]); fence_regs(p[1]);
        uint32_t again = shifted;
        asm volatile("" : "+r"(again));
        if (again) break;
        float s2[4] = {0.f, 0.f, 0.f, 0.f};
        #pragma unroll
        for (int i = 0; i < 32; i++) { float& x = p[i >> 4][i & 15]; x *= cc[i >> 4][(i >> 1) & 1]; s2[i & 3] = fmaf(x, x, s2[i & 3]); }
        if (!__any_sync(~0u, !((s2[0] < ARG_LIM2) & (s2[1] < ARG_LIM2) & (s2[2] < ARG_LIM2) & (s2[3] < ARG_LIM2)))) break;
        shifted = 1;
      }
      if (e == 1 || e == 2) bar_sync(NB_TOK + e - 1, 256);
      TK(64 + 4 * turn);
      float ac[4][20];
      auto numer = [&](int h) {
        const uint32_t (*f)[8] = &ph[2 * h];
        const uint32_t db = dlo(SB0 + OFF_KVZ, 128) + (half ? e : h) * 320;
        wg_fence();
        #pragma unroll
        for (int i = 0; i < 2; i++) {
          wgmma_rz_n40<1, dhi(256, 0)>(ac[2*h+i], f[i][0], f[i][1], f[i][2], f[i][3], db + i * 160);
          wgmma_ra_n40<1, dhi(256, 0)>(ac[2*h+i], f[i][4], f[i][5], f[i][6], f[i][7], db + (i * 160 + 80));
        }
        wg_commit();
      };
      const uint32_t oa = (16 * wp + g) * 128 + (((lane & 3) ^ g) << 4);
      auto finish = [&](int h) {
        const float* ap = ac[2 * h]; const float* am = ac[2 * h + 1];
        const float ip0 = rcp(ap[17]), im0 = rcp(am[17]), ip1 = rcp(ap[19]), im1 = rcp(am[19]);
        const float d0 = rcp(fmaf(ap[16], ip0, fmaf(am[16], im0, 1e-6f))), d1 = rcp(fmaf(ap[18], ip1, fmaf(am[18], im1, 1e-6f)));
        const float a0 = ip0 * d0, b0 = im0 * d0, a1 = ip1 * d1, b1 = im1 * d1;
        #pragma unroll
        for (int r = 0; r < 2; r++) {
          const float a = r ? a1 : a0, b = r ? b1 : b0;
          uint32_t w[4];
          #pragma unroll
          for (int k = 0; k < 4; k++) w[k] = pack_bf16(fmaf(ap[4*k+2*r], a, am[4*k+2*r] * b), fmaf(ap[4*k+2*r+1], a, am[4*k+2*r+1] * b));
          const uint32_t off = (oa ^ ((half ? rank : h) << 6)) + r * 1024;
          st128_rlx(reinterpret_cast<uint8_t*>(G->o + (m128 * 16 + (half ? 2 * (j & 6) + 2 * hh + 1 : 2 * j)) * 8192 + (half ? h : hh) * 4096) + off, w[0], w[1], w[2], w[3]);
          if (!half) sts128(sb + ao + off, w[0], w[1], w[2], w[3]);
        }
      };
      if (!shifted) exps(0);
      numer(0);
      if (!shifted) exps(1);
      if (turn < 2) bar_arrive(NB_TOK + turn, 256);
      if (wg == 0) bar_sync(NB_DN, 256);
      numer(1);
      wg_wait<1>();
      TK(65 + 4 * turn);
      fence_regs(ac[0]); fence_regs(ac[1]);
      finish(0);
      wg_wait<0>();
      fence_regs(ac[2]); fence_regs(ac[3]);
      #pragma unroll
      for (int i = 0; i < 32; i++) asm volatile("mov.b32 %0, 0;" : "=f"(p[i >> 4][i & 15]));
      if (e == 2) project_r(3);
      finish(1);
      TK(66 + 4 * turn);
      if (!half) fence_async_smem();
      __syncwarp();
      if (lane == 0) mbar_arrive(sb + B_UO + 8 * e);
      wg_wait<0>();
      TK(67 + 4 * turn);
    }
    if (isq) cluster_arrive();
  }

  {
  int lane;
  asm volatile("mov.u32 %0, %%laneid;" : "=r"(lane));
  const int g = lane >> 2, q = lane & 3;
  if (wg < 2) {
    float h[64];
    {
      if (wg == 0) { TK(83); }
      #pragma unroll
      for (int i = 0; i < 32; i++) { h[2*i] = bf_lo(xr[i]); h[2*i+1] = bf_hi(xr[i]); }
      fence_regs(h);
      TK(80 + wg);
      const uint32_t emptyb = mapa(sb + B_EMPTY5, t & 1);
      uint32_t s = 1 + rank, ps = 0;
      mbar_wait2(sb + B_FULL5 + 8 * s, 1, sb + B_UO + 8 * wg, 0);
      if (wg == 0) { TSW(14); }
      #pragma unroll
      for (int i = 0; i < 16; i++) {
        if (wg == 1 && (i & 12) == TKW) { TK(84 + (i & 3)); }
        if (!KT && wg == 0) { TK(32 + i); }
        const uint32_t da = dlo(SB0, 16) + s * 2048 + wg * 512, db = dlo(SB0 + 16384, 8192) + s * 2048;
        wg_fence();
        #pragma unroll
        for (int k = 0; k < 4; k++) wgmma_sa_n128<0, 1, H128, H128>(h, da + k * 2, db + k * 128);
        wg_commit();
        const uint32_t ns = i ? (i + 2) % 6 : 2 - rank;
        const uint32_t b0 = sb + B_FULL5 + 8 * ns, p0 = (1 + (i + 2) / 6) & 1, b1 = sb + B_FULLA + 16 * ns + 8 * wg, p1 = ((i + 1) / 6) & 1;
        const bool here = i == 15 || mbar_test2(b0, p0, b1, p1);
        wg_wait<1>();
        if (!(((2 * REL + 1) >> i) & 1) && i < 14 && t < 2) mbar_arrive_remote(emptyb + 8 * ps, 1);
        if ((REL >> i) & 1) { wg_wait<0>(); if (t < 2) mbar_arrive_remote(emptyb + 8 * s, 1); }
        if (!here) mbar_wait2(b0, p0, b1, p1);
        ps = s; s = ns;
      }
    }
    cluster_arrive();
    float2 wr[16];
    #pragma unroll
    for (int i = 0; i < 16; i++) wr[i] = lds64f(sb + OFF_WR + 32 * i + 8 * q);
    const int r0 = 64 * wg + 16 * wp + g;
    float sum0, sum1, dot0, dot1, sq0, sq1;
    uint32_t redo = 0;
    asm volatile("" : "+r"(redo));
    #pragma unroll 1
    for (;;) {
    if (!(XP & 32) && redo) {
      wg_wait<0>();
      const int r = r0;
      #pragma unroll 1
      for (int n = 0; n < 16; n++) {
        const uint32_t* xp = reinterpret_cast<const uint32_t*>(P.x + (size_t)(128 * m128 + r) * DM + 128 * j + 8 * n) + q;
        const uint32_t x0 = xp[0], x1 = xp[4 * DM];
        float d0 = bf_lo(x0), d1 = bf_hi(x0), d2 = bf_lo(x1), d3 = bf_hi(x1);
        #pragma unroll 1
        for (int ks = 0; ks < 64; ks++) {
          const int kb = ks >> 2, kk = 16 * (ks & 3);
          const bf16* op = G->o + (m128 * 16 + kb) * 8192 + r * 64 + 2 * q;
          const int o0 = ((kk >> 3) ^ g) << 3;
          const uint16_t* w = reinterpret_cast<const uint16_t*>(P.wo_p) + (size_t)(((kb & 1) ? 256 * (kb >> 2) + 32 * (kb & 2) + 32 + 4 * (kk & 32) : 64 * kb + 2 * (kk & 32)) + ((kk & 16) >> 2) + 8 * q) * DM + 128 * j + 8 * n + g;
          const uint32_t b0 = w[0] | (w[DM] << 16), b1 = w[2 * DM] | (w[3 * DM] << 16);
          uint32_t a0, a1, a2, a3, it = 0;
          do { a0 = ld32_rlx(op + o0); a1 = ld32_rlx(op + 512 + o0); a2 = ld32_rlx(op + (o0 ^ 8)); a3 = ld32_rlx(op + 512 + (o0 ^ 8)); }
          while (max(max(a0, a1), max(a2, a3)) == ~0u && ++it < POLL_LIMIT);
          __syncwarp();
          mma16816(d0, d1, d2, d3, a0, a1, a2, a3, b0, b1);
        }
        #pragma unroll
        for (int i = 0; i < 60; i++) h[i] = h[i + 4];
        h[60] = d0; h[61] = d1; h[62] = d2; h[63] = d3;
      }
    }
    wg_wait<0>();
    fence_regs(h);
    if (wg == 0) { TSW(16); }
    sum0 = 0.f, sum1 = 0.f, dot0 = 0.f, dot1 = 0.f, sq0 = 0.f, sq1 = 0.f;
    #pragma unroll
    for (int i = 0; i < 16; i++) {
      sum0 += h[4*i] + h[4*i+1]; sum1 += h[4*i+2] + h[4*i+3];
      sq0 = fmaf(h[4*i], h[4*i], fmaf(h[4*i+1], h[4*i+1], sq0)); sq1 = fmaf(h[4*i+2], h[4*i+2], fmaf(h[4*i+3], h[4*i+3], sq1));
      dot0 = fmaf(h[4*i], wr[i].x, fmaf(h[4*i+1], wr[i].y, dot0)); dot1 = fmaf(h[4*i+2], wr[i].x, fmaf(h[4*i+3], wr[i].y, dot1));
    }
    if (!__any_sync(~0u, !redo & (h[0] != h[0] | h[2] != h[2]))) break;
    redo = 1;
    }
    float4* const rs = &G->rstat[128 * m128 + r0];
    {
      const bool up = q & 2;
      float a = up ? sum1 : sum0, b = up ? sq1 : sq0, d = up ? dot1 : dot0;
      a += __shfl_xor_sync(~0u, up ? sum0 : sum1, 2); b += __shfl_xor_sync(~0u, up ? sq0 : sq1, 2); d += __shfl_xor_sync(~0u, up ? dot0 : dot1, 2);
      a += __shfl_xor_sync(~0u, a, 1); b += __shfl_xor_sync(~0u, b, 1); d += __shfl_xor_sync(~0u, d, 1);
      if ((q & 1) == 0) red_add_f32x4(rs + 4 * q, a, b, d, 1.f);
    }
    if (TRKL == 0) bar_arrive(NB_G2E, 384);
    if (wg == 0) { TSW(24); }
    bar_sync(NB_WG01, 256);
    uint32_t wa[8][4][4];
    const uint32_t wb = sb + 16384 * (((uint32_t)FF_SLOT >> (4 * warp)) & 15) + ((lane & 7) + ((lane >> 4) << 3)) * 64 + ((((lane >> 3) & 1) ^ ((lane >> 1) & 3)) << 4);
    auto getw = [&](int ks) {
      #pragma unroll
      for (int m = 0; m < 4; m++) ldsm4t((wb ^ ((m & 1) << 5)) + (m >> 1) * 8192 + ks * 1024, wa[ks][m][0], wa[ks][m][1], wa[ks][m][2], wa[ks][m][3]);
    };
    if (GPRE && f < NFFN_L) mbar_wait(sb + B_F + 8 * warp, 0);
    if (warp == 7) { TK(60); }
    #pragma unroll
    for (int ks = 0; ks < GPRE; ks++) getw(ks);
    float rstd[2], bm[2];
    uint32_t best;
    {
      const float2 swa = lds64f(sb + OFF_SUMWR), swb = lds64f(sb + OFF_SUMWR + 8);
      const float sw = (swa.x + swa.y) + (swb.x + swb.y);
      uint4 a[2]; uint32_t it = 0, key[2];
      do { a[0] = ld128_rlx(rs); a[1] = ld128_rlx(rs + 8); } while (__any_sync(~0u, (a[0].w & a[1].w) != 0x41000000u) && ++it < POLL_LIMIT);
      #pragma unroll
      for (int i = 0; i < 2; i++) {
        const float mean = __uint_as_float(a[i].x) * (1.f / DM);
        rstd[i] = rsqrtf(fmaxf(__uint_as_float(a[i].y) * (1.f / DM) - mean * mean, 0.f) + 1e-5f);
        bm[i] = -mean * rstd[i];
        const uint32_t rr = __float_as_uint(fmaf(__uint_as_float(a[i].z), rstd[i], sw * bm[i]));
        key[i] = ((rr ^ ((uint32_t)((int32_t)rr >> 31) | 0x80000000u)) & ~2047u) | (2047 - 128 * m128 - r0 - 8 * i);
      }
      asm volatile("redux.sync.max.u32 %0, %1, 0xffffffff;" : "=r"(best) : "r"(max(key[0], key[1])));
    }
    if (TRKL == 2) bar_arrive(NB_G2E, 384);
    if (TRKL == 3 && wg == 0) bar_arrive(NB_G2E, 256);
    if (wg == 0) { TSW(17); }
    const int slot = m128 * 8 + warp, win = ~best & 15;
    if (lane < KR) st32_rlx(&G->key[(KR * j + lane) * 128 + slot], best);
    if ((win & 7) == g) {
      const bool up = win & 8;
      const float ra = up ? rstd[1] : rstd[0], rb = up ? bm[1] : bm[0];
      uint32_t x[16];
      #pragma unroll
      for (int i = 0; i < 16; i++) x[i] = pack_bf16(fmaf(up ? h[4*i+2] : h[4*i], ra, rb), fmaf(up ? h[4*i+3] : h[4*i+1], ra, rb));
      #pragma unroll
      for (int i = 0; i < 4; i++) st128_rlx(&G->cand[slot * 512 + 64 * j + 16 * i + 4 * q], x[4*i], x[4*i+1], x[4*i+2], x[4*i+3]);
    }
    __syncwarp();
    if (TRKL == 1) bar_arrive(NB_G2E, 384);
    if (wg == 0) { TSW(27); }
    {
      const float a0 = 1.f + rstd[0], b0 = bm[0], a1 = 1.f + rstd[1], b1 = bm[1];
      #pragma unroll
      for (int k = 0; k < 8; k++)
        stsm4(((sb + OFF_OUT + wg * 8192 + sa) ^ ((k & 3) << 5)) + (k >> 2) * 16384,
              pack_bf16(fmaf(h[8*k], a0, b0), fmaf(h[8*k+1], a0, b0)),     pack_bf16(fmaf(h[8*k+2], a1, b1), fmaf(h[8*k+3], a1, b1)),
              pack_bf16(fmaf(h[8*k+4], a0, b0), fmaf(h[8*k+5], a0, b0)),   pack_bf16(fmaf(h[8*k+6], a1, b1), fmaf(h[8*k+7], a1, b1)));
      fence_async_smem();
      __syncwarp();
      if (lane == 0) mbar_arrive(sb + B_OUT + 8 * wg);
    }
    if (wg == 0) { TSW(28); }
    {
      if (!GPRE && f < NFFN_L) mbar_wait(sb + B_F + 8 * warp, 0);
      #pragma unroll
      for (int ks = GPRE; ks < GRES; ks++) getw(ks);
      if (wg == 0) { TSW(15); }
      bar_sync(NB_XS, 384);
      uint4 xs[4];
      #pragma unroll
      for (int i = 0; i < 4; i++) xs[i] = lds128(sb + OFF_XSEL + 256 * warp + 64 * i + 16 * q);
      float d[4][4];
      #pragma unroll
      for (int ks = 0; ks < 8; ks++) {
        if (ks >= 1 && GRES + ks - 1 < 8) getw(GRES + ks - 1);
        #pragma unroll
        for (int m = 0; m < 4; m++) {
          if (ks == 0) { d[m][0] = 0.f; d[m][1] = 0.f; d[m][2] = 0.f; d[m][3] = 0.f; }
          mma16816(d[m][0], d[m][1], d[m][2], d[m][3], wa[ks][m][0], wa[ks][m][1], wa[ks][m][2], wa[ks][m][3],
                   (ks & 1) ? xs[ks >> 1].z : xs[ks >> 1].x, (ks & 1) ? xs[ks >> 1].w : xs[ks >> 1].y);
        }
      }
      if (q == 0) {
        #pragma unroll
        for (int m = 0; m < 8; m++) stsf(sb + OFF_GU + (8 * m + g) * 48 + 4 * warp, d[m >> 1][2 * (m & 1)]);
      }
      bar_arrive(NB_ACT, 384);
    }
    {
      const uint32_t ky = __float_as_uint(ldsf(sb + OFF_KEY));
      const int row = 2047 - (ky & 2047) - 128 * m128;
      if ((uint32_t)row < 128u) {
        const int l = tid >> 3, vi = (j & 1) + ((lane >> 2) & 1), e = 3 * vi + q - 4 * (j & 1);
        const float kr = __uint_as_float((ky & ~2047u) ^ ((ky >> 31) ? 0x80000000u : 0xfffff800u));
        const int col = 32 * (l & 3) + 16 * (e & 1) + 4 * (e & 2) + (l >> 2);
        const float sg = rcp(1.f + ex2(-LOG2E * kr));
        const uint32_t base = __float_as_uint(ldsf(sb + OFF_OUT + (col >> 6) * 16384 + row * 128 + ((((col >> 3) ^ row) & 7) << 4) + 2 * (col & 6)));
        const float4* yp = &G->yacc[(q * 3 + vi) * 128 + 32 * (j >> 1) + l];
        uint32_t it = 0;
        uint4 v;
        mbar_wait(sb + B_SD, 0);
        do { v = ld128_rlx(yp); } while (__any_sync(~0u, __uint_as_float(v.w) != (float)(NFFN / 4)) && ++it < POLL_LIMIT);
        float y0 = __uint_as_float(v.x), y1 = __uint_as_float(v.y), y2 = __uint_as_float(v.z);
        #pragma unroll
        for (int o = 1; o < 4; o <<= 1) { y0 += __shfl_xor_sync(~0u, y0, o); y1 += __shfl_xor_sync(~0u, y1, o); y2 += __shfl_xor_sync(~0u, y2, o); }
        if (q < 3 && (uint32_t)e < 4u)
          P.out_p[(size_t)(128 * m128 + row) * DM + 128 * j + col] = __float2bfloat16(fmaf(q == 0 ? y0 : q == 1 ? y1 : y2, sg, (col & 1) ? bf_hi(base) : bf_lo(base)));
      }
      if (c == 0 && tid == 0) st32_rlx(&G->epoch, __float_as_uint(ldsf(sb + OFF_EP)));
      if (warp == 0) { TSW(22); }
      if (wg == 0) { TDUMP(); }
    }
  }
  if (wg == 2) {
    uint32_t wf[16][2][4];
    {
      const uint32_t wb = sb + OFF_S + 16384 * (wp & 1) + ((lane & 7) + ((lane >> 4) << 3)) * 128 + ((((lane >> 3) & 1) ^ (lane & 7)) << 4);
      if (f < NFFN_L) mbar_wait(sb + B_WD + 8 * wp, 0);
      if (wp == 0) { TK(61); }
      #pragma unroll
      for (int i = 0; i < 32; i++) ldsm4t((wb ^ (((i >> 1) & 3) << 5)) + (i >> 3) * 4096 + (i & 1) * 2048, wf[i >> 1][i & 1][0], wf[i >> 1][i & 1][1], wf[i >> 1][i & 1][2], wf[i >> 1][i & 1][3]);
      fence_async_smem();
      __syncwarp();
      if (lane == 0) mbar_arrive(sb + B_WC + 8 * wp);
      if (wp == 0) { TK(62); }
    }
    bar_sync(NB_G2E, TRKL == 3 ? 256 : 384);
    {
      uint32_t cur = 0;
      uint4 v;
      #pragma unroll 1
      for (uint32_t it = 0; it < POLL_LIMIT; it++) {
        const uint4 kx = ld128_rlx(&G->key[(KSEL & (8 * KR - 1)) * 128 + 4 * lane]);
        v = ld128_rlx(&G->cand[((~cur >> 4) & 127) * 512 + 4 * t]);
        uint32_t best;
        asm volatile("redux.sync.max.u32 %0, %1, 0xffffffff;" : "=r"(best) : "r"(max(max(kx.x, kx.y), max(kx.z, kx.w))));
        if (!__any_sync(~0u, min(min(kx.x, kx.y), min(kx.z, kx.w)) == 0 || v.w == ~0u) && best == cur) break;
        cur = best;
      }
      sts128(sb + OFF_XSEL + 16 * t, v.x, v.y, v.z, v.w);
      sts32(sb + OFF_KEY, cur);
      bar_arrive(NB_XS, 384);
      TSW(18);
      bar_sync(NB_ACT, 384);
    }
    float gu[2];
    #pragma unroll
    for (int i = 0; i < 2; i++) {
      const uint4 v0 = lds128(sb + OFF_GU + (32 * i + lane) * 48), v1 = lds128(sb + OFF_GU + (32 * i + lane) * 48 + 16);
      gu[i] = ((__uint_as_float(v0.x) + __uint_as_float(v0.y)) + (__uint_as_float(v0.z) + __uint_as_float(v0.w))) +
              ((__uint_as_float(v1.x) + __uint_as_float(v1.y)) + (__uint_as_float(v1.z) + __uint_as_float(v1.w)));
    }
    const float act = gu[0] * gu[1] * rcp(1.f + ex2(-LOG2E * gu[0]));
    const uint32_t ap = pack_bf16(act, __shfl_down_sync(~0u, act, 1));
    uint32_t bf[4];
    #pragma unroll
    for (int i = 0; i < 4; i++) bf[i] = __shfl_sync(~0u, ap, 2 * q + 8 * i);
    TSW(20);
    float d[16][4];
    #pragma unroll
    for (int k = 0; k < 2; k++)
      #pragma unroll
      for (int i = 0; i < 16; i++) {
        if (k == 0) { d[i][0] = 0.f; d[i][1] = 0.f; d[i][2] = 0.f; d[i][3] = 0.f; }
        mma16816(d[i][0], d[i][1], d[i][2], d[i][3], wf[i][k][0], wf[i][k][1], wf[i][k][2], wf[i][k][3], bf[2*k], bf[2*k+1]);
      }
    float y[9];
    #pragma unroll
    for (int e = 0; e < 8; e++) {
      const int n = 2 * (e & 4) + (e & 1);
      const float lo = (q & 1) ? d[n + 2][e & 2] : d[n][e & 2], hi = (q & 1) ? d[n + 6][e & 2] : d[n + 4][e & 2];
      y[e] = (q & 2) ? hi : lo;
    }
    y[8] = 0.f;
    if (f < NFFN) {
      #pragma unroll
      for (int i = 0; i < 3; i++) red_add_f32x4(&G->yacc[((f & 3) * 3 + i) * 128 + t], y[3*i], y[3*i+1], y[3*i+2], 1.f);
    }
    TSW(21);
  }
  }
  cluster_wait();
}

typedef CUresult (*EncodeFn)(CUtensorMap*, CUtensorMapDataType, cuuint32_t, void*, const cuuint64_t*, const cuuint64_t*,
                             const cuuint32_t*, const cuuint32_t*, CUtensorMapInterleave, CUtensorMapSwizzle,
                             CUtensorMapL2promotion, CUtensorMapFloatOOBfill);

void make_map(EncodeFn enc, CUtensorMap* m, const void* p, int n, const cuuint64_t* dims, const cuuint64_t* str, const cuuint32_t* box,
              CUtensorMapSwizzle sw, CUtensorMapL2promotion promo) {
  cuuint32_t es[5] = {1, 1, 1, 1, 1};
  enc(m, CU_TENSOR_MAP_DATA_TYPE_BFLOAT16, n, const_cast<void*>(p), dims, str, box, es, CU_TENSOR_MAP_INTERLEAVE_NONE, sw, promo,
      CU_TENSOR_MAP_FLOAT_OOB_FILL_NONE);
}
void map2(EncodeFn enc, CUtensorMap* m, const void* p, uint64_t cols, uint64_t rows, uint32_t bc, uint32_t br, CUtensorMapSwizzle sw,
          CUtensorMapL2promotion promo) {
  const cuuint64_t dims[2] = {cols, rows}, str[1] = {cols * 2};
  const cuuint32_t box[2] = {bc, br};
  make_map(enc, m, p, 2, dims, str, box, sw, promo);
}
void map3(EncodeFn enc, CUtensorMap* m, const void* p, uint64_t cols, uint64_t rows, uint32_t br, uint32_t nb) {
  const cuuint64_t dims[3] = {64, rows, cols / 64}, str[2] = {cols * 2, 128};
  const cuuint32_t box[3] = {64, br, nb};
  make_map(enc, m, p, 3, dims, str, box, CU_TENSOR_MAP_SWIZZLE_128B, CU_TENSOR_MAP_L2_PROMOTION_L2_128B);
}

}

extern "C" void kernel_launch(void* const* d_in, const int* in_sizes, int n_in, void* d_out, int out_size) {
  (void)in_sizes; (void)n_in; (void)out_size;
  static EncodeFn enc = nullptr;
  static void* o_ptr = nullptr;
  if (!enc) {
    void* f = nullptr; cudaDriverEntryPointQueryResult qr;
    cudaGetDriverEntryPoint("cuTensorMapEncodeTiled", &f, cudaEnableDefault, &qr);
    enc = (EncodeFn)f;
    cudaGetSymbolAddress(&o_ptr, g_scr);
    cudaFuncSetAttribute(fused_kernel, cudaFuncAttributeMaxDynamicSharedMemorySize, SMEM_BYTES);
  }
  const bf16* x = (const bf16*)d_in[0];
  const bf16* wqkv = (const bf16*)d_in[1];
  const bf16* wphi = (const bf16*)d_in[2];
  const bf16* wo = (const bf16*)d_in[3];
  const bf16* wr = (const bf16*)d_in[5];
  const bf16* wgate = (const bf16*)d_in[6];
  const bf16* wup = (const bf16*)d_in[7];
  const bf16* wdown = (const bf16*)d_in[8];
  Params P;
  const CUtensorMapSwizzle S128 = CU_TENSOR_MAP_SWIZZLE_128B, S64 = CU_TENSOR_MAP_SWIZZLE_64B;
  const CUtensorMapL2promotion L128 = CU_TENSOR_MAP_L2_PROMOTION_L2_128B, L256 = CU_TENSOR_MAP_L2_PROMOTION_L2_256B,
                               L64 = CU_TENSOR_MAP_L2_PROMOTION_L2_64B;
  map2(enc, &P.x128, x, DM, SEQ, 64, 128, S128, L256);
  map2(enc, &P.x64, x, DM, SEQ, 64, 64, S128, L128);
  {
    const cuuint64_t dims[4] = {64, DM, 16, 3}, str[3] = {6 * DM, 128, 2 * DM};
    const cuuint32_t box[4] = {64, 64, 1, 2};
    make_map(enc, &P.wkv, wqkv, 4, dims, str, box, S128, L128);
  }
  map3(enc, &P.wq, wqkv, 3 * DM, DM, 64, 2);
  for (int i = 0; i < 2; i++) {
    const cuuint64_t dims[5] = {DM, (cuuint64_t)(DM - 94 - 64 * i), 4, 4, 2}, str[4] = {2 * DM, 16 * DM, 4 * DM, (cuuint64_t)(128 * DM) << i};
    const cuuint32_t box[5] = {64, 2, 4, 4, 2};
    make_map(enc, &P.wo[i], wo, 5, dims, str, box, S128, L128);
  }
  map3(enc, &P.wd, wdown, DM, FF, 32, 4);
  map2(enc, &P.wg, wgate, FF, DM, 32, 128, S64, L64);
  map2(enc, &P.wu, wup, FF, DM, 32, 128, S64, L64);
  map2(enc, &P.tg, wgate, FF, DM, 8, 16, CU_TENSOR_MAP_SWIZZLE_NONE, L128);
  map2(enc, &P.tu, wup, FF, DM, 8, 16, CU_TENSOR_MAP_SWIZZLE_NONE, L128);
  map2(enc, &P.td, wdown, 128, FF * 8, 8, 16, CU_TENSOR_MAP_SWIZZLE_NONE, L256);
  map2(enc, &P.xs, x, DM, SEQ, 128, 16, CU_TENSOR_MAP_SWIZZLE_NONE, L256);
  map2(enc, &P.ws, wqkv, 3 * DM, DM, 16, 128, CU_TENSOR_MAP_SWIZZLE_NONE, L128);
  map2(enc, &P.qs, wqkv, 3 * DM, DM, 32, 128, CU_TENSOR_MAP_SWIZZLE_NONE, L64);
  map2(enc, &P.out, d_out, DM, SEQ, 64, 16, S128, L128);
  map2(enc, &P.phi, wphi, 32, 1024, 32, 32, S64, L64);
  P.x = x; P.wqkv = wqkv; P.wo_p = wo; P.wd_p = wdown; P.wg_p = wgate; P.wu_p = wup; P.wr = wr; P.out_p = (bf16*)d_out; P.g = (Scratch*)o_ptr; P.zero = 0;

  cudaLaunchConfig_t cfg = {};
  cfg.gridDim = dim3(128); cfg.blockDim = dim3(512); cfg.dynamicSmemBytes = SMEM_BYTES; cfg.stream = cudaStreamPerThread;
  cudaLaunchAttribute at[1];
  at[0].id = cudaLaunchAttributeClusterDimension; at[0].val.clusterDim.x = 2; at[0].val.clusterDim.y = 1; at[0].val.clusterDim.z = 1;
  cfg.attrs = at; cfg.numAttrs = 1;
  cudaLaunchKernelEx(&cfg, fused_kernel, P);
}
```

```cpp
#include <cuda_runtime.h>
#include <cuda.h>
#include <cuda_bf16.h>
#include <stdint.h>

namespace {

typedef __nv_bfloat16 bf16;

__device__ __forceinline__ uint32_t smem_u32(const void* p){ return (uint32_t)__cvta_generic_to_shared(p); }
__device__ __forceinline__ void mbar_init(uint32_t bar, uint32_t cnt){ asm volatile("mbarrier.init.shared::cta.b64 [%0], %1;"::"r"(bar),"r"(cnt):"memory"); }
__device__ __forceinline__ void mbar_expect_tx(uint32_t bar, uint32_t bytes){ asm volatile("mbarrier.arrive.expect_tx.shared::cta.b64 _, [%0], %1;"::"r"(bar),"r"(bytes):"memory"); }
__device__ __forceinline__ void mbar_arrive(uint32_t bar){ asm volatile("mbarrier.arrive.shared::cta.b64 _, [%0];"::"r"(bar):"memory"); }
__device__ __forceinline__ uint32_t mapa(uint32_t addr, uint32_t cta){ uint32_t r; asm volatile("mapa.shared::cluster.u32 %0, %1, %2;":"=r"(r):"r"(addr),"r"(cta)); return r; }
__device__ __forceinline__ void mbar_arrive_at(uint32_t bar, uint32_t cta, uint32_t cnt){
  asm volatile("{\n.reg .b32 ra;\nmapa.shared::cluster.u32 ra, %0, %1;\nmbarrier.arrive.shared::cluster.b64 _, [ra], %2;\n}\n"::"r"(bar),"r"(cta),"r"(cnt):"memory"); }
__device__ __forceinline__ void mbar_arrive_remote(uint32_t cluster_addr, uint32_t cnt){
  asm volatile("mbarrier.arrive.shared::cluster.b64 _, [%0], %1;"::"r"(cluster_addr),"r"(cnt):"memory"); }
__device__ __forceinline__ void mbar_wait(uint32_t bar, uint32_t parity){
  asm volatile("{\n.reg .pred p;\n.reg .u32 c;\nmov.u32 c, 0;\nLW:\nmbarrier.try_wait.parity.shared::cta.b64 p, [%0], %1;\n@p bra LD;\nadd.u32 c, c, 1;\nsetp.lt.u32 p, c, 2000000;\n@p bra LW;\ntrap;\nLD:\n}\n"::"r"(bar),"r"(parity):"memory"); }
__device__ __forceinline__ void mbar_wait2(uint32_t bar0, uint32_t par0, uint32_t bar1, uint32_t par1){
  asm volatile("{\n.reg .pred p, q;\n.reg .u32 c;\nmov.u32 c, 0;\nLW:\nmbarrier.try_wait.parity.shared::cta.b64 p, [%0], %1;\nmbarrier.try_wait.parity.shared::cta.b64 q, [%2], %3;\nand.pred p, p, q;\n@p bra LD;\nadd.u32 c, c, 1;\nsetp.lt.u32 p, c, 2000000;\n@p bra LW;\ntrap;\nLD:\n}\n"::"r"(bar0),"r"(par0),"r"(bar1),"r"(par1):"memory"); }
__device__ __forceinline__ bool mbar_test2(uint32_t bar0, uint32_t par0, uint32_t bar1, uint32_t par1){
  uint32_t r;
  asm volatile("{\n.reg .pred p, q;\nmbarrier.test_wait.parity.shared::cta.b64 p, [%1], %2;\nmbarrier.test_wait.parity.shared::cta.b64 q, [%3], %4;\nand.pred p, p, q;\nselp.u32 %0, 1, 0, p;\n}\n":"=r"(r):"r"(bar0),"r"(par0),"r"(bar1),"r"(par1):"memory");
  return r; }
__device__ __forceinline__ void tma_2d(uint32_t dst, const CUtensorMap* m, int c0, int c1, uint32_t bar){
  asm volatile("cp.async.bulk.tensor.2d.shared::cluster.global.mbarrier::complete_tx::bytes [%0], [%1, {%3, %4}], [%2];"::"r"(dst),"l"(m),"r"(bar),"r"(c0),"r"(c1):"memory"); }
__device__ __forceinline__ void tma_2d_mc(uint32_t dst, const CUtensorMap* m, int c0, int c1, uint32_t bar){
  asm volatile("cp.async.bulk.tensor.2d.shared::cluster.global.mbarrier::complete_tx::bytes.multicast::cluster [%0], [%1, {%3, %4}], [%2], %5;"::"r"(dst),"l"(m),"r"(bar),"r"(c0),"r"(c1),"h"((uint16_t)3):"memory"); }
__device__ __forceinline__ void tma_2d_mc_h(uint32_t dst, const CUtensorMap* m, int c0, int c1, uint32_t bar, uint64_t pol){
  asm volatile("cp.async.bulk.tensor.2d.shared::cluster.global.mbarrier::complete_tx::bytes.multicast::cluster.L2::cache_hint [%0], [%1, {%3, %4}], [%2], %5, %6;"::"r"(dst),"l"(m),"r"(bar),"r"(c0),"r"(c1),"h"((uint16_t)3),"l"(pol):"memory"); }
__device__ __forceinline__ void tma_4d(uint32_t dst, const CUtensorMap* m, int c0, int c1, int c2, int c3, uint32_t bar){
  asm volatile("cp.async.bulk.tensor.4d.shared::cluster.global.mbarrier::complete_tx::bytes [%0], [%1, {%3, %4, %5, %6}], [%2];"::"r"(dst),"l"(m),"r"(bar),"r"(c0),"r"(c1),"r"(c2),"r"(c3):"memory"); }
__device__ __forceinline__ uint64_t policy_evict_first(){ uint64_t p; asm volatile("createpolicy.fractional.L2::evict_first.b64 %0, 1.0;":"=l"(p)); return p; }
__device__ __forceinline__ uint64_t policy_evict_normal(){ uint64_t p; asm("createpolicy.fractional.L2::evict_normal.b64 %0, 1.0;":"=l"(p)); return p; }
__device__ __forceinline__ void tma_3d_h(uint32_t dst, const CUtensorMap* m, int c0, int c1, int c2, uint32_t bar, uint64_t pol){
  asm volatile("cp.async.bulk.tensor.3d.shared::cluster.global.mbarrier::complete_tx::bytes.L2::cache_hint [%0], [%1, {%3, %4, %5}], [%2], %6;"::"r"(dst),"l"(m),"r"(bar),"r"(c0),"r"(c1),"r"(c2),"l"(pol):"memory"); }
__device__ __forceinline__ void tma_4d_h(uint32_t dst, const CUtensorMap* m, int c0, int c1, int c2, int c3, uint32_t bar, uint64_t pol){
  asm volatile("cp.async.bulk.tensor.4d.shared::cluster.global.mbarrier::complete_tx::bytes.L2::cache_hint [%0], [%1, {%3, %4, %5, %6}], [%2], %7;"::"r"(dst),"l"(m),"r"(bar),"r"(c0),"r"(c1),"r"(c2),"r"(c3),"l"(pol):"memory"); }
__device__ __forceinline__ void red_add_f32x4(float4* p, float x, float y, float z, float w){ asm volatile("red.relaxed.gpu.global.add.v4.f32 [%0], {%1,%2,%3,%4};"::"l"(p),"f"(x),"f"(y),"f"(z),"f"(w):"memory"); }
__device__ __forceinline__ void tma_5d_h(uint32_t dst, const CUtensorMap* m, int c0, int c1, uint32_t bar, uint64_t pol){
  asm volatile("cp.async.bulk.tensor.5d.shared::cluster.global.mbarrier::complete_tx::bytes.L2::cache_hint [%0], [%1, {%3, %4, 0, 0, 0}], [%2], %5;"::"r"(dst),"l"(m),"r"(bar),"r"(c0),"r"(c1),"l"(pol):"memory"); }
__device__ __forceinline__ void tma_store_2d(const CUtensorMap* m, int c0, int c1, uint32_t src){
  asm volatile("cp.async.bulk.tensor.2d.global.shared::cta.bulk_group [%0, {%2, %3}], [%1];"::"l"(m),"r"(src),"r"(c0),"r"(c1):"memory"); }
__device__ __forceinline__ void bulk_commit(){ asm volatile("cp.async.bulk.commit_group;":::"memory"); }
__device__ __forceinline__ void bulk_wait_all(){ asm volatile("cp.async.bulk.wait_group 0;":::"memory"); }
__device__ __forceinline__ void fence_async_global(){ asm volatile("fence.proxy.async.global;":::"memory"); }
__device__ __forceinline__ bool elect_one(){ uint32_t p; asm volatile("{\n.reg .pred P;\nelect.sync _|P, 0xffffffff;\nselp.b32 %0, 1, 0, P;\n}\n":"=r"(p)); return p; }
__device__ __forceinline__ void bulk_prefetch(const void* p, uint32_t bytes){
  asm volatile("cp.async.bulk.prefetch.L2.global [%0], %1;"::"l"(p),"r"(bytes):"memory"); }
__device__ __forceinline__ void bulk_s2peer(uint32_t dst_cluster, uint32_t src, uint32_t bytes, uint32_t bar_cluster){
  asm volatile("cp.async.bulk.shared::cluster.shared::cta.mbarrier::complete_tx::bytes [%0], [%1], %2, [%3];"::"r"(dst_cluster),"r"(src),"r"(bytes),"r"(bar_cluster):"memory"); }
__device__ __forceinline__ void bulk_g2s_mc(uint32_t dst, const void* src, uint32_t bytes, uint32_t bar, uint64_t pol){
  asm volatile("cp.async.bulk.shared::cluster.global.mbarrier::complete_tx::bytes.multicast::cluster.L2::cache_hint [%0], [%1], %2, [%3], %4, %5;"::"r"(dst),"l"(src),"r"(bytes),"r"(bar),"h"((uint16_t)3),"l"(pol):"memory"); }
__device__ __forceinline__ void prefetch_map(const CUtensorMap* m){ asm volatile("prefetch.tensormap [%0];"::"l"(m):"memory"); }
__device__ __forceinline__ void fence_async_smem(){ asm volatile("fence.proxy.async.shared::cta;":::"memory"); }
__device__ __forceinline__ void fence_acquire_gpu(){ asm volatile("fence.acquire.gpu;":::"memory"); }
__device__ __forceinline__ void fence_gpu(){ asm volatile("fence.acq_rel.gpu;":::"memory"); }
__device__ __forceinline__ void wg_fence(){ asm volatile("wgmma.fence.sync.aligned;":::"memory"); }
__device__ __forceinline__ void wg_commit(){ asm volatile("wgmma.commit_group.sync.aligned;":::"memory"); }
template<int N> __device__ __forceinline__ void wg_wait(){ asm volatile("wgmma.wait_group.sync.aligned %0;"::"n"(N):"memory"); }
template<int N> __device__ __forceinline__ void fence_regs(float (&d)[N]){
  #pragma unroll
  for(int i=0;i<N;i++) asm volatile("":"+f"(d[i])::"memory"); }
__device__ __forceinline__ void bar_sync(int id, int n){ asm volatile("bar.sync %0, %1;"::"r"(id),"r"(n):"memory"); }
__device__ __forceinline__ void bar_arrive(int id, int n){ asm volatile("bar.arrive %0, %1;"::"r"(id),"r"(n):"memory"); }
__device__ __forceinline__ void cluster_arrive(){ asm volatile("barrier.cluster.arrive.relaxed.aligned;":::"memory"); }
__device__ __forceinline__ void cluster_wait(){ asm volatile("barrier.cluster.wait.aligned;":::"memory"); }
__host__ __device__ constexpr uint32_t dlo(uint32_t addr, uint32_t lbo){ return (addr >> 4) | ((lbo >> 4) << 16); }
__host__ __device__ constexpr uint32_t dhi(uint32_t sbo, uint32_t sw){ return (sbo >> 4) | (sw << 30); }
constexpr uint32_t H128 = dhi(1024, 1), H64 = dhi(512, 2), H0 = dhi(128, 0);
__device__ __forceinline__ uint32_t pack_bf16(float lo, float hi){ uint32_t r; asm("cvt.rn.bf16x2.f32 %0, %1, %2;":"=r"(r):"f"(hi),"f"(lo)); return r; }
__device__ __forceinline__ float bf_lo(uint32_t v){ return __uint_as_float(v<<16); }
__device__ __forceinline__ float bf_hi(uint32_t v){ return __uint_as_float(v&0xffff0000u); }
__device__ __forceinline__ float ex2(float x){ float r; asm("ex2.approx.ftz.f32 %0, %1;":"=f"(r):"f"(x)); return r; }
__device__ __forceinline__ float rcp(float x){ float r; asm("rcp.approx.ftz.f32 %0, %1;":"=f"(r):"f"(x)); return r; }
__device__ __forceinline__ void stsm4(uint32_t addr, uint32_t a, uint32_t b, uint32_t c, uint32_t d){
  asm volatile("stmatrix.sync.aligned.m8n8.x4.shared.b16 [%0], {%1,%2,%3,%4};"::"r"(addr),"r"(a),"r"(b),"r"(c),"r"(d)); }
__device__ __forceinline__ void stsm2(uint32_t addr, uint32_t a, uint32_t b){
  asm volatile("stmatrix.sync.aligned.m8n8.x2.shared.b16 [%0], {%1,%2};"::"r"(addr),"r"(a),"r"(b)); }
__device__ __forceinline__ void mma16816(float& d0, float& d1, float& d2, float& d3, uint32_t a0, uint32_t a1, uint32_t a2, uint32_t a3, uint32_t b0, uint32_t b1){
  asm volatile("mma.sync.aligned.m16n8k16.row.col.f32.bf16.bf16.f32 {%0,%1,%2,%3}, {%4,%5,%6,%7}, {%8,%9}, {%0,%1,%2,%3};"
               : "+f"(d0), "+f"(d1), "+f"(d2), "+f"(d3) : "r"(a0), "r"(a1), "r"(a2), "r"(a3), "r"(b0), "r"(b1)); }
__device__ __forceinline__ void ldsm4(uint32_t addr, uint32_t& a, uint32_t& b, uint32_t& c, uint32_t& d){
  asm volatile("ldmatrix.sync.aligned.m8n8.x4.shared.b16 {%0,%1,%2,%3}, [%4];":"=r"(a),"=r"(b),"=r"(c),"=r"(d):"r"(addr):"memory"); }
__device__ __forceinline__ void ldsm4t(uint32_t addr, uint32_t& a, uint32_t& b, uint32_t& c, uint32_t& d){
  asm volatile("ldmatrix.sync.aligned.m8n8.x4.trans.shared.b16 {%0,%1,%2,%3}, [%4];":"=r"(a),"=r"(b),"=r"(c),"=r"(d):"r"(addr):"memory"); }
__device__ __forceinline__ void sts32(uint32_t a, uint32_t v){ asm volatile("st.shared.b32 [%0], %1;"::"r"(a),"r"(v):"memory"); }
__device__ __forceinline__ void stsf(uint32_t a, float v){ asm volatile("st.shared.f32 [%0], %1;"::"r"(a),"f"(v):"memory"); }
__device__ __forceinline__ void sts64(uint32_t a, uint32_t x, uint32_t y){ asm volatile("st.shared.v2.b32 [%0], {%1,%2};"::"r"(a),"r"(x),"r"(y):"memory"); }
__device__ __forceinline__ void sts128(uint32_t a, uint32_t x, uint32_t y, uint32_t z, uint32_t w){ asm volatile("st.shared.v4.b32 [%0], {%1,%2,%3,%4};"::"r"(a),"r"(x),"r"(y),"r"(z),"r"(w):"memory"); }
__device__ __forceinline__ float ldsf(uint32_t a){ float v; asm volatile("ld.shared.f32 %0, [%1];":"=f"(v):"r"(a):"memory"); return v; }
__device__ __forceinline__ float2 lds64f(uint32_t a){ float2 v; asm volatile("ld.shared.v2.f32 {%0,%1}, [%2];":"=f"(v.x),"=f"(v.y):"r"(a):"memory"); return v; }
__device__ __forceinline__ uint4 lds128(uint32_t a){ uint4 v; asm volatile("ld.shared.v4.u32 {%0,%1,%2,%3}, [%4];":"=r"(v.x),"=r"(v.y),"=r"(v.z),"=r"(v.w):"r"(a):"memory"); return v; }
__device__ __forceinline__ uint4 ld128_keep(const void* p){ uint4 v; asm volatile("ld.global.v4.u32 {%0,%1,%2,%3}, [%4];":"=r"(v.x),"=r"(v.y),"=r"(v.z),"=r"(v.w):"l"(p):"memory"); return v; }
__device__ __forceinline__ uint4 ld128_rlx(const void* p){ uint4 v; asm volatile("ld.relaxed.gpu.global.v4.u32 {%0,%1,%2,%3}, [%4];":"=r"(v.x),"=r"(v.y),"=r"(v.z),"=r"(v.w):"l"(p):"memory"); return v; }
__device__ __forceinline__ uint32_t ld32_rlx(const void* p){ uint32_t v; asm volatile("ld.relaxed.gpu.global.u32 %0, [%1];":"=r"(v):"l"(p):"memory"); return v; }
__device__ __forceinline__ void st128_rlx(void* p, uint32_t x, uint32_t y, uint32_t z, uint32_t w){ asm volatile("st.relaxed.gpu.global.v4.u32 [%0], {%1,%2,%3,%4};"::"l"(p),"r"(x),"r"(y),"r"(z),"r"(w):"memory"); }
__device__ __forceinline__ void st64_rlx(void* p, uint32_t x, uint32_t y){ asm volatile("st.relaxed.gpu.global.v2.u32 [%0], {%1,%2};"::"l"(p),"r"(x),"r"(y):"memory"); }
__device__ __forceinline__ void st32_rlx(void* p, uint32_t x){ asm volatile("st.relaxed.gpu.global.u32 [%0], %1;"::"l"(p),"r"(x):"memory"); }
__device__ __forceinline__ uint32_t tagw(float x, uint32_t t){ return (__float_as_uint(x) & ~3u) | t; }
__device__ __forceinline__ float untag(uint32_t w){ return __uint_as_float(w & ~3u); }

template<int TA, int TB, uint32_t HA, uint32_t HB> __device__ __forceinline__ void wgmma_ss_n128(float (&d)[64], uint32_t da, uint32_t db, int scale_d){
  asm volatile("{\n.reg .pred p;\n.reg .b64 a, b;\nsetp.ne.b32 p, %70, 0;\nmov.b64 a, {%64, %68};\nmov.b64 b, {%65, %69};\n"
  "wgmma.mma_async.sync.aligned.m64n128k16.f32.bf16.bf16 {%0, %1, %2, %3, %4, %5, %6, %7, %8, %9, %10, %11, %12, %13, %14, %15, %16, %17, %18, %19, %20, %21, %22, %23, %24, %25, %26, %27, %28, %29, %30, %31, %32, %33, %34, %35, %36, %37, %38, %39, %40, %41, %42, %43, %44, %45, %46, %47, %48, %49, %50, %51, %52, %53, %54, %55, %56, %57, %58, %59, %60, %61, %62, %63}, a, b, p, 1, 1, %66, %67;\n}\n"
  : "+f"(d[0]), "+f"(d[1]), "+f"(d[2]), "+f"(d[3]), "+f"(d[4]), "+f"(d[5]), "+f"(d[6]), "+f"(d[7]), "+f"(d[8]), "+f"(d[9]), "+f"(d[10]), "+f"(d[11]), "+f"(d[12]), "+f"(d[13]), "+f"(d[14]), "+f"(d[15]), "+f"(d[16]), "+f"(d[17]), "+f"(d[18]), "+f"(d[19]), "+f"(d[20]), "+f"(d[21]), "+f"(d[22]), "+f"(d[23]), "+f"(d[24]), "+f"(d[25]), "+f"(d[26]), "+f"(d[27]), "+f"(d[28]), "+f"(d[29]), "+f"(d[30]), "+f"(d[31]), "+f"(d[32]), "+f"(d[33]), "+f"(d[34]), "+f"(d[35]), "+f"(d[36]), "+f"(d[37]), "+f"(d[38]), "+f"(d[39]), "+f"(d[40]), "+f"(d[41]), "+f"(d[42]), "+f"(d[43]), "+f"(d[44]), "+f"(d[45]), "+f"(d[46]), "+f"(d[47]), "+f"(d[48]), "+f"(d[49]), "+f"(d[50]), "+f"(d[51]), "+f"(d[52]), "+f"(d[53]), "+f"(d[54]), "+f"(d[55]), "+f"(d[56]), "+f"(d[57]), "+f"(d[58]), "+f"(d[59]), "+f"(d[60]), "+f"(d[61]), "+f"(d[62]), "+f"(d[63])
  : "r"(da), "r"(db), "n"(TA), "n"(TB), "n"(HA), "n"(HB), "r"(scale_d));
}
template<int TA, int TB, uint32_t HA, uint32_t HB> __device__ __forceinline__ void wgmma_sa_n128(float (&d)[64], uint32_t da, uint32_t db){
  asm volatile("{\n.reg .pred p;\n.reg .b64 a, b;\nsetp.ne.b32 p, 1, 0;\nmov.b64 a, {%64, %68};\nmov.b64 b, {%65, %69};\n"
  "wgmma.mma_async.sync.aligned.m64n128k16.f32.bf16.bf16 {%0, %1, %2, %3, %4, %5, %6, %7, %8, %9, %10, %11, %12, %13, %14, %15, %16, %17, %18, %19, %20, %21, %22, %23, %24, %25, %26, %27, %28, %29, %30, %31, %32, %33, %34, %35, %36, %37, %38, %39, %40, %41, %42, %43, %44, %45, %46, %47, %48, %49, %50, %51, %52, %53, %54, %55, %56, %57, %58, %59, %60, %61, %62, %63}, a, b, p, 1, 1, %66, %67;\n}\n"
  : "+f"(d[0]), "+f"(d[1]), "+f"(d[2]), "+f"(d[3]), "+f"(d[4]), "+f"(d[5]), "+f"(d[6]), "+f"(d[7]), "+f"(d[8]), "+f"(d[9]), "+f"(d[10]), "+f"(d[11]), "+f"(d[12]), "+f"(d[13]), "+f"(d[14]), "+f"(d[15]), "+f"(d[16]), "+f"(d[17]), "+f"(d[18]), "+f"(d[19]), "+f"(d[20]), "+f"(d[21]), "+f"(d[22]), "+f"(d[23]), "+f"(d[24]), "+f"(d[25]), "+f"(d[26]), "+f"(d[27]), "+f"(d[28]), "+f"(d[29]), "+f"(d[30]), "+f"(d[31]), "+f"(d[32]), "+f"(d[33]), "+f"(d[34]), "+f"(d[35]), "+f"(d[36]), "+f"(d[37]), "+f"(d[38]), "+f"(d[39]), "+f"(d[40]), "+f"(d[41]), "+f"(d[42]), "+f"(d[43]), "+f"(d[44]), "+f"(d[45]), "+f"(d[46]), "+f"(d[47]), "+f"(d[48]), "+f"(d[49]), "+f"(d[50]), "+f"(d[51]), "+f"(d[52]), "+f"(d[53]), "+f"(d[54]), "+f"(d[55]), "+f"(d[56]), "+f"(d[57]), "+f"(d[58]), "+f"(d[59]), "+f"(d[60]), "+f"(d[61]), "+f"(d[62]), "+f"(d[63])
  : "r"(da), "r"(db), "n"(TA), "n"(TB), "n"(HA), "n"(HB));
}
template<int TA, int TB, uint32_t HA, uint32_t HB> __device__ __forceinline__ void wgmma_sa_n40(float (&d)[20], uint32_t da, uint32_t db){
  asm volatile("{\n.reg .pred p;\n.reg .b64 a, b;\nsetp.ne.b32 p, 1, 0;\nmov.b64 a, {%20, %24};\nmov.b64 b, {%21, %25};\n"
  "wgmma.mma_async.sync.aligned.m64n40k16.f32.bf16.bf16 {%0, %1, %2, %3, %4, %5, %6, %7, %8, %9, %10, %11, %12, %13, %14, %15, %16, %17, %18, %19}, a, b, p, 1, 1, %22, %23;\n}\n"
  : "+f"(d[0]), "+f"(d[1]), "+f"(d[2]), "+f"(d[3]), "+f"(d[4]), "+f"(d[5]), "+f"(d[6]), "+f"(d[7]), "+f"(d[8]), "+f"(d[9]), "+f"(d[10]), "+f"(d[11]), "+f"(d[12]), "+f"(d[13]), "+f"(d[14]), "+f"(d[15]), "+f"(d[16]), "+f"(d[17]), "+f"(d[18]), "+f"(d[19])
  : "r"(da), "r"(db), "n"(TA), "n"(TB), "n"(HA), "n"(HB));
}
template<int TA, int TB, uint32_t HA, uint32_t HB> __device__ __forceinline__ void wgmma_sz_n40(float (&d)[20], uint32_t da, uint32_t db){
  asm volatile("{\n.reg .pred p;\n.reg .b64 a, b;\nsetp.ne.b32 p, 0, 0;\nmov.b64 a, {%20, %24};\nmov.b64 b, {%21, %25};\n"
  "wgmma.mma_async.sync.aligned.m64n40k16.f32.bf16.bf16 {%0, %1, %2, %3, %4, %5, %6, %7, %8, %9, %10, %11, %12, %13, %14, %15, %16, %17, %18, %19}, a, b, p, 1, 1, %22, %23;\n}\n"
  : "=f"(d[0]), "=f"(d[1]), "=f"(d[2]), "=f"(d[3]), "=f"(d[4]), "=f"(d[5]), "=f"(d[6]), "=f"(d[7]), "=f"(d[8]), "=f"(d[9]), "=f"(d[10]), "=f"(d[11]), "=f"(d[12]), "=f"(d[13]), "=f"(d[14]), "=f"(d[15]), "=f"(d[16]), "=f"(d[17]), "=f"(d[18]), "=f"(d[19])
  : "r"(da), "r"(db), "n"(TA), "n"(TB), "n"(HA), "n"(HB));
}
template<int TA, int TB, uint32_t HA, uint32_t HB> __device__ __forceinline__ void wgmma_sa_n32(float (&d)[16], uint32_t da, uint32_t db){
  asm volatile("{\n.reg .pred p;\n.reg .b64 a, b;\nsetp.ne.b32 p, 1, 0;\nmov.b64 a, {%16, %20};\nmov.b64 b, {%17, %21};\n"
  "wgmma.mma_async.sync.aligned.m64n32k16.f32.bf16.bf16 {%0, %1, %2, %3, %4, %5, %6, %7, %8, %9, %10, %11, %12, %13, %14, %15}, a, b, p, 1, 1, %18, %19;\n}\n"
  : "+f"(d[0]), "+f"(d[1]), "+f"(d[2]), "+f"(d[3]), "+f"(d[4]), "+f"(d[5]), "+f"(d[6]), "+f"(d[7]), "+f"(d[8]), "+f"(d[9]), "+f"(d[10]), "+f"(d[11]), "+f"(d[12]), "+f"(d[13]), "+f"(d[14]), "+f"(d[15])
  : "r"(da), "r"(db), "n"(TA), "n"(TB), "n"(HA), "n"(HB));
}
template<int TA, int TB, uint32_t HA, uint32_t HB> __device__ __forceinline__ void wgmma_ss_n32(float (&d)[16], uint32_t da, uint32_t db, int scale_d){
  asm volatile("{\n.reg .pred p;\n.reg .b64 a, b;\nsetp.ne.b32 p, %22, 0;\nmov.b64 a, {%16, %20};\nmov.b64 b, {%17, %21};\n"
  "wgmma.mma_async.sync.aligned.m64n32k16.f32.bf16.bf16 {%0, %1, %2, %3, %4, %5, %6, %7, %8, %9, %10, %11, %12, %13, %14, %15}, a, b, p, 1, 1, %18, %19;\n}\n"
  : "+f"(d[0]), "+f"(d[1]), "+f"(d[2]), "+f"(d[3]), "+f"(d[4]), "+f"(d[5]), "+f"(d[6]), "+f"(d[7]), "+f"(d[8]), "+f"(d[9]), "+f"(d[10]), "+f"(d[11]), "+f"(d[12]), "+f"(d[13]), "+f"(d[14]), "+f"(d[15])
  : "r"(da), "r"(db), "n"(TA), "n"(TB), "n"(HA), "n"(HB), "r"(scale_d));
}
template<int TB, uint32_t HB> __device__ __forceinline__ void wgmma_ra_n32(float (&d)[16], uint32_t a0, uint32_t a1, uint32_t a2, uint32_t a3, uint32_t db){
  asm volatile("{\n.reg .pred p;\n.reg .b64 a, b;\nsetp.ne.b32 p, 1, 0;\nmov.b64 b, {%20, %22};\n"
  "wgmma.mma_async.sync.aligned.m64n32k16.f32.bf16.bf16 {%0, %1, %2, %3, %4, %5, %6, %7, %8, %9, %10, %11, %12, %13, %14, %15}, {%16,%17,%18,%19}, b, p, 1, 1, %21;\n}\n"
  : "+f"(d[0]), "+f"(d[1]), "+f"(d[2]), "+f"(d[3]), "+f"(d[4]), "+f"(d[5]), "+f"(d[6]), "+f"(d[7]), "+f"(d[8]), "+f"(d[9]), "+f"(d[10]), "+f"(d[11]), "+f"(d[12]), "+f"(d[13]), "+f"(d[14]), "+f"(d[15])
  : "r"(a0), "r"(a1), "r"(a2), "r"(a3), "r"(db), "n"(TB), "n"(HB));
}
template<int TB, uint32_t HB> __device__ __forceinline__ void wgmma_rs_n32(float (&d)[16], uint32_t a0, uint32_t a1, uint32_t a2, uint32_t a3, uint32_t db, int scale_d){
  asm volatile("{\n.reg .pred p;\n.reg .b64 a, b;\nsetp.ne.b32 p, %23, 0;\nmov.b64 b, {%20, %22};\n"
  "wgmma.mma_async.sync.aligned.m64n32k16.f32.bf16.bf16 {%0, %1, %2, %3, %4, %5, %6, %7, %8, %9, %10, %11, %12, %13, %14, %15}, {%16,%17,%18,%19}, b, p, 1, 1, %21;\n}\n"
  : "+f"(d[0]), "+f"(d[1]), "+f"(d[2]), "+f"(d[3]), "+f"(d[4]), "+f"(d[5]), "+f"(d[6]), "+f"(d[7]), "+f"(d[8]), "+f"(d[9]), "+f"(d[10]), "+f"(d[11]), "+f"(d[12]), "+f"(d[13]), "+f"(d[14]), "+f"(d[15])
  : "r"(a0), "r"(a1), "r"(a2), "r"(a3), "r"(db), "n"(TB), "n"(HB), "r"(scale_d));
}
template<int TB, uint32_t HB> __device__ __forceinline__ void wgmma_ra_n40(float (&d)[20], uint32_t a0, uint32_t a1, uint32_t a2, uint32_t a3, uint32_t db){
  asm volatile("{\n.reg .pred p;\n.reg .b64 a, b;\nsetp.ne.b32 p, 1, 0;\nmov.b64 b, {%24, %26};\n"
  "wgmma.mma_async.sync.aligned.m64n40k16.f32.bf16.bf16 {%0, %1, %2, %3, %4, %5, %6, %7, %8, %9, %10, %11, %12, %13, %14, %15, %16, %17, %18, %19}, {%20,%21,%22,%23}, b, p, 1, 1, %25;\n}\n"
  : "+f"(d[0]), "+f"(d[1]), "+f"(d[2]), "+f"(d[3]), "+f"(d[4]), "+f"(d[5]), "+f"(d[6]), "+f"(d[7]), "+f"(d[8]), "+f"(d[9]), "+f"(d[10]), "+f"(d[11]), "+f"(d[12]), "+f"(d[13]), "+f"(d[14]), "+f"(d[15]), "+f"(d[16]), "+f"(d[17]), "+f"(d[18]), "+f"(d[19])
  : "r"(a0), "r"(a1), "r"(a2), "r"(a3), "r"(db), "n"(TB), "n"(HB));
}
template<int TB, uint32_t HB> __device__ __forceinline__ void wgmma_rz_n40(float (&d)[20], uint32_t a0, uint32_t a1, uint32_t a2, uint32_t a3, uint32_t db){
  asm volatile("{\n.reg .pred p;\n.reg .b64 a, b;\nsetp.ne.b32 p, 0, 0;\nmov.b64 b, {%24, %26};\n"
  "wgmma.mma_async.sync.aligned.m64n40k16.f32.bf16.bf16 {%0, %1, %2, %3, %4, %5, %6, %7, %8, %9, %10, %11, %12, %13, %14, %15, %16, %17, %18, %19}, {%20,%21,%22,%23}, b, p, 1, 1, %25;\n}\n"
  : "=f"(d[0]), "=f"(d[1]), "=f"(d[2]), "=f"(d[3]), "=f"(d[4]), "=f"(d[5]), "=f"(d[6]), "=f"(d[7]), "=f"(d[8]), "=f"(d[9]), "=f"(d[10]), "=f"(d[11]), "=f"(d[12]), "=f"(d[13]), "=f"(d[14]), "=f"(d[15]), "=f"(d[16]), "=f"(d[17]), "=f"(d[18]), "=f"(d[19])
  : "r"(a0), "r"(a1), "r"(a2), "r"(a3), "r"(db), "n"(TB), "n"(HB));
}
template<int TB, uint32_t HB> __device__ __forceinline__ void wgmma_rz_n8(float (&d)[4], uint32_t a0, uint32_t a1, uint32_t a2, uint32_t a3, uint32_t db){
  asm volatile("{\n.reg .pred p;\n.reg .b64 a, b;\nsetp.ne.b32 p, 0, 0;\nmov.b64 b, {%8, %10};\n"
  "wgmma.mma_async.sync.aligned.m64n8k16.f32.bf16.bf16 {%0, %1, %2, %3}, {%4,%5,%6,%7}, b, p, 1, 1, %9;\n}\n"
  : "=f"(d[0]), "=f"(d[1]), "=f"(d[2]), "=f"(d[3])
  : "r"(a0), "r"(a1), "r"(a2), "r"(a3), "r"(db), "n"(TB), "n"(HB));
}

constexpr int SEQ = 2048, DM = 1024, FF = 3584;
constexpr float LOG2E = 1.4426950408889634f;
constexpr uint32_t POLL_LIMIT = 1u << 22;
#define NPRE0 1
#define NPREN 2
constexpr int NPRE = NPREN;
#define QW 4
#define RS_N 22
#define RS_D1 430
#define RS_D2 300
#define SKM 0x154
#define LAG 2
#define PF_T0 5000
#define PF_DT 800
#define NFFN_L NFFN
#define FF_DT 500
#define GRES 8
#define TMASK 0xffffff
#define PMASK 0xffffff
#define FF_T0 400
#define GPRE 0
#define REL 6
#define EFI 11
#define TKW 8
#define SLOT 0
#define SLOTW 48
#define FF_ORD 0x76543210ba98ull
#define KT 0
#define KK(id) do { if (KT) { TK(32 * wg + (id)); } } while (0)
#define PF_I0 0
#define PF_ST 7
#define PRK 3
#define TRKL 1
#define KR 4
#define KSEL c
#define XP 0
#define CAPL 2
#define OUT_D 400
#define OUT_0 0
constexpr int NFFN = 112;

constexpr uint32_t SB0 = 1024;
constexpr uint32_t KV_STAGE = 49152, R5 = 32768;
constexpr uint32_t OFF_X = 163840, OFF_S = 196608, OFF_WPHI = OFF_S + 20480, OFF_M = 229376, SMEM_BYTES = 232448;
constexpr uint32_t OFF_RS256 = 212992, OFF_ONES = OFF_RS256 + 1024, OFF_WPHIK1 = OFF_ONES + 1024, OFF_KVZ = OFF_S;
constexpr uint32_t OFF_WPHIK = OFF_S, OFF_BXK = OFF_S + 2048, OFF_AXK = OFF_S + 4096, OFF_G = OFF_S + 8192;
constexpr uint32_t OFF_AXQ = OFF_WPHI, OFF_BXQ = OFF_WPHI + 2048, OFF_WPHIQ = OFF_WPHI + 4096;
constexpr uint32_t B_FULLKV = OFF_M  , B_EMPTYKV = OFF_M + 32  ;
constexpr uint32_t B_EMPTY5 = OFF_M + 64  , B_UO = B_EMPTY5 + 48  , B_RC = B_UO + 32  ;
constexpr uint32_t B_OUT = B_RC + 16  , B_SD = B_OUT + 16, B_AUX = B_SD + 8, B_AUXQ = B_AUX + 8, B_RX = B_AUXQ + 8;
constexpr uint32_t B_FULL5 = B_RX + 8  , B_FULLA = B_FULL5 + 48  , B_F = B_FULLA + 96  , B_WD = B_F + 64  ;
constexpr uint32_t B_WC = B_WD + 32  , B_DR = B_WC + 32  , B_W = B_DR + 24, B_OS = B_W + 8, B_R = B_W + 16, B_KD = B_W + 24, B_R1 = B_W + 32, B_T = B_W + 40, B_G = B_W + 48, B_END = B_W + 56, B_S0 = B_END;
static_assert(B_S0 < OFF_M + 592 && B_END <= OFF_M + 592 && B_FULL5 + 40 >= OFF_M + 208 && B_FULL5 + 40 < OFF_M + 400, "barriers");
constexpr uint32_t OFF_SUMWR = OFF_M + 608, OFF_EP = OFF_M + 624, OFF_KEY = OFF_M + 628;
constexpr uint32_t OFF_RSQ = OFF_M + 640, OFF_TL = OFF_M + 1152, OFF_SEL = OFF_M + 1648, OFF_T = OFF_M + 1792, OFF_WR = OFF_M + 2048, OFF_SCR = OFF_M + 2432;
constexpr uint32_t OFF_XSEL = 2 * R5, OFF_GU = OFF_XSEL + 4096, OFF_OUT = 3 * R5;
constexpr uint64_t FF_SLOT = 0xdcdc3210dcbaull;
constexpr int KVP = 6 * 128;

enum { NB_G2E = 1, NB_XS = 2, NB_WG01 = 3, NB_ACT = 4, NB_Q0 = 5  , NB_ST = 14, NB_DN = 9, NB_ZERO = 10, NB_PUB = 11, NB_TOK = 10  , NB_L0 = 12  , NB_WG2 = 7, NB_QGO = 15 };

struct Scratch {
  bf16     o[SEQ * DM];
  float4   rstat[SEQ];
  uint32_t key[8 * KR * 128];
  uint32_t cand[128 * 512];
  float4   yacc[4 * 3 * 128];
  float4   kvacc[32 * KVP];
  uint2    stats[SEQ];
  uint32_t cskv[2 * DM];
  uint32_t csq[4 * DM];
  uint32_t oset[128 * 16];
  uint32_t epoch;
};
__device__ __align__(1024) Scratch g_scr;
#define TS(id)
#define TDUMP()
#define TS0_DECL()
#define TS0_READ()
#define TS0_WRITE()
#define TK(id)
#define TSW(id)

struct Params {
  CUtensorMap x128, x64, wkv, wq, wo[2], wd, wg, wu, phi, tg, tu, td, xs, ws, qs, out;
  const bf16 *x, *wqkv, *wo_p, *wg_p, *wu_p, *wd_p, *wr;
  bf16* out_p;
  Scratch* g;
  uint32_t zero;
};

constexpr float EXP_LIM = 1.1529215e18f, ARG_LIM2 = 3600.f;
template<bool PR> __device__ __forceinline__ void dual_exp2(const float (&p)[16], uint32_t (&ep)[8], uint32_t (&em)[8]) {
  #pragma unroll
  for (int k = 0; k < 8; k++) {
    const float a = ex2(p[2*k]), b = ex2(p[2*k+1]);
    ep[k] = pack_bf16(a, b);
    if (PR) { const float r = rcp(a * b); em[k] = pack_bf16(r * b, r * a); }
    else em[k] = pack_bf16(ex2(-p[2*k]), ex2(-p[2*k+1]));
  }
}
__device__ __forceinline__ void dual_exp2_shifted(const float (&pp)[2][16], uint32_t (&ph)[4][8]) {
  #pragma unroll
  for (int h = 0; h < 2; h++) {
    const float* p = pp[h];
    float m[4] = {p[0], p[2], p[0], p[2]};
    #pragma unroll
    for (int i = 0; i < 16; i++) { m[(i >> 1) & 1] = fmaxf(m[(i >> 1) & 1], p[i]); m[2 + ((i >> 1) & 1)] = fminf(m[2 + ((i >> 1) & 1)], p[i]); }
    #pragma unroll
    for (int o = 1; o < 4; o <<= 1) {
      m[0] = fmaxf(m[0], __shfl_xor_sync(~0u, m[0], o)); m[1] = fmaxf(m[1], __shfl_xor_sync(~0u, m[1], o));
      m[2] = fminf(m[2], __shfl_xor_sync(~0u, m[2], o)); m[3] = fminf(m[3], __shfl_xor_sync(~0u, m[3], o));
    }
    #pragma unroll
    for (int k = 0; k < 8; k++) {
      ph[2*h][k] = pack_bf16(ex2(p[2*k] - m[k & 1]), ex2(p[2*k+1] - m[k & 1]));
      ph[2*h+1][k] = pack_bf16(ex2(m[2 + (k & 1)] - p[2*k]), ex2(m[2 + (k & 1)] - p[2*k+1]));
    }
  }
}
__device__ __forceinline__ uint32_t add_bf16x2(uint32_t a, uint32_t b) { uint32_t r; asm("add.rn.bf16x2 %0, %1, %2;" : "=r"(r) : "r"(a), "r"(b)); return r; }
__device__ __forceinline__ void row_sums(float (&s)[2][4], const uint32_t (&ph)[4][8], uint32_t sel) {
  uint32_t u[8];
  #pragma unroll
  for (int i = 0; i < 8; i++) { const uint32_t* f = &ph[i >> 1][i & 1]; u[i] = add_bf16x2(add_bf16x2(f[0], f[2]), add_bf16x2(f[4], f[6])); }
  wg_fence();
  wgmma_rz_n8<0, H0>(s[0], u[0], u[1], u[2], u[3], sel);
  wgmma_rz_n8<0, H0>(s[1], u[4], u[5], u[6], u[7], sel);
  wg_commit();
}
__device__ __forceinline__ uint32_t mul_bf16x2(uint32_t a, uint32_t b) { uint32_t r; asm("mul.rn.bf16x2 %0, %1, %2;" : "=r"(r) : "r"(a), "r"(b)); return r; }
__device__ __forceinline__ void normalize(uint32_t (&ph)[4][8], const float (&s)[2][4]) {
  #pragma unroll
  for (int i = 0; i < 4; i++) {
    const float i0 = rcp(s[i >> 1][i & 1]), i1 = rcp(s[i >> 1][2 + (i & 1)]);
    const uint32_t n0 = pack_bf16(i0, i0), n1 = pack_bf16(i1, i1);
    #pragma unroll
    for (int k = 0; k < 4; k++) { ph[i][2*k] = mul_bf16x2(ph[i][2*k], n0); ph[i][2*k+1] = mul_bf16x2(ph[i][2*k+1], n1); }
  }
}
__device__ __forceinline__ void split_bf16(float a, float b, uint32_t& hi, uint32_t& lo) { hi = pack_bf16(a, b); lo = pack_bf16(a - bf_lo(hi), b - bf_hi(hi)); }
__device__ __forceinline__ void put_colsums(uint32_t base, int lane, float a, float b, float c, float d) {
  uint32_t h0, l0, h1, l1;
  split_bf16(a, b, h0, l0); split_bf16(c, d, h1, l1);
  const uint32_t ad = base + (lane >> 1) * 128 + (lane & 1) * 8;
  sts64(ad, h0, h1); sts64(ad + 16, l0, l1); sts64(ad + 32, h0, h1); sts64(ad + 48, l0, l1);
  sts128(base + (lane >> 1) * 128 + 64 + (lane & 1) * 32, 0, 0, 0, 0); sts128(base + (lane >> 1) * 128 + 80 + (lane & 1) * 32, 0, 0, 0, 0);
}
__device__ __forceinline__ float reduce8(const float (&v)[8], int lane) {
  const bool b4 = lane & 16, b3 = lane & 8, b2 = lane & 4;
  float a[4], b[2];
  #pragma unroll
  for (int i = 0; i < 4; i++) a[i] = (b4 ? v[4 + i] : v[i]) + __shfl_xor_sync(~0u, b4 ? v[i] : v[4 + i], 16);
  #pragma unroll
  for (int i = 0; i < 2; i++) b[i] = (b3 ? a[2 + i] : a[i]) + __shfl_xor_sync(~0u, b3 ? a[i] : a[2 + i], 8);
  return (b2 ? b[1] : b[0]) + __shfl_xor_sync(~0u, b2 ? b[0] : b[1], 4);
}
__device__ __forceinline__ bool tag_bad(uint4 v, uint32_t tg) { return (((v.x ^ tg) | (v.y ^ tg) | (v.z ^ tg) | (v.w ^ tg)) & 3) != 0; }

__global__ void __launch_bounds__(512, 1) fused_kernel(const __grid_constant__ Params P) {
  extern __shared__ __align__(1024) uint8_t smem_raw[];
  const uint32_t sb = smem_u32(smem_raw);
  const int tid = threadIdx.x, lane = tid & 31;
  TS0_DECL();
  TS0_READ();
  if (tid == 352) { prefetch_map(&P.wkv); prefetch_map(&P.x128); }
  const int cp = blockIdx.x >> 1, rank = blockIdx.x & 1;
  const int cr = cp < 4 ? 32 + 8 * cp : cp - 4 + max((cp * 37 - 1076) >> 8, 0);
  const int c = (cr & 62) + 64 * (cr & 1) + rank;
  const int m256 = c >> 4, nkv = c & 15, m128 = c >> 3, j = c & 7;
  if ((tid >> 5) == 12 && elect_one()) {
    mbar_init(sb + B_S0, 1); mbar_init(sb + B_FULLKV, 1); mbar_init(sb + B_FULLKV + 8, 1);
    fence_async_smem();
    mbar_expect_tx(sb + B_S0, 32768);
    tma_4d(sb + 32768, &P.wkv, 0, 0, nkv, 1, sb + B_S0);
    tma_2d(sb, &P.x128, 0, 256 * m256, sb + B_S0);
    mbar_expect_tx(sb + B_FULLKV, 16384);
    tma_2d(sb + 16384, &P.x128, 0, 256 * m256 + 128, sb + B_FULLKV);
    if (NPRE0 > 1) {
      mbar_expect_tx(sb + B_FULLKV + 8, KV_STAGE);
      tma_4d(sb + KV_STAGE + 32768, &P.wkv, 0, 64, nkv, 1, sb + B_FULLKV + 8);
      tma_2d(sb + KV_STAGE, &P.x128, 64, 256 * m256, sb + B_FULLKV + 8);
      tma_2d(sb + KV_STAGE + 16384, &P.x128, 64, 256 * m256 + 128, sb + B_FULLKV + 8);
    }
    asm volatile("fence.mbarrier_init.release.cluster;" ::: "memory");
  }
  #pragma unroll
  for (int w = 0; w < 3; w++)
    if (tid == 32 + 32 * w) {
      #pragma unroll
      for (uint32_t b = B_FULLKV + 16 + 192 * w; b < B_FULLKV + 208 + 192 * w && b < B_END; b += 8)
        mbar_init(sb + b, b < B_EMPTYKV ? 1 : b < B_EMPTY5 ? 12 : b < B_SD ? 4 : b < B_RX || b == B_W ? 2 : b == B_RX ? 8 : 1);
      if (w == 1) mbar_arrive(sb + B_FULL5 + 40);
      asm volatile("fence.mbarrier_init.release.cluster;" ::: "memory");
      fence_async_smem();
    }
  const int warp = __shfl_sync(~0u, tid >> 5, 0), wg = warp >> 2, wp = warp & 3;
  const int f = 16 * ((cr + 7) & 7) + 2 * (cr >> 3) + rank;
  const int ha = 4 * (nkv >> 1) + (nkv & 1);
  Scratch* const G = P.g;
  if ((sb & 0x3ffff) != SB0) asm volatile("trap;");
  __syncthreads();
  cluster_arrive();
  if (warp == 12) {
    TK(88 - 32);
    if (elect_one()) {
      #pragma unroll
      for (int s = NPRE0; s < NPRE; s++) {
        const uint32_t st = sb + s * KV_STAGE, fb = sb + B_FULLKV + 8 * s;
        mbar_expect_tx(fb, KV_STAGE);
        tma_4d(st + 32768, &P.wkv, 0, 64 * s, nkv, 1, fb);
        tma_2d(st, &P.x128, 64 * s, 256 * m256, fb);
        tma_2d(st + 16384, &P.x128, 64 * s, 256 * m256 + 128, fb);
      }
    }
    __syncwarp();
  }

  if (wg == 3) {
    asm volatile("setmaxnreg.dec.sync.aligned.u32 32;");
    cluster_wait();
    if (wp == 0) { TK(89 - 32); }
    const bool el = elect_one();
    const uint64_t ef = policy_evict_first(), en = policy_evict_normal();
    auto fetch_o = [&](const int t0, uint32_t so, uint32_t par) {
      const int sh = t0 & 1;
      uint32_t ready = 0;
      const bf16* base = G->o + (m128 * 16 + t0) * 8192 + rank * 4096;
      const bf16* hint = base + (lane & 3) * 1024 + 966 + (((j & 6) + ((lane >> 2) & ~sh)) & 7) * 16384 + 8 * sh * (~lane & 4);
      #pragma unroll 1
      for (int i = 2 - 2 * sh; i < 8; i += 1 + sh) {
        uint32_t it = 0;
        while ((~ready >> (4 * i) & (15 + 240 * sh)) && ++it < POLL_LIMIT) ready = __ballot_sync(~0u, ld32_rlx(hint) != ~0u);
        mbar_wait(sb + B_EMPTY5 + so, par);
        if (el) {
          bulk_g2s_mc(sb + so * 4096 + rank * 8192, base + (((j & 6) + i) & 7) * 16384, 8192, sb + B_FULLA + 2 * so + 8 * rank, ef);
          if (i == 2 - 2 * sh) TS(t0 == 0 ? (rank ? 4 : 12) : t0 == 3 ? (rank ? 31 : 10) : (rank ? 9 : 13));
        }
        so += 8;
        if (so == 48) { so = 0; par ^= 1; }
      }
    };
    if (wp == 0) {
      {
        #pragma unroll 1
        for (int kb = NPRE; kb < 16; kb++) {
          const uint32_t st = sb + (kb & 3) * KV_STAGE, fb = sb + B_FULLKV + 8 * (kb & 3);
          mbar_wait(fb + (B_EMPTYKV - B_FULLKV), ~(kb >> 2) & 1);
          if (el) {
            mbar_expect_tx(fb, KV_STAGE);
            tma_2d_mc(st + rank * 16384, &P.x128, 64 * kb, 256 * m256 + 128 * rank, fb);
            tma_4d_h(st + 32768, &P.wkv, 0, 64 * kb, nkv, 1, fb, ef);
          }
        }
        uint64_t ord = 0xf3120edcba987654ull;
        uint32_t so = 0, par = 1;
        #pragma unroll 1
        for (int i = 0; i < 16; i++) {
          const uint32_t st = sb + so * 4096, fb = sb + B_FULL5 + so;
          const int k0 = (64 * (uint32_t)ord + 128 * (j & 6)) & 960;
          mbar_wait(i < 5 ? sb + B_EMPTYKV + so - (i > 1 ? 8 : 0) : fb + (B_EMPTY5 - B_FULL5), par);
          if (el) {
            mbar_expect_tx(fb, R5);
            tma_2d_mc_h(st + rank * 8192, &P.x64, k0, 128 * m128 + 64 * rank, fb, i >= EFI ? ef : en);
            tma_3d_h(st + 16384, &P.wq, 0, k0, 2 * j, fb, ef);
          }
          ord >>= 4; so += 8;
          if (so == 40) { so = 0; par ^= 1; }
        }
        mbar_wait(sb + B_FULL5 + 8 + 8 * rank, 0); if (el) mbar_arrive(sb + B_R);
        mbar_wait(sb + B_FULL5 + 24 + 8 * rank, 0); if (el) mbar_arrive(sb + B_R1);
        #pragma unroll 1
        for (int i = 0; i < 19; i++) {
          const uint32_t fb = sb + B_FULL5 + so, fa = sb + B_FULLA + 2 * so, na = i == rank ? 0 : 8192;
          mbar_wait(fb + (B_EMPTY5 - B_FULL5), par);
          if (SLOT) { while (((uint32_t)clock() & (uint32_t)(SLOT - 1)) >= SLOTW) {} }
          if (el) {
            if (i < 16) {
              mbar_expect_tx(fb, 16384);
              const int row = i < 8 ? 128 * (((j & 6) + i) & 7) : 256 * (((j >> 1) + i) & 3) + 32 + 16 * (i & 4);
              tma_5d_h(sb + so * 4096 + 16384, &P.wo[i >> 3], 128 * j, row, fb, ef);
              tma_5d_h(sb + so * 4096 + 24576, &P.wo[i >> 3], 128 * j + 64, row, fb, ef);
              mbar_expect_tx(fa, na); mbar_expect_tx(fa + 8, na);
            } else mbar_arrive(sb + B_DR + 8 * (i - 16));
          }
          so += 8;
          if (so == 48) { so = 0; par ^= 1; }
        }
      }
    } else if (wp == 3) {
      const uint32_t t_start = (uint32_t)clock();
      if (el) {
        mbar_expect_tx(sb + B_W, 12288);
        #pragma unroll 1
        for (int i = 0; i < 6; i++) tma_2d(sb + (i == 0 ? OFF_WPHIK : i == 1 ? OFF_WPHIK1 : OFF_WPHIQ + 2048 * (i - 2)), &P.phi, 0, 32 * (i < 2 ? 2 * nkv + i : 4 * j + 2 * (i & 1) + ((i - 2) >> 1)), sb + B_W);
        prefetch_map(&P.x64); prefetch_map(&P.wq); prefetch_map(&P.wo[0]); prefetch_map(&P.wo[1]);
        prefetch_map(&P.wd); prefetch_map(&P.out); prefetch_map(&P.wg); prefetch_map(&P.wu);
      }
      #pragma unroll 1
      for (int i = 0; i < 8; i++) {
        if (lane < 16) st128_rlx(&G->cand[(m128 * 8 + i) * 512 + 64 * j + 4 * lane], ~0u, ~0u, ~0u, ~0u);
      }
      if (lane < 16) st128_rlx(&G->rstat[16 * c + lane], 0, 0, 0, 0);
      if (lane < 12) st128_rlx(&G->yacc[12 * c + lane], 0, 0, 0, 0);
      {
        const uint32_t nt = ld32_rlx(&G->epoch);
        if (lane < 8) { st128_rlx(&G->stats[16 * c + 2 * lane], nt, nt, nt, nt); st128_rlx(&G->csq[32 * c + 4 * lane], nt, nt, nt, nt); }
        if (lane < 4) { st128_rlx(&G->cskv[128 * nkv + 16 * m256 + 4 * lane], nt, nt, nt, nt); st128_rlx(&G->oset[16 * c + 4 * lane], nt, nt, nt, nt); }
      }
      if (lane < 2 * KR) st128_rlx(&G->key[(KR * j + (lane >> 1)) * 128 + m128 * 8 + 4 * (lane & 1)], 0, 0, 0, 0);
      if (c < 32) {
        #pragma unroll 1
        for (int i = lane; i < KVP; i += 32) st128_rlx(&G->kvacc[(ha + 2 * m256) * KVP + i], 0, 0, 0, 0);
      }
      fence_gpu();
      bar_arrive(NB_ZERO, 160);
      TS0_WRITE();
      if (el) {
        #pragma unroll 1
        for (int i = PF_I0; i < ((XP & 4) ? 0 : 30); i++) {
          while ((uint32_t)clock() - t_start < (uint32_t)(PF_T0 + PF_DT * (i - PF_I0) + PF_ST * f)) __nanosleep(64);
          if (i < 4) { bulk_prefetch(P.wqkv + (size_t)(256 * i + c) * (3 * DM), 2048); bulk_prefetch(P.wqkv + (size_t)(256 * i + 128 + c) * (3 * DM), 2048); }
          else if (i < 6) bulk_prefetch(P.wo_p + (size_t)c * 8192 + (i - 4) * 4096, 8192);
          else if ((TMASK >> (i - 6)) & 1) {
            const int k = i - 6;
            if (f < NFFN) {
              if (k < 16) {
                #pragma unroll 1
                for (int e = 0; e < 4; e++) tma_2d(sb + OFF_T, rank ? &P.tu : &P.tg, 32 * (f & ~1), 64 * k + 16 * e, sb + B_T);
              } else { tma_2d(sb + OFF_T, &P.td, 0, 256 * f + 32 * (k - 16), sb + B_T); tma_2d(sb + OFF_T, &P.td, 0, 256 * f + 32 * (k - 16) + 16, sb + B_T); }
            }
          }
          else if (!((PMASK >> (i - 6)) & 1)) {}
          else if (i < 22) bulk_prefetch(((i & 1) ? P.wu_p : P.wg_p) + (size_t)((i - 6) >> 1) * 458752 + c * 3584, 7168);
          else bulk_prefetch(P.wd_p + (size_t)(i - 22) * 458752 + c * 3584, 7168);
        }
      }
      __syncwarp();
      mbar_wait2(sb + B_OS, 0, sb + B_RX, 0);
      #pragma unroll 1
      for (int t0 = 0; t0 < 4; t0 += 3) fetch_o(t0, t0 ? 8 : 24, 0);
    } else {
      const int half = wp - 1;
      const uint32_t ep1 = ld32_rlx(&G->epoch) + 1, tg = ep1 & 3;
      {
        uint32_t it = 0;
        sts128(sb + OFF_ONES + half * 512 + lane * 16, 0x3f803f80u, 0x3f803f80u, 0x3f803f80u, 0x3f803f80u);
        if (lane < 9) { const uint32_t v = (lane & 1) ? 0 : 0x3f803f80u; sts128(sb + OFF_SEL + lane * 16, v, v, v, v); }
        auto reset_o = [&](int i0, int i1, uint32_t dt) {
          uint32_t t0 = (uint32_t)clock();
          #pragma unroll 1
          for (int i = i0; i < i1; i++) {
            if (!(XP & 2)) st128_rlx(G->o + (m128 * 16 + 2 * j + half) * 8192 + 256 * i + 8 * lane, ~0u, ~0u, ~0u, ~0u);
            while ((uint32_t)clock() - t0 < dt) __nanosleep(40);
            t0 += dt;
          }
        };
        mbar_wait(sb + B_S0, 0);
        reset_o(0, RS_N, RS_D1);
        bar_sync(NB_PUB, 192);
        const uint4* src = reinterpret_cast<const uint4*>(&G->stats[256 * m256 + 128 * half]) + lane;
        const uint4* srk = reinterpret_cast<const uint4*>(&G->cskv[128 * nkv]) + lane;
        uint4 v0, v1, vk;
        it = 0;
        do { v0 = ld128_rlx(src); v1 = ld128_rlx(src + 32); vk = ld128_rlx(srk); }
        while ((tag_bad(v0, tg) || tag_bad(v1, tg) || tag_bad(vk, tg)) && ++it < POLL_LIMIT);
        fence_acquire_gpu();
        if (half) put_colsums(sb + OFF_BXK, lane, untag(vk.x), untag(vk.y), untag(vk.z), untag(vk.w));
        #pragma unroll
        for (int i = 0; i < 2; i++) {
          const uint4 v = i ? v1 : v0;
          uint32_t hi, lo;
          split_bf16(-0.5f * untag(v.x), -0.5f * untag(v.z), hi, lo);
          const uint32_t h0 = __byte_perm(hi, hi, 0x1010), h1 = __byte_perm(hi, hi, 0x3232), l0 = __byte_perm(lo, lo, 0x1010), l1 = __byte_perm(lo, lo, 0x3232);
          const uint32_t a = sb + OFF_AXK + half * 2048 + i * 1024 + lane * 32;
          sts128(a, h0, l0, 0, 0); sts128(a + 16, h1, l1, 0, 0);
          sts64(sb + OFF_RS256 + half * 512 + i * 256 + lane * 8, v.y & ~3u, v.w & ~3u);
          if (half == (m128 & 1)) {
            const uint32_t aq = sb + OFF_AXQ + i * 1024 + lane * 32;
            sts128(aq, h0, l0, 0, 0); sts128(aq + 16, h1, l1, 0, 0);
            sts64(sb + OFF_RSQ + i * 256 + lane * 8, v.y & ~3u, v.w & ~3u);
          }
        }
        fence_async_smem();
        __syncwarp();
        if (el) { sts32(sb + OFF_EP, ep1); mbar_arrive(sb + B_AUX); if (!half) TS(1); }
        reset_o(RS_N, 32, RS_D2);
        fence_gpu();
        __syncwarp();
        if (el) { st32_rlx(&G->oset[16 * c + 8 * half], ep1); if (half) mbar_arrive(sb + B_AUXQ); }
        if (!half) {
          const uint4* src = reinterpret_cast<const uint4*>(&G->csq[128 * j]) + lane;
          uint4 v0, v1, v2, v3;
          do { v0 = ld128_rlx(src); v1 = ld128_rlx(src + DM / 4); v2 = ld128_rlx(src + DM / 2); v3 = ld128_rlx(src + 3 * DM / 4); }
          while ((tag_bad(v0, tg) || tag_bad(v1, tg) || tag_bad(v2, tg) || tag_bad(v3, tg)) && ++it < POLL_LIMIT);
          put_colsums(sb + OFF_BXQ, lane, (untag(v0.x) + untag(v1.x)) + (untag(v2.x) + untag(v3.x)), (untag(v0.y) + untag(v1.y)) + (untag(v2.y) + untag(v3.y)),
                      (untag(v0.z) + untag(v1.z)) + (untag(v2.z) + untag(v3.z)), (untag(v0.w) + untag(v1.w)) + (untag(v2.w) + untag(v3.w)));
          fence_async_smem();
          __syncwarp();
          if (el) mbar_arrive(sb + B_AUXQ);
        }
      }
      if (half == 0) {
        for (uint32_t it = 0; __any_sync(~0u, ld32_rlx(&G->oset[m128 * 128 + 8 * (lane & 15)]) != ep1) && it < POLL_LIMIT; it++) {}
        fence_acquire_gpu();
        if (el) mbar_arrive(sb + B_OS);
      }
      if (!half) {
        #pragma unroll 1
        for (int hh = 0; hh < 2; hh++) {
          const uint32_t src = sb + (1 + rank) * R5 + hh * 8192, fa = sb + B_FULLA + 16 + 16 * rank + 8 * hh;
          mbar_wait(fa, 0);
          mbar_wait(sb + B_UO + 8 * hh, 0);
          if (el) bulk_s2peer(mapa(src, rank ^ 1), src, 8192, mapa(fa, rank ^ 1));
        }
        fetch_o(1, 24, 1);
      }
      else if (f < NFFN_L) {
        mbar_wait2(sb + B_UO, 0, sb + B_UO + 8, 0);
        mbar_wait(sb + B_UO + 24, 0);
        uint32_t t0 = (uint32_t)clock();
        while ((uint32_t)clock() - t0 < (uint32_t)FF_T0) __nanosleep(32);
        t0 -= FF_DT;
        #pragma unroll 1
        for (int i = 0; i < 12; i++) {
          const int e = (FF_ORD >> (4 * i)) & 15;
          const uint32_t dst = sb + 16384 * ((FF_SLOT >> (4 * e)) & 15), fb = sb + B_F + 8 * e;
          if (i >= 2) mbar_wait(sb + B_WC + 8 * ((0x100066553244ull >> (4 * e)) & 15), 0);
          while ((uint32_t)clock() - t0 < (uint32_t)FF_DT) __nanosleep(32);
          t0 = (uint32_t)clock();
          if (i < 8) { TK(48 + i); }
          if (el) {
            mbar_expect_tx(fb, 16384);
            if (e >= 8) tma_3d_h(dst, &P.wd, 0, 32 * f, 4 * e - 32, fb, ef);
            else { tma_2d(dst, &P.wg, 32 * f, 128 * e, fb); tma_2d(dst + 8192, &P.wu, 32 * f, 128 * e, fb); }
          }
        }
      }
      __syncwarp();
    }
    if (wp & 1) {
      __syncwarp();
      mbar_wait(sb + B_OUT + 8 * (wp >> 1), 0);
      uint32_t t0 = (uint32_t)clock() + OUT_0;
      #pragma unroll 1
      for (int i = 0; i < 8; i++) {
        while ((int32_t)((uint32_t)clock() - t0) < 0) __nanosleep(20);
        if (el) tma_store_2d(&P.out, 128 * j + 64 * (i & 1), 128 * m128 + 32 * (wp & 2) + 8 * (i & 6), sb + OFF_OUT + (i & 1) * 16384 + (wp & 2) * 4096 + (i & 6) * 1024);
        t0 += OUT_D;
      }
      if (el) { bulk_commit(); bulk_wait_all(); fence_async_global(); mbar_arrive(sb + B_SD); TS(19); }
    }
    __syncwarp();
    cluster_arrive(); cluster_wait();
    return;
  }

  asm volatile("setmaxnreg.inc.sync.aligned.u32 160;");
  cluster_wait();
  const int t = tid & 127, g = lane >> 2;
  const uint32_t sa = (16 * wp + (lane & 15)) * 128 + (((lane >> 4) ^ (lane & 7)) << 4);

  if (wg == 2) {
    float s[2] = {0.f, 0.f}, s2[2] = {0.f, 0.f}, ck[8] = {0.f, 0.f, 0.f, 0.f, 0.f, 0.f, 0.f, 0.f}, cs[8] = {0.f, 0.f, 0.f, 0.f, 0.f, 0.f, 0.f, 0.f};
    const uint32_t ebr = mapa(sb + B_EMPTYKV, lane & 1), tg = (ld32_rlx(&G->epoch) + 1) & 3;
    auto addx = [&](const uint4 v) {
      const uint32_t w[4] = {v.x, v.y, v.z, v.w};
      #pragma unroll
      for (int e = 0; e < 4; e++) { const float a = bf_lo(w[e]), d = bf_hi(w[e]); s[0] += a; s[1] += d; s2[0] = fmaf(a, a, s2[0]); s2[1] = fmaf(d, d, s2[1]); }
    };
    auto addc = [&](const uint4 v, float (&o)[8]) {
      o[0] += bf_lo(v.x); o[1] += bf_hi(v.x); o[2] += bf_lo(v.y); o[3] += bf_hi(v.y); o[4] += bf_lo(v.z); o[5] += bf_hi(v.z); o[6] += bf_lo(v.w); o[7] += bf_hi(v.w);
    };
    {
      const uint32_t ra = (16 * nkv + (t >> 3)) * 128 + (t & 7) * 16;
      const uint32_t ca = 32768 + (m256 >> 2) * 8192 + (t >> 1) * 128 + (((2 * (m256 & 3) + (t & 1)) ^ ((t >> 1) & 7)) << 4);
      int rd = 0;
      mbar_wait(sb + B_S0, 0);
      #pragma unroll 1
      for (int kb = 0; kb < 10; kb++) {
        const uint32_t st = sb + (kb & 3) * KV_STAGE;
        mbar_wait(sb + B_FULLKV + 8 * (kb & 3), (kb >> 2) & 1);
        const uint4 x0 = lds128(st + ra), w0 = lds128(st + ca);
        if (!(XP & 1)) { addx(x0); addc(w0, ck); } else s[0] += __uint_as_float(x0.x ^ w0.x);
        __syncwarp();
        if (lane < 2) mbar_arrive_remote(ebr + 8 * (kb & 3), 1);
        if ((SKM >> kb) & 1) {
          if (rd) {
            mbar_wait(sb + B_G, (rd - 1) & 1);
            const uint32_t a = sb + OFF_G + (t >> 3) * 256 + (t & 7) * 16;
            const uint4 x1 = lds128(a), x2 = lds128(a + 128), w1 = lds128(sb + OFF_G + 4096 + t * 16), w2 = lds128(sb + OFF_G + 6144 + t * 16);
            addx(x1); addx(x2); addc(w1, ck); addc(w2, ck);
            bar_sync(NB_WG2, 128);
          }
          if (wp == 0 && elect_one()) {
            mbar_expect_tx(sb + B_G, 8192);
            if (rd < 3) {
              tma_2d(sb + OFF_G, &P.xs, 640 + 128 * rd, 256 * m256 + 16 * nkv, sb + B_G);
              tma_2d(sb + OFF_G + 4096, &P.ws, (1 + (m256 >> 2)) * DM + 64 * nkv + 16 * (m256 & 3), 640 + 128 * rd, sb + B_G);
            } else tma_2d(sb + OFF_G, &P.qs, 32 * (c & 31), 256 * (c >> 5), sb + B_G);
          }
          rd++;
        }
      }
    }
    TK(82);
    const uint32_t scr = sb + OFF_SCR + 128;
    float sx = s[0] + s[1], sq = s2[0] + s2[1];
    #pragma unroll
    for (int o = 1; o < 8; o <<= 1) { sx += __shfl_xor_sync(~0u, sx, o); sq += __shfl_xor_sync(~0u, sq, o); }
    float v = reduce8(ck, lane);
    v += __shfl_xor_sync(~0u, v, 2);
    if (!(lane & 2)) stsf(scr + (wp * 16 + 8 * (lane & 1) + (lane >> 2)) * 4, v);

    bar_sync(NB_ZERO, 160);
    if ((lane & 7) == 0) {
      const float mean = sx * (1.f / DM);
      st64_rlx(&G->stats[256 * m256 + 16 * nkv + (t >> 3)], tagw(mean, tg), tagw(rsqrtf(fmaxf(sq * (1.f / DM) - mean * mean, 0.f) + 1e-5f), tg));
    }
    if (wp == 1 && lane < 16) {
      const uint32_t a = scr + lane * 4;
      st32_rlx(&G->cskv[128 * nkv + 16 * m256 + lane], tagw((ldsf(a) + ldsf(a + 64)) + (ldsf(a + 128) + ldsf(a + 192)), tg));
    }
    __syncwarp();
    bar_arrive(NB_PUB, 192);
    TSW(23);
    const uint4 wv = ld128_keep(P.wr + t * 8);
    #pragma unroll 1
    for (int i = 0; i < 2; i++) {
      mbar_wait(sb + B_G, i ^ 1);
      const uint32_t a = sb + OFF_G + t * 16;
      const uint4 u0 = lds128(a), u1 = lds128(a + 2048), u2 = lds128(a + 4096), u3 = lds128(a + 6144);
      addc(u0, cs); addc(u1, cs); addc(u2, cs); addc(u3, cs);
      bar_sync(NB_WG2, 128);
      if (i == 0 && wp == 0 && elect_one()) { mbar_expect_tx(sb + B_G, 8192); tma_2d(sb + OFF_G, &P.qs, 32 * (c & 31), 256 * (c >> 5) + 128, sb + B_G); }
    }
    if (t == 0) mbar_arrive(sb + B_W);
    float sw = (bf_lo(wv.x) + bf_hi(wv.x)) + (bf_lo(wv.y) + bf_hi(wv.y)) + (bf_lo(wv.z) + bf_hi(wv.z)) + (bf_lo(wv.w) + bf_hi(wv.w));
    #pragma unroll
    for (int o = 16; o; o >>= 1) sw += __shfl_xor_sync(~0u, sw, o);
    if (lane == 0) stsf(sb + OFF_SUMWR + wp * 4, sw);
    if ((t >> 4) == j) {
      const uint32_t a = sb + OFF_WR + (t & 15) * 32;
      sts128(a, wv.x << 16, wv.x & 0xffff0000u, wv.y << 16, wv.y & 0xffff0000u);
      sts128(a + 16, wv.z << 16, wv.z & 0xffff0000u, wv.w << 16, wv.w & 0xffff0000u);
    }
    v = reduce8(cs, lane);
    stsf(scr + (wp * 32 + 8 * (lane & 3) + (lane >> 2)) * 4, v);
    bar_sync(NB_WG2, 128);
    if (wp == 0) {
      const uint32_t a = scr + lane * 4;
      st32_rlx(&G->csq[(c >> 5) * DM + 32 * (c & 31) + lane], tagw((ldsf(a) + ldsf(a + 128)) + (ldsf(a + 256) + ldsf(a + 384)), tg));
    }
  }

  uint32_t xr[32];
  {
    const bool isq = wg == 2;
    float acc[2][64];
    {
      const uint32_t emptyb = mapa(sb + (isq ? B_EMPTY5 : B_EMPTYKV), t & 1);
      if (!isq) {
        mbar_wait(sb + B_S0, 0);
        if (wg) mbar_wait(sb + B_FULLKV, 0);
        if (wg == 0) { TSW(2); }
        #pragma unroll 1
        for (int kb = 0; kb < 16; kb++) {
          if (!KT && wg == 0) { TK(kb); }
          const uint32_t da = dlo(SB0, 16) + wg * 1024 + (kb & 3) * (KV_STAGE >> 4), db = dlo(SB0 + 32768, 8192) + (kb & 3) * (KV_STAGE >> 4);
          wg_fence();
          #pragma unroll
          for (int k = 0; k < 4; k++) {
            wgmma_ss_n128<0, 1, H128, H128>(acc[0], da + 2 * k, db + 128 * k, k > 0 || kb != 0);
            wgmma_ss_n128<0, 1, H128, H128>(acc[1], da + 512 + 2 * k, db + 128 * k, k > 0 || kb != 0);
          }
          wg_commit();
          wg_wait<1>();
          if (kb > 0 && t < 2) mbar_arrive_remote(emptyb + 8 * ((kb - 1) & 3), kb > 10 ? 3 : 1);
          if (kb < 15) mbar_wait(sb + B_FULLKV + 8 * ((kb + 1) & 3), ((kb + 1) >> 2) & 1);
          if (kb == 15 - LAG && wg == 1) bar_sync(NB_WG01, 256);
        }
        bar_arrive(wg ? NB_QGO : NB_WG01, 256);
      } else {
        uint32_t so = 0, po = 0, par = 0;
        mbar_wait(sb + B_FULL5, 0);
        bar_sync(NB_QGO, 256);
        TSW(11);
        #pragma unroll 1
        for (int kb = 0; kb < 16; kb++) {
          TK(16 + kb);
          const uint32_t da = dlo(SB0, 16) + so * 256, db = dlo(SB0 + 16384, 8192) + so * 256;
          #pragma unroll
          for (int k = 0; k < 4; k++) {
            wg_fence();
            wgmma_ss_n128<0, 1, H128, H128>(acc[0], da + 2 * k, db + 128 * k, k > 0 || kb != 0);
            wgmma_ss_n128<0, 1, H128, H128>(acc[1], da + 512 + 2 * k, db + 128 * k, k > 0 || kb != 0);
            wg_commit();
            if (k == 1 && kb > 0 && t < 2) mbar_arrive_remote(emptyb + po, 2);
            if (k == 3) {
              po = so; so += 8;
              if (so == 40) { so = 0; par ^= 1; }
              if (kb < 15) mbar_wait(sb + B_FULL5 + so, par);
            }
            if ((QW >> k) & 1) wg_wait<2>(); else wg_wait<1>();
          }
        }
        mbar_wait(sb + B_AUXQ, 0);
      }
      mbar_wait(sb + B_AUX, 0);
      const uint32_t xa = dlo(SB0, 0) + (isq ? OFF_AXQ >> 4 : (OFF_AXK >> 4) + wg * 128), xb = dlo(SB0, 0) + (isq ? OFF_BXQ >> 4 : OFF_BXK >> 4);
      wg_fence();
      wgmma_sa_n128<0, 1, H0, H0>(acc[0], xa, xb);
      wgmma_sa_n128<0, 1, H0, H0>(acc[1], xa + 64, xb);
      wg_commit();
      if (isq) mbar_wait(sb + B_RC, 0);
      wg_wait<0>();
      if (t < 2) mbar_arrive_remote(emptyb + (isq ? 0 : 24), isq ? 2 : 3);
      if (wg != 1) { TSW(wg ? 8 : 3); }
      fence_regs(acc[0]); fence_regs(acc[1]);
    }
    if (isq) {
      #pragma unroll
      for (int i = 0; i < 2; i++) {
        const uint32_t ta = sb + (1 + rank) * R5 + sa + i * 8192;
        if (i == 1) mbar_wait(sb + B_RC + 8, 0);
        #pragma unroll
        for (int k = 0; k < 4; k++) {
          const float* a = &acc[i][32 * (k >> 1) + 8 * (k & 1)];
          stsm4(ta ^ (k << 5), pack_bf16(a[0], a[1]), pack_bf16(a[2], a[3]), pack_bf16(a[4], a[5]), pack_bf16(a[6], a[7]));
        }
        fence_async_smem();
        bar_arrive(NB_Q0 + i, 256);
      }
      #pragma unroll
      for (int i = 0; i < 32; i++) { const float* a = &acc[(i >> 3) & 1][16 + 32 * (i >> 4) + 2 * (i & 7)]; xr[i] = pack_bf16(a[0], a[1]); }
      TSW(26);
    } else {
      const uint32_t stg = sb + OFF_X + (1 - wg) * 24576;
      const uint32_t va = stg + 16384 + (16 * wp + (lane & 15)) * 64 + (((lane >> 4) ^ ((lane >> 1) & 3)) << 4);
      const uint32_t ra = sb + OFF_RS256 + (128 * wg + 16 * wp + g) * 4;
      const float rs[4] = {ldsf(ra), ldsf(ra + 32), ldsf(ra + 256), ldsf(ra + 288)};
      float p[2][16];
      uint32_t vf[16], kf[2][16];
      auto project = [&](const uint32_t (&f)[16], uint32_t db) {
        wg_fence();
        #pragma unroll
        for (int i = 0; i < 2; i++) {
          wgmma_rs_n32<1, H64>(p[i], f[8*i], f[8*i+1], f[8*i+2], f[8*i+3], db, 0);
          wgmma_ra_n32<1, H64>(p[i], f[8*i+4], f[8*i+5], f[8*i+6], f[8*i+7], db + 64);
        }
        wg_commit();
      };
      auto fold = [&](uint32_t (&f)[16], int col, float sc) {
        #pragma unroll
        for (int i = 0; i < 16; i++) {
          const float r = rs[2 * (i >> 3) + (i & 1)] * sc;
          f[i] = pack_bf16(acc[i >> 3][col + 2 * (i & 7)] * r, acc[i >> 3][col + 2 * (i & 7) + 1] * r);
          asm volatile("" : "+r"(f[i]));
        }
      };
      auto put_v = [&](const uint32_t (&f)[16]) {
        #pragma unroll
        for (int k = 0; k < 4; k++) stsm4((va ^ ((k & 1) << 5)) + (k >> 1) * 4096, f[4*k], f[4*k+1], f[4*k+2], f[4*k+3]);
      };
      KK(0);
      fold(vf, 48, 1.f);
      mbar_wait(sb + B_W, 0);
      fold(kf[0], 0, LOG2E);
      #pragma unroll
      for (int i = 0; i < 32; i++) p[i >> 4][i & 15] = acc[i >> 4][i & 15];
      project(kf[0], dlo(SB0 + OFF_WPHIK, 16));
      mbar_wait(sb + B_W, 0);
      KK(1);
      {
        uint32_t v0[16];
        fold(kf[1], 16, LOG2E);
        fold(v0, 32, 1.f);
        if (wg == 1) bar_sync(NB_DN, 256);
        put_v(v0);
      }
      wg_wait<0>();
      fence_regs(p[0]); fence_regs(p[1]);
      if (wg == 1) bar_arrive(NB_WG01, 256);
      KK(2);
      #pragma unroll 1
      for (int h = 0; h < 2; h++) {
        uint32_t ph[4][8];
        float rsum[2][4];
        dual_exp2<PRK & 1>(p[0], ph[0], ph[1]); dual_exp2<(PRK >> 1)>(p[1], ph[2], ph[3]);
        row_sums(rsum, ph, dlo(SB0 + OFF_SEL, 16));
        KK(3 + 6 * h);
        if (wg == 0 && h == 0) { bar_arrive(NB_DN, 256); bar_sync(NB_WG01, 256); }
        if (h == 1) {
          if (wg == 1) bar_sync(NB_DN, 256);
          put_v(vf);
        }
        wg_wait<0>();
        KK(4 + 6 * h);
        fence_regs(rsum[0]); fence_regs(rsum[1]);
        if (!(XP & 8) && __builtin_expect(__any_sync(~0u, !((rsum[0][0] + rsum[0][1]) + (rsum[0][2] + rsum[0][3]) + (rsum[1][0] + rsum[1][1]) + (rsum[1][2] + rsum[1][3]) < EXP_LIM)), 0)) {
          dual_exp2_shifted(p, ph);
          #pragma unroll
          for (int i = 0; i < 8; i++) {
            const uint32_t* f = &ph[i >> 1][i & 1];
            float a = (bf_lo(f[0]) + bf_hi(f[0])) + (bf_lo(f[2]) + bf_hi(f[2])) + (bf_lo(f[4]) + bf_hi(f[4])) + (bf_lo(f[6]) + bf_hi(f[6]));
            a += __shfl_xor_sync(~0u, a, 1);
            rsum[i >> 2][2 * (i & 1) + ((i >> 1) & 1)] = a + __shfl_xor_sync(~0u, a, 2);
          }
        }
        if (h == 0) project(kf[1], dlo(SB0 + OFF_WPHIK1, 16));
        normalize(ph, rsum);
        #pragma unroll
        for (int i = 0; i < 8; i++) {
          const uint32_t* f = &ph[i >> 1][4 * (i & 1)];
          stsm4(((stg + sa) ^ ((i & 3) << 5)) + (i >> 2) * 8192, f[0], f[1], f[2], f[3]);
        }
        KK(5 + 6 * h);
        fence_async_smem();
        KK(6 + 6 * h);
        if (wg != h) { KK(7 + 6 * h); }
        if (wg == h) {
          float kv[20];
          #pragma unroll
          for (int w = 0; w < 2; w++) {
            const uint32_t da = dlo(SB0 + OFF_X, 16) + (h ^ w ^ 1) * 1536, db = dlo(SB0 + OFF_X + 16384, OFF_ONES - OFF_X - 16384) - (h ^ w ^ 1) * (1536 * 65535);
            if (w) bar_sync(NB_ST, 256); else bar_sync(NB_L0 + h, 128);
            wg_fence();
            #pragma unroll
            for (int k = 0; k < 8; k++) {
              if (k == 0 && w == 0) wgmma_sz_n40<1, 1, H128, H64>(kv, da, db);
              else wgmma_sa_n40<1, 1, H128, H64>(kv, da + k * 128, db - k * (64 * 65535));
            }
            wg_commit();
          }
          float4* dst = &G->kvacc[(ha + 2 * h) * KVP + t];
          wg_wait<0>();
          fence_regs(kv);
          KK(7 + 6 * h);
          if (h == 0) bar_arrive(NB_DN, 256); else if (t < 2) { mbar_arrive_at(sb + B_EMPTY5 + 40, t, 2); if (t == 0) mbar_arrive(sb + B_KD); }
          kv[17] = kv[18];
          #pragma unroll
          for (int i = 0; i < 6; i++) red_add_f32x4(dst + 128 * i, kv[3*i], kv[3*i+1], kv[3*i+2], 1.f);
          TSW(29 + h);
        } else bar_arrive(NB_ST, 256);
        wg_wait<0>();
        KK(8 + 6 * h);
        fence_regs(p[0]); fence_regs(p[1]);
      }
      #pragma unroll
      for (int i = 0; i < 32; i++) asm volatile("mov.b32 %0, 0;" : "=r"(xr[i]));
    }
    float p[2][16];
    #pragma unroll
    for (int i = 0; i < 32; i++) asm volatile("mov.b32 %0, 0;" : "=f"(p[i >> 4][i & 15]));
    auto project_r = [&](int w) {
      wg_fence();
      #pragma unroll
      for (int h = 0; h < 2; h++) {
        wgmma_rs_n32<1, H64>(p[h], xr[8*h], xr[8*h+1], xr[8*h+2], xr[8*h+3], dlo(SB0 + OFF_WPHIQ, 16) + 128 * w, 0);
        wgmma_ra_n32<1, H64>(p[h], xr[8*h+4], xr[8*h+5], xr[8*h+6], xr[8*h+7], dlo(SB0 + OFF_WPHIQ, 16) + 128 * w + 64);
      }
      wg_commit();
    };
    auto capture = [&](const int i) {
      if (!i || CAPL != 2) mbar_wait(sb + (i ? B_R1 : B_R), 0);
      #pragma unroll
      for (int k = 0; k < 4; k++) ldsm4(((sb + (1 + rank) * R5 + wg * 8192 + sa) ^ (k << 5)) + i * 2 * R5, xr[16*i+4*k], xr[16*i+4*k+1], xr[16*i+4*k+2], xr[16*i+4*k+3]);
      const uint32_t one = (((xr[16*i] | xr[16*i+4]) | (xr[16*i+8] | xr[16*i+12])) & P.zero) + 1;
      if (lane == 0) mbar_arrive_at(sb + (i ? B_RX : B_RC + 8 * wg), i ? wg : rank, one);
    };
    {
      const uint4* src = reinterpret_cast<const uint4*>(&G->kvacc[(4 * j + wg) * KVP + t]);
      uint4 v[12];
      #pragma unroll
      for (int i = 0; i < 12; i++) v[i] = i < 6 || isq ? ld128_rlx(src + 128 * i) : make_uint4(0, 0, 0, 0x41000000u);
      if (isq) {
        project_r(2);
        wg_wait<0>();
        #pragma unroll
        for (int i = 0; i < 16; i++) xr[i] = xr[16 + i];
      } else {
        capture(0);
        if (CAPL == 0) capture(1);
      }
      #pragma unroll 1
      for (uint32_t it = 0; it < POLL_LIMIT; it++) {
        uint32_t bad = 0;
        #pragma unroll
        for (int i = 0; i < 12; i++) bad |= v[i].w ^ 0x41000000u;
        if (!__any_sync(~0u, bad != 0)) break;
        #pragma unroll
        for (int i = 0; i < 12; i++) if (i < 6 || isq) v[i] = ld128_rlx(src + 128 * i);
      }
      mbar_wait(sb + B_KD, 0);
      #pragma unroll
      for (int e = 0; e < 2; e++) {
        if (e == 0 || isq) {
          float f[18];
          #pragma unroll
          for (int i = 0; i < 6; i++) { f[3*i] = __uint_as_float(v[6*e+i].x); f[3*i+1] = __uint_as_float(v[6*e+i].y); f[3*i+2] = __uint_as_float(v[6*e+i].z); }
          const uint32_t ka = sb + OFF_KVZ + (wg + e) * 5120 + wp * 1280 + lane * 16;
          stsm4(ka, pack_bf16(f[0], f[1]), pack_bf16(f[2], f[3]), pack_bf16(f[4], f[5]), pack_bf16(f[6], f[7]));
          stsm4(ka + 512, pack_bf16(f[8], f[9]), pack_bf16(f[10], f[11]), pack_bf16(f[12], f[13]), pack_bf16(f[14], f[15]));
          stsm2(ka + 1024, pack_bf16(f[16], 1.f), pack_bf16(f[17], 1.f));
        }
      }
    }
    fence_async_smem();
    if (wg == 1) bar_arrive(NB_DN, 256);
    if (CAPL == 1 && !isq) capture(1);
    if (isq) mbar_wait(sb + B_OS, 0);
    TSW(wg == 0 ? 5 : wg == 1 ? 25 : 6);
    #pragma unroll 1
    for (int e = wg; e < wg + 1 + (wg >> 1); e++) {
      const int half = e >> 1, hh = e & 1, turn = e;
      const uint32_t ao = (1 + rank) * R5 + hh * 8192;
      const uint32_t ra = sb + OFF_RSQ + (16 * wp + g) * 4 + (e == 1 ? 256 : 0), rb = ra + 256 * half;
      const float cc[2][2] = {{ldsf(ra) * LOG2E, ldsf(ra + 32) * LOG2E}, {ldsf(rb) * LOG2E, ldsf(rb + 32) * LOG2E}};
      uint32_t ph[4][8];
      #pragma unroll
      for (int i = 0; i < 32; i++) asm volatile("mov.b32 %0, 0;" : "=r"(ph[i >> 3][i & 7]));
      uint32_t shifted = 0;
      asm volatile("" : "+r"(shifted));
      #pragma unroll 1
      for (;;) {
        if (!(XP & 16) && shifted) dual_exp2_shifted(p, ph);
        uint32_t first = (shifted ^ 1) & !isq;
        asm volatile("" : "+r"(first));
        if (first) {
          if (wg == 0) { TSW(7); }
          bar_sync(NB_Q0 + wg, 256);
          const uint32_t da = dlo(SB0, 16) + (ao >> 4), db = dlo(SB0 + OFF_WPHIQ, 16);
          wg_fence();
          #pragma unroll
          for (int h = 0; h < 2; h++) {
            wgmma_ss_n32<0, 1, H128, H64>(p[h], da + 4 * h, db + 128 * h, 0);
            wgmma_sa_n32<0, 1, H128, H64>(p[h], da + 4 * h + 2, db + 128 * h + 64);
          }
          wg_commit();
          if (CAPL == 2) capture(1);
          wg_wait<0>();
        }
        fence_regs(p[0]); fence_regs(p[1]);
        uint32_t again = shifted;
        asm volatile("" : "+r"(again));
        if (again) break;
        float s2[4] = {0.f, 0.f, 0.f, 0.f};
        #pragma unroll
        for (int i = 0; i < 32; i++) { float& x = p[i >> 4][i & 15]; x *= cc[i >> 4][(i >> 1) & 1]; s2[i & 3] = fmaf(x, x, s2[i & 3]); }
        if (!__any_sync(~0u, !((s2[0] < ARG_LIM2) & (s2[1] < ARG_LIM2) & (s2[2] < ARG_LIM2) & (s2[3] < ARG_LIM2)))) break;
        shifted = 1;
      }
      if (e == 1 || e == 2) bar_sync(NB_TOK + e - 1, 256);
      TK(64 + 4 * turn);
      float ac[4][20];
      auto numer = [&](int h) {
        const uint32_t (*f)[8] = &ph[2 * h];
        const uint32_t db = dlo(SB0 + OFF_KVZ, 128) + (half ? e : h) * 320;
        wg_fence();
        #pragma unroll
        for (int i = 0; i < 2; i++) {
          wgmma_rz_n40<1, dhi(256, 0)>(ac[2*h+i], f[i][0], f[i][1], f[i][2], f[i][3], db + i * 160);
          wgmma_ra_n40<1, dhi(256, 0)>(ac[2*h+i], f[i][4], f[i][5], f[i][6], f[i][7], db + (i * 160 + 80));
        }
        wg_commit();
      };
      const uint32_t oa = (16 * wp + g) * 128 + (((lane & 3) ^ g) << 4);
      auto finish = [&](int h) {
        const float* ap = ac[2 * h]; const float* am = ac[2 * h + 1];
        const float ip0 = rcp(ap[17]), im0 = rcp(am[17]), ip1 = rcp(ap[19]), im1 = rcp(am[19]);
        const float d0 = rcp(fmaf(ap[16], ip0, fmaf(am[16], im0, 1e-6f))), d1 = rcp(fmaf(ap[18], ip1, fmaf(am[18], im1, 1e-6f)));
        const float a0 = ip0 * d0, b0 = im0 * d0, a1 = ip1 * d1, b1 = im1 * d1;
        #pragma unroll
        for (int r = 0; r < 2; r++) {
          const float a = r ? a1 : a0, b = r ? b1 : b0;
          uint32_t w[4];
          #pragma unroll
          for (int k = 0; k < 4; k++) w[k] = pack_bf16(fmaf(ap[4*k+2*r], a, am[4*k+2*r] * b), fmaf(ap[4*k+2*r+1], a, am[4*k+2*r+1] * b));
          const uint32_t off = (oa ^ ((half ? rank : h) << 6)) + r * 1024;
          st128_rlx(reinterpret_cast<uint8_t*>(G->o + (m128 * 16 + (half ? 2 * (j & 6) + 2 * hh + 1 : 2 * j)) * 8192 + (half ? h : hh) * 4096) + off, w[0], w[1], w[2], w[3]);
          if (!half) sts128(sb + ao + off, w[0], w[1], w[2], w[3]);
        }
      };
      if (!shifted) dual_exp2<true>(p[0], ph[0], ph[1]);
      numer(0);
      if (!shifted) dual_exp2<true>(p[1], ph[2], ph[3]);
      if (turn < 2) bar_arrive(NB_TOK + turn, 256);
      if (wg == 0) bar_sync(NB_DN, 256);
      numer(1);
      wg_wait<1>();
      TK(65 + 4 * turn);
      fence_regs(ac[0]); fence_regs(ac[1]);
      finish(0);
      wg_wait<0>();
      fence_regs(ac[2]); fence_regs(ac[3]);
      #pragma unroll
      for (int i = 0; i < 32; i++) asm volatile("mov.b32 %0, 0;" : "=f"(p[i >> 4][i & 15]));
      if (e == 2) project_r(3);
      finish(1);
      TK(66 + 4 * turn);
      if (!half) fence_async_smem();
      __syncwarp();
      if (lane == 0) mbar_arrive(sb + B_UO + 8 * e);
      wg_wait<0>();
      TK(67 + 4 * turn);
    }
    if (isq) cluster_arrive();
  }

  {
  int lane;
  asm volatile("mov.u32 %0, %%laneid;" : "=r"(lane));
  const int g = lane >> 2, q = lane & 3;
  if (wg < 2) {
    float h[64];
    {
      if (wg == 0) { TK(83); }
      #pragma unroll
      for (int i = 0; i < 32; i++) { h[2*i] = bf_lo(xr[i]); h[2*i+1] = bf_hi(xr[i]); }
      fence_regs(h);
      TK(80 + wg);
      const uint32_t emptyb = mapa(sb + B_EMPTY5, t & 1);
      uint32_t s = 1 + rank, ps = 0;
      mbar_wait2(sb + B_FULL5 + 8 * s, 1, sb + B_UO + 8 * wg, 0);
      if (wg == 0) { TSW(14); }
      #pragma unroll
      for (int i = 0; i < 16; i++) {
        if (wg == 1 && (i & 12) == TKW) { TK(84 + (i & 3)); }
        if (!KT && wg == 0) { TK(32 + i); }
        const uint32_t da = dlo(SB0, 16) + s * 2048 + wg * 512, db = dlo(SB0 + 16384, 8192) + s * 2048;
        wg_fence();
        #pragma unroll
        for (int k = 0; k < 4; k++) wgmma_sa_n128<0, 1, H128, H128>(h, da + k * 2, db + k * 128);
        wg_commit();
        const uint32_t ns = i ? (i + 2) % 6 : 2 - rank;
        const uint32_t b0 = sb + B_FULL5 + 8 * ns, p0 = (1 + (i + 2) / 6) & 1, b1 = sb + B_FULLA + 16 * ns + 8 * wg, p1 = ((i + 1) / 6) & 1;
        const bool here = i == 15 || mbar_test2(b0, p0, b1, p1);
        wg_wait<1>();
        if (!(((2 * REL + 1) >> i) & 1) && i < 14 && t < 2) mbar_arrive_remote(emptyb + 8 * ps, 1);
        if ((REL >> i) & 1) { wg_wait<0>(); if (t < 2) mbar_arrive_remote(emptyb + 8 * s, 1); }
        if (!here) mbar_wait2(b0, p0, b1, p1);
        ps = s; s = ns;
      }
    }
    cluster_arrive();
    float2 wr[16];
    #pragma unroll
    for (int i = 0; i < 16; i++) wr[i] = lds64f(sb + OFF_WR + 32 * i + 8 * q);
    const int r0 = 64 * wg + 16 * wp + g;
    float sum0, sum1, dot0, dot1, sq0, sq1;
    uint32_t redo = 0;
    asm volatile("" : "+r"(redo));
    #pragma unroll 1
    for (;;) {
    if (!(XP & 32) && redo) {
      wg_wait<0>();
      const int r = r0;
      #pragma unroll 1
      for (int n = 0; n < 16; n++) {
        const uint32_t* xp = reinterpret_cast<const uint32_t*>(P.x + (size_t)(128 * m128 + r) * DM + 128 * j + 8 * n) + q;
        const uint32_t x0 = xp[0], x1 = xp[4 * DM];
        float d0 = bf_lo(x0), d1 = bf_hi(x0), d2 = bf_lo(x1), d3 = bf_hi(x1);
        #pragma unroll 1
        for (int ks = 0; ks < 64; ks++) {
          const int kb = ks >> 2, kk = 16 * (ks & 3);
          const bf16* op = G->o + (m128 * 16 + kb) * 8192 + r * 64 + 2 * q;
          const int o0 = ((kk >> 3) ^ g) << 3;
          const uint16_t* w = reinterpret_cast<const uint16_t*>(P.wo_p) + (size_t)(((kb & 1) ? 256 * (kb >> 2) + 32 * (kb & 2) + 32 + 4 * (kk & 32) : 64 * kb + 2 * (kk & 32)) + ((kk & 16) >> 2) + 8 * q) * DM + 128 * j + 8 * n + g;
          const uint32_t b0 = w[0] | (w[DM] << 16), b1 = w[2 * DM] | (w[3 * DM] << 16);
          uint32_t a0, a1, a2, a3, it = 0;
          do { a0 = ld32_rlx(op + o0); a1 = ld32_rlx(op + 512 + o0); a2 = ld32_rlx(op + (o0 ^ 8)); a3 = ld32_rlx(op + 512 + (o0 ^ 8)); }
          while (max(max(a0, a1), max(a2, a3)) == ~0u && ++it < POLL_LIMIT);
          __syncwarp();
          mma16816(d0, d1, d2, d3, a0, a1, a2, a3, b0, b1);
        }
        #pragma unroll
        for (int i = 0; i < 60; i++) h[i] = h[i + 4];
        h[60] = d0; h[61] = d1; h[62] = d2; h[63] = d3;
      }
    }
    wg_wait<0>();
    fence_regs(h);
    if (wg == 0) { TSW(16); }
    sum0 = 0.f, sum1 = 0.f, dot0 = 0.f, dot1 = 0.f, sq0 = 0.f, sq1 = 0.f;
    #pragma unroll
    for (int i = 0; i < 16; i++) {
      sum0 += h[4*i] + h[4*i+1]; sum1 += h[4*i+2] + h[4*i+3];
      sq0 = fmaf(h[4*i], h[4*i], fmaf(h[4*i+1], h[4*i+1], sq0)); sq1 = fmaf(h[4*i+2], h[4*i+2], fmaf(h[4*i+3], h[4*i+3], sq1));
      dot0 = fmaf(h[4*i], wr[i].x, fmaf(h[4*i+1], wr[i].y, dot0)); dot1 = fmaf(h[4*i+2], wr[i].x, fmaf(h[4*i+3], wr[i].y, dot1));
    }
    if (!__any_sync(~0u, !redo & (h[0] != h[0] | h[2] != h[2]))) break;
    redo = 1;
    }
    float4* const rs = &G->rstat[128 * m128 + r0];
    {
      const bool up = q & 2;
      float a = up ? sum1 : sum0, b = up ? sq1 : sq0, d = up ? dot1 : dot0;
      a += __shfl_xor_sync(~0u, up ? sum0 : sum1, 2); b += __shfl_xor_sync(~0u, up ? sq0 : sq1, 2); d += __shfl_xor_sync(~0u, up ? dot0 : dot1, 2);
      a += __shfl_xor_sync(~0u, a, 1); b += __shfl_xor_sync(~0u, b, 1); d += __shfl_xor_sync(~0u, d, 1);
      if ((q & 1) == 0) red_add_f32x4(rs + 4 * q, a, b, d, 1.f);
    }
    if (TRKL == 0) bar_arrive(NB_G2E, 384);
    if (wg == 0) { TSW(24); }
    bar_sync(NB_WG01, 256);
    uint32_t wa[8][4][4];
    const uint32_t wb = sb + 16384 * (((uint32_t)FF_SLOT >> (4 * warp)) & 15) + ((lane & 7) + ((lane >> 4) << 3)) * 64 + ((((lane >> 3) & 1) ^ ((lane >> 1) & 3)) << 4);
    auto getw = [&](int ks) {
      #pragma unroll
      for (int m = 0; m < 4; m++) ldsm4t((wb ^ ((m & 1) << 5)) + (m >> 1) * 8192 + ks * 1024, wa[ks][m][0], wa[ks][m][1], wa[ks][m][2], wa[ks][m][3]);
    };
    if (GPRE && f < NFFN_L) mbar_wait(sb + B_F + 8 * warp, 0);
    if (warp == 7) { TK(60); }
    #pragma unroll
    for (int ks = 0; ks < GPRE; ks++) getw(ks);
    float rstd[2], bm[2];
    uint32_t best;
    {
      const float2 swa = lds64f(sb + OFF_SUMWR), swb = lds64f(sb + OFF_SUMWR + 8);
      const float sw = (swa.x + swa.y) + (swb.x + swb.y);
      uint4 a[2]; uint32_t it = 0, key[2];
      do { a[0] = ld128_rlx(rs); a[1] = ld128_rlx(rs + 8); } while (__any_sync(~0u, (a[0].w & a[1].w) != 0x41000000u) && ++it < POLL_LIMIT);
      #pragma unroll
      for (int i = 0; i < 2; i++) {
        const float mean = __uint_as_float(a[i].x) * (1.f / DM);
        rstd[i] = rsqrtf(fmaxf(__uint_as_float(a[i].y) * (1.f / DM) - mean * mean, 0.f) + 1e-5f);
        bm[i] = -mean * rstd[i];
        const uint32_t rr = __float_as_uint(fmaf(__uint_as_float(a[i].z), rstd[i], sw * bm[i]));
        key[i] = ((rr ^ ((uint32_t)((int32_t)rr >> 31) | 0x80000000u)) & ~2047u) | (2047 - 128 * m128 - r0 - 8 * i);
      }
      asm volatile("redux.sync.max.u32 %0, %1, 0xffffffff;" : "=r"(best) : "r"(max(key[0], key[1])));
    }
    if (TRKL == 2) bar_arrive(NB_G2E, 384);
    if (TRKL == 3 && wg == 0) bar_arrive(NB_G2E, 256);
    if (wg == 0) { TSW(17); }
    const int slot = m128 * 8 + warp, win = ~best & 15;
    if (lane < KR) st32_rlx(&G->key[(KR * j + lane) * 128 + slot], best);
    if ((win & 7) == g) {
      const bool up = win & 8;
      const float ra = up ? rstd[1] : rstd[0], rb = up ? bm[1] : bm[0];
      uint32_t x[16];
      #pragma unroll
      for (int i = 0; i < 16; i++) x[i] = pack_bf16(fmaf(up ? h[4*i+2] : h[4*i], ra, rb), fmaf(up ? h[4*i+3] : h[4*i+1], ra, rb));
      #pragma unroll
      for (int i = 0; i < 4; i++) st128_rlx(&G->cand[slot * 512 + 64 * j + 16 * i + 4 * q], x[4*i], x[4*i+1], x[4*i+2], x[4*i+3]);
    }
    __syncwarp();
    if (TRKL == 1) bar_arrive(NB_G2E, 384);
    if (wg == 0) { TSW(27); }
    {
      const float a0 = 1.f + rstd[0], b0 = bm[0], a1 = 1.f + rstd[1], b1 = bm[1];
      #pragma unroll
      for (int k = 0; k < 8; k++)
        stsm4(((sb + OFF_OUT + wg * 8192 + sa) ^ ((k & 3) << 5)) + (k >> 2) * 16384,
              pack_bf16(fmaf(h[8*k], a0, b0), fmaf(h[8*k+1], a0, b0)),     pack_bf16(fmaf(h[8*k+2], a1, b1), fmaf(h[8*k+3], a1, b1)),
              pack_bf16(fmaf(h[8*k+4], a0, b0), fmaf(h[8*k+5], a0, b0)),   pack_bf16(fmaf(h[8*k+6], a1, b1), fmaf(h[8*k+7], a1, b1)));
      fence_async_smem();
      __syncwarp();
      if (lane == 0) mbar_arrive(sb + B_OUT + 8 * wg);
    }
    if (wg == 0) { TSW(28); }
    {
      if (!GPRE && f < NFFN_L) mbar_wait(sb + B_F + 8 * warp, 0);
      #pragma unroll
      for (int ks = GPRE; ks < GRES; ks++) getw(ks);
      if (wg == 0) { TSW(15); }
      bar_sync(NB_XS, 384);
      uint4 xs[4];
      #pragma unroll
      for (int i = 0; i < 4; i++) xs[i] = lds128(sb + OFF_XSEL + 256 * warp + 64 * i + 16 * q);
      float d[4][4];
      #pragma unroll
      for (int ks = 0; ks < 8; ks++) {
        if (ks >= 1 && GRES + ks - 1 < 8) getw(GRES + ks - 1);
        #pragma unroll
        for (int m = 0; m < 4; m++) {
          if (ks == 0) { d[m][0] = 0.f; d[m][1] = 0.f; d[m][2] = 0.f; d[m][3] = 0.f; }
          mma16816(d[m][0], d[m][1], d[m][2], d[m][3], wa[ks][m][0], wa[ks][m][1], wa[ks][m][2], wa[ks][m][3],
                   (ks & 1) ? xs[ks >> 1].z : xs[ks >> 1].x, (ks & 1) ? xs[ks >> 1].w : xs[ks >> 1].y);
        }
      }
      if (q == 0) {
        #pragma unroll
        for (int m = 0; m < 8; m++) stsf(sb + OFF_GU + (8 * m + g) * 48 + 4 * warp, d[m >> 1][2 * (m & 1)]);
      }
      bar_arrive(NB_ACT, 384);
    }
    {
      const uint32_t ky = __float_as_uint(ldsf(sb + OFF_KEY));
      const int row = 2047 - (ky & 2047) - 128 * m128;
      if ((uint32_t)row < 128u) {
        const int l = tid >> 3, vi = (j & 1) + ((lane >> 2) & 1), e = 3 * vi + q - 4 * (j & 1);
        const float kr = __uint_as_float((ky & ~2047u) ^ ((ky >> 31) ? 0x80000000u : 0xfffff800u));
        const int col = 32 * (l & 3) + 16 * (e & 1) + 4 * (e & 2) + (l >> 2);
        const float sg = rcp(1.f + ex2(-LOG2E * kr));
        const uint32_t base = __float_as_uint(ldsf(sb + OFF_OUT + (col >> 6) * 16384 + row * 128 + ((((col >> 3) ^ row) & 7) << 4) + 2 * (col & 6)));
        const float4* yp = &G->yacc[(q * 3 + vi) * 128 + 32 * (j >> 1) + l];
        uint32_t it = 0;
        uint4 v;
        mbar_wait(sb + B_SD, 0);
        do { v = ld128_rlx(yp); } while (__any_sync(~0u, __uint_as_float(v.w) != (float)(NFFN / 4)) && ++it < POLL_LIMIT);
        float y0 = __uint_as_float(v.x), y1 = __uint_as_float(v.y), y2 = __uint_as_float(v.z);
        #pragma unroll
        for (int o = 1; o < 4; o <<= 1) { y0 += __shfl_xor_sync(~0u, y0, o); y1 += __shfl_xor_sync(~0u, y1, o); y2 += __shfl_xor_sync(~0u, y2, o); }
        if (q < 3 && (uint32_t)e < 4u)
          P.out_p[(size_t)(128 * m128 + row) * DM + 128 * j + col] = __float2bfloat16(fmaf(q == 0 ? y0 : q == 1 ? y1 : y2, sg, (col & 1) ? bf_hi(base) : bf_lo(base)));
      }
      if (c == 0 && tid == 0) st32_rlx(&G->epoch, __float_as_uint(ldsf(sb + OFF_EP)));
      if (warp == 0) { TSW(22); }
      if (wg == 0) { TDUMP(); }
    }
  }
  if (wg == 2) {
    uint32_t wf[16][2][4];
    {
      const uint32_t wb = sb + OFF_S + 16384 * (wp & 1) + ((lane & 7) + ((lane >> 4) << 3)) * 128 + ((((lane >> 3) & 1) ^ (lane & 7)) << 4);
      if (f < NFFN_L) mbar_wait(sb + B_WD + 8 * wp, 0);
      if (wp == 0) { TK(61); }
      #pragma unroll
      for (int i = 0; i < 32; i++) ldsm4t((wb ^ (((i >> 1) & 3) << 5)) + (i >> 3) * 4096 + (i & 1) * 2048, wf[i >> 1][i & 1][0], wf[i >> 1][i & 1][1], wf[i >> 1][i & 1][2], wf[i >> 1][i & 1][3]);
      fence_async_smem();
      __syncwarp();
      if (lane == 0) mbar_arrive(sb + B_WC + 8 * wp);
      if (wp == 0) { TK(62); }
    }
    bar_sync(NB_G2E, TRKL == 3 ? 256 : 384);
    {
      uint32_t cur = 0;
      uint4 v;
      #pragma unroll 1
      for (uint32_t it = 0; it < POLL_LIMIT; it++) {
        const uint4 kx = ld128_rlx(&G->key[(KSEL & (8 * KR - 1)) * 128 + 4 * lane]);
        v = ld128_rlx(&G->cand[((~cur >> 4) & 127) * 512 + 4 * t]);
        uint32_t best;
        asm volatile("redux.sync.max.u32 %0, %1, 0xffffffff;" : "=r"(best) : "r"(max(max(kx.x, kx.y), max(kx.z, kx.w))));
        if (!__any_sync(~0u, min(min(kx.x, kx.y), min(kx.z, kx.w)) == 0 || v.w == ~0u) && best == cur) break;
        cur = best;
      }
      sts128(sb + OFF_XSEL + 16 * t, v.x, v.y, v.z, v.w);
      sts32(sb + OFF_KEY, cur);
      bar_arrive(NB_XS, 384);
      TSW(18);
      bar_sync(NB_ACT, 384);
    }
    float gu[2];
    #pragma unroll
    for (int i = 0; i < 2; i++) {
      const uint4 v0 = lds128(sb + OFF_GU + (32 * i + lane) * 48), v1 = lds128(sb + OFF_GU + (32 * i + lane) * 48 + 16);
      gu[i] = ((__uint_as_float(v0.x) + __uint_as_float(v0.y)) + (__uint_as_float(v0.z) + __uint_as_float(v0.w))) +
              ((__uint_as_float(v1.x) + __uint_as_float(v1.y)) + (__uint_as_float(v1.z) + __uint_as_float(v1.w)));
    }
    const float act = gu[0] * gu[1] * rcp(1.f + ex2(-LOG2E * gu[0]));
    const uint32_t ap = pack_bf16(act, __shfl_down_sync(~0u, act, 1));
    uint32_t bf[4];
    #pragma unroll
    for (int i = 0; i < 4; i++) bf[i] = __shfl_sync(~0u, ap, 2 * q + 8 * i);
    TSW(20);
    float d[16][4];
    #pragma unroll
    for (int k = 0; k < 2; k++)
      #pragma unroll
      for (int i = 0; i < 16; i++) {
        if (k == 0) { d[i][0] = 0.f; d[i][1] = 0.f; d[i][2] = 0.f; d[i][3] = 0.f; }
        mma16816(d[i][0], d[i][1], d[i][2], d[i][3], wf[i][k][0], wf[i][k][1], wf[i][k][2], wf[i][k][3], bf[2*k], bf[2*k+1]);
      }
    float y[9];
    #pragma unroll
    for (int e = 0; e < 8; e++) {
      const int n = 2 * (e & 4) + (e & 1);
      const float lo = (q & 1) ? d[n + 2][e & 2] : d[n][e & 2], hi = (q & 1) ? d[n + 6][e & 2] : d[n + 4][e & 2];
      y[e] = (q & 2) ? hi : lo;
    }
    y[8] = 0.f;
    if (f < NFFN) {
      #pragma unroll
      for (int i = 0; i < 3; i++) red_add_f32x4(&G->yacc[((f & 3) * 3 + i) * 128 + t], y[3*i], y[3*i+1], y[3*i+2], 1.f);
    }
    TSW(21);
  }
  }
  cluster_wait();
}

typedef CUresult (*EncodeFn)(CUtensorMap*, CUtensorMapDataType, cuuint32_t, void*, const cuuint64_t*, const cuuint64_t*,
                             const cuuint32_t*, const cuuint32_t*, CUtensorMapInterleave, CUtensorMapSwizzle,
                             CUtensorMapL2promotion, CUtensorMapFloatOOBfill);

void make_map(EncodeFn enc, CUtensorMap* m, const void* p, int n, const cuuint64_t* dims, const cuuint64_t* str, const cuuint32_t* box,
              CUtensorMapSwizzle sw, CUtensorMapL2promotion promo) {
  cuuint32_t es[5] = {1, 1, 1, 1, 1};
  enc(m, CU_TENSOR_MAP_DATA_TYPE_BFLOAT16, n, const_cast<void*>(p), dims, str, box, es, CU_TENSOR_MAP_INTERLEAVE_NONE, sw, promo,
      CU_TENSOR_MAP_FLOAT_OOB_FILL_NONE);
}
void map2(EncodeFn enc, CUtensorMap* m, const void* p, uint64_t cols, uint64_t rows, uint32_t bc, uint32_t br, CUtensorMapSwizzle sw,
          CUtensorMapL2promotion promo) {
  const cuuint64_t dims[2] = {cols, rows}, str[1] = {cols * 2};
  const cuuint32_t box[2] = {bc, br};
  make_map(enc, m, p, 2, dims, str, box, sw, promo);
}
void map3(EncodeFn enc, CUtensorMap* m, const void* p, uint64_t cols, uint64_t rows, uint32_t br, uint32_t nb) {
  const cuuint64_t dims[3] = {64, rows, cols / 64}, str[2] = {cols * 2, 128};
  const cuuint32_t box[3] = {64, br, nb};
  make_map(enc, m, p, 3, dims, str, box, CU_TENSOR_MAP_SWIZZLE_128B, CU_TENSOR_MAP_L2_PROMOTION_L2_128B);
}

}

extern "C" void kernel_launch(void* const* d_in, const int* in_sizes, int n_in, void* d_out, int out_size) {
  (void)in_sizes; (void)n_in; (void)out_size;
  static EncodeFn enc = nullptr;
  static void* o_ptr = nullptr;
  if (!enc) {
    void* f = nullptr; cudaDriverEntryPointQueryResult qr;
    cudaGetDriverEntryPoint("cuTensorMapEncodeTiled", &f, cudaEnableDefault, &qr);
    enc = (EncodeFn)f;
    cudaGetSymbolAddress(&o_ptr, g_scr);
    cudaFuncSetAttribute(fused_kernel, cudaFuncAttributeMaxDynamicSharedMemorySize, SMEM_BYTES);
  }
  const bf16* x = (const bf16*)d_in[0];
  const bf16* wqkv = (const bf16*)d_in[1];
  const bf16* wphi = (const bf16*)d_in[2];
  const bf16* wo = (const bf16*)d_in[3];
  const bf16* wr = (const bf16*)d_in[5];
  const bf16* wgate = (const bf16*)d_in[6];
  const bf16* wup = (const bf16*)d_in[7];
  const bf16* wdown = (const bf16*)d_in[8];
  Params P;
  const CUtensorMapSwizzle S128 = CU_TENSOR_MAP_SWIZZLE_128B, S64 = CU_TENSOR_MAP_SWIZZLE_64B;
  const CUtensorMapL2promotion L128 = CU_TENSOR_MAP_L2_PROMOTION_L2_128B, L256 = CU_TENSOR_MAP_L2_PROMOTION_L2_256B,
                               L64 = CU_TENSOR_MAP_L2_PROMOTION_L2_64B;
  map2(enc, &P.x128, x, DM, SEQ, 64, 128, S128, L256);
  map2(enc, &P.x64, x, DM, SEQ, 64, 64, S128, L128);
  {
    const cuuint64_t dims[4] = {64, DM, 16, 3}, str[3] = {6 * DM, 128, 2 * DM};
    const cuuint32_t box[4] = {64, 64, 1, 2};
    make_map(enc, &P.wkv, wqkv, 4, dims, str, box, S128, L128);
  }
  map3(enc, &P.wq, wqkv, 3 * DM, DM, 64, 2);
  for (int i = 0; i < 2; i++) {
    const cuuint64_t dims[5] = {DM, (cuuint64_t)(DM - 94 - 64 * i), 4, 4, 2}, str[4] = {2 * DM, 16 * DM, 4 * DM, (cuuint64_t)(128 * DM) << i};
    const cuuint32_t box[5] = {64, 2, 4, 4, 2};
    make_map(enc, &P.wo[i], wo, 5, dims, str, box, S128, L128);
  }
  map3(enc, &P.wd, wdown, DM, FF, 32, 4);
  map2(enc, &P.wg, wgate, FF, DM, 32, 128, S64, L64);
  map2(enc, &P.wu, wup, FF, DM, 32, 128, S64, L64);
  map2(enc, &P.tg, wgate, FF, DM, 8, 16, CU_TENSOR_MAP_SWIZZLE_NONE, L128);
  map2(enc, &P.tu, wup, FF, DM, 8, 16, CU_TENSOR_MAP_SWIZZLE_NONE, L128);
  map2(enc, &P.td, wdown, 128, FF * 8, 8, 16, CU_TENSOR_MAP_SWIZZLE_NONE, L256);
  map2(enc, &P.xs, x, DM, SEQ, 128, 16, CU_TENSOR_MAP_SWIZZLE_NONE, L256);
  map2(enc, &P.ws, wqkv, 3 * DM, DM, 16, 128, CU_TENSOR_MAP_SWIZZLE_NONE, L128);
  map2(enc, &P.qs, wqkv, 3 * DM, DM, 32, 128, CU_TENSOR_MAP_SWIZZLE_NONE, L64);
  map2(enc, &P.out, d_out, DM, SEQ, 64, 16, S128, L128);
  map2(enc, &P.phi, wphi, 32, 1024, 32, 32, S64, L64);
  P.x = x; P.wqkv = wqkv; P.wo_p = wo; P.wd_p = wdown; P.wg_p = wgate; P.wu_p = wup; P.wr = wr; P.out_p = (bf16*)d_out; P.g = (Scratch*)o_ptr; P.zero = 0;

  cudaLaunchConfig_t cfg = {};
  cfg.gridDim = dim3(128); cfg.blockDim = dim3(512); cfg.dynamicSmemBytes = SMEM_BYTES; cfg.stream = cudaStreamPerThread;
  cudaLaunchAttribute at[1];
  at[0].id = cudaLaunchAttributeClusterDimension; at[0].val.clusterDim.x = 2; at[0].val.clusterDim.y = 1; at[0].val.clusterDim.z = 1;
  cfg.attrs = at; cfg.numAttrs = 1;
  cudaLaunchKernelEx(&cfg, fused_kernel, P);
}
```

```cpp
#include <cuda_runtime.h>
#include <cuda.h>
#include <cuda_bf16.h>
#include <stdint.h>

namespace {

typedef __nv_bfloat16 bf16;

__device__ __forceinline__ uint32_t smem_u32(const void* p){ return (uint32_t)__cvta_generic_to_shared(p); }
__device__ __forceinline__ void mbar_init(uint32_t bar, uint32_t cnt){ asm volatile("mbarrier.init.shared::cta.b64 [%0], %1;"::"r"(bar),"r"(cnt):"memory"); }
__device__ __forceinline__ void mbar_expect_tx(uint32_t bar, uint32_t bytes){ asm volatile("mbarrier.arrive.expect_tx.shared::cta.b64 _, [%0], %1;"::"r"(bar),"r"(bytes):"memory"); }
__device__ __forceinline__ void mbar_arrive(uint32_t bar){ asm volatile("mbarrier.arrive.shared::cta.b64 _, [%0];"::"r"(bar):"memory"); }
__device__ __forceinline__ uint32_t mapa(uint32_t addr, uint32_t cta){ uint32_t r; asm volatile("mapa.shared::cluster.u32 %0, %1, %2;":"=r"(r):"r"(addr),"r"(cta)); return r; }
__device__ __forceinline__ void mbar_arrive_at(uint32_t bar, uint32_t cta, uint32_t cnt){
  asm volatile("{\n.reg .b32 ra;\nmapa.shared::cluster.u32 ra, %0, %1;\nmbarrier.arrive.shared::cluster.b64 _, [ra], %2;\n}\n"::"r"(bar),"r"(cta),"r"(cnt):"memory"); }
__device__ __forceinline__ void mbar_arrive_remote(uint32_t cluster_addr, uint32_t cnt){
  asm volatile("mbarrier.arrive.shared::cluster.b64 _, [%0], %1;"::"r"(cluster_addr),"r"(cnt):"memory"); }
__device__ __forceinline__ void mbar_wait(uint32_t bar, uint32_t parity){
  asm volatile("{\n.reg .pred p;\n.reg .u32 c;\nmov.u32 c, 0;\nLW:\nmbarrier.try_wait.parity.shared::cta.b64 p, [%0], %1;\n@p bra LD;\nadd.u32 c, c, 1;\nsetp.lt.u32 p, c, 2000000;\n@p bra LW;\ntrap;\nLD:\n}\n"::"r"(bar),"r"(parity):"memory"); }
__device__ __forceinline__ void mbar_wait2(uint32_t bar0, uint32_t par0, uint32_t bar1, uint32_t par1){
  asm volatile("{\n.reg .pred p, q;\n.reg .u32 c;\nmov.u32 c, 0;\nLW:\nmbarrier.try_wait.parity.shared::cta.b64 p, [%0], %1;\nmbarrier.try_wait.parity.shared::cta.b64 q, [%2], %3;\nand.pred p, p, q;\n@p bra LD;\nadd.u32 c, c, 1;\nsetp.lt.u32 p, c, 2000000;\n@p bra LW;\ntrap;\nLD:\n}\n"::"r"(bar0),"r"(par0),"r"(bar1),"r"(par1):"memory"); }
__device__ __forceinline__ bool mbar_test2(uint32_t bar0, uint32_t par0, uint32_t bar1, uint32_t par1){
  uint32_t r;
  asm volatile("{\n.reg .pred p, q;\nmbarrier.test_wait.parity.shared::cta.b64 p, [%1], %2;\nmbarrier.test_wait.parity.shared::cta.b64 q, [%3], %4;\nand.pred p, p, q;\nselp.u32 %0, 1, 0, p;\n}\n":"=r"(r):"r"(bar0),"r"(par0),"r"(bar1),"r"(par1):"memory");
  return r; }
__device__ __forceinline__ void tma_2d(uint32_t dst, const CUtensorMap* m, int c0, int c1, uint32_t bar){
  asm volatile("cp.async.bulk.tensor.2d.shared::cluster.global.mbarrier::complete_tx::bytes [%0], [%1, {%3, %4}], [%2];"::"r"(dst),"l"(m),"r"(bar),"r"(c0),"r"(c1):"memory"); }
__device__ __forceinline__ void tma_2d_mc(uint32_t dst, const CUtensorMap* m, int c0, int c1, uint32_t bar){
  asm volatile("cp.async.bulk.tensor.2d.shared::cluster.global.mbarrier::complete_tx::bytes.multicast::cluster [%0], [%1, {%3, %4}], [%2], %5;"::"r"(dst),"l"(m),"r"(bar),"r"(c0),"r"(c1),"h"((uint16_t)3):"memory"); }
__device__ __forceinline__ void tma_2d_mc_h(uint32_t dst, const CUtensorMap* m, int c0, int c1, uint32_t bar, uint64_t pol){
  asm volatile("cp.async.bulk.tensor.2d.shared::cluster.global.mbarrier::complete_tx::bytes.multicast::cluster.L2::cache_hint [%0], [%1, {%3, %4}], [%2], %5, %6;"::"r"(dst),"l"(m),"r"(bar),"r"(c0),"r"(c1),"h"((uint16_t)3),"l"(pol):"memory"); }
__device__ __forceinline__ void tma_4d(uint32_t dst, const CUtensorMap* m, int c0, int c1, int c2, int c3, uint32_t bar){
  asm volatile("cp.async.bulk.tensor.4d.shared::cluster.global.mbarrier::complete_tx::bytes [%0], [%1, {%3, %4, %5, %6}], [%2];"::"r"(dst),"l"(m),"r"(bar),"r"(c0),"r"(c1),"r"(c2),"r"(c3):"memory"); }
__device__ __forceinline__ uint64_t policy_evict_first(){ uint64_t p; asm volatile("createpolicy.fractional.L2::evict_first.b64 %0, 1.0;":"=l"(p)); return p; }
__device__ __forceinline__ uint64_t policy_evict_normal(){ uint64_t p; asm("createpolicy.fractional.L2::evict_normal.b64 %0, 1.0;":"=l"(p)); return p; }
__device__ __forceinline__ void tma_3d_h(uint32_t dst, const CUtensorMap* m, int c0, int c1, int c2, uint32_t bar, uint64_t pol){
  asm volatile("cp.async.bulk.tensor.3d.shared::cluster.global.mbarrier::complete_tx::bytes.L2::cache_hint [%0], [%1, {%3, %4, %5}], [%2], %6;"::"r"(dst),"l"(m),"r"(bar),"r"(c0),"r"(c1),"r"(c2),"l"(pol):"memory"); }
__device__ __forceinline__ void tma_4d_h(uint32_t dst, const CUtensorMap* m, int c0, int c1, int c2, int c3, uint32_t bar, uint64_t pol){
  asm volatile("cp.async.bulk.tensor.4d.shared::cluster.global.mbarrier::complete_tx::bytes.L2::cache_hint [%0], [%1, {%3, %4, %5, %6}], [%2], %7;"::"r"(dst),"l"(m),"r"(bar),"r"(c0),"r"(c1),"r"(c2),"r"(c3),"l"(pol):"memory"); }
__device__ __forceinline__ void red_add_f32x4(float4* p, float x, float y, float z, float w){ asm volatile("red.relaxed.gpu.global.add.v4.f32 [%0], {%1,%2,%3,%4};"::"l"(p),"f"(x),"f"(y),"f"(z),"f"(w):"memory"); }
__device__ __forceinline__ void tma_5d_h(uint32_t dst, const CUtensorMap* m, int c0, int c1, uint32_t bar, uint64_t pol){
  asm volatile("cp.async.bulk.tensor.5d.shared::cluster.global.mbarrier::complete_tx::bytes.L2::cache_hint [%0], [%1, {%3, %4, 0, 0, 0}], [%2], %5;"::"r"(dst),"l"(m),"r"(bar),"r"(c0),"r"(c1),"l"(pol):"memory"); }
__device__ __forceinline__ void tma_store_2d(const CUtensorMap* m, int c0, int c1, uint32_t src){
  asm volatile("cp.async.bulk.tensor.2d.global.shared::cta.bulk_group [%0, {%2, %3}], [%1];"::"l"(m),"r"(src),"r"(c0),"r"(c1):"memory"); }
__device__ __forceinline__ void bulk_commit(){ asm volatile("cp.async.bulk.commit_group;":::"memory"); }
__device__ __forceinline__ void bulk_wait_all(){ asm volatile("cp.async.bulk.wait_group 0;":::"memory"); }
__device__ __forceinline__ void fence_async_global(){ asm volatile("fence.proxy.async.global;":::"memory"); }
__device__ __forceinline__ bool elect_one(){ uint32_t p; asm volatile("{\n.reg .pred P;\nelect.sync _|P, 0xffffffff;\nselp.b32 %0, 1, 0, P;\n}\n":"=r"(p)); return p; }
__device__ __forceinline__ void bulk_prefetch(const void* p, uint32_t bytes){
  asm volatile("cp.async.bulk.prefetch.L2.global [%0], %1;"::"l"(p),"r"(bytes):"memory"); }
__device__ __forceinline__ void bulk_s2peer(uint32_t dst_cluster, uint32_t src, uint32_t bytes, uint32_t bar_cluster){
  asm volatile("cp.async.bulk.shared::cluster.shared::cta.mbarrier::complete_tx::bytes [%0], [%1], %2, [%3];"::"r"(dst_cluster),"r"(src),"r"(bytes),"r"(bar_cluster):"memory"); }
__device__ __forceinline__ void bulk_g2s_mc(uint32_t dst, const void* src, uint32_t bytes, uint32_t bar, uint64_t pol){
  asm volatile("cp.async.bulk.shared::cluster.global.mbarrier::complete_tx::bytes.multicast::cluster.L2::cache_hint [%0], [%1], %2, [%3], %4, %5;"::"r"(dst),"l"(src),"r"(bytes),"r"(bar),"h"((uint16_t)3),"l"(pol):"memory"); }
__device__ __forceinline__ void prefetch_map(const CUtensorMap* m){ asm volatile("prefetch.tensormap [%0];"::"l"(m):"memory"); }
__device__ __forceinline__ void fence_async_smem(){ asm volatile("fence.proxy.async.shared::cta;":::"memory"); }
__device__ __forceinline__ void fence_acquire_gpu(){ asm volatile("fence.acquire.gpu;":::"memory"); }
__device__ __forceinline__ void fence_gpu(){ asm volatile("fence.acq_rel.gpu;":::"memory"); }
__device__ __forceinline__ void wg_fence(){ asm volatile("wgmma.fence.sync.aligned;":::"memory"); }
__device__ __forceinline__ void wg_commit(){ asm volatile("wgmma.commit_group.sync.aligned;":::"memory"); }
template<int N> __device__ __forceinline__ void wg_wait(){ asm volatile("wgmma.wait_group.sync.aligned %0;"::"n"(N):"memory"); }
template<int N> __device__ __forceinline__ void fence_regs(float (&d)[N]){
  #pragma unroll
  for(int i=0;i<N;i++) asm volatile("":"+f"(d[i])::"memory"); }
__device__ __forceinline__ void bar_sync(int id, int n){ asm volatile("bar.sync %0, %1;"::"r"(id),"r"(n):"memory"); }
__device__ __forceinline__ void bar_arrive(int id, int n){ asm volatile("bar.arrive %0, %1;"::"r"(id),"r"(n):"memory"); }
__device__ __forceinline__ void cluster_arrive(){ asm volatile("barrier.cluster.arrive.relaxed.aligned;":::"memory"); }
__device__ __forceinline__ void cluster_wait(){ asm volatile("barrier.cluster.wait.aligned;":::"memory"); }
__host__ __device__ constexpr uint32_t dlo(uint32_t addr, uint32_t lbo){ return (addr >> 4) | ((lbo >> 4) << 16); }
__host__ __device__ constexpr uint32_t dhi(uint32_t sbo, uint32_t sw){ return (sbo >> 4) | (sw << 30); }
constexpr uint32_t H128 = dhi(1024, 1), H64 = dhi(512, 2), H0 = dhi(128, 0);
__device__ __forceinline__ uint32_t pack_bf16(float lo, float hi){ uint32_t r; asm("cvt.rn.bf16x2.f32 %0, %1, %2;":"=r"(r):"f"(hi),"f"(lo)); return r; }
__device__ __forceinline__ float bf_lo(uint32_t v){ return __uint_as_float(v<<16); }
__device__ __forceinline__ float bf_hi(uint32_t v){ return __uint_as_float(v&0xffff0000u); }
__device__ __forceinline__ float ex2(float x){ float r; asm("ex2.approx.ftz.f32 %0, %1;":"=f"(r):"f"(x)); return r; }
__device__ __forceinline__ float rcp(float x){ float r; asm("rcp.approx.ftz.f32 %0, %1;":"=f"(r):"f"(x)); return r; }
__device__ __forceinline__ void stsm4(uint32_t addr, uint32_t a, uint32_t b, uint32_t c, uint32_t d){
  asm volatile("stmatrix.sync.aligned.m8n8.x4.shared.b16 [%0], {%1,%2,%3,%4};"::"r"(addr),"r"(a),"r"(b),"r"(c),"r"(d)); }
__device__ __forceinline__ void stsm2(uint32_t addr, uint32_t a, uint32_t b){
  asm volatile("stmatrix.sync.aligned.m8n8.x2.shared.b16 [%0], {%1,%2};"::"r"(addr),"r"(a),"r"(b)); }
__device__ __forceinline__ void mma16816(float& d0, float& d1, float& d2, float& d3, uint32_t a0, uint32_t a1, uint32_t a2, uint32_t a3, uint32_t b0, uint32_t b1){
  asm volatile("mma.sync.aligned.m16n8k16.row.col.f32.bf16.bf16.f32 {%0,%1,%2,%3}, {%4,%5,%6,%7}, {%8,%9}, {%0,%1,%2,%3};"
               : "+f"(d0), "+f"(d1), "+f"(d2), "+f"(d3) : "r"(a0), "r"(a1), "r"(a2), "r"(a3), "r"(b0), "r"(b1)); }
__device__ __forceinline__ void ldsm4(uint32_t addr, uint32_t& a, uint32_t& b, uint32_t& c, uint32_t& d){
  asm volatile("ldmatrix.sync.aligned.m8n8.x4.shared.b16 {%0,%1,%2,%3}, [%4];":"=r"(a),"=r"(b),"=r"(c),"=r"(d):"r"(addr):"memory"); }
__device__ __forceinline__ void ldsm4t(uint32_t addr, uint32_t& a, uint32_t& b, uint32_t& c, uint32_t& d){
  asm volatile("ldmatrix.sync.aligned.m8n8.x4.trans.shared.b16 {%0,%1,%2,%3}, [%4];":"=r"(a),"=r"(b),"=r"(c),"=r"(d):"r"(addr):"memory"); }
__device__ __forceinline__ void sts32(uint32_t a, uint32_t v){ asm volatile("st.shared.b32 [%0], %1;"::"r"(a),"r"(v):"memory"); }
__device__ __forceinline__ void stsf(uint32_t a, float v){ asm volatile("st.shared.f32 [%0], %1;"::"r"(a),"f"(v):"memory"); }
__device__ __forceinline__ void sts64(uint32_t a, uint32_t x, uint32_t y){ asm volatile("st.shared.v2.b32 [%0], {%1,%2};"::"r"(a),"r"(x),"r"(y):"memory"); }
__device__ __forceinline__ void sts128(uint32_t a, uint32_t x, uint32_t y, uint32_t z, uint32_t w){ asm volatile("st.shared.v4.b32 [%0], {%1,%2,%3,%4};"::"r"(a),"r"(x),"r"(y),"r"(z),"r"(w):"memory"); }
__device__ __forceinline__ float ldsf(uint32_t a){ float v; asm volatile("ld.shared.f32 %0, [%1];":"=f"(v):"r"(a):"memory"); return v; }
__device__ __forceinline__ float2 lds64f(uint32_t a){ float2 v; asm volatile("ld.shared.v2.f32 {%0,%1}, [%2];":"=f"(v.x),"=f"(v.y):"r"(a):"memory"); return v; }
__device__ __forceinline__ uint4 lds128(uint32_t a){ uint4 v; asm volatile("ld.shared.v4.u32 {%0,%1,%2,%3}, [%4];":"=r"(v.x),"=r"(v.y),"=r"(v.z),"=r"(v.w):"r"(a):"memory"); return v; }
__device__ __forceinline__ uint4 ld128_keep(const void* p){ uint4 v; asm volatile("ld.global.v4.u32 {%0,%1,%2,%3}, [%4];":"=r"(v.x),"=r"(v.y),"=r"(v.z),"=r"(v.w):"l"(p):"memory"); return v; }
__device__ __forceinline__ uint4 ld128_rlx(const void* p){ uint4 v; asm volatile("ld.relaxed.gpu.global.v4.u32 {%0,%1,%2,%3}, [%4];":"=r"(v.x),"=r"(v.y),"=r"(v.z),"=r"(v.w):"l"(p):"memory"); return v; }
__device__ __forceinline__ uint32_t ld32_rlx(const void* p){ uint32_t v; asm volatile("ld.relaxed.gpu.global.u32 %0, [%1];":"=r"(v):"l"(p):"memory"); return v; }
__device__ __forceinline__ void st128_rlx(void* p, uint32_t x, uint32_t y, uint32_t z, uint32_t w){ asm volatile("st.relaxed.gpu.global.v4.u32 [%0], {%1,%2,%3,%4};"::"l"(p),"r"(x),"r"(y),"r"(z),"r"(w):"memory"); }
__device__ __forceinline__ void st64_rlx(void* p, uint32_t x, uint32_t y){ asm volatile("st.relaxed.gpu.global.v2.u32 [%0], {%1,%2};"::"l"(p),"r"(x),"r"(y):"memory"); }
__device__ __forceinline__ void st32_rlx(void* p, uint32_t x){ asm volatile("st.relaxed.gpu.global.u32 [%0], %1;"::"l"(p),"r"(x):"memory"); }
__device__ __forceinline__ uint32_t tagw(float x, uint32_t t){ return (__float_as_uint(x) & ~3u) | t; }
__device__ __forceinline__ float untag(uint32_t w){ return __uint_as_float(w & ~3u); }

template<int TA, int TB, uint32_t HA, uint32_t HB> __device__ __forceinline__ void wgmma_ss_n128(float (&d)[64], uint32_t da, uint32_t db, int scale_d){
  asm volatile("{\n.reg .pred p;\n.reg .b64 a, b;\nsetp.ne.b32 p, %70, 0;\nmov.b64 a, {%64, %68};\nmov.b64 b, {%65, %69};\n"
  "wgmma.mma_async.sync.aligned.m64n128k16.f32.bf16.bf16 {%0, %1, %2, %3, %4, %5, %6, %7, %8, %9, %10, %11, %12, %13, %14, %15, %16, %17, %18, %19, %20, %21, %22, %23, %24, %25, %26, %27, %28, %29, %30, %31, %32, %33, %34, %35, %36, %37, %38, %39, %40, %41, %42, %43, %44, %45, %46, %47, %48, %49, %50, %51, %52, %53, %54, %55, %56, %57, %58, %59, %60, %61, %62, %63}, a, b, p, 1, 1, %66, %67;\n}\n"
  : "+f"(d[0]), "+f"(d[1]), "+f"(d[2]), "+f"(d[3]), "+f"(d[4]), "+f"(d[5]), "+f"(d[6]), "+f"(d[7]), "+f"(d[8]), "+f"(d[9]), "+f"(d[10]), "+f"(d[11]), "+f"(d[12]), "+f"(d[13]), "+f"(d[14]), "+f"(d[15]), "+f"(d[16]), "+f"(d[17]), "+f"(d[18]), "+f"(d[19]), "+f"(d[20]), "+f"(d[21]), "+f"(d[22]), "+f"(d[23]), "+f"(d[24]), "+f"(d[25]), "+f"(d[26]), "+f"(d[27]), "+f"(d[28]), "+f"(d[29]), "+f"(d[30]), "+f"(d[31]), "+f"(d[32]), "+f"(d[33]), "+f"(d[34]), "+f"(d[35]), "+f"(d[36]), "+f"(d[37]), "+f"(d[38]), "+f"(d[39]), "+f"(d[40]), "+f"(d[41]), "+f"(d[42]), "+f"(d[43]), "+f"(d[44]), "+f"(d[45]), "+f"(d[46]), "+f"(d[47]), "+f"(d[48]), "+f"(d[49]), "+f"(d[50]), "+f"(d[51]), "+f"(d[52]), "+f"(d[53]), "+f"(d[54]), "+f"(d[55]), "+f"(d[56]), "+f"(d[57]), "+f"(d[58]), "+f"(d[59]), "+f"(d[60]), "+f"(d[61]), "+f"(d[62]), "+f"(d[63])
  : "r"(da), "r"(db), "n"(TA), "n"(TB), "n"(HA), "n"(HB), "r"(scale_d));
}
template<int TA, int TB, uint32_t HA, uint32_t HB> __device__ __forceinline__ void wgmma_sa_n128(float (&d)[64], uint32_t da, uint32_t db){
  asm volatile("{\n.reg .pred p;\n.reg .b64 a, b;\nsetp.ne.b32 p, 1, 0;\nmov.b64 a, {%64, %68};\nmov.b64 b, {%65, %69};\n"
  "wgmma.mma_async.sync.aligned.m64n128k16.f32.bf16.bf16 {%0, %1, %2, %3, %4, %5, %6, %7, %8, %9, %10, %11, %12, %13, %14, %15, %16, %17, %18, %19, %20, %21, %22, %23, %24, %25, %26, %27, %28, %29, %30, %31, %32, %33, %34, %35, %36, %37, %38, %39, %40, %41, %42, %43, %44, %45, %46, %47, %48, %49, %50, %51, %52, %53, %54, %55, %56, %57, %58, %59, %60, %61, %62, %63}, a, b, p, 1, 1, %66, %67;\n}\n"
  : "+f"(d[0]), "+f"(d[1]), "+f"(d[2]), "+f"(d[3]), "+f"(d[4]), "+f"(d[5]), "+f"(d[6]), "+f"(d[7]), "+f"(d[8]), "+f"(d[9]), "+f"(d[10]), "+f"(d[11]), "+f"(d[12]), "+f"(d[13]), "+f"(d[14]), "+f"(d[15]), "+f"(d[16]), "+f"(d[17]), "+f"(d[18]), "+f"(d[19]), "+f"(d[20]), "+f"(d[21]), "+f"(d[22]), "+f"(d[23]), "+f"(d[24]), "+f"(d[25]), "+f"(d[26]), "+f"(d[27]), "+f"(d[28]), "+f"(d[29]), "+f"(d[30]), "+f"(d[31]), "+f"(d[32]), "+f"(d[33]), "+f"(d[34]), "+f"(d[35]), "+f"(d[36]), "+f"(d[37]), "+f"(d[38]), "+f"(d[39]), "+f"(d[40]), "+f"(d[41]), "+f"(d[42]), "+f"(d[43]), "+f"(d[44]), "+f"(d[45]), "+f"(d[46]), "+f"(d[47]), "+f"(d[48]), "+f"(d[49]), "+f"(d[50]), "+f"(d[51]), "+f"(d[52]), "+f"(d[53]), "+f"(d[54]), "+f"(d[55]), "+f"(d[56]), "+f"(d[57]), "+f"(d[58]), "+f"(d[59]), "+f"(d[60]), "+f"(d[61]), "+f"(d[62]), "+f"(d[63])
  : "r"(da), "r"(db), "n"(TA), "n"(TB), "n"(HA), "n"(HB));
}
template<int TA, int TB, uint32_t HA, uint32_t HB> __device__ __forceinline__ void wgmma_sa_n40(float (&d)[20], uint32_t da, uint32_t db){
  asm volatile("{\n.reg .pred p;\n.reg .b64 a, b;\nsetp.ne.b32 p, 1, 0;\nmov.b64 a, {%20, %24};\nmov.b64 b, {%21, %25};\n"
  "wgmma.mma_async.sync.aligned.m64n40k16.f32.bf16.bf16 {%0, %1, %2, %3, %4, %5, %6, %7, %8, %9, %10, %11, %12, %13, %14, %15, %16, %17, %18, %19}, a, b, p, 1, 1, %22, %23;\n}\n"
  : "+f"(d[0]), "+f"(d[1]), "+f"(d[2]), "+f"(d[3]), "+f"(d[4]), "+f"(d[5]), "+f"(d[6]), "+f"(d[7]), "+f"(d[8]), "+f"(d[9]), "+f"(d[10]), "+f"(d[11]), "+f"(d[12]), "+f"(d[13]), "+f"(d[14]), "+f"(d[15]), "+f"(d[16]), "+f"(d[17]), "+f"(d[18]), "+f"(d[19])
  : "r"(da), "r"(db), "n"(TA), "n"(TB), "n"(HA), "n"(HB));
}
template<int TA, int TB, uint32_t HA, uint32_t HB> __device__ __forceinline__ void wgmma_sz_n40(float (&d)[20], uint32_t da, uint32_t db){
  asm volatile("{\n.reg .pred p;\n.reg .b64 a, b;\nsetp.ne.b32 p, 0, 0;\nmov.b64 a, {%20, %24};\nmov.b64 b, {%21, %25};\n"
  "wgmma.mma_async.sync.aligned.m64n40k16.f32.bf16.bf16 {%0, %1, %2, %3, %4, %5, %6, %7, %8, %9, %10, %11, %12, %13, %14, %15, %16, %17, %18, %19}, a, b, p, 1, 1, %22, %23;\n}\n"
  : "=f"(d[0]), "=f"(d[1]), "=f"(d[2]), "=f"(d[3]), "=f"(d[4]), "=f"(d[5]), "=f"(d[6]), "=f"(d[7]), "=f"(d[8]), "=f"(d[9]), "=f"(d[10]), "=f"(d[11]), "=f"(d[12]), "=f"(d[13]), "=f"(d[14]), "=f"(d[15]), "=f"(d[16]), "=f"(d[17]), "=f"(d[18]), "=f"(d[19])
  : "r"(da), "r"(db), "n"(TA), "n"(TB), "n"(HA), "n"(HB));
}
template<int TA, int TB, uint32_t HA, uint32_t HB> __device__ __forceinline__ void wgmma_sa_n32(float (&d)[16], uint32_t da, uint32_t db){
  asm volatile("{\n.reg .pred p;\n.reg .b64 a, b;\nsetp.ne.b32 p, 1, 0;\nmov.b64 a, {%16, %20};\nmov.b64 b, {%17, %21};\n"
  "wgmma.mma_async.sync.aligned.m64n32k16.f32.bf16.bf16 {%0, %1, %2, %3, %4, %5, %6, %7, %8, %9, %10, %11, %12, %13, %14, %15}, a, b, p, 1, 1, %18, %19;\n}\n"
  : "+f"(d[0]), "+f"(d[1]), "+f"(d[2]), "+f"(d[3]), "+f"(d[4]), "+f"(d[5]), "+f"(d[6]), "+f"(d[7]), "+f"(d[8]), "+f"(d[9]), "+f"(d[10]), "+f"(d[11]), "+f"(d[12]), "+f"(d[13]), "+f"(d[14]), "+f"(d[15])
  : "r"(da), "r"(db), "n"(TA), "n"(TB), "n"(HA), "n"(HB));
}
template<int TA, int TB, uint32_t HA, uint32_t HB> __device__ __forceinline__ void wgmma_ss_n32(float (&d)[16], uint32_t da, uint32_t db, int scale_d){
  asm volatile("{\n.reg .pred p;\n.reg .b64 a, b;\nsetp.ne.b32 p, %22, 0;\nmov.b64 a, {%16, %20};\nmov.b64 b, {%17, %21};\n"
  "wgmma.mma_async.sync.aligned.m64n32k16.f32.bf16.bf16 {%0, %1, %2, %3, %4, %5, %6, %7, %8, %9, %10, %11, %12, %13, %14, %15}, a, b, p, 1, 1, %18, %19;\n}\n"
  : "+f"(d[0]), "+f"(d[1]), "+f"(d[2]), "+f"(d[3]), "+f"(d[4]), "+f"(d[5]), "+f"(d[6]), "+f"(d[7]), "+f"(d[8]), "+f"(d[9]), "+f"(d[10]), "+f"(d[11]), "+f"(d[12]), "+f"(d[13]), "+f"(d[14]), "+f"(d[15])
  : "r"(da), "r"(db), "n"(TA), "n"(TB), "n"(HA), "n"(HB), "r"(scale_d));
}
template<int TB, uint32_t HB> __device__ __forceinline__ void wgmma_ra_n32(float (&d)[16], uint32_t a0, uint32_t a1, uint32_t a2, uint32_t a3, uint32_t db){
  asm volatile("{\n.reg .pred p;\n.reg .b64 a, b;\nsetp.ne.b32 p, 1, 0;\nmov.b64 b, {%20, %22};\n"
  "wgmma.mma_async.sync.aligned.m64n32k16.f32.bf16.bf16 {%0, %1, %2, %3, %4, %5, %6, %7, %8, %9, %10, %11, %12, %13, %14, %15}, {%16,%17,%18,%19}, b, p, 1, 1, %21;\n}\n"
  : "+f"(d[0]), "+f"(d[1]), "+f"(d[2]), "+f"(d[3]), "+f"(d[4]), "+f"(d[5]), "+f"(d[6]), "+f"(d[7]), "+f"(d[8]), "+f"(d[9]), "+f"(d[10]), "+f"(d[11]), "+f"(d[12]), "+f"(d[13]), "+f"(d[14]), "+f"(d[15])
  : "r"(a0), "r"(a1), "r"(a2), "r"(a3), "r"(db), "n"(TB), "n"(HB));
}
template<int TB, uint32_t HB> __device__ __forceinline__ void wgmma_rs_n32(float (&d)[16], uint32_t a0, uint32_t a1, uint32_t a2, uint32_t a3, uint32_t db, int scale_d){
  asm volatile("{\n.reg .pred p;\n.reg .b64 a, b;\nsetp.ne.b32 p, %23, 0;\nmov.b64 b, {%20, %22};\n"
  "wgmma.mma_async.sync.aligned.m64n32k16.f32.bf16.bf16 {%0, %1, %2, %3, %4, %5, %6, %7, %8, %9, %10, %11, %12, %13, %14, %15}, {%16,%17,%18,%19}, b, p, 1, 1, %21;\n}\n"
  : "+f"(d[0]), "+f"(d[1]), "+f"(d[2]), "+f"(d[3]), "+f"(d[4]), "+f"(d[5]), "+f"(d[6]), "+f"(d[7]), "+f"(d[8]), "+f"(d[9]), "+f"(d[10]), "+f"(d[11]), "+f"(d[12]), "+f"(d[13]), "+f"(d[14]), "+f"(d[15])
  : "r"(a0), "r"(a1), "r"(a2), "r"(a3), "r"(db), "n"(TB), "n"(HB), "r"(scale_d));
}
template<int TB, uint32_t HB> __device__ __forceinline__ void wgmma_ra_n40(float (&d)[20], uint32_t a0, uint32_t a1, uint32_t a2, uint32_t a3, uint32_t db){
  asm volatile("{\n.reg .pred p;\n.reg .b64 a, b;\nsetp.ne.b32 p, 1, 0;\nmov.b64 b, {%24, %26};\n"
  "wgmma.mma_async.sync.aligned.m64n40k16.f32.bf16.bf16 {%0, %1, %2, %3, %4, %5, %6, %7, %8, %9, %10, %11, %12, %13, %14, %15, %16, %17, %18, %19}, {%20,%21,%22,%23}, b, p, 1, 1, %25;\n}\n"
  : "+f"(d[0]), "+f"(d[1]), "+f"(d[2]), "+f"(d[3]), "+f"(d[4]), "+f"(d[5]), "+f"(d[6]), "+f"(d[7]), "+f"(d[8]), "+f"(d[9]), "+f"(d[10]), "+f"(d[11]), "+f"(d[12]), "+f"(d[13]), "+f"(d[14]), "+f"(d[15]), "+f"(d[16]), "+f"(d[17]), "+f"(d[18]), "+f"(d[19])
  : "r"(a0), "r"(a1), "r"(a2), "r"(a3), "r"(db), "n"(TB), "n"(HB));
}
template<int TB, uint32_t HB> __device__ __forceinline__ void wgmma_rz_n40(float (&d)[20], uint32_t a0, uint32_t a1, uint32_t a2, uint32_t a3, uint32_t db){
  asm volatile("{\n.reg .pred p;\n.reg .b64 a, b;\nsetp.ne.b32 p, 0, 0;\nmov.b64 b, {%24, %26};\n"
  "wgmma.mma_async.sync.aligned.m64n40k16.f32.bf16.bf16 {%0, %1, %2, %3, %4, %5, %6, %7, %8, %9, %10, %11, %12, %13, %14, %15, %16, %17, %18, %19}, {%20,%21,%22,%23}, b, p, 1, 1, %25;\n}\n"
  : "=f"(d[0]), "=f"(d[1]), "=f"(d[2]), "=f"(d[3]), "=f"(d[4]), "=f"(d[5]), "=f"(d[6]), "=f"(d[7]), "=f"(d[8]), "=f"(d[9]), "=f"(d[10]), "=f"(d[11]), "=f"(d[12]), "=f"(d[13]), "=f"(d[14]), "=f"(d[15]), "=f"(d[16]), "=f"(d[17]), "=f"(d[18]), "=f"(d[19])
  : "r"(a0), "r"(a1), "r"(a2), "r"(a3), "r"(db), "n"(TB), "n"(HB));
}
template<int TB, uint32_t HB> __device__ __forceinline__ void wgmma_rz_n8(float (&d)[4], uint32_t a0, uint32_t a1, uint32_t a2, uint32_t a3, uint32_t db){
  asm volatile("{\n.reg .pred p;\n.reg .b64 a, b;\nsetp.ne.b32 p, 0, 0;\nmov.b64 b, {%8, %10};\n"
  "wgmma.mma_async.sync.aligned.m64n8k16.f32.bf16.bf16 {%0, %1, %2, %3}, {%4,%5,%6,%7}, b, p, 1, 1, %9;\n}\n"
  : "=f"(d[0]), "=f"(d[1]), "=f"(d[2]), "=f"(d[3])
  : "r"(a0), "r"(a1), "r"(a2), "r"(a3), "r"(db), "n"(TB), "n"(HB));
}

constexpr int SEQ = 2048, DM = 1024, FF = 3584;
constexpr float LOG2E = 1.4426950408889634f;
constexpr uint32_t POLL_LIMIT = 1u << 22;
#define NPRE0 1
#define NPREN 2
constexpr int NPRE = NPREN;
#define QW 4
#define RS_N 22
#define RS_D1 430
#define RS_D2 300
#define SKM 0x154
#define LAG 2
#define PF_T0 5000
#define PF_DT 800
#define NFFN_L NFFN
#define FF_DT 500
#define GRES 8
#define TMASK 0xffffff
#define PMASK 0xffffff
#define FF_T0 400
#define GPRE 0
#define REL 6
#define EFI 11
#define TKW 8
#define SLOT 0
#define SLOTW 48
#define FF_ORD 0x76543210ba98ull
#define KT 0
#define KK(id) do { if (KT) { TK(32 * wg + (id)); } } while (0)
#define PF_I0 0
#define PF_ST 7
#define PRK 3
#define TRKL 1
#define KR 4
#define KSEL c
#define XP 0
#define CAPL 2
#define OUT_D 400
#define OUT_0 0
#define ML 2
#define H2 1
#define H3 1
constexpr int NFFN = 112;

constexpr uint32_t SB0 = 1024;
constexpr uint32_t KV_STAGE = 49152, R5 = 32768;
constexpr uint32_t OFF_X = 163840, OFF_S = 196608, OFF_WPHI = OFF_S + 20480, OFF_M = 229376, SMEM_BYTES = 232448;
constexpr uint32_t OFF_RS256 = 212992, OFF_ONES = OFF_RS256 + 1024, OFF_WPHIK1 = OFF_ONES + 1024, OFF_KVZ = OFF_S;
constexpr uint32_t OFF_WPHIK = OFF_S, OFF_BXK = OFF_S + 2048, OFF_AXK = OFF_S + 4096, OFF_G = OFF_S + 8192;
constexpr uint32_t OFF_AXQ = OFF_WPHI, OFF_BXQ = OFF_WPHI + 2048, OFF_WPHIQ = OFF_WPHI + 4096;
constexpr uint32_t B_FULLKV = OFF_M  , B_EMPTYKV = OFF_M + 32  ;
constexpr uint32_t B_EMPTY5 = OFF_M + 64  , B_UO = B_EMPTY5 + 48  , B_RC = B_UO + 32  ;
constexpr uint32_t B_OUT = B_RC + 16  , B_SD = B_OUT + 16, B_AUX = B_SD + 8, B_AUXQ = B_AUX + 8, B_RX = B_AUXQ + 8;
constexpr uint32_t B_FULL5 = B_RX + 8  , B_FULLA = B_FULL5 + 48  , B_F = B_FULLA + 96  , B_WD = B_F + 64  ;
constexpr uint32_t B_WC = B_WD + 32  , B_DR = B_WC + 32  , B_W = B_DR + 24, B_OS = B_W + 8, B_R = B_W + 16, B_KD = B_W + 24, B_R1 = B_W + 32, B_T = B_W + 40, B_G = B_W + 48, B_END = B_W + 56, B_S0 = B_END;
static_assert(B_S0 < OFF_M + 592 && B_END <= OFF_M + 592 && B_FULL5 + 40 >= OFF_M + 208 && B_FULL5 + 40 < OFF_M + 400, "barriers");
constexpr uint32_t OFF_SUMWR = OFF_M + 608, OFF_EP = OFF_M + 624, OFF_KEY = OFF_M + 628;
constexpr uint32_t OFF_RSQ = OFF_M + 640, OFF_TL = OFF_M + 1152, OFF_SEL = OFF_M + 1648, OFF_T = OFF_M + 1792, OFF_WR = OFF_M + 2048, OFF_SCR = OFF_M + 2432;
constexpr uint32_t OFF_XSEL = 2 * R5, OFF_GU = OFF_XSEL + 4096, OFF_OUT = 3 * R5;
constexpr uint64_t FF_SLOT = 0xdcdc3210dcbaull;
constexpr int KVP = 6 * 128;

enum { NB_G2E = 1, NB_XS = 2, NB_WG01 = 3, NB_ACT = 4, NB_Q0 = 5  , NB_ST = 14, NB_DN = 9, NB_ZERO = 10, NB_PUB = 11, NB_TOK = 10  , NB_L0 = 12  , NB_WG2 = 7, NB_QGO = 15 };

struct Scratch {
  bf16     o[SEQ * DM];
  float4   rstat[SEQ];
  uint32_t key[8 * KR * 128];
  uint32_t cand[128 * 512];
  float4   yacc[4 * 3 * 128];
  float4   kvacc[32 * KVP];
  uint2    stats[SEQ];
  uint32_t cskv[2 * DM];
  uint32_t csq[4 * DM];
  uint32_t oset[128 * 16];
  uint32_t epoch;
};
__device__ __align__(1024) Scratch g_scr;
#define TS(id)
#define TDUMP()
#define TS0_DECL()
#define TS0_READ()
#define TS0_WRITE()
#define TK(id)
#define TSW(id)

struct Params {
  CUtensorMap x128, x64, wkv, wq, wo[2], wd, wg, wu, phi, tg, tu, td, xs, ws, qs, out;
  const bf16 *x, *wqkv, *wo_p, *wg_p, *wu_p, *wd_p, *wr;
  bf16* out_p;
  Scratch* g;
  uint32_t zero;
};

constexpr float EXP_LIM = 1.1529215e18f, ARG_LIM2 = 3600.f;
template<bool PR> __device__ __forceinline__ void dual_exp2(const float (&p)[16], uint32_t (&ep)[8], uint32_t (&em)[8]) {
  #pragma unroll
  for (int k = 0; k < 8; k++) {
    const float a = ex2(p[2*k]), b = ex2(p[2*k+1]);
    ep[k] = pack_bf16(a, b);
    if (PR) { const float r = rcp(a * b); em[k] = pack_bf16(r * b, r * a); }
    else em[k] = pack_bf16(ex2(-p[2*k]), ex2(-p[2*k+1]));
  }
}
__device__ __forceinline__ void dual_exp2_shifted(const float (&pp)[2][16], uint32_t (&ph)[4][8]) {
  #pragma unroll
  for (int h = 0; h < 2; h++) {
    const float* p = pp[h];
    float m[4] = {p[0], p[2], p[0], p[2]};
    #pragma unroll
    for (int i = 0; i < 16; i++) { m[(i >> 1) & 1] = fmaxf(m[(i >> 1) & 1], p[i]); m[2 + ((i >> 1) & 1)] = fminf(m[2 + ((i >> 1) & 1)], p[i]); }
    #pragma unroll
    for (int o = 1; o < 4; o <<= 1) {
      m[0] = fmaxf(m[0], __shfl_xor_sync(~0u, m[0], o)); m[1] = fmaxf(m[1], __shfl_xor_sync(~0u, m[1], o));
      m[2] = fminf(m[2], __shfl_xor_sync(~0u, m[2], o)); m[3] = fminf(m[3], __shfl_xor_sync(~0u, m[3], o));
    }
    #pragma unroll
    for (int k = 0; k < 8; k++) {
      ph[2*h][k] = pack_bf16(ex2(p[2*k] - m[k & 1]), ex2(p[2*k+1] - m[k & 1]));
      ph[2*h+1][k] = pack_bf16(ex2(m[2 + (k & 1)] - p[2*k]), ex2(m[2 + (k & 1)] - p[2*k+1]));
    }
  }
}
__device__ __forceinline__ uint32_t add_bf16x2(uint32_t a, uint32_t b) { uint32_t r; asm("add.rn.bf16x2 %0, %1, %2;" : "=r"(r) : "r"(a), "r"(b)); return r; }
__device__ __forceinline__ void row_sums(float (&s)[2][4], const uint32_t (&ph)[4][8], uint32_t sel) {
  uint32_t u[8];
  #pragma unroll
  for (int i = 0; i < 8; i++) { const uint32_t* f = &ph[i >> 1][i & 1]; u[i] = add_bf16x2(add_bf16x2(f[0], f[2]), add_bf16x2(f[4], f[6])); }
  wg_fence();
  wgmma_rz_n8<0, H0>(s[0], u[0], u[1], u[2], u[3], sel);
  wgmma_rz_n8<0, H0>(s[1], u[4], u[5], u[6], u[7], sel);
  wg_commit();
}
__device__ __forceinline__ uint32_t mul_bf16x2(uint32_t a, uint32_t b) { uint32_t r; asm("mul.rn.bf16x2 %0, %1, %2;" : "=r"(r) : "r"(a), "r"(b)); return r; }
__device__ __forceinline__ void normalize(uint32_t (&ph)[4][8], const float (&s)[2][4]) {
  #pragma unroll
  for (int i = 0; i < 4; i++) {
    const float i0 = rcp(s[i >> 1][i & 1]), i1 = rcp(s[i >> 1][2 + (i & 1)]);
    const uint32_t n0 = pack_bf16(i0, i0), n1 = pack_bf16(i1, i1);
    #pragma unroll
    for (int k = 0; k < 4; k++) { ph[i][2*k] = mul_bf16x2(ph[i][2*k], n0); ph[i][2*k+1] = mul_bf16x2(ph[i][2*k+1], n1); }
  }
}
__device__ __forceinline__ void split_bf16(float a, float b, uint32_t& hi, uint32_t& lo) { hi = pack_bf16(a, b); lo = pack_bf16(a - bf_lo(hi), b - bf_hi(hi)); }
__device__ __forceinline__ void put_colsums(uint32_t base, int lane, float a, float b, float c, float d) {
  uint32_t h0, l0, h1, l1;
  split_bf16(a, b, h0, l0); split_bf16(c, d, h1, l1);
  const uint32_t ad = base + (lane >> 1) * 128 + (lane & 1) * 8;
  sts64(ad, h0, h1); sts64(ad + 16, l0, l1); sts64(ad + 32, h0, h1); sts64(ad + 48, l0, l1);
  sts128(base + (lane >> 1) * 128 + 64 + (lane & 1) * 32, 0, 0, 0, 0); sts128(base + (lane >> 1) * 128 + 80 + (lane & 1) * 32, 0, 0, 0, 0);
}
__device__ __forceinline__ float reduce8(const float (&v)[8], int lane) {
  const bool b4 = lane & 16, b3 = lane & 8, b2 = lane & 4;
  float a[4], b[2];
  #pragma unroll
  for (int i = 0; i < 4; i++) a[i] = (b4 ? v[4 + i] : v[i]) + __shfl_xor_sync(~0u, b4 ? v[i] : v[4 + i], 16);
  #pragma unroll
  for (int i = 0; i < 2; i++) b[i] = (b3 ? a[2 + i] : a[i]) + __shfl_xor_sync(~0u, b3 ? a[i] : a[2 + i], 8);
  return (b2 ? b[1] : b[0]) + __shfl_xor_sync(~0u, b2 ? b[0] : b[1], 4);
}
__device__ __forceinline__ bool tag_bad(uint4 v, uint32_t tg) { return (((v.x ^ tg) | (v.y ^ tg) | (v.z ^ tg) | (v.w ^ tg)) & 3) != 0; }

__global__ void __launch_bounds__(512, 1) fused_kernel(const __grid_constant__ Params P) {
  extern __shared__ __align__(1024) uint8_t smem_raw[];
  const uint32_t sb = smem_u32(smem_raw);
  const int tid = threadIdx.x, lane = tid & 31;
  TS0_DECL();
  TS0_READ();
  if (tid == 352) { prefetch_map(&P.wkv); prefetch_map(&P.x128); }
  const int cp = blockIdx.x >> 1, rank = blockIdx.x & 1;
  const int cr = cp < 4 ? 32 + 8 * cp : cp - 4 + max((cp * 37 - 1076) >> 8, 0);
  const int c = (cr & 62) + 64 * (cr & 1) + rank;
  const int m256 = c >> 4, nkv = c & 15, m128 = c >> 3, j = c & 7;
  if ((tid >> 5) == 12 && elect_one()) {
    mbar_init(sb + B_S0, 1); mbar_init(sb + B_FULLKV, 1); mbar_init(sb + B_FULLKV + 8, 1);
    fence_async_smem();
    mbar_expect_tx(sb + B_S0, 32768);
    tma_4d(sb + 32768, &P.wkv, 0, 0, nkv, 1, sb + B_S0);
    tma_2d(sb, &P.x128, 0, 256 * m256, sb + B_S0);
    mbar_expect_tx(sb + B_FULLKV, 16384);
    tma_2d(sb + 16384, &P.x128, 0, 256 * m256 + 128, sb + B_FULLKV);
    if (NPRE0 > 1) {
      mbar_expect_tx(sb + B_FULLKV + 8, KV_STAGE);
      tma_4d(sb + KV_STAGE + 32768, &P.wkv, 0, 64, nkv, 1, sb + B_FULLKV + 8);
      tma_2d(sb + KV_STAGE, &P.x128, 64, 256 * m256, sb + B_FULLKV + 8);
      tma_2d(sb + KV_STAGE + 16384, &P.x128, 64, 256 * m256 + 128, sb + B_FULLKV + 8);
    }
    asm volatile("fence.mbarrier_init.release.cluster;" ::: "memory");
  }
  #pragma unroll
  for (int w = 0; w < 3; w++)
    if (tid == 32 + 32 * w) {
      #pragma unroll
      for (uint32_t b = B_FULLKV + 16 + 192 * w; b < B_FULLKV + 208 + 192 * w && b < B_END; b += 8)
        mbar_init(sb + b, b < B_EMPTYKV ? 1 : b < B_EMPTY5 ? 12 : b < B_SD ? 4 : b < B_RX || b == B_W ? 2 : b == B_RX ? 8 : 1);
      if (w == 1) mbar_arrive(sb + B_FULL5 + 40);
      asm volatile("fence.mbarrier_init.release.cluster;" ::: "memory");
      fence_async_smem();
    }
  const int warp = __shfl_sync(~0u, tid >> 5, 0), wg = warp >> 2, wp = warp & 3;
  const int f = 16 * ((cr + 7) & 7) + 2 * (cr >> 3) + rank;
  const int ha = 4 * (nkv >> 1) + (nkv & 1);
  Scratch* const G = P.g;
  if ((sb & 0x3ffff) != SB0) asm volatile("trap;");
  __syncthreads();
  cluster_arrive();
  if (warp == 12) {
    TK(88 - 32);
    if (elect_one()) {
      #pragma unroll
      for (int s = NPRE0; s < NPRE; s++) {
        const uint32_t st = sb + s * KV_STAGE, fb = sb + B_FULLKV + 8 * s;
        mbar_expect_tx(fb, KV_STAGE);
        tma_4d(st + 32768, &P.wkv, 0, 64 * s, nkv, 1, fb);
        tma_2d(st, &P.x128, 64 * s, 256 * m256, fb);
        tma_2d(st + 16384, &P.x128, 64 * s, 256 * m256 + 128, fb);
      }
    }
    __syncwarp();
  }

  if (wg == 3) {
    asm volatile("setmaxnreg.dec.sync.aligned.u32 32;");
    cluster_wait();
    if (wp == 0) { TK(89 - 32); }
    const bool el = elect_one();
    const uint64_t ef = policy_evict_first(), en = policy_evict_normal();
    auto fetch_o = [&](const int t0, uint32_t so, uint32_t par) {
      const int sh = t0 & 1;
      uint32_t ready = 0;
      const bf16* base = G->o + (m128 * 16 + t0) * 8192 + rank * 4096;
      const bf16* hint = base + (lane & 3) * 1024 + 966 + (((j & 6) + ((lane >> 2) & ~sh)) & 7) * 16384 + 8 * sh * (~lane & 4);
      #pragma unroll 1
      for (int i = 2 - 2 * sh; i < 8; i += 1 + sh) {
        uint32_t it = 0;
        while ((~ready >> (4 * i) & (15 + 240 * sh)) && ++it < POLL_LIMIT) ready = __ballot_sync(~0u, ld32_rlx(hint) != ~0u);
        mbar_wait(sb + B_EMPTY5 + so, par);
        if (el) {
          bulk_g2s_mc(sb + so * 4096 + rank * 8192, base + (((j & 6) + i) & 7) * 16384, 8192, sb + B_FULLA + 2 * so + 8 * rank, ef);
          if (i == 2 - 2 * sh) TS(t0 == 0 ? (rank ? 4 : 12) : t0 == 3 ? (rank ? 31 : 10) : (rank ? 9 : 13));
        }
        so += 8;
        if (so == 48) { so = 0; par ^= 1; }
      }
    };
    if (wp == 0) {
      {
        #pragma unroll 1
        for (int kb = NPRE; kb < 16; kb++) {
          const uint32_t st = sb + (kb & 3) * KV_STAGE, fb = sb + B_FULLKV + 8 * (kb & 3);
          mbar_wait(fb + (B_EMPTYKV - B_FULLKV), ~(kb >> 2) & 1);
          if (el) {
            mbar_expect_tx(fb, KV_STAGE);
            tma_2d_mc(st + rank * 16384, &P.x128, 64 * kb, 256 * m256 + 128 * rank, fb);
            tma_4d_h(st + 32768, &P.wkv, 0, 64 * kb, nkv, 1, fb, ef);
          }
        }
        uint64_t ord = 0xf3120edcba987654ull;
        uint32_t so = 0, par = 1;
        #pragma unroll 1
        for (int i = 0; i < 16; i++) {
          const uint32_t st = sb + so * 4096, fb = sb + B_FULL5 + so;
          const int k0 = (64 * (uint32_t)ord + 128 * (j & 6)) & 960;
          mbar_wait(i < 5 ? sb + B_EMPTYKV + so - (i > 1 ? 8 : 0) : fb + (B_EMPTY5 - B_FULL5), par);
          if (el) {
            mbar_expect_tx(fb, R5);
            tma_2d_mc_h(st + rank * 8192, &P.x64, k0, 128 * m128 + 64 * rank, fb, i >= EFI ? ef : en);
            tma_3d_h(st + 16384, &P.wq, 0, k0, 2 * j, fb, ef);
          }
          ord >>= 4; so += 8;
          if (so == 40) { so = 0; par ^= 1; }
        }
        mbar_wait(sb + B_FULL5 + 8 + 8 * rank, 0); if (el) mbar_arrive(sb + B_R);
        mbar_wait(sb + B_FULL5 + 24 + 8 * rank, 0); if (el) mbar_arrive(sb + B_R1);
        #pragma unroll 1
        for (int i = 0; i < 19; i++) {
          const uint32_t fb = sb + B_FULL5 + so, fa = sb + B_FULLA + 2 * so, na = i == rank ? 0 : 8192;
          mbar_wait(fb + (B_EMPTY5 - B_FULL5), par);
          if (SLOT) { while (((uint32_t)clock() & (uint32_t)(SLOT - 1)) >= SLOTW) {} }
          if (el) {
            if (i < 16) {
              mbar_expect_tx(fb, 16384);
              const int row = i < 8 ? 128 * (((j & 6) + i) & 7) : 256 * (((j >> 1) + i) & 3) + 32 + 16 * (i & 4);
              tma_5d_h(sb + so * 4096 + 16384, &P.wo[i >> 3], 128 * j, row, fb, ef);
              tma_5d_h(sb + so * 4096 + 24576, &P.wo[i >> 3], 128 * j + 64, row, fb, ef);
              mbar_expect_tx(fa, na); mbar_expect_tx(fa + 8, na);
            } else mbar_arrive(sb + B_DR + 8 * (i - 16));
          }
          so += 8;
          if (so == 48) { so = 0; par ^= 1; }
        }
      }
    } else if (wp == 3) {
      const uint32_t t_start = (uint32_t)clock();
      if (el) {
        mbar_expect_tx(sb + B_W, 12288);
        #pragma unroll 1
        for (int i = 0; i < 6; i++) tma_2d(sb + (i == 0 ? OFF_WPHIK : i == 1 ? OFF_WPHIK1 : OFF_WPHIQ + 2048 * (i - 2)), &P.phi, 0, 32 * (i < 2 ? 2 * nkv + i : 4 * j + 2 * (i & 1) + ((i - 2) >> 1)), sb + B_W);
        prefetch_map(&P.x64); prefetch_map(&P.wq); prefetch_map(&P.wo[0]); prefetch_map(&P.wo[1]);
        prefetch_map(&P.wd); prefetch_map(&P.out); prefetch_map(&P.wg); prefetch_map(&P.wu);
      }
      #pragma unroll 1
      for (int i = 0; i < 8; i++) {
        if (lane < 16) st128_rlx(&G->cand[(m128 * 8 + i) * 512 + 64 * j + 4 * lane], ~0u, ~0u, ~0u, ~0u);
      }
      if (lane < 16) st128_rlx(&G->rstat[16 * c + lane], 0, 0, 0, 0);
      if (lane < 12) st128_rlx(&G->yacc[12 * c + lane], 0, 0, 0, 0);
      {
        const uint32_t nt = ld32_rlx(&G->epoch);
        if (lane < 8) { st128_rlx(&G->stats[16 * c + 2 * lane], nt, nt, nt, nt); st128_rlx(&G->csq[32 * c + 4 * lane], nt, nt, nt, nt); }
        if (lane < 4) { st128_rlx(&G->cskv[128 * nkv + 16 * m256 + 4 * lane], nt, nt, nt, nt); st128_rlx(&G->oset[16 * c + 4 * lane], nt, nt, nt, nt); }
      }
      if (lane < 2 * KR) st128_rlx(&G->key[(KR * j + (lane >> 1)) * 128 + m128 * 8 + 4 * (lane & 1)], 0, 0, 0, 0);
      if (c < 32) {
        #pragma unroll 1
        for (int i = lane; i < KVP; i += 32) st128_rlx(&G->kvacc[(ha + 2 * m256) * KVP + i], 0, 0, 0, 0);
      }
      fence_gpu();
      bar_arrive(NB_ZERO, 160);
      TS0_WRITE();
      if (el) {
        #pragma unroll 1
        for (int i = PF_I0; i < ((XP & 4) ? 0 : 30); i++) {
          while ((uint32_t)clock() - t_start < (uint32_t)(PF_T0 + PF_DT * (i - PF_I0) + PF_ST * f)) __nanosleep(64);
          if (i < 4) { bulk_prefetch(P.wqkv + (size_t)(256 * i + c) * (3 * DM), 2048); bulk_prefetch(P.wqkv + (size_t)(256 * i + 128 + c) * (3 * DM), 2048); }
          else if (i < 6) bulk_prefetch(P.wo_p + (size_t)c * 8192 + (i - 4) * 4096, 8192);
          else if ((TMASK >> (i - 6)) & 1) {
            const int k = i - 6;
            if (f < NFFN) {
              if (k < 16) {
                #pragma unroll 1
                for (int e = 0; e < 4; e++) tma_2d(sb + OFF_T, rank ? &P.tu : &P.tg, 32 * (f & ~1), 64 * k + 16 * e, sb + B_T);
              } else { tma_2d(sb + OFF_T, &P.td, 0, 256 * f + 32 * (k - 16), sb + B_T); tma_2d(sb + OFF_T, &P.td, 0, 256 * f + 32 * (k - 16) + 16, sb + B_T); }
            }
          }
          else if (!((PMASK >> (i - 6)) & 1)) {}
          else if (i < 22) bulk_prefetch(((i & 1) ? P.wu_p : P.wg_p) + (size_t)((i - 6) >> 1) * 458752 + c * 3584, 7168);
          else bulk_prefetch(P.wd_p + (size_t)(i - 22) * 458752 + c * 3584, 7168);
        }
      }
      __syncwarp();
      mbar_wait2(sb + B_OS, 0, sb + B_RX, 0);
      #pragma unroll 1
      for (int t0 = 0; t0 < 4; t0 += 3) fetch_o(t0, t0 ? 8 : 24, 0);
    } else {
      const int half = wp - 1;
      const uint32_t ep1 = ld32_rlx(&G->epoch) + 1, tg = ep1 & 3;
      {
        uint32_t it = 0;
        sts128(sb + OFF_ONES + half * 512 + lane * 16, 0x3f803f80u, 0x3f803f80u, 0x3f803f80u, 0x3f803f80u);
        if (lane < 9) { const uint32_t v = (lane & 1) ? 0 : 0x3f803f80u; sts128(sb + OFF_SEL + lane * 16, v, v, v, v); }
        auto reset_o = [&](int i0, int i1, uint32_t dt) {
          uint32_t t0 = (uint32_t)clock();
          #pragma unroll 1
          for (int i = i0; i < i1; i++) {
            if (!(XP & 2)) st128_rlx(G->o + (m128 * 16 + 2 * j + half) * 8192 + 256 * i + 8 * lane, ~0u, ~0u, ~0u, ~0u);
            while ((uint32_t)clock() - t0 < dt) __nanosleep(40);
            t0 += dt;
          }
        };
        mbar_wait(sb + B_S0, 0);
        reset_o(0, RS_N, RS_D1);
        bar_sync(NB_PUB, 192);
        const uint4* src = reinterpret_cast<const uint4*>(&G->stats[256 * m256 + 128 * half]) + lane;
        const uint4* srk = reinterpret_cast<const uint4*>(&G->cskv[128 * nkv]) + lane;
        uint4 v0, v1, vk;
        it = 0;
        do { v0 = ld128_rlx(src); v1 = ld128_rlx(src + 32); vk = ld128_rlx(srk); }
        while ((tag_bad(v0, tg) || tag_bad(v1, tg) || tag_bad(vk, tg)) && ++it < POLL_LIMIT);
        fence_acquire_gpu();
        if (half) put_colsums(sb + OFF_BXK, lane, untag(vk.x), untag(vk.y), untag(vk.z), untag(vk.w));
        #pragma unroll
        for (int i = 0; i < 2; i++) {
          const uint4 v = i ? v1 : v0;
          uint32_t hi, lo;
          split_bf16(-0.5f * untag(v.x), -0.5f * untag(v.z), hi, lo);
          const uint32_t h0 = __byte_perm(hi, hi, 0x1010), h1 = __byte_perm(hi, hi, 0x3232), l0 = __byte_perm(lo, lo, 0x1010), l1 = __byte_perm(lo, lo, 0x3232);
          const uint32_t a = sb + OFF_AXK + half * 2048 + i * 1024 + lane * 32;
          sts128(a, h0, l0, 0, 0); sts128(a + 16, h1, l1, 0, 0);
          sts64(sb + OFF_RS256 + half * 512 + i * 256 + lane * 8, v.y & ~3u, v.w & ~3u);
          if (half == (m128 & 1)) {
            const uint32_t aq = sb + OFF_AXQ + i * 1024 + lane * 32;
            sts128(aq, h0, l0, 0, 0); sts128(aq + 16, h1, l1, 0, 0);
            sts64(sb + OFF_RSQ + i * 256 + lane * 8, v.y & ~3u, v.w & ~3u);
          }
        }
        fence_async_smem();
        __syncwarp();
        if (el) { sts32(sb + OFF_EP, ep1); mbar_arrive(sb + B_AUX); }
        reset_o(RS_N, 32, RS_D2);
        fence_gpu();
        __syncwarp();
        if (el) { st32_rlx(&G->oset[16 * c + 8 * half], ep1); if (half) mbar_arrive(sb + B_AUXQ); }
        if (!half) {
          const uint4* src = reinterpret_cast<const uint4*>(&G->csq[128 * j]) + lane;
          uint4 v0, v1, v2, v3;
          do { v0 = ld128_rlx(src); v1 = ld128_rlx(src + DM / 4); v2 = ld128_rlx(src + DM / 2); v3 = ld128_rlx(src + 3 * DM / 4); }
          while ((tag_bad(v0, tg) || tag_bad(v1, tg) || tag_bad(v2, tg) || tag_bad(v3, tg)) && ++it < POLL_LIMIT);
          put_colsums(sb + OFF_BXQ, lane, (untag(v0.x) + untag(v1.x)) + (untag(v2.x) + untag(v3.x)), (untag(v0.y) + untag(v1.y)) + (untag(v2.y) + untag(v3.y)),
                      (untag(v0.z) + untag(v1.z)) + (untag(v2.z) + untag(v3.z)), (untag(v0.w) + untag(v1.w)) + (untag(v2.w) + untag(v3.w)));
          fence_async_smem();
          __syncwarp();
          if (el) mbar_arrive(sb + B_AUXQ);
        }
      }
      if (half == 0) {
        for (uint32_t it = 0; __any_sync(~0u, ld32_rlx(&G->oset[m128 * 128 + 8 * (lane & 15)]) != ep1) && it < POLL_LIMIT; it++) {}
        fence_acquire_gpu();
        if (el) mbar_arrive(sb + B_OS);
      }
      if (!half) {
        #pragma unroll 1
        for (int hh = 0; hh < 2; hh++) {
          const uint32_t src = sb + (1 + rank) * R5 + hh * 8192, fa = sb + B_FULLA + 16 + 16 * rank + 8 * hh;
          mbar_wait(fa, 0);
          mbar_wait(sb + B_UO + 8 * hh, 0);
          if (el) bulk_s2peer(mapa(src, rank ^ 1), src, 8192, mapa(fa, rank ^ 1));
        }
        fetch_o(1, 24, 1);
      }
      else if (f < NFFN_L) {
        mbar_wait2(sb + B_UO, 0, sb + B_UO + 8, 0);
        mbar_wait(sb + B_UO + 24, 0);
        uint32_t t0 = (uint32_t)clock();
        while ((uint32_t)clock() - t0 < (uint32_t)FF_T0) __nanosleep(32);
        t0 -= FF_DT;
        #pragma unroll 1
        for (int i = 0; i < 12; i++) {
          const int e = (FF_ORD >> (4 * i)) & 15;
          const uint32_t dst = sb + 16384 * ((FF_SLOT >> (4 * e)) & 15), fb = sb + B_F + 8 * e;
          if (i >= 2) mbar_wait(sb + B_WC + 8 * ((0x100066553244ull >> (4 * e)) & 15), 0);
          while ((uint32_t)clock() - t0 < (uint32_t)FF_DT) __nanosleep(32);
          t0 = (uint32_t)clock();
          if (i < 8) { TK(48 + i); }
          if (el) {
            mbar_expect_tx(fb, 16384);
            if (e >= 8) tma_3d_h(dst, &P.wd, 0, 32 * f, 4 * e - 32, fb, ef);
            else { tma_2d(dst, &P.wg, 32 * f, 128 * e, fb); tma_2d(dst + 8192, &P.wu, 32 * f, 128 * e, fb); }
          }
        }
      }
      __syncwarp();
    }
    if (wp & 1) {
      __syncwarp();
      mbar_wait(sb + B_OUT + 8 * (wp >> 1), 0);
      uint32_t t0 = (uint32_t)clock() + OUT_0;
      #pragma unroll 1
      for (int i = 0; i < 8; i++) {
        while ((int32_t)((uint32_t)clock() - t0) < 0) __nanosleep(20);
        if (el) tma_store_2d(&P.out, 128 * j + 64 * (i & 1), 128 * m128 + 32 * (wp & 2) + 8 * (i & 6), sb + OFF_OUT + (i & 1) * 16384 + (wp & 2) * 4096 + (i & 6) * 1024);
        t0 += OUT_D;
      }
      if (el) { bulk_commit(); bulk_wait_all(); fence_async_global(); mbar_arrive(sb + B_SD); TS(19); }
    }
    __syncwarp();
    cluster_arrive(); cluster_wait();
    return;
  }

  asm volatile("setmaxnreg.inc.sync.aligned.u32 160;");
  cluster_wait();
  const int t = tid & 127, g = lane >> 2;
  const uint32_t sa = (16 * wp + (lane & 15)) * 128 + (((lane >> 4) ^ (lane & 7)) << 4);

  if (wg == 2) {
    float s[2] = {0.f, 0.f}, s2[2] = {0.f, 0.f}, ck[8] = {0.f, 0.f, 0.f, 0.f, 0.f, 0.f, 0.f, 0.f}, cs[8] = {0.f, 0.f, 0.f, 0.f, 0.f, 0.f, 0.f, 0.f};
    const uint32_t ebr = mapa(sb + B_EMPTYKV, lane & 1), tg = (ld32_rlx(&G->epoch) + 1) & 3;
    auto addx = [&](const uint4 v) {
      const uint32_t w[4] = {v.x, v.y, v.z, v.w};
      #pragma unroll
      for (int e = 0; e < 4; e++) { const float a = bf_lo(w[e]), d = bf_hi(w[e]); s[0] += a; s[1] += d; s2[0] = fmaf(a, a, s2[0]); s2[1] = fmaf(d, d, s2[1]); }
    };
    auto addc = [&](const uint4 v, float (&o)[8]) {
      o[0] += bf_lo(v.x); o[1] += bf_hi(v.x); o[2] += bf_lo(v.y); o[3] += bf_hi(v.y); o[4] += bf_lo(v.z); o[5] += bf_hi(v.z); o[6] += bf_lo(v.w); o[7] += bf_hi(v.w);
    };
    {
      const uint32_t ra = (16 * nkv + (t >> 3)) * 128 + (t & 7) * 16;
      const uint32_t ca = 32768 + (m256 >> 2) * 8192 + (t >> 1) * 128 + (((2 * (m256 & 3) + (t & 1)) ^ ((t >> 1) & 7)) << 4);
      int rd = 0;
      mbar_wait(sb + B_S0, 0);
      #pragma unroll 1
      for (int kb = 0; kb < 10; kb++) {
        const uint32_t st = sb + (kb & 3) * KV_STAGE;
        mbar_wait(sb + B_FULLKV + 8 * (kb & 3), (kb >> 2) & 1);
        const uint4 x0 = lds128(st + ra), w0 = lds128(st + ca);
        if (!(XP & 1)) { addx(x0); addc(w0, ck); } else s[0] += __uint_as_float(x0.x ^ w0.x);
        __syncwarp();
        if (lane < 2) mbar_arrive_remote(ebr + 8 * (kb & 3), 1);
        if ((SKM >> kb) & 1) {
          if (rd) {
            mbar_wait(sb + B_G, (rd - 1) & 1);
            const uint32_t a = sb + OFF_G + (t >> 3) * 256 + (t & 7) * 16;
            const uint4 x1 = lds128(a), x2 = lds128(a + 128), w1 = lds128(sb + OFF_G + 4096 + t * 16), w2 = lds128(sb + OFF_G + 6144 + t * 16);
            addx(x1); addx(x2); addc(w1, ck); addc(w2, ck);
            bar_sync(NB_WG2, 128);
          }
          if (wp == 0 && elect_one()) {
            mbar_expect_tx(sb + B_G, 8192);
            if (rd < 3) {
              tma_2d(sb + OFF_G, &P.xs, 640 + 128 * rd, 256 * m256 + 16 * nkv, sb + B_G);
              tma_2d(sb + OFF_G + 4096, &P.ws, (1 + (m256 >> 2)) * DM + 64 * nkv + 16 * (m256 & 3), 640 + 128 * rd, sb + B_G);
            } else tma_2d(sb + OFF_G, &P.qs, 32 * (c & 31), 256 * (c >> 5), sb + B_G);
          }
          rd++;
        }
      }
    }
    TK(82);
    const uint32_t scr = sb + OFF_SCR + 128;
    float sx = s[0] + s[1], sq = s2[0] + s2[1];
    #pragma unroll
    for (int o = 1; o < 8; o <<= 1) { sx += __shfl_xor_sync(~0u, sx, o); sq += __shfl_xor_sync(~0u, sq, o); }
    float v = reduce8(ck, lane);
    v += __shfl_xor_sync(~0u, v, 2);
    if (!(lane & 2)) stsf(scr + (wp * 16 + 8 * (lane & 1) + (lane >> 2)) * 4, v);

    bar_sync(NB_ZERO, 160);
    if ((lane & 7) == 0) {
      const float mean = sx * (1.f / DM);
      st64_rlx(&G->stats[256 * m256 + 16 * nkv + (t >> 3)], tagw(mean, tg), tagw(rsqrtf(fmaxf(sq * (1.f / DM) - mean * mean, 0.f) + 1e-5f), tg));
    }
    if (wp == 1 && lane < 16) {
      const uint32_t a = scr + lane * 4;
      st32_rlx(&G->cskv[128 * nkv + 16 * m256 + lane], tagw((ldsf(a) + ldsf(a + 64)) + (ldsf(a + 128) + ldsf(a + 192)), tg));
    }
    __syncwarp();
    bar_arrive(NB_PUB, 192);
    TSW(23);
    const uint4 wv = ld128_keep(P.wr + t * 8);
    #pragma unroll 1
    for (int i = 0; i < 2; i++) {
      mbar_wait(sb + B_G, i ^ 1);
      const uint32_t a = sb + OFF_G + t * 16;
      const uint4 u0 = lds128(a), u1 = lds128(a + 2048), u2 = lds128(a + 4096), u3 = lds128(a + 6144);
      addc(u0, cs); addc(u1, cs); addc(u2, cs); addc(u3, cs);
      bar_sync(NB_WG2, 128);
      if (i == 0 && wp == 0 && elect_one()) { mbar_expect_tx(sb + B_G, 8192); tma_2d(sb + OFF_G, &P.qs, 32 * (c & 31), 256 * (c >> 5) + 128, sb + B_G); }
    }
    if (t == 0) mbar_arrive(sb + B_W);
    float sw = (bf_lo(wv.x) + bf_hi(wv.x)) + (bf_lo(wv.y) + bf_hi(wv.y)) + (bf_lo(wv.z) + bf_hi(wv.z)) + (bf_lo(wv.w) + bf_hi(wv.w));
    #pragma unroll
    for (int o = 16; o; o >>= 1) sw += __shfl_xor_sync(~0u, sw, o);
    if (lane == 0) stsf(sb + OFF_SUMWR + wp * 4, sw);
    if ((t >> 4) == j) {
      const uint32_t a = sb + OFF_WR + (t & 15) * 32;
      sts128(a, wv.x << 16, wv.x & 0xffff0000u, wv.y << 16, wv.y & 0xffff0000u);
      sts128(a + 16, wv.z << 16, wv.z & 0xffff0000u, wv.w << 16, wv.w & 0xffff0000u);
    }
    v = reduce8(cs, lane);
    stsf(scr + (wp * 32 + 8 * (lane & 3) + (lane >> 2)) * 4, v);
    bar_sync(NB_WG2, 128);
    if (wp == 0) {
      const uint32_t a = scr + lane * 4;
      st32_rlx(&G->csq[(c >> 5) * DM + 32 * (c & 31) + lane], tagw((ldsf(a) + ldsf(a + 128)) + (ldsf(a + 256) + ldsf(a + 384)), tg));
    }
  }

  uint32_t xr[32];
  {
    const bool isq = wg == 2;
    float acc[2][64];
    {
      const uint32_t emptyb = mapa(sb + (isq ? B_EMPTY5 : B_EMPTYKV), t & 1);
      auto correct = [&](uint32_t xa, uint32_t xb) {
        wg_fence();
        wgmma_sa_n128<0, 1, H0, H0>(acc[0], dlo(SB0, 0) + (xa >> 4), dlo(SB0, 0) + (xb >> 4));
        wgmma_sa_n128<0, 1, H0, H0>(acc[1], dlo(SB0, 0) + (xa >> 4) + 64, dlo(SB0, 0) + (xb >> 4));
        wg_commit();
      };
      if (!isq) {
        mbar_wait(sb + B_S0, 0);
        if (wg) mbar_wait(sb + B_FULLKV, 0);
        if (wg == 0) { TSW(2); }
        #pragma unroll 1
        for (int kb = 0; kb < 16; kb++) {
          if (!KT && wg == 0) { TK(kb); }
          const uint32_t da = dlo(SB0, 16) + wg * 1024 + (kb & 3) * (KV_STAGE >> 4), db = dlo(SB0 + 32768, 8192) + (kb & 3) * (KV_STAGE >> 4);
          wg_fence();
          #pragma unroll
          for (int k = 0; k < 4; k++) {
            wgmma_ss_n128<0, 1, H128, H128>(acc[0], da + 2 * k, db + 128 * k, k > 0 || kb != 0);
            wgmma_ss_n128<0, 1, H128, H128>(acc[1], da + 512 + 2 * k, db + 128 * k, k > 0 || kb != 0);
          }
          wg_commit();
          wg_wait<1>();
          if (kb > 0 && t < 2) mbar_arrive_remote(emptyb + 8 * ((kb - 1) & 3), kb > 10 ? 3 : 1);
          if (kb < 15) mbar_wait(sb + B_FULLKV + 8 * ((kb + 1) & 3), ((kb + 1) >> 2) & 1);
          if (kb == 15 - LAG && wg == 1) bar_sync(NB_WG01, 256);
        }
        bar_arrive(wg ? NB_QGO : NB_WG01, 256);
        mbar_wait(sb + B_AUX, 0);
        correct(OFF_AXK + wg * 2048, OFF_BXK);
        wg_wait<0>();
        if (t < 2) mbar_arrive_remote(emptyb + 24, 3);
        if (wg == 0) { TSW(3); }
        fence_regs(acc[0]); fence_regs(acc[1]);
      const uint32_t stg = sb + OFF_X + (1 - wg) * 24576;
      const uint32_t va = stg + 16384 + (16 * wp + (lane & 15)) * 64 + (((lane >> 4) ^ ((lane >> 1) & 3)) << 4);
      const uint32_t ra = sb + OFF_RS256 + (128 * wg + 16 * wp + g) * 4;
      const float rs[4] = {ldsf(ra), ldsf(ra + 32), ldsf(ra + 256), ldsf(ra + 288)};
      float p[2][16];
      uint32_t vf[16], kf[2][16];
      auto project = [&](const uint32_t (&f)[16], uint32_t db) {
        wg_fence();
        #pragma unroll
        for (int i = 0; i < 2; i++) {
          wgmma_rs_n32<1, H64>(p[i], f[8*i], f[8*i+1], f[8*i+2], f[8*i+3], db, 0);
          wgmma_ra_n32<1, H64>(p[i], f[8*i+4], f[8*i+5], f[8*i+6], f[8*i+7], db + 64);
        }
        wg_commit();
      };
      auto fold = [&](uint32_t (&f)[16], int col, float sc) {
        #pragma unroll
        for (int i = 0; i < 16; i++) {
          const float r = rs[2 * (i >> 3) + (i & 1)] * sc;
          f[i] = pack_bf16(acc[i >> 3][col + 2 * (i & 7)] * r, acc[i >> 3][col + 2 * (i & 7) + 1] * r);
          asm volatile("" : "+r"(f[i]));
        }
      };
      auto put_v = [&](const uint32_t (&f)[16]) {
        #pragma unroll
        for (int k = 0; k < 4; k++) stsm4((va ^ ((k & 1) << 5)) + (k >> 1) * 4096, f[4*k], f[4*k+1], f[4*k+2], f[4*k+3]);
      };
      KK(0);
      fold(vf, 48, 1.f);
      mbar_wait(sb + B_W, 0);
      fold(kf[0], 0, LOG2E);
      #pragma unroll
      for (int i = 0; i < 32; i++) p[i >> 4][i & 15] = acc[i >> 4][i & 15];
      project(kf[0], dlo(SB0 + OFF_WPHIK, 16));
      mbar_wait(sb + B_W, 0);
      KK(1);
      {
        uint32_t v0[16];
        fold(kf[1], 16, LOG2E);
        fold(v0, 32, 1.f);
        if (wg == 1) bar_sync(NB_DN, 256);
        put_v(v0);
      }
      wg_wait<0>();
      fence_regs(p[0]); fence_regs(p[1]);
      if (wg == 1) bar_arrive(NB_WG01, 256);
      KK(2);
      #pragma unroll 1
      for (int h = 0; h < 2; h++) {
        uint32_t ph[4][8];
        float rsum[2][4];
        dual_exp2<PRK & 1>(p[0], ph[0], ph[1]); dual_exp2<(PRK >> 1)>(p[1], ph[2], ph[3]);
        row_sums(rsum, ph, dlo(SB0 + OFF_SEL, 16));
        KK(3 + 6 * h);
        if (wg == 0 && h == 0) { bar_arrive(NB_DN, 256); bar_sync(NB_WG01, 256); }
        if (h == 1) {
          if (wg == 1) bar_sync(NB_DN, 256);
          put_v(vf);
        }
        wg_wait<0>();
        KK(4 + 6 * h);
        fence_regs(rsum[0]); fence_regs(rsum[1]);
        if (!(XP & 8) && __builtin_expect(__any_sync(~0u, !((rsum[0][0] + rsum[0][1]) + (rsum[0][2] + rsum[0][3]) + (rsum[1][0] + rsum[1][1]) + (rsum[1][2] + rsum[1][3]) < EXP_LIM)), 0)) {
          dual_exp2_shifted(p, ph);
          #pragma unroll
          for (int i = 0; i < 8; i++) {
            const uint32_t* f = &ph[i >> 1][i & 1];
            float a = (bf_lo(f[0]) + bf_hi(f[0])) + (bf_lo(f[2]) + bf_hi(f[2])) + (bf_lo(f[4]) + bf_hi(f[4])) + (bf_lo(f[6]) + bf_hi(f[6]));
            a += __shfl_xor_sync(~0u, a, 1);
            rsum[i >> 2][2 * (i & 1) + ((i >> 1) & 1)] = a + __shfl_xor_sync(~0u, a, 2);
          }
        }
        if (h == 0) project(kf[1], dlo(SB0 + OFF_WPHIK1, 16));
        normalize(ph, rsum);
        #pragma unroll
        for (int i = 0; i < 8; i++) {
          const uint32_t* f = &ph[i >> 1][4 * (i & 1)];
          stsm4(((stg + sa) ^ ((i & 3) << 5)) + (i >> 2) * 8192, f[0], f[1], f[2], f[3]);
        }
        KK(5 + 6 * h);
        fence_async_smem();
        KK(6 + 6 * h);
        if (wg != h) { KK(7 + 6 * h); }
        if (wg == h) {
          float kv[20];
          #pragma unroll
          for (int w = 0; w < 2; w++) {
            const uint32_t da = dlo(SB0 + OFF_X, 16) + (h ^ w ^ 1) * 1536, db = dlo(SB0 + OFF_X + 16384, OFF_ONES - OFF_X - 16384) - (h ^ w ^ 1) * (1536 * 65535);
            if (w) bar_sync(NB_ST, 256); else bar_sync(NB_L0 + h, 128);
            wg_fence();
            #pragma unroll
            for (int k = 0; k < 8; k++) {
              if (k == 0 && w == 0) wgmma_sz_n40<1, 1, H128, H64>(kv, da, db);
              else wgmma_sa_n40<1, 1, H128, H64>(kv, da + k * 128, db - k * (64 * 65535));
            }
            wg_commit();
          }
          float4* dst = &G->kvacc[(ha + 2 * h) * KVP + t];
          wg_wait<0>();
          fence_regs(kv);
          KK(7 + 6 * h);
          if (h == 0) bar_arrive(NB_DN, 256); else if (t < 2) { mbar_arrive_at(sb + B_EMPTY5 + 40, t, 2); if (t == 0) mbar_arrive(sb + B_KD); }
          kv[17] = kv[18];
          #pragma unroll
          for (int i = 0; i < 6; i++) red_add_f32x4(dst + 128 * i, kv[3*i], kv[3*i+1], kv[3*i+2], 1.f);
          TSW(29 + h);
        } else bar_arrive(NB_ST, 256);
        wg_wait<0>();
        KK(8 + 6 * h);
        fence_regs(p[0]); fence_regs(p[1]);
      }
      #pragma unroll
      for (int i = 0; i < 32; i++) asm volatile("mov.b32 %0, 0;" : "=r"(xr[i]));
      } else {
        uint32_t so = 0, po = 0, par = 0;
        mbar_wait(sb + B_FULL5, 0);
        bar_sync(NB_QGO, 256);
        TSW(11);
        #pragma unroll 1
        for (int kb = 0; kb < 16 - ML; kb++) {
          TK(16 + kb);
          const uint32_t da = dlo(SB0, 16) + so * 256, db = dlo(SB0 + 16384, 8192) + so * 256;
          #pragma unroll
          for (int k = 0; k < 4; k++) {
            wg_fence();
            wgmma_ss_n128<0, 1, H128, H128>(acc[0], da + 2 * k, db + 128 * k, k > 0 || kb != 0);
            wgmma_ss_n128<0, 1, H128, H128>(acc[1], da + 512 + 2 * k, db + 128 * k, k > 0 || kb != 0);
            wg_commit();
            if (k == 1 && kb > 0 && t < 2) mbar_arrive_remote(emptyb + po, 2);
            if (k == 3) {
              po = so; so += 8;
              if (so == 40) { so = 0; par ^= 1; }
              mbar_wait(sb + B_FULL5 + so, par);
            }
            if ((QW >> k) & 1) wg_wait<2>(); else wg_wait<1>();
          }
        }
        auto block = [&](const int kb, const int i) {
          wg_fence();
          #pragma unroll
          for (int k = 0; k < 4; k++) wgmma_sa_n128<0, 1, H128, H128>(acc[i], dlo(SB0, 16) + (kb % 5) * 2048 + 512 * i + 2 * k, dlo(SB0 + 16384, 8192) + (kb % 5) * 2048 + 128 * k);
          wg_commit();
        };
        auto hand_over = [&](const int i) {
          const uint32_t ta = sb + (1 + rank) * R5 + sa + i * 8192;
          #pragma unroll
          for (int k = 0; k < 4; k++) {
            const float* a = &acc[i][32 * (k >> 1) + 8 * (k & 1)];
            stsm4(ta ^ (k << 5), pack_bf16(a[0], a[1]), pack_bf16(a[2], a[3]), pack_bf16(a[4], a[5]), pack_bf16(a[6], a[7]));
          }
        };
        mbar_wait(sb + B_AUXQ, 0);
        correct(OFF_AXQ, OFF_BXQ);
        #pragma unroll
        for (int kb = 16 - ML; kb < 16; kb++) {
          TK(16 + kb);
          block(kb, 0);
          if (kb < 15) mbar_wait(sb + B_FULL5 + 8 * ((kb + 1) % 5), ((kb + 1) / 5) & 1);
          if (kb == 16 - ML) wg_wait<2>(); else if (!H3) wg_wait<1>();
          if (kb == 16 - ML && t < 2) mbar_arrive_remote(emptyb + 8 * ((kb - 1) % 5), 2);
        }
        mbar_wait(sb + B_RC, 0);
        block(16 - ML, 1);
        if (H2) { block(17 - ML, 1); wg_wait<2>(); } else wg_wait<1>();
        fence_regs(acc[0]);
        hand_over(0);
        if (!H2) block(17 - ML, 1);
        fence_async_smem();
        bar_arrive(NB_Q0, 256);
        TSW(1);
        #pragma unroll
        for (int kb = 18 - ML; kb <= 16; kb++) {
          wg_wait<1>();
          if (t < 2) mbar_arrive_remote(emptyb + 8 * ((kb - 2) % 5), 2);
          if (kb < 16) block(kb, 1);
        }
        mbar_wait(sb + B_RC + 8, 0);
        wg_wait<0>();
        if (t < 2) mbar_arrive_remote(emptyb, 2);
        TSW(8);
        fence_regs(acc[1]);
        hand_over(1);
        fence_async_smem();
        bar_arrive(NB_Q0 + 1, 256);
        #pragma unroll
        for (int i = 0; i < 32; i++) { const float* a = &acc[(i >> 3) & 1][16 + 32 * (i >> 4) + 2 * (i & 7)]; xr[i] = pack_bf16(a[0], a[1]); }
        TSW(26);
      }
    }
    float p[2][16];
    #pragma unroll
    for (int i = 0; i < 32; i++) asm volatile("mov.b32 %0, 0;" : "=f"(p[i >> 4][i & 15]));
    auto project_r = [&](int w) {
      wg_fence();
      #pragma unroll
      for (int h = 0; h < 2; h++) {
        wgmma_rs_n32<1, H64>(p[h], xr[8*h], xr[8*h+1], xr[8*h+2], xr[8*h+3], dlo(SB0 + OFF_WPHIQ, 16) + 128 * w, 0);
        wgmma_ra_n32<1, H64>(p[h], xr[8*h+4], xr[8*h+5], xr[8*h+6], xr[8*h+7], dlo(SB0 + OFF_WPHIQ, 16) + 128 * w + 64);
      }
      wg_commit();
    };
    auto capture = [&](const int i) {
      if (!i || CAPL != 2) mbar_wait(sb + (i ? B_R1 : B_R), 0);
      #pragma unroll
      for (int k = 0; k < 4; k++) ldsm4(((sb + (1 + rank) * R5 + wg * 8192 + sa) ^ (k << 5)) + i * 2 * R5, xr[16*i+4*k], xr[16*i+4*k+1], xr[16*i+4*k+2], xr[16*i+4*k+3]);
      const uint32_t one = (((xr[16*i] | xr[16*i+4]) | (xr[16*i+8] | xr[16*i+12])) & P.zero) + 1;
      if (lane == 0) mbar_arrive_at(sb + (i ? B_RX : B_RC + 8 * wg), i ? wg : rank, one);
    };
    const uint32_t rq = sb + OFF_RSQ + (16 * wp + g) * 4 + 256 * (wg & 1), rb = rq + 128 * (wg & 2);
    const float cc[2][2] = {{ldsf(rq) * LOG2E, ldsf(rq + 32) * LOG2E}, {ldsf(rb) * LOG2E, ldsf(rb + 32) * LOG2E}};
    {
      const uint4* src = reinterpret_cast<const uint4*>(&G->kvacc[(4 * j + wg) * KVP + t]);
      uint4 v[12];
      #pragma unroll
      for (int i = 0; i < 12; i++) v[i] = i < 6 || isq ? ld128_rlx(src + 128 * i) : make_uint4(0, 0, 0, 0x41000000u);
      if (isq) {
        project_r(2);
        wg_wait<0>();
        #pragma unroll
        for (int i = 0; i < 16; i++) xr[i] = xr[16 + i];
      } else {
        capture(0);
        if (CAPL == 0) capture(1);
      }
      #pragma unroll 1
      for (uint32_t it = 0; it < POLL_LIMIT; it++) {
        uint32_t bad = 0;
        #pragma unroll
        for (int i = 0; i < 12; i++) bad |= v[i].w ^ 0x41000000u;
        if (!__any_sync(~0u, bad != 0)) break;
        #pragma unroll
        for (int i = 0; i < 12; i++) if (i < 6 || isq) v[i] = ld128_rlx(src + 128 * i);
      }
      mbar_wait(sb + B_KD, 0);
      #pragma unroll
      for (int e = 0; e < 2; e++) {
        if (e == 0 || isq) {
          float f[18];
          #pragma unroll
          for (int i = 0; i < 6; i++) { f[3*i] = __uint_as_float(v[6*e+i].x); f[3*i+1] = __uint_as_float(v[6*e+i].y); f[3*i+2] = __uint_as_float(v[6*e+i].z); }
          const uint32_t ka = sb + OFF_KVZ + (wg + e) * 5120 + wp * 1280 + lane * 16;
          stsm4(ka, pack_bf16(f[0], f[1]), pack_bf16(f[2], f[3]), pack_bf16(f[4], f[5]), pack_bf16(f[6], f[7]));
          stsm4(ka + 512, pack_bf16(f[8], f[9]), pack_bf16(f[10], f[11]), pack_bf16(f[12], f[13]), pack_bf16(f[14], f[15]));
          stsm2(ka + 1024, pack_bf16(f[16], 1.f), pack_bf16(f[17], 1.f));
        }
      }
    }
    fence_async_smem();
    if (wg == 1) bar_arrive(NB_DN, 256);
    if (CAPL == 1 && !isq) capture(1);
    if (isq) mbar_wait(sb + B_OS, 0);
    TSW(wg == 0 ? 5 : wg == 1 ? 25 : 6);
    #pragma unroll 1
    for (int e = wg; e < wg + 1 + (wg >> 1); e++) {
      const int half = e >> 1, hh = e & 1, turn = e;
      const uint32_t ao = (1 + rank) * R5 + hh * 8192;
      uint32_t ph[4][8];
      #pragma unroll
      for (int i = 0; i < 32; i++) asm volatile("mov.b32 %0, 0;" : "=r"(ph[i >> 3][i & 7]));
      uint32_t shifted = 0;
      asm volatile("" : "+r"(shifted));
      #pragma unroll 1
      for (;;) {
        if (!(XP & 16) && shifted) dual_exp2_shifted(p, ph);
        uint32_t first = (shifted ^ 1) & !isq;
        asm volatile("" : "+r"(first));
        if (first) {
          if (wg == 0) { TSW(7); }
          bar_sync(NB_Q0 + wg, 256);
          const uint32_t da = dlo(SB0, 16) + (ao >> 4), db = dlo(SB0 + OFF_WPHIQ, 16);
          wg_fence();
          #pragma unroll
          for (int h = 0; h < 2; h++) {
            wgmma_ss_n32<0, 1, H128, H64>(p[h], da + 4 * h, db + 128 * h, 0);
            wgmma_sa_n32<0, 1, H128, H64>(p[h], da + 4 * h + 2, db + 128 * h + 64);
          }
          wg_commit();
          if (CAPL == 2) capture(1);
          wg_wait<0>();
        }
        fence_regs(p[0]); fence_regs(p[1]);
        uint32_t again = shifted;
        asm volatile("" : "+r"(again));
        if (again) break;
        float s2[4] = {0.f, 0.f, 0.f, 0.f};
        #pragma unroll
        for (int i = 0; i < 32; i++) { float& x = p[i >> 4][i & 15]; x *= cc[i >> 4][(i >> 1) & 1]; s2[i & 3] = fmaf(x, x, s2[i & 3]); }
        if (!__any_sync(~0u, !((s2[0] < ARG_LIM2) & (s2[1] < ARG_LIM2) & (s2[2] < ARG_LIM2) & (s2[3] < ARG_LIM2)))) break;
        shifted = 1;
      }
      if (e == 1 || e == 2) bar_sync(NB_TOK + e - 1, 256);
      TK(64 + 4 * turn);
      float ac[4][20];
      auto numer = [&](int h) {
        const uint32_t (*f)[8] = &ph[2 * h];
        const uint32_t db = dlo(SB0 + OFF_KVZ, 128) + (half ? e : h) * 320;
        wg_fence();
        #pragma unroll
        for (int i = 0; i < 2; i++) {
          wgmma_rz_n40<1, dhi(256, 0)>(ac[2*h+i], f[i][0], f[i][1], f[i][2], f[i][3], db + i * 160);
          wgmma_ra_n40<1, dhi(256, 0)>(ac[2*h+i], f[i][4], f[i][5], f[i][6], f[i][7], db + (i * 160 + 80));
        }
        wg_commit();
      };
      const uint32_t oa = (16 * wp + g) * 128 + (((lane & 3) ^ g) << 4);
      auto finish = [&](int h) {
        const float* ap = ac[2 * h]; const float* am = ac[2 * h + 1];
        const float ip0 = rcp(ap[17]), im0 = rcp(am[17]), ip1 = rcp(ap[19]), im1 = rcp(am[19]);
        const float d0 = rcp(fmaf(ap[16], ip0, fmaf(am[16], im0, 1e-6f))), d1 = rcp(fmaf(ap[18], ip1, fmaf(am[18], im1, 1e-6f)));
        const float a0 = ip0 * d0, b0 = im0 * d0, a1 = ip1 * d1, b1 = im1 * d1;
        #pragma unroll
        for (int r = 0; r < 2; r++) {
          const float a = r ? a1 : a0, b = r ? b1 : b0;
          uint32_t w[4];
          #pragma unroll
          for (int k = 0; k < 4; k++) w[k] = pack_bf16(fmaf(ap[4*k+2*r], a, am[4*k+2*r] * b), fmaf(ap[4*k+2*r+1], a, am[4*k+2*r+1] * b));
          const uint32_t off = (oa ^ ((half ? rank : h) << 6)) + r * 1024;
          st128_rlx(reinterpret_cast<uint8_t*>(G->o + (m128 * 16 + (half ? 2 * (j & 6) + 2 * hh + 1 : 2 * j)) * 8192 + (half ? h : hh) * 4096) + off, w[0], w[1], w[2], w[3]);
          if (!half) sts128(sb + ao + off, w[0], w[1], w[2], w[3]);
        }
      };
      if (!shifted) dual_exp2<true>(p[0], ph[0], ph[1]);
      numer(0);
      if (!shifted) dual_exp2<true>(p[1], ph[2], ph[3]);
      if (turn < 2) bar_arrive(NB_TOK + turn, 256);
      if (wg == 0) bar_sync(NB_DN, 256);
      numer(1);
      wg_wait<1>();
      TK(65 + 4 * turn);
      fence_regs(ac[0]); fence_regs(ac[1]);
      finish(0);
      wg_wait<0>();
      fence_regs(ac[2]); fence_regs(ac[3]);
      #pragma unroll
      for (int i = 0; i < 32; i++) asm volatile("mov.b32 %0, 0;" : "=f"(p[i >> 4][i & 15]));
      if (e == 2) project_r(3);
      finish(1);
      TK(66 + 4 * turn);
      if (!half) fence_async_smem();
      __syncwarp();
      if (lane == 0) mbar_arrive(sb + B_UO + 8 * e);
      wg_wait<0>();
      TK(67 + 4 * turn);
    }
    if (isq) cluster_arrive();
  }

  {
  int lane;
  asm volatile("mov.u32 %0, %%laneid;" : "=r"(lane));
  const int g = lane >> 2, q = lane & 3;
  if (wg < 2) {
    float h[64];
    {
      if (wg == 0) { TK(83); }
      #pragma unroll
      for (int i = 0; i < 32; i++) { h[2*i] = bf_lo(xr[i]); h[2*i+1] = bf_hi(xr[i]); }
      fence_regs(h);
      TK(80 + wg);
      const uint32_t emptyb = mapa(sb + B_EMPTY5, t & 1);
      uint32_t s = 1 + rank, ps = 0;
      mbar_wait2(sb + B_FULL5 + 8 * s, 1, sb + B_UO + 8 * wg, 0);
      if (wg == 0) { TSW(14); }
      #pragma unroll
      for (int i = 0; i < 16; i++) {
        if (wg == 1 && (i & 12) == TKW) { TK(84 + (i & 3)); }
        if (!KT && wg == 0) { TK(32 + i); }
        const uint32_t da = dlo(SB0, 16) + s * 2048 + wg * 512, db = dlo(SB0 + 16384, 8192) + s * 2048;
        wg_fence();
        #pragma unroll
        for (int k = 0; k < 4; k++) wgmma_sa_n128<0, 1, H128, H128>(h, da + k * 2, db + k * 128);
        wg_commit();
        const uint32_t ns = i ? (i + 2) % 6 : 2 - rank;
        const uint32_t b0 = sb + B_FULL5 + 8 * ns, p0 = (1 + (i + 2) / 6) & 1, b1 = sb + B_FULLA + 16 * ns + 8 * wg, p1 = ((i + 1) / 6) & 1;
        const bool here = i == 15 || mbar_test2(b0, p0, b1, p1);
        wg_wait<1>();
        if (!(((2 * REL + 1) >> i) & 1) && i < 14 && t < 2) mbar_arrive_remote(emptyb + 8 * ps, 1);
        if ((REL >> i) & 1) { wg_wait<0>(); if (t < 2) mbar_arrive_remote(emptyb + 8 * s, 1); }
        if (!here) mbar_wait2(b0, p0, b1, p1);
        ps = s; s = ns;
      }
    }
    cluster_arrive();
    float2 wr[16];
    #pragma unroll
    for (int i = 0; i < 16; i++) wr[i] = lds64f(sb + OFF_WR + 32 * i + 8 * q);
    const int r0 = 64 * wg + 16 * wp + g;
    float sum0, sum1, dot0, dot1, sq0, sq1;
    uint32_t redo = 0;
    asm volatile("" : "+r"(redo));
    #pragma unroll 1
    for (;;) {
    if (!(XP & 32) && redo) {
      wg_wait<0>();
      const int r = r0;
      #pragma unroll 1
      for (int n = 0; n < 16; n++) {
        const uint32_t* xp = reinterpret_cast<const uint32_t*>(P.x + (size_t)(128 * m128 + r) * DM + 128 * j + 8 * n) + q;
        const uint32_t x0 = xp[0], x1 = xp[4 * DM];
        float d0 = bf_lo(x0), d1 = bf_hi(x0), d2 = bf_lo(x1), d3 = bf_hi(x1);
        #pragma unroll 1
        for (int ks = 0; ks < 64; ks++) {
          const int kb = ks >> 2, kk = 16 * (ks & 3);
          const bf16* op = G->o + (m128 * 16 + kb) * 8192 + r * 64 + 2 * q;
          const int o0 = ((kk >> 3) ^ g) << 3;
          const uint16_t* w = reinterpret_cast<const uint16_t*>(P.wo_p) + (size_t)(((kb & 1) ? 256 * (kb >> 2) + 32 * (kb & 2) + 32 + 4 * (kk & 32) : 64 * kb + 2 * (kk & 32)) + ((kk & 16) >> 2) + 8 * q) * DM + 128 * j + 8 * n + g;
          const uint32_t b0 = w[0] | (w[DM] << 16), b1 = w[2 * DM] | (w[3 * DM] << 16);
          uint32_t a0, a1, a2, a3, it = 0;
          do { a0 = ld32_rlx(op + o0); a1 = ld32_rlx(op + 512 + o0); a2 = ld32_rlx(op + (o0 ^ 8)); a3 = ld32_rlx(op + 512 + (o0 ^ 8)); }
          while (max(max(a0, a1), max(a2, a3)) == ~0u && ++it < POLL_LIMIT);
          __syncwarp();
          mma16816(d0, d1, d2, d3, a0, a1, a2, a3, b0, b1);
        }
        #pragma unroll
        for (int i = 0; i < 60; i++) h[i] = h[i + 4];
        h[60] = d0; h[61] = d1; h[62] = d2; h[63] = d3;
      }
    }
    wg_wait<0>();
    fence_regs(h);
    if (wg == 0) { TSW(16); }
    sum0 = 0.f, sum1 = 0.f, dot0 = 0.f, dot1 = 0.f, sq0 = 0.f, sq1 = 0.f;
    #pragma unroll
    for (int i = 0; i < 16; i++) {
      sum0 += h[4*i] + h[4*i+1]; sum1 += h[4*i+2] + h[4*i+3];
      sq0 = fmaf(h[4*i], h[4*i], fmaf(h[4*i+1], h[4*i+1], sq0)); sq1 = fmaf(h[4*i+2], h[4*i+2], fmaf(h[4*i+3], h[4*i+3], sq1));
      dot0 = fmaf(h[4*i], wr[i].x, fmaf(h[4*i+1], wr[i].y, dot0)); dot1 = fmaf(h[4*i+2], wr[i].x, fmaf(h[4*i+3], wr[i].y, dot1));
    }
    if (!__any_sync(~0u, !redo & (h[0] != h[0] | h[2] != h[2]))) break;
    redo = 1;
    }
    float4* const rs = &G->rstat[128 * m128 + r0];
    {
      const bool up = q & 2;
      float a = up ? sum1 : sum0, b = up ? sq1 : sq0, d = up ? dot1 : dot0;
      a += __shfl_xor_sync(~0u, up ? sum0 : sum1, 2); b += __shfl_xor_sync(~0u, up ? sq0 : sq1, 2); d += __shfl_xor_sync(~0u, up ? dot0 : dot1, 2);
      a += __shfl_xor_sync(~0u, a, 1); b += __shfl_xor_sync(~0u, b, 1); d += __shfl_xor_sync(~0u, d, 1);
      if ((q & 1) == 0) red_add_f32x4(rs + 4 * q, a, b, d, 1.f);
    }
    if (TRKL == 0) bar_arrive(NB_G2E, 384);
    if (wg == 0) { TSW(24); }
    bar_sync(NB_WG01, 256);
    uint32_t wa[8][4][4];
    const uint32_t wb = sb + 16384 * (((uint32_t)FF_SLOT >> (4 * warp)) & 15) + ((lane & 7) + ((lane >> 4) << 3)) * 64 + ((((lane >> 3) & 1) ^ ((lane >> 1) & 3)) << 4);
    auto getw = [&](int ks) {
      #pragma unroll
      for (int m = 0; m < 4; m++) ldsm4t((wb ^ ((m & 1) << 5)) + (m >> 1) * 8192 + ks * 1024, wa[ks][m][0], wa[ks][m][1], wa[ks][m][2], wa[ks][m][3]);
    };
    if (GPRE && f < NFFN_L) mbar_wait(sb + B_F + 8 * warp, 0);
    if (warp == 7) { TK(60); }
    #pragma unroll
    for (int ks = 0; ks < GPRE; ks++) getw(ks);
    float rstd[2], bm[2];
    uint32_t best;
    {
      const float2 swa = lds64f(sb + OFF_SUMWR), swb = lds64f(sb + OFF_SUMWR + 8);
      const float sw = (swa.x + swa.y) + (swb.x + swb.y);
      uint4 a[2]; uint32_t it = 0, key[2];
      do { a[0] = ld128_rlx(rs); a[1] = ld128_rlx(rs + 8); } while (__any_sync(~0u, (a[0].w & a[1].w) != 0x41000000u) && ++it < POLL_LIMIT);
      #pragma unroll
      for (int i = 0; i < 2; i++) {
        const float mean = __uint_as_float(a[i].x) * (1.f / DM);
        rstd[i] = rsqrtf(fmaxf(__uint_as_float(a[i].y) * (1.f / DM) - mean * mean, 0.f) + 1e-5f);
        bm[i] = -mean * rstd[i];
        const uint32_t rr = __float_as_uint(fmaf(__uint_as_float(a[i].z), rstd[i], sw * bm[i]));
        key[i] = ((rr ^ ((uint32_t)((int32_t)rr >> 31) | 0x80000000u)) & ~2047u) | (2047 - 128 * m128 - r0 - 8 * i);
      }
      asm volatile("redux.sync.max.u32 %0, %1, 0xffffffff;" : "=r"(best) : "r"(max(key[0], key[1])));
    }
    if (TRKL == 2) bar_arrive(NB_G2E, 384);
    if (TRKL == 3 && wg == 0) bar_arrive(NB_G2E, 256);
    if (wg == 0) { TSW(17); }
    const int slot = m128 * 8 + warp, win = ~best & 15;
    if (lane < KR) st32_rlx(&G->key[(KR * j + lane) * 128 + slot], best);
    if ((win & 7) == g) {
      const bool up = win & 8;
      const float ra = up ? rstd[1] : rstd[0], rb = up ? bm[1] : bm[0];
      uint32_t x[16];
      #pragma unroll
      for (int i = 0; i < 16; i++) x[i] = pack_bf16(fmaf(up ? h[4*i+2] : h[4*i], ra, rb), fmaf(up ? h[4*i+3] : h[4*i+1], ra, rb));
      #pragma unroll
      for (int i = 0; i < 4; i++) st128_rlx(&G->cand[slot * 512 + 64 * j + 16 * i + 4 * q], x[4*i], x[4*i+1], x[4*i+2], x[4*i+3]);
    }
    __syncwarp();
    if (TRKL == 1) bar_arrive(NB_G2E, 384);
    if (wg == 0) { TSW(27); }
    {
      const float a0 = 1.f + rstd[0], b0 = bm[0], a1 = 1.f + rstd[1], b1 = bm[1];
      #pragma unroll
      for (int k = 0; k < 8; k++)
        stsm4(((sb + OFF_OUT + wg * 8192 + sa) ^ ((k & 3) << 5)) + (k >> 2) * 16384,
              pack_bf16(fmaf(h[8*k], a0, b0), fmaf(h[8*k+1], a0, b0)),     pack_bf16(fmaf(h[8*k+2], a1, b1), fmaf(h[8*k+3], a1, b1)),
              pack_bf16(fmaf(h[8*k+4], a0, b0), fmaf(h[8*k+5], a0, b0)),   pack_bf16(fmaf(h[8*k+6], a1, b1), fmaf(h[8*k+7], a1, b1)));
      fence_async_smem();
      __syncwarp();
      if (lane == 0) mbar_arrive(sb + B_OUT + 8 * wg);
    }
    if (wg == 0) { TSW(28); }
    {
      if (!GPRE && f < NFFN_L) mbar_wait(sb + B_F + 8 * warp, 0);
      #pragma unroll
      for (int ks = GPRE; ks < GRES; ks++) getw(ks);
      if (wg == 0) { TSW(15); }
      bar_sync(NB_XS, 384);
      uint4 xs[4];
      #pragma unroll
      for (int i = 0; i < 4; i++) xs[i] = lds128(sb + OFF_XSEL + 256 * warp + 64 * i + 16 * q);
      float d[4][4];
      #pragma unroll
      for (int ks = 0; ks < 8; ks++) {
        if (ks >= 1 && GRES + ks - 1 < 8) getw(GRES + ks - 1);
        #pragma unroll
        for (int m = 0; m < 4; m++) {
          if (ks == 0) { d[m][0] = 0.f; d[m][1] = 0.f; d[m][2] = 0.f; d[m][3] = 0.f; }
          mma16816(d[m][0], d[m][1], d[m][2], d[m][3], wa[ks][m][0], wa[ks][m][1], wa[ks][m][2], wa[ks][m][3],
                   (ks & 1) ? xs[ks >> 1].z : xs[ks >> 1].x, (ks & 1) ? xs[ks >> 1].w : xs[ks >> 1].y);
        }
      }
      if (q == 0) {
        #pragma unroll
        for (int m = 0; m < 8; m++) stsf(sb + OFF_GU + (8 * m + g) * 48 + 4 * warp, d[m >> 1][2 * (m & 1)]);
      }
      bar_arrive(NB_ACT, 384);
    }
    {
      const uint32_t ky = __float_as_uint(ldsf(sb + OFF_KEY));
      const int row = 2047 - (ky & 2047) - 128 * m128;
      if ((uint32_t)row < 128u) {
        const int l = tid >> 3, vi = (j & 1) + ((lane >> 2) & 1), e = 3 * vi + q - 4 * (j & 1);
        const float kr = __uint_as_float((ky & ~2047u) ^ ((ky >> 31) ? 0x80000000u : 0xfffff800u));
        const int col = 32 * (l & 3) + 16 * (e & 1) + 4 * (e & 2) + (l >> 2);
        const float sg = rcp(1.f + ex2(-LOG2E * kr));
        const uint32_t base = __float_as_uint(ldsf(sb + OFF_OUT + (col >> 6) * 16384 + row * 128 + ((((col >> 3) ^ row) & 7) << 4) + 2 * (col & 6)));
        const float4* yp = &G->yacc[(q * 3 + vi) * 128 + 32 * (j >> 1) + l];
        uint32_t it = 0;
        uint4 v;
        mbar_wait(sb + B_SD, 0);
        do { v = ld128_rlx(yp); } while (__any_sync(~0u, __uint_as_float(v.w) != (float)(NFFN / 4)) && ++it < POLL_LIMIT);
        float y0 = __uint_as_float(v.x), y1 = __uint_as_float(v.y), y2 = __uint_as_float(v.z);
        #pragma unroll
        for (int o = 1; o < 4; o <<= 1) { y0 += __shfl_xor_sync(~0u, y0, o); y1 += __shfl_xor_sync(~0u, y1, o); y2 += __shfl_xor_sync(~0u, y2, o); }
        if (q < 3 && (uint32_t)e < 4u)
          P.out_p[(size_t)(128 * m128 + row) * DM + 128 * j + col] = __float2bfloat16(fmaf(q == 0 ? y0 : q == 1 ? y1 : y2, sg, (col & 1) ? bf_hi(base) : bf_lo(base)));
      }
      if (c == 0 && tid == 0) st32_rlx(&G->epoch, __float_as_uint(ldsf(sb + OFF_EP)));
      if (warp == 0) { TSW(22); }
      if (wg == 0) { TDUMP(); }
    }
  }
  if (wg == 2) {
    uint32_t wf[16][2][4];
    {
      const uint32_t wb = sb + OFF_S + 16384 * (wp & 1) + ((lane & 7) + ((lane >> 4) << 3)) * 128 + ((((lane >> 3) & 1) ^ (lane & 7)) << 4);
      if (f < NFFN_L) mbar_wait(sb + B_WD + 8 * wp, 0);
      if (wp == 0) { TK(61); }
      #pragma unroll
      for (int i = 0; i < 32; i++) ldsm4t((wb ^ (((i >> 1) & 3) << 5)) + (i >> 3) * 4096 + (i & 1) * 2048, wf[i >> 1][i & 1][0], wf[i >> 1][i & 1][1], wf[i >> 1][i & 1][2], wf[i >> 1][i & 1][3]);
      fence_async_smem();
      __syncwarp();
      if (lane == 0) mbar_arrive(sb + B_WC + 8 * wp);
      if (wp == 0) { TK(62); }
    }
    bar_sync(NB_G2E, TRKL == 3 ? 256 : 384);
    {
      uint32_t cur = 0;
      uint4 v;
      #pragma unroll 1
      for (uint32_t it = 0; it < POLL_LIMIT; it++) {
        const uint4 kx = ld128_rlx(&G->key[(KSEL & (8 * KR - 1)) * 128 + 4 * lane]);
        v = ld128_rlx(&G->cand[((~cur >> 4) & 127) * 512 + 4 * t]);
        uint32_t best;
        asm volatile("redux.sync.max.u32 %0, %1, 0xffffffff;" : "=r"(best) : "r"(max(max(kx.x, kx.y), max(kx.z, kx.w))));
        if (!__any_sync(~0u, min(min(kx.x, kx.y), min(kx.z, kx.w)) == 0 || v.w == ~0u) && best == cur) break;
        cur = best;
      }
      sts128(sb + OFF_XSEL + 16 * t, v.x, v.y, v.z, v.w);
      sts32(sb + OFF_KEY, cur);
      bar_arrive(NB_XS, 384);
      TSW(18);
      bar_sync(NB_ACT, 384);
    }
    float gu[2];
    #pragma unroll
    for (int i = 0; i < 2; i++) {
      const uint4 v0 = lds128(sb + OFF_GU + (32 * i + lane) * 48), v1 = lds128(sb + OFF_GU + (32 * i + lane) * 48 + 16);
      gu[i] = ((__uint_as_float(v0.x) + __uint_as_float(v0.y)) + (__uint_as_float(v0.z) + __uint_as_float(v0.w))) +
              ((__uint_as_float(v1.x) + __uint_as_float(v1.y)) + (__uint_as_float(v1.z) + __uint_as_float(v1.w)));
    }
    const float act = gu[0] * gu[1] * rcp(1.f + ex2(-LOG2E * gu[0]));
    const uint32_t ap = pack_bf16(act, __shfl_down_sync(~0u, act, 1));
    uint32_t bf[4];
    #pragma unroll
    for (int i = 0; i < 4; i++) bf[i] = __shfl_sync(~0u, ap, 2 * q + 8 * i);
    TSW(20);
    float d[16][4];
    #pragma unroll
    for (int k = 0; k < 2; k++)
      #pragma unroll
      for (int i = 0; i < 16; i++) {
        if (k == 0) { d[i][0] = 0.f; d[i][1] = 0.f; d[i][2] = 0.f; d[i][3] = 0.f; }
        mma16816(d[i][0], d[i][1], d[i][2], d[i][3], wf[i][k][0], wf[i][k][1], wf[i][k][2], wf[i][k][3], bf[2*k], bf[2*k+1]);
      }
    float y[9];
    #pragma unroll
    for (int e = 0; e < 8; e++) {
      const int n = 2 * (e & 4) + (e & 1);
      const float lo = (q & 1) ? d[n + 2][e & 2] : d[n][e & 2], hi = (q & 1) ? d[n + 6][e & 2] : d[n + 4][e & 2];
      y[e] = (q & 2) ? hi : lo;
    }
    y[8] = 0.f;
    if (f < NFFN) {
      #pragma unroll
      for (int i = 0; i < 3; i++) red_add_f32x4(&G->yacc[((f & 3) * 3 + i) * 128 + t], y[3*i], y[3*i+1], y[3*i+2], 1.f);
    }
    TSW(21);
  }
  }
  cluster_wait();
}

typedef CUresult (*EncodeFn)(CUtensorMap*, CUtensorMapDataType, cuuint32_t, void*, const cuuint64_t*, const cuuint64_t*,
                             const cuuint32_t*, const cuuint32_t*, CUtensorMapInterleave, CUtensorMapSwizzle,
                             CUtensorMapL2promotion, CUtensorMapFloatOOBfill);

void make_map(EncodeFn enc, CUtensorMap* m, const void* p, int n, const cuuint64_t* dims, const cuuint64_t* str, const cuuint32_t* box,
              CUtensorMapSwizzle sw, CUtensorMapL2promotion promo) {
  cuuint32_t es[5] = {1, 1, 1, 1, 1};
  enc(m, CU_TENSOR_MAP_DATA_TYPE_BFLOAT16, n, const_cast<void*>(p), dims, str, box, es, CU_TENSOR_MAP_INTERLEAVE_NONE, sw, promo,
      CU_TENSOR_MAP_FLOAT_OOB_FILL_NONE);
}
void map2(EncodeFn enc, CUtensorMap* m, const void* p, uint64_t cols, uint64_t rows, uint32_t bc, uint32_t br, CUtensorMapSwizzle sw,
          CUtensorMapL2promotion promo) {
  const cuuint64_t dims[2] = {cols, rows}, str[1] = {cols * 2};
  const cuuint32_t box[2] = {bc, br};
  make_map(enc, m, p, 2, dims, str, box, sw, promo);
}
void map3(EncodeFn enc, CUtensorMap* m, const void* p, uint64_t cols, uint64_t rows, uint32_t br, uint32_t nb) {
  const cuuint64_t dims[3] = {64, rows, cols / 64}, str[2] = {cols * 2, 128};
  const cuuint32_t box[3] = {64, br, nb};
  make_map(enc, m, p, 3, dims, str, box, CU_TENSOR_MAP_SWIZZLE_128B, CU_TENSOR_MAP_L2_PROMOTION_L2_128B);
}

}

extern "C" void kernel_launch(void* const* d_in, const int* in_sizes, int n_in, void* d_out, int out_size) {
  (void)in_sizes; (void)n_in; (void)out_size;
  static EncodeFn enc = nullptr;
  static void* o_ptr = nullptr;
  if (!enc) {
    void* f = nullptr; cudaDriverEntryPointQueryResult qr;
    cudaGetDriverEntryPoint("cuTensorMapEncodeTiled", &f, cudaEnableDefault, &qr);
    enc = (EncodeFn)f;
    cudaGetSymbolAddress(&o_ptr, g_scr);
    cudaFuncSetAttribute(fused_kernel, cudaFuncAttributeMaxDynamicSharedMemorySize, SMEM_BYTES);
  }
  const bf16* x = (const bf16*)d_in[0];
  const bf16* wqkv = (const bf16*)d_in[1];
  const bf16* wphi = (const bf16*)d_in[2];
  const bf16* wo = (const bf16*)d_in[3];
  const bf16* wr = (const bf16*)d_in[5];
  const bf16* wgate = (const bf16*)d_in[6];
  const bf16* wup = (const bf16*)d_in[7];
  const bf16* wdown = (const bf16*)d_in[8];
  Params P;
  const CUtensorMapSwizzle S128 = CU_TENSOR_MAP_SWIZZLE_128B, S64 = CU_TENSOR_MAP_SWIZZLE_64B;
  const CUtensorMapL2promotion L128 = CU_TENSOR_MAP_L2_PROMOTION_L2_128B, L256 = CU_TENSOR_MAP_L2_PROMOTION_L2_256B,
                               L64 = CU_TENSOR_MAP_L2_PROMOTION_L2_64B;
  map2(enc, &P.x128, x, DM, SEQ, 64, 128, S128, L256);
  map2(enc, &P.x64, x, DM, SEQ, 64, 64, S128, L128);
  {
    const cuuint64_t dims[4] = {64, DM, 16, 3}, str[3] = {6 * DM, 128, 2 * DM};
    const cuuint32_t box[4] = {64, 64, 1, 2};
    make_map(enc, &P.wkv, wqkv, 4, dims, str, box, S128, L128);
  }
  map3(enc, &P.wq, wqkv, 3 * DM, DM, 64, 2);
  for (int i = 0; i < 2; i++) {
    const cuuint64_t dims[5] = {DM, (cuuint64_t)(DM - 94 - 64 * i), 4, 4, 2}, str[4] = {2 * DM, 16 * DM, 4 * DM, (cuuint64_t)(128 * DM) << i};
    const cuuint32_t box[5] = {64, 2, 4, 4, 2};
    make_map(enc, &P.wo[i], wo, 5, dims, str, box, S128, L128);
  }
  map3(enc, &P.wd, wdown, DM, FF, 32, 4);
  map2(enc, &P.wg, wgate, FF, DM, 32, 128, S64, L64);
  map2(enc, &P.wu, wup, FF, DM, 32, 128, S64, L64);
  map2(enc, &P.tg, wgate, FF, DM, 8, 16, CU_TENSOR_MAP_SWIZZLE_NONE, L128);
  map2(enc, &P.tu, wup, FF, DM, 8, 16, CU_TENSOR_MAP_SWIZZLE_NONE, L128);
  map2(enc, &P.td, wdown, 128, FF * 8, 8, 16, CU_TENSOR_MAP_SWIZZLE_NONE, L256);
  map2(enc, &P.xs, x, DM, SEQ, 128, 16, CU_TENSOR_MAP_SWIZZLE_NONE, L256);
  map2(enc, &P.ws, wqkv, 3 * DM, DM, 16, 128, CU_TENSOR_MAP_SWIZZLE_NONE, L128);
  map2(enc, &P.qs, wqkv, 3 * DM, DM, 32, 128, CU_TENSOR_MAP_SWIZZLE_NONE, L64);
  map2(enc, &P.out, d_out, DM, SEQ, 64, 16, S128, L128);
  map2(enc, &P.phi, wphi, 32, 1024, 32, 32, S64, L64);
  P.x = x; P.wqkv = wqkv; P.wo_p = wo; P.wd_p = wdown; P.wg_p = wgate; P.wu_p = wup; P.wr = wr; P.out_p = (bf16*)d_out; P.g = (Scratch*)o_ptr; P.zero = 0;

  cudaLaunchConfig_t cfg = {};
  cfg.gridDim = dim3(128); cfg.blockDim = dim3(512); cfg.dynamicSmemBytes = SMEM_BYTES; cfg.stream = cudaStreamPerThread;
  cudaLaunchAttribute at[1];
  at[0].id = cudaLaunchAttributeClusterDimension; at[0].val.clusterDim.x = 2; at[0].val.clusterDim.y = 1; at[0].val.clusterDim.z = 1;
  cfg.attrs = at; cfg.numAttrs = 1;
  cudaLaunchKernelEx(&cfg, fused_kernel, P);
}
```

```cpp
#include <cuda_runtime.h>
#include <cuda.h>
#include <cuda_bf16.h>
#include <stdint.h>

namespace {

typedef __nv_bfloat16 bf16;

__device__ __forceinline__ uint32_t smem_u32(const void* p){ return (uint32_t)__cvta_generic_to_shared(p); }
__device__ __forceinline__ void mbar_init(uint32_t bar, uint32_t cnt){ asm volatile("mbarrier.init.shared::cta.b64 [%0], %1;"::"r"(bar),"r"(cnt):"memory"); }
__device__ __forceinline__ void mbar_expect_tx(uint32_t bar, uint32_t bytes){ asm volatile("mbarrier.arrive.expect_tx.shared::cta.b64 _, [%0], %1;"::"r"(bar),"r"(bytes):"memory"); }
__device__ __forceinline__ void mbar_arrive(uint32_t bar){ asm volatile("mbarrier.arrive.shared::cta.b64 _, [%0];"::"r"(bar):"memory"); }
__device__ __forceinline__ uint32_t mapa(uint32_t addr, uint32_t cta){ uint32_t r; asm volatile("mapa.shared::cluster.u32 %0, %1, %2;":"=r"(r):"r"(addr),"r"(cta)); return r; }
__device__ __forceinline__ void mbar_arrive_at(uint32_t bar, uint32_t cta, uint32_t cnt){
  asm volatile("{\n.reg .b32 ra;\nmapa.shared::cluster.u32 ra, %0, %1;\nmbarrier.arrive.shared::cluster.b64 _, [ra], %2;\n}\n"::"r"(bar),"r"(cta),"r"(cnt):"memory"); }
__device__ __forceinline__ void mbar_arrive_remote(uint32_t cluster_addr, uint32_t cnt){
  asm volatile("mbarrier.arrive.shared::cluster.b64 _, [%0], %1;"::"r"(cluster_addr),"r"(cnt):"memory"); }
__device__ __forceinline__ void mbar_wait(uint32_t bar, uint32_t parity){
  asm volatile("{\n.reg .pred p;\n.reg .u32 c;\nmov.u32 c, 0;\nLW:\nmbarrier.try_wait.parity.shared::cta.b64 p, [%0], %1;\n@p bra LD;\nadd.u32 c, c, 1;\nsetp.lt.u32 p, c, 2000000;\n@p bra LW;\ntrap;\nLD:\n}\n"::"r"(bar),"r"(parity):"memory"); }
__device__ __forceinline__ void mbar_wait2(uint32_t bar0, uint32_t par0, uint32_t bar1, uint32_t par1){
  asm volatile("{\n.reg .pred p, q;\n.reg .u32 c;\nmov.u32 c, 0;\nLW:\nmbarrier.try_wait.parity.shared::cta.b64 p, [%0], %1;\nmbarrier.try_wait.parity.shared::cta.b64 q, [%2], %3;\nand.pred p, p, q;\n@p bra LD;\nadd.u32 c, c, 1;\nsetp.lt.u32 p, c, 2000000;\n@p bra LW;\ntrap;\nLD:\n}\n"::"r"(bar0),"r"(par0),"r"(bar1),"r"(par1):"memory"); }
__device__ __forceinline__ bool mbar_test2(uint32_t bar0, uint32_t par0, uint32_t bar1, uint32_t par1){
  uint32_t r;
  asm volatile("{\n.reg .pred p, q;\nmbarrier.test_wait.parity.shared::cta.b64 p, [%1], %2;\nmbarrier.test_wait.parity.shared::cta.b64 q, [%3], %4;\nand.pred p, p, q;\nselp.u32 %0, 1, 0, p;\n}\n":"=r"(r):"r"(bar0),"r"(par0),"r"(bar1),"r"(par1):"memory");
  return r; }
__device__ __forceinline__ void tma_2d(uint32_t dst, const CUtensorMap* m, int c0, int c1, uint32_t bar){
  asm volatile("cp.async.bulk.tensor.2d.shared::cluster.global.mbarrier::complete_tx::bytes [%0], [%1, {%3, %4}], [%2];"::"r"(dst),"l"(m),"r"(bar),"r"(c0),"r"(c1):"memory"); }
__device__ __forceinline__ void tma_2d_mc(uint32_t dst, const CUtensorMap* m, int c0, int c1, uint32_t bar){
  asm volatile("cp.async.bulk.tensor.2d.shared::cluster.global.mbarrier::complete_tx::bytes.multicast::cluster [%0], [%1, {%3, %4}], [%2], %5;"::"r"(dst),"l"(m),"r"(bar),"r"(c0),"r"(c1),"h"((uint16_t)3):"memory"); }
__device__ __forceinline__ void tma_2d_mc_h(uint32_t dst, const CUtensorMap* m, int c0, int c1, uint32_t bar, uint64_t pol){
  asm volatile("cp.async.bulk.tensor.2d.shared::cluster.global.mbarrier::complete_tx::bytes.multicast::cluster.L2::cache_hint [%0], [%1, {%3, %4}], [%2], %5, %6;"::"r"(dst),"l"(m),"r"(bar),"r"(c0),"r"(c1),"h"((uint16_t)3),"l"(pol):"memory"); }
__device__ __forceinline__ void tma_4d(uint32_t dst, const CUtensorMap* m, int c0, int c1, int c2, int c3, uint32_t bar){
  asm volatile("cp.async.bulk.tensor.4d.shared::cluster.global.mbarrier::complete_tx::bytes [%0], [%1, {%3, %4, %5, %6}], [%2];"::"r"(dst),"l"(m),"r"(bar),"r"(c0),"r"(c1),"r"(c2),"r"(c3):"memory"); }
__device__ __forceinline__ uint64_t policy_evict_first(){ uint64_t p; asm volatile("createpolicy.fractional.L2::evict_first.b64 %0, 1.0;":"=l"(p)); return p; }
__device__ __forceinline__ uint64_t policy_evict_normal(){ uint64_t p; asm("createpolicy.fractional.L2::evict_normal.b64 %0, 1.0;":"=l"(p)); return p; }
__device__ __forceinline__ void tma_3d_h(uint32_t dst, const CUtensorMap* m, int c0, int c1, int c2, uint32_t bar, uint64_t pol){
  asm volatile("cp.async.bulk.tensor.3d.shared::cluster.global.mbarrier::complete_tx::bytes.L2::cache_hint [%0], [%1, {%3, %4, %5}], [%2], %6;"::"r"(dst),"l"(m),"r"(bar),"r"(c0),"r"(c1),"r"(c2),"l"(pol):"memory"); }
__device__ __forceinline__ void tma_4d_h(uint32_t dst, const CUtensorMap* m, int c0, int c1, int c2, int c3, uint32_t bar, uint64_t pol){
  asm volatile("cp.async.bulk.tensor.4d.shared::cluster.global.mbarrier::complete_tx::bytes.L2::cache_hint [%0], [%1, {%3, %4, %5, %6}], [%2], %7;"::"r"(dst),"l"(m),"r"(bar),"r"(c0),"r"(c1),"r"(c2),"r"(c3),"l"(pol):"memory"); }
__device__ __forceinline__ void red_add_f32x4(float4* p, float x, float y, float z, float w){ asm volatile("red.relaxed.gpu.global.add.v4.f32 [%0], {%1,%2,%3,%4};"::"l"(p),"f"(x),"f"(y),"f"(z),"f"(w):"memory"); }
__device__ __forceinline__ void tma_5d_h(uint32_t dst, const CUtensorMap* m, int c0, int c1, uint32_t bar, uint64_t pol){
  asm volatile("cp.async.bulk.tensor.5d.shared::cluster.global.mbarrier::complete_tx::bytes.L2::cache_hint [%0], [%1, {%3, %4, 0, 0, 0}], [%2], %5;"::"r"(dst),"l"(m),"r"(bar),"r"(c0),"r"(c1),"l"(pol):"memory"); }
__device__ __forceinline__ void tma_store_2d(const CUtensorMap* m, int c0, int c1, uint32_t src){
  asm volatile("cp.async.bulk.tensor.2d.global.shared::cta.bulk_group [%0, {%2, %3}], [%1];"::"l"(m),"r"(src),"r"(c0),"r"(c1):"memory"); }
__device__ __forceinline__ void bulk_commit(){ asm volatile("cp.async.bulk.commit_group;":::"memory"); }
__device__ __forceinline__ void bulk_wait_all(){ asm volatile("cp.async.bulk.wait_group 0;":::"memory"); }
__device__ __forceinline__ void fence_async_global(){ asm volatile("fence.proxy.async.global;":::"memory"); }
__device__ __forceinline__ bool elect_one(){ uint32_t p; asm volatile("{\n.reg .pred P;\nelect.sync _|P, 0xffffffff;\nselp.b32 %0, 1, 0, P;\n}\n":"=r"(p)); return p; }
__device__ __forceinline__ void bulk_prefetch(const void* p, uint32_t bytes){
  asm volatile("cp.async.bulk.prefetch.L2.global [%0], %1;"::"l"(p),"r"(bytes):"memory"); }
__device__ __forceinline__ void bulk_s2peer(uint32_t dst_cluster, uint32_t src, uint32_t bytes, uint32_t bar_cluster){
  asm volatile("cp.async.bulk.shared::cluster.shared::cta.mbarrier::complete_tx::bytes [%0], [%1], %2, [%3];"::"r"(dst_cluster),"r"(src),"r"(bytes),"r"(bar_cluster):"memory"); }
__device__ __forceinline__ void bulk_g2s_mc(uint32_t dst, const void* src, uint32_t bytes, uint32_t bar, uint64_t pol){
  asm volatile("cp.async.bulk.shared::cluster.global.mbarrier::complete_tx::bytes.multicast::cluster.L2::cache_hint [%0], [%1], %2, [%3], %4, %5;"::"r"(dst),"l"(src),"r"(bytes),"r"(bar),"h"((uint16_t)3),"l"(pol):"memory"); }
__device__ __forceinline__ void prefetch_map(const CUtensorMap* m){ asm volatile("prefetch.tensormap [%0];"::"l"(m):"memory"); }
__device__ __forceinline__ void fence_async_smem(){ asm volatile("fence.proxy.async.shared::cta;":::"memory"); }
__device__ __forceinline__ void fence_acquire_gpu(){ asm volatile("fence.acquire.gpu;":::"memory"); }
__device__ __forceinline__ void fence_gpu(){ asm volatile("fence.acq_rel.gpu;":::"memory"); }
__device__ __forceinline__ void wg_fence(){ asm volatile("wgmma.fence.sync.aligned;":::"memory"); }
__device__ __forceinline__ void wg_commit(){ asm volatile("wgmma.commit_group.sync.aligned;":::"memory"); }
template<int N> __device__ __forceinline__ void wg_wait(){ asm volatile("wgmma.wait_group.sync.aligned %0;"::"n"(N):"memory"); }
template<int N> __device__ __forceinline__ void fence_regs(float (&d)[N]){
  #pragma unroll
  for(int i=0;i<N;i++) asm volatile("":"+f"(d[i])::"memory"); }
__device__ __forceinline__ void bar_sync(int id, int n){ asm volatile("bar.sync %0, %1;"::"r"(id),"r"(n):"memory"); }
__device__ __forceinline__ void bar_arrive(int id, int n){ asm volatile("bar.arrive %0, %1;"::"r"(id),"r"(n):"memory"); }
__device__ __forceinline__ void cluster_arrive(){ asm volatile("barrier.cluster.arrive.relaxed.aligned;":::"memory"); }
__device__ __forceinline__ void cluster_wait(){ asm volatile("barrier.cluster.wait.aligned;":::"memory"); }
__host__ __device__ constexpr uint32_t dlo(uint32_t addr, uint32_t lbo){ return (addr >> 4) | ((lbo >> 4) << 16); }
__host__ __device__ constexpr uint32_t dhi(uint32_t sbo, uint32_t sw){ return (sbo >> 4) | (sw << 30); }
constexpr uint32_t H128 = dhi(1024, 1), H64 = dhi(512, 2), H0 = dhi(128, 0);
__device__ __forceinline__ uint32_t pack_bf16(float lo, float hi){ uint32_t r; asm("cvt.rn.bf16x2.f32 %0, %1, %2;":"=r"(r):"f"(hi),"f"(lo)); return r; }
__device__ __forceinline__ float bf_lo(uint32_t v){ return __uint_as_float(v<<16); }
__device__ __forceinline__ float bf_hi(uint32_t v){ return __uint_as_float(v&0xffff0000u); }
__device__ __forceinline__ float ex2(float x){ float r; asm("ex2.approx.ftz.f32 %0, %1;":"=f"(r):"f"(x)); return r; }
__device__ __forceinline__ float rcp(float x){ float r; asm("rcp.approx.ftz.f32 %0, %1;":"=f"(r):"f"(x)); return r; }
__device__ __forceinline__ void stsm4(uint32_t addr, uint32_t a, uint32_t b, uint32_t c, uint32_t d){
  asm volatile("stmatrix.sync.aligned.m8n8.x4.shared.b16 [%0], {%1,%2,%3,%4};"::"r"(addr),"r"(a),"r"(b),"r"(c),"r"(d)); }
__device__ __forceinline__ void stsm2(uint32_t addr, uint32_t a, uint32_t b){
  asm volatile("stmatrix.sync.aligned.m8n8.x2.shared.b16 [%0], {%1,%2};"::"r"(addr),"r"(a),"r"(b)); }
__device__ __forceinline__ void mma16816(float& d0, float& d1, float& d2, float& d3, uint32_t a0, uint32_t a1, uint32_t a2, uint32_t a3, uint32_t b0, uint32_t b1){
  asm volatile("mma.sync.aligned.m16n8k16.row.col.f32.bf16.bf16.f32 {%0,%1,%2,%3}, {%4,%5,%6,%7}, {%8,%9}, {%0,%1,%2,%3};"
               : "+f"(d0), "+f"(d1), "+f"(d2), "+f"(d3) : "r"(a0), "r"(a1), "r"(a2), "r"(a3), "r"(b0), "r"(b1)); }
__device__ __forceinline__ uint32_t transpose8(uint32_t a){ uint32_t r; asm volatile("movmatrix.sync.aligned.m8n8.trans.b16 %0, %1;":"=r"(r):"r"(a)); return r; }
__device__ __forceinline__ void ldsm4(uint32_t addr, uint32_t& a, uint32_t& b, uint32_t& c, uint32_t& d){
  asm volatile("ldmatrix.sync.aligned.m8n8.x4.shared.b16 {%0,%1,%2,%3}, [%4];":"=r"(a),"=r"(b),"=r"(c),"=r"(d):"r"(addr):"memory"); }
__device__ __forceinline__ void ldsm4t(uint32_t addr, uint32_t& a, uint32_t& b, uint32_t& c, uint32_t& d){
  asm volatile("ldmatrix.sync.aligned.m8n8.x4.trans.shared.b16 {%0,%1,%2,%3}, [%4];":"=r"(a),"=r"(b),"=r"(c),"=r"(d):"r"(addr):"memory"); }
__device__ __forceinline__ void sts32(uint32_t a, uint32_t v){ asm volatile("st.shared.b32 [%0], %1;"::"r"(a),"r"(v):"memory"); }
__device__ __forceinline__ void stsf(uint32_t a, float v){ asm volatile("st.shared.f32 [%0], %1;"::"r"(a),"f"(v):"memory"); }
__device__ __forceinline__ void sts64(uint32_t a, uint32_t x, uint32_t y){ asm volatile("st.shared.v2.b32 [%0], {%1,%2};"::"r"(a),"r"(x),"r"(y):"memory"); }
__device__ __forceinline__ void sts128(uint32_t a, uint32_t x, uint32_t y, uint32_t z, uint32_t w){ asm volatile("st.shared.v4.b32 [%0], {%1,%2,%3,%4};"::"r"(a),"r"(x),"r"(y),"r"(z),"r"(w):"memory"); }
__device__ __forceinline__ float ldsf(uint32_t a){ float v; asm volatile("ld.shared.f32 %0, [%1];":"=f"(v):"r"(a):"memory"); return v; }
__device__ __forceinline__ float2 lds64f(uint32_t a){ float2 v; asm volatile("ld.shared.v2.f32 {%0,%1}, [%2];":"=f"(v.x),"=f"(v.y):"r"(a):"memory"); return v; }
__device__ __forceinline__ uint4 lds128(uint32_t a){ uint4 v; asm volatile("ld.shared.v4.u32 {%0,%1,%2,%3}, [%4];":"=r"(v.x),"=r"(v.y),"=r"(v.z),"=r"(v.w):"r"(a):"memory"); return v; }
__device__ __forceinline__ uint4 ld128_keep(const void* p){ uint4 v; asm volatile("ld.global.v4.u32 {%0,%1,%2,%3}, [%4];":"=r"(v.x),"=r"(v.y),"=r"(v.z),"=r"(v.w):"l"(p):"memory"); return v; }
__device__ __forceinline__ uint4 ld128_rlx(const void* p){ uint4 v; asm volatile("ld.relaxed.gpu.global.v4.u32 {%0,%1,%2,%3}, [%4];":"=r"(v.x),"=r"(v.y),"=r"(v.z),"=r"(v.w):"l"(p):"memory"); return v; }
__device__ __forceinline__ uint32_t ld32_rlx(const void* p){ uint32_t v; asm volatile("ld.relaxed.gpu.global.u32 %0, [%1];":"=r"(v):"l"(p):"memory"); return v; }
__device__ __forceinline__ void st128_rlx(void* p, uint32_t x, uint32_t y, uint32_t z, uint32_t w){ asm volatile("st.relaxed.gpu.global.v4.u32 [%0], {%1,%2,%3,%4};"::"l"(p),"r"(x),"r"(y),"r"(z),"r"(w):"memory"); }
__device__ __forceinline__ void st64_rlx(void* p, uint32_t x, uint32_t y){ asm volatile("st.relaxed.gpu.global.v2.u32 [%0], {%1,%2};"::"l"(p),"r"(x),"r"(y):"memory"); }
__device__ __forceinline__ void st32_rlx(void* p, uint32_t x){ asm volatile("st.relaxed.gpu.global.u32 [%0], %1;"::"l"(p),"r"(x):"memory"); }
__device__ __forceinline__ uint32_t tagw(float x, uint32_t t){ return (__float_as_uint(x) & ~3u) | t; }
__device__ __forceinline__ float untag(uint32_t w){ return __uint_as_float(w & ~3u); }

template<int TA, int TB, uint32_t HA, uint32_t HB> __device__ __forceinline__ void wgmma_ss_n128(float (&d)[64], uint32_t da, uint32_t db, int scale_d){
  asm volatile("{\n.reg .pred p;\n.reg .b64 a, b;\nsetp.ne.b32 p, %70, 0;\nmov.b64 a, {%64, %68};\nmov.b64 b, {%65, %69};\n"
  "wgmma.mma_async.sync.aligned.m64n128k16.f32.bf16.bf16 {%0, %1, %2, %3, %4, %5, %6, %7, %8, %9, %10, %11, %12, %13, %14, %15, %16, %17, %18, %19, %20, %21, %22, %23, %24, %25, %26, %27, %28, %29, %30, %31, %32, %33, %34, %35, %36, %37, %38, %39, %40, %41, %42, %43, %44, %45, %46, %47, %48, %49, %50, %51, %52, %53, %54, %55, %56, %57, %58, %59, %60, %61, %62, %63}, a, b, p, 1, 1, %66, %67;\n}\n"
  : "+f"(d[0]), "+f"(d[1]), "+f"(d[2]), "+f"(d[3]), "+f"(d[4]), "+f"(d[5]), "+f"(d[6]), "+f"(d[7]), "+f"(d[8]), "+f"(d[9]), "+f"(d[10]), "+f"(d[11]), "+f"(d[12]), "+f"(d[13]), "+f"(d[14]), "+f"(d[15]), "+f"(d[16]), "+f"(d[17]), "+f"(d[18]), "+f"(d[19]), "+f"(d[20]), "+f"(d[21]), "+f"(d[22]), "+f"(d[23]), "+f"(d[24]), "+f"(d[25]), "+f"(d[26]), "+f"(d[27]), "+f"(d[28]), "+f"(d[29]), "+f"(d[30]), "+f"(d[31]), "+f"(d[32]), "+f"(d[33]), "+f"(d[34]), "+f"(d[35]), "+f"(d[36]), "+f"(d[37]), "+f"(d[38]), "+f"(d[39]), "+f"(d[40]), "+f"(d[41]), "+f"(d[42]), "+f"(d[43]), "+f"(d[44]), "+f"(d[45]), "+f"(d[46]), "+f"(d[47]), "+f"(d[48]), "+f"(d[49]), "+f"(d[50]), "+f"(d[51]), "+f"(d[52]), "+f"(d[53]), "+f"(d[54]), "+f"(d[55]), "+f"(d[56]), "+f"(d[57]), "+f"(d[58]), "+f"(d[59]), "+f"(d[60]), "+f"(d[61]), "+f"(d[62]), "+f"(d[63])
  : "r"(da), "r"(db), "n"(TA), "n"(TB), "n"(HA), "n"(HB), "r"(scale_d));
}
template<int TA, int TB, uint32_t HA, uint32_t HB> __device__ __forceinline__ void wgmma_sa_n128(float (&d)[64], uint32_t da, uint32_t db){
  asm volatile("{\n.reg .pred p;\n.reg .b64 a, b;\nsetp.ne.b32 p, 1, 0;\nmov.b64 a, {%64, %68};\nmov.b64 b, {%65, %69};\n"
  "wgmma.mma_async.sync.aligned.m64n128k16.f32.bf16.bf16 {%0, %1, %2, %3, %4, %5, %6, %7, %8, %9, %10, %11, %12, %13, %14, %15, %16, %17, %18, %19, %20, %21, %22, %23, %24, %25, %26, %27, %28, %29, %30, %31, %32, %33, %34, %35, %36, %37, %38, %39, %40, %41, %42, %43, %44, %45, %46, %47, %48, %49, %50, %51, %52, %53, %54, %55, %56, %57, %58, %59, %60, %61, %62, %63}, a, b, p, 1, 1, %66, %67;\n}\n"
  : "+f"(d[0]), "+f"(d[1]), "+f"(d[2]), "+f"(d[3]), "+f"(d[4]), "+f"(d[5]), "+f"(d[6]), "+f"(d[7]), "+f"(d[8]), "+f"(d[9]), "+f"(d[10]), "+f"(d[11]), "+f"(d[12]), "+f"(d[13]), "+f"(d[14]), "+f"(d[15]), "+f"(d[16]), "+f"(d[17]), "+f"(d[18]), "+f"(d[19]), "+f"(d[20]), "+f"(d[21]), "+f"(d[22]), "+f"(d[23]), "+f"(d[24]), "+f"(d[25]), "+f"(d[26]), "+f"(d[27]), "+f"(d[28]), "+f"(d[29]), "+f"(d[30]), "+f"(d[31]), "+f"(d[32]), "+f"(d[33]), "+f"(d[34]), "+f"(d[35]), "+f"(d[36]), "+f"(d[37]), "+f"(d[38]), "+f"(d[39]), "+f"(d[40]), "+f"(d[41]), "+f"(d[42]), "+f"(d[43]), "+f"(d[44]), "+f"(d[45]), "+f"(d[46]), "+f"(d[47]), "+f"(d[48]), "+f"(d[49]), "+f"(d[50]), "+f"(d[51]), "+f"(d[52]), "+f"(d[53]), "+f"(d[54]), "+f"(d[55]), "+f"(d[56]), "+f"(d[57]), "+f"(d[58]), "+f"(d[59]), "+f"(d[60]), "+f"(d[61]), "+f"(d[62]), "+f"(d[63])
  : "r"(da), "r"(db), "n"(TA), "n"(TB), "n"(HA), "n"(HB));
}
template<int TA, int TB, uint32_t HA, uint32_t HB> __device__ __forceinline__ void wgmma_sa_n40(float (&d)[20], uint32_t da, uint32_t db){
  asm volatile("{\n.reg .pred p;\n.reg .b64 a, b;\nsetp.ne.b32 p, 1, 0;\nmov.b64 a, {%20, %24};\nmov.b64 b, {%21, %25};\n"
  "wgmma.mma_async.sync.aligned.m64n40k16.f32.bf16.bf16 {%0, %1, %2, %3, %4, %5, %6, %7, %8, %9, %10, %11, %12, %13, %14, %15, %16, %17, %18, %19}, a, b, p, 1, 1, %22, %23;\n}\n"
  : "+f"(d[0]), "+f"(d[1]), "+f"(d[2]), "+f"(d[3]), "+f"(d[4]), "+f"(d[5]), "+f"(d[6]), "+f"(d[7]), "+f"(d[8]), "+f"(d[9]), "+f"(d[10]), "+f"(d[11]), "+f"(d[12]), "+f"(d[13]), "+f"(d[14]), "+f"(d[15]), "+f"(d[16]), "+f"(d[17]), "+f"(d[18]), "+f"(d[19])
  : "r"(da), "r"(db), "n"(TA), "n"(TB), "n"(HA), "n"(HB));
}
template<int TA, int TB, uint32_t HA, uint32_t HB> __device__ __forceinline__ void wgmma_sz_n40(float (&d)[20], uint32_t da, uint32_t db){
  asm volatile("{\n.reg .pred p;\n.reg .b64 a, b;\nsetp.ne.b32 p, 0, 0;\nmov.b64 a, {%20, %24};\nmov.b64 b, {%21, %25};\n"
  "wgmma.mma_async.sync.aligned.m64n40k16.f32.bf16.bf16 {%0, %1, %2, %3, %4, %5, %6, %7, %8, %9, %10, %11, %12, %13, %14, %15, %16, %17, %18, %19}, a, b, p, 1, 1, %22, %23;\n}\n"
  : "=f"(d[0]), "=f"(d[1]), "=f"(d[2]), "=f"(d[3]), "=f"(d[4]), "=f"(d[5]), "=f"(d[6]), "=f"(d[7]), "=f"(d[8]), "=f"(d[9]), "=f"(d[10]), "=f"(d[11]), "=f"(d[12]), "=f"(d[13]), "=f"(d[14]), "=f"(d[15]), "=f"(d[16]), "=f"(d[17]), "=f"(d[18]), "=f"(d[19])
  : "r"(da), "r"(db), "n"(TA), "n"(TB), "n"(HA), "n"(HB));
}
template<int TA, int TB, uint32_t HA, uint32_t HB> __device__ __forceinline__ void wgmma_sa_n32(float (&d)[16], uint32_t da, uint32_t db){
  asm volatile("{\n.reg .pred p;\n.reg .b64 a, b;\nsetp.ne.b32 p, 1, 0;\nmov.b64 a, {%16, %20};\nmov.b64 b, {%17, %21};\n"
  "wgmma.mma_async.sync.aligned.m64n32k16.f32.bf16.bf16 {%0, %1, %2, %3, %4, %5, %6, %7, %8, %9, %10, %11, %12, %13, %14, %15}, a, b, p, 1, 1, %18, %19;\n}\n"
  : "+f"(d[0]), "+f"(d[1]), "+f"(d[2]), "+f"(d[3]), "+f"(d[4]), "+f"(d[5]), "+f"(d[6]), "+f"(d[7]), "+f"(d[8]), "+f"(d[9]), "+f"(d[10]), "+f"(d[11]), "+f"(d[12]), "+f"(d[13]), "+f"(d[14]), "+f"(d[15])
  : "r"(da), "r"(db), "n"(TA), "n"(TB), "n"(HA), "n"(HB));
}
template<int TA, int TB, uint32_t HA, uint32_t HB> __device__ __forceinline__ void wgmma_ss_n32(float (&d)[16], uint32_t da, uint32_t db, int scale_d){
  asm volatile("{\n.reg .pred p;\n.reg .b64 a, b;\nsetp.ne.b32 p, %22, 0;\nmov.b64 a, {%16, %20};\nmov.b64 b, {%17, %21};\n"
  "wgmma.mma_async.sync.aligned.m64n32k16.f32.bf16.bf16 {%0, %1, %2, %3, %4, %5, %6, %7, %8, %9, %10, %11, %12, %13, %14, %15}, a, b, p, 1, 1, %18, %19;\n}\n"
  : "+f"(d[0]), "+f"(d[1]), "+f"(d[2]), "+f"(d[3]), "+f"(d[4]), "+f"(d[5]), "+f"(d[6]), "+f"(d[7]), "+f"(d[8]), "+f"(d[9]), "+f"(d[10]), "+f"(d[11]), "+f"(d[12]), "+f"(d[13]), "+f"(d[14]), "+f"(d[15])
  : "r"(da), "r"(db), "n"(TA), "n"(TB), "n"(HA), "n"(HB), "r"(scale_d));
}
template<int TB, uint32_t HB> __device__ __forceinline__ void wgmma_ra_n32(float (&d)[16], uint32_t a0, uint32_t a1, uint32_t a2, uint32_t a3, uint32_t db){
  asm volatile("{\n.reg .pred p;\n.reg .b64 a, b;\nsetp.ne.b32 p, 1, 0;\nmov.b64 b, {%20, %22};\n"
  "wgmma.mma_async.sync.aligned.m64n32k16.f32.bf16.bf16 {%0, %1, %2, %3, %4, %5, %6, %7, %8, %9, %10, %11, %12, %13, %14, %15}, {%16,%17,%18,%19}, b, p, 1, 1, %21;\n}\n"
  : "+f"(d[0]), "+f"(d[1]), "+f"(d[2]), "+f"(d[3]), "+f"(d[4]), "+f"(d[5]), "+f"(d[6]), "+f"(d[7]), "+f"(d[8]), "+f"(d[9]), "+f"(d[10]), "+f"(d[11]), "+f"(d[12]), "+f"(d[13]), "+f"(d[14]), "+f"(d[15])
  : "r"(a0), "r"(a1), "r"(a2), "r"(a3), "r"(db), "n"(TB), "n"(HB));
}
template<int TB, uint32_t HB> __device__ __forceinline__ void wgmma_rs_n32(float (&d)[16], uint32_t a0, uint32_t a1, uint32_t a2, uint32_t a3, uint32_t db, int scale_d){
  asm volatile("{\n.reg .pred p;\n.reg .b64 a, b;\nsetp.ne.b32 p, %23, 0;\nmov.b64 b, {%20, %22};\n"
  "wgmma.mma_async.sync.aligned.m64n32k16.f32.bf16.bf16 {%0, %1, %2, %3, %4, %5, %6, %7, %8, %9, %10, %11, %12, %13, %14, %15}, {%16,%17,%18,%19}, b, p, 1, 1, %21;\n}\n"
  : "+f"(d[0]), "+f"(d[1]), "+f"(d[2]), "+f"(d[3]), "+f"(d[4]), "+f"(d[5]), "+f"(d[6]), "+f"(d[7]), "+f"(d[8]), "+f"(d[9]), "+f"(d[10]), "+f"(d[11]), "+f"(d[12]), "+f"(d[13]), "+f"(d[14]), "+f"(d[15])
  : "r"(a0), "r"(a1), "r"(a2), "r"(a3), "r"(db), "n"(TB), "n"(HB), "r"(scale_d));
}
template<int TB, uint32_t HB> __device__ __forceinline__ void wgmma_ra_n40(float (&d)[20], uint32_t a0, uint32_t a1, uint32_t a2, uint32_t a3, uint32_t db){
  asm volatile("{\n.reg .pred p;\n.reg .b64 a, b;\nsetp.ne.b32 p, 1, 0;\nmov.b64 b, {%24, %26};\n"
  "wgmma.mma_async.sync.aligned.m64n40k16.f32.bf16.bf16 {%0, %1, %2, %3, %4, %5, %6, %7, %8, %9, %10, %11, %12, %13, %14, %15, %16, %17, %18, %19}, {%20,%21,%22,%23}, b, p, 1, 1, %25;\n}\n"
  : "+f"(d[0]), "+f"(d[1]), "+f"(d[2]), "+f"(d[3]), "+f"(d[4]), "+f"(d[5]), "+f"(d[6]), "+f"(d[7]), "+f"(d[8]), "+f"(d[9]), "+f"(d[10]), "+f"(d[11]), "+f"(d[12]), "+f"(d[13]), "+f"(d[14]), "+f"(d[15]), "+f"(d[16]), "+f"(d[17]), "+f"(d[18]), "+f"(d[19])
  : "r"(a0), "r"(a1), "r"(a2), "r"(a3), "r"(db), "n"(TB), "n"(HB));
}
template<int TB, uint32_t HB> __device__ __forceinline__ void wgmma_rz_n40(float (&d)[20], uint32_t a0, uint32_t a1, uint32_t a2, uint32_t a3, uint32_t db){
  asm volatile("{\n.reg .pred p;\n.reg .b64 a, b;\nsetp.ne.b32 p, 0, 0;\nmov.b64 b, {%24, %26};\n"
  "wgmma.mma_async.sync.aligned.m64n40k16.f32.bf16.bf16 {%0, %1, %2, %3, %4, %5, %6, %7, %8, %9, %10, %11, %12, %13, %14, %15, %16, %17, %18, %19}, {%20,%21,%22,%23}, b, p, 1, 1, %25;\n}\n"
  : "=f"(d[0]), "=f"(d[1]), "=f"(d[2]), "=f"(d[3]), "=f"(d[4]), "=f"(d[5]), "=f"(d[6]), "=f"(d[7]), "=f"(d[8]), "=f"(d[9]), "=f"(d[10]), "=f"(d[11]), "=f"(d[12]), "=f"(d[13]), "=f"(d[14]), "=f"(d[15]), "=f"(d[16]), "=f"(d[17]), "=f"(d[18]), "=f"(d[19])
  : "r"(a0), "r"(a1), "r"(a2), "r"(a3), "r"(db), "n"(TB), "n"(HB));
}
template<int TB, uint32_t HB> __device__ __forceinline__ void wgmma_rz_n8(float (&d)[4], uint32_t a0, uint32_t a1, uint32_t a2, uint32_t a3, uint32_t db){
  asm volatile("{\n.reg .pred p;\n.reg .b64 a, b;\nsetp.ne.b32 p, 0, 0;\nmov.b64 b, {%8, %10};\n"
  "wgmma.mma_async.sync.aligned.m64n8k16.f32.bf16.bf16 {%0, %1, %2, %3}, {%4,%5,%6,%7}, b, p, 1, 1, %9;\n}\n"
  : "=f"(d[0]), "=f"(d[1]), "=f"(d[2]), "=f"(d[3])
  : "r"(a0), "r"(a1), "r"(a2), "r"(a3), "r"(db), "n"(TB), "n"(HB));
}

constexpr int SEQ = 2048, DM = 1024, FF = 3584;
constexpr float LOG2E = 1.4426950408889634f;
constexpr uint32_t POLL_LIMIT = 1u << 22;
#define NPRE0 1
#define NPREN 2
constexpr int NPRE = NPREN;
#define QW 4
#define RS_N 22
#define RS_D1 430
#define RS_D2 300
#define SKM 0x154
#define LAG 2
#define PF_T0 5000
#define PF_DT 800
#define NFFN_L NFFN
#define FF_DT 500
#define GRES 8
#define TMASK 0xffffff
#define PMASK 0xffffff
#define FF_T0 1
#define GPRE 0
#define REL 6
#define EFI 11
#define TKW 8
#define SLOT 0
#define SLOTW 48
#define FF_ORD 0x76543210ba98ull
#define KT 0
#define KK(id) do { if (KT) { TK(32 * wg + (id)); } } while (0)
#define PF_I0 0
#define PF_ST 7
#define PRK 3
#define TRKL 1
#define KR 4
#define KSEL c
#define XP 0
#define CAPL 2
#define OUT_D 400
#define OUT_0 0
#define ML 2
#define H2 1
#define H3 1
constexpr int NFFN = 112;

constexpr uint32_t SB0 = 1024;
constexpr uint32_t KV_STAGE = 49152, R5 = 32768;
constexpr uint32_t OFF_X = 163840, OFF_S = 196608, OFF_WPHI = OFF_S + 20480, OFF_M = 229376, SMEM_BYTES = 232448;
constexpr uint32_t OFF_RS256 = 212992, OFF_ONES = OFF_RS256 + 1024, OFF_WPHIK1 = OFF_ONES + 1024, OFF_KVZ = OFF_S;
constexpr uint32_t OFF_WPHIK = OFF_S, OFF_BXK = OFF_S + 2048, OFF_AXK = OFF_S + 4096, OFF_G = OFF_S + 8192;
constexpr uint32_t OFF_AXQ = OFF_WPHI, OFF_BXQ = OFF_WPHI + 2048, OFF_WPHIQ = OFF_WPHI + 4096;
constexpr uint32_t B_FULLKV = OFF_M  , B_EMPTYKV = OFF_M + 32  ;
constexpr uint32_t B_EMPTY5 = OFF_M + 64  , B_UO = B_EMPTY5 + 48  , B_RC = B_UO + 32  ;
constexpr uint32_t B_OUT = B_RC + 16  , B_SD = B_OUT + 16, B_AUX = B_SD + 8, B_AUXQ = B_AUX + 8, B_RX = B_AUXQ + 8;
constexpr uint32_t B_FULL5 = B_RX + 8  , B_FULLA = B_FULL5 + 48  , B_F = B_FULLA + 96  , B_WD = B_F + 64  ;
constexpr uint32_t B_WC = B_WD + 32  , B_DR = B_WC + 32  , B_W = B_DR + 24, B_OS = B_W + 8, B_R = B_W + 16, B_KD = B_W + 24, B_R1 = B_W + 32, B_T = B_W + 40, B_G = B_W + 48, B_END = B_W + 56, B_S0 = B_END;
static_assert(B_S0 < OFF_M + 592 && B_END <= OFF_M + 592 && B_FULL5 + 40 >= OFF_M + 208 && B_FULL5 + 40 < OFF_M + 400, "barriers");
constexpr uint32_t OFF_SUMWR = OFF_M + 608, OFF_EP = OFF_M + 624, OFF_KEY = OFF_M + 628;
constexpr uint32_t OFF_RSQ = OFF_M + 640, OFF_TL = OFF_M + 1152, OFF_SEL = OFF_M + 1648, OFF_T = OFF_M + 1792, OFF_WR = OFF_M + 2048, OFF_SCR = OFF_M + 2432;
constexpr uint32_t OFF_XSEL = 2 * R5, OFF_GU = OFF_XSEL + 4096, OFF_OUT = 3 * R5;
constexpr uint64_t FF_SLOT = 0xdcdc3210dcbaull;
constexpr int KVP = 6 * 128;

enum { NB_G2E = 1, NB_XS = 2, NB_WG01 = 3, NB_ACT = 4, NB_Q0 = 5  , NB_ST = 14, NB_DN = 9, NB_ZERO = 10, NB_PUB = 11, NB_TOK = 10  , NB_L0 = 12  , NB_WG2 = 7, NB_QGO = 15 };

struct Scratch {
  bf16     o[SEQ * DM];
  float4   rstat[SEQ];
  uint32_t key[8 * KR * 128];
  uint32_t cand[128 * 512];
  float4   yacc[4 * 3 * 128];
  float4   kvacc[32 * KVP];
  uint2    stats[SEQ];
  uint32_t cskv[2 * DM];
  uint32_t csq[4 * DM];
  uint32_t oset[128 * 16];
  uint32_t oflag[16 * 6 * 32];
  uint32_t epoch;
};
__device__ __align__(1024) Scratch g_scr;
#define TS(id)
#define TDUMP()
#define TS0_DECL()
#define TS0_READ()
#define TS0_WRITE()
#define TK(id)
#define TSW(id)

struct Params {
  CUtensorMap x128, x64, wkv, wq, wo[2], wd, wg, wu, phi, tg, tu, td, xs, ws, qs, out;
  const bf16 *x, *wqkv, *wo_p, *wg_p, *wu_p, *wd_p, *wr;
  bf16* out_p;
  Scratch* g;
  uint32_t zero;
};

constexpr float EXP_LIM = 1.1529215e18f, ARG_LIM2 = 3600.f;
template<bool PR> __device__ __forceinline__ void dual_exp2(const float (&p)[16], uint32_t (&ep)[8], uint32_t (&em)[8]) {
  #pragma unroll
  for (int k = 0; k < 8; k++) {
    const float a = ex2(p[2*k]), b = ex2(p[2*k+1]);
    ep[k] = pack_bf16(a, b);
    if (PR) { const float r = rcp(a * b); em[k] = pack_bf16(r * b, r * a); }
    else em[k] = pack_bf16(ex2(-p[2*k]), ex2(-p[2*k+1]));
  }
}
__device__ __forceinline__ void dual_exp2_shifted(const float (&pp)[2][16], uint32_t (&ph)[4][8]) {
  #pragma unroll
  for (int h = 0; h < 2; h++) {
    const float* p = pp[h];
    float m[4] = {p[0], p[2], p[0], p[2]};
    #pragma unroll
    for (int i = 0; i < 16; i++) { m[(i >> 1) & 1] = fmaxf(m[(i >> 1) & 1], p[i]); m[2 + ((i >> 1) & 1)] = fminf(m[2 + ((i >> 1) & 1)], p[i]); }
    #pragma unroll
    for (int o = 1; o < 4; o <<= 1) {
      m[0] = fmaxf(m[0], __shfl_xor_sync(~0u, m[0], o)); m[1] = fmaxf(m[1], __shfl_xor_sync(~0u, m[1], o));
      m[2] = fminf(m[2], __shfl_xor_sync(~0u, m[2], o)); m[3] = fminf(m[3], __shfl_xor_sync(~0u, m[3], o));
    }
    #pragma unroll
    for (int k = 0; k < 8; k++) {
      ph[2*h][k] = pack_bf16(ex2(p[2*k] - m[k & 1]), ex2(p[2*k+1] - m[k & 1]));
      ph[2*h+1][k] = pack_bf16(ex2(m[2 + (k & 1)] - p[2*k]), ex2(m[2 + (k & 1)] - p[2*k+1]));
    }
  }
}
__device__ __forceinline__ uint32_t add_bf16x2(uint32_t a, uint32_t b) { uint32_t r; asm("add.rn.bf16x2 %0, %1, %2;" : "=r"(r) : "r"(a), "r"(b)); return r; }
__device__ __forceinline__ void row_sums(float (&s)[2][4], const uint32_t (&ph)[4][8], uint32_t sel) {
  uint32_t u[8];
  #pragma unroll
  for (int i = 0; i < 8; i++) { const uint32_t* f = &ph[i >> 1][i & 1]; u[i] = add_bf16x2(add_bf16x2(f[0], f[2]), add_bf16x2(f[4], f[6])); }
  wg_fence();
  wgmma_rz_n8<0, H0>(s[0], u[0], u[1], u[2], u[3], sel);
  wgmma_rz_n8<0, H0>(s[1], u[4], u[5], u[6], u[7], sel);
  wg_commit();
}
__device__ __forceinline__ uint32_t mul_bf16x2(uint32_t a, uint32_t b) { uint32_t r; asm("mul.rn.bf16x2 %0, %1, %2;" : "=r"(r) : "r"(a), "r"(b)); return r; }
__device__ __forceinline__ void normalize(uint32_t (&ph)[4][8], const float (&s)[2][4]) {
  #pragma unroll
  for (int i = 0; i < 4; i++) {
    const float i0 = rcp(s[i >> 1][i & 1]), i1 = rcp(s[i >> 1][2 + (i & 1)]);
    const uint32_t n0 = pack_bf16(i0, i0), n1 = pack_bf16(i1, i1);
    #pragma unroll
    for (int k = 0; k < 4; k++) { ph[i][2*k] = mul_bf16x2(ph[i][2*k], n0); ph[i][2*k+1] = mul_bf16x2(ph[i][2*k+1], n1); }
  }
}
__device__ __forceinline__ void split_bf16(float a, float b, uint32_t& hi, uint32_t& lo) { hi = pack_bf16(a, b); lo = pack_bf16(a - bf_lo(hi), b - bf_hi(hi)); }
__device__ __forceinline__ void put_colsums(uint32_t base, int lane, float a, float b, float c, float d) {
  uint32_t h0, l0, h1, l1;
  split_bf16(a, b, h0, l0); split_bf16(c, d, h1, l1);
  const uint32_t ad = base + (lane >> 1) * 128 + (lane & 1) * 8;
  sts64(ad, h0, h1); sts64(ad + 16, l0, l1); sts64(ad + 32, h0, h1); sts64(ad + 48, l0, l1);
  sts128(base + (lane >> 1) * 128 + 64 + (lane & 1) * 32, 0, 0, 0, 0); sts128(base + (lane >> 1) * 128 + 80 + (lane & 1) * 32, 0, 0, 0, 0);
}
__device__ __forceinline__ float reduce8(const float (&v)[8], int lane) {
  const bool b4 = lane & 16, b3 = lane & 8, b2 = lane & 4;
  float a[4], b[2];
  #pragma unroll
  for (int i = 0; i < 4; i++) a[i] = (b4 ? v[4 + i] : v[i]) + __shfl_xor_sync(~0u, b4 ? v[i] : v[4 + i], 16);
  #pragma unroll
  for (int i = 0; i < 2; i++) b[i] = (b3 ? a[2 + i] : a[i]) + __shfl_xor_sync(~0u, b3 ? a[i] : a[2 + i], 8);
  return (b2 ? b[1] : b[0]) + __shfl_xor_sync(~0u, b2 ? b[0] : b[1], 4);
}
__device__ __forceinline__ bool tag_bad(uint4 v, uint32_t tg) { return (((v.x ^ tg) | (v.y ^ tg) | (v.z ^ tg) | (v.w ^ tg)) & 3) != 0; }

__global__ void __launch_bounds__(512, 1) fused_kernel(const __grid_constant__ Params P) {
  extern __shared__ __align__(1024) uint8_t smem_raw[];
  const uint32_t sb = smem_u32(smem_raw);
  const int tid = threadIdx.x, lane = tid & 31;
  TS0_DECL();
  TS0_READ();
  if (tid == 352) { prefetch_map(&P.wkv); prefetch_map(&P.x128); }
  const int cp = blockIdx.x >> 1, rank = blockIdx.x & 1;
  const int cr = cp < 4 ? 32 + 8 * cp : cp - 4 + max((cp * 37 - 1076) >> 8, 0);
  const int c = (cr & 62) + 64 * (cr & 1) + rank;
  const int m256 = c >> 4, nkv = c & 15, m128 = c >> 3, j = c & 7;
  if ((tid >> 5) == 12 && elect_one()) {
    mbar_init(sb + B_S0, 1); mbar_init(sb + B_FULLKV, 1); mbar_init(sb + B_FULLKV + 8, 1);
    fence_async_smem();
    mbar_expect_tx(sb + B_S0, 32768);
    tma_4d(sb + 32768, &P.wkv, 0, 0, nkv, 1, sb + B_S0);
    tma_2d(sb, &P.x128, 0, 256 * m256, sb + B_S0);
    mbar_expect_tx(sb + B_FULLKV, 16384);
    tma_2d(sb + 16384, &P.x128, 0, 256 * m256 + 128, sb + B_FULLKV);
    if (NPRE0 > 1) {
      mbar_expect_tx(sb + B_FULLKV + 8, KV_STAGE);
      tma_4d(sb + KV_STAGE + 32768, &P.wkv, 0, 64, nkv, 1, sb + B_FULLKV + 8);
      tma_2d(sb + KV_STAGE, &P.x128, 64, 256 * m256, sb + B_FULLKV + 8);
      tma_2d(sb + KV_STAGE + 16384, &P.x128, 64, 256 * m256 + 128, sb + B_FULLKV + 8);
    }
    asm volatile("fence.mbarrier_init.release.cluster;" ::: "memory");
  }
  #pragma unroll
  for (int w = 0; w < 3; w++)
    if (tid == 32 + 32 * w) {
      #pragma unroll
      for (uint32_t b = B_FULLKV + 16 + 192 * w; b < B_FULLKV + 208 + 192 * w && b < B_END; b += 8)
        mbar_init(sb + b, b < B_EMPTYKV ? 1 : b < B_EMPTY5 ? 12 : b < B_SD ? 4 : b < B_RX || b == B_W ? 2 : b == B_RX ? 8 : 1);
      if (w == 1) mbar_arrive(sb + B_FULL5 + 40);
      asm volatile("fence.mbarrier_init.release.cluster;" ::: "memory");
      fence_async_smem();
    }
  const int warp = __shfl_sync(~0u, tid >> 5, 0), wg = warp >> 2, wp = warp & 3;
  const int f = 16 * ((cr + 7) & 7) + 2 * (cr >> 3) + rank;
  const int ha = 4 * (nkv >> 1) + (nkv & 1);
  Scratch* const G = P.g;
  if ((sb & 0x3ffff) != SB0) asm volatile("trap;");
  __syncthreads();
  cluster_arrive();
  if (warp == 12) {
    TK(88 - 32);
    if (elect_one()) {
      #pragma unroll
      for (int s = NPRE0; s < NPRE; s++) {
        const uint32_t st = sb + s * KV_STAGE, fb = sb + B_FULLKV + 8 * s;
        mbar_expect_tx(fb, KV_STAGE);
        tma_4d(st + 32768, &P.wkv, 0, 64 * s, nkv, 1, fb);
        tma_2d(st, &P.x128, 64 * s, 256 * m256, fb);
        tma_2d(st + 16384, &P.x128, 64 * s, 256 * m256 + 128, fb);
      }
    }
    __syncwarp();
  }

  if (wg == 3) {
    asm volatile("setmaxnreg.dec.sync.aligned.u32 32;");
    cluster_wait();
    if (wp == 0) { TK(89 - 32); }
    const bool el = elect_one();
    const uint64_t ef = policy_evict_first(), en = policy_evict_normal();
    auto fetch_o = [&](const int t0, uint32_t so, uint32_t par) {
      const int sh = t0 & 1;
      uint32_t ready = 0;
      const bf16* base = G->o + (m128 * 16 + t0) * 8192 + rank * 4096;
      const uint32_t* hint = &G->oflag[(m128 * 6 + ((t0 + 1) & 6) + rank) * 32 + ((4 * (j & 6) + lane) & 31)];
      #pragma unroll 1
      for (int i = 2 - 2 * sh; i < 8; i += 1 + sh) {
        uint32_t it = 0;
        while ((~ready >> (4 * i) & (15 + 240 * sh)) && ++it < POLL_LIMIT) ready = __ballot_sync(~0u, ld32_rlx(hint) != 0);
        mbar_wait(sb + B_EMPTY5 + so, par);
        if (el) {
          bulk_g2s_mc(sb + so * 4096 + rank * 8192, base + (((j & 6) + i) & 7) * 16384, 8192, sb + B_FULLA + 2 * so + 8 * rank, ef);
          if (i == 2 - 2 * sh) TS(t0 == 0 ? (rank ? 4 : 12) : t0 == 3 ? (rank ? 31 : 10) : (rank ? 9 : 13));
        }
        so += 8;
        if (so == 48) { so = 0; par ^= 1; }
      }
    };
    if (wp == 0) {
      {
        #pragma unroll 1
        for (int kb = NPRE; kb < 16; kb++) {
          const uint32_t st = sb + (kb & 3) * KV_STAGE, fb = sb + B_FULLKV + 8 * (kb & 3);
          mbar_wait(fb + (B_EMPTYKV - B_FULLKV), ~(kb >> 2) & 1);
          if (el) {
            mbar_expect_tx(fb, KV_STAGE);
            tma_2d_mc(st + rank * 16384, &P.x128, 64 * kb, 256 * m256 + 128 * rank, fb);
            tma_4d_h(st + 32768, &P.wkv, 0, 64 * kb, nkv, 1, fb, ef);
          }
        }
        uint64_t ord = 0xf3120edcba987654ull;
        uint32_t so = 0, par = 1;
        #pragma unroll 1
        for (int i = 0; i < 16; i++) {
          const uint32_t st = sb + so * 4096, fb = sb + B_FULL5 + so;
          const int k0 = (64 * (uint32_t)ord + 128 * (j & 6)) & 960;
          mbar_wait(i < 5 ? sb + B_EMPTYKV + so - (i > 1 ? 8 : 0) : fb + (B_EMPTY5 - B_FULL5), par);
          if (el) {
            mbar_expect_tx(fb, R5);
            tma_2d_mc_h(st + rank * 8192, &P.x64, k0, 128 * m128 + 64 * rank, fb, i >= EFI ? ef : en);
            tma_3d_h(st + 16384, &P.wq, 0, k0, 2 * j, fb, ef);
          }
          ord >>= 4; so += 8;
          if (so == 40) { so = 0; par ^= 1; }
        }
        mbar_wait(sb + B_FULL5 + 8 + 8 * rank, 0); if (el) mbar_arrive(sb + B_R);
        mbar_wait(sb + B_FULL5 + 24 + 8 * rank, 0); if (el) mbar_arrive(sb + B_R1);
        #pragma unroll 1
        for (int i = 0; i < 19; i++) {
          const uint32_t fb = sb + B_FULL5 + so, fa = sb + B_FULLA + 2 * so, na = i == rank ? 0 : 8192;
          mbar_wait(fb + (B_EMPTY5 - B_FULL5), par);
          if (SLOT) { while (((uint32_t)clock() & (uint32_t)(SLOT - 1)) >= SLOTW) {} }
          if (el) {
            if (i < 16) {
              mbar_expect_tx(fb, 16384);
              const int row = i < 8 ? 128 * (((j & 6) + i) & 7) : 256 * (((j >> 1) + i) & 3) + 32 + 16 * (i & 4);
              tma_5d_h(sb + so * 4096 + 16384, &P.wo[i >> 3], 128 * j, row, fb, ef);
              tma_5d_h(sb + so * 4096 + 24576, &P.wo[i >> 3], 128 * j + 64, row, fb, ef);
              mbar_expect_tx(fa, na); mbar_expect_tx(fa + 8, na);
            } else mbar_arrive(sb + B_DR + 8 * (i - 16));
          }
          so += 8;
          if (so == 48) { so = 0; par ^= 1; }
        }
      }
    } else if (wp == 3) {
      const uint32_t t_start = (uint32_t)clock();
      if (el) {
        mbar_expect_tx(sb + B_W, 12288);
        #pragma unroll 1
        for (int i = 0; i < 6; i++) tma_2d(sb + (i == 0 ? OFF_WPHIK : i == 1 ? OFF_WPHIK1 : OFF_WPHIQ + 2048 * (i - 2)), &P.phi, 0, 32 * (i < 2 ? 2 * nkv + i : 4 * j + 2 * (i & 1) + ((i - 2) >> 1)), sb + B_W);
        prefetch_map(&P.x64); prefetch_map(&P.wq); prefetch_map(&P.wo[0]); prefetch_map(&P.wo[1]);
        prefetch_map(&P.wd); prefetch_map(&P.out); prefetch_map(&P.wg); prefetch_map(&P.wu);
      }
      #pragma unroll 1
      for (int i = 0; i < 8; i++) {
        if (lane < 16) st128_rlx(&G->cand[(m128 * 8 + i) * 512 + 64 * j + 4 * lane], ~0u, ~0u, ~0u, ~0u);
      }
      if (lane < 16) st128_rlx(&G->rstat[16 * c + lane], 0, 0, 0, 0);
      if (lane < 12) st128_rlx(&G->yacc[12 * c + lane], 0, 0, 0, 0);
      {
        const uint32_t nt = ld32_rlx(&G->epoch);
        if (lane < 8) { st128_rlx(&G->stats[16 * c + 2 * lane], nt, nt, nt, nt); st128_rlx(&G->csq[32 * c + 4 * lane], nt, nt, nt, nt); }
        if (lane < 4) { st128_rlx(&G->cskv[128 * nkv + 16 * m256 + 4 * lane], nt, nt, nt, nt); st128_rlx(&G->oset[16 * c + 4 * lane], nt, nt, nt, nt); }
      }
      if (lane < 2 * KR) st128_rlx(&G->key[(KR * j + (lane >> 1)) * 128 + m128 * 8 + 4 * (lane & 1)], 0, 0, 0, 0);
      if (c < 32) {
        #pragma unroll 1
        for (int i = lane; i < KVP; i += 32) st128_rlx(&G->kvacc[(ha + 2 * m256) * KVP + i], 0, 0, 0, 0);
      }
      fence_gpu();
      bar_arrive(NB_ZERO, 160);
      TS0_WRITE();
      if (el) {
        #pragma unroll 1
        for (int i = PF_I0; i < ((XP & 4) ? 0 : 30); i++) {
          while ((uint32_t)clock() - t_start < (uint32_t)(PF_T0 + PF_DT * (i - PF_I0) + PF_ST * f)) __nanosleep(64);
          if (i < 4) { bulk_prefetch(P.wqkv + (size_t)(256 * i + c) * (3 * DM), 2048); bulk_prefetch(P.wqkv + (size_t)(256 * i + 128 + c) * (3 * DM), 2048); }
          else if (i < 6) bulk_prefetch(P.wo_p + (size_t)c * 8192 + (i - 4) * 4096, 8192);
          else if ((TMASK >> (i - 6)) & 1) {
            const int k = i - 6;
            if (f < NFFN) {
              if (k < 16) {
                #pragma unroll 1
                for (int e = 0; e < 4; e++) tma_2d(sb + OFF_T, rank ? &P.tu : &P.tg, 32 * (f & ~1), 64 * k + 16 * e, sb + B_T);
              } else { tma_2d(sb + OFF_T, &P.td, 0, 256 * f + 32 * (k - 16), sb + B_T); tma_2d(sb + OFF_T, &P.td, 0, 256 * f + 32 * (k - 16) + 16, sb + B_T); }
            }
          }
          else if (!((PMASK >> (i - 6)) & 1)) {}
          else if (i < 22) bulk_prefetch(((i & 1) ? P.wu_p : P.wg_p) + (size_t)((i - 6) >> 1) * 458752 + c * 3584, 7168);
          else bulk_prefetch(P.wd_p + (size_t)(i - 22) * 458752 + c * 3584, 7168);
        }
      }
      __syncwarp();
      mbar_wait2(sb + B_OS, 0, sb + B_RX, 0);
      #pragma unroll 1
      for (int t0 = 0; t0 < 4; t0 += 3) fetch_o(t0, t0 ? 8 : 24, 0);
    } else {
      const int half = wp - 1;
      const uint32_t ep1 = ld32_rlx(&G->epoch) + 1, tg = ep1 & 3;
      {
        uint32_t it = 0;
        sts128(sb + OFF_ONES + half * 512 + lane * 16, 0x3f803f80u, 0x3f803f80u, 0x3f803f80u, 0x3f803f80u);
        if (lane < 9) { const uint32_t v = (lane & 1) ? 0 : 0x3f803f80u; sts128(sb + OFF_SEL + lane * 16, v, v, v, v); }
        auto reset_o = [&](int i0, int i1, uint32_t dt) {
          uint32_t t0 = (uint32_t)clock();
          #pragma unroll 1
          for (int i = i0; i < i1; i++) {
            if (!(XP & 2)) st128_rlx(G->o + (m128 * 16 + 2 * j + half) * 8192 + 256 * i + 8 * lane, ~0u, ~0u, ~0u, ~0u);
            while ((uint32_t)clock() - t0 < dt) __nanosleep(40);
            t0 += dt;
          }
        };
        mbar_wait(sb + B_S0, 0);
        reset_o(0, RS_N, RS_D1);
        bar_sync(NB_PUB, 192);
        const uint4* src = reinterpret_cast<const uint4*>(&G->stats[256 * m256 + 128 * half]) + lane;
        const uint4* srk = reinterpret_cast<const uint4*>(&G->cskv[128 * nkv]) + lane;
        uint4 v0, v1, vk;
        it = 0;
        do { v0 = ld128_rlx(src); v1 = ld128_rlx(src + 32); vk = ld128_rlx(srk); }
        while ((tag_bad(v0, tg) || tag_bad(v1, tg) || tag_bad(vk, tg)) && ++it < POLL_LIMIT);
        fence_acquire_gpu();
        if (half) put_colsums(sb + OFF_BXK, lane, untag(vk.x), untag(vk.y), untag(vk.z), untag(vk.w));
        #pragma unroll
        for (int i = 0; i < 2; i++) {
          const uint4 v = i ? v1 : v0;
          uint32_t hi, lo;
          split_bf16(-0.5f * untag(v.x), -0.5f * untag(v.z), hi, lo);
          const uint32_t h0 = __byte_perm(hi, hi, 0x1010), h1 = __byte_perm(hi, hi, 0x3232), l0 = __byte_perm(lo, lo, 0x1010), l1 = __byte_perm(lo, lo, 0x3232);
          const uint32_t a = sb + OFF_AXK + half * 2048 + i * 1024 + lane * 32;
          sts128(a, h0, l0, 0, 0); sts128(a + 16, h1, l1, 0, 0);
          sts64(sb + OFF_RS256 + half * 512 + i * 256 + lane * 8, v.y & ~3u, v.w & ~3u);
          if (half == (m128 & 1)) {
            const uint32_t aq = sb + OFF_AXQ + i * 1024 + lane * 32;
            sts128(aq, h0, l0, 0, 0); sts128(aq + 16, h1, l1, 0, 0);
            sts64(sb + OFF_RSQ + i * 256 + lane * 8, v.y & ~3u, v.w & ~3u);
          }
        }
        fence_async_smem();
        __syncwarp();
        if (el) { sts32(sb + OFF_EP, ep1); mbar_arrive(sb + B_AUX); }
        reset_o(RS_N, 32, RS_D2);
        if (half == 0 && rank == 0 && lane < 12) st128_rlx(&G->oflag[(m128 * 6 + (lane >> 1)) * 32 + 4 * j + 4 * (lane & 1)], 0, 0, 0, 0);
        fence_gpu();
        __syncwarp();
        if (el) { st32_rlx(&G->oset[16 * c + 8 * half], ep1); if (half) mbar_arrive(sb + B_AUXQ); }
        if (!half) {
          const uint4* src = reinterpret_cast<const uint4*>(&G->csq[128 * j]) + lane;
          uint4 v0, v1, v2, v3;
          do { v0 = ld128_rlx(src); v1 = ld128_rlx(src + DM / 4); v2 = ld128_rlx(src + DM / 2); v3 = ld128_rlx(src + 3 * DM / 4); }
          while ((tag_bad(v0, tg) || tag_bad(v1, tg) || tag_bad(v2, tg) || tag_bad(v3, tg)) && ++it < POLL_LIMIT);
          put_colsums(sb + OFF_BXQ, lane, (untag(v0.x) + untag(v1.x)) + (untag(v2.x) + untag(v3.x)), (untag(v0.y) + untag(v1.y)) + (untag(v2.y) + untag(v3.y)),
                      (untag(v0.z) + untag(v1.z)) + (untag(v2.z) + untag(v3.z)), (untag(v0.w) + untag(v1.w)) + (untag(v2.w) + untag(v3.w)));
          fence_async_smem();
          __syncwarp();
          if (el) mbar_arrive(sb + B_AUXQ);
        }
      }
      if (half == 0) {
        for (uint32_t it = 0; __any_sync(~0u, ld32_rlx(&G->oset[m128 * 128 + 8 * (lane & 15)]) != ep1) && it < POLL_LIMIT; it++) {}
        fence_acquire_gpu();
        if (el) mbar_arrive(sb + B_OS);
      }
      if (!half) {
        #pragma unroll 1
        for (int hh = 0; hh < 2; hh++) {
          const uint32_t src = sb + (1 + rank) * R5 + hh * 8192, fa = sb + B_FULLA + 16 + 16 * rank + 8 * hh;
          mbar_wait(fa, 0);
          mbar_wait(sb + B_UO + 8 * hh, 0);
          if (el) bulk_s2peer(mapa(src, rank ^ 1), src, 8192, mapa(fa, rank ^ 1));
        }
        fetch_o(1, 24, 1);
      }
      else if (f < NFFN_L) {
        mbar_wait2(sb + B_UO, 0, sb + B_UO + 8, 0);
        mbar_wait(sb + B_UO + 24, 0);
        uint32_t t0 = (uint32_t)clock();
        while ((uint32_t)clock() - t0 < (uint32_t)FF_T0) __nanosleep(32);
        t0 -= FF_DT;
        #pragma unroll 1
        for (int i = 0; i < 12; i++) {
          const int e = (FF_ORD >> (4 * i)) & 15;
          const uint32_t dst = sb + 16384 * ((FF_SLOT >> (4 * e)) & 15), fb = sb + B_F + 8 * e;
          if (i >= 2) mbar_wait(sb + B_WC + 8 * ((0x100066553244ull >> (4 * e)) & 15), 0);
          while ((uint32_t)clock() - t0 < (uint32_t)FF_DT) __nanosleep(32);
          t0 = (uint32_t)clock();
          if (i < 8) { TK(48 + i); }
          if (el) {
            mbar_expect_tx(fb, 16384);
            if (e >= 8) tma_3d_h(dst, &P.wd, 0, 32 * f, 4 * e - 32, fb, ef);
            else { tma_2d(dst, &P.wg, 32 * f, 128 * e, fb); tma_2d(dst + 8192, &P.wu, 32 * f, 128 * e, fb); }
          }
        }
      }
      __syncwarp();
    }
    if (wp & 1) {
      __syncwarp();
      mbar_wait(sb + B_OUT + 8 * (wp >> 1), 0);
      uint32_t t0 = (uint32_t)clock() + OUT_0;
      #pragma unroll 1
      for (int i = 0; i < 8; i++) {
        while ((int32_t)((uint32_t)clock() - t0) < 0) __nanosleep(20);
        if (el) tma_store_2d(&P.out, 128 * j + 64 * (i & 1), 128 * m128 + 32 * (wp & 2) + 8 * (i & 6), sb + OFF_OUT + (i & 1) * 16384 + (wp & 2) * 4096 + (i & 6) * 1024);
        t0 += OUT_D;
      }
      if (el) { bulk_commit(); bulk_wait_all(); fence_async_global(); mbar_arrive(sb + B_SD); TS(19); }
    }
    __syncwarp();
    cluster_arrive(); cluster_wait();
    return;
  }

  asm volatile("setmaxnreg.inc.sync.aligned.u32 160;");
  cluster_wait();
  const int t = tid & 127, g = lane >> 2;
  const uint32_t sa = (16 * wp + (lane & 15)) * 128 + (((lane >> 4) ^ (lane & 7)) << 4);

  if (wg == 2) {
    float s[2] = {0.f, 0.f}, s2[2] = {0.f, 0.f}, ck[8] = {0.f, 0.f, 0.f, 0.f, 0.f, 0.f, 0.f, 0.f}, cs[8] = {0.f, 0.f, 0.f, 0.f, 0.f, 0.f, 0.f, 0.f};
    const uint32_t ebr = mapa(sb + B_EMPTYKV, lane & 1), tg = (ld32_rlx(&G->epoch) + 1) & 3;
    auto addx = [&](const uint4 v) {
      const uint32_t w[4] = {v.x, v.y, v.z, v.w};
      #pragma unroll
      for (int e = 0; e < 4; e++) { const float a = bf_lo(w[e]), d = bf_hi(w[e]); s[0] += a; s[1] += d; s2[0] = fmaf(a, a, s2[0]); s2[1] = fmaf(d, d, s2[1]); }
    };
    auto addc = [&](const uint4 v, float (&o)[8]) {
      o[0] += bf_lo(v.x); o[1] += bf_hi(v.x); o[2] += bf_lo(v.y); o[3] += bf_hi(v.y); o[4] += bf_lo(v.z); o[5] += bf_hi(v.z); o[6] += bf_lo(v.w); o[7] += bf_hi(v.w);
    };
    {
      const uint32_t ra = (16 * nkv + (t >> 3)) * 128 + (t & 7) * 16;
      const uint32_t ca = 32768 + (m256 >> 2) * 8192 + (t >> 1) * 128 + (((2 * (m256 & 3) + (t & 1)) ^ ((t >> 1) & 7)) << 4);
      int rd = 0;
      mbar_wait(sb + B_S0, 0);
      #pragma unroll 1
      for (int kb = 0; kb < 10; kb++) {
        const uint32_t st = sb + (kb & 3) * KV_STAGE;
        mbar_wait(sb + B_FULLKV + 8 * (kb & 3), (kb >> 2) & 1);
        const uint4 x0 = lds128(st + ra), w0 = lds128(st + ca);
        if (!(XP & 1)) { addx(x0); addc(w0, ck); } else s[0] += __uint_as_float(x0.x ^ w0.x);
        __syncwarp();
        if (lane < 2) mbar_arrive_remote(ebr + 8 * (kb & 3), 1);
        if ((SKM >> kb) & 1) {
          if (rd) {
            mbar_wait(sb + B_G, (rd - 1) & 1);
            const uint32_t a = sb + OFF_G + (t >> 3) * 256 + (t & 7) * 16;
            const uint4 x1 = lds128(a), x2 = lds128(a + 128), w1 = lds128(sb + OFF_G + 4096 + t * 16), w2 = lds128(sb + OFF_G + 6144 + t * 16);
            addx(x1); addx(x2); addc(w1, ck); addc(w2, ck);
            bar_sync(NB_WG2, 128);
          }
          if (wp == 0 && elect_one()) {
            mbar_expect_tx(sb + B_G, 8192);
            if (rd < 3) {
              tma_2d(sb + OFF_G, &P.xs, 640 + 128 * rd, 256 * m256 + 16 * nkv, sb + B_G);
              tma_2d(sb + OFF_G + 4096, &P.ws, (1 + (m256 >> 2)) * DM + 64 * nkv + 16 * (m256 & 3), 640 + 128 * rd, sb + B_G);
            } else tma_2d(sb + OFF_G, &P.qs, 32 * (c & 31), 256 * (c >> 5), sb + B_G);
          }
          rd++;
        }
      }
    }
    TK(82);
    const uint32_t scr = sb + OFF_SCR + 128;
    float sx = s[0] + s[1], sq = s2[0] + s2[1];
    #pragma unroll
    for (int o = 1; o < 8; o <<= 1) { sx += __shfl_xor_sync(~0u, sx, o); sq += __shfl_xor_sync(~0u, sq, o); }
    float v = reduce8(ck, lane);
    v += __shfl_xor_sync(~0u, v, 2);
    if (!(lane & 2)) stsf(scr + (wp * 16 + 8 * (lane & 1) + (lane >> 2)) * 4, v);

    bar_sync(NB_ZERO, 160);
    if ((lane & 7) == 0) {
      const float mean = sx * (1.f / DM);
      st64_rlx(&G->stats[256 * m256 + 16 * nkv + (t >> 3)], tagw(mean, tg), tagw(rsqrtf(fmaxf(sq * (1.f / DM) - mean * mean, 0.f) + 1e-5f), tg));
    }
    if (wp == 1 && lane < 16) {
      const uint32_t a = scr + lane * 4;
      st32_rlx(&G->cskv[128 * nkv + 16 * m256 + lane], tagw((ldsf(a) + ldsf(a + 64)) + (ldsf(a + 128) + ldsf(a + 192)), tg));
    }
    __syncwarp();
    bar_arrive(NB_PUB, 192);
    TSW(23);
    const uint4 wv = ld128_keep(P.wr + t * 8);
    #pragma unroll 1
    for (int i = 0; i < 2; i++) {
      mbar_wait(sb + B_G, i ^ 1);
      const uint32_t a = sb + OFF_G + t * 16;
      const uint4 u0 = lds128(a), u1 = lds128(a + 2048), u2 = lds128(a + 4096), u3 = lds128(a + 6144);
      addc(u0, cs); addc(u1, cs); addc(u2, cs); addc(u3, cs);
      bar_sync(NB_WG2, 128);
      if (i == 0 && wp == 0 && elect_one()) { mbar_expect_tx(sb + B_G, 8192); tma_2d(sb + OFF_G, &P.qs, 32 * (c & 31), 256 * (c >> 5) + 128, sb + B_G); }
    }
    if (t == 0) mbar_arrive(sb + B_W);
    float sw = (bf_lo(wv.x) + bf_hi(wv.x)) + (bf_lo(wv.y) + bf_hi(wv.y)) + (bf_lo(wv.z) + bf_hi(wv.z)) + (bf_lo(wv.w) + bf_hi(wv.w));
    #pragma unroll
    for (int o = 16; o; o >>= 1) sw += __shfl_xor_sync(~0u, sw, o);
    if (lane == 0) stsf(sb + OFF_SUMWR + wp * 4, sw);
    if ((t >> 4) == j) {
      const uint32_t a = sb + OFF_WR + (t & 15) * 32;
      sts128(a, wv.x << 16, wv.x & 0xffff0000u, wv.y << 16, wv.y & 0xffff0000u);
      sts128(a + 16, wv.z << 16, wv.z & 0xffff0000u, wv.w << 16, wv.w & 0xffff0000u);
    }
    v = reduce8(cs, lane);
    stsf(scr + (wp * 32 + 8 * (lane & 3) + (lane >> 2)) * 4, v);
    bar_sync(NB_WG2, 128);
    if (wp == 0) {
      const uint32_t a = scr + lane * 4;
      st32_rlx(&G->csq[(c >> 5) * DM + 32 * (c & 31) + lane], tagw((ldsf(a) + ldsf(a + 128)) + (ldsf(a + 256) + ldsf(a + 384)), tg));
    }
  }

  uint32_t xr[32];
  {
    const bool isq = wg == 2;
    float acc[2][64];
    {
      const uint32_t emptyb = mapa(sb + (isq ? B_EMPTY5 : B_EMPTYKV), t & 1);
      auto correct = [&](uint32_t xa, uint32_t xb) {
        wg_fence();
        wgmma_sa_n128<0, 1, H0, H0>(acc[0], dlo(SB0, 0) + (xa >> 4), dlo(SB0, 0) + (xb >> 4));
        wgmma_sa_n128<0, 1, H0, H0>(acc[1], dlo(SB0, 0) + (xa >> 4) + 64, dlo(SB0, 0) + (xb >> 4));
        wg_commit();
      };
      if (!isq) {
        mbar_wait(sb + B_S0, 0);
        if (wg) mbar_wait(sb + B_FULLKV, 0);
        if (wg == 0) { TSW(2); }
        #pragma unroll 1
        for (int kb = 0; kb < 16; kb++) {
          if (!KT && wg == 0) { TK(kb); }
          const uint32_t da = dlo(SB0, 16) + wg * 1024 + (kb & 3) * (KV_STAGE >> 4), db = dlo(SB0 + 32768, 8192) + (kb & 3) * (KV_STAGE >> 4);
          wg_fence();
          #pragma unroll
          for (int k = 0; k < 4; k++) {
            wgmma_ss_n128<0, 1, H128, H128>(acc[0], da + 2 * k, db + 128 * k, k > 0 || kb != 0);
            wgmma_ss_n128<0, 1, H128, H128>(acc[1], da + 512 + 2 * k, db + 128 * k, k > 0 || kb != 0);
          }
          wg_commit();
          wg_wait<1>();
          if (kb > 0 && t < 2) mbar_arrive_remote(emptyb + 8 * ((kb - 1) & 3), kb > 10 ? 3 : 1);
          if (kb < 15) mbar_wait(sb + B_FULLKV + 8 * ((kb + 1) & 3), ((kb + 1) >> 2) & 1);
          if (kb == 15 - LAG && wg == 1) bar_sync(NB_WG01, 256);
        }
        bar_arrive(wg ? NB_QGO : NB_WG01, 256);
        mbar_wait(sb + B_AUX, 0);
        correct(OFF_AXK + wg * 2048, OFF_BXK);
        wg_wait<0>();
        if (t < 2) mbar_arrive_remote(emptyb + 24, 3);
        if (wg == 0) { TSW(3); }
        fence_regs(acc[0]); fence_regs(acc[1]);
      const uint32_t stg = sb + OFF_X + (1 - wg) * 24576;
      const uint32_t va = stg + 16384 + (16 * wp + (lane & 15)) * 64 + (((lane >> 4) ^ ((lane >> 1) & 3)) << 4);
      const uint32_t ra = sb + OFF_RS256 + (128 * wg + 16 * wp + g) * 4;
      const float rs[4] = {ldsf(ra), ldsf(ra + 32), ldsf(ra + 256), ldsf(ra + 288)};
      float p[2][16];
      uint32_t vf[16], kf[2][16];
      auto project = [&](const uint32_t (&f)[16], uint32_t db) {
        wg_fence();
        #pragma unroll
        for (int i = 0; i < 2; i++) {
          wgmma_rs_n32<1, H64>(p[i], f[8*i], f[8*i+1], f[8*i+2], f[8*i+3], db, 0);
          wgmma_ra_n32<1, H64>(p[i], f[8*i+4], f[8*i+5], f[8*i+6], f[8*i+7], db + 64);
        }
        wg_commit();
      };
      auto fold = [&](uint32_t (&f)[16], int col, float sc) {
        #pragma unroll
        for (int i = 0; i < 16; i++) {
          const float r = rs[2 * (i >> 3) + (i & 1)] * sc;
          f[i] = pack_bf16(acc[i >> 3][col + 2 * (i & 7)] * r, acc[i >> 3][col + 2 * (i & 7) + 1] * r);
          asm volatile("" : "+r"(f[i]));
        }
      };
      auto put_v = [&](const uint32_t (&f)[16]) {
        #pragma unroll
        for (int k = 0; k < 4; k++) stsm4((va ^ ((k & 1) << 5)) + (k >> 1) * 4096, f[4*k], f[4*k+1], f[4*k+2], f[4*k+3]);
      };
      KK(0);
      fold(vf, 48, 1.f);
      mbar_wait(sb + B_W, 0);
      fold(kf[0], 0, LOG2E);
      #pragma unroll
      for (int i = 0; i < 32; i++) p[i >> 4][i & 15] = acc[i >> 4][i & 15];
      project(kf[0], dlo(SB0 + OFF_WPHIK, 16));
      mbar_wait(sb + B_W, 0);
      KK(1);
      {
        uint32_t v0[16];
        fold(kf[1], 16, LOG2E);
        fold(v0, 32, 1.f);
        if (wg == 1) bar_sync(NB_DN, 256);
        put_v(v0);
      }
      wg_wait<0>();
      fence_regs(p[0]); fence_regs(p[1]);
      if (wg == 1) bar_arrive(NB_WG01, 256);
      KK(2);
      #pragma unroll 1
      for (int h = 0; h < 2; h++) {
        uint32_t ph[4][8];
        float rsum[2][4];
        dual_exp2<PRK & 1>(p[0], ph[0], ph[1]); dual_exp2<(PRK >> 1)>(p[1], ph[2], ph[3]);
        row_sums(rsum, ph, dlo(SB0 + OFF_SEL, 16));
        KK(3 + 6 * h);
        if (wg == 0 && h == 0) { bar_arrive(NB_DN, 256); bar_sync(NB_WG01, 256); }
        if (h == 1) {
          if (wg == 1) bar_sync(NB_DN, 256);
          put_v(vf);
        }
        wg_wait<0>();
        KK(4 + 6 * h);
        fence_regs(rsum[0]); fence_regs(rsum[1]);
        if (!(XP & 8) && __builtin_expect(__any_sync(~0u, !((rsum[0][0] + rsum[0][1]) + (rsum[0][2] + rsum[0][3]) + (rsum[1][0] + rsum[1][1]) + (rsum[1][2] + rsum[1][3]) < EXP_LIM)), 0)) {
          dual_exp2_shifted(p, ph);
          #pragma unroll
          for (int i = 0; i < 8; i++) {
            const uint32_t* f = &ph[i >> 1][i & 1];
            float a = (bf_lo(f[0]) + bf_hi(f[0])) + (bf_lo(f[2]) + bf_hi(f[2])) + (bf_lo(f[4]) + bf_hi(f[4])) + (bf_lo(f[6]) + bf_hi(f[6]));
            a += __shfl_xor_sync(~0u, a, 1);
            rsum[i >> 2][2 * (i & 1) + ((i >> 1) & 1)] = a + __shfl_xor_sync(~0u, a, 2);
          }
        }
        if (h == 0) project(kf[1], dlo(SB0 + OFF_WPHIK1, 16));
        normalize(ph, rsum);
        #pragma unroll
        for (int i = 0; i < 8; i++) {
          const uint32_t* f = &ph[i >> 1][4 * (i & 1)];
          stsm4(((stg + sa) ^ ((i & 3) << 5)) + (i >> 2) * 8192, f[0], f[1], f[2], f[3]);
        }
        KK(5 + 6 * h);
        fence_async_smem();
        KK(6 + 6 * h);
        if (wg != h) { KK(7 + 6 * h); }
        if (wg == h) {
          float kv[20];
          #pragma unroll
          for (int w = 0; w < 2; w++) {
            const uint32_t da = dlo(SB0 + OFF_X, 16) + (h ^ w ^ 1) * 1536, db = dlo(SB0 + OFF_X + 16384, OFF_ONES - OFF_X - 16384) - (h ^ w ^ 1) * (1536 * 65535);
            if (w) bar_sync(NB_ST, 256); else bar_sync(NB_L0 + h, 128);
            wg_fence();
            #pragma unroll
            for (int k = 0; k < 8; k++) {
              if (k == 0 && w == 0) wgmma_sz_n40<1, 1, H128, H64>(kv, da, db);
              else wgmma_sa_n40<1, 1, H128, H64>(kv, da + k * 128, db - k * (64 * 65535));
            }
            wg_commit();
          }
          float4* dst = &G->kvacc[(ha + 2 * h) * KVP + t];
          wg_wait<0>();
          fence_regs(kv);
          KK(7 + 6 * h);
          if (h == 0) bar_arrive(NB_DN, 256); else if (t < 2) { mbar_arrive_at(sb + B_EMPTY5 + 40, t, 2); if (t == 0) mbar_arrive(sb + B_KD); }
          kv[17] = kv[18];
          #pragma unroll
          for (int i = 0; i < 6; i++) red_add_f32x4(dst + 128 * i, kv[3*i], kv[3*i+1], kv[3*i+2], 1.f);
          TSW(29 + h);
        } else bar_arrive(NB_ST, 256);
        wg_wait<0>();
        KK(8 + 6 * h);
        fence_regs(p[0]); fence_regs(p[1]);
      }
      #pragma unroll
      for (int i = 0; i < 32; i++) asm volatile("mov.b32 %0, 0;" : "=r"(xr[i]));
      } else {
        uint32_t so = 0, po = 0, par = 0;
        mbar_wait(sb + B_FULL5, 0);
        bar_sync(NB_QGO, 256);
        TSW(11);
        #pragma unroll 1
        for (int kb = 0; kb < 16 - ML; kb++) {
          TK(16 + kb);
          const uint32_t da = dlo(SB0, 16) + so * 256, db = dlo(SB0 + 16384, 8192) + so * 256;
          #pragma unroll
          for (int k = 0; k < 4; k++) {
            wg_fence();
            wgmma_ss_n128<0, 1, H128, H128>(acc[0], da + 2 * k, db + 128 * k, k > 0 || kb != 0);
            wgmma_ss_n128<0, 1, H128, H128>(acc[1], da + 512 + 2 * k, db + 128 * k, k > 0 || kb != 0);
            wg_commit();
            if (k == 1 && kb > 0 && t < 2) mbar_arrive_remote(emptyb + po, 2);
            if (k == 3) {
              po = so; so += 8;
              if (so == 40) { so = 0; par ^= 1; }
              mbar_wait(sb + B_FULL5 + so, par);
            }
            if ((QW >> k) & 1) wg_wait<2>(); else wg_wait<1>();
          }
        }
        auto block = [&](const int kb, const int i) {
          wg_fence();
          #pragma unroll
          for (int k = 0; k < 4; k++) wgmma_sa_n128<0, 1, H128, H128>(acc[i], dlo(SB0, 16) + (kb % 5) * 2048 + 512 * i + 2 * k, dlo(SB0 + 16384, 8192) + (kb % 5) * 2048 + 128 * k);
          wg_commit();
        };
        auto hand_over = [&](const int i) {
          const uint32_t ta = sb + (1 + rank) * R5 + sa + i * 8192;
          #pragma unroll
          for (int k = 0; k < 4; k++) {
            const float* a = &acc[i][32 * (k >> 1) + 8 * (k & 1)];
            stsm4(ta ^ (k << 5), pack_bf16(a[0], a[1]), pack_bf16(a[2], a[3]), pack_bf16(a[4], a[5]), pack_bf16(a[6], a[7]));
          }
        };
        mbar_wait2(sb + B_AUXQ, 0, sb + B_OS, 0);
        correct(OFF_AXQ, OFF_BXQ);
        #pragma unroll
        for (int kb = 16 - ML; kb < 16; kb++) {
          TK(16 + kb);
          block(kb, 0);
          if (kb < 15) mbar_wait(sb + B_FULL5 + 8 * ((kb + 1) % 5), ((kb + 1) / 5) & 1);
          if (kb == 16 - ML) wg_wait<2>(); else if (!H3) wg_wait<1>();
          if (kb == 16 - ML && t < 2) mbar_arrive_remote(emptyb + 8 * ((kb - 1) % 5), 2);
        }
        mbar_wait(sb + B_RC, 0);
        block(16 - ML, 1);
        if (H2) { block(17 - ML, 1); wg_wait<2>(); } else wg_wait<1>();
        fence_regs(acc[0]);
        hand_over(0);
        if (!H2) block(17 - ML, 1);
        fence_async_smem();
        bar_arrive(NB_Q0, 256);
        TSW(1);
        #pragma unroll
        for (int kb = 18 - ML; kb <= 16; kb++) {
          wg_wait<1>();
          if (t < 2) mbar_arrive_remote(emptyb + 8 * ((kb - 2) % 5), 2);
          if (kb < 16) block(kb, 1);
        }
        mbar_wait(sb + B_RC + 8, 0);
        wg_wait<0>();
        if (t < 2) mbar_arrive_remote(emptyb, 2);
        TSW(8);
        fence_regs(acc[1]);
        hand_over(1);
        fence_async_smem();
        bar_arrive(NB_Q0 + 1, 256);
        #pragma unroll
        for (int i = 0; i < 32; i++) { const float* a = &acc[(i >> 3) & 1][16 + 32 * (i >> 4) + 2 * (i & 7)]; xr[i] = pack_bf16(a[0], a[1]); }
        TSW(26);
      }
    }
    float p[2][16];
    #pragma unroll
    for (int i = 0; i < 32; i++) asm volatile("mov.b32 %0, 0;" : "=f"(p[i >> 4][i & 15]));
    auto project_r = [&](int w) {
      wg_fence();
      #pragma unroll
      for (int h = 0; h < 2; h++) {
        wgmma_rs_n32<1, H64>(p[h], xr[8*h], xr[8*h+1], xr[8*h+2], xr[8*h+3], dlo(SB0 + OFF_WPHIQ, 16) + 128 * w, 0);
        wgmma_ra_n32<1, H64>(p[h], xr[8*h+4], xr[8*h+5], xr[8*h+6], xr[8*h+7], dlo(SB0 + OFF_WPHIQ, 16) + 128 * w + 64);
      }
      wg_commit();
    };
    auto capture = [&](const int i) {
      if (!i || CAPL != 2) mbar_wait(sb + (i ? B_R1 : B_R), 0);
      #pragma unroll
      for (int k = 0; k < 4; k++) ldsm4(((sb + (1 + rank) * R5 + wg * 8192 + sa) ^ (k << 5)) + i * 2 * R5, xr[16*i+4*k], xr[16*i+4*k+1], xr[16*i+4*k+2], xr[16*i+4*k+3]);
      const uint32_t one = (((xr[16*i] | xr[16*i+4]) | (xr[16*i+8] | xr[16*i+12])) & P.zero) + 1;
      if (lane == 0) mbar_arrive_at(sb + (i ? B_RX : B_RC + 8 * wg), i ? wg : rank, one);
    };
    const uint32_t rq = sb + OFF_RSQ + (16 * wp + g) * 4 + 256 * (wg & 1), rb = rq + 128 * (wg & 2);
    const float cc[2][2] = {{ldsf(rq) * LOG2E, ldsf(rq + 32) * LOG2E}, {ldsf(rb) * LOG2E, ldsf(rb + 32) * LOG2E}};
    {
      const uint4* src = reinterpret_cast<const uint4*>(&G->kvacc[(4 * j + wg) * KVP + t]);
      uint4 v[12];
      #pragma unroll
      for (int i = 0; i < 12; i++) v[i] = i < 6 || isq ? ld128_rlx(src + 128 * i) : make_uint4(0, 0, 0, 0x41000000u);
      if (isq) {
        project_r(2);
        wg_wait<0>();
        #pragma unroll
        for (int i = 0; i < 16; i++) xr[i] = xr[16 + i];
      } else {
        capture(0);
        if (CAPL == 0) capture(1);
      }
      #pragma unroll 1
      for (uint32_t it = 0; it < POLL_LIMIT; it++) {
        uint32_t bad = 0;
        #pragma unroll
        for (int i = 0; i < 12; i++) bad |= v[i].w ^ 0x41000000u;
        if (!__any_sync(~0u, bad != 0)) break;
        #pragma unroll
        for (int i = 0; i < 12; i++) if (i < 6 || isq) v[i] = ld128_rlx(src + 128 * i);
      }
      mbar_wait(sb + B_KD, 0);
      #pragma unroll
      for (int e = 0; e < 2; e++) {
        if (e == 0 || isq) {
          float f[18];
          #pragma unroll
          for (int i = 0; i < 6; i++) { f[3*i] = __uint_as_float(v[6*e+i].x); f[3*i+1] = __uint_as_float(v[6*e+i].y); f[3*i+2] = __uint_as_float(v[6*e+i].z); }
          const uint32_t ka = sb + OFF_KVZ + (wg + e) * 5120 + wp * 1280 + lane * 16;
          stsm4(ka, pack_bf16(f[0], f[1]), pack_bf16(f[2], f[3]), pack_bf16(f[4], f[5]), pack_bf16(f[6], f[7]));
          stsm4(ka + 512, pack_bf16(f[8], f[9]), pack_bf16(f[10], f[11]), pack_bf16(f[12], f[13]), pack_bf16(f[14], f[15]));
          stsm2(ka + 1024, pack_bf16(f[16], 1.f), pack_bf16(f[17], 1.f));
        }
      }
    }
    fence_async_smem();
    if (wg == 1) bar_arrive(NB_DN, 256);
    if (CAPL == 1 && !isq) capture(1);
    TSW(wg == 0 ? 5 : wg == 1 ? 25 : 6);
    #pragma unroll 1
    for (int e = wg; e < wg + 1 + (wg >> 1); e++) {
      const int half = e >> 1, hh = e & 1, turn = e;
      const uint32_t ao = (1 + rank) * R5 + hh * 8192;
      uint32_t ph[4][8];
      #pragma unroll
      for (int i = 0; i < 32; i++) asm volatile("mov.b32 %0, 0;" : "=r"(ph[i >> 3][i & 7]));
      uint32_t shifted = 0;
      asm volatile("" : "+r"(shifted));
      #pragma unroll 1
      for (;;) {
        if (!(XP & 16) && shifted) dual_exp2_shifted(p, ph);
        uint32_t first = (shifted ^ 1) & !isq;
        asm volatile("" : "+r"(first));
        if (first) {
          if (wg == 0) { TSW(7); }
          bar_sync(NB_Q0 + wg, 256);
          const uint32_t da = dlo(SB0, 16) + (ao >> 4), db = dlo(SB0 + OFF_WPHIQ, 16);
          wg_fence();
          #pragma unroll
          for (int h = 0; h < 2; h++) {
            wgmma_ss_n32<0, 1, H128, H64>(p[h], da + 4 * h, db + 128 * h, 0);
            wgmma_sa_n32<0, 1, H128, H64>(p[h], da + 4 * h + 2, db + 128 * h + 64);
          }
          wg_commit();
          if (CAPL == 2) capture(1);
          wg_wait<0>();
        }
        fence_regs(p[0]); fence_regs(p[1]);
        uint32_t again = shifted;
        asm volatile("" : "+r"(again));
        if (again) break;
        float s2[4] = {0.f, 0.f, 0.f, 0.f};
        #pragma unroll
        for (int i = 0; i < 32; i++) { float& x = p[i >> 4][i & 15]; x *= cc[i >> 4][(i >> 1) & 1]; s2[i & 3] = fmaf(x, x, s2[i & 3]); }
        if (!__any_sync(~0u, !((s2[0] < ARG_LIM2) & (s2[1] < ARG_LIM2) & (s2[2] < ARG_LIM2) & (s2[3] < ARG_LIM2)))) break;
        shifted = 1;
      }
      if (e == 1 || e == 2) bar_sync(NB_TOK + e - 1, 256);
      TK(64 + 4 * turn);
      float ac[4][20];
      auto numer = [&](int h) {
        const uint32_t (*f)[8] = &ph[2 * h];
        const uint32_t db = dlo(SB0 + OFF_KVZ, 128) + (half ? e : h) * 320;
        wg_fence();
        #pragma unroll
        for (int i = 0; i < 2; i++) {
          wgmma_rz_n40<1, dhi(256, 0)>(ac[2*h+i], f[i][0], f[i][1], f[i][2], f[i][3], db + i * 160);
          wgmma_ra_n40<1, dhi(256, 0)>(ac[2*h+i], f[i][4], f[i][5], f[i][6], f[i][7], db + (i * 160 + 80));
        }
        wg_commit();
      };
      const uint32_t oa = (16 * wp + g) * 128 + (((lane & 3) ^ g) << 4);
      auto finish = [&](int h) {
        const float* ap = ac[2 * h]; const float* am = ac[2 * h + 1];
        const float ip0 = rcp(ap[17]), im0 = rcp(am[17]), ip1 = rcp(ap[19]), im1 = rcp(am[19]);
        const float d0 = rcp(fmaf(ap[16], ip0, fmaf(am[16], im0, 1e-6f))), d1 = rcp(fmaf(ap[18], ip1, fmaf(am[18], im1, 1e-6f)));
        const float a0 = ip0 * d0, b0 = im0 * d0, a1 = ip1 * d1, b1 = im1 * d1;
        #pragma unroll
        for (int r = 0; r < 2; r++) {
          const float a = r ? a1 : a0, b = r ? b1 : b0;
          uint32_t w[4];
          #pragma unroll
          for (int k = 0; k < 4; k++) w[k] = pack_bf16(fmaf(ap[4*k+2*r], a, am[4*k+2*r] * b), fmaf(ap[4*k+2*r+1], a, am[4*k+2*r+1] * b));
          const uint32_t off = (oa ^ ((half ? rank : h) << 6)) + r * 1024;
          st128_rlx(reinterpret_cast<uint8_t*>(G->o + (m128 * 16 + (half ? 2 * (j & 6) + 2 * hh + 1 : 2 * j)) * 8192 + (half ? h : hh) * 4096) + off, w[0], w[1], w[2], w[3]);
          if (!half) sts128(sb + ao + off, w[0], w[1], w[2], w[3]);
        }
        if ((half || h) && lane == 0) st32_rlx(&G->oflag[(m128 * 6 + (half ? 2 * e - 2 + h : hh)) * 32 + 4 * j + wp], 1);
      };
      if (!shifted) dual_exp2<true>(p[0], ph[0], ph[1]);
      numer(0);
      if (!shifted) dual_exp2<true>(p[1], ph[2], ph[3]);
      if (turn < 2) bar_arrive(NB_TOK + turn, 256);
      if (wg == 0) bar_sync(NB_DN, 256);
      numer(1);
      wg_wait<1>();
      TK(65 + 4 * turn);
      fence_regs(ac[0]); fence_regs(ac[1]);
      finish(0);
      wg_wait<0>();
      fence_regs(ac[2]); fence_regs(ac[3]);
      #pragma unroll
      for (int i = 0; i < 32; i++) asm volatile("mov.b32 %0, 0;" : "=f"(p[i >> 4][i & 15]));
      if (e == 2) project_r(3);
      finish(1);
      TK(66 + 4 * turn);
      if (!half) fence_async_smem();
      __syncwarp();
      if (lane == 0) mbar_arrive(sb + B_UO + 8 * e);
      wg_wait<0>();
      TK(67 + 4 * turn);
    }
    if (isq) cluster_arrive();
  }

  {
  int lane;
  asm volatile("mov.u32 %0, %%laneid;" : "=r"(lane));
  const int g = lane >> 2, q = lane & 3;
  if (wg < 2) {
    float h[64];
    {
      if (wg == 0) { TK(83); }
      #pragma unroll
      for (int i = 0; i < 32; i++) { h[2*i] = bf_lo(xr[i]); h[2*i+1] = bf_hi(xr[i]); }
      fence_regs(h);
      TK(80 + wg);
      const uint32_t emptyb = mapa(sb + B_EMPTY5, t & 1);
      uint32_t s = 1 + rank, ps = 0;
      mbar_wait2(sb + B_FULL5 + 8 * s, 1, sb + B_UO + 8 * wg, 0);
      if (wg == 0) { TSW(14); }
      #pragma unroll
      for (int i = 0; i < 16; i++) {
        if (wg == 1 && (i & 12) == TKW) { TK(84 + (i & 3)); }
        if (!KT && wg == 0) { TK(32 + i); }
        const uint32_t da = dlo(SB0, 16) + s * 2048 + wg * 512, db = dlo(SB0 + 16384, 8192) + s * 2048;
        wg_fence();
        #pragma unroll
        for (int k = 0; k < 4; k++) wgmma_sa_n128<0, 1, H128, H128>(h, da + k * 2, db + k * 128);
        wg_commit();
        const uint32_t ns = i ? (i + 2) % 6 : 2 - rank;
        const uint32_t b0 = sb + B_FULL5 + 8 * ns, p0 = (1 + (i + 2) / 6) & 1, b1 = sb + B_FULLA + 16 * ns + 8 * wg, p1 = ((i + 1) / 6) & 1;
        const bool here = i == 15 || mbar_test2(b0, p0, b1, p1);
        wg_wait<1>();
        if (!(((2 * REL + 1) >> i) & 1) && i < 14 && t < 2) mbar_arrive_remote(emptyb + 8 * ps, 1);
        if ((REL >> i) & 1) { wg_wait<0>(); if (t < 2) mbar_arrive_remote(emptyb + 8 * s, 1); }
        if (!here) mbar_wait2(b0, p0, b1, p1);
        ps = s; s = ns;
      }
    }
    cluster_arrive();
    float2 wr[16];
    #pragma unroll
    for (int i = 0; i < 16; i++) wr[i] = lds64f(sb + OFF_WR + 32 * i + 8 * q);
    const int r0 = 64 * wg + 16 * wp + g;
    float sum0, sum1, dot0, dot1, sq0, sq1;
    uint32_t redo = 0;
    asm volatile("" : "+r"(redo));
    #pragma unroll 1
    for (;;) {
    if (!(XP & 32) && redo) {
      wg_wait<0>();
      const uint32_t* xp = reinterpret_cast<const uint32_t*>(P.x + (size_t)(128 * m128 + r0) * DM + 128 * j) + q;
      #pragma unroll
      for (int i = 0; i < 32; i++) { const uint32_t v = xp[4 * (i >> 1) + (i & 1) * 4 * DM]; h[2*i] = bf_lo(v); h[2*i+1] = bf_hi(v); }
      #pragma unroll 1
      for (int ks = 0; ks < 64; ks++) {
        const int kb = ks >> 2, kk = 16 * (ks & 3);
        const bf16* op = G->o + (m128 * 16 + kb) * 8192 + r0 * 64 + 2 * q;
        const int o0 = ((kk >> 3) ^ g) << 3;
        const uint32_t* w = reinterpret_cast<const uint32_t*>(P.wo_p + (size_t)(((kb & 1) ? 256 * (kb >> 2) + 32 * (kb & 2) + 32 + 4 * (kk & 32) : 64 * kb + 2 * (kk & 32)) +
                                                                              ((kk & 16) >> 2) + 4 * (g & 6) + (g & 1)) * DM + 128 * j) + q;
        uint32_t b[32], a0, a1, a2, a3, it = 0;
        #pragma unroll
        for (int n = 0; n < 32; n++) b[n] = w[4 * (n >> 1) + (n & 1) * DM];
        do { a0 = ld32_rlx(op + o0); a1 = ld32_rlx(op + 512 + o0); a2 = ld32_rlx(op + (o0 ^ 8)); a3 = ld32_rlx(op + 512 + (o0 ^ 8)); }
        while (max(max(a0, a1), max(a2, a3)) == ~0u && ++it < POLL_LIMIT);
        __syncwarp();
        #pragma unroll
        for (int n = 0; n < 16; n++) mma16816(h[4*n], h[4*n+1], h[4*n+2], h[4*n+3], a0, a1, a2, a3, transpose8(b[2*n]), transpose8(b[2*n+1]));
      }
    }
    wg_wait<0>();
    fence_regs(h);
    if (wg == 0) { TSW(16); }
    sum0 = 0.f, sum1 = 0.f, dot0 = 0.f, dot1 = 0.f, sq0 = 0.f, sq1 = 0.f;
    #pragma unroll
    for (int i = 0; i < 16; i++) {
      sum0 += h[4*i] + h[4*i+1]; sum1 += h[4*i+2] + h[4*i+3];
      sq0 = fmaf(h[4*i], h[4*i], fmaf(h[4*i+1], h[4*i+1], sq0)); sq1 = fmaf(h[4*i+2], h[4*i+2], fmaf(h[4*i+3], h[4*i+3], sq1));
      dot0 = fmaf(h[4*i], wr[i].x, fmaf(h[4*i+1], wr[i].y, dot0)); dot1 = fmaf(h[4*i+2], wr[i].x, fmaf(h[4*i+3], wr[i].y, dot1));
    }
    if (!__any_sync(~0u, !redo & (h[0] != h[0] | h[2] != h[2]))) break;
    redo = 1;
    }
    float4* const rs = &G->rstat[128 * m128 + r0];
    {
      const bool up = q & 2;
      float a = up ? sum1 : sum0, b = up ? sq1 : sq0, d = up ? dot1 : dot0;
      a += __shfl_xor_sync(~0u, up ? sum0 : sum1, 2); b += __shfl_xor_sync(~0u, up ? sq0 : sq1, 2); d += __shfl_xor_sync(~0u, up ? dot0 : dot1, 2);
      a += __shfl_xor_sync(~0u, a, 1); b += __shfl_xor_sync(~0u, b, 1); d += __shfl_xor_sync(~0u, d, 1);
      if ((q & 1) == 0) red_add_f32x4(rs + 4 * q, a, b, d, 1.f);
    }
    if (TRKL == 0) bar_arrive(NB_G2E, 384);
    if (wg == 0) { TSW(24); }
    bar_sync(NB_WG01, 256);
    uint32_t wa[8][4][4];
    const uint32_t wb = sb + 16384 * (((uint32_t)FF_SLOT >> (4 * warp)) & 15) + ((lane & 7) + ((lane >> 4) << 3)) * 64 + ((((lane >> 3) & 1) ^ ((lane >> 1) & 3)) << 4);
    auto getw = [&](int ks) {
      #pragma unroll
      for (int m = 0; m < 4; m++) ldsm4t((wb ^ ((m & 1) << 5)) + (m >> 1) * 8192 + ks * 1024, wa[ks][m][0], wa[ks][m][1], wa[ks][m][2], wa[ks][m][3]);
    };
    if (GPRE && f < NFFN_L) mbar_wait(sb + B_F + 8 * warp, 0);
    if (warp == 7) { TK(60); }
    #pragma unroll
    for (int ks = 0; ks < GPRE; ks++) getw(ks);
    float rstd[2], bm[2];
    uint32_t best;
    {
      const float2 swa = lds64f(sb + OFF_SUMWR), swb = lds64f(sb + OFF_SUMWR + 8);
      const float sw = (swa.x + swa.y) + (swb.x + swb.y);
      uint4 a[2]; uint32_t it = 0, key[2];
      do { a[0] = ld128_rlx(rs); a[1] = ld128_rlx(rs + 8); } while (__any_sync(~0u, (a[0].w & a[1].w) != 0x41000000u) && ++it < POLL_LIMIT);
      #pragma unroll
      for (int i = 0; i < 2; i++) {
        const float mean = __uint_as_float(a[i].x) * (1.f / DM);
        rstd[i] = rsqrtf(fmaxf(__uint_as_float(a[i].y) * (1.f / DM) - mean * mean, 0.f) + 1e-5f);
        bm[i] = -mean * rstd[i];
        const uint32_t rr = __float_as_uint(fmaf(__uint_as_float(a[i].z), rstd[i], sw * bm[i]));
        key[i] = ((rr ^ ((uint32_t)((int32_t)rr >> 31) | 0x80000000u)) & ~2047u) | (2047 - 128 * m128 - r0 - 8 * i);
      }
      asm volatile("redux.sync.max.u32 %0, %1, 0xffffffff;" : "=r"(best) : "r"(max(key[0], key[1])));
    }
    if (TRKL == 2) bar_arrive(NB_G2E, 384);
    if (TRKL == 3 && wg == 0) bar_arrive(NB_G2E, 256);
    if (wg == 0) { TSW(17); }
    const int slot = m128 * 8 + warp, win = ~best & 15;
    if (lane < KR) st32_rlx(&G->key[(KR * j + lane) * 128 + slot], best);
    if ((win & 7) == g) {
      const bool up = win & 8;
      const float ra = up ? rstd[1] : rstd[0], rb = up ? bm[1] : bm[0];
      uint32_t x[16];
      #pragma unroll
      for (int i = 0; i < 16; i++) x[i] = pack_bf16(fmaf(up ? h[4*i+2] : h[4*i], ra, rb), fmaf(up ? h[4*i+3] : h[4*i+1], ra, rb));
      #pragma unroll
      for (int i = 0; i < 4; i++) st128_rlx(&G->cand[slot * 512 + 64 * j + 16 * i + 4 * q], x[4*i], x[4*i+1], x[4*i+2], x[4*i+3]);
    }
    __syncwarp();
    if (TRKL == 1) bar_arrive(NB_G2E, 384);
    if (wg == 0) { TSW(27); }
    {
      const float a0 = 1.f + rstd[0], b0 = bm[0], a1 = 1.f + rstd[1], b1 = bm[1];
      #pragma unroll
      for (int k = 0; k < 8; k++)
        stsm4(((sb + OFF_OUT + wg * 8192 + sa) ^ ((k & 3) << 5)) + (k >> 2) * 16384,
              pack_bf16(fmaf(h[8*k], a0, b0), fmaf(h[8*k+1], a0, b0)),     pack_bf16(fmaf(h[8*k+2], a1, b1), fmaf(h[8*k+3], a1, b1)),
              pack_bf16(fmaf(h[8*k+4], a0, b0), fmaf(h[8*k+5], a0, b0)),   pack_bf16(fmaf(h[8*k+6], a1, b1), fmaf(h[8*k+7], a1, b1)));
      fence_async_smem();
      __syncwarp();
      if (lane == 0) mbar_arrive(sb + B_OUT + 8 * wg);
    }
    if (wg == 0) { TSW(28); }
    {
      if (!GPRE && f < NFFN_L) mbar_wait(sb + B_F + 8 * warp, 0);
      #pragma unroll
      for (int ks = GPRE; ks < GRES; ks++) getw(ks);
      if (wg == 0) { TSW(15); }
      bar_sync(NB_XS, 384);
      uint4 xs[4];
      #pragma unroll
      for (int i = 0; i < 4; i++) xs[i] = lds128(sb + OFF_XSEL + 256 * warp + 64 * i + 16 * q);
      float d[4][4];
      #pragma unroll
      for (int ks = 0; ks < 8; ks++) {
        if (ks >= 1 && GRES + ks - 1 < 8) getw(GRES + ks - 1);
        #pragma unroll
        for (int m = 0; m < 4; m++) {
          if (ks == 0) { d[m][0] = 0.f; d[m][1] = 0.f; d[m][2] = 0.f; d[m][3] = 0.f; }
          mma16816(d[m][0], d[m][1], d[m][2], d[m][3], wa[ks][m][0], wa[ks][m][1], wa[ks][m][2], wa[ks][m][3],
                   (ks & 1) ? xs[ks >> 1].z : xs[ks >> 1].x, (ks & 1) ? xs[ks >> 1].w : xs[ks >> 1].y);
        }
      }
      if (q == 0) {
        #pragma unroll
        for (int m = 0; m < 8; m++) stsf(sb + OFF_GU + (8 * m + g) * 48 + 4 * warp, d[m >> 1][2 * (m & 1)]);
      }
      bar_arrive(NB_ACT, 384);
    }
    {
      const uint32_t ky = __float_as_uint(ldsf(sb + OFF_KEY));
      const int row = 2047 - (ky & 2047) - 128 * m128;
      if ((uint32_t)row < 128u) {
        const int l = tid >> 3, vi = (j & 1) + ((lane >> 2) & 1), e = 3 * vi + q - 4 * (j & 1);
        const float kr = __uint_as_float((ky & ~2047u) ^ ((ky >> 31) ? 0x80000000u : 0xfffff800u));
        const int col = 32 * (l & 3) + 16 * (e & 1) + 4 * (e & 2) + (l >> 2);
        const float sg = rcp(1.f + ex2(-LOG2E * kr));
        const uint32_t base = __float_as_uint(ldsf(sb + OFF_OUT + (col >> 6) * 16384 + row * 128 + ((((col >> 3) ^ row) & 7) << 4) + 2 * (col & 6)));
        const float4* yp = &G->yacc[(q * 3 + vi) * 128 + 32 * (j >> 1) + l];
        uint32_t it = 0;
        uint4 v;
        mbar_wait(sb + B_SD, 0);
        do { v = ld128_rlx(yp); } while (__any_sync(~0u, __uint_as_float(v.w) != (float)(NFFN / 4)) && ++it < POLL_LIMIT);
        float y0 = __uint_as_float(v.x), y1 = __uint_as_float(v.y), y2 = __uint_as_float(v.z);
        #pragma unroll
        for (int o = 1; o < 4; o <<= 1) { y0 += __shfl_xor_sync(~0u, y0, o); y1 += __shfl_xor_sync(~0u, y1, o); y2 += __shfl_xor_sync(~0u, y2, o); }
        if (q < 3 && (uint32_t)e < 4u)
          P.out_p[(size_t)(128 * m128 + row) * DM + 128 * j + col] = __float2bfloat16(fmaf(q == 0 ? y0 : q == 1 ? y1 : y2, sg, (col & 1) ? bf_hi(base) : bf_lo(base)));
      }
      if (c == 0 && tid == 0) st32_rlx(&G->epoch, __float_as_uint(ldsf(sb + OFF_EP)));
      if (warp == 0) { TSW(22); }
      if (wg == 0) { TDUMP(); }
    }
  }
  if (wg == 2) {
    uint32_t wf[16][2][4];
    {
      const uint32_t wb = sb + OFF_S + 16384 * (wp & 1) + ((lane & 7) + ((lane >> 4) << 3)) * 128 + ((((lane >> 3) & 1) ^ (lane & 7)) << 4);
      if (f < NFFN_L) mbar_wait(sb + B_WD + 8 * wp, 0);
      if (wp == 0) { TK(61); }
      #pragma unroll
      for (int i = 0; i < 32; i++) ldsm4t((wb ^ (((i >> 1) & 3) << 5)) + (i >> 3) * 4096 + (i & 1) * 2048, wf[i >> 1][i & 1][0], wf[i >> 1][i & 1][1], wf[i >> 1][i & 1][2], wf[i >> 1][i & 1][3]);
      fence_async_smem();
      __syncwarp();
      if (lane == 0) mbar_arrive(sb + B_WC + 8 * wp);
      if (wp == 0) { TK(62); }
    }
    bar_sync(NB_G2E, TRKL == 3 ? 256 : 384);
    {
      uint32_t cur = 0;
      uint4 v;
      #pragma unroll 1
      for (uint32_t it = 0; it < POLL_LIMIT; it++) {
        const uint4 kx = ld128_rlx(&G->key[(KSEL & (8 * KR - 1)) * 128 + 4 * lane]);
        v = ld128_rlx(&G->cand[((~cur >> 4) & 127) * 512 + 4 * t]);
        uint32_t best;
        asm volatile("redux.sync.max.u32 %0, %1, 0xffffffff;" : "=r"(best) : "r"(max(max(kx.x, kx.y), max(kx.z, kx.w))));
        if (!__any_sync(~0u, min(min(kx.x, kx.y), min(kx.z, kx.w)) == 0 || v.w == ~0u) && best == cur) break;
        cur = best;
      }
      sts128(sb + OFF_XSEL + 16 * t, v.x, v.y, v.z, v.w);
      sts32(sb + OFF_KEY, cur);
      bar_arrive(NB_XS, 384);
      TSW(18);
      bar_sync(NB_ACT, 384);
    }
    float gu[2];
    #pragma unroll
    for (int i = 0; i < 2; i++) {
      const uint4 v0 = lds128(sb + OFF_GU + (32 * i + lane) * 48), v1 = lds128(sb + OFF_GU + (32 * i + lane) * 48 + 16);
      gu[i] = ((__uint_as_float(v0.x) + __uint_as_float(v0.y)) + (__uint_as_float(v0.z) + __uint_as_float(v0.w))) +
              ((__uint_as_float(v1.x) + __uint_as_float(v1.y)) + (__uint_as_float(v1.z) + __uint_as_float(v1.w)));
    }
    const float act = gu[0] * gu[1] * rcp(1.f + ex2(-LOG2E * gu[0]));
    const uint32_t ap = pack_bf16(act, __shfl_down_sync(~0u, act, 1));
    uint32_t bf[4];
    #pragma unroll
    for (int i = 0; i < 4; i++) bf[i] = __shfl_sync(~0u, ap, 2 * q + 8 * i);
    TSW(20);
    float d[16][4];
    #pragma unroll
    for (int k = 0; k < 2; k++)
      #pragma unroll
      for (int i = 0; i < 16; i++) {
        if (k == 0) { d[i][0] = 0.f; d[i][1] = 0.f; d[i][2] = 0.f; d[i][3] = 0.f; }
        mma16816(d[i][0], d[i][1], d[i][2], d[i][3], wf[i][k][0], wf[i][k][1], wf[i][k][2], wf[i][k][3], bf[2*k], bf[2*k+1]);
      }
    float y[9];
    #pragma unroll
    for (int e = 0; e < 8; e++) {
      const int n = 2 * (e & 4) + (e & 1);
      const float lo = (q & 1) ? d[n + 2][e & 2] : d[n][e & 2], hi = (q & 1) ? d[n + 6][e & 2] : d[n + 4][e & 2];
      y[e] = (q & 2) ? hi : lo;
    }
    y[8] = 0.f;
    if (f < NFFN) {
      #pragma unroll
      for (int i = 0; i < 3; i++) red_add_f32x4(&G->yacc[((f & 3) * 3 + i) * 128 + t], y[3*i], y[3*i+1], y[3*i+2], 1.f);
    }
    TSW(21);
  }
  }
  cluster_wait();
}

typedef CUresult (*EncodeFn)(CUtensorMap*, CUtensorMapDataType, cuuint32_t, void*, const cuuint64_t*, const cuuint64_t*,
                             const cuuint32_t*, const cuuint32_t*, CUtensorMapInterleave, CUtensorMapSwizzle,
                             CUtensorMapL2promotion, CUtensorMapFloatOOBfill);

void make_map(EncodeFn enc, CUtensorMap* m, const void* p, int n, const cuuint64_t* dims, const cuuint64_t* str, const cuuint32_t* box,
              CUtensorMapSwizzle sw, CUtensorMapL2promotion promo) {
  cuuint32_t es[5] = {1, 1, 1, 1, 1};
  enc(m, CU_TENSOR_MAP_DATA_TYPE_BFLOAT16, n, const_cast<void*>(p), dims, str, box, es, CU_TENSOR_MAP_INTERLEAVE_NONE, sw, promo,
      CU_TENSOR_MAP_FLOAT_OOB_FILL_NONE);
}
void map2(EncodeFn enc, CUtensorMap* m, const void* p, uint64_t cols, uint64_t rows, uint32_t bc, uint32_t br, CUtensorMapSwizzle sw,
          CUtensorMapL2promotion promo) {
  const cuuint64_t dims[2] = {cols, rows}, str[1] = {cols * 2};
  const cuuint32_t box[2] = {bc, br};
  make_map(enc, m, p, 2, dims, str, box, sw, promo);
}
void map3(EncodeFn enc, CUtensorMap* m, const void* p, uint64_t cols, uint64_t rows, uint32_t br, uint32_t nb) {
  const cuuint64_t dims[3] = {64, rows, cols / 64}, str[2] = {cols * 2, 128};
  const cuuint32_t box[3] = {64, br, nb};
  make_map(enc, m, p, 3, dims, str, box, CU_TENSOR_MAP_SWIZZLE_128B, CU_TENSOR_MAP_L2_PROMOTION_L2_128B);
}

}

extern "C" void kernel_launch(void* const* d_in, const int* in_sizes, int n_in, void* d_out, int out_size) {
  (void)in_sizes; (void)n_in; (void)out_size;
  static EncodeFn enc = nullptr;
  static void* o_ptr = nullptr;
  if (!enc) {
    void* f = nullptr; cudaDriverEntryPointQueryResult qr;
    cudaGetDriverEntryPoint("cuTensorMapEncodeTiled", &f, cudaEnableDefault, &qr);
    enc = (EncodeFn)f;
    cudaGetSymbolAddress(&o_ptr, g_scr);
    cudaFuncSetAttribute(fused_kernel, cudaFuncAttributeMaxDynamicSharedMemorySize, SMEM_BYTES);
  }
  const bf16* x = (const bf16*)d_in[0];
  const bf16* wqkv = (const bf16*)d_in[1];
  const bf16* wphi = (const bf16*)d_in[2];
  const bf16* wo = (const bf16*)d_in[3];
  const bf16* wr = (const bf16*)d_in[5];
  const bf16* wgate = (const bf16*)d_in[6];
  const bf16* wup = (const bf16*)d_in[7];
  const bf16* wdown = (const bf16*)d_in[8];
  Params P;
  const CUtensorMapSwizzle S128 = CU_TENSOR_MAP_SWIZZLE_128B, S64 = CU_TENSOR_MAP_SWIZZLE_64B;
  const CUtensorMapL2promotion L128 = CU_TENSOR_MAP_L2_PROMOTION_L2_128B, L256 = CU_TENSOR_MAP_L2_PROMOTION_L2_256B,
                               L64 = CU_TENSOR_MAP_L2_PROMOTION_L2_64B;
  map2(enc, &P.x128, x, DM, SEQ, 64, 128, S128, L256);
  map2(enc, &P.x64, x, DM, SEQ, 64, 64, S128, L128);
  {
    const cuuint64_t dims[4] = {64, DM, 16, 3}, str[3] = {6 * DM, 128, 2 * DM};
    const cuuint32_t box[4] = {64, 64, 1, 2};
    make_map(enc, &P.wkv, wqkv, 4, dims, str, box, S128, L128);
  }
  map3(enc, &P.wq, wqkv, 3 * DM, DM, 64, 2);
  for (int i = 0; i < 2; i++) {
    const cuuint64_t dims[5] = {DM, (cuuint64_t)(DM - 94 - 64 * i), 4, 4, 2}, str[4] = {2 * DM, 16 * DM, 4 * DM, (cuuint64_t)(128 * DM) << i};
    const cuuint32_t box[5] = {64, 2, 4, 4, 2};
    make_map(enc, &P.wo[i], wo, 5, dims, str, box, S128, L128);
  }
  map3(enc, &P.wd, wdown, DM, FF, 32, 4);
  map2(enc, &P.wg, wgate, FF, DM, 32, 128, S64, L64);
  map2(enc, &P.wu, wup, FF, DM, 32, 128, S64, L64);
  map2(enc, &P.tg, wgate, FF, DM, 8, 16, CU_TENSOR_MAP_SWIZZLE_NONE, L128);
  map2(enc, &P.tu, wup, FF, DM, 8, 16, CU_TENSOR_MAP_SWIZZLE_NONE, L128);
  map2(enc, &P.td, wdown, 128, FF * 8, 8, 16, CU_TENSOR_MAP_SWIZZLE_NONE, L256);
  map2(enc, &P.xs, x, DM, SEQ, 128, 16, CU_TENSOR_MAP_SWIZZLE_NONE, L256);
  map2(enc, &P.ws, wqkv, 3 * DM, DM, 16, 128, CU_TENSOR_MAP_SWIZZLE_NONE, L128);
  map2(enc, &P.qs, wqkv, 3 * DM, DM, 32, 128, CU_TENSOR_MAP_SWIZZLE_NONE, L64);
  map2(enc, &P.out, d_out, DM, SEQ, 64, 16, S128, L128);
  map2(enc, &P.phi, wphi, 32, 1024, 32, 32, S64, L64);
  P.x = x; P.wqkv = wqkv; P.wo_p = wo; P.wd_p = wdown; P.wg_p = wgate; P.wu_p = wup; P.wr = wr; P.out_p = (bf16*)d_out; P.g = (Scratch*)o_ptr; P.zero = 0;

  cudaLaunchConfig_t cfg = {};
  cfg.gridDim = dim3(128); cfg.blockDim = dim3(512); cfg.dynamicSmemBytes = SMEM_BYTES; cfg.stream = cudaStreamPerThread;
  cudaLaunchAttribute at[1];
  at[0].id = cudaLaunchAttributeClusterDimension; at[0].val.clusterDim.x = 2; at[0].val.clusterDim.y = 1; at[0].val.clusterDim.z = 1;
  cfg.attrs = at; cfg.numAttrs = 1;
  cudaLaunchKernelEx(&cfg, fused_kernel, P);
}
```

```cpp
#include <cuda_runtime.h>
#include <cuda.h>
#include <cuda_bf16.h>
#include <stdint.h>

namespace {

typedef __nv_bfloat16 bf16;

__device__ __forceinline__ uint32_t smem_u32(const void* p){ return (uint32_t)__cvta_generic_to_shared(p); }
__device__ __forceinline__ void mbar_init(uint32_t bar, uint32_t cnt){ asm volatile("mbarrier.init.shared::cta.b64 [%0], %1;"::"r"(bar),"r"(cnt):"memory"); }
__device__ __forceinline__ void mbar_expect_tx(uint32_t bar, uint32_t bytes){ asm volatile("mbarrier.arrive.expect_tx.shared::cta.b64 _, [%0], %1;"::"r"(bar),"r"(bytes):"memory"); }
__device__ __forceinline__ void mbar_arrive(uint32_t bar){ asm volatile("mbarrier.arrive.shared::cta.b64 _, [%0];"::"r"(bar):"memory"); }
__device__ __forceinline__ uint32_t mapa(uint32_t addr, uint32_t cta){ uint32_t r; asm volatile("mapa.shared::cluster.u32 %0, %1, %2;":"=r"(r):"r"(addr),"r"(cta)); return r; }
__device__ __forceinline__ void mbar_arrive_at(uint32_t bar, uint32_t cta, uint32_t cnt){
  asm volatile("{\n.reg .b32 ra;\nmapa.shared::cluster.u32 ra, %0, %1;\nmbarrier.arrive.shared::cluster.b64 _, [ra], %2;\n}\n"::"r"(bar),"r"(cta),"r"(cnt):"memory"); }
__device__ __forceinline__ void mbar_arrive_remote(uint32_t cluster_addr, uint32_t cnt){
  asm volatile("mbarrier.arrive.shared::cluster.b64 _, [%0], %1;"::"r"(cluster_addr),"r"(cnt):"memory"); }
__device__ __forceinline__ void mbar_wait(uint32_t bar, uint32_t parity){
  asm volatile("{\n.reg .pred p;\n.reg .u32 c;\nmov.u32 c, 0;\nLW:\nmbarrier.try_wait.parity.shared::cta.b64 p, [%0], %1;\n@p bra LD;\nadd.u32 c, c, 1;\nsetp.lt.u32 p, c, 2000000;\n@p bra LW;\ntrap;\nLD:\n}\n"::"r"(bar),"r"(parity):"memory"); }
__device__ __forceinline__ void mbar_wait2(uint32_t bar0, uint32_t par0, uint32_t bar1, uint32_t par1){
  asm volatile("{\n.reg .pred p, q;\n.reg .u32 c;\nmov.u32 c, 0;\nLW:\nmbarrier.try_wait.parity.shared::cta.b64 p, [%0], %1;\nmbarrier.try_wait.parity.shared::cta.b64 q, [%2], %3;\nand.pred p, p, q;\n@p bra LD;\nadd.u32 c, c, 1;\nsetp.lt.u32 p, c, 2000000;\n@p bra LW;\ntrap;\nLD:\n}\n"::"r"(bar0),"r"(par0),"r"(bar1),"r"(par1):"memory"); }
__device__ __forceinline__ bool mbar_test2(uint32_t bar0, uint32_t par0, uint32_t bar1, uint32_t par1){
  uint32_t r;
  asm volatile("{\n.reg .pred p, q;\nmbarrier.test_wait.parity.shared::cta.b64 p, [%1], %2;\nmbarrier.test_wait.parity.shared::cta.b64 q, [%3], %4;\nand.pred p, p, q;\nselp.u32 %0, 1, 0, p;\n}\n":"=r"(r):"r"(bar0),"r"(par0),"r"(bar1),"r"(par1):"memory");
  return r; }
__device__ __forceinline__ void tma_2d(uint32_t dst, const CUtensorMap* m, int c0, int c1, uint32_t bar){
  asm volatile("cp.async.bulk.tensor.2d.shared::cluster.global.mbarrier::complete_tx::bytes [%0], [%1, {%3, %4}], [%2];"::"r"(dst),"l"(m),"r"(bar),"r"(c0),"r"(c1):"memory"); }
__device__ __forceinline__ void tma_2d_mc(uint32_t dst, const CUtensorMap* m, int c0, int c1, uint32_t bar){
  asm volatile("cp.async.bulk.tensor.2d.shared::cluster.global.mbarrier::complete_tx::bytes.multicast::cluster [%0], [%1, {%3, %4}], [%2], %5;"::"r"(dst),"l"(m),"r"(bar),"r"(c0),"r"(c1),"h"((uint16_t)3):"memory"); }
__device__ __forceinline__ void tma_2d_mc_h(uint32_t dst, const CUtensorMap* m, int c0, int c1, uint32_t bar, uint64_t pol){
  asm volatile("cp.async.bulk.tensor.2d.shared::cluster.global.mbarrier::complete_tx::bytes.multicast::cluster.L2::cache_hint [%0], [%1, {%3, %4}], [%2], %5, %6;"::"r"(dst),"l"(m),"r"(bar),"r"(c0),"r"(c1),"h"((uint16_t)3),"l"(pol):"memory"); }
__device__ __forceinline__ void tma_4d(uint32_t dst, const CUtensorMap* m, int c0, int c1, int c2, int c3, uint32_t bar){
  asm volatile("cp.async.bulk.tensor.4d.shared::cluster.global.mbarrier::complete_tx::bytes [%0], [%1, {%3, %4, %5, %6}], [%2];"::"r"(dst),"l"(m),"r"(bar),"r"(c0),"r"(c1),"r"(c2),"r"(c3):"memory"); }
__device__ __forceinline__ uint64_t policy_evict_first(){ uint64_t p; asm volatile("createpolicy.fractional.L2::evict_first.b64 %0, 1.0;":"=l"(p)); return p; }
__device__ __forceinline__ uint64_t policy_evict_normal(){ uint64_t p; asm("createpolicy.fractional.L2::evict_normal.b64 %0, 1.0;":"=l"(p)); return p; }
__device__ __forceinline__ void tma_3d_h(uint32_t dst, const CUtensorMap* m, int c0, int c1, int c2, uint32_t bar, uint64_t pol){
  asm volatile("cp.async.bulk.tensor.3d.shared::cluster.global.mbarrier::complete_tx::bytes.L2::cache_hint [%0], [%1, {%3, %4, %5}], [%2], %6;"::"r"(dst),"l"(m),"r"(bar),"r"(c0),"r"(c1),"r"(c2),"l"(pol):"memory"); }
__device__ __forceinline__ void tma_4d_h(uint32_t dst, const CUtensorMap* m, int c0, int c1, int c2, int c3, uint32_t bar, uint64_t pol){
  asm volatile("cp.async.bulk.tensor.4d.shared::cluster.global.mbarrier::complete_tx::bytes.L2::cache_hint [%0], [%1, {%3, %4, %5, %6}], [%2], %7;"::"r"(dst),"l"(m),"r"(bar),"r"(c0),"r"(c1),"r"(c2),"r"(c3),"l"(pol):"memory"); }
__device__ __forceinline__ void red_add_f32x4(float4* p, float x, float y, float z, float w){ asm volatile("red.relaxed.gpu.global.add.v4.f32 [%0], {%1,%2,%3,%4};"::"l"(p),"f"(x),"f"(y),"f"(z),"f"(w):"memory"); }
__device__ __forceinline__ void tma_5d_h(uint32_t dst, const CUtensorMap* m, int c0, int c1, uint32_t bar, uint64_t pol){
  asm volatile("cp.async.bulk.tensor.5d.shared::cluster.global.mbarrier::complete_tx::bytes.L2::cache_hint [%0], [%1, {%3, %4, 0, 0, 0}], [%2], %5;"::"r"(dst),"l"(m),"r"(bar),"r"(c0),"r"(c1),"l"(pol):"memory"); }
__device__ __forceinline__ void tma_store_2d(const CUtensorMap* m, int c0, int c1, uint32_t src){
  asm volatile("cp.async.bulk.tensor.2d.global.shared::cta.bulk_group [%0, {%2, %3}], [%1];"::"l"(m),"r"(src),"r"(c0),"r"(c1):"memory"); }
__device__ __forceinline__ void bulk_commit(){ asm volatile("cp.async.bulk.commit_group;":::"memory"); }
__device__ __forceinline__ void bulk_wait_all(){ asm volatile("cp.async.bulk.wait_group 0;":::"memory"); }
__device__ __forceinline__ void fence_async_global(){ asm volatile("fence.proxy.async.global;":::"memory"); }
__device__ __forceinline__ bool elect_one(){ uint32_t p; asm volatile("{\n.reg .pred P;\nelect.sync _|P, 0xffffffff;\nselp.b32 %0, 1, 0, P;\n}\n":"=r"(p)); return p; }
__device__ __forceinline__ void bulk_prefetch(const void* p, uint32_t bytes){
  asm volatile("cp.async.bulk.prefetch.L2.global [%0], %1;"::"l"(p),"r"(bytes):"memory"); }
__device__ __forceinline__ void bulk_s2peer(uint32_t dst_cluster, uint32_t src, uint32_t bytes, uint32_t bar_cluster){
  asm volatile("cp.async.bulk.shared::cluster.shared::cta.mbarrier::complete_tx::bytes [%0], [%1], %2, [%3];"::"r"(dst_cluster),"r"(src),"r"(bytes),"r"(bar_cluster):"memory"); }
__device__ __forceinline__ void prefetch_map(const CUtensorMap* m){ asm volatile("prefetch.tensormap [%0];"::"l"(m):"memory"); }
__device__ __forceinline__ void fence_async_smem(){ asm volatile("fence.proxy.async.shared::cta;":::"memory"); }
__device__ __forceinline__ void fence_acquire_gpu(){ asm volatile("fence.acquire.gpu;":::"memory"); }
__device__ __forceinline__ void fence_gpu(){ asm volatile("fence.acq_rel.gpu;":::"memory"); }
__device__ __forceinline__ void wg_fence(){ asm volatile("wgmma.fence.sync.aligned;":::"memory"); }
__device__ __forceinline__ void wg_commit(){ asm volatile("wgmma.commit_group.sync.aligned;":::"memory"); }
template<int N> __device__ __forceinline__ void wg_wait(){ asm volatile("wgmma.wait_group.sync.aligned %0;"::"n"(N):"memory"); }
template<int N> __device__ __forceinline__ void fence_regs(float (&d)[N]){
  #pragma unroll
  for(int i=0;i<N;i++) asm volatile("":"+f"(d[i])::"memory"); }
__device__ __forceinline__ void bar_sync(int id, int n){ asm volatile("bar.sync %0, %1;"::"r"(id),"r"(n):"memory"); }
__device__ __forceinline__ void bar_arrive(int id, int n){ asm volatile("bar.arrive %0, %1;"::"r"(id),"r"(n):"memory"); }
__device__ __forceinline__ void cluster_arrive(){ asm volatile("barrier.cluster.arrive.relaxed.aligned;":::"memory"); }
__device__ __forceinline__ void cluster_wait(){ asm volatile("barrier.cluster.wait.aligned;":::"memory"); }
__host__ __device__ constexpr uint32_t dlo(uint32_t addr, uint32_t lbo){ return (addr >> 4) | ((lbo >> 4) << 16); }
__host__ __device__ constexpr uint32_t dhi(uint32_t sbo, uint32_t sw){ return (sbo >> 4) | (sw << 30); }
constexpr uint32_t H128 = dhi(1024, 1), H64 = dhi(512, 2), H0 = dhi(128, 0);
__device__ __forceinline__ uint32_t pack_bf16(float lo, float hi){ uint32_t r; asm("cvt.rn.bf16x2.f32 %0, %1, %2;":"=r"(r):"f"(hi),"f"(lo)); return r; }
__device__ __forceinline__ float bf_lo(uint32_t v){ return __uint_as_float(v<<16); }
__device__ __forceinline__ float bf_hi(uint32_t v){ return __uint_as_float(v&0xffff0000u); }
__device__ __forceinline__ float ex2(float x){ float r; asm("ex2.approx.ftz.f32 %0, %1;":"=f"(r):"f"(x)); return r; }
__device__ __forceinline__ float rcp(float x){ float r; asm("rcp.approx.ftz.f32 %0, %1;":"=f"(r):"f"(x)); return r; }
__device__ __forceinline__ void stsm4(uint32_t addr, uint32_t a, uint32_t b, uint32_t c, uint32_t d){
  asm volatile("stmatrix.sync.aligned.m8n8.x4.shared.b16 [%0], {%1,%2,%3,%4};"::"r"(addr),"r"(a),"r"(b),"r"(c),"r"(d)); }
__device__ __forceinline__ void stsm2(uint32_t addr, uint32_t a, uint32_t b){
  asm volatile("stmatrix.sync.aligned.m8n8.x2.shared.b16 [%0], {%1,%2};"::"r"(addr),"r"(a),"r"(b)); }
__device__ __forceinline__ void mma16816(float& d0, float& d1, float& d2, float& d3, uint32_t a0, uint32_t a1, uint32_t a2, uint32_t a3, uint32_t b0, uint32_t b1){
  asm volatile("mma.sync.aligned.m16n8k16.row.col.f32.bf16.bf16.f32 {%0,%1,%2,%3}, {%4,%5,%6,%7}, {%8,%9}, {%0,%1,%2,%3};"
               : "+f"(d0), "+f"(d1), "+f"(d2), "+f"(d3) : "r"(a0), "r"(a1), "r"(a2), "r"(a3), "r"(b0), "r"(b1)); }
__device__ __forceinline__ uint32_t transpose8(uint32_t a){ uint32_t r; asm volatile("movmatrix.sync.aligned.m8n8.trans.b16 %0, %1;":"=r"(r):"r"(a)); return r; }
__device__ __forceinline__ void ldsm4(uint32_t addr, uint32_t& a, uint32_t& b, uint32_t& c, uint32_t& d){
  asm volatile("ldmatrix.sync.aligned.m8n8.x4.shared.b16 {%0,%1,%2,%3}, [%4];":"=r"(a),"=r"(b),"=r"(c),"=r"(d):"r"(addr):"memory"); }
__device__ __forceinline__ void ldsm4t(uint32_t addr, uint32_t& a, uint32_t& b, uint32_t& c, uint32_t& d){
  asm volatile("ldmatrix.sync.aligned.m8n8.x4.trans.shared.b16 {%0,%1,%2,%3}, [%4];":"=r"(a),"=r"(b),"=r"(c),"=r"(d):"r"(addr):"memory"); }
__device__ __forceinline__ void sts32(uint32_t a, uint32_t v){ asm volatile("st.shared.b32 [%0], %1;"::"r"(a),"r"(v):"memory"); }
__device__ __forceinline__ void stsf(uint32_t a, float v){ asm volatile("st.shared.f32 [%0], %1;"::"r"(a),"f"(v):"memory"); }
__device__ __forceinline__ void sts64(uint32_t a, uint32_t x, uint32_t y){ asm volatile("st.shared.v2.b32 [%0], {%1,%2};"::"r"(a),"r"(x),"r"(y):"memory"); }
__device__ __forceinline__ void sts128(uint32_t a, uint32_t x, uint32_t y, uint32_t z, uint32_t w){ asm volatile("st.shared.v4.b32 [%0], {%1,%2,%3,%4};"::"r"(a),"r"(x),"r"(y),"r"(z),"r"(w):"memory"); }
__device__ __forceinline__ float ldsf(uint32_t a){ float v; asm volatile("ld.shared.f32 %0, [%1];":"=f"(v):"r"(a):"memory"); return v; }
__device__ __forceinline__ float2 lds64f(uint32_t a){ float2 v; asm volatile("ld.shared.v2.f32 {%0,%1}, [%2];":"=f"(v.x),"=f"(v.y):"r"(a):"memory"); return v; }
__device__ __forceinline__ uint4 lds128(uint32_t a){ uint4 v; asm volatile("ld.shared.v4.u32 {%0,%1,%2,%3}, [%4];":"=r"(v.x),"=r"(v.y),"=r"(v.z),"=r"(v.w):"r"(a):"memory"); return v; }
__device__ __forceinline__ uint4 ld128_keep(const void* p){ uint4 v; asm volatile("ld.global.v4.u32 {%0,%1,%2,%3}, [%4];":"=r"(v.x),"=r"(v.y),"=r"(v.z),"=r"(v.w):"l"(p):"memory"); return v; }
__device__ __forceinline__ uint4 ld128_rlx(const void* p){ uint4 v; asm volatile("ld.relaxed.gpu.global.v4.u32 {%0,%1,%2,%3}, [%4];":"=r"(v.x),"=r"(v.y),"=r"(v.z),"=r"(v.w):"l"(p):"memory"); return v; }
__device__ __forceinline__ uint32_t ld32_rlx(const void* p){ uint32_t v; asm volatile("ld.relaxed.gpu.global.u32 %0, [%1];":"=r"(v):"l"(p):"memory"); return v; }
__device__ __forceinline__ void st128_rlx(void* p, uint32_t x, uint32_t y, uint32_t z, uint32_t w){ asm volatile("st.relaxed.gpu.global.v4.u32 [%0], {%1,%2,%3,%4};"::"l"(p),"r"(x),"r"(y),"r"(z),"r"(w):"memory"); }
__device__ __forceinline__ void st64_rlx(void* p, uint32_t x, uint32_t y){ asm volatile("st.relaxed.gpu.global.v2.u32 [%0], {%1,%2};"::"l"(p),"r"(x),"r"(y):"memory"); }
__device__ __forceinline__ void st32_rlx(void* p, uint32_t x){ asm volatile("st.relaxed.gpu.global.u32 [%0], %1;"::"l"(p),"r"(x):"memory"); }
__device__ __forceinline__ void flags_wait(uint32_t& missing, const uint32_t* p, uint32_t need){
  asm volatile("{\n.reg .pred p;\n.reg .u32 c, v;\nmov.u32 c, 0;\nLW:\nand.b32 v, %0, %2;\nsetp.eq.u32 p, v, 0;\n@p bra.uni LD;\nld.relaxed.gpu.global.u32 v, [%1];\nsetp.eq.u32 p, v, 0;\n"
               "vote.sync.ballot.b32 %0, p, 0xffffffff;\nadd.u32 c, c, 1;\nsetp.lt.u32 p, c, 4000000;\n@p bra.uni LW;\nLD:\n}\n":"+r"(missing):"l"(p),"r"(need):"memory"); }
__device__ __forceinline__ uint32_t tagw(float x, uint32_t t){ return (__float_as_uint(x) & ~3u) | t; }
__device__ __forceinline__ float untag(uint32_t w){ return __uint_as_float(w & ~3u); }

template<int TA, int TB, uint32_t HA, uint32_t HB> __device__ __forceinline__ void wgmma_ss_n128(float (&d)[64], uint32_t da, uint32_t db, int scale_d){
  asm volatile("{\n.reg .pred p;\n.reg .b64 a, b;\nsetp.ne.b32 p, %70, 0;\nmov.b64 a, {%64, %68};\nmov.b64 b, {%65, %69};\n"
  "wgmma.mma_async.sync.aligned.m64n128k16.f32.bf16.bf16 {%0, %1, %2, %3, %4, %5, %6, %7, %8, %9, %10, %11, %12, %13, %14, %15, %16, %17, %18, %19, %20, %21, %22, %23, %24, %25, %26, %27, %28, %29, %30, %31, %32, %33, %34, %35, %36, %37, %38, %39, %40, %41, %42, %43, %44, %45, %46, %47, %48, %49, %50, %51, %52, %53, %54, %55, %56, %57, %58, %59, %60, %61, %62, %63}, a, b, p, 1, 1, %66, %67;\n}\n"
  : "+f"(d[0]), "+f"(d[1]), "+f"(d[2]), "+f"(d[3]), "+f"(d[4]), "+f"(d[5]), "+f"(d[6]), "+f"(d[7]), "+f"(d[8]), "+f"(d[9]), "+f"(d[10]), "+f"(d[11]), "+f"(d[12]), "+f"(d[13]), "+f"(d[14]), "+f"(d[15]), "+f"(d[16]), "+f"(d[17]), "+f"(d[18]), "+f"(d[19]), "+f"(d[20]), "+f"(d[21]), "+f"(d[22]), "+f"(d[23]), "+f"(d[24]), "+f"(d[25]), "+f"(d[26]), "+f"(d[27]), "+f"(d[28]), "+f"(d[29]), "+f"(d[30]), "+f"(d[31]), "+f"(d[32]), "+f"(d[33]), "+f"(d[34]), "+f"(d[35]), "+f"(d[36]), "+f"(d[37]), "+f"(d[38]), "+f"(d[39]), "+f"(d[40]), "+f"(d[41]), "+f"(d[42]), "+f"(d[43]), "+f"(d[44]), "+f"(d[45]), "+f"(d[46]), "+f"(d[47]), "+f"(d[48]), "+f"(d[49]), "+f"(d[50]), "+f"(d[51]), "+f"(d[52]), "+f"(d[53]), "+f"(d[54]), "+f"(d[55]), "+f"(d[56]), "+f"(d[57]), "+f"(d[58]), "+f"(d[59]), "+f"(d[60]), "+f"(d[61]), "+f"(d[62]), "+f"(d[63])
  : "r"(da), "r"(db), "n"(TA), "n"(TB), "n"(HA), "n"(HB), "r"(scale_d));
}
template<int TA, int TB, uint32_t HA, uint32_t HB> __device__ __forceinline__ void wgmma_sa_n128(float (&d)[64], uint32_t da, uint32_t db){
  asm volatile("{\n.reg .pred p;\n.reg .b64 a, b;\nsetp.ne.b32 p, 1, 0;\nmov.b64 a, {%64, %68};\nmov.b64 b, {%65, %69};\n"
  "wgmma.mma_async.sync.aligned.m64n128k16.f32.bf16.bf16 {%0, %1, %2, %3, %4, %5, %6, %7, %8, %9, %10, %11, %12, %13, %14, %15, %16, %17, %18, %19, %20, %21, %22, %23, %24, %25, %26, %27, %28, %29, %30, %31, %32, %33, %34, %35, %36, %37, %38, %39, %40, %41, %42, %43, %44, %45, %46, %47, %48, %49, %50, %51, %52, %53, %54, %55, %56, %57, %58, %59, %60, %61, %62, %63}, a, b, p, 1, 1, %66, %67;\n}\n"
  : "+f"(d[0]), "+f"(d[1]), "+f"(d[2]), "+f"(d[3]), "+f"(d[4]), "+f"(d[5]), "+f"(d[6]), "+f"(d[7]), "+f"(d[8]), "+f"(d[9]), "+f"(d[10]), "+f"(d[11]), "+f"(d[12]), "+f"(d[13]), "+f"(d[14]), "+f"(d[15]), "+f"(d[16]), "+f"(d[17]), "+f"(d[18]), "+f"(d[19]), "+f"(d[20]), "+f"(d[21]), "+f"(d[22]), "+f"(d[23]), "+f"(d[24]), "+f"(d[25]), "+f"(d[26]), "+f"(d[27]), "+f"(d[28]), "+f"(d[29]), "+f"(d[30]), "+f"(d[31]), "+f"(d[32]), "+f"(d[33]), "+f"(d[34]), "+f"(d[35]), "+f"(d[36]), "+f"(d[37]), "+f"(d[38]), "+f"(d[39]), "+f"(d[40]), "+f"(d[41]), "+f"(d[42]), "+f"(d[43]), "+f"(d[44]), "+f"(d[45]), "+f"(d[46]), "+f"(d[47]), "+f"(d[48]), "+f"(d[49]), "+f"(d[50]), "+f"(d[51]), "+f"(d[52]), "+f"(d[53]), "+f"(d[54]), "+f"(d[55]), "+f"(d[56]), "+f"(d[57]), "+f"(d[58]), "+f"(d[59]), "+f"(d[60]), "+f"(d[61]), "+f"(d[62]), "+f"(d[63])
  : "r"(da), "r"(db), "n"(TA), "n"(TB), "n"(HA), "n"(HB));
}
template<int TA, int TB, uint32_t HA, uint32_t HB> __device__ __forceinline__ void wgmma_sa_n40(float (&d)[20], uint32_t da, uint32_t db){
  asm volatile("{\n.reg .pred p;\n.reg .b64 a, b;\nsetp.ne.b32 p, 1, 0;\nmov.b64 a, {%20, %24};\nmov.b64 b, {%21, %25};\n"
  "wgmma.mma_async.sync.aligned.m64n40k16.f32.bf16.bf16 {%0, %1, %2, %3, %4, %5, %6, %7, %8, %9, %10, %11, %12, %13, %14, %15, %16, %17, %18, %19}, a, b, p, 1, 1, %22, %23;\n}\n"
  : "+f"(d[0]), "+f"(d[1]), "+f"(d[2]), "+f"(d[3]), "+f"(d[4]), "+f"(d[5]), "+f"(d[6]), "+f"(d[7]), "+f"(d[8]), "+f"(d[9]), "+f"(d[10]), "+f"(d[11]), "+f"(d[12]), "+f"(d[13]), "+f"(d[14]), "+f"(d[15]), "+f"(d[16]), "+f"(d[17]), "+f"(d[18]), "+f"(d[19])
  : "r"(da), "r"(db), "n"(TA), "n"(TB), "n"(HA), "n"(HB));
}
template<int TA, int TB, uint32_t HA, uint32_t HB> __device__ __forceinline__ void wgmma_sz_n40(float (&d)[20], uint32_t da, uint32_t db){
  asm volatile("{\n.reg .pred p;\n.reg .b64 a, b;\nsetp.ne.b32 p, 0, 0;\nmov.b64 a, {%20, %24};\nmov.b64 b, {%21, %25};\n"
  "wgmma.mma_async.sync.aligned.m64n40k16.f32.bf16.bf16 {%0, %1, %2, %3, %4, %5, %6, %7, %8, %9, %10, %11, %12, %13, %14, %15, %16, %17, %18, %19}, a, b, p, 1, 1, %22, %23;\n}\n"
  : "=f"(d[0]), "=f"(d[1]), "=f"(d[2]), "=f"(d[3]), "=f"(d[4]), "=f"(d[5]), "=f"(d[6]), "=f"(d[7]), "=f"(d[8]), "=f"(d[9]), "=f"(d[10]), "=f"(d[11]), "=f"(d[12]), "=f"(d[13]), "=f"(d[14]), "=f"(d[15]), "=f"(d[16]), "=f"(d[17]), "=f"(d[18]), "=f"(d[19])
  : "r"(da), "r"(db), "n"(TA), "n"(TB), "n"(HA), "n"(HB));
}
template<int TA, int TB, uint32_t HA, uint32_t HB> __device__ __forceinline__ void wgmma_sa_n32(float (&d)[16], uint32_t da, uint32_t db){
  asm volatile("{\n.reg .pred p;\n.reg .b64 a, b;\nsetp.ne.b32 p, 1, 0;\nmov.b64 a, {%16, %20};\nmov.b64 b, {%17, %21};\n"
  "wgmma.mma_async.sync.aligned.m64n32k16.f32.bf16.bf16 {%0, %1, %2, %3, %4, %5, %6, %7, %8, %9, %10, %11, %12, %13, %14, %15}, a, b, p, 1, 1, %18, %19;\n}\n"
  : "+f"(d[0]), "+f"(d[1]), "+f"(d[2]), "+f"(d[3]), "+f"(d[4]), "+f"(d[5]), "+f"(d[6]), "+f"(d[7]), "+f"(d[8]), "+f"(d[9]), "+f"(d[10]), "+f"(d[11]), "+f"(d[12]), "+f"(d[13]), "+f"(d[14]), "+f"(d[15])
  : "r"(da), "r"(db), "n"(TA), "n"(TB), "n"(HA), "n"(HB));
}
template<int TA, int TB, uint32_t HA, uint32_t HB> __device__ __forceinline__ void wgmma_ss_n32(float (&d)[16], uint32_t da, uint32_t db, int scale_d){
  asm volatile("{\n.reg .pred p;\n.reg .b64 a, b;\nsetp.ne.b32 p, %22, 0;\nmov.b64 a, {%16, %20};\nmov.b64 b, {%17, %21};\n"
  "wgmma.mma_async.sync.aligned.m64n32k16.f32.bf16.bf16 {%0, %1, %2, %3, %4, %5, %6, %7, %8, %9, %10, %11, %12, %13, %14, %15}, a, b, p, 1, 1, %18, %19;\n}\n"
  : "+f"(d[0]), "+f"(d[1]), "+f"(d[2]), "+f"(d[3]), "+f"(d[4]), "+f"(d[5]), "+f"(d[6]), "+f"(d[7]), "+f"(d[8]), "+f"(d[9]), "+f"(d[10]), "+f"(d[11]), "+f"(d[12]), "+f"(d[13]), "+f"(d[14]), "+f"(d[15])
  : "r"(da), "r"(db), "n"(TA), "n"(TB), "n"(HA), "n"(HB), "r"(scale_d));
}
template<int TB, uint32_t HB> __device__ __forceinline__ void wgmma_ra_n32(float (&d)[16], uint32_t a0, uint32_t a1, uint32_t a2, uint32_t a3, uint32_t db){
  asm volatile("{\n.reg .pred p;\n.reg .b64 a, b;\nsetp.ne.b32 p, 1, 0;\nmov.b64 b, {%20, %22};\n"
  "wgmma.mma_async.sync.aligned.m64n32k16.f32.bf16.bf16 {%0, %1, %2, %3, %4, %5, %6, %7, %8, %9, %10, %11, %12, %13, %14, %15}, {%16,%17,%18,%19}, b, p, 1, 1, %21;\n}\n"
  : "+f"(d[0]), "+f"(d[1]), "+f"(d[2]), "+f"(d[3]), "+f"(d[4]), "+f"(d[5]), "+f"(d[6]), "+f"(d[7]), "+f"(d[8]), "+f"(d[9]), "+f"(d[10]), "+f"(d[11]), "+f"(d[12]), "+f"(d[13]), "+f"(d[14]), "+f"(d[15])
  : "r"(a0), "r"(a1), "r"(a2), "r"(a3), "r"(db), "n"(TB), "n"(HB));
}
template<int TB, uint32_t HB> __device__ __forceinline__ void wgmma_rs_n32(float (&d)[16], uint32_t a0, uint32_t a1, uint32_t a2, uint32_t a3, uint32_t db, int scale_d){
  asm volatile("{\n.reg .pred p;\n.reg .b64 a, b;\nsetp.ne.b32 p, %23, 0;\nmov.b64 b, {%20, %22};\n"
  "wgmma.mma_async.sync.aligned.m64n32k16.f32.bf16.bf16 {%0, %1, %2, %3, %4, %5, %6, %7, %8, %9, %10, %11, %12, %13, %14, %15}, {%16,%17,%18,%19}, b, p, 1, 1, %21;\n}\n"
  : "+f"(d[0]), "+f"(d[1]), "+f"(d[2]), "+f"(d[3]), "+f"(d[4]), "+f"(d[5]), "+f"(d[6]), "+f"(d[7]), "+f"(d[8]), "+f"(d[9]), "+f"(d[10]), "+f"(d[11]), "+f"(d[12]), "+f"(d[13]), "+f"(d[14]), "+f"(d[15])
  : "r"(a0), "r"(a1), "r"(a2), "r"(a3), "r"(db), "n"(TB), "n"(HB), "r"(scale_d));
}
template<int TB, uint32_t HB> __device__ __forceinline__ void wgmma_ra_n40(float (&d)[20], uint32_t a0, uint32_t a1, uint32_t a2, uint32_t a3, uint32_t db){
  asm volatile("{\n.reg .pred p;\n.reg .b64 a, b;\nsetp.ne.b32 p, 1, 0;\nmov.b64 b, {%24, %26};\n"
  "wgmma.mma_async.sync.aligned.m64n40k16.f32.bf16.bf16 {%0, %1, %2, %3, %4, %5, %6, %7, %8, %9, %10, %11, %12, %13, %14, %15, %16, %17, %18, %19}, {%20,%21,%22,%23}, b, p, 1, 1, %25;\n}\n"
  : "+f"(d[0]), "+f"(d[1]), "+f"(d[2]), "+f"(d[3]), "+f"(d[4]), "+f"(d[5]), "+f"(d[6]), "+f"(d[7]), "+f"(d[8]), "+f"(d[9]), "+f"(d[10]), "+f"(d[11]), "+f"(d[12]), "+f"(d[13]), "+f"(d[14]), "+f"(d[15]), "+f"(d[16]), "+f"(d[17]), "+f"(d[18]), "+f"(d[19])
  : "r"(a0), "r"(a1), "r"(a2), "r"(a3), "r"(db), "n"(TB), "n"(HB));
}
template<int TB, uint32_t HB> __device__ __forceinline__ void wgmma_rz_n40(float (&d)[20], uint32_t a0, uint32_t a1, uint32_t a2, uint32_t a3, uint32_t db){
  asm volatile("{\n.reg .pred p;\n.reg .b64 a, b;\nsetp.ne.b32 p, 0, 0;\nmov.b64 b, {%24, %26};\n"
  "wgmma.mma_async.sync.aligned.m64n40k16.f32.bf16.bf16 {%0, %1, %2, %3, %4, %5, %6, %7, %8, %9, %10, %11, %12, %13, %14, %15, %16, %17, %18, %19}, {%20,%21,%22,%23}, b, p, 1, 1, %25;\n}\n"
  : "=f"(d[0]), "=f"(d[1]), "=f"(d[2]), "=f"(d[3]), "=f"(d[4]), "=f"(d[5]), "=f"(d[6]), "=f"(d[7]), "=f"(d[8]), "=f"(d[9]), "=f"(d[10]), "=f"(d[11]), "=f"(d[12]), "=f"(d[13]), "=f"(d[14]), "=f"(d[15]), "=f"(d[16]), "=f"(d[17]), "=f"(d[18]), "=f"(d[19])
  : "r"(a0), "r"(a1), "r"(a2), "r"(a3), "r"(db), "n"(TB), "n"(HB));
}
template<int TB, uint32_t HB> __device__ __forceinline__ void wgmma_rz_n8(float (&d)[4], uint32_t a0, uint32_t a1, uint32_t a2, uint32_t a3, uint32_t db){
  asm volatile("{\n.reg .pred p;\n.reg .b64 a, b;\nsetp.ne.b32 p, 0, 0;\nmov.b64 b, {%8, %10};\n"
  "wgmma.mma_async.sync.aligned.m64n8k16.f32.bf16.bf16 {%0, %1, %2, %3}, {%4,%5,%6,%7}, b, p, 1, 1, %9;\n}\n"
  : "=f"(d[0]), "=f"(d[1]), "=f"(d[2]), "=f"(d[3])
  : "r"(a0), "r"(a1), "r"(a2), "r"(a3), "r"(db), "n"(TB), "n"(HB));
}

constexpr int SEQ = 2048, DM = 1024, FF = 3584;
constexpr float LOG2E = 1.4426950408889634f;
constexpr uint32_t POLL_LIMIT = 1u << 22;
#define NPRE0 1
#define NPREN 2
constexpr int NPRE = NPREN;
#define QW 4
#define RS_N 22
#define RS_D1 430
#define RS_D2 300
#define SKM 0x154
#define LAG 2
#define PF_T0 5000
#define PF_DT 800
#define NFFN_L NFFN
#define FF_DT 500
#define GRES 8
#define TMASK 0xffffff
#define PMASK 0xffffff
#define FF_T0 1
#define GPRE 0
#define REL 6
#define EFI 11
#define TKW 8
#define FF_ORD 0x76543210ba98ull
#define KT 0
#define KM 0xffff
#define KR2 1
#define KK(id) do { if (KT == 1) { TK(32 * wg + (id)); } } while (0)
#define PF_I0 0
#define PF_ST 7
#define PRK 3
#define TRKL 1
#define KR 4
#define KSEL c
#define XP 0
#define CAPL 2
#define OUT_D 400
#define OUT_0 0
#define ML 2
#define H2 1
#define H3 1
#define FUNN 1
constexpr int FUN = FUNN;
#define FF_N 6
#define FF_D2 350
constexpr int NFFN = 112;

constexpr uint32_t SB0 = 1024;
constexpr uint32_t KV_STAGE = 49152, R5 = 32768;
constexpr uint32_t OFF_X = 163840, OFF_S = 196608, OFF_WPHI = OFF_S + 20480, OFF_M = 229376, SMEM_BYTES = 232448;
constexpr uint32_t OFF_RS256 = 212992, OFF_ONES = OFF_RS256 + 1024, OFF_WPHIK1 = OFF_ONES + 1024, OFF_KVZ = OFF_S;
constexpr uint32_t OFF_WPHIK = OFF_S, OFF_BXK = OFF_S + 2048, OFF_AXK = OFF_S + 4096, OFF_G = OFF_S + 8192;
constexpr uint32_t OFF_AXQ = OFF_WPHI, OFF_BXQ = OFF_WPHI + 2048, OFF_WPHIQ = OFF_WPHI + 4096;
constexpr uint32_t B_FULLKV = OFF_M  , B_EMPTYKV = OFF_M + 32  ;
constexpr uint32_t B_EMPTY5 = OFF_M + 64  , B_UO = B_EMPTY5 + 48  , B_RC = B_UO + 32  ;
constexpr uint32_t B_OUT = B_RC + 16  , B_SD = B_OUT + 16, B_AUX = B_SD + 8, B_AUXQ = B_AUX + 8, B_RX = B_AUXQ + 8;
constexpr uint32_t B_FULL5 = B_RX + 8  , B_F = B_FULL5 + 40  , B_WD = B_F + 64  ;
constexpr uint32_t B_WC = B_WD + 32  , B_DR = B_WC + 32  , B_W = B_DR + 24, B_OS = B_W + 8, B_R = B_W + 16, B_KD = B_W + 24, B_R1 = B_W + 32, B_T = B_W + 40, B_G = B_W + 48, B_END = B_W + 56, B_S0 = B_END;
static_assert(B_END <= OFF_M + 16 + 3 * 152, "barriers");
constexpr uint32_t B_GB = OFF_M + 2560  , B_GA = B_GB + 128  ;
constexpr uint32_t OFF_SUMWR = OFF_M + 608, OFF_EP = OFF_M + 624, OFF_KEY = OFF_M + 628;
constexpr uint32_t OFF_RSQ = OFF_M + 640, OFF_TL = OFF_M + 1152, OFF_SEL = OFF_M + 1648, OFF_T = OFF_M + 1792, OFF_WR = OFF_M + 2048;
constexpr uint32_t OFF_XSEL = 2 * R5, OFF_GU = OFF_XSEL + 4096, OFF_OUT = 3 * R5;
constexpr uint64_t FF_SLOT = 0xdcdc3210dcbaull;
constexpr int KVP = 6 * 128;

enum { NB_G2E = 1, NB_XS = 2, NB_WG01 = 3, NB_ACT = 4, NB_Q0 = 5  , NB_ST = 14, NB_DN = 9, NB_ZERO = 10, NB_PUB = 11, NB_TOK = 10  , NB_L0 = 12  , NB_WG2 = 7, NB_QGO = 15 };

struct Scratch {
  bf16     o[SEQ * DM];
  float4   rstat[SEQ];
  uint32_t key[8 * KR * 128];
  uint32_t cand[128 * 512];
  float4   yacc[4 * 3 * 128];
  float4   kvacc[32 * KVP];
  uint2    stats[SEQ];
  uint32_t cskv[2 * DM];
  uint32_t csq[4 * DM];
  uint32_t oset[128 * 16];
  uint32_t oflag[16 * 6 * 32];
  uint32_t epoch;
};
__device__ __align__(1024) Scratch g_scr;
#define TS(id)
#define TDUMP()
#define TS0_DECL()
#define TS0_READ()
#define TS0_WRITE()
#define TK(id)
#define TSW(id)

struct Params {
  CUtensorMap x128, x64, wkv, wq, wo[2], wd, wg, wu, phi, tg, tu, td, xs, ws, qs, out, o;
  const bf16 *x, *wqkv, *wo_p, *wg_p, *wu_p, *wd_p, *wr;
  bf16* out_p;
  Scratch* g;
  uint32_t zero;
};

constexpr float EXP_LIM = 1.1529215e18f, ARG_LIM2 = 3600.f;
template<bool PR> __device__ __forceinline__ void dual_exp2(const float (&p)[16], uint32_t (&ep)[8], uint32_t (&em)[8]) {
  #pragma unroll
  for (int k = 0; k < 8; k++) {
    const float a = ex2(p[2*k]), b = ex2(p[2*k+1]);
    ep[k] = pack_bf16(a, b);
    if (PR) { const float r = rcp(a * b); em[k] = pack_bf16(r * b, r * a); }
    else em[k] = pack_bf16(ex2(-p[2*k]), ex2(-p[2*k+1]));
  }
}
__device__ __forceinline__ void dual_exp2_shifted(const float (&pp)[2][16], uint32_t (&ph)[4][8]) {
  #pragma unroll
  for (int h = 0; h < 2; h++) {
    const float* p = pp[h];
    float m[4] = {p[0], p[2], p[0], p[2]};
    #pragma unroll
    for (int i = 0; i < 16; i++) { m[(i >> 1) & 1] = fmaxf(m[(i >> 1) & 1], p[i]); m[2 + ((i >> 1) & 1)] = fminf(m[2 + ((i >> 1) & 1)], p[i]); }
    #pragma unroll
    for (int o = 1; o < 4; o <<= 1) {
      m[0] = fmaxf(m[0], __shfl_xor_sync(~0u, m[0], o)); m[1] = fmaxf(m[1], __shfl_xor_sync(~0u, m[1], o));
      m[2] = fminf(m[2], __shfl_xor_sync(~0u, m[2], o)); m[3] = fminf(m[3], __shfl_xor_sync(~0u, m[3], o));
    }
    #pragma unroll
    for (int k = 0; k < 8; k++) {
      ph[2*h][k] = pack_bf16(ex2(p[2*k] - m[k & 1]), ex2(p[2*k+1] - m[k & 1]));
      ph[2*h+1][k] = pack_bf16(ex2(m[2 + (k & 1)] - p[2*k]), ex2(m[2 + (k & 1)] - p[2*k+1]));
    }
  }
}
__device__ __forceinline__ uint32_t add_bf16x2(uint32_t a, uint32_t b) { uint32_t r; asm("add.rn.bf16x2 %0, %1, %2;" : "=r"(r) : "r"(a), "r"(b)); return r; }
__device__ __forceinline__ void row_sums(float (&s)[2][4], const uint32_t (&ph)[4][8], uint32_t sel) {
  uint32_t u[8];
  #pragma unroll
  for (int i = 0; i < 8; i++) { const uint32_t* f = &ph[i >> 1][i & 1]; u[i] = add_bf16x2(add_bf16x2(f[0], f[2]), add_bf16x2(f[4], f[6])); }
  wg_fence();
  wgmma_rz_n8<0, H0>(s[0], u[0], u[1], u[2], u[3], sel);
  wgmma_rz_n8<0, H0>(s[1], u[4], u[5], u[6], u[7], sel);
  wg_commit();
}
__device__ __forceinline__ uint32_t mul_bf16x2(uint32_t a, uint32_t b) { uint32_t r; asm("mul.rn.bf16x2 %0, %1, %2;" : "=r"(r) : "r"(a), "r"(b)); return r; }
__device__ __forceinline__ void normalize(uint32_t (&ph)[4][8], const float (&s)[2][4]) {
  #pragma unroll
  for (int i = 0; i < 4; i++) {
    const float i0 = rcp(s[i >> 1][i & 1]), i1 = rcp(s[i >> 1][2 + (i & 1)]);
    const uint32_t n0 = pack_bf16(i0, i0), n1 = pack_bf16(i1, i1);
    #pragma unroll
    for (int k = 0; k < 4; k++) { ph[i][2*k] = mul_bf16x2(ph[i][2*k], n0); ph[i][2*k+1] = mul_bf16x2(ph[i][2*k+1], n1); }
  }
}
__device__ __forceinline__ void split_bf16(float a, float b, uint32_t& hi, uint32_t& lo) { hi = pack_bf16(a, b); lo = pack_bf16(a - bf_lo(hi), b - bf_hi(hi)); }
__device__ __forceinline__ void put_colsums(uint32_t base, int lane, float a, float b, float c, float d) {
  uint32_t h0, l0, h1, l1;
  split_bf16(a, b, h0, l0); split_bf16(c, d, h1, l1);
  const uint32_t ad = base + (lane >> 1) * 128 + (lane & 1) * 8;
  sts64(ad, h0, h1); sts64(ad + 16, l0, l1); sts64(ad + 32, h0, h1); sts64(ad + 48, l0, l1);
  sts128(base + (lane >> 1) * 128 + 64 + (lane & 1) * 32, 0, 0, 0, 0); sts128(base + (lane >> 1) * 128 + 80 + (lane & 1) * 32, 0, 0, 0, 0);
}
__device__ __forceinline__ float reduce8(const float (&v)[8], int lane) {
  const bool b4 = lane & 16, b3 = lane & 8, b2 = lane & 4;
  float a[4], b[2];
  #pragma unroll
  for (int i = 0; i < 4; i++) a[i] = (b4 ? v[4 + i] : v[i]) + __shfl_xor_sync(~0u, b4 ? v[i] : v[4 + i], 16);
  #pragma unroll
  for (int i = 0; i < 2; i++) b[i] = (b3 ? a[2 + i] : a[i]) + __shfl_xor_sync(~0u, b3 ? a[i] : a[2 + i], 8);
  return (b2 ? b[1] : b[0]) + __shfl_xor_sync(~0u, b2 ? b[0] : b[1], 4);
}
__device__ __forceinline__ bool tag_bad(uint4 v, uint32_t tg) { return (((v.x ^ tg) | (v.y ^ tg) | (v.z ^ tg) | (v.w ^ tg)) & 3) != 0; }

__global__ void __launch_bounds__(512, 1) fused_kernel(const __grid_constant__ Params P) {
  extern __shared__ __align__(1024) uint8_t smem_raw[];
  const uint32_t sb = smem_u32(smem_raw);
  const int tid = threadIdx.x, lane = tid & 31;
  TS0_DECL();
  TS0_READ();
  if (tid == 352) { prefetch_map(&P.wkv); prefetch_map(&P.x128); }
  const int cp = blockIdx.x >> 1, rank = blockIdx.x & 1;
  const int cr = cp < 4 ? 32 + 8 * cp : cp - 4 + max((cp * 37 - 1076) >> 8, 0);
  const int c = (cr & 62) + 64 * (cr & 1) + rank;
  const int m256 = c >> 4, nkv = c & 15, m128 = c >> 3, j = c & 7;
  if ((tid >> 5) == 12 && elect_one()) {
    mbar_init(sb + B_S0, 1); mbar_init(sb + B_FULLKV, 1); mbar_init(sb + B_FULLKV + 8, 1);
    fence_async_smem();
    mbar_expect_tx(sb + B_S0, 32768);
    tma_4d(sb + 32768, &P.wkv, 0, 0, nkv, 1, sb + B_S0);
    tma_2d(sb, &P.x128, 0, 256 * m256, sb + B_S0);
    mbar_expect_tx(sb + B_FULLKV, 16384);
    tma_2d(sb + 16384, &P.x128, 0, 256 * m256 + 128, sb + B_FULLKV);
    if (NPRE0 > 1) {
      mbar_expect_tx(sb + B_FULLKV + 8, KV_STAGE);
      tma_4d(sb + KV_STAGE + 32768, &P.wkv, 0, 64, nkv, 1, sb + B_FULLKV + 8);
      tma_2d(sb + KV_STAGE, &P.x128, 64, 256 * m256, sb + B_FULLKV + 8);
      tma_2d(sb + KV_STAGE + 16384, &P.x128, 64, 256 * m256 + 128, sb + B_FULLKV + 8);
    }
    asm volatile("fence.mbarrier_init.release.cluster;" ::: "memory");
  }
  #pragma unroll
  for (int w = 0; w < 3; w++)
    if (tid == 32 + 32 * w) {
      #pragma unroll
      for (uint32_t b = B_FULLKV + 16 + 152 * w; b < B_FULLKV + 168 + 152 * w && b < B_END; b += 8)
        mbar_init(sb + b, b < B_EMPTYKV ? 1 : b < B_EMPTY5 ? 12 : b < B_SD ? 4 : b < B_RX || b == B_W ? 2 : b == B_RX ? 8 : 1);
      asm volatile("fence.mbarrier_init.release.cluster;" ::: "memory");
      fence_async_smem();
    }
  const int warp = __shfl_sync(~0u, tid >> 5, 0), wg = warp >> 2, wp = warp & 3;
  const int f = 16 * ((cr + 7) & 7) + 2 * (cr >> 3) + rank;
  const int ha = 4 * (nkv >> 1) + (nkv & 1);
  Scratch* const G = P.g;
  if ((sb & 0x3ffff) != SB0) asm volatile("trap;");
  __syncthreads();
  cluster_arrive();
  if (warp == 12) {
    TK(88 - 32);
    if (elect_one()) {
      #pragma unroll
      for (int s = NPRE0; s < NPRE; s++) {
        const uint32_t st = sb + s * KV_STAGE, fb = sb + B_FULLKV + 8 * s;
        mbar_expect_tx(fb, KV_STAGE);
        tma_4d(st + 32768, &P.wkv, 0, 64 * s, nkv, 1, fb);
        tma_2d(st, &P.x128, 64 * s, 256 * m256, fb);
        tma_2d(st + 16384, &P.x128, 64 * s, 256 * m256 + 128, fb);
      }
    }
    __syncwarp();
  }

  if (wg == 3) {
    asm volatile("setmaxnreg.dec.sync.aligned.u32 32;");
    cluster_wait();
    if (wp == 0) { TK(89 - 32); }
    const bool el = elect_one();
    const uint64_t ef = policy_evict_first(), en = policy_evict_normal();
    auto fetch_o = [&](const int t0) {
      const int sh = t0 & 1;
      uint32_t missing = ~0u;
      const uint32_t* hint = &G->oflag[(m128 * 6 + ((t0 + 1) & 6) + rank) * 32 + ((4 * (j & 6) + lane) & 31)];
      #pragma unroll FUN
      for (int i = 2 - 2 * sh; i < 8; i += 1 + sh) {
        const int blk = sh ? 6 + 2 * t0 + (i >> 1) : i, wrap = t0 == 3 ? 2 : (blk >= 5) + (blk >= 11), s = blk + 1 - 6 * wrap;
        flags_wait(missing, hint, (15u + 240u * sh) << (4 * i));
        if (blk > 5) mbar_wait(sb + B_EMPTY5 + 8 * s, wrap & 1);
        if (el) {
          tma_2d_mc_h(sb + s * R5 + rank * 8192, &P.o, 0, (m128 * 16 + t0 + 2 * (((j & 6) + i) & 7)) * 32 + 16 * rank, sb + B_GA + 16 * blk + 8 * rank, ef);
          if (KT == 2 && rank == KR2 && ((KM >> blk) & 1)) { TK(16 + blk); }
          if (KT != 2 && i == 2 - 2 * sh) TS(t0 == 0 ? (rank ? 4 : 12) : t0 == 3 ? (rank ? 31 : 10) : (rank ? 9 : 13));
        }
      }
    };
    if (wp == 0) {
      {
        #pragma unroll 1
        for (int kb = NPRE; kb < 16; kb++) {
          const uint32_t st = sb + (kb & 3) * KV_STAGE, fb = sb + B_FULLKV + 8 * (kb & 3);
          mbar_wait(fb + (B_EMPTYKV - B_FULLKV), ~(kb >> 2) & 1);
          if (el) {
            mbar_expect_tx(fb, KV_STAGE);
            tma_2d_mc(st + rank * 16384, &P.x128, 64 * kb, 256 * m256 + 128 * rank, fb);
            tma_4d_h(st + 32768, &P.wkv, 0, 64 * kb, nkv, 1, fb, ef);
          }
        }
        uint64_t ord = 0xf3120edcba987654ull;
        uint32_t so = 0, par = 1;
        #pragma unroll 1
        for (int i = 0; i < 16; i++) {
          const uint32_t st = sb + so * 4096, fb = sb + B_FULL5 + so;
          const int k0 = (64 * (uint32_t)ord + 128 * (j & 6)) & 960;
          mbar_wait(i < 5 ? sb + B_EMPTYKV + so - (i > 1 ? 8 : 0) : fb + (B_EMPTY5 - B_FULL5), par);
          if (el) {
            mbar_expect_tx(fb, R5);
            tma_2d_mc_h(st + rank * 8192, &P.x64, k0, 128 * m128 + 64 * rank, fb, i >= EFI ? ef : en);
            tma_3d_h(st + 16384, &P.wq, 0, k0, 2 * j, fb, ef);
          }
          ord >>= 4; so += 8;
          if (so == 40) { so = 0; par ^= 1; }
        }
        mbar_wait(sb + B_FULL5 + 8 + 8 * rank, 0); if (el) mbar_arrive(sb + B_R);
        mbar_wait(sb + B_FULL5 + 24 + 8 * rank, 0); if (el) mbar_arrive(sb + B_R1);
        #pragma unroll 1
        for (int i = 0; i < 19; i++) {
          const int row = i < 8 ? 128 * (((j & 6) + i) & 7) : 256 * (((j >> 1) + i) & 3) + 32 + 16 * (i & 4);
          mbar_wait(sb + B_EMPTY5 + so, par);
          if (el) {
            if (i < 16) {
              tma_5d_h(sb + so * 4096 + 16384, &P.wo[i >> 3], 128 * j, row, sb + B_GB + 8 * i, ef);
              tma_5d_h(sb + so * 4096 + 24576, &P.wo[i >> 3], 128 * j + 64, row, sb + B_GB + 8 * i, ef);
            } else mbar_arrive(sb + B_DR + 8 * (i - 16));
          }
          so += 8;
          if (so == 48) { so = 0; par ^= 1; }
        }
      }
    } else if (wp == 3) {
      const uint32_t t_start = (uint32_t)clock();
      if (el) {
        mbar_expect_tx(sb + B_W, 12288);
        #pragma unroll 1
        for (int i = 0; i < 6; i++) tma_2d(sb + (i == 0 ? OFF_WPHIK : i == 1 ? OFF_WPHIK1 : OFF_WPHIQ + 2048 * (i - 2)), &P.phi, 0, 32 * (i < 2 ? 2 * nkv + i : 4 * j + 2 * (i & 1) + ((i - 2) >> 1)), sb + B_W);
        prefetch_map(&P.x64); prefetch_map(&P.wq); prefetch_map(&P.wo[0]); prefetch_map(&P.wo[1]);
        prefetch_map(&P.o); prefetch_map(&P.wd); prefetch_map(&P.out); prefetch_map(&P.wg); prefetch_map(&P.wu);
      }
      #pragma unroll 1
      for (int i = 0; i < 8; i++) {
        if (lane < 16) st128_rlx(&G->cand[(m128 * 8 + i) * 512 + 64 * j + 4 * lane], ~0u, ~0u, ~0u, ~0u);
      }
      if (lane < 16) st128_rlx(&G->rstat[16 * c + lane], 0, 0, 0, 0);
      if (lane < 12) st128_rlx(&G->yacc[12 * c + lane], 0, 0, 0, 0);
      {
        const uint32_t nt = ld32_rlx(&G->epoch);
        if (lane < 8) { st128_rlx(&G->stats[16 * c + 2 * lane], nt, nt, nt, nt); st128_rlx(&G->csq[32 * c + 4 * lane], nt, nt, nt, nt); }
        if (lane < 4) { st128_rlx(&G->cskv[128 * nkv + 16 * m256 + 4 * lane], nt, nt, nt, nt); st128_rlx(&G->oset[16 * c + 4 * lane], nt, nt, nt, nt); }
      }
      if (lane < 2 * KR) st128_rlx(&G->key[(KR * j + (lane >> 1)) * 128 + m128 * 8 + 4 * (lane & 1)], 0, 0, 0, 0);
      if (c < 32) {
        #pragma unroll 1
        for (int i = lane; i < KVP; i += 32) st128_rlx(&G->kvacc[(ha + 2 * m256) * KVP + i], 0, 0, 0, 0);
      }
      fence_gpu();
      bar_arrive(NB_ZERO, 160);
      TS0_WRITE();
      if (el) {
        #pragma unroll 1
        for (int i = PF_I0; i < ((XP & 4) ? 0 : 30); i++) {
          while ((uint32_t)clock() - t_start < (uint32_t)(PF_T0 + PF_DT * (i - PF_I0) + PF_ST * f)) __nanosleep(64);
          if (i < 4) { bulk_prefetch(P.wqkv + (size_t)(256 * i + c) * (3 * DM), 2048); bulk_prefetch(P.wqkv + (size_t)(256 * i + 128 + c) * (3 * DM), 2048); }
          else if (i < 6) bulk_prefetch(P.wo_p + (size_t)c * 8192 + (i - 4) * 4096, 8192);
          else if ((TMASK >> (i - 6)) & 1) {
            const int k = i - 6;
            if (f < NFFN) {
              if (k < 16) {
                #pragma unroll 1
                for (int e = 0; e < 4; e++) tma_2d(sb + OFF_T, rank ? &P.tu : &P.tg, 32 * (f & ~1), 64 * k + 16 * e, sb + B_T);
              } else { tma_2d(sb + OFF_T, &P.td, 0, 256 * f + 32 * (k - 16), sb + B_T); tma_2d(sb + OFF_T, &P.td, 0, 256 * f + 32 * (k - 16) + 16, sb + B_T); }
            }
          }
          else if (!((PMASK >> (i - 6)) & 1)) {}
          else if (i < 22) bulk_prefetch(((i & 1) ? P.wu_p : P.wg_p) + (size_t)((i - 6) >> 1) * 458752 + c * 3584, 7168);
          else bulk_prefetch(P.wd_p + (size_t)(i - 22) * 458752 + c * 3584, 7168);
        }
      }
      __syncwarp();
      mbar_wait2(sb + B_OS, 0, sb + B_RX, 0);
      mbar_wait2(sb + B_EMPTY5 + 24, 0, sb + B_EMPTY5 + 32, 0);
      mbar_wait2(sb + B_EMPTY5 + 40, 0, sb + B_EMPTY5, 1);
      fetch_o(0);
      fetch_o(3);
    } else {
      const int half = wp - 1;
      const uint32_t ep1 = ld32_rlx(&G->epoch) + 1, tg = ep1 & 3;
      {
        uint32_t it = 0;
        sts128(sb + OFF_ONES + half * 512 + lane * 16, 0x3f803f80u, 0x3f803f80u, 0x3f803f80u, 0x3f803f80u);
        if (lane < 9) { const uint32_t v = (lane & 1) ? 0 : 0x3f803f80u; sts128(sb + OFF_SEL + lane * 16, v, v, v, v); }
        auto reset_o = [&](int i0, int i1, uint32_t dt) {
          uint32_t t0 = (uint32_t)clock();
          #pragma unroll 1
          for (int i = i0; i < i1; i++) {
            if (!(XP & 2)) st128_rlx(G->o + (m128 * 16 + 2 * j + half) * 8192 + 256 * i + 8 * lane, ~0u, ~0u, ~0u, ~0u);
            while ((uint32_t)clock() - t0 < dt) __nanosleep(40);
            t0 += dt;
          }
        };
        if (el) {
          #pragma unroll 1
          for (int i = 24 * half; i < 24 * half + 24; i++) { mbar_init(sb + B_GB + 8 * i, 1); mbar_expect_tx(sb + B_GB + 8 * i, i < 16 ? 16384 : 8192); }
          asm volatile("fence.mbarrier_init.release.cluster;" ::: "memory");
        }
        mbar_wait(sb + B_S0, 0);
        reset_o(0, RS_N, RS_D1);
        bar_sync(NB_PUB, 192);
        const uint4* src = reinterpret_cast<const uint4*>(&G->stats[256 * m256 + 128 * half]) + lane;
        const uint4* srk = reinterpret_cast<const uint4*>(&G->cskv[128 * nkv]) + lane;
        uint4 v0, v1, vk;
        it = 0;
        do { v0 = ld128_rlx(src); v1 = ld128_rlx(src + 32); vk = ld128_rlx(srk); }
        while ((tag_bad(v0, tg) || tag_bad(v1, tg) || tag_bad(vk, tg)) && ++it < POLL_LIMIT);
        fence_acquire_gpu();
        if (half) put_colsums(sb + OFF_BXK, lane, untag(vk.x), untag(vk.y), untag(vk.z), untag(vk.w));
        #pragma unroll
        for (int i = 0; i < 2; i++) {
          const uint4 v = i ? v1 : v0;
          uint32_t hi, lo;
          split_bf16(-0.5f * untag(v.x), -0.5f * untag(v.z), hi, lo);
          const uint32_t h0 = __byte_perm(hi, hi, 0x1010), h1 = __byte_perm(hi, hi, 0x3232), l0 = __byte_perm(lo, lo, 0x1010), l1 = __byte_perm(lo, lo, 0x3232);
          const uint32_t a = sb + OFF_AXK + half * 2048 + i * 1024 + lane * 32;
          sts128(a, h0, l0, 0, 0); sts128(a + 16, h1, l1, 0, 0);
          sts64(sb + OFF_RS256 + half * 512 + i * 256 + lane * 8, v.y & ~3u, v.w & ~3u);
          if (half == (m128 & 1)) {
            const uint32_t aq = sb + OFF_AXQ + i * 1024 + lane * 32;
            sts128(aq, h0, l0, 0, 0); sts128(aq + 16, h1, l1, 0, 0);
            sts64(sb + OFF_RSQ + i * 256 + lane * 8, v.y & ~3u, v.w & ~3u);
          }
        }
        fence_async_smem();
        __syncwarp();
        if (el) { sts32(sb + OFF_EP, ep1); mbar_arrive(sb + B_AUX); }
        reset_o(RS_N, 32, RS_D2);
        if (half == 0 && rank == 0 && lane < 12) st128_rlx(&G->oflag[(m128 * 6 + (lane >> 1)) * 32 + 4 * j + 4 * (lane & 1)], 0, 0, 0, 0);
        fence_gpu();
        __syncwarp();
        if (el) { st32_rlx(&G->oset[16 * c + 8 * half], ep1); if (half) mbar_arrive(sb + B_AUXQ); }
        if (!half) {
          const uint4* src = reinterpret_cast<const uint4*>(&G->csq[128 * j]) + lane;
          uint4 v0, v1, v2, v3;
          do { v0 = ld128_rlx(src); v1 = ld128_rlx(src + DM / 4); v2 = ld128_rlx(src + DM / 2); v3 = ld128_rlx(src + 3 * DM / 4); }
          while ((tag_bad(v0, tg) || tag_bad(v1, tg) || tag_bad(v2, tg) || tag_bad(v3, tg)) && ++it < POLL_LIMIT);
          put_colsums(sb + OFF_BXQ, lane, (untag(v0.x) + untag(v1.x)) + (untag(v2.x) + untag(v3.x)), (untag(v0.y) + untag(v1.y)) + (untag(v2.y) + untag(v3.y)),
                      (untag(v0.z) + untag(v1.z)) + (untag(v2.z) + untag(v3.z)), (untag(v0.w) + untag(v1.w)) + (untag(v2.w) + untag(v3.w)));
          fence_async_smem();
          __syncwarp();
          if (el) mbar_arrive(sb + B_AUXQ);
        }
      }
      if (half == 0) {
        for (uint32_t it = 0; __any_sync(~0u, ld32_rlx(&G->oset[m128 * 128 + 8 * (lane & 15)]) != ep1) && it < POLL_LIMIT; it++) {}
        fence_acquire_gpu();
        if (el) mbar_arrive(sb + B_OS);
      }
      if (!half) {
        #pragma unroll 1
        for (int hh = 0; hh < 2; hh++) {
          const uint32_t src = sb + (1 + rank) * R5 + hh * 8192, fa = sb + B_GA + 16 * rank + 8 * hh;
          mbar_wait2(sb + B_UO + 8 * hh, 0, sb + B_GB + 8 * rank, 0);
          if (el) bulk_s2peer(mapa(src, rank ^ 1), src, 8192, mapa(fa, rank ^ 1));
        }
        fetch_o(1);
      }
      else if (f < NFFN_L) {
        mbar_wait2(sb + B_UO, 0, sb + B_UO + 8, 0);
        mbar_wait(sb + B_UO + 24, 0);
        uint32_t t0 = (uint32_t)clock();
        while ((uint32_t)clock() - t0 < (uint32_t)FF_T0) __nanosleep(32);
        t0 -= FF_DT;
        #pragma unroll 1
        for (int i = 0; i < 12; i++) {
          const int e = (FF_ORD >> (4 * i)) & 15;
          const uint32_t dst = sb + 16384 * ((FF_SLOT >> (4 * e)) & 15), fb = sb + B_F + 8 * e;
          if (i >= 2) mbar_wait(sb + B_WC + 8 * ((0x100066553244ull >> (4 * e)) & 15), 0);
          while ((uint32_t)clock() - t0 < (uint32_t)(i < FF_N ? FF_DT : FF_D2)) __nanosleep(32);
          t0 = (uint32_t)clock();
          if (i < 8) { TK(48 + i); }
          if (el) {
            mbar_expect_tx(fb, 16384);
            if (e >= 8) tma_3d_h(dst, &P.wd, 0, 32 * f, 4 * e - 32, fb, ef);
            else { tma_2d(dst, &P.wg, 32 * f, 128 * e, fb); tma_2d(dst + 8192, &P.wu, 32 * f, 128 * e, fb); }
          }
        }
      }
      __syncwarp();
    }
    if (wp & 1) {
      __syncwarp();
      mbar_wait(sb + B_OUT + 8 * (wp >> 1), 0);
      uint32_t t0 = (uint32_t)clock() + OUT_0;
      #pragma unroll 1
      for (int i = 0; i < 8; i++) {
        while ((int32_t)((uint32_t)clock() - t0) < 0) __nanosleep(20);
        if (el) tma_store_2d(&P.out, 128 * j + 64 * (i & 1), 128 * m128 + 32 * (wp & 2) + 8 * (i & 6), sb + OFF_OUT + (i & 1) * 16384 + (wp & 2) * 4096 + (i & 6) * 1024);
        t0 += OUT_D;
      }
      if (el) { bulk_commit(); bulk_wait_all(); fence_async_global(); mbar_arrive(sb + B_SD); TS(19); }
    }
    __syncwarp();
    cluster_arrive(); cluster_wait();
    return;
  }

  asm volatile("setmaxnreg.inc.sync.aligned.u32 160;");
  cluster_wait();
  const int t = tid & 127, g = lane >> 2;
  const uint32_t sa = (16 * wp + (lane & 15)) * 128 + (((lane >> 4) ^ (lane & 7)) << 4);

  if (wg == 2) {
    float s[2] = {0.f, 0.f}, s2[2] = {0.f, 0.f}, ck[8] = {0.f, 0.f, 0.f, 0.f, 0.f, 0.f, 0.f, 0.f}, cs[8] = {0.f, 0.f, 0.f, 0.f, 0.f, 0.f, 0.f, 0.f};
    const uint32_t ebr = mapa(sb + B_EMPTYKV, lane & 1), tg = (ld32_rlx(&G->epoch) + 1) & 3;
    auto addx = [&](const uint4 v) {
      const uint32_t w[4] = {v.x, v.y, v.z, v.w};
      #pragma unroll
      for (int e = 0; e < 4; e++) { const float a = bf_lo(w[e]), d = bf_hi(w[e]); s[0] += a; s[1] += d; s2[0] = fmaf(a, a, s2[0]); s2[1] = fmaf(d, d, s2[1]); }
    };
    auto addc = [&](const uint4 v, float (&o)[8]) {
      o[0] += bf_lo(v.x); o[1] += bf_hi(v.x); o[2] += bf_lo(v.y); o[3] += bf_hi(v.y); o[4] += bf_lo(v.z); o[5] += bf_hi(v.z); o[6] += bf_lo(v.w); o[7] += bf_hi(v.w);
    };
    {
      const uint32_t ra = (16 * nkv + (t >> 3)) * 128 + (t & 7) * 16;
      const uint32_t ca = 32768 + (m256 >> 2) * 8192 + (t >> 1) * 128 + (((2 * (m256 & 3) + (t & 1)) ^ ((t >> 1) & 7)) << 4);
      int rd = 0;
      mbar_wait(sb + B_S0, 0);
      #pragma unroll 1
      for (int kb = 0; kb < 10; kb++) {
        const uint32_t st = sb + (kb & 3) * KV_STAGE;
        mbar_wait(sb + B_FULLKV + 8 * (kb & 3), (kb >> 2) & 1);
        const uint4 x0 = lds128(st + ra), w0 = lds128(st + ca);
        if (!(XP & 1)) { addx(x0); addc(w0, ck); } else s[0] += __uint_as_float(x0.x ^ w0.x);
        __syncwarp();
        if (lane < 2) mbar_arrive_remote(ebr + 8 * (kb & 3), 1);
        if ((SKM >> kb) & 1) {
          if (rd) {
            mbar_wait(sb + B_G, (rd - 1) & 1);
            const uint32_t a = sb + OFF_G + (t >> 3) * 256 + (t & 7) * 16;
            const uint4 x1 = lds128(a), x2 = lds128(a + 128), w1 = lds128(sb + OFF_G + 4096 + t * 16), w2 = lds128(sb + OFF_G + 6144 + t * 16);
            addx(x1); addx(x2); addc(w1, ck); addc(w2, ck);
            bar_sync(NB_WG2, 128);
          }
          if (wp == 0 && elect_one()) {
            mbar_expect_tx(sb + B_G, 8192);
            if (rd < 3) {
              tma_2d(sb + OFF_G, &P.xs, 640 + 128 * rd, 256 * m256 + 16 * nkv, sb + B_G);
              tma_2d(sb + OFF_G + 4096, &P.ws, (1 + (m256 >> 2)) * DM + 64 * nkv + 16 * (m256 & 3), 640 + 128 * rd, sb + B_G);
            } else tma_2d(sb + OFF_G, &P.qs, 32 * (c & 31), 256 * (c >> 5), sb + B_G);
          }
          rd++;
        }
      }
    }
    TK(82);
    const uint32_t scr = sb + OFF_WR;
    float sx = s[0] + s[1], sq = s2[0] + s2[1];
    #pragma unroll
    for (int o = 1; o < 8; o <<= 1) { sx += __shfl_xor_sync(~0u, sx, o); sq += __shfl_xor_sync(~0u, sq, o); }
    float v = reduce8(ck, lane);
    v += __shfl_xor_sync(~0u, v, 2);
    if (!(lane & 2)) stsf(scr + (wp * 16 + 8 * (lane & 1) + (lane >> 2)) * 4, v);

    bar_sync(NB_ZERO, 160);
    if ((lane & 7) == 0) {
      const float mean = sx * (1.f / DM);
      st64_rlx(&G->stats[256 * m256 + 16 * nkv + (t >> 3)], tagw(mean, tg), tagw(rsqrtf(fmaxf(sq * (1.f / DM) - mean * mean, 0.f) + 1e-5f), tg));
    }
    if (wp == 1 && lane < 16) {
      const uint32_t a = scr + lane * 4;
      st32_rlx(&G->cskv[128 * nkv + 16 * m256 + lane], tagw((ldsf(a) + ldsf(a + 64)) + (ldsf(a + 128) + ldsf(a + 192)), tg));
    }
    __syncwarp();
    bar_arrive(NB_PUB, 192);
    TSW(23);
    const uint4 wv = ld128_keep(P.wr + t * 8);
    #pragma unroll 1
    for (int i = 0; i < 2; i++) {
      mbar_wait(sb + B_G, i ^ 1);
      const uint32_t a = sb + OFF_G + t * 16;
      const uint4 u0 = lds128(a), u1 = lds128(a + 2048), u2 = lds128(a + 4096), u3 = lds128(a + 6144);
      addc(u0, cs); addc(u1, cs); addc(u2, cs); addc(u3, cs);
      bar_sync(NB_WG2, 128);
      if (i == 0 && wp == 0 && elect_one()) { mbar_expect_tx(sb + B_G, 8192); tma_2d(sb + OFF_G, &P.qs, 32 * (c & 31), 256 * (c >> 5) + 128, sb + B_G); }
    }
    float sw = (bf_lo(wv.x) + bf_hi(wv.x)) + (bf_lo(wv.y) + bf_hi(wv.y)) + (bf_lo(wv.z) + bf_hi(wv.z)) + (bf_lo(wv.w) + bf_hi(wv.w));
    #pragma unroll
    for (int o = 16; o; o >>= 1) sw += __shfl_xor_sync(~0u, sw, o);
    if (lane == 0) stsf(sb + OFF_SUMWR + wp * 4, sw);
    if ((t >> 4) == j) {
      const uint32_t a = sb + OFF_WR + (t & 15) * 32;
      sts128(a, wv.x << 16, wv.x & 0xffff0000u, wv.y << 16, wv.y & 0xffff0000u);
      sts128(a + 16, wv.z << 16, wv.z & 0xffff0000u, wv.w << 16, wv.w & 0xffff0000u);
    }
    v = reduce8(cs, lane);
    stsf(sb + OFF_G + (wp * 32 + 8 * (lane & 3) + (lane >> 2)) * 4, v);
    bar_sync(NB_WG2, 128);
    if (wp == 0) {
      const uint32_t a = sb + OFF_G + lane * 4, cq = tagw((ldsf(a) + ldsf(a + 128)) + (ldsf(a + 256) + ldsf(a + 384)), tg);
      st32_rlx(&G->csq[(c >> 5) * DM + 32 * (c & 31) + lane], cq);
      if (lane == 0) mbar_arrive_at(sb + B_W, rank, (cq & P.zero) + 1);
    }
  }

  uint32_t xr[32];
  {
    const bool isq = wg == 2;
    float acc[2][64];
    {
      const uint32_t emptyb = mapa(sb + (isq ? B_EMPTY5 : B_EMPTYKV), t & 1);
      auto correct = [&](uint32_t xa, uint32_t xb) {
        wg_fence();
        wgmma_sa_n128<0, 1, H0, H0>(acc[0], dlo(SB0, 0) + (xa >> 4), dlo(SB0, 0) + (xb >> 4));
        wgmma_sa_n128<0, 1, H0, H0>(acc[1], dlo(SB0, 0) + (xa >> 4) + 64, dlo(SB0, 0) + (xb >> 4));
        wg_commit();
      };
      if (!isq) {
        mbar_wait(sb + B_S0, 0);
        if (wg) mbar_wait(sb + B_FULLKV, 0);
        if (wg == 0) { TSW(2); }
        #pragma unroll 1
        for (int kb = 0; kb < 16; kb++) {
          if (!KT && wg == 0) { TK(kb); }
          const uint32_t da = dlo(SB0, 16) + wg * 1024 + (kb & 3) * (KV_STAGE >> 4), db = dlo(SB0 + 32768, 8192) + (kb & 3) * (KV_STAGE >> 4);
          wg_fence();
          #pragma unroll
          for (int k = 0; k < 4; k++) {
            wgmma_ss_n128<0, 1, H128, H128>(acc[0], da + 2 * k, db + 128 * k, k > 0 || kb != 0);
            wgmma_ss_n128<0, 1, H128, H128>(acc[1], da + 512 + 2 * k, db + 128 * k, k > 0 || kb != 0);
          }
          wg_commit();
          wg_wait<1>();
          if (kb > 0 && t < 2) mbar_arrive_remote(emptyb + 8 * ((kb - 1) & 3), kb > 10 ? 3 : 1);
          if (kb < 15) mbar_wait(sb + B_FULLKV + 8 * ((kb + 1) & 3), ((kb + 1) >> 2) & 1);
          if (kb == 15 - LAG && wg == 1) bar_sync(NB_WG01, 256);
        }
        bar_arrive(wg ? NB_QGO : NB_WG01, 256);
        mbar_wait(sb + B_AUX, 0);
        correct(OFF_AXK + wg * 2048, OFF_BXK);
        wg_wait<0>();
        if (t < 2) mbar_arrive_remote(emptyb + 24, 3);
        if (wg == 0) { TSW(3); }
        fence_regs(acc[0]); fence_regs(acc[1]);
      const uint32_t stg = sb + OFF_X + (1 - wg) * 24576;
      const uint32_t va = stg + 16384 + (16 * wp + (lane & 15)) * 64 + (((lane >> 4) ^ ((lane >> 1) & 3)) << 4);
      const uint32_t ra = sb + OFF_RS256 + (128 * wg + 16 * wp + g) * 4;
      const float rs[4] = {ldsf(ra), ldsf(ra + 32), ldsf(ra + 256), ldsf(ra + 288)};
      float p[2][16];
      uint32_t vf[16], kf[2][16];
      auto project = [&](const uint32_t (&f)[16], uint32_t db) {
        wg_fence();
        #pragma unroll
        for (int i = 0; i < 2; i++) {
          wgmma_rs_n32<1, H64>(p[i], f[8*i], f[8*i+1], f[8*i+2], f[8*i+3], db, 0);
          wgmma_ra_n32<1, H64>(p[i], f[8*i+4], f[8*i+5], f[8*i+6], f[8*i+7], db + 64);
        }
        wg_commit();
      };
      auto fold = [&](uint32_t (&f)[16], int col, float sc) {
        #pragma unroll
        for (int i = 0; i < 16; i++) {
          const float r = rs[2 * (i >> 3) + (i & 1)] * sc;
          f[i] = pack_bf16(acc[i >> 3][col + 2 * (i & 7)] * r, acc[i >> 3][col + 2 * (i & 7) + 1] * r);
          asm volatile("" : "+r"(f[i]));
        }
      };
      auto put_v = [&](const uint32_t (&f)[16]) {
        #pragma unroll
        for (int k = 0; k < 4; k++) stsm4((va ^ ((k & 1) << 5)) + (k >> 1) * 4096, f[4*k], f[4*k+1], f[4*k+2], f[4*k+3]);
      };
      KK(0);
      fold(vf, 48, 1.f);
      mbar_wait(sb + B_W, 0);
      fold(kf[0], 0, LOG2E);
      #pragma unroll
      for (int i = 0; i < 32; i++) p[i >> 4][i & 15] = acc[i >> 4][i & 15];
      project(kf[0], dlo(SB0 + OFF_WPHIK, 16));
      mbar_wait(sb + B_W, 0);
      KK(1);
      {
        uint32_t v0[16];
        fold(kf[1], 16, LOG2E);
        fold(v0, 32, 1.f);
        if (wg == 1) bar_sync(NB_DN, 256);
        put_v(v0);
      }
      wg_wait<0>();
      fence_regs(p[0]); fence_regs(p[1]);
      if (wg == 1) bar_arrive(NB_WG01, 256);
      KK(2);
      #pragma unroll 1
      for (int h = 0; h < 2; h++) {
        uint32_t ph[4][8];
        float rsum[2][4];
        dual_exp2<PRK & 1>(p[0], ph[0], ph[1]); dual_exp2<(PRK >> 1)>(p[1], ph[2], ph[3]);
        row_sums(rsum, ph, dlo(SB0 + OFF_SEL, 16));
        KK(3 + 6 * h);
        if (wg == 0 && h == 0) { bar_arrive(NB_DN, 256); bar_sync(NB_WG01, 256); }
        if (h == 1) {
          if (wg == 1) bar_sync(NB_DN, 256);
          put_v(vf);
        }
        wg_wait<0>();
        KK(4 + 6 * h);
        fence_regs(rsum[0]); fence_regs(rsum[1]);
        if (!(XP & 8) && __builtin_expect(__any_sync(~0u, !((rsum[0][0] + rsum[0][1]) + (rsum[0][2] + rsum[0][3]) + (rsum[1][0] + rsum[1][1]) + (rsum[1][2] + rsum[1][3]) < EXP_LIM)), 0)) {
          dual_exp2_shifted(p, ph);
          #pragma unroll
          for (int i = 0; i < 8; i++) {
            const uint32_t* f = &ph[i >> 1][i & 1];
            float a = (bf_lo(f[0]) + bf_hi(f[0])) + (bf_lo(f[2]) + bf_hi(f[2])) + (bf_lo(f[4]) + bf_hi(f[4])) + (bf_lo(f[6]) + bf_hi(f[6]));
            a += __shfl_xor_sync(~0u, a, 1);
            rsum[i >> 2][2 * (i & 1) + ((i >> 1) & 1)] = a + __shfl_xor_sync(~0u, a, 2);
          }
        }
        if (h == 0) project(kf[1], dlo(SB0 + OFF_WPHIK1, 16));
        normalize(ph, rsum);
        #pragma unroll
        for (int i = 0; i < 8; i++) {
          const uint32_t* f = &ph[i >> 1][4 * (i & 1)];
          stsm4(((stg + sa) ^ ((i & 3) << 5)) + (i >> 2) * 8192, f[0], f[1], f[2], f[3]);
        }
        KK(5 + 6 * h);
        fence_async_smem();
        KK(6 + 6 * h);
        if (wg != h) { KK(7 + 6 * h); }
        if (wg == h) {
          float kv[20];
          #pragma unroll
          for (int w = 0; w < 2; w++) {
            const uint32_t da = dlo(SB0 + OFF_X, 16) + (h ^ w ^ 1) * 1536, db = dlo(SB0 + OFF_X + 16384, OFF_ONES - OFF_X - 16384) - (h ^ w ^ 1) * (1536 * 65535);
            if (w) bar_sync(NB_ST, 256); else bar_sync(NB_L0 + h, 128);
            wg_fence();
            #pragma unroll
            for (int k = 0; k < 8; k++) {
              if (k == 0 && w == 0) wgmma_sz_n40<1, 1, H128, H64>(kv, da, db);
              else wgmma_sa_n40<1, 1, H128, H64>(kv, da + k * 128, db - k * (64 * 65535));
            }
            wg_commit();
          }
          float4* dst = &G->kvacc[(ha + 2 * h) * KVP + t];
          wg_wait<0>();
          fence_regs(kv);
          KK(7 + 6 * h);
          if (h == 0) bar_arrive(NB_DN, 256); else if (t < 2) { mbar_arrive_at(sb + B_EMPTY5 + 40, t, 2); if (t == 0) mbar_arrive(sb + B_KD); }
          kv[17] = kv[18];
          #pragma unroll
          for (int i = 0; i < 6; i++) red_add_f32x4(dst + 128 * i, kv[3*i], kv[3*i+1], kv[3*i+2], 1.f);
          TSW(29 + h);
        } else bar_arrive(NB_ST, 256);
        wg_wait<0>();
        KK(8 + 6 * h);
        fence_regs(p[0]); fence_regs(p[1]);
      }
      #pragma unroll
      for (int i = 0; i < 32; i++) asm volatile("mov.b32 %0, 0;" : "=r"(xr[i]));
      } else {
        uint32_t so = 0, po = 0, par = 0;
        mbar_wait(sb + B_FULL5, 0);
        bar_sync(NB_QGO, 256);
        TSW(11);
        #pragma unroll 1
        for (int kb = 0; kb < 16 - ML; kb++) {
          if (KT != 2) { TK(16 + kb); }
          const uint32_t da = dlo(SB0, 16) + so * 256, db = dlo(SB0 + 16384, 8192) + so * 256;
          #pragma unroll
          for (int k = 0; k < 4; k++) {
            wg_fence();
            wgmma_ss_n128<0, 1, H128, H128>(acc[0], da + 2 * k, db + 128 * k, k > 0 || kb != 0);
            wgmma_ss_n128<0, 1, H128, H128>(acc[1], da + 512 + 2 * k, db + 128 * k, k > 0 || kb != 0);
            wg_commit();
            if (k == 1 && kb > 0 && t < 2) mbar_arrive_remote(emptyb + po, 2);
            if (k == 3) {
              po = so; so += 8;
              if (so == 40) { so = 0; par ^= 1; }
              mbar_wait(sb + B_FULL5 + so, par);
            }
            if ((QW >> k) & 1) wg_wait<2>(); else wg_wait<1>();
          }
        }
        auto block = [&](const int kb, const int i) {
          wg_fence();
          #pragma unroll
          for (int k = 0; k < 4; k++) wgmma_sa_n128<0, 1, H128, H128>(acc[i], dlo(SB0, 16) + (kb % 5) * 2048 + 512 * i + 2 * k, dlo(SB0 + 16384, 8192) + (kb % 5) * 2048 + 128 * k);
          wg_commit();
        };
        auto hand_over = [&](const int i) {
          const uint32_t ta = sb + (1 + rank) * R5 + sa + i * 8192;
          #pragma unroll
          for (int k = 0; k < 4; k++) {
            const float* a = &acc[i][32 * (k >> 1) + 8 * (k & 1)];
            stsm4(ta ^ (k << 5), pack_bf16(a[0], a[1]), pack_bf16(a[2], a[3]), pack_bf16(a[4], a[5]), pack_bf16(a[6], a[7]));
          }
        };
        mbar_wait2(sb + B_AUXQ, 0, sb + B_OS, 0);
        correct(OFF_AXQ, OFF_BXQ);
        #pragma unroll
        for (int kb = 16 - ML; kb < 16; kb++) {
          if (KT != 2) { TK(16 + kb); }
          block(kb, 0);
          if (kb < 15) mbar_wait(sb + B_FULL5 + 8 * ((kb + 1) % 5), ((kb + 1) / 5) & 1);
          if (kb == 16 - ML) wg_wait<2>(); else if (!H3) wg_wait<1>();
          if (kb == 16 - ML && t < 2) mbar_arrive_remote(emptyb + 8 * ((kb - 1) % 5), 2);
        }
        mbar_wait(sb + B_RC, 0);
        block(16 - ML, 1);
        if (H2) { block(17 - ML, 1); wg_wait<2>(); } else wg_wait<1>();
        fence_regs(acc[0]);
        hand_over(0);
        if (!H2) block(17 - ML, 1);
        fence_async_smem();
        bar_arrive(NB_Q0, 256);
        TSW(1);
        #pragma unroll
        for (int kb = 18 - ML; kb <= 16; kb++) {
          wg_wait<1>();
          if (t < 2) mbar_arrive_remote(emptyb + 8 * ((kb - 2) % 5), 2);
          if (kb < 16) block(kb, 1);
        }
        mbar_wait(sb + B_RC + 8, 0);
        wg_wait<0>();
        if (t < 2) mbar_arrive_remote(emptyb, 2);
        TSW(8);
        fence_regs(acc[1]);
        hand_over(1);
        fence_async_smem();
        bar_arrive(NB_Q0 + 1, 256);
        #pragma unroll
        for (int i = 0; i < 32; i++) { const float* a = &acc[(i >> 3) & 1][16 + 32 * (i >> 4) + 2 * (i & 7)]; xr[i] = pack_bf16(a[0], a[1]); }
        TSW(26);
      }
    }
    float p[2][16];
    #pragma unroll
    for (int i = 0; i < 32; i++) asm volatile("mov.b32 %0, 0;" : "=f"(p[i >> 4][i & 15]));
    auto project_r = [&](int w) {
      wg_fence();
      #pragma unroll
      for (int h = 0; h < 2; h++) {
        wgmma_rs_n32<1, H64>(p[h], xr[8*h], xr[8*h+1], xr[8*h+2], xr[8*h+3], dlo(SB0 + OFF_WPHIQ, 16) + 128 * w, 0);
        wgmma_ra_n32<1, H64>(p[h], xr[8*h+4], xr[8*h+5], xr[8*h+6], xr[8*h+7], dlo(SB0 + OFF_WPHIQ, 16) + 128 * w + 64);
      }
      wg_commit();
    };
    auto capture = [&](const int i) {
      if (!i || CAPL != 2) mbar_wait(sb + (i ? B_R1 : B_R), 0);
      #pragma unroll
      for (int k = 0; k < 4; k++) ldsm4(((sb + (1 + rank) * R5 + wg * 8192 + sa) ^ (k << 5)) + i * 2 * R5, xr[16*i+4*k], xr[16*i+4*k+1], xr[16*i+4*k+2], xr[16*i+4*k+3]);
      const uint32_t one = (((xr[16*i] | xr[16*i+4]) | (xr[16*i+8] | xr[16*i+12])) & P.zero) + 1;
      if (lane == 0) mbar_arrive_at(sb + (i ? B_RX : B_RC + 8 * wg), i ? wg : rank, one);
    };
    const uint32_t rq = sb + OFF_RSQ + (16 * wp + g) * 4 + 256 * (wg & 1), rb = rq + 128 * (wg & 2);
    const float cc[2][2] = {{ldsf(rq) * LOG2E, ldsf(rq + 32) * LOG2E}, {ldsf(rb) * LOG2E, ldsf(rb + 32) * LOG2E}};
    {
      const uint4* src = reinterpret_cast<const uint4*>(&G->kvacc[(4 * j + wg) * KVP + t]);
      uint4 v[12];
      #pragma unroll
      for (int i = 0; i < 12; i++) v[i] = i < 6 || isq ? ld128_rlx(src + 128 * i) : make_uint4(0, 0, 0, 0x41000000u);
      if (isq) {
        project_r(2);
        wg_wait<0>();
        #pragma unroll
        for (int i = 0; i < 16; i++) xr[i] = xr[16 + i];
      } else {
        capture(0);
        if (CAPL == 0) capture(1);
      }
      #pragma unroll 1
      for (uint32_t it = 0; it < POLL_LIMIT; it++) {
        uint32_t bad = 0;
        #pragma unroll
        for (int i = 0; i < 12; i++) bad |= v[i].w ^ 0x41000000u;
        if (!__any_sync(~0u, bad != 0)) break;
        #pragma unroll
        for (int i = 0; i < 12; i++) if (i < 6 || isq) v[i] = ld128_rlx(src + 128 * i);
      }
      mbar_wait(sb + B_KD, 0);
      #pragma unroll
      for (int e = 0; e < 2; e++) {
        if (e == 0 || isq) {
          float f[18];
          #pragma unroll
          for (int i = 0; i < 6; i++) { f[3*i] = __uint_as_float(v[6*e+i].x); f[3*i+1] = __uint_as_float(v[6*e+i].y); f[3*i+2] = __uint_as_float(v[6*e+i].z); }
          const uint32_t ka = sb + OFF_KVZ + (wg + e) * 5120 + wp * 1280 + lane * 16;
          stsm4(ka, pack_bf16(f[0], f[1]), pack_bf16(f[2], f[3]), pack_bf16(f[4], f[5]), pack_bf16(f[6], f[7]));
          stsm4(ka + 512, pack_bf16(f[8], f[9]), pack_bf16(f[10], f[11]), pack_bf16(f[12], f[13]), pack_bf16(f[14], f[15]));
          stsm2(ka + 1024, pack_bf16(f[16], 1.f), pack_bf16(f[17], 1.f));
        }
      }
    }
    fence_async_smem();
    if (wg == 1) bar_arrive(NB_DN, 256);
    if (CAPL == 1 && !isq) capture(1);
    TSW(wg == 0 ? 5 : wg == 1 ? 25 : 6);
    #pragma unroll 1
    for (int e = wg; e < wg + 1 + (wg >> 1); e++) {
      const int half = e >> 1, hh = e & 1, turn = e;
      const uint32_t ao = (1 + rank) * R5 + hh * 8192;
      uint32_t ph[4][8];
      #pragma unroll
      for (int i = 0; i < 32; i++) asm volatile("mov.b32 %0, 0;" : "=r"(ph[i >> 3][i & 7]));
      uint32_t shifted = 0;
      asm volatile("" : "+r"(shifted));
      #pragma unroll 1
      for (;;) {
        if (!(XP & 16) && shifted) dual_exp2_shifted(p, ph);
        uint32_t first = (shifted ^ 1) & !isq;
        asm volatile("" : "+r"(first));
        if (first) {
          if (wg == 0) { TSW(7); }
          bar_sync(NB_Q0 + wg, 256);
          const uint32_t da = dlo(SB0, 16) + (ao >> 4), db = dlo(SB0 + OFF_WPHIQ, 16);
          wg_fence();
          #pragma unroll
          for (int h = 0; h < 2; h++) {
            wgmma_ss_n32<0, 1, H128, H64>(p[h], da + 4 * h, db + 128 * h, 0);
            wgmma_sa_n32<0, 1, H128, H64>(p[h], da + 4 * h + 2, db + 128 * h + 64);
          }
          wg_commit();
          if (CAPL == 2) capture(1);
          wg_wait<0>();
        }
        fence_regs(p[0]); fence_regs(p[1]);
        uint32_t again = shifted;
        asm volatile("" : "+r"(again));
        if (again) break;
        float s2[4] = {0.f, 0.f, 0.f, 0.f};
        #pragma unroll
        for (int i = 0; i < 32; i++) { float& x = p[i >> 4][i & 15]; x *= cc[i >> 4][(i >> 1) & 1]; s2[i & 3] = fmaf(x, x, s2[i & 3]); }
        if (!__any_sync(~0u, !((s2[0] < ARG_LIM2) & (s2[1] < ARG_LIM2) & (s2[2] < ARG_LIM2) & (s2[3] < ARG_LIM2)))) break;
        shifted = 1;
      }
      if (e == 1 || e == 2) bar_sync(NB_TOK + e - 1, 256);
      TK(64 + 4 * turn);
      float ac[4][20];
      auto numer = [&](int h) {
        const uint32_t (*f)[8] = &ph[2 * h];
        const uint32_t db = dlo(SB0 + OFF_KVZ, 128) + (half ? e : h) * 320;
        wg_fence();
        #pragma unroll
        for (int i = 0; i < 2; i++) {
          wgmma_rz_n40<1, dhi(256, 0)>(ac[2*h+i], f[i][0], f[i][1], f[i][2], f[i][3], db + i * 160);
          wgmma_ra_n40<1, dhi(256, 0)>(ac[2*h+i], f[i][4], f[i][5], f[i][6], f[i][7], db + (i * 160 + 80));
        }
        wg_commit();
      };
      const uint32_t oa = (16 * wp + g) * 128 + (((lane & 3) ^ g) << 4);
      auto finish = [&](int h) {
        const float* ap = ac[2 * h]; const float* am = ac[2 * h + 1];
        const float ip0 = rcp(ap[17]), im0 = rcp(am[17]), ip1 = rcp(ap[19]), im1 = rcp(am[19]);
        const float d0 = rcp(fmaf(ap[16], ip0, fmaf(am[16], im0, 1e-6f))), d1 = rcp(fmaf(ap[18], ip1, fmaf(am[18], im1, 1e-6f)));
        const float a0 = ip0 * d0, b0 = im0 * d0, a1 = ip1 * d1, b1 = im1 * d1;
        #pragma unroll
        for (int r = 0; r < 2; r++) {
          const float a = r ? a1 : a0, b = r ? b1 : b0;
          uint32_t w[4];
          #pragma unroll
          for (int k = 0; k < 4; k++) w[k] = pack_bf16(fmaf(ap[4*k+2*r], a, am[4*k+2*r] * b), fmaf(ap[4*k+2*r+1], a, am[4*k+2*r+1] * b));
          const uint32_t off = (oa ^ ((half ? rank : h) << 6)) + r * 1024;
          st128_rlx(reinterpret_cast<uint8_t*>(G->o + (m128 * 16 + (half ? 2 * (j & 6) + 2 * hh + 1 : 2 * j)) * 8192 + (half ? h : hh) * 4096) + off, w[0], w[1], w[2], w[3]);
          if (!half) sts128(sb + ao + off, w[0], w[1], w[2], w[3]);
        }
        if ((half || h) && lane == 0) st32_rlx(&G->oflag[(m128 * 6 + (half ? 2 * e - 2 + h : hh)) * 32 + 4 * j + wp], 1);
      };
      if (!shifted) dual_exp2<true>(p[0], ph[0], ph[1]);
      numer(0);
      if (!shifted) dual_exp2<true>(p[1], ph[2], ph[3]);
      if (turn < 2) bar_arrive(NB_TOK + turn, 256);
      if (wg == 0) bar_sync(NB_DN, 256);
      numer(1);
      wg_wait<1>();
      TK(65 + 4 * turn);
      fence_regs(ac[0]); fence_regs(ac[1]);
      finish(0);
      wg_wait<0>();
      fence_regs(ac[2]); fence_regs(ac[3]);
      #pragma unroll
      for (int i = 0; i < 32; i++) asm volatile("mov.b32 %0, 0;" : "=f"(p[i >> 4][i & 15]));
      if (e == 2) project_r(3);
      finish(1);
      TK(66 + 4 * turn);
      if (!half) fence_async_smem();
      __syncwarp();
      if (lane == 0) mbar_arrive(sb + B_UO + 8 * e);
      wg_wait<0>();
      TK(67 + 4 * turn);
    }
    if (isq) cluster_arrive();
  }

  {
  int lane;
  asm volatile("mov.u32 %0, %%laneid;" : "=r"(lane));
  const int g = lane >> 2, q = lane & 3;
  if (wg < 2) {
    float h[64];
    {
      if (wg == 0) { TK(83); }
      #pragma unroll
      for (int i = 0; i < 32; i++) { h[2*i] = bf_lo(xr[i]); h[2*i+1] = bf_hi(xr[i]); }
      fence_regs(h);
      TK(80 + wg);
      const uint32_t emptyb = mapa(sb + B_EMPTY5, t & 1);
      uint32_t s = 1 + rank, ps = 0;
      mbar_wait2(sb + B_GB + 8 * rank, 0, sb + B_UO + 8 * wg, 0);
      if (wg == 0) { TSW(14); }
      #pragma unroll
      for (int i = 0; i < 16; i++) {
        if (KT == 2 && wg == 1) { TK(i); }
        if (KT != 1 && wg == 0) { TK(32 + i); }
        const uint32_t da = dlo(SB0, 16) + s * 2048 + wg * 512, db = dlo(SB0 + 16384, 8192) + s * 2048;
        wg_fence();
        #pragma unroll
        for (int k = 0; k < 4; k++) wgmma_sa_n128<0, 1, H128, H128>(h, da + k * 2, db + k * 128);
        wg_commit();
        const uint32_t ns = i ? (i + 2) % 6 : 2 - rank;
        const uint32_t nb = i ? i + 1 : 1 - rank, b0 = sb + B_GB + 8 * nb, b1 = sb + B_GA + 16 * nb + 8 * wg;
        const bool here = i == 15 || mbar_test2(b0, 0, b1, 0);
        wg_wait<1>();
        if (!(((2 * REL + 1) >> i) & 1) && i < 14 && t < 2) mbar_arrive_remote(emptyb + 8 * ps, 1);
        if ((REL >> i) & 1) { wg_wait<0>(); if (t < 2) mbar_arrive_remote(emptyb + 8 * s, 1); }
        if (!here) mbar_wait2(b0, 0, b1, 0);
        ps = s; s = ns;
      }
    }
    cluster_arrive();
    float2 wr[16];
    #pragma unroll
    for (int i = 0; i < 16; i++) wr[i] = lds64f(sb + OFF_WR + 32 * i + 8 * q);
    const int r0 = 64 * wg + 16 * wp + g;
    float sum0, sum1, dot0, dot1, sq0, sq1;
    uint32_t redo = 0;
    asm volatile("" : "+r"(redo));
    #pragma unroll 1
    for (;;) {
    if (!(XP & 32) && redo) {
      wg_wait<0>();
      const uint32_t* xp = reinterpret_cast<const uint32_t*>(P.x + (size_t)(128 * m128 + r0) * DM + 128 * j) + q;
      #pragma unroll
      for (int i = 0; i < 32; i++) { const uint32_t v = xp[4 * (i >> 1) + (i & 1) * 4 * DM]; h[2*i] = bf_lo(v); h[2*i+1] = bf_hi(v); }
      #pragma unroll 1
      for (int ks = 0; ks < 64; ks++) {
        const int kb = ks >> 2, kk = 16 * (ks & 3);
        const bf16* op = G->o + (m128 * 16 + kb) * 8192 + r0 * 64 + 2 * q;
        const int o0 = ((kk >> 3) ^ g) << 3;
        const uint32_t* w = reinterpret_cast<const uint32_t*>(P.wo_p + (size_t)(((kb & 1) ? 256 * (kb >> 2) + 32 * (kb & 2) + 32 + 4 * (kk & 32) : 64 * kb + 2 * (kk & 32)) +
                                                                              ((kk & 16) >> 2) + 4 * (g & 6) + (g & 1)) * DM + 128 * j) + q;
        uint32_t b[32], a0, a1, a2, a3, it = 0;
        #pragma unroll
        for (int n = 0; n < 32; n++) b[n] = w[4 * (n >> 1) + (n & 1) * DM];
        do { a0 = ld32_rlx(op + o0); a1 = ld32_rlx(op + 512 + o0); a2 = ld32_rlx(op + (o0 ^ 8)); a3 = ld32_rlx(op + 512 + (o0 ^ 8)); }
        while (max(max(a0, a1), max(a2, a3)) == ~0u && ++it < POLL_LIMIT);
        __syncwarp();
        #pragma unroll
        for (int n = 0; n < 16; n++) mma16816(h[4*n], h[4*n+1], h[4*n+2], h[4*n+3], a0, a1, a2, a3, transpose8(b[2*n]), transpose8(b[2*n+1]));
      }
    }
    wg_wait<0>();
    fence_regs(h);
    if (wg == 0) { TSW(16); }
    sum0 = 0.f, sum1 = 0.f, dot0 = 0.f, dot1 = 0.f, sq0 = 0.f, sq1 = 0.f;
    #pragma unroll
    for (int i = 0; i < 16; i++) {
      sum0 += h[4*i] + h[4*i+1]; sum1 += h[4*i+2] + h[4*i+3];
      sq0 = fmaf(h[4*i], h[4*i], fmaf(h[4*i+1], h[4*i+1], sq0)); sq1 = fmaf(h[4*i+2], h[4*i+2], fmaf(h[4*i+3], h[4*i+3], sq1));
      dot0 = fmaf(h[4*i], wr[i].x, fmaf(h[4*i+1], wr[i].y, dot0)); dot1 = fmaf(h[4*i+2], wr[i].x, fmaf(h[4*i+3], wr[i].y, dot1));
    }
    if (!__any_sync(~0u, !redo & (h[0] != h[0] | h[2] != h[2]))) break;
    redo = 1;
    }
    float4* const rs = &G->rstat[128 * m128 + r0];
    {
      const bool up = q & 2;
      float a = up ? sum1 : sum0, b = up ? sq1 : sq0, d = up ? dot1 : dot0;
      a += __shfl_xor_sync(~0u, up ? sum0 : sum1, 2); b += __shfl_xor_sync(~0u, up ? sq0 : sq1, 2); d += __shfl_xor_sync(~0u, up ? dot0 : dot1, 2);
      a += __shfl_xor_sync(~0u, a, 1); b += __shfl_xor_sync(~0u, b, 1); d += __shfl_xor_sync(~0u, d, 1);
      if ((q & 1) == 0) red_add_f32x4(rs + 4 * q, a, b, d, 1.f);
    }
    if (TRKL == 0) bar_arrive(NB_G2E, 384);
    if (wg == 0) { TSW(24); }
    bar_sync(NB_WG01, 256);
    uint32_t wa[8][4][4];
    const uint32_t wb = sb + 16384 * (((uint32_t)FF_SLOT >> (4 * warp)) & 15) + ((lane & 7) + ((lane >> 4) << 3)) * 64 + ((((lane >> 3) & 1) ^ ((lane >> 1) & 3)) << 4);
    auto getw = [&](int ks) {
      #pragma unroll
      for (int m = 0; m < 4; m++) ldsm4t((wb ^ ((m & 1) << 5)) + (m >> 1) * 8192 + ks * 1024, wa[ks][m][0], wa[ks][m][1], wa[ks][m][2], wa[ks][m][3]);
    };
    if (GPRE && f < NFFN_L) mbar_wait(sb + B_F + 8 * warp, 0);
    if (warp == 7) { TK(60); }
    #pragma unroll
    for (int ks = 0; ks < GPRE; ks++) getw(ks);
    float rstd[2], bm[2];
    uint32_t best;
    {
      const float2 swa = lds64f(sb + OFF_SUMWR), swb = lds64f(sb + OFF_SUMWR + 8);
      const float sw = (swa.x + swa.y) + (swb.x + swb.y);
      uint4 a[2]; uint32_t it = 0, key[2];
      do { a[0] = ld128_rlx(rs); a[1] = ld128_rlx(rs + 8); } while (__any_sync(~0u, (a[0].w & a[1].w) != 0x41000000u) && ++it < POLL_LIMIT);
      #pragma unroll
      for (int i = 0; i < 2; i++) {
        const float mean = __uint_as_float(a[i].x) * (1.f / DM);
        rstd[i] = rsqrtf(fmaxf(__uint_as_float(a[i].y) * (1.f / DM) - mean * mean, 0.f) + 1e-5f);
        bm[i] = -mean * rstd[i];
        const uint32_t rr = __float_as_uint(fmaf(__uint_as_float(a[i].z), rstd[i], sw * bm[i]));
        key[i] = ((rr ^ ((uint32_t)((int32_t)rr >> 31) | 0x80000000u)) & ~2047u) | (2047 - 128 * m128 - r0 - 8 * i);
      }
      asm volatile("redux.sync.max.u32 %0, %1, 0xffffffff;" : "=r"(best) : "r"(max(key[0], key[1])));
    }
    if (TRKL == 2) bar_arrive(NB_G2E, 384);
    if (TRKL == 3 && wg == 0) bar_arrive(NB_G2E, 256);
    if (wg == 0) { TSW(17); }
    const int slot = m128 * 8 + warp, win = ~best & 15;
    if (lane < KR) st32_rlx(&G->key[(KR * j + lane) * 128 + slot], best);
    if ((win & 7) == g) {
      const bool up = win & 8;
      const float ra = up ? rstd[1] : rstd[0], rb = up ? bm[1] : bm[0];
      uint32_t x[16];
      #pragma unroll
      for (int i = 0; i < 16; i++) x[i] = pack_bf16(fmaf(up ? h[4*i+2] : h[4*i], ra, rb), fmaf(up ? h[4*i+3] : h[4*i+1], ra, rb));
      #pragma unroll
      for (int i = 0; i < 4; i++) st128_rlx(&G->cand[slot * 512 + 64 * j + 16 * i + 4 * q], x[4*i], x[4*i+1], x[4*i+2], x[4*i+3]);
    }
    __syncwarp();
    if (TRKL == 1) bar_arrive(NB_G2E, 384);
    if (wg == 0) { TSW(27); }
    {
      const float a0 = 1.f + rstd[0], b0 = bm[0], a1 = 1.f + rstd[1], b1 = bm[1];
      #pragma unroll
      for (int k = 0; k < 8; k++)
        stsm4(((sb + OFF_OUT + wg * 8192 + sa) ^ ((k & 3) << 5)) + (k >> 2) * 16384,
              pack_bf16(fmaf(h[8*k], a0, b0), fmaf(h[8*k+1], a0, b0)),     pack_bf16(fmaf(h[8*k+2], a1, b1), fmaf(h[8*k+3], a1, b1)),
              pack_bf16(fmaf(h[8*k+4], a0, b0), fmaf(h[8*k+5], a0, b0)),   pack_bf16(fmaf(h[8*k+6], a1, b1), fmaf(h[8*k+7], a1, b1)));
      fence_async_smem();
      __syncwarp();
      if (lane == 0) mbar_arrive(sb + B_OUT + 8 * wg);
    }
    if (wg == 0) { TSW(28); }
    {
      if (!GPRE && f < NFFN_L) mbar_wait(sb + B_F + 8 * warp, 0);
      #pragma unroll
      for (int ks = GPRE; ks < GRES; ks++) getw(ks);
      if (wg == 0) { TSW(15); }
      bar_sync(NB_XS, 384);
      uint4 xs[4];
      #pragma unroll
      for (int i = 0; i < 4; i++) xs[i] = lds128(sb + OFF_XSEL + 256 * warp + 64 * i + 16 * q);
      float d[4][4];
      #pragma unroll
      for (int ks = 0; ks < 8; ks++) {
        if (ks >= 1 && GRES + ks - 1 < 8) getw(GRES + ks - 1);
        #pragma unroll
        for (int m = 0; m < 4; m++) {
          if (ks == 0) { d[m][0] = 0.f; d[m][1] = 0.f; d[m][2] = 0.f; d[m][3] = 0.f; }
          mma16816(d[m][0], d[m][1], d[m][2], d[m][3], wa[ks][m][0], wa[ks][m][1], wa[ks][m][2], wa[ks][m][3],
                   (ks & 1) ? xs[ks >> 1].z : xs[ks >> 1].x, (ks & 1) ? xs[ks >> 1].w : xs[ks >> 1].y);
        }
      }
      if (q == 0) {
        #pragma unroll
        for (int m = 0; m < 8; m++) stsf(sb + OFF_GU + (8 * m + g) * 48 + 4 * warp, d[m >> 1][2 * (m & 1)]);
      }
      bar_arrive(NB_ACT, 384);
    }
    {
      const uint32_t ky = __float_as_uint(ldsf(sb + OFF_KEY));
      const int row = 2047 - (ky & 2047) - 128 * m128;
      if ((uint32_t)row < 128u) {
        const int l = tid >> 3, vi = (j & 1) + ((lane >> 2) & 1), e = 3 * vi + q - 4 * (j & 1);
        const float kr = __uint_as_float((ky & ~2047u) ^ ((ky >> 31) ? 0x80000000u : 0xfffff800u));
        const int col = 32 * (l & 3) + 16 * (e & 1) + 4 * (e & 2) + (l >> 2);
        const float sg = rcp(1.f + ex2(-LOG2E * kr));
        const uint32_t base = __float_as_uint(ldsf(sb + OFF_OUT + (col >> 6) * 16384 + row * 128 + ((((col >> 3) ^ row) & 7) << 4) + 2 * (col & 6)));
        const float4* yp = &G->yacc[(q * 3 + vi) * 128 + 32 * (j >> 1) + l];
        uint32_t it = 0;
        uint4 v;
        mbar_wait(sb + B_SD, 0);
        do { v = ld128_rlx(yp); } while (__any_sync(~0u, __uint_as_float(v.w) != (float)(NFFN / 4)) && ++it < POLL_LIMIT);
        float y0 = __uint_as_float(v.x), y1 = __uint_as_float(v.y), y2 = __uint_as_float(v.z);
        #pragma unroll
        for (int o = 1; o < 4; o <<= 1) { y0 += __shfl_xor_sync(~0u, y0, o); y1 += __shfl_xor_sync(~0u, y1, o); y2 += __shfl_xor_sync(~0u, y2, o); }
        if (q < 3 && (uint32_t)e < 4u)
          P.out_p[(size_t)(128 * m128 + row) * DM + 128 * j + col] = __float2bfloat16(fmaf(q == 0 ? y0 : q == 1 ? y1 : y2, sg, (col & 1) ? bf_hi(base) : bf_lo(base)));
      }
      if (c == 0 && tid == 0) st32_rlx(&G->epoch, __float_as_uint(ldsf(sb + OFF_EP)));
      if (warp == 0) { TSW(22); }
      if (wg == 0) { TDUMP(); }
    }
  }
  if (wg == 2) {
    uint32_t wf[16][2][4];
    {
      const uint32_t wb = sb + OFF_S + 16384 * (wp & 1) + ((lane & 7) + ((lane >> 4) << 3)) * 128 + ((((lane >> 3) & 1) ^ (lane & 7)) << 4);
      if (f < NFFN_L) mbar_wait(sb + B_WD + 8 * wp, 0);
      if (wp == 0) { TK(61); }
      #pragma unroll
      for (int i = 0; i < 32; i++) ldsm4t((wb ^ (((i >> 1) & 3) << 5)) + (i >> 3) * 4096 + (i & 1) * 2048, wf[i >> 1][i & 1][0], wf[i >> 1][i & 1][1], wf[i >> 1][i & 1][2], wf[i >> 1][i & 1][3]);
      fence_async_smem();
      __syncwarp();
      if (lane == 0) mbar_arrive(sb + B_WC + 8 * wp);
      if (wp == 0) { TK(62); }
    }
    bar_sync(NB_G2E, TRKL == 3 ? 256 : 384);
    {
      uint32_t cur = 0;
      uint4 v;
      #pragma unroll 1
      for (uint32_t it = 0; it < POLL_LIMIT; it++) {
        const uint4 kx = ld128_rlx(&G->key[(KSEL & (8 * KR - 1)) * 128 + 4 * lane]);
        v = ld128_rlx(&G->cand[((~cur >> 4) & 127) * 512 + 4 * t]);
        uint32_t best;
        asm volatile("redux.sync.max.u32 %0, %1, 0xffffffff;" : "=r"(best) : "r"(max(max(kx.x, kx.y), max(kx.z, kx.w))));
        if (!__any_sync(~0u, min(min(kx.x, kx.y), min(kx.z, kx.w)) == 0 || v.w == ~0u) && best == cur) break;
        cur = best;
      }
      sts128(sb + OFF_XSEL + 16 * t, v.x, v.y, v.z, v.w);
      sts32(sb + OFF_KEY, cur);
      bar_arrive(NB_XS, 384);
      TSW(18);
      bar_sync(NB_ACT, 384);
    }
    float gu[2];
    #pragma unroll
    for (int i = 0; i < 2; i++) {
      const uint4 v0 = lds128(sb + OFF_GU + (32 * i + lane) * 48), v1 = lds128(sb + OFF_GU + (32 * i + lane) * 48 + 16);
      gu[i] = ((__uint_as_float(v0.x) + __uint_as_float(v0.y)) + (__uint_as_float(v0.z) + __uint_as_float(v0.w))) +
              ((__uint_as_float(v1.x) + __uint_as_float(v1.y)) + (__uint_as_float(v1.z) + __uint_as_float(v1.w)));
    }
    const float act = gu[0] * gu[1] * rcp(1.f + ex2(-LOG2E * gu[0]));
    const uint32_t ap = pack_bf16(act, __shfl_down_sync(~0u, act, 1));
    uint32_t bf[4];
    #pragma unroll
    for (int i = 0; i < 4; i++) bf[i] = __shfl_sync(~0u, ap, 2 * q + 8 * i);
    TSW(20);
    float d[16][4];
    #pragma unroll
    for (int k = 0; k < 2; k++)
      #pragma unroll
      for (int i = 0; i < 16; i++) {
        if (k == 0) { d[i][0] = 0.f; d[i][1] = 0.f; d[i][2] = 0.f; d[i][3] = 0.f; }
        mma16816(d[i][0], d[i][1], d[i][2], d[i][3], wf[i][k][0], wf[i][k][1], wf[i][k][2], wf[i][k][3], bf[2*k], bf[2*k+1]);
      }
    float y[9];
    #pragma unroll
    for (int e = 0; e < 8; e++) {
      const int n = 2 * (e & 4) + (e & 1);
      const float lo = (q & 1) ? d[n + 2][e & 2] : d[n][e & 2], hi = (q & 1) ? d[n + 6][e & 2] : d[n + 4][e & 2];
      y[e] = (q & 2) ? hi : lo;
    }
    y[8] = 0.f;
    if (f < NFFN) {
      #pragma unroll
      for (int i = 0; i < 3; i++) red_add_f32x4(&G->yacc[((f & 3) * 3 + i) * 128 + t], y[3*i], y[3*i+1], y[3*i+2], 1.f);
    }
    TSW(21);
  }
  }
  cluster_wait();
}

typedef CUresult (*EncodeFn)(CUtensorMap*, CUtensorMapDataType, cuuint32_t, void*, const cuuint64_t*, const cuuint64_t*,
                             const cuuint32_t*, const cuuint32_t*, CUtensorMapInterleave, CUtensorMapSwizzle,
                             CUtensorMapL2promotion, CUtensorMapFloatOOBfill);

void make_map(EncodeFn enc, CUtensorMap* m, const void* p, int n, const cuuint64_t* dims, const cuuint64_t* str, const cuuint32_t* box,
              CUtensorMapSwizzle sw, CUtensorMapL2promotion promo) {
  cuuint32_t es[5] = {1, 1, 1, 1, 1};
  enc(m, CU_TENSOR_MAP_DATA_TYPE_BFLOAT16, n, const_cast<void*>(p), dims, str, box, es, CU_TENSOR_MAP_INTERLEAVE_NONE, sw, promo,
      CU_TENSOR_MAP_FLOAT_OOB_FILL_NONE);
}
void map2(EncodeFn enc, CUtensorMap* m, const void* p, uint64_t cols, uint64_t rows, uint32_t bc, uint32_t br, CUtensorMapSwizzle sw,
          CUtensorMapL2promotion promo) {
  const cuuint64_t dims[2] = {cols, rows}, str[1] = {cols * 2};
  const cuuint32_t box[2] = {bc, br};
  make_map(enc, m, p, 2, dims, str, box, sw, promo);
}
void map3(EncodeFn enc, CUtensorMap* m, const void* p, uint64_t cols, uint64_t rows, uint32_t br, uint32_t nb) {
  const cuuint64_t dims[3] = {64, rows, cols / 64}, str[2] = {cols * 2, 128};
  const cuuint32_t box[3] = {64, br, nb};
  make_map(enc, m, p, 3, dims, str, box, CU_TENSOR_MAP_SWIZZLE_128B, CU_TENSOR_MAP_L2_PROMOTION_L2_128B);
}

}

extern "C" void kernel_launch(void* const* d_in, const int* in_sizes, int n_in, void* d_out, int out_size) {
  (void)in_sizes; (void)n_in; (void)out_size;
  static EncodeFn enc = nullptr;
  static void* o_ptr = nullptr;
  if (!enc) {
    void* f = nullptr; cudaDriverEntryPointQueryResult qr;
    cudaGetDriverEntryPoint("cuTensorMapEncodeTiled", &f, cudaEnableDefault, &qr);
    enc = (EncodeFn)f;
    cudaGetSymbolAddress(&o_ptr, g_scr);
    cudaFuncSetAttribute(fused_kernel, cudaFuncAttributeMaxDynamicSharedMemorySize, SMEM_BYTES);
  }
  const bf16* x = (const bf16*)d_in[0];
  const bf16* wqkv = (const bf16*)d_in[1];
  const bf16* wphi = (const bf16*)d_in[2];
  const bf16* wo = (const bf16*)d_in[3];
  const bf16* wr = (const bf16*)d_in[5];
  const bf16* wgate = (const bf16*)d_in[6];
  const bf16* wup = (const bf16*)d_in[7];
  const bf16* wdown = (const bf16*)d_in[8];
  Params P;
  const CUtensorMapSwizzle S128 = CU_TENSOR_MAP_SWIZZLE_128B, S64 = CU_TENSOR_MAP_SWIZZLE_64B;
  const CUtensorMapL2promotion L128 = CU_TENSOR_MAP_L2_PROMOTION_L2_128B, L256 = CU_TENSOR_MAP_L2_PROMOTION_L2_256B,
                               L64 = CU_TENSOR_MAP_L2_PROMOTION_L2_64B;
  map2(enc, &P.x128, x, DM, SEQ, 64, 128, S128, L256);
  map2(enc, &P.x64, x, DM, SEQ, 64, 64, S128, L128);
  {
    const cuuint64_t dims[4] = {64, DM, 16, 3}, str[3] = {6 * DM, 128, 2 * DM};
    const cuuint32_t box[4] = {64, 64, 1, 2};
    make_map(enc, &P.wkv, wqkv, 4, dims, str, box, S128, L128);
  }
  map3(enc, &P.wq, wqkv, 3 * DM, DM, 64, 2);
  for (int i = 0; i < 2; i++) {
    const cuuint64_t dims[5] = {DM, (cuuint64_t)(DM - 94 - 64 * i), 4, 4, 2}, str[4] = {2 * DM, 16 * DM, 4 * DM, (cuuint64_t)(128 * DM) << i};
    const cuuint32_t box[5] = {64, 2, 4, 4, 2};
    make_map(enc, &P.wo[i], wo, 5, dims, str, box, S128, L128);
  }
  map3(enc, &P.wd, wdown, DM, FF, 32, 4);
  map2(enc, &P.wg, wgate, FF, DM, 32, 128, S64, L64);
  map2(enc, &P.wu, wup, FF, DM, 32, 128, S64, L64);
  map2(enc, &P.tg, wgate, FF, DM, 8, 16, CU_TENSOR_MAP_SWIZZLE_NONE, L128);
  map2(enc, &P.tu, wup, FF, DM, 8, 16, CU_TENSOR_MAP_SWIZZLE_NONE, L128);
  map2(enc, &P.td, wdown, 128, FF * 8, 8, 16, CU_TENSOR_MAP_SWIZZLE_NONE, L256);
  map2(enc, &P.xs, x, DM, SEQ, 128, 16, CU_TENSOR_MAP_SWIZZLE_NONE, L256);
  map2(enc, &P.ws, wqkv, 3 * DM, DM, 16, 128, CU_TENSOR_MAP_SWIZZLE_NONE, L128);
  map2(enc, &P.qs, wqkv, 3 * DM, DM, 32, 128, CU_TENSOR_MAP_SWIZZLE_NONE, L64);
  map2(enc, &P.out, d_out, DM, SEQ, 64, 16, S128, L128);
  map2(enc, &P.o, o_ptr, 256, SEQ * DM / 256, 256, 16, CU_TENSOR_MAP_SWIZZLE_NONE, L128);
  map2(enc, &P.phi, wphi, 32, 1024, 32, 32, S64, L64);
  P.x = x; P.wqkv = wqkv; P.wo_p = wo; P.wd_p = wdown; P.wg_p = wgate; P.wu_p = wup; P.wr = wr; P.out_p = (bf16*)d_out; P.g = (Scratch*)o_ptr; P.zero = 0;

  cudaLaunchConfig_t cfg = {};
  cfg.gridDim = dim3(128); cfg.blockDim = dim3(512); cfg.dynamicSmemBytes = SMEM_BYTES; cfg.stream = cudaStreamPerThread;
  cudaLaunchAttribute at[1];
  at[0].id = cudaLaunchAttributeClusterDimension; at[0].val.clusterDim.x = 2; at[0].val.clusterDim.y = 1; at[0].val.clusterDim.z = 1;
  cfg.attrs = at; cfg.numAttrs = 1;
  cudaLaunchKernelEx(&cfg, fused_kernel, P);
}
```

```cpp
#include <cuda_runtime.h>
#include <cuda.h>
#include <cuda_bf16.h>
#include <stdint.h>

namespace {

typedef __nv_bfloat16 bf16;

#define JIT()
__device__ __forceinline__ uint32_t smem_u32(const void* p){ return (uint32_t)__cvta_generic_to_shared(p); }
__device__ __forceinline__ void mbar_init(uint32_t bar, uint32_t cnt){ asm volatile("mbarrier.init.shared::cta.b64 [%0], %1;"::"r"(bar),"r"(cnt):"memory"); }
__device__ __forceinline__ void mbar_expect_tx(uint32_t bar, uint32_t bytes){ asm volatile("mbarrier.arrive.expect_tx.shared::cta.b64 _, [%0], %1;"::"r"(bar),"r"(bytes):"memory"); }
__device__ __forceinline__ void mbar_arrive(uint32_t bar){ JIT(); asm volatile("mbarrier.arrive.shared::cta.b64 _, [%0];"::"r"(bar):"memory"); }
__device__ __forceinline__ uint32_t mapa(uint32_t addr, uint32_t cta){ uint32_t r; asm volatile("mapa.shared::cluster.u32 %0, %1, %2;":"=r"(r):"r"(addr),"r"(cta)); return r; }
__device__ __forceinline__ void mbar_arrive_at(uint32_t bar, uint32_t cta, uint32_t cnt){ JIT();
  asm volatile("{\n.reg .b32 ra;\nmapa.shared::cluster.u32 ra, %0, %1;\nmbarrier.arrive.shared::cluster.b64 _, [ra], %2;\n}\n"::"r"(bar),"r"(cta),"r"(cnt):"memory"); }
__device__ __forceinline__ void mbar_arrive_remote(uint32_t cluster_addr, uint32_t cnt){ JIT();
  asm volatile("mbarrier.arrive.shared::cluster.b64 _, [%0], %1;"::"r"(cluster_addr),"r"(cnt):"memory"); }
__device__ __forceinline__ void mbar_wait(uint32_t bar, uint32_t parity){ JIT();
  asm volatile("{\n.reg .pred p;\n.reg .u32 c;\nmov.u32 c, 0;\nLW:\nmbarrier.try_wait.parity.shared::cta.b64 p, [%0], %1;\n@p bra LD;\nadd.u32 c, c, 1;\nsetp.lt.u32 p, c, 2000000;\n@p bra LW;\ntrap;\nLD:\n}\n"::"r"(bar),"r"(parity):"memory"); }
__device__ __forceinline__ void mbar_wait2(uint32_t bar0, uint32_t par0, uint32_t bar1, uint32_t par1){ JIT();
  asm volatile("{\n.reg .pred p, q;\n.reg .u32 c;\nmov.u32 c, 0;\nLW:\nmbarrier.try_wait.parity.shared::cta.b64 p, [%0], %1;\nmbarrier.try_wait.parity.shared::cta.b64 q, [%2], %3;\nand.pred p, p, q;\n@p bra LD;\nadd.u32 c, c, 1;\nsetp.lt.u32 p, c, 2000000;\n@p bra LW;\ntrap;\nLD:\n}\n"::"r"(bar0),"r"(par0),"r"(bar1),"r"(par1):"memory"); }
__device__ __forceinline__ bool mbar_test2(uint32_t bar0, uint32_t par0, uint32_t bar1, uint32_t par1){
  uint32_t r;
  asm volatile("{\n.reg .pred p, q;\nmbarrier.test_wait.parity.shared::cta.b64 p, [%1], %2;\nmbarrier.test_wait.parity.shared::cta.b64 q, [%3], %4;\nand.pred p, p, q;\nselp.u32 %0, 1, 0, p;\n}\n":"=r"(r):"r"(bar0),"r"(par0),"r"(bar1),"r"(par1):"memory");
  return r; }
__device__ __forceinline__ void tma_2d(uint32_t dst, const CUtensorMap* m, int c0, int c1, uint32_t bar){
  asm volatile("cp.async.bulk.tensor.2d.shared::cluster.global.mbarrier::complete_tx::bytes [%0], [%1, {%3, %4}], [%2];"::"r"(dst),"l"(m),"r"(bar),"r"(c0),"r"(c1):"memory"); }
__device__ __forceinline__ void tma_2d_mc(uint32_t dst, const CUtensorMap* m, int c0, int c1, uint32_t bar){
  asm volatile("cp.async.bulk.tensor.2d.shared::cluster.global.mbarrier::complete_tx::bytes.multicast::cluster [%0], [%1, {%3, %4}], [%2], %5;"::"r"(dst),"l"(m),"r"(bar),"r"(c0),"r"(c1),"h"((uint16_t)3):"memory"); }
__device__ __forceinline__ void tma_2d_mc_h(uint32_t dst, const CUtensorMap* m, int c0, int c1, uint32_t bar, uint64_t pol){
  asm volatile("cp.async.bulk.tensor.2d.shared::cluster.global.mbarrier::complete_tx::bytes.multicast::cluster.L2::cache_hint [%0], [%1, {%3, %4}], [%2], %5, %6;"::"r"(dst),"l"(m),"r"(bar),"r"(c0),"r"(c1),"h"((uint16_t)3),"l"(pol):"memory"); }
__device__ __forceinline__ void tma_4d(uint32_t dst, const CUtensorMap* m, int c0, int c1, int c2, int c3, uint32_t bar){
  asm volatile("cp.async.bulk.tensor.4d.shared::cluster.global.mbarrier::complete_tx::bytes [%0], [%1, {%3, %4, %5, %6}], [%2];"::"r"(dst),"l"(m),"r"(bar),"r"(c0),"r"(c1),"r"(c2),"r"(c3):"memory"); }
__device__ __forceinline__ uint64_t policy_evict_first(){ uint64_t p; asm volatile("createpolicy.fractional.L2::evict_first.b64 %0, 1.0;":"=l"(p)); return p; }
__device__ __forceinline__ uint64_t policy_evict_normal(){ uint64_t p; asm("createpolicy.fractional.L2::evict_normal.b64 %0, 1.0;":"=l"(p)); return p; }
__device__ __forceinline__ void tma_3d_h(uint32_t dst, const CUtensorMap* m, int c0, int c1, int c2, uint32_t bar, uint64_t pol){
  asm volatile("cp.async.bulk.tensor.3d.shared::cluster.global.mbarrier::complete_tx::bytes.L2::cache_hint [%0], [%1, {%3, %4, %5}], [%2], %6;"::"r"(dst),"l"(m),"r"(bar),"r"(c0),"r"(c1),"r"(c2),"l"(pol):"memory"); }
__device__ __forceinline__ void tma_4d_h(uint32_t dst, const CUtensorMap* m, int c0, int c1, int c2, int c3, uint32_t bar, uint64_t pol){
  asm volatile("cp.async.bulk.tensor.4d.shared::cluster.global.mbarrier::complete_tx::bytes.L2::cache_hint [%0], [%1, {%3, %4, %5, %6}], [%2], %7;"::"r"(dst),"l"(m),"r"(bar),"r"(c0),"r"(c1),"r"(c2),"r"(c3),"l"(pol):"memory"); }
__device__ __forceinline__ void red_add_f32x4(float4* p, float x, float y, float z, float w){ asm volatile("red.relaxed.gpu.global.add.v4.f32 [%0], {%1,%2,%3,%4};"::"l"(p),"f"(x),"f"(y),"f"(z),"f"(w):"memory"); }
__device__ __forceinline__ void tma_5d_h(uint32_t dst, const CUtensorMap* m, int c0, int c1, uint32_t bar, uint64_t pol){
  asm volatile("cp.async.bulk.tensor.5d.shared::cluster.global.mbarrier::complete_tx::bytes.L2::cache_hint [%0], [%1, {%3, %4, 0, 0, 0}], [%2], %5;"::"r"(dst),"l"(m),"r"(bar),"r"(c0),"r"(c1),"l"(pol):"memory"); }
__device__ __forceinline__ void tma_store_2d(const CUtensorMap* m, int c0, int c1, uint32_t src){
  asm volatile("cp.async.bulk.tensor.2d.global.shared::cta.bulk_group [%0, {%2, %3}], [%1];"::"l"(m),"r"(src),"r"(c0),"r"(c1):"memory"); }
__device__ __forceinline__ void bulk_commit(){ asm volatile("cp.async.bulk.commit_group;":::"memory"); }
__device__ __forceinline__ void bulk_wait_all(){ asm volatile("cp.async.bulk.wait_group 0;":::"memory"); }
__device__ __forceinline__ void fence_async_global(){ asm volatile("fence.proxy.async.global;":::"memory"); }
__device__ __forceinline__ bool elect_one(){ uint32_t p; asm volatile("{\n.reg .pred P;\nelect.sync _|P, 0xffffffff;\nselp.b32 %0, 1, 0, P;\n}\n":"=r"(p)); return p; }
__device__ __forceinline__ void bulk_prefetch(const void* p, uint32_t bytes){
  asm volatile("cp.async.bulk.prefetch.L2.global [%0], %1;"::"l"(p),"r"(bytes):"memory"); }
__device__ __forceinline__ void bulk_s2peer(uint32_t dst_cluster, uint32_t src, uint32_t bytes, uint32_t bar_cluster){
  asm volatile("cp.async.bulk.shared::cluster.shared::cta.mbarrier::complete_tx::bytes [%0], [%1], %2, [%3];"::"r"(dst_cluster),"r"(src),"r"(bytes),"r"(bar_cluster):"memory"); }
__device__ __forceinline__ void prefetch_map(const CUtensorMap* m){ asm volatile("prefetch.tensormap [%0];"::"l"(m):"memory"); }
__device__ __forceinline__ void fence_async_smem(){ asm volatile("fence.proxy.async.shared::cta;":::"memory"); }
__device__ __forceinline__ void fence_acquire_gpu(){ asm volatile("fence.acquire.gpu;":::"memory"); }
__device__ __forceinline__ void fence_gpu(){ asm volatile("fence.acq_rel.gpu;":::"memory"); }
__device__ __forceinline__ void wg_fence(){ asm volatile("wgmma.fence.sync.aligned;":::"memory"); }
__device__ __forceinline__ void wg_commit(){ asm volatile("wgmma.commit_group.sync.aligned;":::"memory"); }
template<int N> __device__ __forceinline__ void wg_wait(){ asm volatile("wgmma.wait_group.sync.aligned %0;"::"n"(N):"memory"); }
template<int N> __device__ __forceinline__ void fence_regs(float (&d)[N]){
  #pragma unroll
  for(int i=0;i<N;i++) asm volatile("":"+f"(d[i])::"memory"); }
__device__ __forceinline__ void bar_sync(int id, int n){ JIT(); asm volatile("bar.sync %0, %1;"::"r"(id),"r"(n):"memory"); }
__device__ __forceinline__ void bar_arrive(int id, int n){ JIT(); asm volatile("bar.arrive %0, %1;"::"r"(id),"r"(n):"memory"); }
__device__ __forceinline__ void cluster_arrive(){ asm volatile("barrier.cluster.arrive.relaxed.aligned;":::"memory"); }
__device__ __forceinline__ void cluster_wait(){ asm volatile("barrier.cluster.wait.aligned;":::"memory"); }
__host__ __device__ constexpr uint32_t dlo(uint32_t addr, uint32_t lbo){ return (addr >> 4) | ((lbo >> 4) << 16); }
__host__ __device__ constexpr uint32_t dhi(uint32_t sbo, uint32_t sw){ return (sbo >> 4) | (sw << 30); }
constexpr uint32_t H128 = dhi(1024, 1), H64 = dhi(512, 2), H0 = dhi(128, 0);
__device__ __forceinline__ uint32_t pack_bf16(float lo, float hi){ uint32_t r; asm("cvt.rn.bf16x2.f32 %0, %1, %2;":"=r"(r):"f"(hi),"f"(lo)); return r; }
__device__ __forceinline__ float bf_lo(uint32_t v){ return __uint_as_float(v<<16); }
__device__ __forceinline__ float bf_hi(uint32_t v){ return __uint_as_float(v&0xffff0000u); }
__device__ __forceinline__ float ex2(float x){ float r; asm("ex2.approx.ftz.f32 %0, %1;":"=f"(r):"f"(x)); return r; }
__device__ __forceinline__ float rcp(float x){ float r; asm("rcp.approx.ftz.f32 %0, %1;":"=f"(r):"f"(x)); return r; }
__device__ __forceinline__ void stsm4(uint32_t addr, uint32_t a, uint32_t b, uint32_t c, uint32_t d){
  asm volatile("stmatrix.sync.aligned.m8n8.x4.shared.b16 [%0], {%1,%2,%3,%4};"::"r"(addr),"r"(a),"r"(b),"r"(c),"r"(d)); }
__device__ __forceinline__ void stsm2(uint32_t addr, uint32_t a, uint32_t b){
  asm volatile("stmatrix.sync.aligned.m8n8.x2.shared.b16 [%0], {%1,%2};"::"r"(addr),"r"(a),"r"(b)); }
__device__ __forceinline__ void mma16816(float& d0, float& d1, float& d2, float& d3, uint32_t a0, uint32_t a1, uint32_t a2, uint32_t a3, uint32_t b0, uint32_t b1){
  asm volatile("mma.sync.aligned.m16n8k16.row.col.f32.bf16.bf16.f32 {%0,%1,%2,%3}, {%4,%5,%6,%7}, {%8,%9}, {%0,%1,%2,%3};"
               : "+f"(d0), "+f"(d1), "+f"(d2), "+f"(d3) : "r"(a0), "r"(a1), "r"(a2), "r"(a3), "r"(b0), "r"(b1)); }
__device__ __forceinline__ uint32_t transpose8(uint32_t a){ uint32_t r; asm volatile("movmatrix.sync.aligned.m8n8.trans.b16 %0, %1;":"=r"(r):"r"(a)); return r; }
__device__ __forceinline__ void ldsm4(uint32_t addr, uint32_t& a, uint32_t& b, uint32_t& c, uint32_t& d){
  asm volatile("ldmatrix.sync.aligned.m8n8.x4.shared.b16 {%0,%1,%2,%3}, [%4];":"=r"(a),"=r"(b),"=r"(c),"=r"(d):"r"(addr):"memory"); }
__device__ __forceinline__ void ldsm4t(uint32_t addr, uint32_t& a, uint32_t& b, uint32_t& c, uint32_t& d){
  asm volatile("ldmatrix.sync.aligned.m8n8.x4.trans.shared.b16 {%0,%1,%2,%3}, [%4];":"=r"(a),"=r"(b),"=r"(c),"=r"(d):"r"(addr):"memory"); }
__device__ __forceinline__ void sts32(uint32_t a, uint32_t v){ asm volatile("st.shared.b32 [%0], %1;"::"r"(a),"r"(v):"memory"); }
__device__ __forceinline__ void stsf(uint32_t a, float v){ asm volatile("st.shared.f32 [%0], %1;"::"r"(a),"f"(v):"memory"); }
__device__ __forceinline__ void sts64(uint32_t a, uint32_t x, uint32_t y){ asm volatile("st.shared.v2.b32 [%0], {%1,%2};"::"r"(a),"r"(x),"r"(y):"memory"); }
__device__ __forceinline__ void sts128(uint32_t a, uint32_t x, uint32_t y, uint32_t z, uint32_t w){ asm volatile("st.shared.v4.b32 [%0], {%1,%2,%3,%4};"::"r"(a),"r"(x),"r"(y),"r"(z),"r"(w):"memory"); }
__device__ __forceinline__ float ldsf(uint32_t a){ float v; asm volatile("ld.shared.f32 %0, [%1];":"=f"(v):"r"(a):"memory"); return v; }
__device__ __forceinline__ float2 lds64f(uint32_t a){ float2 v; asm volatile("ld.shared.v2.f32 {%0,%1}, [%2];":"=f"(v.x),"=f"(v.y):"r"(a):"memory"); return v; }
__device__ __forceinline__ uint4 lds128(uint32_t a){ uint4 v; asm volatile("ld.shared.v4.u32 {%0,%1,%2,%3}, [%4];":"=r"(v.x),"=r"(v.y),"=r"(v.z),"=r"(v.w):"r"(a):"memory"); return v; }
__device__ __forceinline__ uint4 ld128_keep(const void* p){ uint4 v; asm volatile("ld.global.v4.u32 {%0,%1,%2,%3}, [%4];":"=r"(v.x),"=r"(v.y),"=r"(v.z),"=r"(v.w):"l"(p):"memory"); return v; }
__device__ __forceinline__ uint4 ld128_rlx(const void* p){ uint4 v; asm volatile("ld.relaxed.gpu.global.v4.u32 {%0,%1,%2,%3}, [%4];":"=r"(v.x),"=r"(v.y),"=r"(v.z),"=r"(v.w):"l"(p):"memory"); return v; }
__device__ __forceinline__ uint32_t ld32_rlx(const void* p){ uint32_t v; asm volatile("ld.relaxed.gpu.global.u32 %0, [%1];":"=r"(v):"l"(p):"memory"); return v; }
__device__ __forceinline__ void st128_rlx(void* p, uint32_t x, uint32_t y, uint32_t z, uint32_t w){ asm volatile("st.relaxed.gpu.global.v4.u32 [%0], {%1,%2,%3,%4};"::"l"(p),"r"(x),"r"(y),"r"(z),"r"(w):"memory"); }
__device__ __forceinline__ void st64_rlx(void* p, uint32_t x, uint32_t y){ asm volatile("st.relaxed.gpu.global.v2.u32 [%0], {%1,%2};"::"l"(p),"r"(x),"r"(y):"memory"); }
__device__ __forceinline__ void st32_rlx(void* p, uint32_t x){ asm volatile("st.relaxed.gpu.global.u32 [%0], %1;"::"l"(p),"r"(x):"memory"); }
__device__ __forceinline__ void flags_wait(uint32_t& missing, const uint32_t* p, uint32_t need){
  asm volatile("{\n.reg .pred p;\n.reg .u32 c, v;\nmov.u32 c, 0;\nLW:\nand.b32 v, %0, %2;\nsetp.eq.u32 p, v, 0;\n@p bra.uni LD;\nld.relaxed.gpu.global.u32 v, [%1];\nsetp.eq.u32 p, v, 0;\n"
               "vote.sync.ballot.b32 %0, p, 0xffffffff;\nadd.u32 c, c, 1;\nsetp.lt.u32 p, c, 4000000;\n@p bra.uni LW;\nLD:\n}\n":"+r"(missing):"l"(p),"r"(need):"memory"); }
__device__ __forceinline__ uint32_t tagw(float x, uint32_t t){ return (__float_as_uint(x) & ~3u) | t; }
__device__ __forceinline__ float untag(uint32_t w){ return __uint_as_float(w & ~3u); }

template<int TA, int TB, uint32_t HA, uint32_t HB> __device__ __forceinline__ void wgmma_ss_n128(float (&d)[64], uint32_t da, uint32_t db, int scale_d){
  asm volatile("{\n.reg .pred p;\n.reg .b64 a, b;\nsetp.ne.b32 p, %70, 0;\nmov.b64 a, {%64, %68};\nmov.b64 b, {%65, %69};\n"
  "wgmma.mma_async.sync.aligned.m64n128k16.f32.bf16.bf16 {%0, %1, %2, %3, %4, %5, %6, %7, %8, %9, %10, %11, %12, %13, %14, %15, %16, %17, %18, %19, %20, %21, %22, %23, %24, %25, %26, %27, %28, %29, %30, %31, %32, %33, %34, %35, %36, %37, %38, %39, %40, %41, %42, %43, %44, %45, %46, %47, %48, %49, %50, %51, %52, %53, %54, %55, %56, %57, %58, %59, %60, %61, %62, %63}, a, b, p, 1, 1, %66, %67;\n}\n"
  : "+f"(d[0]), "+f"(d[1]), "+f"(d[2]), "+f"(d[3]), "+f"(d[4]), "+f"(d[5]), "+f"(d[6]), "+f"(d[7]), "+f"(d[8]), "+f"(d[9]), "+f"(d[10]), "+f"(d[11]), "+f"(d[12]), "+f"(d[13]), "+f"(d[14]), "+f"(d[15]), "+f"(d[16]), "+f"(d[17]), "+f"(d[18]), "+f"(d[19]), "+f"(d[20]), "+f"(d[21]), "+f"(d[22]), "+f"(d[23]), "+f"(d[24]), "+f"(d[25]), "+f"(d[26]), "+f"(d[27]), "+f"(d[28]), "+f"(d[29]), "+f"(d[30]), "+f"(d[31]), "+f"(d[32]), "+f"(d[33]), "+f"(d[34]), "+f"(d[35]), "+f"(d[36]), "+f"(d[37]), "+f"(d[38]), "+f"(d[39]), "+f"(d[40]), "+f"(d[41]), "+f"(d[42]), "+f"(d[43]), "+f"(d[44]), "+f"(d[45]), "+f"(d[46]), "+f"(d[47]), "+f"(d[48]), "+f"(d[49]), "+f"(d[50]), "+f"(d[51]), "+f"(d[52]), "+f"(d[53]), "+f"(d[54]), "+f"(d[55]), "+f"(d[56]), "+f"(d[57]), "+f"(d[58]), "+f"(d[59]), "+f"(d[60]), "+f"(d[61]), "+f"(d[62]), "+f"(d[63])
  : "r"(da), "r"(db), "n"(TA), "n"(TB), "n"(HA), "n"(HB), "r"(scale_d));
}
template<int TA, int TB, uint32_t HA, uint32_t HB> __device__ __forceinline__ void wgmma_sa_n128(float (&d)[64], uint32_t da, uint32_t db){
  asm volatile("{\n.reg .pred p;\n.reg .b64 a, b;\nsetp.ne.b32 p, 1, 0;\nmov.b64 a, {%64, %68};\nmov.b64 b, {%65, %69};\n"
  "wgmma.mma_async.sync.aligned.m64n128k16.f32.bf16.bf16 {%0, %1, %2, %3, %4, %5, %6, %7, %8, %9, %10, %11, %12, %13, %14, %15, %16, %17, %18, %19, %20, %21, %22, %23, %24, %25, %26, %27, %28, %29, %30, %31, %32, %33, %34, %35, %36, %37, %38, %39, %40, %41, %42, %43, %44, %45, %46, %47, %48, %49, %50, %51, %52, %53, %54, %55, %56, %57, %58, %59, %60, %61, %62, %63}, a, b, p, 1, 1, %66, %67;\n}\n"
  : "+f"(d[0]), "+f"(d[1]), "+f"(d[2]), "+f"(d[3]), "+f"(d[4]), "+f"(d[5]), "+f"(d[6]), "+f"(d[7]), "+f"(d[8]), "+f"(d[9]), "+f"(d[10]), "+f"(d[11]), "+f"(d[12]), "+f"(d[13]), "+f"(d[14]), "+f"(d[15]), "+f"(d[16]), "+f"(d[17]), "+f"(d[18]), "+f"(d[19]), "+f"(d[20]), "+f"(d[21]), "+f"(d[22]), "+f"(d[23]), "+f"(d[24]), "+f"(d[25]), "+f"(d[26]), "+f"(d[27]), "+f"(d[28]), "+f"(d[29]), "+f"(d[30]), "+f"(d[31]), "+f"(d[32]), "+f"(d[33]), "+f"(d[34]), "+f"(d[35]), "+f"(d[36]), "+f"(d[37]), "+f"(d[38]), "+f"(d[39]), "+f"(d[40]), "+f"(d[41]), "+f"(d[42]), "+f"(d[43]), "+f"(d[44]), "+f"(d[45]), "+f"(d[46]), "+f"(d[47]), "+f"(d[48]), "+f"(d[49]), "+f"(d[50]), "+f"(d[51]), "+f"(d[52]), "+f"(d[53]), "+f"(d[54]), "+f"(d[55]), "+f"(d[56]), "+f"(d[57]), "+f"(d[58]), "+f"(d[59]), "+f"(d[60]), "+f"(d[61]), "+f"(d[62]), "+f"(d[63])
  : "r"(da), "r"(db), "n"(TA), "n"(TB), "n"(HA), "n"(HB));
}
template<int TA, int TB, uint32_t HA, uint32_t HB> __device__ __forceinline__ void wgmma_sa_n40(float (&d)[20], uint32_t da, uint32_t db){
  asm volatile("{\n.reg .pred p;\n.reg .b64 a, b;\nsetp.ne.b32 p, 1, 0;\nmov.b64 a, {%20, %24};\nmov.b64 b, {%21, %25};\n"
  "wgmma.mma_async.sync.aligned.m64n40k16.f32.bf16.bf16 {%0, %1, %2, %3, %4, %5, %6, %7, %8, %9, %10, %11, %12, %13, %14, %15, %16, %17, %18, %19}, a, b, p, 1, 1, %22, %23;\n}\n"
  : "+f"(d[0]), "+f"(d[1]), "+f"(d[2]), "+f"(d[3]), "+f"(d[4]), "+f"(d[5]), "+f"(d[6]), "+f"(d[7]), "+f"(d[8]), "+f"(d[9]), "+f"(d[10]), "+f"(d[11]), "+f"(d[12]), "+f"(d[13]), "+f"(d[14]), "+f"(d[15]), "+f"(d[16]), "+f"(d[17]), "+f"(d[18]), "+f"(d[19])
  : "r"(da), "r"(db), "n"(TA), "n"(TB), "n"(HA), "n"(HB));
}
template<int TA, int TB, uint32_t HA, uint32_t HB> __device__ __forceinline__ void wgmma_sz_n40(float (&d)[20], uint32_t da, uint32_t db){
  asm volatile("{\n.reg .pred p;\n.reg .b64 a, b;\nsetp.ne.b32 p, 0, 0;\nmov.b64 a, {%20, %24};\nmov.b64 b, {%21, %25};\n"
  "wgmma.mma_async.sync.aligned.m64n40k16.f32.bf16.bf16 {%0, %1, %2, %3, %4, %5, %6, %7, %8, %9, %10, %11, %12, %13, %14, %15, %16, %17, %18, %19}, a, b, p, 1, 1, %22, %23;\n}\n"
  : "=f"(d[0]), "=f"(d[1]), "=f"(d[2]), "=f"(d[3]), "=f"(d[4]), "=f"(d[5]), "=f"(d[6]), "=f"(d[7]), "=f"(d[8]), "=f"(d[9]), "=f"(d[10]), "=f"(d[11]), "=f"(d[12]), "=f"(d[13]), "=f"(d[14]), "=f"(d[15]), "=f"(d[16]), "=f"(d[17]), "=f"(d[18]), "=f"(d[19])
  : "r"(da), "r"(db), "n"(TA), "n"(TB), "n"(HA), "n"(HB));
}
template<int TA, int TB, uint32_t HA, uint32_t HB> __device__ __forceinline__ void wgmma_sa_n32(float (&d)[16], uint32_t da, uint32_t db){
  asm volatile("{\n.reg .pred p;\n.reg .b64 a, b;\nsetp.ne.b32 p, 1, 0;\nmov.b64 a, {%16, %20};\nmov.b64 b, {%17, %21};\n"
  "wgmma.mma_async.sync.aligned.m64n32k16.f32.bf16.bf16 {%0, %1, %2, %3, %4, %5, %6, %7, %8, %9, %10, %11, %12, %13, %14, %15}, a, b, p, 1, 1, %18, %19;\n}\n"
  : "+f"(d[0]), "+f"(d[1]), "+f"(d[2]), "+f"(d[3]), "+f"(d[4]), "+f"(d[5]), "+f"(d[6]), "+f"(d[7]), "+f"(d[8]), "+f"(d[9]), "+f"(d[10]), "+f"(d[11]), "+f"(d[12]), "+f"(d[13]), "+f"(d[14]), "+f"(d[15])
  : "r"(da), "r"(db), "n"(TA), "n"(TB), "n"(HA), "n"(HB));
}
template<int TA, int TB, uint32_t HA, uint32_t HB> __device__ __forceinline__ void wgmma_ss_n32(float (&d)[16], uint32_t da, uint32_t db, int scale_d){
  asm volatile("{\n.reg .pred p;\n.reg .b64 a, b;\nsetp.ne.b32 p, %22, 0;\nmov.b64 a, {%16, %20};\nmov.b64 b, {%17, %21};\n"
  "wgmma.mma_async.sync.aligned.m64n32k16.f32.bf16.bf16 {%0, %1, %2, %3, %4, %5, %6, %7, %8, %9, %10, %11, %12, %13, %14, %15}, a, b, p, 1, 1, %18, %19;\n}\n"
  : "+f"(d[0]), "+f"(d[1]), "+f"(d[2]), "+f"(d[3]), "+f"(d[4]), "+f"(d[5]), "+f"(d[6]), "+f"(d[7]), "+f"(d[8]), "+f"(d[9]), "+f"(d[10]), "+f"(d[11]), "+f"(d[12]), "+f"(d[13]), "+f"(d[14]), "+f"(d[15])
  : "r"(da), "r"(db), "n"(TA), "n"(TB), "n"(HA), "n"(HB), "r"(scale_d));
}
template<int TB, uint32_t HB> __device__ __forceinline__ void wgmma_ra_n32(float (&d)[16], uint32_t a0, uint32_t a1, uint32_t a2, uint32_t a3, uint32_t db){
  asm volatile("{\n.reg .pred p;\n.reg .b64 a, b;\nsetp.ne.b32 p, 1, 0;\nmov.b64 b, {%20, %22};\n"
  "wgmma.mma_async.sync.aligned.m64n32k16.f32.bf16.bf16 {%0, %1, %2, %3, %4, %5, %6, %7, %8, %9, %10, %11, %12, %13, %14, %15}, {%16,%17,%18,%19}, b, p, 1, 1, %21;\n}\n"
  : "+f"(d[0]), "+f"(d[1]), "+f"(d[2]), "+f"(d[3]), "+f"(d[4]), "+f"(d[5]), "+f"(d[6]), "+f"(d[7]), "+f"(d[8]), "+f"(d[9]), "+f"(d[10]), "+f"(d[11]), "+f"(d[12]), "+f"(d[13]), "+f"(d[14]), "+f"(d[15])
  : "r"(a0), "r"(a1), "r"(a2), "r"(a3), "r"(db), "n"(TB), "n"(HB));
}
template<int TB, uint32_t HB> __device__ __forceinline__ void wgmma_rs_n32(float (&d)[16], uint32_t a0, uint32_t a1, uint32_t a2, uint32_t a3, uint32_t db, int scale_d){
  asm volatile("{\n.reg .pred p;\n.reg .b64 a, b;\nsetp.ne.b32 p, %23, 0;\nmov.b64 b, {%20, %22};\n"
  "wgmma.mma_async.sync.aligned.m64n32k16.f32.bf16.bf16 {%0, %1, %2, %3, %4, %5, %6, %7, %8, %9, %10, %11, %12, %13, %14, %15}, {%16,%17,%18,%19}, b, p, 1, 1, %21;\n}\n"
  : "+f"(d[0]), "+f"(d[1]), "+f"(d[2]), "+f"(d[3]), "+f"(d[4]), "+f"(d[5]), "+f"(d[6]), "+f"(d[7]), "+f"(d[8]), "+f"(d[9]), "+f"(d[10]), "+f"(d[11]), "+f"(d[12]), "+f"(d[13]), "+f"(d[14]), "+f"(d[15])
  : "r"(a0), "r"(a1), "r"(a2), "r"(a3), "r"(db), "n"(TB), "n"(HB), "r"(scale_d));
}
template<int TB, uint32_t HB> __device__ __forceinline__ void wgmma_ra_n40(float (&d)[20], uint32_t a0, uint32_t a1, uint32_t a2, uint32_t a3, uint32_t db){
  asm volatile("{\n.reg .pred p;\n.reg .b64 a, b;\nsetp.ne.b32 p, 1, 0;\nmov.b64 b, {%24, %26};\n"
  "wgmma.mma_async.sync.aligned.m64n40k16.f32.bf16.bf16 {%0, %1, %2, %3, %4, %5, %6, %7, %8, %9, %10, %11, %12, %13, %14, %15, %16, %17, %18, %19}, {%20,%21,%22,%23}, b, p, 1, 1, %25;\n}\n"
  : "+f"(d[0]), "+f"(d[1]), "+f"(d[2]), "+f"(d[3]), "+f"(d[4]), "+f"(d[5]), "+f"(d[6]), "+f"(d[7]), "+f"(d[8]), "+f"(d[9]), "+f"(d[10]), "+f"(d[11]), "+f"(d[12]), "+f"(d[13]), "+f"(d[14]), "+f"(d[15]), "+f"(d[16]), "+f"(d[17]), "+f"(d[18]), "+f"(d[19])
  : "r"(a0), "r"(a1), "r"(a2), "r"(a3), "r"(db), "n"(TB), "n"(HB));
}
template<int TB, uint32_t HB> __device__ __forceinline__ void wgmma_rz_n40(float (&d)[20], uint32_t a0, uint32_t a1, uint32_t a2, uint32_t a3, uint32_t db){
  asm volatile("{\n.reg .pred p;\n.reg .b64 a, b;\nsetp.ne.b32 p, 0, 0;\nmov.b64 b, {%24, %26};\n"
  "wgmma.mma_async.sync.aligned.m64n40k16.f32.bf16.bf16 {%0, %1, %2, %3, %4, %5, %6, %7, %8, %9, %10, %11, %12, %13, %14, %15, %16, %17, %18, %19}, {%20,%21,%22,%23}, b, p, 1, 1, %25;\n}\n"
  : "=f"(d[0]), "=f"(d[1]), "=f"(d[2]), "=f"(d[3]), "=f"(d[4]), "=f"(d[5]), "=f"(d[6]), "=f"(d[7]), "=f"(d[8]), "=f"(d[9]), "=f"(d[10]), "=f"(d[11]), "=f"(d[12]), "=f"(d[13]), "=f"(d[14]), "=f"(d[15]), "=f"(d[16]), "=f"(d[17]), "=f"(d[18]), "=f"(d[19])
  : "r"(a0), "r"(a1), "r"(a2), "r"(a3), "r"(db), "n"(TB), "n"(HB));
}
template<int TB, uint32_t HB> __device__ __forceinline__ void wgmma_rz_n8(float (&d)[4], uint32_t a0, uint32_t a1, uint32_t a2, uint32_t a3, uint32_t db){
  asm volatile("{\n.reg .pred p;\n.reg .b64 a, b;\nsetp.ne.b32 p, 0, 0;\nmov.b64 b, {%8, %10};\n"
  "wgmma.mma_async.sync.aligned.m64n8k16.f32.bf16.bf16 {%0, %1, %2, %3}, {%4,%5,%6,%7}, b, p, 1, 1, %9;\n}\n"
  : "=f"(d[0]), "=f"(d[1]), "=f"(d[2]), "=f"(d[3])
  : "r"(a0), "r"(a1), "r"(a2), "r"(a3), "r"(db), "n"(TB), "n"(HB));
}

constexpr int SEQ = 2048, DM = 1024, FF = 3584;
constexpr float LOG2E = 1.4426950408889634f;
constexpr uint32_t POLL_LIMIT = 1u << 22;
#define NPRE0 1
#define NPREN 2
constexpr int NPRE = NPREN;
#define QW 0
#define RS_N 22
#define RS_D1 430
#define RS_D2 300
#define SKM 0x154
#define LAG 2
#define PF_T0 5000
#define PF_DT 800
#define NFFN_L NFFN
#define FF_DT 500
#define GRES 8
#define TMASK 0xffffff
#define PMASK 0xffffff
#define FF_T0 1
#define GPRE 0
#define REL 6
#define EFI 11
#define TKW 8
#define FF_ORD 0x76543210ba98ull
#define KT 0
#define KM 0xffff
#define KR2 1
#define KK(id) do { if (KT == 1) { TK(32 * wg + (id)); } } while (0)
#define PF_I0 0
#define PF_ST 7
#define PRK 3
#define TRKL 1
#define KR 4
#define KSEL c
#define XP 0
#define CAPL 2
#define OUT_D 400
#define OUT_0 0
#define ML 2
#define H2 1
#define H3 1
#define FUNN 1
constexpr int FUN = FUNN;
#define FF_N 6
#define FF_D2 350
constexpr int NFFN = 112;

constexpr uint32_t SB0 = 1024;
constexpr uint32_t KV_STAGE = 49152, R5 = 32768;
constexpr uint32_t OFF_X = 163840, OFF_S = 196608, OFF_WPHI = OFF_S + 20480, OFF_M = 229376, SMEM_BYTES = 232448;
constexpr uint32_t OFF_RS256 = 212992, OFF_ONES = OFF_RS256 + 1024, OFF_WPHIK1 = OFF_ONES + 1024, OFF_KVZ = OFF_S;
constexpr uint32_t OFF_WPHIK = OFF_S, OFF_BXK = OFF_S + 2048, OFF_AXK = OFF_S + 4096, OFF_G = OFF_S + 8192;
constexpr uint32_t OFF_AXQ = OFF_WPHI, OFF_BXQ = OFF_WPHI + 2048, OFF_WPHIQ = OFF_WPHI + 4096;
constexpr uint32_t B_FULLKV = OFF_M  , B_EMPTYKV = OFF_M + 32  ;
constexpr uint32_t B_EMPTY5 = OFF_M + 64  , B_UO = B_EMPTY5 + 48  , B_RC = B_UO + 32  ;
constexpr uint32_t B_OUT = B_RC + 16  , B_SD = B_OUT + 16, B_AUX = B_SD + 8, B_AUXQ = B_AUX + 8, B_RX = B_AUXQ + 8;
constexpr uint32_t B_FULL5 = B_RX + 8  , B_F = B_FULL5 + 40  , B_WD = B_F + 64  ;
constexpr uint32_t B_WC = B_WD + 32  , B_DR = B_WC + 32  , B_W = B_DR + 24, B_OS = B_W + 8, B_R = B_W + 16, B_KD = B_W + 24, B_R1 = B_W + 32, B_T = B_W + 40, B_G = B_W + 48, B_END = B_W + 56, B_S0 = B_END;
static_assert(B_END <= OFF_M + 16 + 3 * 152, "barriers");
constexpr uint32_t B_GB = OFF_M + 2560  , B_GA = B_GB + 128  ;
constexpr uint32_t OFF_SUMWR = OFF_M + 608, OFF_EP = OFF_M + 624, OFF_KEY = OFF_M + 628;
constexpr uint32_t OFF_RSQ = OFF_M + 640, OFF_TL = OFF_M + 1152, OFF_SEL = OFF_M + 1648, OFF_T = OFF_M + 1792, OFF_WR = OFF_M + 2048;
constexpr uint32_t OFF_XSEL = 2 * R5, OFF_GU = OFF_XSEL + 4096, OFF_OUT = 3 * R5;
constexpr uint64_t FF_SLOT = 0xdcdc3210dcbaull;
constexpr int KVP = 6 * 128;

enum { NB_G2E = 1, NB_XS = 2, NB_WG01 = 3, NB_ACT = 4, NB_Q0 = 5  , NB_ST = 14, NB_LAG = 8, NB_DN = 9, NB_ZERO = 10, NB_PUB = 11, NB_TOK = 10  , NB_L0 = 12  , NB_WG2 = 7, NB_QGO = 15 };

struct Scratch {
  bf16     o[SEQ * DM];
  float4   rstat[SEQ];
  uint32_t key[8 * KR * 128];
  uint32_t cand[128 * 512];
  float4   yacc[4 * 3 * 128];
  float4   kvacc[32 * KVP];
  uint2    stats[SEQ];
  uint32_t cskv[2 * DM];
  uint32_t csq[4 * DM];
  uint32_t oset[128 * 16];
  uint32_t oflag[16 * 6 * 32];
  uint32_t epoch;
};
__device__ __align__(1024) Scratch g_scr;
#define TS(id)
#define TDUMP()
#define TS0_DECL()
#define TS0_READ()
#define TS0_WRITE()
#define TK(id)
#define TSW(id)

struct Params {
  CUtensorMap x128, x64, wkv, wq, wo[2], wd, wg, wu, phi, tg, tu, td, xs, ws, qs, out, o;
  const bf16 *x, *wqkv, *wo_p, *wg_p, *wu_p, *wd_p, *wr;
  bf16* out_p;
  Scratch* g;
  uint32_t zero;
};

constexpr float EXP_LIM = 1.1529215e18f, ARG_LIM2 = 3600.f;
template<bool PR> __device__ __forceinline__ void dual_exp2(const float (&p)[16], uint32_t (&ep)[8], uint32_t (&em)[8]) {
  #pragma unroll
  for (int k = 0; k < 8; k++) {
    const float a = ex2(p[2*k]), b = ex2(p[2*k+1]);
    ep[k] = pack_bf16(a, b);
    if (PR) { const float r = rcp(a * b); em[k] = pack_bf16(r * b, r * a); }
    else em[k] = pack_bf16(ex2(-p[2*k]), ex2(-p[2*k+1]));
  }
}
__device__ __forceinline__ void dual_exp2_shifted(const float (&pp)[2][16], uint32_t (&ph)[4][8]) {
  #pragma unroll
  for (int h = 0; h < 2; h++) {
    const float* p = pp[h];
    float m[4] = {p[0], p[2], p[0], p[2]};
    #pragma unroll
    for (int i = 0; i < 16; i++) { m[(i >> 1) & 1] = fmaxf(m[(i >> 1) & 1], p[i]); m[2 + ((i >> 1) & 1)] = fminf(m[2 + ((i >> 1) & 1)], p[i]); }
    #pragma unroll
    for (int o = 1; o < 4; o <<= 1) {
      m[0] = fmaxf(m[0], __shfl_xor_sync(~0u, m[0], o)); m[1] = fmaxf(m[1], __shfl_xor_sync(~0u, m[1], o));
      m[2] = fminf(m[2], __shfl_xor_sync(~0u, m[2], o)); m[3] = fminf(m[3], __shfl_xor_sync(~0u, m[3], o));
    }
    #pragma unroll
    for (int k = 0; k < 8; k++) {
      ph[2*h][k] = pack_bf16(ex2(p[2*k] - m[k & 1]), ex2(p[2*k+1] - m[k & 1]));
      ph[2*h+1][k] = pack_bf16(ex2(m[2 + (k & 1)] - p[2*k]), ex2(m[2 + (k & 1)] - p[2*k+1]));
    }
  }
}
__device__ __forceinline__ uint32_t add_bf16x2(uint32_t a, uint32_t b) { uint32_t r; asm("add.rn.bf16x2 %0, %1, %2;" : "=r"(r) : "r"(a), "r"(b)); return r; }
__device__ __forceinline__ void row_sums(float (&s)[2][4], const uint32_t (&ph)[4][8], uint32_t sel) {
  uint32_t u[8];
  #pragma unroll
  for (int i = 0; i < 8; i++) { const uint32_t* f = &ph[i >> 1][i & 1]; u[i] = add_bf16x2(add_bf16x2(f[0], f[2]), add_bf16x2(f[4], f[6])); }
  wg_fence();
  wgmma_rz_n8<0, H0>(s[0], u[0], u[1], u[2], u[3], sel);
  wgmma_rz_n8<0, H0>(s[1], u[4], u[5], u[6], u[7], sel);
  wg_commit();
}
__device__ __forceinline__ uint32_t mul_bf16x2(uint32_t a, uint32_t b) { uint32_t r; asm("mul.rn.bf16x2 %0, %1, %2;" : "=r"(r) : "r"(a), "r"(b)); return r; }
__device__ __forceinline__ void normalize(uint32_t (&ph)[4][8], const float (&s)[2][4]) {
  #pragma unroll
  for (int i = 0; i < 4; i++) {
    const float i0 = rcp(s[i >> 1][i & 1]), i1 = rcp(s[i >> 1][2 + (i & 1)]);
    const uint32_t n0 = pack_bf16(i0, i0), n1 = pack_bf16(i1, i1);
    #pragma unroll
    for (int k = 0; k < 4; k++) { ph[i][2*k] = mul_bf16x2(ph[i][2*k], n0); ph[i][2*k+1] = mul_bf16x2(ph[i][2*k+1], n1); }
  }
}
__device__ __forceinline__ void split_bf16(float a, float b, uint32_t& hi, uint32_t& lo) { hi = pack_bf16(a, b); lo = pack_bf16(a - bf_lo(hi), b - bf_hi(hi)); }
__device__ __forceinline__ void put_colsums(uint32_t base, int lane, float a, float b, float c, float d) {
  uint32_t h0, l0, h1, l1;
  split_bf16(a, b, h0, l0); split_bf16(c, d, h1, l1);
  const uint32_t ad = base + (lane >> 1) * 128 + (lane & 1) * 8;
  sts64(ad, h0, h1); sts64(ad + 16, l0, l1); sts64(ad + 32, h0, h1); sts64(ad + 48, l0, l1);
  sts128(base + (lane >> 1) * 128 + 64 + (lane & 1) * 32, 0, 0, 0, 0); sts128(base + (lane >> 1) * 128 + 80 + (lane & 1) * 32, 0, 0, 0, 0);
}
__device__ __forceinline__ float reduce8(const float (&v)[8], int lane) {
  const bool b4 = lane & 16, b3 = lane & 8, b2 = lane & 4;
  float a[4], b[2];
  #pragma unroll
  for (int i = 0; i < 4; i++) a[i] = (b4 ? v[4 + i] : v[i]) + __shfl_xor_sync(~0u, b4 ? v[i] : v[4 + i], 16);
  #pragma unroll
  for (int i = 0; i < 2; i++) b[i] = (b3 ? a[2 + i] : a[i]) + __shfl_xor_sync(~0u, b3 ? a[i] : a[2 + i], 8);
  return (b2 ? b[1] : b[0]) + __shfl_xor_sync(~0u, b2 ? b[0] : b[1], 4);
}
__device__ __forceinline__ bool tag_bad(uint4 v, uint32_t tg) { return (((v.x ^ tg) | (v.y ^ tg) | (v.z ^ tg) | (v.w ^ tg)) & 3) != 0; }

__global__ void __launch_bounds__(512, 1) fused_kernel(const __grid_constant__ Params P) {
  extern __shared__ __align__(1024) uint8_t smem_raw[];
  const uint32_t sb = smem_u32(smem_raw);
  const int tid = threadIdx.x, lane = tid & 31;
  TS0_DECL();
  TS0_READ();
  if (tid == 352) { prefetch_map(&P.wkv); prefetch_map(&P.x128); }
  const int cp = blockIdx.x >> 1, rank = blockIdx.x & 1;
  const int cr = cp < 4 ? 32 + 8 * cp : cp - 4 + max((cp * 37 - 1076) >> 8, 0);
  const int c = (cr & 62) + 64 * (cr & 1) + rank;
  const int m256 = c >> 4, nkv = c & 15, m128 = c >> 3, j = c & 7;
  if ((tid >> 5) == 12 && elect_one()) {
    mbar_init(sb + B_S0, 1); mbar_init(sb + B_FULLKV, 1); mbar_init(sb + B_FULLKV + 8, 1);
    fence_async_smem();
    mbar_expect_tx(sb + B_S0, 32768);
    tma_4d(sb + 32768, &P.wkv, 0, 0, nkv, 1, sb + B_S0);
    tma_2d(sb, &P.x128, 0, 256 * m256, sb + B_S0);
    mbar_expect_tx(sb + B_FULLKV, 16384);
    tma_2d(sb + 16384, &P.x128, 0, 256 * m256 + 128, sb + B_FULLKV);
    if (NPRE0 > 1) {
      mbar_expect_tx(sb + B_FULLKV + 8, KV_STAGE);
      tma_4d(sb + KV_STAGE + 32768, &P.wkv, 0, 64, nkv, 1, sb + B_FULLKV + 8);
      tma_2d(sb + KV_STAGE, &P.x128, 64, 256 * m256, sb + B_FULLKV + 8);
      tma_2d(sb + KV_STAGE + 16384, &P.x128, 64, 256 * m256 + 128, sb + B_FULLKV + 8);
    }
    asm volatile("fence.mbarrier_init.release.cluster;" ::: "memory");
  }
  #pragma unroll
  for (int w = 0; w < 3; w++)
    if (tid == 32 + 32 * w) {
      #pragma unroll
      for (uint32_t b = B_FULLKV + 16 + 152 * w; b < B_FULLKV + 168 + 152 * w && b < B_END; b += 8)
        mbar_init(sb + b, b < B_EMPTYKV ? 1 : b < B_EMPTY5 ? 12 : b < B_SD ? 4 : b < B_RX || b == B_W ? 2 : b == B_RX ? 8 : 1);
      asm volatile("fence.mbarrier_init.release.cluster;" ::: "memory");
      fence_async_smem();
    }
  const int warp = __shfl_sync(~0u, tid >> 5, 0), wg = warp >> 2, wp = warp & 3;
  const int f = 16 * ((cr + 7) & 7) + 2 * (cr >> 3) + rank;
  const int ha = 4 * (nkv >> 1) + (nkv & 1);
  Scratch* const G = P.g;
  if ((sb & 0x3ffff) != SB0) asm volatile("trap;");
  __syncthreads();
  cluster_arrive();
  if (warp == 12) {
    TK(88 - 32);
    if (elect_one()) {
      #pragma unroll
      for (int s = NPRE0; s < NPRE; s++) {
        const uint32_t st = sb + s * KV_STAGE, fb = sb + B_FULLKV + 8 * s;
        mbar_expect_tx(fb, KV_STAGE);
        tma_4d(st + 32768, &P.wkv, 0, 64 * s, nkv, 1, fb);
        tma_2d(st, &P.x128, 64 * s, 256 * m256, fb);
        tma_2d(st + 16384, &P.x128, 64 * s, 256 * m256 + 128, fb);
      }
    }
    __syncwarp();
  }

  if (wg == 3) {
    asm volatile("setmaxnreg.dec.sync.aligned.u32 32;");
    cluster_wait();
    if (wp == 0) { TK(89 - 32); }
    const bool el = elect_one();
    const uint64_t ef = policy_evict_first(), en = policy_evict_normal();
    auto fetch_o = [&](const int t0) {
      const int sh = t0 & 1;
      uint32_t missing = ~0u;
      const uint32_t* hint = &G->oflag[(m128 * 6 + ((t0 + 1) & 6) + rank) * 32 + ((4 * (j & 6) + lane) & 31)];
      #pragma unroll FUN
      for (int i = 2 - 2 * sh; i < 8; i += 1 + sh) {
        const int blk = sh ? 6 + 2 * t0 + (i >> 1) : i, wrap = t0 == 3 ? 2 : (blk >= 5) + (blk >= 11), s = blk + 1 - 6 * wrap;
        flags_wait(missing, hint, (15u + 240u * sh) << (4 * i));
        if (blk > 5) mbar_wait(sb + B_EMPTY5 + 8 * s, wrap & 1);
        if (el) {
          tma_2d_mc_h(sb + s * R5 + rank * 8192, &P.o, 0, (m128 * 16 + t0 + 2 * (((j & 6) + i) & 7)) * 32 + 16 * rank, sb + B_GA + 16 * blk + 8 * rank, ef);
          if (KT == 2 && rank == KR2 && ((KM >> blk) & 1)) { TK(16 + blk); }
          if (KT != 2 && i == 2 - 2 * sh) TS(t0 == 0 ? (rank ? 4 : 12) : t0 == 3 ? (rank ? 31 : 10) : (rank ? 9 : 13));
        }
      }
    };
    if (wp == 0) {
      {
        #pragma unroll 1
        for (int kb = NPRE; kb < 16; kb++) {
          const uint32_t st = sb + (kb & 3) * KV_STAGE, fb = sb + B_FULLKV + 8 * (kb & 3);
          mbar_wait(fb + (B_EMPTYKV - B_FULLKV), ~(kb >> 2) & 1);
          if (el) {
            mbar_expect_tx(fb, KV_STAGE);
            tma_2d_mc(st + rank * 16384, &P.x128, 64 * kb, 256 * m256 + 128 * rank, fb);
            tma_4d_h(st + 32768, &P.wkv, 0, 64 * kb, nkv, 1, fb, ef);
          }
        }
        uint64_t ord = 0xf3120edcba987654ull;
        uint32_t so = 0, par = 1;
        #pragma unroll 1
        for (int i = 0; i < 16; i++) {
          const uint32_t st = sb + so * 4096, fb = sb + B_FULL5 + so;
          const int k0 = (64 * (uint32_t)ord + 128 * (j & 6)) & 960;
          mbar_wait(i < 5 ? sb + B_EMPTYKV + so - (i > 1 ? 8 : 0) : fb + (B_EMPTY5 - B_FULL5), par);
          if (el) {
            mbar_expect_tx(fb, R5);
            tma_2d_mc_h(st + rank * 8192, &P.x64, k0, 128 * m128 + 64 * rank, fb, i >= EFI ? ef : en);
            tma_3d_h(st + 16384, &P.wq, 0, k0, 2 * j, fb, ef);
          }
          ord >>= 4; so += 8;
          if (so == 40) { so = 0; par ^= 1; }
        }
        mbar_wait(sb + B_FULL5 + 8 + 8 * rank, 0); if (el) mbar_arrive(sb + B_R);
        mbar_wait(sb + B_FULL5 + 24 + 8 * rank, 0); if (el) mbar_arrive(sb + B_R1);
        #pragma unroll 1
        for (int i = 0; i < 19; i++) {
          const int row = i < 8 ? 128 * (((j & 6) + i) & 7) : 256 * (((j >> 1) + i) & 3) + 32 + 16 * (i & 4);
          mbar_wait(sb + B_EMPTY5 + so, par);
          if (el) {
            if (i < 16) {
              tma_5d_h(sb + so * 4096 + 16384, &P.wo[i >> 3], 128 * j, row, sb + B_GB + 8 * i, ef);
              tma_5d_h(sb + so * 4096 + 24576, &P.wo[i >> 3], 128 * j + 64, row, sb + B_GB + 8 * i, ef);
            } else mbar_arrive(sb + B_DR + 8 * (i - 16));
          }
          so += 8;
          if (so == 48) { so = 0; par ^= 1; }
        }
      }
    } else if (wp == 3) {
      const uint32_t t_start = (uint32_t)clock();
      if (el) {
        mbar_expect_tx(sb + B_W, 12288);
        #pragma unroll 1
        for (int i = 0; i < 6; i++) tma_2d(sb + (i == 0 ? OFF_WPHIK : i == 1 ? OFF_WPHIK1 : OFF_WPHIQ + 2048 * (i - 2)), &P.phi, 0, 32 * (i < 2 ? 2 * nkv + i : 4 * j + 2 * (i & 1) + ((i - 2) >> 1)), sb + B_W);
        prefetch_map(&P.x64); prefetch_map(&P.wq); prefetch_map(&P.wo[0]); prefetch_map(&P.wo[1]);
        prefetch_map(&P.o); prefetch_map(&P.wd); prefetch_map(&P.out); prefetch_map(&P.wg); prefetch_map(&P.wu);
      }
      #pragma unroll 1
      for (int i = 0; i < 8; i++) {
        if (lane < 16) st128_rlx(&G->cand[(m128 * 8 + i) * 512 + 64 * j + 4 * lane], ~0u, ~0u, ~0u, ~0u);
      }
      if (lane < 16) st128_rlx(&G->rstat[16 * c + lane], 0, 0, 0, 0);
      if (lane < 12) st128_rlx(&G->yacc[12 * c + lane], 0, 0, 0, 0);
      {
        const uint32_t nt = ld32_rlx(&G->epoch);
        if (lane < 8) { st128_rlx(&G->stats[16 * c + 2 * lane], nt, nt, nt, nt); st128_rlx(&G->csq[32 * c + 4 * lane], nt, nt, nt, nt); }
        if (lane < 4) { st128_rlx(&G->cskv[128 * nkv + 16 * m256 + 4 * lane], nt, nt, nt, nt); st128_rlx(&G->oset[16 * c + 4 * lane], nt, nt, nt, nt); }
      }
      if (lane < 2 * KR) st128_rlx(&G->key[(KR * j + (lane >> 1)) * 128 + m128 * 8 + 4 * (lane & 1)], 0, 0, 0, 0);
      if (c < 32) {
        #pragma unroll 1
        for (int i = lane; i < KVP; i += 32) st128_rlx(&G->kvacc[(ha + 2 * m256) * KVP + i], 0, 0, 0, 0);
      }
      fence_gpu();
      bar_arrive(NB_ZERO, 160);
      TS0_WRITE();
      if (el) {
        #pragma unroll 1
        for (int i = PF_I0; i < ((XP & 4) ? 0 : 30); i++) {
          while ((uint32_t)clock() - t_start < (uint32_t)(PF_T0 + PF_DT * (i - PF_I0) + PF_ST * f)) __nanosleep(64);
          if (i < 4) { bulk_prefetch(P.wqkv + (size_t)(256 * i + c) * (3 * DM), 2048); bulk_prefetch(P.wqkv + (size_t)(256 * i + 128 + c) * (3 * DM), 2048); }
          else if (i < 6) bulk_prefetch(P.wo_p + (size_t)c * 8192 + (i - 4) * 4096, 8192);
          else if ((TMASK >> (i - 6)) & 1) {
            const int k = i - 6;
            if (f < NFFN) {
              if (k < 16) {
                #pragma unroll 1
                for (int e = 0; e < 4; e++) tma_2d(sb + OFF_T, rank ? &P.tu : &P.tg, 32 * (f & ~1), 64 * k + 16 * e, sb + B_T);
              } else { tma_2d(sb + OFF_T, &P.td, 0, 256 * f + 32 * (k - 16), sb + B_T); tma_2d(sb + OFF_T, &P.td, 0, 256 * f + 32 * (k - 16) + 16, sb + B_T); }
            }
          }
          else if (!((PMASK >> (i - 6)) & 1)) {}
          else if (i < 22) bulk_prefetch(((i & 1) ? P.wu_p : P.wg_p) + (size_t)((i - 6) >> 1) * 458752 + c * 3584, 7168);
          else bulk_prefetch(P.wd_p + (size_t)(i - 22) * 458752 + c * 3584, 7168);
        }
      }
      __syncwarp();
      mbar_wait2(sb + B_OS, 0, sb + B_RX, 0);
      mbar_wait2(sb + B_EMPTY5 + 24, 0, sb + B_EMPTY5 + 32, 0);
      mbar_wait2(sb + B_EMPTY5 + 40, 0, sb + B_EMPTY5, 1);
      fetch_o(0);
      fetch_o(3);
    } else {
      const int half = wp - 1;
      const uint32_t ep1 = ld32_rlx(&G->epoch) + 1, tg = ep1 & 3;
      {
        uint32_t it = 0;
        sts128(sb + OFF_ONES + half * 512 + lane * 16, 0x3f803f80u, 0x3f803f80u, 0x3f803f80u, 0x3f803f80u);
        if (lane < 9) { const uint32_t v = (lane & 1) ? 0 : 0x3f803f80u; sts128(sb + OFF_SEL + lane * 16, v, v, v, v); }
        auto reset_o = [&](int i0, int i1, uint32_t dt) {
          uint32_t t0 = (uint32_t)clock();
          #pragma unroll 1
          for (int i = i0; i < i1; i++) {
            if (!(XP & 2)) st128_rlx(G->o + (m128 * 16 + 2 * j + half) * 8192 + 256 * i + 8 * lane, ~0u, ~0u, ~0u, ~0u);
            while ((uint32_t)clock() - t0 < dt) __nanosleep(40);
            t0 += dt;
          }
        };
        if (el) {
          #pragma unroll 1
          for (int i = 24 * half; i < 24 * half + 24; i++) { mbar_init(sb + B_GB + 8 * i, 1); mbar_expect_tx(sb + B_GB + 8 * i, i < 16 ? 16384 : 8192); }
          asm volatile("fence.mbarrier_init.release.cluster;" ::: "memory");
        }
        mbar_wait(sb + B_S0, 0);
        reset_o(0, RS_N, RS_D1);
        bar_sync(NB_PUB, 192);
        const uint4* src = reinterpret_cast<const uint4*>(&G->stats[256 * m256 + 128 * half]) + lane;
        const uint4* srk = reinterpret_cast<const uint4*>(&G->cskv[128 * nkv]) + lane;
        uint4 v0, v1, vk;
        it = 0;
        do { v0 = ld128_rlx(src); v1 = ld128_rlx(src + 32); vk = ld128_rlx(srk); }
        while ((tag_bad(v0, tg) || tag_bad(v1, tg) || tag_bad(vk, tg)) && ++it < POLL_LIMIT);
        fence_acquire_gpu();
        if (half) put_colsums(sb + OFF_BXK, lane, untag(vk.x), untag(vk.y), untag(vk.z), untag(vk.w));
        #pragma unroll
        for (int i = 0; i < 2; i++) {
          const uint4 v = i ? v1 : v0;
          uint32_t hi, lo;
          split_bf16(-0.5f * untag(v.x), -0.5f * untag(v.z), hi, lo);
          const uint32_t h0 = __byte_perm(hi, hi, 0x1010), h1 = __byte_perm(hi, hi, 0x3232), l0 = __byte_perm(lo, lo, 0x1010), l1 = __byte_perm(lo, lo, 0x3232);
          const uint32_t a = sb + OFF_AXK + half * 2048 + i * 1024 + lane * 32;
          sts128(a, h0, l0, 0, 0); sts128(a + 16, h1, l1, 0, 0);
          sts64(sb + OFF_RS256 + half * 512 + i * 256 + lane * 8, v.y & ~3u, v.w & ~3u);
          if (half == (m128 & 1)) {
            const uint32_t aq = sb + OFF_AXQ + i * 1024 + lane * 32;
            sts128(aq, h0, l0, 0, 0); sts128(aq + 16, h1, l1, 0, 0);
            sts64(sb + OFF_RSQ + i * 256 + lane * 8, v.y & ~3u, v.w & ~3u);
          }
        }
        fence_async_smem();
        __syncwarp();
        if (el) { sts32(sb + OFF_EP, ep1); mbar_arrive(sb + B_AUX); }
        reset_o(RS_N, 32, RS_D2);
        if (half == 0 && rank == 0 && lane < 12) st128_rlx(&G->oflag[(m128 * 6 + (lane >> 1)) * 32 + 4 * j + 4 * (lane & 1)], 0, 0, 0, 0);
        fence_gpu();
        __syncwarp();
        if (el) { st32_rlx(&G->oset[16 * c + 8 * half], ep1); if (half) mbar_arrive(sb + B_AUXQ); }
        if (!half) {
          const uint4* src = reinterpret_cast<const uint4*>(&G->csq[128 * j]) + lane;
          uint4 v0, v1, v2, v3;
          do { v0 = ld128_rlx(src); v1 = ld128_rlx(src + DM / 4); v2 = ld128_rlx(src + DM / 2); v3 = ld128_rlx(src + 3 * DM / 4); }
          while ((tag_bad(v0, tg) || tag_bad(v1, tg) || tag_bad(v2, tg) || tag_bad(v3, tg)) && ++it < POLL_LIMIT);
          put_colsums(sb + OFF_BXQ, lane, (untag(v0.x) + untag(v1.x)) + (untag(v2.x) + untag(v3.x)), (untag(v0.y) + untag(v1.y)) + (untag(v2.y) + untag(v3.y)),
                      (untag(v0.z) + untag(v1.z)) + (untag(v2.z) + untag(v3.z)), (untag(v0.w) + untag(v1.w)) + (untag(v2.w) + untag(v3.w)));
          fence_async_smem();
          __syncwarp();
          if (el) mbar_arrive(sb + B_AUXQ);
        }
      }
      if (half == 0) {
        for (uint32_t it = 0; __any_sync(~0u, ld32_rlx(&G->oset[m128 * 128 + 8 * (lane & 15)]) != ep1) && it < POLL_LIMIT; it++) {}
        fence_acquire_gpu();
        if (el) mbar_arrive(sb + B_OS);
      }
      if (!half) {
        #pragma unroll 1
        for (int hh = 0; hh < 2; hh++) {
          const uint32_t src = sb + (1 + rank) * R5 + hh * 8192, fa = sb + B_GA + 16 * rank + 8 * hh;
          mbar_wait2(sb + B_UO + 8 * hh, 0, sb + B_GB + 8 * rank, 0);
          if (el) bulk_s2peer(mapa(src, rank ^ 1), src, 8192, mapa(fa, rank ^ 1));
        }
        fetch_o(1);
      }
      else if (f < NFFN_L) {
        mbar_wait(sb + B_UO + 24, 0);
        mbar_wait2(sb + B_UO, 0, sb + B_UO + 8, 0);
        uint32_t t0 = (uint32_t)clock();
        while ((uint32_t)clock() - t0 < (uint32_t)FF_T0) __nanosleep(32);
        t0 -= FF_DT;
        #pragma unroll 1
        for (int i = 0; i < 12; i++) {
          const int e = (FF_ORD >> (4 * i)) & 15;
          const uint32_t dst = sb + 16384 * ((FF_SLOT >> (4 * e)) & 15), fb = sb + B_F + 8 * e;
          if (i >= 2) mbar_wait(sb + B_WC + 8 * ((0x100066553244ull >> (4 * e)) & 15), 0);
          while ((uint32_t)clock() - t0 < (uint32_t)(i < FF_N ? FF_DT : FF_D2)) __nanosleep(32);
          t0 = (uint32_t)clock();
          if (i < 8) { TK(48 + i); }
          if (el) {
            mbar_expect_tx(fb, 16384);
            if (e >= 8) tma_3d_h(dst, &P.wd, 0, 32 * f, 4 * e - 32, fb, ef);
            else { tma_2d(dst, &P.wg, 32 * f, 128 * e, fb); tma_2d(dst + 8192, &P.wu, 32 * f, 128 * e, fb); }
          }
        }
      }
      __syncwarp();
    }
    if (wp & 1) {
      __syncwarp();
      mbar_wait(sb + B_OUT + 8 * (wp >> 1), 0);
      uint32_t t0 = (uint32_t)clock() + OUT_0;
      #pragma unroll 1
      for (int i = 0; i < 8; i++) {
        while ((int32_t)((uint32_t)clock() - t0) < 0) __nanosleep(20);
        if (el) tma_store_2d(&P.out, 128 * j + 64 * (i & 1), 128 * m128 + 32 * (wp & 2) + 8 * (i & 6), sb + OFF_OUT + (i & 1) * 16384 + (wp & 2) * 4096 + (i & 6) * 1024);
        t0 += OUT_D;
      }
      if (el) { bulk_commit(); bulk_wait_all(); fence_async_global(); mbar_arrive(sb + B_SD); TS(19); }
    }
    __syncwarp();
    cluster_arrive(); cluster_wait();
    return;
  }

  asm volatile("setmaxnreg.inc.sync.aligned.u32 160;");
  cluster_wait();
  const int t = tid & 127, g = lane >> 2;
  const uint32_t sa = (16 * wp + (lane & 15)) * 128 + (((lane >> 4) ^ (lane & 7)) << 4);

  if (wg == 2) {
    float s[2] = {0.f, 0.f}, s2[2] = {0.f, 0.f}, ck[8] = {0.f, 0.f, 0.f, 0.f, 0.f, 0.f, 0.f, 0.f}, cs[8] = {0.f, 0.f, 0.f, 0.f, 0.f, 0.f, 0.f, 0.f};
    const uint32_t ebr = mapa(sb + B_EMPTYKV, lane & 1), tg = (ld32_rlx(&G->epoch) + 1) & 3;
    auto addx = [&](const uint4 v) {
      const uint32_t w[4] = {v.x, v.y, v.z, v.w};
      #pragma unroll
      for (int e = 0; e < 4; e++) { const float a = bf_lo(w[e]), d = bf_hi(w[e]); s[0] += a; s[1] += d; s2[0] = fmaf(a, a, s2[0]); s2[1] = fmaf(d, d, s2[1]); }
    };
    auto addc = [&](const uint4 v, float (&o)[8]) {
      o[0] += bf_lo(v.x); o[1] += bf_hi(v.x); o[2] += bf_lo(v.y); o[3] += bf_hi(v.y); o[4] += bf_lo(v.z); o[5] += bf_hi(v.z); o[6] += bf_lo(v.w); o[7] += bf_hi(v.w);
    };
    {
      const uint32_t ra = (16 * nkv + (t >> 3)) * 128 + (t & 7) * 16;
      const uint32_t ca = 32768 + (m256 >> 2) * 8192 + (t >> 1) * 128 + (((2 * (m256 & 3) + (t & 1)) ^ ((t >> 1) & 7)) << 4);
      int rd = 0;
      mbar_wait(sb + B_S0, 0);
      #pragma unroll 1
      for (int kb = 0; kb < 10; kb++) {
        const uint32_t st = sb + (kb & 3) * KV_STAGE;
        mbar_wait(sb + B_FULLKV + 8 * (kb & 3), (kb >> 2) & 1);
        const uint4 x0 = lds128(st + ra), w0 = lds128(st + ca);
        if (!(XP & 1)) { addx(x0); addc(w0, ck); } else s[0] += __uint_as_float(x0.x ^ w0.x);
        __syncwarp();
        if (lane < 2) mbar_arrive_remote(ebr + 8 * (kb & 3), 1);
        if ((SKM >> kb) & 1) {
          if (rd) {
            mbar_wait(sb + B_G, (rd - 1) & 1);
            const uint32_t a = sb + OFF_G + (t >> 3) * 256 + (t & 7) * 16;
            const uint4 x1 = lds128(a), x2 = lds128(a + 128), w1 = lds128(sb + OFF_G + 4096 + t * 16), w2 = lds128(sb + OFF_G + 6144 + t * 16);
            addx(x1); addx(x2); addc(w1, ck); addc(w2, ck);
            bar_sync(NB_WG2, 128);
          }
          if (wp == 0 && elect_one()) {
            mbar_expect_tx(sb + B_G, 8192);
            if (rd < 3) {
              tma_2d(sb + OFF_G, &P.xs, 640 + 128 * rd, 256 * m256 + 16 * nkv, sb + B_G);
              tma_2d(sb + OFF_G + 4096, &P.ws, (1 + (m256 >> 2)) * DM + 64 * nkv + 16 * (m256 & 3), 640 + 128 * rd, sb + B_G);
            } else tma_2d(sb + OFF_G, &P.qs, 32 * (c & 31), 256 * (c >> 5), sb + B_G);
          }
          rd++;
        }
      }
    }
    TK(82);
    const uint32_t scr = sb + OFF_WR;
    float sx = s[0] + s[1], sq = s2[0] + s2[1];
    #pragma unroll
    for (int o = 1; o < 8; o <<= 1) { sx += __shfl_xor_sync(~0u, sx, o); sq += __shfl_xor_sync(~0u, sq, o); }
    float v = reduce8(ck, lane);
    v += __shfl_xor_sync(~0u, v, 2);
    if (!(lane & 2)) stsf(scr + (wp * 16 + 8 * (lane & 1) + (lane >> 2)) * 4, v);

    bar_sync(NB_ZERO, 160);
    if ((lane & 7) == 0) {
      const float mean = sx * (1.f / DM);
      st64_rlx(&G->stats[256 * m256 + 16 * nkv + (t >> 3)], tagw(mean, tg), tagw(rsqrtf(fmaxf(sq * (1.f / DM) - mean * mean, 0.f) + 1e-5f), tg));
    }
    if (wp == 1 && lane < 16) {
      const uint32_t a = scr + lane * 4;
      st32_rlx(&G->cskv[128 * nkv + 16 * m256 + lane], tagw((ldsf(a) + ldsf(a + 64)) + (ldsf(a + 128) + ldsf(a + 192)), tg));
    }
    __syncwarp();
    bar_arrive(NB_PUB, 192);
    TSW(23);
    const uint4 wv = ld128_keep(P.wr + t * 8);
    #pragma unroll 1
    for (int i = 0; i < 2; i++) {
      mbar_wait(sb + B_G, i ^ 1);
      const uint32_t a = sb + OFF_G + t * 16;
      const uint4 u0 = lds128(a), u1 = lds128(a + 2048), u2 = lds128(a + 4096), u3 = lds128(a + 6144);
      addc(u0, cs); addc(u1, cs); addc(u2, cs); addc(u3, cs);
      bar_sync(NB_WG2, 128);
      if (i == 0 && wp == 0 && elect_one()) { mbar_expect_tx(sb + B_G, 8192); tma_2d(sb + OFF_G, &P.qs, 32 * (c & 31), 256 * (c >> 5) + 128, sb + B_G); }
    }
    float sw = (bf_lo(wv.x) + bf_hi(wv.x)) + (bf_lo(wv.y) + bf_hi(wv.y)) + (bf_lo(wv.z) + bf_hi(wv.z)) + (bf_lo(wv.w) + bf_hi(wv.w));
    #pragma unroll
    for (int o = 16; o; o >>= 1) sw += __shfl_xor_sync(~0u, sw, o);
    if (lane == 0) stsf(sb + OFF_SUMWR + wp * 4, sw);
    if ((t >> 4) == j) {
      const uint32_t a = sb + OFF_WR + (t & 15) * 32;
      sts128(a, wv.x << 16, wv.x & 0xffff0000u, wv.y << 16, wv.y & 0xffff0000u);
      sts128(a + 16, wv.z << 16, wv.z & 0xffff0000u, wv.w << 16, wv.w & 0xffff0000u);
    }
    v = reduce8(cs, lane);
    stsf(sb + OFF_G + (wp * 32 + 8 * (lane & 3) + (lane >> 2)) * 4, v);
    bar_sync(NB_WG2, 128);
    if (wp == 0) {
      const uint32_t a = sb + OFF_G + lane * 4, cq = tagw((ldsf(a) + ldsf(a + 128)) + (ldsf(a + 256) + ldsf(a + 384)), tg);
      st32_rlx(&G->csq[(c >> 5) * DM + 32 * (c & 31) + lane], cq);
      if (lane == 0) mbar_arrive_at(sb + B_W, rank, (cq & P.zero) + 1);
    }
  }

  uint32_t xr[32];
  {
    const bool isq = wg == 2;
    float acc[2][64];
    {
      const uint32_t emptyb = mapa(sb + (isq ? B_EMPTY5 : B_EMPTYKV), t & 1);
      auto correct = [&](uint32_t xa, uint32_t xb) {
        wg_fence();
        wgmma_sa_n128<0, 1, H0, H0>(acc[0], dlo(SB0, 0) + (xa >> 4), dlo(SB0, 0) + (xb >> 4));
        wgmma_sa_n128<0, 1, H0, H0>(acc[1], dlo(SB0, 0) + (xa >> 4) + 64, dlo(SB0, 0) + (xb >> 4));
        wg_commit();
      };
      if (!isq) {
        mbar_wait(sb + B_S0, 0);
        if (wg) mbar_wait(sb + B_FULLKV, 0);
        if (wg == 0) { TSW(2); }
        #pragma unroll 1
        for (int kb = 0; kb < 16; kb++) {
          if (!KT && wg == 0) { TK(kb); }
          const uint32_t da = dlo(SB0, 16) + wg * 1024 + (kb & 3) * (KV_STAGE >> 4), db = dlo(SB0 + 32768, 8192) + (kb & 3) * (KV_STAGE >> 4);
          wg_fence();
          #pragma unroll
          for (int k = 0; k < 4; k++) {
            wgmma_ss_n128<0, 1, H128, H128>(acc[0], da + 2 * k, db + 128 * k, k > 0 || kb != 0);
            wgmma_ss_n128<0, 1, H128, H128>(acc[1], da + 512 + 2 * k, db + 128 * k, k > 0 || kb != 0);
          }
          wg_commit();
          wg_wait<1>();
          if (kb > 0 && t < 2) mbar_arrive_remote(emptyb + 8 * ((kb - 1) & 3), kb > 10 ? 3 : 1);
          if (kb < 15) mbar_wait(sb + B_FULLKV + 8 * ((kb + 1) & 3), ((kb + 1) >> 2) & 1);
          if (kb == 0) mbar_wait(sb + B_FULLKV, 0);
          if (kb == 15 - LAG && wg == 1) bar_sync(NB_LAG, 256);
        }
        bar_arrive(wg ? NB_QGO : NB_LAG, 256);
        mbar_wait(sb + B_AUX, 0);
        correct(OFF_AXK + wg * 2048, OFF_BXK);
        wg_wait<0>();
        if (t < 2) mbar_arrive_remote(emptyb + 24, 3);
        if (wg == 0) { TSW(3); }
        fence_regs(acc[0]); fence_regs(acc[1]);
      const uint32_t stg = sb + OFF_X + (1 - wg) * 24576;
      const uint32_t va = stg + 16384 + (16 * wp + (lane & 15)) * 64 + (((lane >> 4) ^ ((lane >> 1) & 3)) << 4);
      const uint32_t ra = sb + OFF_RS256 + (128 * wg + 16 * wp + g) * 4;
      const float rs[4] = {ldsf(ra), ldsf(ra + 32), ldsf(ra + 256), ldsf(ra + 288)};
      float p[2][16];
      uint32_t vf[16], kf[2][16];
      auto project = [&](const uint32_t (&f)[16], uint32_t db) {
        wg_fence();
        #pragma unroll
        for (int i = 0; i < 2; i++) {
          wgmma_rs_n32<1, H64>(p[i], f[8*i], f[8*i+1], f[8*i+2], f[8*i+3], db, 0);
          wgmma_ra_n32<1, H64>(p[i], f[8*i+4], f[8*i+5], f[8*i+6], f[8*i+7], db + 64);
        }
        wg_commit();
      };
      auto fold = [&](uint32_t (&f)[16], int col, float sc) {
        #pragma unroll
        for (int i = 0; i < 16; i++) {
          const float r = rs[2 * (i >> 3) + (i & 1)] * sc;
          f[i] = pack_bf16(acc[i >> 3][col + 2 * (i & 7)] * r, acc[i >> 3][col + 2 * (i & 7) + 1] * r);
          asm volatile("" : "+r"(f[i]));
        }
      };
      auto put_v = [&](const uint32_t (&f)[16]) {
        #pragma unroll
        for (int k = 0; k < 4; k++) stsm4((va ^ ((k & 1) << 5)) + (k >> 1) * 4096, f[4*k], f[4*k+1], f[4*k+2], f[4*k+3]);
      };
      KK(0);
      fold(vf, 48, 1.f);
      mbar_wait(sb + B_W, 0);
      fold(kf[0], 0, LOG2E);
      #pragma unroll
      for (int i = 0; i < 32; i++) p[i >> 4][i & 15] = acc[i >> 4][i & 15];
      project(kf[0], dlo(SB0 + OFF_WPHIK, 16));
      mbar_wait(sb + B_W, 0);
      KK(1);
      {
        uint32_t v0[16];
        fold(kf[1], 16, LOG2E);
        fold(v0, 32, 1.f);
        if (wg == 1) bar_sync(NB_DN, 256);
        put_v(v0);
      }
      wg_wait<0>();
      fence_regs(p[0]); fence_regs(p[1]);
      if (wg == 1) bar_arrive(NB_WG01, 256);
      KK(2);
      #pragma unroll 1
      for (int h = 0; h < 2; h++) {
        uint32_t ph[4][8];
        float rsum[2][4];
        dual_exp2<PRK & 1>(p[0], ph[0], ph[1]); dual_exp2<(PRK >> 1)>(p[1], ph[2], ph[3]);
        row_sums(rsum, ph, dlo(SB0 + OFF_SEL, 16));
        KK(3 + 6 * h);
        if (wg == 0 && h == 0) { bar_arrive(NB_DN, 256); bar_sync(NB_WG01, 256); }
        if (h == 1) {
          if (wg == 1) bar_sync(NB_DN, 256);
          put_v(vf);
        }
        wg_wait<0>();
        KK(4 + 6 * h);
        fence_regs(rsum[0]); fence_regs(rsum[1]);
        if (!(XP & 8) && __builtin_expect(__any_sync(~0u, !((rsum[0][0] + rsum[0][1]) + (rsum[0][2] + rsum[0][3]) + (rsum[1][0] + rsum[1][1]) + (rsum[1][2] + rsum[1][3]) < EXP_LIM)), 0)) {
          dual_exp2_shifted(p, ph);
          #pragma unroll
          for (int i = 0; i < 8; i++) {
            const uint32_t* f = &ph[i >> 1][i & 1];
            float a = (bf_lo(f[0]) + bf_hi(f[0])) + (bf_lo(f[2]) + bf_hi(f[2])) + (bf_lo(f[4]) + bf_hi(f[4])) + (bf_lo(f[6]) + bf_hi(f[6]));
            a += __shfl_xor_sync(~0u, a, 1);
            rsum[i >> 2][2 * (i & 1) + ((i >> 1) & 1)] = a + __shfl_xor_sync(~0u, a, 2);
          }
        }
        if (h == 0) project(kf[1], dlo(SB0 + OFF_WPHIK1, 16));
        normalize(ph, rsum);
        #pragma unroll
        for (int i = 0; i < 8; i++) {
          const uint32_t* f = &ph[i >> 1][4 * (i & 1)];
          stsm4(((stg + sa) ^ ((i & 3) << 5)) + (i >> 2) * 8192, f[0], f[1], f[2], f[3]);
        }
        KK(5 + 6 * h);
        fence_async_smem();
        KK(6 + 6 * h);
        if (wg != h) { KK(7 + 6 * h); }
        if (wg == h) {
          float kv[20];
          #pragma unroll
          for (int w = 0; w < 2; w++) {
            const uint32_t da = dlo(SB0 + OFF_X, 16) + (h ^ w ^ 1) * 1536, db = dlo(SB0 + OFF_X + 16384, OFF_ONES - OFF_X - 16384) - (h ^ w ^ 1) * (1536 * 65535);
            if (w) bar_sync(NB_ST, 256); else bar_sync(NB_L0 + h, 128);
            wg_fence();
            #pragma unroll
            for (int k = 0; k < 8; k++) {
              if (k == 0 && w == 0) wgmma_sz_n40<1, 1, H128, H64>(kv, da, db);
              else wgmma_sa_n40<1, 1, H128, H64>(kv, da + k * 128, db - k * (64 * 65535));
            }
            wg_commit();
          }
          float4* dst = &G->kvacc[(ha + 2 * h) * KVP + t];
          wg_wait<0>();
          fence_regs(kv);
          KK(7 + 6 * h);
          if (h == 0) bar_arrive(NB_DN, 256); else if (t < 2) { mbar_arrive_at(sb + B_EMPTY5 + 40, t, 2); if (t == 0) mbar_arrive(sb + B_KD); }
          kv[17] = kv[18];
          #pragma unroll
          for (int i = 0; i < 6; i++) red_add_f32x4(dst + 128 * i, kv[3*i], kv[3*i+1], kv[3*i+2], 1.f);
          TSW(29 + h);
        } else bar_arrive(NB_ST, 256);
        wg_wait<0>();
        KK(8 + 6 * h);
        fence_regs(p[0]); fence_regs(p[1]);
      }
      #pragma unroll
      for (int i = 0; i < 32; i++) asm volatile("mov.b32 %0, 0;" : "=r"(xr[i]));
      } else {
        uint32_t so = 0, po = 0, par = 0;
        mbar_wait(sb + B_FULL5, 0);
        bar_sync(NB_QGO, 256);
        TSW(11);
        #pragma unroll 1
        for (int kb = 0; kb < 16 - ML; kb++) {
          if (KT != 2) { TK(16 + kb); }
          const uint32_t da = dlo(SB0, 16) + so * 256, db = dlo(SB0 + 16384, 8192) + so * 256;
          #pragma unroll
          for (int k = 0; k < 4; k++) {
            wg_fence();
            wgmma_ss_n128<0, 1, H128, H128>(acc[0], da + 2 * k, db + 128 * k, k > 0 || kb != 0);
            wgmma_ss_n128<0, 1, H128, H128>(acc[1], da + 512 + 2 * k, db + 128 * k, k > 0 || kb != 0);
            wg_commit();
            if (k == 1 && kb > 0 && t < 2) mbar_arrive_remote(emptyb + po, 2);
            if (k == 3) {
              po = so; so += 8;
              if (so == 40) { so = 0; par ^= 1; }
              mbar_wait(sb + B_FULL5 + so, par);
            }
            if ((QW >> k) & 1) wg_wait<2>(); else wg_wait<1>();
          }
        }
        auto block = [&](const int kb, const int i) {
          wg_fence();
          #pragma unroll
          for (int k = 0; k < 4; k++) wgmma_sa_n128<0, 1, H128, H128>(acc[i], dlo(SB0, 16) + (kb % 5) * 2048 + 512 * i + 2 * k, dlo(SB0 + 16384, 8192) + (kb % 5) * 2048 + 128 * k);
          wg_commit();
        };
        auto hand_over = [&](const int i) {
          const uint32_t ta = sb + (1 + rank) * R5 + sa + i * 8192;
          #pragma unroll
          for (int k = 0; k < 4; k++) {
            const float* a = &acc[i][32 * (k >> 1) + 8 * (k & 1)];
            stsm4(ta ^ (k << 5), pack_bf16(a[0], a[1]), pack_bf16(a[2], a[3]), pack_bf16(a[4], a[5]), pack_bf16(a[6], a[7]));
          }
        };
        mbar_wait2(sb + B_AUXQ, 0, sb + B_OS, 0);
        correct(OFF_AXQ, OFF_BXQ);
        #pragma unroll
        for (int kb = 16 - ML; kb < 16; kb++) {
          if (KT != 2) { TK(16 + kb); }
          block(kb, 0);
          if (kb < 15) mbar_wait(sb + B_FULL5 + 8 * ((kb + 1) % 5), ((kb + 1) / 5) & 1);
          if (kb == 16 - ML) wg_wait<2>(); else if (!H3) wg_wait<1>();
          if (kb == 16 - ML && t < 2) mbar_arrive_remote(emptyb + 8 * ((kb - 1) % 5), 2);
        }
        mbar_wait(sb + B_RC, 0);
        block(16 - ML, 1);
        if (H2) { block(17 - ML, 1); wg_wait<2>(); } else wg_wait<1>();
        fence_regs(acc[0]);
        hand_over(0);
        if (!H2) block(17 - ML, 1);
        fence_async_smem();
        bar_arrive(NB_Q0, 256);
        TSW(1);
        #pragma unroll
        for (int kb = 18 - ML; kb <= 16; kb++) {
          wg_wait<1>();
          if (t < 2) mbar_arrive_remote(emptyb + 8 * ((kb - 2) % 5), 2);
          if (kb < 16) block(kb, 1);
        }
        mbar_wait(sb + B_RC + 8, 0);
        wg_wait<0>();
        if (t < 2) mbar_arrive_remote(emptyb, 2);
        TSW(8);
        fence_regs(acc[1]);
        hand_over(1);
        fence_async_smem();
        bar_arrive(NB_Q0 + 1, 256);
        #pragma unroll
        for (int i = 0; i < 32; i++) { const float* a = &acc[(i >> 3) & 1][16 + 32 * (i >> 4) + 2 * (i & 7)]; xr[i] = pack_bf16(a[0], a[1]); }
        TSW(26);
      }
    }
    float p[2][16];
    #pragma unroll
    for (int i = 0; i < 32; i++) asm volatile("mov.b32 %0, 0;" : "=f"(p[i >> 4][i & 15]));
    auto project_r = [&](int w) {
      wg_fence();
      #pragma unroll
      for (int h = 0; h < 2; h++) {
        wgmma_rs_n32<1, H64>(p[h], xr[8*h], xr[8*h+1], xr[8*h+2], xr[8*h+3], dlo(SB0 + OFF_WPHIQ, 16) + 128 * w, 0);
        wgmma_ra_n32<1, H64>(p[h], xr[8*h+4], xr[8*h+5], xr[8*h+6], xr[8*h+7], dlo(SB0 + OFF_WPHIQ, 16) + 128 * w + 64);
      }
      wg_commit();
    };
    auto capture = [&](const int i) {
      if (!i || CAPL != 2) mbar_wait(sb + (i ? B_R1 : B_R), 0);
      #pragma unroll
      for (int k = 0; k < 4; k++) ldsm4(((sb + (1 + rank) * R5 + wg * 8192 + sa) ^ (k << 5)) + i * 2 * R5, xr[16*i+4*k], xr[16*i+4*k+1], xr[16*i+4*k+2], xr[16*i+4*k+3]);
      const uint32_t one = (((xr[16*i] | xr[16*i+4]) | (xr[16*i+8] | xr[16*i+12])) & P.zero) + 1;
      if (lane == 0) mbar_arrive_at(sb + (i ? B_RX : B_RC + 8 * wg), i ? wg : rank, one);
    };
    const uint32_t rq = sb + OFF_RSQ + (16 * wp + g) * 4 + 256 * (wg & 1), rb = rq + 128 * (wg & 2);
    const float cc[2][2] = {{ldsf(rq) * LOG2E, ldsf(rq + 32) * LOG2E}, {ldsf(rb) * LOG2E, ldsf(rb + 32) * LOG2E}};
    {
      const uint4* src = reinterpret_cast<const uint4*>(&G->kvacc[(4 * j + wg) * KVP + t]);
      uint4 v[12];
      #pragma unroll
      for (int i = 0; i < 12; i++) v[i] = i < 6 || isq ? ld128_rlx(src + 128 * i) : make_uint4(0, 0, 0, 0x41000000u);
      if (isq) {
        project_r(2);
        wg_wait<0>();
        #pragma unroll
        for (int i = 0; i < 16; i++) xr[i] = xr[16 + i];
      } else {
        capture(0);
        if (CAPL == 0) capture(1);
      }
      #pragma unroll 1
      for (uint32_t it = 0; it < POLL_LIMIT; it++) {
        uint32_t bad = 0;
        #pragma unroll
        for (int i = 0; i < 12; i++) bad |= v[i].w ^ 0x41000000u;
        if (!__any_sync(~0u, bad != 0)) break;
        #pragma unroll
        for (int i = 0; i < 12; i++) if (i < 6 || isq) v[i] = ld128_rlx(src + 128 * i);
      }
      mbar_wait(sb + B_KD, 0);
      #pragma unroll
      for (int e = 0; e < 2; e++) {
        if (e == 0 || isq) {
          float f[18];
          #pragma unroll
          for (int i = 0; i < 6; i++) { f[3*i] = __uint_as_float(v[6*e+i].x); f[3*i+1] = __uint_as_float(v[6*e+i].y); f[3*i+2] = __uint_as_float(v[6*e+i].z); }
          const uint32_t ka = sb + OFF_KVZ + (wg + e) * 5120 + wp * 1280 + lane * 16;
          stsm4(ka, pack_bf16(f[0], f[1]), pack_bf16(f[2], f[3]), pack_bf16(f[4], f[5]), pack_bf16(f[6], f[7]));
          stsm4(ka + 512, pack_bf16(f[8], f[9]), pack_bf16(f[10], f[11]), pack_bf16(f[12], f[13]), pack_bf16(f[14], f[15]));
          stsm2(ka + 1024, pack_bf16(f[16], 1.f), pack_bf16(f[17], 1.f));
        }
      }
    }
    fence_async_smem();
    if (wg == 1) bar_arrive(NB_DN, 256);
    if (CAPL == 1 && !isq) capture(1);
    TSW(wg == 0 ? 5 : wg == 1 ? 25 : 6);
    #pragma unroll 1
    for (int e = wg; e < wg + 1 + (wg >> 1); e++) {
      const int half = e >> 1, hh = e & 1, turn = e;
      const uint32_t ao = (1 + rank) * R5 + hh * 8192;
      uint32_t ph[4][8];
      #pragma unroll
      for (int i = 0; i < 32; i++) asm volatile("mov.b32 %0, 0;" : "=r"(ph[i >> 3][i & 7]));
      uint32_t shifted = 0;
      asm volatile("" : "+r"(shifted));
      #pragma unroll 1
      for (;;) {
        if (!(XP & 16) && shifted) dual_exp2_shifted(p, ph);
        uint32_t first = (shifted ^ 1) & !isq;
        asm volatile("" : "+r"(first));
        if (first) {
          if (wg == 0) { TSW(7); }
          bar_sync(NB_Q0 + wg, 256);
          const uint32_t da = dlo(SB0, 16) + (ao >> 4), db = dlo(SB0 + OFF_WPHIQ, 16);
          wg_fence();
          #pragma unroll
          for (int h = 0; h < 2; h++) {
            wgmma_ss_n32<0, 1, H128, H64>(p[h], da + 4 * h, db + 128 * h, 0);
            wgmma_sa_n32<0, 1, H128, H64>(p[h], da + 4 * h + 2, db + 128 * h + 64);
          }
          wg_commit();
          if (CAPL == 2) capture(1);
          wg_wait<0>();
        }
        fence_regs(p[0]); fence_regs(p[1]);
        uint32_t again = shifted;
        asm volatile("" : "+r"(again));
        if (again) break;
        float s2[4] = {0.f, 0.f, 0.f, 0.f};
        #pragma unroll
        for (int i = 0; i < 32; i++) { float& x = p[i >> 4][i & 15]; x *= cc[i >> 4][(i >> 1) & 1]; s2[i & 3] = fmaf(x, x, s2[i & 3]); }
        if (!__any_sync(~0u, !((s2[0] < ARG_LIM2) & (s2[1] < ARG_LIM2) & (s2[2] < ARG_LIM2) & (s2[3] < ARG_LIM2)))) break;
        shifted = 1;
      }
      if (e == 1 || e == 2) bar_sync(NB_TOK + e - 1, 256);
      TK(64 + 4 * turn);
      float ac[4][20];
      auto numer = [&](int h) {
        const uint32_t (*f)[8] = &ph[2 * h];
        const uint32_t db = dlo(SB0 + OFF_KVZ, 128) + (half ? e : h) * 320;
        wg_fence();
        #pragma unroll
        for (int i = 0; i < 2; i++) {
          wgmma_rz_n40<1, dhi(256, 0)>(ac[2*h+i], f[i][0], f[i][1], f[i][2], f[i][3], db + i * 160);
          wgmma_ra_n40<1, dhi(256, 0)>(ac[2*h+i], f[i][4], f[i][5], f[i][6], f[i][7], db + (i * 160 + 80));
        }
        wg_commit();
      };
      const uint32_t oa = (16 * wp + g) * 128 + (((lane & 3) ^ g) << 4);
      auto finish = [&](int h) {
        const float* ap = ac[2 * h]; const float* am = ac[2 * h + 1];
        const float ip0 = rcp(ap[17]), im0 = rcp(am[17]), ip1 = rcp(ap[19]), im1 = rcp(am[19]);
        const float d0 = rcp(fmaf(ap[16], ip0, fmaf(am[16], im0, 1e-6f))), d1 = rcp(fmaf(ap[18], ip1, fmaf(am[18], im1, 1e-6f)));
        const float a0 = ip0 * d0, b0 = im0 * d0, a1 = ip1 * d1, b1 = im1 * d1;
        #pragma unroll
        for (int r = 0; r < 2; r++) {
          const float a = r ? a1 : a0, b = r ? b1 : b0;
          uint32_t w[4];
          #pragma unroll
          for (int k = 0; k < 4; k++) w[k] = pack_bf16(fmaf(ap[4*k+2*r], a, am[4*k+2*r] * b), fmaf(ap[4*k+2*r+1], a, am[4*k+2*r+1] * b));
          const uint32_t off = (oa ^ ((half ? rank : h) << 6)) + r * 1024;
          st128_rlx(reinterpret_cast<uint8_t*>(G->o + (m128 * 16 + (half ? 2 * (j & 6) + 2 * hh + 1 : 2 * j)) * 8192 + (half ? h : hh) * 4096) + off, w[0], w[1], w[2], w[3]);
          if (!half) sts128(sb + ao + off, w[0], w[1], w[2], w[3]);
        }
        if ((half || h) && lane == 0) st32_rlx(&G->oflag[(m128 * 6 + (half ? 2 * e - 2 + h : hh)) * 32 + 4 * j + wp], 1);
      };
      if (!shifted) dual_exp2<true>(p[0], ph[0], ph[1]);
      numer(0);
      if (!shifted) dual_exp2<true>(p[1], ph[2], ph[3]);
      if (turn < 2) bar_arrive(NB_TOK + turn, 256);
      if (wg == 0) bar_sync(NB_DN, 256);
      numer(1);
      wg_wait<1>();
      TK(65 + 4 * turn);
      fence_regs(ac[0]); fence_regs(ac[1]);
      finish(0);
      wg_wait<0>();
      fence_regs(ac[2]); fence_regs(ac[3]);
      #pragma unroll
      for (int i = 0; i < 32; i++) asm volatile("mov.b32 %0, 0;" : "=f"(p[i >> 4][i & 15]));
      if (e == 2) project_r(3);
      finish(1);
      TK(66 + 4 * turn);
      if (!half) fence_async_smem();
      __syncwarp();
      if (lane == 0) mbar_arrive(sb + B_UO + 8 * e);
      wg_wait<0>();
      TK(67 + 4 * turn);
    }
    if (isq) cluster_arrive();
  }

  {
  int lane;
  asm volatile("mov.u32 %0, %%laneid;" : "=r"(lane));
  const int g = lane >> 2, q = lane & 3;
  if (wg < 2) {
    float h[64];
    {
      if (wg == 0) { TK(83); }
      #pragma unroll
      for (int i = 0; i < 32; i++) { h[2*i] = bf_lo(xr[i]); h[2*i+1] = bf_hi(xr[i]); }
      fence_regs(h);
      TK(80 + wg);
      const uint32_t emptyb = mapa(sb + B_EMPTY5, t & 1);
      uint32_t s = 1 + rank, ps = 0;
      mbar_wait2(sb + B_GB + 8 * rank, 0, sb + B_UO + 8 * wg, 0);
      if (wg == 0) { TSW(14); }
      #pragma unroll
      for (int i = 0; i < 16; i++) {
        if (KT == 2 && wg == 1) { TK(i); }
        if (KT != 1 && wg == 0) { TK(32 + i); }
        const uint32_t da = dlo(SB0, 16) + s * 2048 + wg * 512, db = dlo(SB0 + 16384, 8192) + s * 2048;
        wg_fence();
        #pragma unroll
        for (int k = 0; k < 4; k++) wgmma_sa_n128<0, 1, H128, H128>(h, da + k * 2, db + k * 128);
        wg_commit();
        const uint32_t ns = i ? (i + 2) % 6 : 2 - rank;
        const uint32_t nb = i ? i + 1 : 1 - rank, b0 = sb + B_GB + 8 * nb, b1 = sb + B_GA + 16 * nb + 8 * wg;
        const bool here = i == 15 || mbar_test2(b0, 0, b1, 0);
        wg_wait<1>();
        if (!(((2 * REL + 1) >> i) & 1) && i < 14 && t < 2) mbar_arrive_remote(emptyb + 8 * ps, 1);
        if ((REL >> i) & 1) { wg_wait<0>(); if (t < 2) mbar_arrive_remote(emptyb + 8 * s, 1); }
        if (!here) mbar_wait2(b0, 0, b1, 0);
        ps = s; s = ns;
      }
    }
    cluster_arrive();
    float2 wr[16];
    #pragma unroll
    for (int i = 0; i < 16; i++) wr[i] = lds64f(sb + OFF_WR + 32 * i + 8 * q);
    const int r0 = 64 * wg + 16 * wp + g;
    float sum0, sum1, dot0, dot1, sq0, sq1;
    uint32_t redo = 0;
    asm volatile("" : "+r"(redo));
    #pragma unroll 1
    for (;;) {
    if (!(XP & 32) && redo) {
      wg_wait<0>();
      const uint32_t* xp = reinterpret_cast<const uint32_t*>(P.x + (size_t)(128 * m128 + r0) * DM + 128 * j) + q;
      #pragma unroll
      for (int i = 0; i < 32; i++) { const uint32_t v = xp[4 * (i >> 1) + (i & 1) * 4 * DM]; h[2*i] = bf_lo(v); h[2*i+1] = bf_hi(v); }
      #pragma unroll 1
      for (int ks = 0; ks < 64; ks++) {
        const int kb = ks >> 2, kk = 16 * (ks & 3);
        const bf16* op = G->o + (m128 * 16 + kb) * 8192 + r0 * 64 + 2 * q;
        const int o0 = ((kk >> 3) ^ g) << 3;
        const uint32_t* w = reinterpret_cast<const uint32_t*>(P.wo_p + (size_t)(((kb & 1) ? 256 * (kb >> 2) + 32 * (kb & 2) + 32 + 4 * (kk & 32) : 64 * kb + 2 * (kk & 32)) +
                                                                              ((kk & 16) >> 2) + 4 * (g & 6) + (g & 1)) * DM + 128 * j) + q;
        uint32_t b[32], a0, a1, a2, a3, it = 0;
        #pragma unroll
        for (int n = 0; n < 32; n++) b[n] = w[4 * (n >> 1) + (n & 1) * DM];
        do { a0 = ld32_rlx(op + o0); a1 = ld32_rlx(op + 512 + o0); a2 = ld32_rlx(op + (o0 ^ 8)); a3 = ld32_rlx(op + 512 + (o0 ^ 8)); }
        while (max(max(a0, a1), max(a2, a3)) == ~0u && ++it < POLL_LIMIT);
        __syncwarp();
        #pragma unroll
        for (int n = 0; n < 16; n++) mma16816(h[4*n], h[4*n+1], h[4*n+2], h[4*n+3], a0, a1, a2, a3, transpose8(b[2*n]), transpose8(b[2*n+1]));
      }
    }
    wg_wait<0>();
    fence_regs(h);
    if (wg == 0) { TSW(16); }
    sum0 = 0.f, sum1 = 0.f, dot0 = 0.f, dot1 = 0.f, sq0 = 0.f, sq1 = 0.f;
    #pragma unroll
    for (int i = 0; i < 16; i++) {
      sum0 += h[4*i] + h[4*i+1]; sum1 += h[4*i+2] + h[4*i+3];
      sq0 = fmaf(h[4*i], h[4*i], fmaf(h[4*i+1], h[4*i+1], sq0)); sq1 = fmaf(h[4*i+2], h[4*i+2], fmaf(h[4*i+3], h[4*i+3], sq1));
      dot0 = fmaf(h[4*i], wr[i].x, fmaf(h[4*i+1], wr[i].y, dot0)); dot1 = fmaf(h[4*i+2], wr[i].x, fmaf(h[4*i+3], wr[i].y, dot1));
    }
    if (!__any_sync(~0u, !redo & (h[0] != h[0] | h[2] != h[2]))) break;
    redo = 1;
    }
    float4* const rs = &G->rstat[128 * m128 + r0];
    {
      const bool up = q & 2;
      float a = up ? sum1 : sum0, b = up ? sq1 : sq0, d = up ? dot1 : dot0;
      a += __shfl_xor_sync(~0u, up ? sum0 : sum1, 2); b += __shfl_xor_sync(~0u, up ? sq0 : sq1, 2); d += __shfl_xor_sync(~0u, up ? dot0 : dot1, 2);
      a += __shfl_xor_sync(~0u, a, 1); b += __shfl_xor_sync(~0u, b, 1); d += __shfl_xor_sync(~0u, d, 1);
      if ((q & 1) == 0) red_add_f32x4(rs + 4 * q, a, b, d, 1.f);
    }
    if (TRKL == 0) bar_arrive(NB_G2E, 384);
    if (wg == 0) { TSW(24); }
    bar_sync(NB_WG01, 256);
    uint32_t wa[8][4][4];
    const uint32_t wb = sb + 16384 * (((uint32_t)FF_SLOT >> (4 * warp)) & 15) + ((lane & 7) + ((lane >> 4) << 3)) * 64 + ((((lane >> 3) & 1) ^ ((lane >> 1) & 3)) << 4);
    auto getw = [&](int ks) {
      #pragma unroll
      for (int m = 0; m < 4; m++) ldsm4t((wb ^ ((m & 1) << 5)) + (m >> 1) * 8192 + ks * 1024, wa[ks][m][0], wa[ks][m][1], wa[ks][m][2], wa[ks][m][3]);
    };
    if (GPRE && f < NFFN_L) mbar_wait(sb + B_F + 8 * warp, 0);
    if (warp == 7) { TK(60); }
    #pragma unroll
    for (int ks = 0; ks < GPRE; ks++) getw(ks);
    float rstd[2], bm[2];
    uint32_t best;
    {
      const float2 swa = lds64f(sb + OFF_SUMWR), swb = lds64f(sb + OFF_SUMWR + 8);
      const float sw = (swa.x + swa.y) + (swb.x + swb.y);
      uint4 a[2]; uint32_t it = 0, key[2];
      do { a[0] = ld128_rlx(rs); a[1] = ld128_rlx(rs + 8); } while (__any_sync(~0u, (a[0].w & a[1].w) != 0x41000000u) && ++it < POLL_LIMIT);
      #pragma unroll
      for (int i = 0; i < 2; i++) {
        const float mean = __uint_as_float(a[i].x) * (1.f / DM);
        rstd[i] = rsqrtf(fmaxf(__uint_as_float(a[i].y) * (1.f / DM) - mean * mean, 0.f) + 1e-5f);
        bm[i] = -mean * rstd[i];
        const uint32_t rr = __float_as_uint(fmaf(__uint_as_float(a[i].z), rstd[i], sw * bm[i]));
        key[i] = ((rr ^ ((uint32_t)((int32_t)rr >> 31) | 0x80000000u)) & ~2047u) | (2047 - 128 * m128 - r0 - 8 * i);
      }
      asm volatile("redux.sync.max.u32 %0, %1, 0xffffffff;" : "=r"(best) : "r"(max(key[0], key[1])));
    }
    if (TRKL == 2) bar_arrive(NB_G2E, 384);
    if (TRKL == 3 && wg == 0) bar_arrive(NB_G2E, 256);
    if (wg == 0) { TSW(17); }
    const int slot = m128 * 8 + warp, win = ~best & 15;
    if (lane < KR) st32_rlx(&G->key[(KR * j + lane) * 128 + slot], best);
    if ((win & 7) == g) {
      const bool up = win & 8;
      const float ra = up ? rstd[1] : rstd[0], rb = up ? bm[1] : bm[0];
      uint32_t x[16];
      #pragma unroll
      for (int i = 0; i < 16; i++) x[i] = pack_bf16(fmaf(up ? h[4*i+2] : h[4*i], ra, rb), fmaf(up ? h[4*i+3] : h[4*i+1], ra, rb));
      #pragma unroll
      for (int i = 0; i < 4; i++) st128_rlx(&G->cand[slot * 512 + 64 * j + 16 * i + 4 * q], x[4*i], x[4*i+1], x[4*i+2], x[4*i+3]);
    }
    __syncwarp();
    if (TRKL == 1) bar_arrive(NB_G2E, 384);
    if (wg == 0) { TSW(27); }
    {
      const float a0 = 1.f + rstd[0], b0 = bm[0], a1 = 1.f + rstd[1], b1 = bm[1];
      #pragma unroll
      for (int k = 0; k < 8; k++)
        stsm4(((sb + OFF_OUT + wg * 8192 + sa) ^ ((k & 3) << 5)) + (k >> 2) * 16384,
              pack_bf16(fmaf(h[8*k], a0, b0), fmaf(h[8*k+1], a0, b0)),     pack_bf16(fmaf(h[8*k+2], a1, b1), fmaf(h[8*k+3], a1, b1)),
              pack_bf16(fmaf(h[8*k+4], a0, b0), fmaf(h[8*k+5], a0, b0)),   pack_bf16(fmaf(h[8*k+6], a1, b1), fmaf(h[8*k+7], a1, b1)));
      fence_async_smem();
      __syncwarp();
      if (lane == 0) mbar_arrive(sb + B_OUT + 8 * wg);
    }
    if (wg == 0) { TSW(28); }
    {
      if (!GPRE && f < NFFN_L) mbar_wait(sb + B_F + 8 * warp, 0);
      #pragma unroll
      for (int ks = GPRE; ks < GRES; ks++) getw(ks);
      if (wg == 0) { TSW(15); }
      bar_sync(NB_XS, 384);
      uint4 xs[4];
      #pragma unroll
      for (int i = 0; i < 4; i++) xs[i] = lds128(sb + OFF_XSEL + 256 * warp + 64 * i + 16 * q);
      float d[4][4];
      #pragma unroll
      for (int ks = 0; ks < 8; ks++) {
        if (ks >= 1 && GRES + ks - 1 < 8) getw(GRES + ks - 1);
        #pragma unroll
        for (int m = 0; m < 4; m++) {
          if (ks == 0) { d[m][0] = 0.f; d[m][1] = 0.f; d[m][2] = 0.f; d[m][3] = 0.f; }
          mma16816(d[m][0], d[m][1], d[m][2], d[m][3], wa[ks][m][0], wa[ks][m][1], wa[ks][m][2], wa[ks][m][3],
                   (ks & 1) ? xs[ks >> 1].z : xs[ks >> 1].x, (ks & 1) ? xs[ks >> 1].w : xs[ks >> 1].y);
        }
      }
      if (q == 0) {
        #pragma unroll
        for (int m = 0; m < 8; m++) stsf(sb + OFF_GU + (8 * m + g) * 48 + 4 * warp, d[m >> 1][2 * (m & 1)]);
      }
      bar_arrive(NB_ACT, 384);
    }
    {
      const uint32_t ky = __float_as_uint(ldsf(sb + OFF_KEY));
      const int row = 2047 - (ky & 2047) - 128 * m128;
      if ((uint32_t)row < 128u) {
        const int l = tid >> 3, vi = (j & 1) + ((lane >> 2) & 1), e = 3 * vi + q - 4 * (j & 1);
        const float kr = __uint_as_float((ky & ~2047u) ^ ((ky >> 31) ? 0x80000000u : 0xfffff800u));
        const int col = 32 * (l & 3) + 16 * (e & 1) + 4 * (e & 2) + (l >> 2);
        const float sg = rcp(1.f + ex2(-LOG2E * kr));
        const uint32_t base = __float_as_uint(ldsf(sb + OFF_OUT + (col >> 6) * 16384 + row * 128 + ((((col >> 3) ^ row) & 7) << 4) + 2 * (col & 6)));
        const float4* yp = &G->yacc[(q * 3 + vi) * 128 + 32 * (j >> 1) + l];
        uint32_t it = 0;
        uint4 v;
        mbar_wait(sb + B_SD, 0);
        do { v = ld128_rlx(yp); } while (__any_sync(~0u, __uint_as_float(v.w) != (float)(NFFN / 4)) && ++it < POLL_LIMIT);
        float y0 = __uint_as_float(v.x), y1 = __uint_as_float(v.y), y2 = __uint_as_float(v.z);
        #pragma unroll
        for (int o = 1; o < 4; o <<= 1) { y0 += __shfl_xor_sync(~0u, y0, o); y1 += __shfl_xor_sync(~0u, y1, o); y2 += __shfl_xor_sync(~0u, y2, o); }
        if (q < 3 && (uint32_t)e < 4u)
          P.out_p[(size_t)(128 * m128 + row) * DM + 128 * j + col] = __float2bfloat16(fmaf(q == 0 ? y0 : q == 1 ? y1 : y2, sg, (col & 1) ? bf_hi(base) : bf_lo(base)));
      }
      if (c == 0 && tid == 0) st32_rlx(&G->epoch, __float_as_uint(ldsf(sb + OFF_EP)));
      if (warp == 0) { TSW(22); }
      if (wg == 0) { TDUMP(); }
    }
  }
  if (wg == 2) {
    uint32_t wf[16][2][4];
    {
      const uint32_t wb = sb + OFF_S + 16384 * (wp & 1) + ((lane & 7) + ((lane >> 4) << 3)) * 128 + ((((lane >> 3) & 1) ^ (lane & 7)) << 4);
      if (f < NFFN_L) mbar_wait(sb + B_WD + 8 * wp, 0);
      if (wp == 0) { TK(61); }
      #pragma unroll
      for (int i = 0; i < 32; i++) ldsm4t((wb ^ (((i >> 1) & 3) << 5)) + (i >> 3) * 4096 + (i & 1) * 2048, wf[i >> 1][i & 1][0], wf[i >> 1][i & 1][1], wf[i >> 1][i & 1][2], wf[i >> 1][i & 1][3]);
      fence_async_smem();
      __syncwarp();
      if (lane == 0) mbar_arrive(sb + B_WC + 8 * wp);
      if (wp == 0) { TK(62); }
    }
    bar_sync(NB_G2E, TRKL == 3 ? 256 : 384);
    {
      uint32_t cur = 0;
      uint4 v;
      #pragma unroll 1
      for (uint32_t it = 0; it < POLL_LIMIT; it++) {
        const uint4 kx = ld128_rlx(&G->key[(KSEL & (8 * KR - 1)) * 128 + 4 * lane]);
        v = ld128_rlx(&G->cand[((~cur >> 4) & 127) * 512 + 4 * t]);
        uint32_t best;
        asm volatile("redux.sync.max.u32 %0, %1, 0xffffffff;" : "=r"(best) : "r"(max(max(kx.x, kx.y), max(kx.z, kx.w))));
        if (!__any_sync(~0u, min(min(kx.x, kx.y), min(kx.z, kx.w)) == 0 || v.w == ~0u) && best == cur) break;
        cur = best;
      }
      sts128(sb + OFF_XSEL + 16 * t, v.x, v.y, v.z, v.w);
      sts32(sb + OFF_KEY, cur);
      bar_arrive(NB_XS, 384);
      TSW(18);
      bar_sync(NB_ACT, 384);
    }
    float gu[2];
    #pragma unroll
    for (int i = 0; i < 2; i++) {
      const uint4 v0 = lds128(sb + OFF_GU + (32 * i + lane) * 48), v1 = lds128(sb + OFF_GU + (32 * i + lane) * 48 + 16);
      gu[i] = ((__uint_as_float(v0.x) + __uint_as_float(v0.y)) + (__uint_as_float(v0.z) + __uint_as_float(v0.w))) +
              ((__uint_as_float(v1.x) + __uint_as_float(v1.y)) + (__uint_as_float(v1.z) + __uint_as_float(v1.w)));
    }
    const float act = gu[0] * gu[1] * rcp(1.f + ex2(-LOG2E * gu[0]));
    const uint32_t ap = pack_bf16(act, __shfl_down_sync(~0u, act, 1));
    uint32_t bf[4];
    #pragma unroll
    for (int i = 0; i < 4; i++) bf[i] = __shfl_sync(~0u, ap, 2 * q + 8 * i);
    TSW(20);
    float d[16][4];
    #pragma unroll
    for (int k = 0; k < 2; k++)
      #pragma unroll
      for (int i = 0; i < 16; i++) {
        if (k == 0) { d[i][0] = 0.f; d[i][1] = 0.f; d[i][2] = 0.f; d[i][3] = 0.f; }
        mma16816(d[i][0], d[i][1], d[i][2], d[i][3], wf[i][k][0], wf[i][k][1], wf[i][k][2], wf[i][k][3], bf[2*k], bf[2*k+1]);
      }
    float y[9];
    #pragma unroll
    for (int e = 0; e < 8; e++) {
      const int n = 2 * (e & 4) + (e & 1);
      const float lo = (q & 1) ? d[n + 2][e & 2] : d[n][e & 2], hi = (q & 1) ? d[n + 6][e & 2] : d[n + 4][e & 2];
      y[e] = (q & 2) ? hi : lo;
    }
    y[8] = 0.f;
    if (f < NFFN) {
      #pragma unroll
      for (int i = 0; i < 3; i++) red_add_f32x4(&G->yacc[((f & 3) * 3 + i) * 128 + t], y[3*i], y[3*i+1], y[3*i+2], 1.f);
    }
    TSW(21);
  }
  }
  cluster_wait();
}

typedef CUresult (*EncodeFn)(CUtensorMap*, CUtensorMapDataType, cuuint32_t, void*, const cuuint64_t*, const cuuint64_t*,
                             const cuuint32_t*, const cuuint32_t*, CUtensorMapInterleave, CUtensorMapSwizzle,
                             CUtensorMapL2promotion, CUtensorMapFloatOOBfill);

void make_map(EncodeFn enc, CUtensorMap* m, const void* p, int n, const cuuint64_t* dims, const cuuint64_t* str, const cuuint32_t* box,
              CUtensorMapSwizzle sw, CUtensorMapL2promotion promo) {
  cuuint32_t es[5] = {1, 1, 1, 1, 1};
  enc(m, CU_TENSOR_MAP_DATA_TYPE_BFLOAT16, n, const_cast<void*>(p), dims, str, box, es, CU_TENSOR_MAP_INTERLEAVE_NONE, sw, promo,
      CU_TENSOR_MAP_FLOAT_OOB_FILL_NONE);
}
void map2(EncodeFn enc, CUtensorMap* m, const void* p, uint64_t cols, uint64_t rows, uint32_t bc, uint32_t br, CUtensorMapSwizzle sw,
          CUtensorMapL2promotion promo) {
  const cuuint64_t dims[2] = {cols, rows}, str[1] = {cols * 2};
  const cuuint32_t box[2] = {bc, br};
  make_map(enc, m, p, 2, dims, str, box, sw, promo);
}
void map3(EncodeFn enc, CUtensorMap* m, const void* p, uint64_t cols, uint64_t rows, uint32_t br, uint32_t nb) {
  const cuuint64_t dims[3] = {64, rows, cols / 64}, str[2] = {cols * 2, 128};
  const cuuint32_t box[3] = {64, br, nb};
  make_map(enc, m, p, 3, dims, str, box, CU_TENSOR_MAP_SWIZZLE_128B, CU_TENSOR_MAP_L2_PROMOTION_L2_128B);
}

}

extern "C" void kernel_launch(void* const* d_in, const int* in_sizes, int n_in, void* d_out, int out_size) {
  (void)in_sizes; (void)n_in; (void)out_size;
  static EncodeFn enc = nullptr;
  static void* o_ptr = nullptr;
  if (!enc) {
    void* f = nullptr; cudaDriverEntryPointQueryResult qr;
    cudaGetDriverEntryPoint("cuTensorMapEncodeTiled", &f, cudaEnableDefault, &qr);
    enc = (EncodeFn)f;
    cudaGetSymbolAddress(&o_ptr, g_scr);
    cudaFuncSetAttribute(fused_kernel, cudaFuncAttributeMaxDynamicSharedMemorySize, SMEM_BYTES);
  }
  const bf16* x = (const bf16*)d_in[0];
  const bf16* wqkv = (const bf16*)d_in[1];
  const bf16* wphi = (const bf16*)d_in[2];
  const bf16* wo = (const bf16*)d_in[3];
  const bf16* wr = (const bf16*)d_in[5];
  const bf16* wgate = (const bf16*)d_in[6];
  const bf16* wup = (const bf16*)d_in[7];
  const bf16* wdown = (const bf16*)d_in[8];
  Params P;
  const CUtensorMapSwizzle S128 = CU_TENSOR_MAP_SWIZZLE_128B, S64 = CU_TENSOR_MAP_SWIZZLE_64B;
  const CUtensorMapL2promotion L128 = CU_TENSOR_MAP_L2_PROMOTION_L2_128B, L256 = CU_TENSOR_MAP_L2_PROMOTION_L2_256B,
                               L64 = CU_TENSOR_MAP_L2_PROMOTION_L2_64B;
  map2(enc, &P.x128, x, DM, SEQ, 64, 128, S128, L256);
  map2(enc, &P.x64, x, DM, SEQ, 64, 64, S128, L128);
  {
    const cuuint64_t dims[4] = {64, DM, 16, 3}, str[3] = {6 * DM, 128, 2 * DM};
    const cuuint32_t box[4] = {64, 64, 1, 2};
    make_map(enc, &P.wkv, wqkv, 4, dims, str, box, S128, L128);
  }
  map3(enc, &P.wq, wqkv, 3 * DM, DM, 64, 2);
  for (int i = 0; i < 2; i++) {
    const cuuint64_t dims[5] = {DM, (cuuint64_t)(DM - 94 - 64 * i), 4, 4, 2}, str[4] = {2 * DM, 16 * DM, 4 * DM, (cuuint64_t)(128 * DM) << i};
    const cuuint32_t box[5] = {64, 2, 4, 4, 2};
    make_map(enc, &P.wo[i], wo, 5, dims, str, box, S128, L128);
  }
  map3(enc, &P.wd, wdown, DM, FF, 32, 4);
  map2(enc, &P.wg, wgate, FF, DM, 32, 128, S64, L64);
  map2(enc, &P.wu, wup, FF, DM, 32, 128, S64, L64);
  map2(enc, &P.tg, wgate, FF, DM, 8, 16, CU_TENSOR_MAP_SWIZZLE_NONE, L128);
  map2(enc, &P.tu, wup, FF, DM, 8, 16, CU_TENSOR_MAP_SWIZZLE_NONE, L128);
  map2(enc, &P.td, wdown, 128, FF * 8, 8, 16, CU_TENSOR_MAP_SWIZZLE_NONE, L256);
  map2(enc, &P.xs, x, DM, SEQ, 128, 16, CU_TENSOR_MAP_SWIZZLE_NONE, L256);
  map2(enc, &P.ws, wqkv, 3 * DM, DM, 16, 128, CU_TENSOR_MAP_SWIZZLE_NONE, L128);
  map2(enc, &P.qs, wqkv, 3 * DM, DM, 32, 128, CU_TENSOR_MAP_SWIZZLE_NONE, L64);
  map2(enc, &P.out, d_out, DM, SEQ, 64, 16, S128, L128);
  map2(enc, &P.o, o_ptr, 256, SEQ * DM / 256, 256, 16, CU_TENSOR_MAP_SWIZZLE_NONE, L128);
  map2(enc, &P.phi, wphi, 32, 1024, 32, 32, S64, L64);
  P.x = x; P.wqkv = wqkv; P.wo_p = wo; P.wd_p = wdown; P.wg_p = wgate; P.wu_p = wup; P.wr = wr; P.out_p = (bf16*)d_out; P.g = (Scratch*)o_ptr; P.zero = 0;

  cudaLaunchConfig_t cfg = {};
  cfg.gridDim = dim3(128); cfg.blockDim = dim3(512); cfg.dynamicSmemBytes = SMEM_BYTES; cfg.stream = cudaStreamPerThread;
  cudaLaunchAttribute at[1];
  at[0].id = cudaLaunchAttributeClusterDimension; at[0].val.clusterDim.x = 2; at[0].val.clusterDim.y = 1; at[0].val.clusterDim.z = 1;
  cfg.attrs = at; cfg.numAttrs = 1;
  cudaLaunchKernelEx(&cfg, fused_kernel, P);
}
```

```cpp
#include <cuda_runtime.h>
#include <cuda.h>
#include <cuda_bf16.h>
#include <stdint.h>

namespace {

typedef __nv_bfloat16 bf16;

#define JIT()
__device__ __forceinline__ uint32_t smem_u32(const void* p){ return (uint32_t)__cvta_generic_to_shared(p); }
__device__ __forceinline__ void mbar_init(uint32_t bar, uint32_t cnt){ asm volatile("mbarrier.init.shared::cta.b64 [%0], %1;"::"r"(bar),"r"(cnt):"memory"); }
__device__ __forceinline__ void mbar_expect_tx(uint32_t bar, uint32_t bytes){ asm volatile("mbarrier.arrive.expect_tx.shared::cta.b64 _, [%0], %1;"::"r"(bar),"r"(bytes):"memory"); }
__device__ __forceinline__ void mbar_arrive(uint32_t bar){ JIT(); asm volatile("mbarrier.arrive.shared::cta.b64 _, [%0];"::"r"(bar):"memory"); }
__device__ __forceinline__ uint32_t mapa(uint32_t addr, uint32_t cta){ uint32_t r; asm volatile("mapa.shared::cluster.u32 %0, %1, %2;":"=r"(r):"r"(addr),"r"(cta)); return r; }
__device__ __forceinline__ void mbar_arrive_at(uint32_t bar, uint32_t cta, uint32_t cnt){ JIT();
  asm volatile("{\n.reg .b32 ra;\nmapa.shared::cluster.u32 ra, %0, %1;\nmbarrier.arrive.shared::cluster.b64 _, [ra], %2;\n}\n"::"r"(bar),"r"(cta),"r"(cnt):"memory"); }
__device__ __forceinline__ void mbar_arrive_remote(uint32_t cluster_addr, uint32_t cnt){ JIT();
  asm volatile("mbarrier.arrive.shared::cluster.b64 _, [%0], %1;"::"r"(cluster_addr),"r"(cnt):"memory"); }
__device__ __forceinline__ void mbar_wait(uint32_t bar, uint32_t parity){ JIT();
  asm volatile("{\n.reg .pred p;\n.reg .u32 c;\nmov.u32 c, 0;\nLW:\nmbarrier.try_wait.parity.shared::cta.b64 p, [%0], %1;\n@p bra LD;\nadd.u32 c, c, 1;\nsetp.lt.u32 p, c, 2000000;\n@p bra LW;\ntrap;\nLD:\n}\n"::"r"(bar),"r"(parity):"memory"); }
__device__ __forceinline__ void mbar_wait2(uint32_t bar0, uint32_t par0, uint32_t bar1, uint32_t par1){ JIT();
  asm volatile("{\n.reg .pred p, q;\n.reg .u32 c;\nmov.u32 c, 0;\nLW:\nmbarrier.try_wait.parity.shared::cta.b64 p, [%0], %1;\nmbarrier.try_wait.parity.shared::cta.b64 q, [%2], %3;\nand.pred p, p, q;\n@p bra LD;\nadd.u32 c, c, 1;\nsetp.lt.u32 p, c, 2000000;\n@p bra LW;\ntrap;\nLD:\n}\n"::"r"(bar0),"r"(par0),"r"(bar1),"r"(par1):"memory"); }
__device__ __forceinline__ bool mbar_test2(uint32_t bar0, uint32_t par0, uint32_t bar1, uint32_t par1){
  uint32_t r;
  asm volatile("{\n.reg .pred p, q;\nmbarrier.test_wait.parity.shared::cta.b64 p, [%1], %2;\nmbarrier.test_wait.parity.shared::cta.b64 q, [%3], %4;\nand.pred p, p, q;\nselp.u32 %0, 1, 0, p;\n}\n":"=r"(r):"r"(bar0),"r"(par0),"r"(bar1),"r"(par1):"memory");
  return r; }
__device__ __forceinline__ void tma_2d(uint32_t dst, const CUtensorMap* m, int c0, int c1, uint32_t bar){
  asm volatile("cp.async.bulk.tensor.2d.shared::cluster.global.mbarrier::complete_tx::bytes [%0], [%1, {%3, %4}], [%2];"::"r"(dst),"l"(m),"r"(bar),"r"(c0),"r"(c1):"memory"); }
__device__ __forceinline__ void tma_2d_h(uint32_t dst, const CUtensorMap* m, int c0, int c1, uint32_t bar, uint64_t pol){
  asm volatile("cp.async.bulk.tensor.2d.shared::cluster.global.mbarrier::complete_tx::bytes.L2::cache_hint [%0], [%1, {%3, %4}], [%2], %5;"::"r"(dst),"l"(m),"r"(bar),"r"(c0),"r"(c1),"l"(pol):"memory"); }
__device__ __forceinline__ void tma_2d_mc(uint32_t dst, const CUtensorMap* m, int c0, int c1, uint32_t bar){
  asm volatile("cp.async.bulk.tensor.2d.shared::cluster.global.mbarrier::complete_tx::bytes.multicast::cluster [%0], [%1, {%3, %4}], [%2], %5;"::"r"(dst),"l"(m),"r"(bar),"r"(c0),"r"(c1),"h"((uint16_t)3):"memory"); }
__device__ __forceinline__ void tma_2d_mc_h(uint32_t dst, const CUtensorMap* m, int c0, int c1, uint32_t bar, uint64_t pol){
  asm volatile("cp.async.bulk.tensor.2d.shared::cluster.global.mbarrier::complete_tx::bytes.multicast::cluster.L2::cache_hint [%0], [%1, {%3, %4}], [%2], %5, %6;"::"r"(dst),"l"(m),"r"(bar),"r"(c0),"r"(c1),"h"((uint16_t)3),"l"(pol):"memory"); }
__device__ __forceinline__ void tma_4d(uint32_t dst, const CUtensorMap* m, int c0, int c1, int c2, int c3, uint32_t bar){
  asm volatile("cp.async.bulk.tensor.4d.shared::cluster.global.mbarrier::complete_tx::bytes [%0], [%1, {%3, %4, %5, %6}], [%2];"::"r"(dst),"l"(m),"r"(bar),"r"(c0),"r"(c1),"r"(c2),"r"(c3):"memory"); }
__device__ __forceinline__ uint64_t policy_evict_first(){ uint64_t p; asm volatile("createpolicy.fractional.L2::evict_first.b64 %0, 1.0;":"=l"(p)); return p; }
__device__ __forceinline__ uint64_t policy_evict_normal(){ uint64_t p; asm("createpolicy.fractional.L2::evict_normal.b64 %0, 1.0;":"=l"(p)); return p; }
__device__ __forceinline__ void tma_3d_h(uint32_t dst, const CUtensorMap* m, int c0, int c1, int c2, uint32_t bar, uint64_t pol){
  asm volatile("cp.async.bulk.tensor.3d.shared::cluster.global.mbarrier::complete_tx::bytes.L2::cache_hint [%0], [%1, {%3, %4, %5}], [%2], %6;"::"r"(dst),"l"(m),"r"(bar),"r"(c0),"r"(c1),"r"(c2),"l"(pol):"memory"); }
__device__ __forceinline__ void tma_4d_h(uint32_t dst, const CUtensorMap* m, int c0, int c1, int c2, int c3, uint32_t bar, uint64_t pol){
  asm volatile("cp.async.bulk.tensor.4d.shared::cluster.global.mbarrier::complete_tx::bytes.L2::cache_hint [%0], [%1, {%3, %4, %5, %6}], [%2], %7;"::"r"(dst),"l"(m),"r"(bar),"r"(c0),"r"(c1),"r"(c2),"r"(c3),"l"(pol):"memory"); }
__device__ __forceinline__ void red_add_f32x4(float4* p, float x, float y, float z, float w){ asm volatile("red.relaxed.gpu.global.add.v4.f32 [%0], {%1,%2,%3,%4};"::"l"(p),"f"(x),"f"(y),"f"(z),"f"(w):"memory"); }
__device__ __forceinline__ void tma_5d_h(uint32_t dst, const CUtensorMap* m, int c0, int c1, uint32_t bar, uint64_t pol){
  asm volatile("cp.async.bulk.tensor.5d.shared::cluster.global.mbarrier::complete_tx::bytes.L2::cache_hint [%0], [%1, {%3, %4, 0, 0, 0}], [%2], %5;"::"r"(dst),"l"(m),"r"(bar),"r"(c0),"r"(c1),"l"(pol):"memory"); }
__device__ __forceinline__ void tma_store_2d(const CUtensorMap* m, int c0, int c1, uint32_t src, uint64_t pol){
  asm volatile("cp.async.bulk.tensor.2d.global.shared::cta.bulk_group.L2::cache_hint [%0, {%2, %3}], [%1], %4;"::"l"(m),"r"(src),"r"(c0),"r"(c1),"l"(pol):"memory"); }
__device__ __forceinline__ void bulk_commit(){ asm volatile("cp.async.bulk.commit_group;":::"memory"); }
__device__ __forceinline__ void bulk_wait_all(){ asm volatile("cp.async.bulk.wait_group 0;":::"memory"); }
__device__ __forceinline__ void fence_async_global(){ asm volatile("fence.proxy.async.global;":::"memory"); }
__device__ __forceinline__ bool elect_one(){ uint32_t p; asm volatile("{\n.reg .pred P;\nelect.sync _|P, 0xffffffff;\nselp.b32 %0, 1, 0, P;\n}\n":"=r"(p)); return p; }
__device__ __forceinline__ void bulk_prefetch(const void* p, uint32_t bytes){
  asm volatile("cp.async.bulk.prefetch.L2.global [%0], %1;"::"l"(p),"r"(bytes):"memory"); }
__device__ __forceinline__ void bulk_s2peer(uint32_t dst_cluster, uint32_t src, uint32_t bytes, uint32_t bar_cluster){
  asm volatile("cp.async.bulk.shared::cluster.shared::cta.mbarrier::complete_tx::bytes [%0], [%1], %2, [%3];"::"r"(dst_cluster),"r"(src),"r"(bytes),"r"(bar_cluster):"memory"); }
__device__ __forceinline__ void prefetch_map(const CUtensorMap* m){ asm volatile("prefetch.tensormap [%0];"::"l"(m):"memory"); }
__device__ __forceinline__ void fence_async_smem(){ asm volatile("fence.proxy.async.shared::cta;":::"memory"); }
__device__ __forceinline__ void fence_acquire_gpu(){ asm volatile("fence.acquire.gpu;":::"memory"); }
__device__ __forceinline__ void fence_gpu(){ asm volatile("fence.acq_rel.gpu;":::"memory"); }
__device__ __forceinline__ void wg_fence(){ asm volatile("wgmma.fence.sync.aligned;":::"memory"); }
__device__ __forceinline__ void wg_commit(){ asm volatile("wgmma.commit_group.sync.aligned;":::"memory"); }
template<int N> __device__ __forceinline__ void wg_wait(){ asm volatile("wgmma.wait_group.sync.aligned %0;"::"n"(N):"memory"); }
template<int N> __device__ __forceinline__ void fence_regs(float (&d)[N]){
  #pragma unroll
  for(int i=0;i<N;i++) asm volatile("":"+f"(d[i])::"memory"); }
__device__ __forceinline__ void bar_sync(int id, int n){ JIT(); asm volatile("bar.sync %0, %1;"::"r"(id),"r"(n):"memory"); }
__device__ __forceinline__ void bar_arrive(int id, int n){ JIT(); asm volatile("bar.arrive %0, %1;"::"r"(id),"r"(n):"memory"); }
__device__ __forceinline__ void cluster_arrive(){ asm volatile("barrier.cluster.arrive.relaxed.aligned;":::"memory"); }
__device__ __forceinline__ void cluster_wait(){ asm volatile("barrier.cluster.wait.aligned;":::"memory"); }
__host__ __device__ constexpr uint32_t dlo(uint32_t addr, uint32_t lbo){ return (addr >> 4) | ((lbo >> 4) << 16); }
__host__ __device__ constexpr uint32_t dhi(uint32_t sbo, uint32_t sw){ return (sbo >> 4) | (sw << 30); }
constexpr uint32_t H128 = dhi(1024, 1), H64 = dhi(512, 2), H0 = dhi(128, 0);
__device__ __forceinline__ uint32_t pack_bf16(float lo, float hi){ uint32_t r; asm("cvt.rn.bf16x2.f32 %0, %1, %2;":"=r"(r):"f"(hi),"f"(lo)); return r; }
__device__ __forceinline__ float bf_lo(uint32_t v){ return __uint_as_float(v<<16); }
__device__ __forceinline__ float bf_hi(uint32_t v){ return __uint_as_float(v&0xffff0000u); }
__device__ __forceinline__ float ex2(float x){ float r; asm("ex2.approx.ftz.f32 %0, %1;":"=f"(r):"f"(x)); return r; }
__device__ __forceinline__ float rcp(float x){ float r; asm("rcp.approx.ftz.f32 %0, %1;":"=f"(r):"f"(x)); return r; }
__device__ __forceinline__ void stsm4(uint32_t addr, uint32_t a, uint32_t b, uint32_t c, uint32_t d){
  asm volatile("stmatrix.sync.aligned.m8n8.x4.shared.b16 [%0], {%1,%2,%3,%4};"::"r"(addr),"r"(a),"r"(b),"r"(c),"r"(d)); }
__device__ __forceinline__ void stsm2(uint32_t addr, uint32_t a, uint32_t b){
  asm volatile("stmatrix.sync.aligned.m8n8.x2.shared.b16 [%0], {%1,%2};"::"r"(addr),"r"(a),"r"(b)); }
__device__ __forceinline__ void mma16816(float& d0, float& d1, float& d2, float& d3, uint32_t a0, uint32_t a1, uint32_t a2, uint32_t a3, uint32_t b0, uint32_t b1){
  asm volatile("mma.sync.aligned.m16n8k16.row.col.f32.bf16.bf16.f32 {%0,%1,%2,%3}, {%4,%5,%6,%7}, {%8,%9}, {%0,%1,%2,%3};"
               : "+f"(d0), "+f"(d1), "+f"(d2), "+f"(d3) : "r"(a0), "r"(a1), "r"(a2), "r"(a3), "r"(b0), "r"(b1)); }
__device__ __forceinline__ uint32_t transpose8(uint32_t a){ uint32_t r; asm volatile("movmatrix.sync.aligned.m8n8.trans.b16 %0, %1;":"=r"(r):"r"(a)); return r; }
__device__ __forceinline__ void ldsm4(uint32_t addr, uint32_t& a, uint32_t& b, uint32_t& c, uint32_t& d){
  asm volatile("ldmatrix.sync.aligned.m8n8.x4.shared.b16 {%0,%1,%2,%3}, [%4];":"=r"(a),"=r"(b),"=r"(c),"=r"(d):"r"(addr):"memory"); }
__device__ __forceinline__ void ldsm4t(uint32_t addr, uint32_t& a, uint32_t& b, uint32_t& c, uint32_t& d){
  asm volatile("ldmatrix.sync.aligned.m8n8.x4.trans.shared.b16 {%0,%1,%2,%3}, [%4];":"=r"(a),"=r"(b),"=r"(c),"=r"(d):"r"(addr):"memory"); }
__device__ __forceinline__ void sts32(uint32_t a, uint32_t v){ asm volatile("st.shared.b32 [%0], %1;"::"r"(a),"r"(v):"memory"); }
__device__ __forceinline__ void stsf(uint32_t a, float v){ asm volatile("st.shared.f32 [%0], %1;"::"r"(a),"f"(v):"memory"); }
__device__ __forceinline__ void sts64(uint32_t a, uint32_t x, uint32_t y){ asm volatile("st.shared.v2.b32 [%0], {%1,%2};"::"r"(a),"r"(x),"r"(y):"memory"); }
__device__ __forceinline__ void sts128(uint32_t a, uint32_t x, uint32_t y, uint32_t z, uint32_t w){ asm volatile("st.shared.v4.b32 [%0], {%1,%2,%3,%4};"::"r"(a),"r"(x),"r"(y),"r"(z),"r"(w):"memory"); }
__device__ __forceinline__ float ldsf(uint32_t a){ float v; asm volatile("ld.shared.f32 %0, [%1];":"=f"(v):"r"(a):"memory"); return v; }
__device__ __forceinline__ float2 lds64f(uint32_t a){ float2 v; asm volatile("ld.shared.v2.f32 {%0,%1}, [%2];":"=f"(v.x),"=f"(v.y):"r"(a):"memory"); return v; }
__device__ __forceinline__ uint4 lds128(uint32_t a){ uint4 v; asm volatile("ld.shared.v4.u32 {%0,%1,%2,%3}, [%4];":"=r"(v.x),"=r"(v.y),"=r"(v.z),"=r"(v.w):"r"(a):"memory"); return v; }
__device__ __forceinline__ uint4 ld128_keep(const void* p){ uint4 v; asm volatile("ld.global.v4.u32 {%0,%1,%2,%3}, [%4];":"=r"(v.x),"=r"(v.y),"=r"(v.z),"=r"(v.w):"l"(p):"memory"); return v; }
__device__ __forceinline__ uint4 ld128_rlx(const void* p){ uint4 v; asm volatile("ld.relaxed.gpu.global.v4.u32 {%0,%1,%2,%3}, [%4];":"=r"(v.x),"=r"(v.y),"=r"(v.z),"=r"(v.w):"l"(p):"memory"); return v; }
__device__ __forceinline__ uint32_t ld32_rlx(const void* p){ uint32_t v; asm volatile("ld.relaxed.gpu.global.u32 %0, [%1];":"=r"(v):"l"(p):"memory"); return v; }
__device__ __forceinline__ void st128_rlx(void* p, uint32_t x, uint32_t y, uint32_t z, uint32_t w){ asm volatile("st.relaxed.gpu.global.v4.u32 [%0], {%1,%2,%3,%4};"::"l"(p),"r"(x),"r"(y),"r"(z),"r"(w):"memory"); }
__device__ __forceinline__ void st64_rlx(void* p, uint32_t x, uint32_t y){ asm volatile("st.relaxed.gpu.global.v2.u32 [%0], {%1,%2};"::"l"(p),"r"(x),"r"(y):"memory"); }
__device__ __forceinline__ void st32_rlx(void* p, uint32_t x){ asm volatile("st.relaxed.gpu.global.u32 [%0], %1;"::"l"(p),"r"(x):"memory"); }
__device__ __forceinline__ void flags_wait(uint32_t& missing, const uint32_t* p, uint32_t need){
  asm volatile("{\n.reg .pred p;\n.reg .u32 c, v;\nmov.u32 c, 0;\nLW:\nand.b32 v, %0, %2;\nsetp.eq.u32 p, v, 0;\n@p bra.uni LD;\nld.relaxed.gpu.global.u32 v, [%1];\nsetp.eq.u32 p, v, 0;\n"
               "vote.sync.ballot.b32 %0, p, 0xffffffff;\nadd.u32 c, c, 1;\nsetp.lt.u32 p, c, 4000000;\n@p bra.uni LW;\nLD:\n}\n":"+r"(missing):"l"(p),"r"(need):"memory"); }
__device__ __forceinline__ uint32_t tagw(float x, uint32_t t){ return (__float_as_uint(x) & ~3u) | t; }
__device__ __forceinline__ float untag(uint32_t w){ return __uint_as_float(w & ~3u); }

template<int TA, int TB, uint32_t HA, uint32_t HB> __device__ __forceinline__ void wgmma_ss_n128(float (&d)[64], uint32_t da, uint32_t db, int scale_d){
  asm volatile("{\n.reg .pred p;\n.reg .b64 a, b;\nsetp.ne.b32 p, %70, 0;\nmov.b64 a, {%64, %68};\nmov.b64 b, {%65, %69};\n"
  "wgmma.mma_async.sync.aligned.m64n128k16.f32.bf16.bf16 {%0, %1, %2, %3, %4, %5, %6, %7, %8, %9, %10, %11, %12, %13, %14, %15, %16, %17, %18, %19, %20, %21, %22, %23, %24, %25, %26, %27, %28, %29, %30, %31, %32, %33, %34, %35, %36, %37, %38, %39, %40, %41, %42, %43, %44, %45, %46, %47, %48, %49, %50, %51, %52, %53, %54, %55, %56, %57, %58, %59, %60, %61, %62, %63}, a, b, p, 1, 1, %66, %67;\n}\n"
  : "+f"(d[0]), "+f"(d[1]), "+f"(d[2]), "+f"(d[3]), "+f"(d[4]), "+f"(d[5]), "+f"(d[6]), "+f"(d[7]), "+f"(d[8]), "+f"(d[9]), "+f"(d[10]), "+f"(d[11]), "+f"(d[12]), "+f"(d[13]), "+f"(d[14]), "+f"(d[15]), "+f"(d[16]), "+f"(d[17]), "+f"(d[18]), "+f"(d[19]), "+f"(d[20]), "+f"(d[21]), "+f"(d[22]), "+f"(d[23]), "+f"(d[24]), "+f"(d[25]), "+f"(d[26]), "+f"(d[27]), "+f"(d[28]), "+f"(d[29]), "+f"(d[30]), "+f"(d[31]), "+f"(d[32]), "+f"(d[33]), "+f"(d[34]), "+f"(d[35]), "+f"(d[36]), "+f"(d[37]), "+f"(d[38]), "+f"(d[39]), "+f"(d[40]), "+f"(d[41]), "+f"(d[42]), "+f"(d[43]), "+f"(d[44]), "+f"(d[45]), "+f"(d[46]), "+f"(d[47]), "+f"(d[48]), "+f"(d[49]), "+f"(d[50]), "+f"(d[51]), "+f"(d[52]), "+f"(d[53]), "+f"(d[54]), "+f"(d[55]), "+f"(d[56]), "+f"(d[57]), "+f"(d[58]), "+f"(d[59]), "+f"(d[60]), "+f"(d[61]), "+f"(d[62]), "+f"(d[63])
  : "r"(da), "r"(db), "n"(TA), "n"(TB), "n"(HA), "n"(HB), "r"(scale_d));
}
template<int TA, int TB, uint32_t HA, uint32_t HB> __device__ __forceinline__ void wgmma_sa_n128(float (&d)[64], uint32_t da, uint32_t db){
  asm volatile("{\n.reg .pred p;\n.reg .b64 a, b;\nsetp.ne.b32 p, 1, 0;\nmov.b64 a, {%64, %68};\nmov.b64 b, {%65, %69};\n"
  "wgmma.mma_async.sync.aligned.m64n128k16.f32.bf16.bf16 {%0, %1, %2, %3, %4, %5, %6, %7, %8, %9, %10, %11, %12, %13, %14, %15, %16, %17, %18, %19, %20, %21, %22, %23, %24, %25, %26, %27, %28, %29, %30, %31, %32, %33, %34, %35, %36, %37, %38, %39, %40, %41, %42, %43, %44, %45, %46, %47, %48, %49, %50, %51, %52, %53, %54, %55, %56, %57, %58, %59, %60, %61, %62, %63}, a, b, p, 1, 1, %66, %67;\n}\n"
  : "+f"(d[0]), "+f"(d[1]), "+f"(d[2]), "+f"(d[3]), "+f"(d[4]), "+f"(d[5]), "+f"(d[6]), "+f"(d[7]), "+f"(d[8]), "+f"(d[9]), "+f"(d[10]), "+f"(d[11]), "+f"(d[12]), "+f"(d[13]), "+f"(d[14]), "+f"(d[15]), "+f"(d[16]), "+f"(d[17]), "+f"(d[18]), "+f"(d[19]), "+f"(d[20]), "+f"(d[21]), "+f"(d[22]), "+f"(d[23]), "+f"(d[24]), "+f"(d[25]), "+f"(d[26]), "+f"(d[27]), "+f"(d[28]), "+f"(d[29]), "+f"(d[30]), "+f"(d[31]), "+f"(d[32]), "+f"(d[33]), "+f"(d[34]), "+f"(d[35]), "+f"(d[36]), "+f"(d[37]), "+f"(d[38]), "+f"(d[39]), "+f"(d[40]), "+f"(d[41]), "+f"(d[42]), "+f"(d[43]), "+f"(d[44]), "+f"(d[45]), "+f"(d[46]), "+f"(d[47]), "+f"(d[48]), "+f"(d[49]), "+f"(d[50]), "+f"(d[51]), "+f"(d[52]), "+f"(d[53]), "+f"(d[54]), "+f"(d[55]), "+f"(d[56]), "+f"(d[57]), "+f"(d[58]), "+f"(d[59]), "+f"(d[60]), "+f"(d[61]), "+f"(d[62]), "+f"(d[63])
  : "r"(da), "r"(db), "n"(TA), "n"(TB), "n"(HA), "n"(HB));
}
template<int TA, int TB, uint32_t HA, uint32_t HB> __device__ __forceinline__ void wgmma_sa_n40(float (&d)[20], uint32_t da, uint32_t db){
  asm volatile("{\n.reg .pred p;\n.reg .b64 a, b;\nsetp.ne.b32 p, 1, 0;\nmov.b64 a, {%20, %24};\nmov.b64 b, {%21, %25};\n"
  "wgmma.mma_async.sync.aligned.m64n40k16.f32.bf16.bf16 {%0, %1, %2, %3, %4, %5, %6, %7, %8, %9, %10, %11, %12, %13, %14, %15, %16, %17, %18, %19}, a, b, p, 1, 1, %22, %23;\n}\n"
  : "+f"(d[0]), "+f"(d[1]), "+f"(d[2]), "+f"(d[3]), "+f"(d[4]), "+f"(d[5]), "+f"(d[6]), "+f"(d[7]), "+f"(d[8]), "+f"(d[9]), "+f"(d[10]), "+f"(d[11]), "+f"(d[12]), "+f"(d[13]), "+f"(d[14]), "+f"(d[15]), "+f"(d[16]), "+f"(d[17]), "+f"(d[18]), "+f"(d[19])
  : "r"(da), "r"(db), "n"(TA), "n"(TB), "n"(HA), "n"(HB));
}
template<int TA, int TB, uint32_t HA, uint32_t HB> __device__ __forceinline__ void wgmma_sz_n40(float (&d)[20], uint32_t da, uint32_t db){
  asm volatile("{\n.reg .pred p;\n.reg .b64 a, b;\nsetp.ne.b32 p, 0, 0;\nmov.b64 a, {%20, %24};\nmov.b64 b, {%21, %25};\n"
  "wgmma.mma_async.sync.aligned.m64n40k16.f32.bf16.bf16 {%0, %1, %2, %3, %4, %5, %6, %7, %8, %9, %10, %11, %12, %13, %14, %15, %16, %17, %18, %19}, a, b, p, 1, 1, %22, %23;\n}\n"
  : "=f"(d[0]), "=f"(d[1]), "=f"(d[2]), "=f"(d[3]), "=f"(d[4]), "=f"(d[5]), "=f"(d[6]), "=f"(d[7]), "=f"(d[8]), "=f"(d[9]), "=f"(d[10]), "=f"(d[11]), "=f"(d[12]), "=f"(d[13]), "=f"(d[14]), "=f"(d[15]), "=f"(d[16]), "=f"(d[17]), "=f"(d[18]), "=f"(d[19])
  : "r"(da), "r"(db), "n"(TA), "n"(TB), "n"(HA), "n"(HB));
}
template<int TA, int TB, uint32_t HA, uint32_t HB> __device__ __forceinline__ void wgmma_sa_n32(float (&d)[16], uint32_t da, uint32_t db){
  asm volatile("{\n.reg .pred p;\n.reg .b64 a, b;\nsetp.ne.b32 p, 1, 0;\nmov.b64 a, {%16, %20};\nmov.b64 b, {%17, %21};\n"
  "wgmma.mma_async.sync.aligned.m64n32k16.f32.bf16.bf16 {%0, %1, %2, %3, %4, %5, %6, %7, %8, %9, %10, %11, %12, %13, %14, %15}, a, b, p, 1, 1, %18, %19;\n}\n"
  : "+f"(d[0]), "+f"(d[1]), "+f"(d[2]), "+f"(d[3]), "+f"(d[4]), "+f"(d[5]), "+f"(d[6]), "+f"(d[7]), "+f"(d[8]), "+f"(d[9]), "+f"(d[10]), "+f"(d[11]), "+f"(d[12]), "+f"(d[13]), "+f"(d[14]), "+f"(d[15])
  : "r"(da), "r"(db), "n"(TA), "n"(TB), "n"(HA), "n"(HB));
}
template<int TA, int TB, uint32_t HA, uint32_t HB> __device__ __forceinline__ void wgmma_ss_n32(float (&d)[16], uint32_t da, uint32_t db, int scale_d){
  asm volatile("{\n.reg .pred p;\n.reg .b64 a, b;\nsetp.ne.b32 p, %22, 0;\nmov.b64 a, {%16, %20};\nmov.b64 b, {%17, %21};\n"
  "wgmma.mma_async.sync.aligned.m64n32k16.f32.bf16.bf16 {%0, %1, %2, %3, %4, %5, %6, %7, %8, %9, %10, %11, %12, %13, %14, %15}, a, b, p, 1, 1, %18, %19;\n}\n"
  : "+f"(d[0]), "+f"(d[1]), "+f"(d[2]), "+f"(d[3]), "+f"(d[4]), "+f"(d[5]), "+f"(d[6]), "+f"(d[7]), "+f"(d[8]), "+f"(d[9]), "+f"(d[10]), "+f"(d[11]), "+f"(d[12]), "+f"(d[13]), "+f"(d[14]), "+f"(d[15])
  : "r"(da), "r"(db), "n"(TA), "n"(TB), "n"(HA), "n"(HB), "r"(scale_d));
}
template<int TB, uint32_t HB> __device__ __forceinline__ void wgmma_ra_n32(float (&d)[16], uint32_t a0, uint32_t a1, uint32_t a2, uint32_t a3, uint32_t db){
  asm volatile("{\n.reg .pred p;\n.reg .b64 a, b;\nsetp.ne.b32 p, 1, 0;\nmov.b64 b, {%20, %22};\n"
  "wgmma.mma_async.sync.aligned.m64n32k16.f32.bf16.bf16 {%0, %1, %2, %3, %4, %5, %6, %7, %8, %9, %10, %11, %12, %13, %14, %15}, {%16,%17,%18,%19}, b, p, 1, 1, %21;\n}\n"
  : "+f"(d[0]), "+f"(d[1]), "+f"(d[2]), "+f"(d[3]), "+f"(d[4]), "+f"(d[5]), "+f"(d[6]), "+f"(d[7]), "+f"(d[8]), "+f"(d[9]), "+f"(d[10]), "+f"(d[11]), "+f"(d[12]), "+f"(d[13]), "+f"(d[14]), "+f"(d[15])
  : "r"(a0), "r"(a1), "r"(a2), "r"(a3), "r"(db), "n"(TB), "n"(HB));
}
template<int TB, uint32_t HB> __device__ __forceinline__ void wgmma_rs_n32(float (&d)[16], uint32_t a0, uint32_t a1, uint32_t a2, uint32_t a3, uint32_t db, int scale_d){
  asm volatile("{\n.reg .pred p;\n.reg .b64 a, b;\nsetp.ne.b32 p, %23, 0;\nmov.b64 b, {%20, %22};\n"
  "wgmma.mma_async.sync.aligned.m64n32k16.f32.bf16.bf16 {%0, %1, %2, %3, %4, %5, %6, %7, %8, %9, %10, %11, %12, %13, %14, %15}, {%16,%17,%18,%19}, b, p, 1, 1, %21;\n}\n"
  : "+f"(d[0]), "+f"(d[1]), "+f"(d[2]), "+f"(d[3]), "+f"(d[4]), "+f"(d[5]), "+f"(d[6]), "+f"(d[7]), "+f"(d[8]), "+f"(d[9]), "+f"(d[10]), "+f"(d[11]), "+f"(d[12]), "+f"(d[13]), "+f"(d[14]), "+f"(d[15])
  : "r"(a0), "r"(a1), "r"(a2), "r"(a3), "r"(db), "n"(TB), "n"(HB), "r"(scale_d));
}
template<int TB, uint32_t HB> __device__ __forceinline__ void wgmma_ra_n40(float (&d)[20], uint32_t a0, uint32_t a1, uint32_t a2, uint32_t a3, uint32_t db){
  asm volatile("{\n.reg .pred p;\n.reg .b64 a, b;\nsetp.ne.b32 p, 1, 0;\nmov.b64 b, {%24, %26};\n"
  "wgmma.mma_async.sync.aligned.m64n40k16.f32.bf16.bf16 {%0, %1, %2, %3, %4, %5, %6, %7, %8, %9, %10, %11, %12, %13, %14, %15, %16, %17, %18, %19}, {%20,%21,%22,%23}, b, p, 1, 1, %25;\n}\n"
  : "+f"(d[0]), "+f"(d[1]), "+f"(d[2]), "+f"(d[3]), "+f"(d[4]), "+f"(d[5]), "+f"(d[6]), "+f"(d[7]), "+f"(d[8]), "+f"(d[9]), "+f"(d[10]), "+f"(d[11]), "+f"(d[12]), "+f"(d[13]), "+f"(d[14]), "+f"(d[15]), "+f"(d[16]), "+f"(d[17]), "+f"(d[18]), "+f"(d[19])
  : "r"(a0), "r"(a1), "r"(a2), "r"(a3), "r"(db), "n"(TB), "n"(HB));
}
template<int TB, uint32_t HB> __device__ __forceinline__ void wgmma_rz_n40(float (&d)[20], uint32_t a0, uint32_t a1, uint32_t a2, uint32_t a3, uint32_t db){
  asm volatile("{\n.reg .pred p;\n.reg .b64 a, b;\nsetp.ne.b32 p, 0, 0;\nmov.b64 b, {%24, %26};\n"
  "wgmma.mma_async.sync.aligned.m64n40k16.f32.bf16.bf16 {%0, %1, %2, %3, %4, %5, %6, %7, %8, %9, %10, %11, %12, %13, %14, %15, %16, %17, %18, %19}, {%20,%21,%22,%23}, b, p, 1, 1, %25;\n}\n"
  : "=f"(d[0]), "=f"(d[1]), "=f"(d[2]), "=f"(d[3]), "=f"(d[4]), "=f"(d[5]), "=f"(d[6]), "=f"(d[7]), "=f"(d[8]), "=f"(d[9]), "=f"(d[10]), "=f"(d[11]), "=f"(d[12]), "=f"(d[13]), "=f"(d[14]), "=f"(d[15]), "=f"(d[16]), "=f"(d[17]), "=f"(d[18]), "=f"(d[19])
  : "r"(a0), "r"(a1), "r"(a2), "r"(a3), "r"(db), "n"(TB), "n"(HB));
}
template<int TB, uint32_t HB> __device__ __forceinline__ void wgmma_rz_n8(float (&d)[4], uint32_t a0, uint32_t a1, uint32_t a2, uint32_t a3, uint32_t db){
  asm volatile("{\n.reg .pred p;\n.reg .b64 a, b;\nsetp.ne.b32 p, 0, 0;\nmov.b64 b, {%8, %10};\n"
  "wgmma.mma_async.sync.aligned.m64n8k16.f32.bf16.bf16 {%0, %1, %2, %3}, {%4,%5,%6,%7}, b, p, 1, 1, %9;\n}\n"
  : "=f"(d[0]), "=f"(d[1]), "=f"(d[2]), "=f"(d[3])
  : "r"(a0), "r"(a1), "r"(a2), "r"(a3), "r"(db), "n"(TB), "n"(HB));
}

constexpr int SEQ = 2048, DM = 1024, FF = 3584;
constexpr float LOG2E = 1.4426950408889634f;
constexpr uint32_t POLL_LIMIT = 1u << 22;
#define NPREN 2
constexpr int NPRE = NPREN;
#define QW 0
#define RS_N 22
#define RS_D1 430
#define RS_D2 300
#define SKM 0x154
#define LAG 2
#define PF_T0 5000
#define PF_DT 800
#define NFFN_L NFFN
#define FF_DT 500
#define GRES 8
#define TMASK 0xffffff
#define PMASK 0xffffff
#define FF_T0 1
#define GPRE 0
#define REL 6
#define EFI 11
#define TKW 8
#define FF_ORD 0x76543210ba98ull
#define KT 0
#define KM 0xffff
#define KR2 1
#define KK(id) do { if (KT == 1) { TK(32 * wg + (id)); } } while (0)
#define PF_I0 0
#define PF_ST 7
#define PRK 3
#define TRKL 1
#define KR 4
#define KSEL c
#define XP 0
#define CAPL 2
#define OUT_D 400
#define OUT_0 0
#define ML 2
#define H2 1
#define H3 1
#define FUNN 1
constexpr int FUN = FUNN;
#define FF_N 6
#define FF_D2 350
#define S2D 300
constexpr int NFFN = 112;

constexpr uint32_t SB0 = 1024;
constexpr uint32_t KV_STAGE = 49152, R5 = 32768;
constexpr uint32_t OFF_X = 163840, OFF_S = 196608, OFF_WPHI = OFF_S + 20480, OFF_M = 229376, SMEM_BYTES = 232448;
constexpr uint32_t OFF_RS256 = 212992, OFF_ONES = OFF_RS256 + 1024, OFF_WPHIK1 = OFF_ONES + 1024, OFF_KVZ = OFF_S;
constexpr uint32_t OFF_WPHIK = OFF_S, OFF_BXK = OFF_S + 2048, OFF_AXK = OFF_S + 4096, OFF_G = OFF_S + 8192;
constexpr uint32_t OFF_AXQ = OFF_WPHI, OFF_BXQ = OFF_WPHI + 2048, OFF_WPHIQ = OFF_WPHI + 4096;
constexpr uint32_t B_FULLKV = OFF_M  , B_EMPTYKV = OFF_M + 32  ;
constexpr uint32_t B_EMPTY5 = OFF_M + 64  , B_UO = B_EMPTY5 + 48  , B_RC = B_UO + 32  ;
constexpr uint32_t B_OUT = B_RC + 16  , B_SD = B_OUT + 16, B_AUX = B_SD + 8, B_AUXQ = B_AUX + 8, B_RX = B_AUXQ + 8;
constexpr uint32_t B_FULL5 = B_RX + 8  , B_F = B_FULL5 + 40  , B_WD = B_F + 64  ;
constexpr uint32_t B_WC = B_WD + 32  , B_DR = B_WC + 32  , B_W = B_DR + 24, B_OS = B_W + 8, B_R = B_W + 16, B_KD = B_W + 24, B_R1 = B_W + 32, B_T = B_W + 40, B_G = B_W + 48, B_END = B_W + 56;
constexpr int NB3 = ((B_END - OFF_M) / 8 + 1) / 3;
constexpr uint32_t B_S0 = OFF_M + 8 + 24 * NB3;
static_assert(B_S0 >= B_END && B_S0 < OFF_M + 600, "barriers");
__host__ __device__ constexpr uint32_t bar_count(int i) {
  const uint32_t b = OFF_M + 8 * i;
  return b < B_EMPTYKV ? 1 : b < B_EMPTY5 ? 12 : b < B_SD ? 4 : b < B_RX || b == B_W ? 2 : b == B_RX ? 8 : 1;
}
constexpr uint32_t B_GB = OFF_M + 2560  , B_GA = B_GB + 128  ;
constexpr uint32_t OFF_SUMWR = OFF_M + 608, OFF_EP = OFF_M + 624, OFF_KEY = OFF_M + 628;
constexpr uint32_t OFF_RSQ = OFF_M + 640, OFF_TL = OFF_M + 1152, OFF_SEL = OFF_M + 1648, OFF_T = OFF_M + 1792, OFF_WR = OFF_M + 2048;
constexpr uint32_t OFF_XSEL = 2 * R5, OFF_GU = OFF_XSEL + 4096, OFF_OUT = 3 * R5;
constexpr uint64_t FF_SLOT = 0xdcdc3210dcbaull;
constexpr int KVP = 6 * 128;

enum { NB_G2E = 1, NB_XS = 2, NB_WG01 = 3, NB_ACT = 4, NB_Q0 = 5  , NB_ST = 14, NB_LAG = 8, NB_DN = 9, NB_ZERO = 10, NB_PUB = 11, NB_TOK = 10  , NB_L0 = 12  , NB_WG2 = 7, NB_QGO = 15 };

struct Scratch {
  bf16     o[SEQ * DM];
  float4   rstat[SEQ];
  uint32_t key[8 * KR * 128];
  uint32_t cand[128 * 512];
  float4   yacc[4 * 3 * 128];
  float4   kvacc[32 * KVP];
  uint2    stats[SEQ];
  uint32_t cskv[2 * DM];
  uint32_t csq[4 * DM];
  uint32_t oset[128 * 16];
  uint32_t oflag[16 * 6 * 32];
  uint32_t epoch;
};
__device__ __align__(1024) Scratch g_scr;
#define TS(id)
#define TDUMP()
#define TS0_DECL()
#define TS0_READ()
#define TS0_WRITE()
#define TK(id)
#define TSW(id)

struct Params {
  const bf16 *x, *wqkv, *wo_p, *wg_p, *wu_p, *wd_p, *wr;
  bf16* out_p;
  Scratch* g;
  uint32_t zero;
  CUtensorMap x128, x64, wkv, wq, wo[2], wd, wg, wu, phi, tg, tu, td, xs, ws, qs, out, o;
};

constexpr float EXP_LIM = 1.1529215e18f, ARG_LIM2 = 3600.f;
template<bool PR> __device__ __forceinline__ void dual_exp2(const float (&p)[16], uint32_t (&ep)[8], uint32_t (&em)[8]) {
  #pragma unroll
  for (int k = 0; k < 8; k++) {
    const float a = ex2(p[2*k]), b = ex2(p[2*k+1]);
    ep[k] = pack_bf16(a, b);
    if (PR) { const float r = rcp(a * b); em[k] = pack_bf16(r * b, r * a); }
    else em[k] = pack_bf16(ex2(-p[2*k]), ex2(-p[2*k+1]));
  }
}
__device__ __forceinline__ void dual_exp2_shifted(const float (&pp)[2][16], uint32_t (&ph)[4][8]) {
  #pragma unroll
  for (int h = 0; h < 2; h++) {
    const float* p = pp[h];
    float m[4] = {p[0], p[2], p[0], p[2]};
    #pragma unroll
    for (int i = 0; i < 16; i++) { m[(i >> 1) & 1] = fmaxf(m[(i >> 1) & 1], p[i]); m[2 + ((i >> 1) & 1)] = fminf(m[2 + ((i >> 1) & 1)], p[i]); }
    #pragma unroll
    for (int o = 1; o < 4; o <<= 1) {
      m[0] = fmaxf(m[0], __shfl_xor_sync(~0u, m[0], o)); m[1] = fmaxf(m[1], __shfl_xor_sync(~0u, m[1], o));
      m[2] = fminf(m[2], __shfl_xor_sync(~0u, m[2], o)); m[3] = fminf(m[3], __shfl_xor_sync(~0u, m[3], o));
    }
    #pragma unroll
    for (int k = 0; k < 8; k++) {
      ph[2*h][k] = pack_bf16(ex2(p[2*k] - m[k & 1]), ex2(p[2*k+1] - m[k & 1]));
      ph[2*h+1][k] = pack_bf16(ex2(m[2 + (k & 1)] - p[2*k]), ex2(m[2 + (k & 1)] - p[2*k+1]));
    }
  }
}
__device__ __forceinline__ uint32_t add_bf16x2(uint32_t a, uint32_t b) { uint32_t r; asm("add.rn.bf16x2 %0, %1, %2;" : "=r"(r) : "r"(a), "r"(b)); return r; }
__device__ __forceinline__ void row_sums(float (&s)[2][4], const uint32_t (&ph)[4][8], uint32_t sel) {
  uint32_t u[8];
  #pragma unroll
  for (int i = 0; i < 8; i++) { const uint32_t* f = &ph[i >> 1][i & 1]; u[i] = add_bf16x2(add_bf16x2(f[0], f[2]), add_bf16x2(f[4], f[6])); }
  wg_fence();
  wgmma_rz_n8<0, H0>(s[0], u[0], u[1], u[2], u[3], sel);
  wgmma_rz_n8<0, H0>(s[1], u[4], u[5], u[6], u[7], sel);
  wg_commit();
}
__device__ __forceinline__ uint32_t mul_bf16x2(uint32_t a, uint32_t b) { uint32_t r; asm("mul.rn.bf16x2 %0, %1, %2;" : "=r"(r) : "r"(a), "r"(b)); return r; }
__device__ __forceinline__ void normalize(uint32_t (&ph)[4][8], const float (&s)[2][4]) {
  #pragma unroll
  for (int i = 0; i < 4; i++) {
    const float i0 = rcp(s[i >> 1][i & 1]), i1 = rcp(s[i >> 1][2 + (i & 1)]);
    const uint32_t n0 = pack_bf16(i0, i0), n1 = pack_bf16(i1, i1);
    #pragma unroll
    for (int k = 0; k < 4; k++) { ph[i][2*k] = mul_bf16x2(ph[i][2*k], n0); ph[i][2*k+1] = mul_bf16x2(ph[i][2*k+1], n1); }
  }
}
__device__ __forceinline__ void split_bf16(float a, float b, uint32_t& hi, uint32_t& lo) { hi = pack_bf16(a, b); lo = pack_bf16(a - bf_lo(hi), b - bf_hi(hi)); }
__device__ __forceinline__ void put_colsums(uint32_t base, int lane, float a, float b, float c, float d) {
  uint32_t h0, l0, h1, l1;
  split_bf16(a, b, h0, l0); split_bf16(c, d, h1, l1);
  const uint32_t ad = base + (lane >> 1) * 128 + (lane & 1) * 8;
  sts64(ad, h0, h1); sts64(ad + 16, l0, l1); sts64(ad + 32, h0, h1); sts64(ad + 48, l0, l1);
  sts128(base + (lane >> 1) * 128 + 64 + (lane & 1) * 32, 0, 0, 0, 0); sts128(base + (lane >> 1) * 128 + 80 + (lane & 1) * 32, 0, 0, 0, 0);
}
__device__ __forceinline__ float reduce8(const float (&v)[8], int lane) {
  const bool b4 = lane & 16, b3 = lane & 8, b2 = lane & 4;
  float a[4], b[2];
  #pragma unroll
  for (int i = 0; i < 4; i++) a[i] = (b4 ? v[4 + i] : v[i]) + __shfl_xor_sync(~0u, b4 ? v[i] : v[4 + i], 16);
  #pragma unroll
  for (int i = 0; i < 2; i++) b[i] = (b3 ? a[2 + i] : a[i]) + __shfl_xor_sync(~0u, b3 ? a[i] : a[2 + i], 8);
  return (b2 ? b[1] : b[0]) + __shfl_xor_sync(~0u, b2 ? b[0] : b[1], 4);
}
__device__ __forceinline__ bool tag_bad(uint4 v, uint32_t tg) { return (((v.x ^ tg) | (v.y ^ tg) | (v.z ^ tg) | (v.w ^ tg)) & 3) != 0; }

__global__ void __launch_bounds__(512, 1) fused_kernel(const __grid_constant__ Params P) {
  extern __shared__ __align__(1024) uint8_t smem_raw[];
  const uint32_t sb = smem_u32(smem_raw);
  const int tid = threadIdx.x, lane = tid & 31;
  TS0_DECL();
  TS0_READ();
  {
    const int n = 16 * blockIdx.x + (lane & 15);
    const bf16* p = (lane < 16 ? P.x : P.wqkv) + (lane < 16 ? n * DM : (n >> 5) * (3 * DM) + DM + 64 * (n & 31));
    asm volatile("{\n.reg .pred p;\nsetp.lt.u32 p, %1, 32;\n@p prefetch.global.L2 [%0];\n}\n" :: "l"(p), "r"(tid));
  }
  const int cp = blockIdx.x >> 1, rank = blockIdx.x & 1;
  const int cr = cp < 4 ? 32 + 8 * cp : cp - 4 + max((cp * 37 - 1076) >> 8, 0);
  const int c = (cr & 62) + 64 * (cr & 1) + rank;
  const int m256 = c >> 4, nkv = c & 15, m128 = c >> 3, j = c & 7;
  if ((tid >> 7) == 2 && elect_one()) {
    if (tid >= 288) {
      const int w = (tid >> 5) - 9;
      #pragma unroll
      for (int i = 0; i < NB3; i++) mbar_init(sb + B_FULLKV + 8 + 8 * NB3 * w + 8 * i, w == 0 ? bar_count(1 + i) : w == 1 ? bar_count(1 + NB3 + i) : bar_count(1 + 2 * NB3 + i));
    } else {
      prefetch_map(&P.wkv); prefetch_map(&P.x128);
      mbar_init(sb + B_S0, 1); mbar_init(sb + B_FULLKV, 1);
      mbar_expect_tx(sb + B_S0, 32768);
      tma_4d(sb + 32768, &P.wkv, 0, 0, nkv, 1, sb + B_S0);
      tma_2d(sb, &P.x128, 0, 256 * m256, sb + B_S0);
      mbar_expect_tx(sb + B_FULLKV, 16384);
      tma_2d(sb + 16384, &P.x128, 0, 256 * m256 + 128, sb + B_FULLKV);
    }
    asm volatile("fence.mbarrier_init.release.cluster;" ::: "memory");
  }
  const int warp = __shfl_sync(~0u, tid >> 5, 0), wg = warp >> 2, wp = warp & 3;
  const int f = 16 * ((cr + 7) & 7) + 2 * (cr >> 3) + rank;
  const int ha = 4 * (nkv >> 1) + (nkv & 1);
  Scratch* const G = P.g;
  if ((sb & 0x3ffff) != SB0) asm volatile("trap;");
  __syncthreads();
  cluster_arrive();
  if (warp == 12) { TK(88 - 32); }
  if (NPRE > 1 && warp == 8 && elect_one()) {
    mbar_expect_tx(sb + B_FULLKV + 8, KV_STAGE);
    tma_4d(sb + KV_STAGE + 32768, &P.wkv, 0, 64, nkv, 1, sb + B_FULLKV + 8);
    tma_2d(sb + KV_STAGE, &P.x128, 64, 256 * m256, sb + B_FULLKV + 8);
    tma_2d(sb + KV_STAGE + 16384, &P.x128, 64, 256 * m256 + 128, sb + B_FULLKV + 8);
  }
  if (wg == 3) {
    asm volatile("setmaxnreg.dec.sync.aligned.u32 32;");
    cluster_wait();
    if (wp == 0) { TK(89 - 32); }
    const bool el = elect_one();
    const uint64_t ef = policy_evict_first(), en = policy_evict_normal();
    auto fetch_o = [&](const int t0) {
      const int sh = t0 & 1;
      uint32_t missing = ~0u;
      const uint32_t* hint = &G->oflag[(m128 * 6 + ((t0 + 1) & 6) + rank) * 32 + ((4 * (j & 6) + lane) & 31)];
      #pragma unroll FUN
      for (int i = 2 - 2 * sh; i < 8; i += 1 + sh) {
        const int blk = sh ? 6 + 2 * t0 + (i >> 1) : i, wrap = t0 == 3 ? 2 : (blk >= 5) + (blk >= 11), s = blk + 1 - 6 * wrap;
        flags_wait(missing, hint, (15u + 240u * sh) << (4 * i));
        if (blk > 5) mbar_wait(sb + B_EMPTY5 + 8 * s, wrap & 1);
        if (el) {
          tma_2d_mc_h(sb + s * R5 + rank * 8192, &P.o, 0, (m128 * 16 + t0 + 2 * (((j & 6) + i) & 7)) * 32 + 16 * rank, sb + B_GA + 16 * blk + 8 * rank, ef);
          if (KT == 2 && rank == KR2 && ((KM >> blk) & 1)) { TK(16 + blk); }
          if (KT != 2 && i == 2 - 2 * sh) TS(t0 == 0 ? (rank ? 4 : 12) : t0 == 3 ? (rank ? 31 : 10) : (rank ? 9 : 13));
        }
      }
    };
    if (wp == 0) {
      {
        if (S2D) { const uint32_t t0 = (uint32_t)clock(); while ((uint32_t)clock() - t0 < S2D) {} }
        #pragma unroll 1
        for (int kb = NPRE; kb < 16; kb++) {
          const uint32_t st = sb + (kb & 3) * KV_STAGE, fb = sb + B_FULLKV + 8 * (kb & 3);
          mbar_wait(fb + (B_EMPTYKV - B_FULLKV), ~(kb >> 2) & 1);
          if (el) {
            mbar_expect_tx(fb, KV_STAGE);
            tma_2d_mc(st + rank * 16384, &P.x128, 64 * kb, 256 * m256 + 128 * rank, fb);
            tma_4d_h(st + 32768, &P.wkv, 0, 64 * kb, nkv, 1, fb, ef);
          }
        }
        uint64_t ord = 0xf3120edcba987654ull;
        uint32_t so = 0, par = 1;
        #pragma unroll 1
        for (int i = 0; i < 16; i++) {
          const uint32_t st = sb + so * 4096, fb = sb + B_FULL5 + so;
          const int k0 = (64 * (uint32_t)ord + 128 * (j & 6)) & 960;
          mbar_wait(i < 5 ? sb + B_EMPTYKV + so - (i > 1 ? 8 : 0) : fb + (B_EMPTY5 - B_FULL5), par);
          if (el) {
            mbar_expect_tx(fb, R5);
            tma_2d_mc_h(st + rank * 8192, &P.x64, k0, 128 * m128 + 64 * rank, fb, i >= EFI ? ef : en);
            tma_3d_h(st + 16384, &P.wq, 0, k0, 2 * j, fb, ef);
          }
          ord >>= 4; so += 8;
          if (so == 40) { so = 0; par ^= 1; }
        }
        mbar_wait(sb + B_FULL5 + 8 + 8 * rank, 0); if (el) mbar_arrive(sb + B_R);
        mbar_wait(sb + B_FULL5 + 24 + 8 * rank, 0); if (el) mbar_arrive(sb + B_R1);
        #pragma unroll 1
        for (int i = 0; i < 19; i++) {
          const int row = i < 8 ? 128 * (((j & 6) + i) & 7) : 256 * (((j >> 1) + i) & 3) + 32 + 16 * (i & 4);
          mbar_wait(sb + B_EMPTY5 + so, par);
          if (el) {
            if (i < 16) {
              tma_5d_h(sb + so * 4096 + 16384, &P.wo[i >> 3], 128 * j, row, sb + B_GB + 8 * i, ef);
              tma_5d_h(sb + so * 4096 + 24576, &P.wo[i >> 3], 128 * j + 64, row, sb + B_GB + 8 * i, ef);
            } else mbar_arrive(sb + B_DR + 8 * (i - 16));
          }
          so += 8;
          if (so == 48) { so = 0; par ^= 1; }
        }
      }
    } else if (wp == 3) {
      const uint32_t t_start = (uint32_t)clock();
      mbar_wait(sb + B_S0, 0);
      if (el) {
        mbar_expect_tx(sb + B_W, 12288);
        #pragma unroll 1
        for (int i = 0; i < 6; i++) tma_2d(sb + (i == 0 ? OFF_WPHIK : i == 1 ? OFF_WPHIK1 : OFF_WPHIQ + 2048 * (i - 2)), &P.phi, 0, 32 * (i < 2 ? 2 * nkv + i : 4 * j + 2 * (i & 1) + ((i - 2) >> 1)), sb + B_W);
        prefetch_map(&P.x64); prefetch_map(&P.wq); prefetch_map(&P.wo[0]); prefetch_map(&P.wo[1]);
        prefetch_map(&P.o); prefetch_map(&P.wd); prefetch_map(&P.out); prefetch_map(&P.wg); prefetch_map(&P.wu);
      }
      #pragma unroll 1
      for (int i = 0; i < 8; i++) {
        if (lane < 16) st128_rlx(&G->cand[(m128 * 8 + i) * 512 + 64 * j + 4 * lane], ~0u, ~0u, ~0u, ~0u);
      }
      if (lane < 16) st128_rlx(&G->rstat[16 * c + lane], 0, 0, 0, 0);
      if (lane < 12) st128_rlx(&G->yacc[12 * c + lane], 0, 0, 0, 0);
      {
        const uint32_t nt = ld32_rlx(&G->epoch);
        if (lane < 8) { st128_rlx(&G->stats[16 * c + 2 * lane], nt, nt, nt, nt); st128_rlx(&G->csq[32 * c + 4 * lane], nt, nt, nt, nt); }
        if (lane < 4) { st128_rlx(&G->cskv[128 * nkv + 16 * m256 + 4 * lane], nt, nt, nt, nt); st128_rlx(&G->oset[16 * c + 4 * lane], nt, nt, nt, nt); }
      }
      if (lane < 2 * KR) st128_rlx(&G->key[(KR * j + (lane >> 1)) * 128 + m128 * 8 + 4 * (lane & 1)], 0, 0, 0, 0);
      if (c < 32) {
        #pragma unroll 1
        for (int i = lane; i < KVP; i += 32) st128_rlx(&G->kvacc[(ha + 2 * m256) * KVP + i], 0, 0, 0, 0);
      }
      fence_gpu();
      bar_arrive(NB_ZERO, 160);
      TS0_WRITE();
      if (el) {
        #pragma unroll 1
        for (int i = PF_I0; i < ((XP & 4) ? 0 : 30); i++) {
          while ((uint32_t)clock() - t_start < (uint32_t)(PF_T0 + PF_DT * (i - PF_I0) + PF_ST * f)) __nanosleep(64);
          if (i < 4) { bulk_prefetch(P.wqkv + (size_t)(256 * i + c) * (3 * DM), 2048); bulk_prefetch(P.wqkv + (size_t)(256 * i + 128 + c) * (3 * DM), 2048); }
          else if (i < 6) bulk_prefetch(P.wo_p + (size_t)c * 8192 + (i - 4) * 4096, 8192);
          else if ((TMASK >> (i - 6)) & 1) {
            const int k = i - 6;
            if (f < NFFN) {
              if (k < 16) {
                #pragma unroll 1
                for (int e = 0; e < 4; e++) tma_2d(sb + OFF_T, rank ? &P.tu : &P.tg, 32 * (f & ~1), 64 * k + 16 * e, sb + B_T);
              } else { tma_2d(sb + OFF_T, &P.td, 0, 256 * f + 32 * (k - 16), sb + B_T); tma_2d(sb + OFF_T, &P.td, 0, 256 * f + 32 * (k - 16) + 16, sb + B_T); }
            }
          }
          else if (!((PMASK >> (i - 6)) & 1)) {}
          else if (i < 22) bulk_prefetch(((i & 1) ? P.wu_p : P.wg_p) + (size_t)((i - 6) >> 1) * 458752 + c * 3584, 7168);
          else bulk_prefetch(P.wd_p + (size_t)(i - 22) * 458752 + c * 3584, 7168);
        }
      }
      __syncwarp();
      mbar_wait2(sb + B_OS, 0, sb + B_RX, 0);
      mbar_wait2(sb + B_EMPTY5 + 24, 0, sb + B_EMPTY5 + 32, 0);
      mbar_wait2(sb + B_EMPTY5 + 40, 0, sb + B_EMPTY5, 1);
      fetch_o(0);
      fetch_o(3);
    } else {
      const int half = wp - 1;
      const uint32_t ep1 = ld32_rlx(&G->epoch) + 1, tg = ep1 & 3;
      {
        uint32_t it = 0;
        sts128(sb + OFF_ONES + half * 512 + lane * 16, 0x3f803f80u, 0x3f803f80u, 0x3f803f80u, 0x3f803f80u);
        if (lane < 9) { const uint32_t v = (lane & 1) ? 0 : 0x3f803f80u; sts128(sb + OFF_SEL + lane * 16, v, v, v, v); }
        auto reset_o = [&](int i0, int i1, uint32_t dt) {
          uint32_t t0 = (uint32_t)clock();
          #pragma unroll 1
          for (int i = i0; i < i1; i++) {
            if (!(XP & 2)) st128_rlx(G->o + (m128 * 16 + 2 * j + half) * 8192 + 256 * i + 8 * lane, ~0u, ~0u, ~0u, ~0u);
            while ((uint32_t)clock() - t0 < dt) __nanosleep(40);
            t0 += dt;
          }
        };
        if (el) {
          #pragma unroll 1
          for (int i = 24 * half; i < 24 * half + 24; i++) { mbar_init(sb + B_GB + 8 * i, 1); mbar_expect_tx(sb + B_GB + 8 * i, i < 16 ? 16384 : 8192); }
          asm volatile("fence.mbarrier_init.release.cluster;" ::: "memory");
        }
        mbar_wait(sb + B_S0, 0);
        reset_o(0, RS_N, RS_D1);
        bar_sync(NB_PUB, 192);
        const uint4* src = reinterpret_cast<const uint4*>(&G->stats[256 * m256 + 128 * half]) + lane;
        const uint4* srk = reinterpret_cast<const uint4*>(&G->cskv[128 * nkv]) + lane;
        uint4 v0, v1, vk;
        it = 0;
        do { v0 = ld128_rlx(src); v1 = ld128_rlx(src + 32); vk = ld128_rlx(srk); }
        while ((tag_bad(v0, tg) || tag_bad(v1, tg) || tag_bad(vk, tg)) && ++it < POLL_LIMIT);
        fence_acquire_gpu();
        if (half) put_colsums(sb + OFF_BXK, lane, untag(vk.x), untag(vk.y), untag(vk.z), untag(vk.w));
        #pragma unroll
        for (int i = 0; i < 2; i++) {
          const uint4 v = i ? v1 : v0;
          uint32_t hi, lo;
          split_bf16(-0.5f * untag(v.x), -0.5f * untag(v.z), hi, lo);
          const uint32_t h0 = __byte_perm(hi, hi, 0x1010), h1 = __byte_perm(hi, hi, 0x3232), l0 = __byte_perm(lo, lo, 0x1010), l1 = __byte_perm(lo, lo, 0x3232);
          const uint32_t a = sb + OFF_AXK + half * 2048 + i * 1024 + lane * 32;
          sts128(a, h0, l0, 0, 0); sts128(a + 16, h1, l1, 0, 0);
          sts64(sb + OFF_RS256 + half * 512 + i * 256 + lane * 8, v.y & ~3u, v.w & ~3u);
          if (half == (m128 & 1)) {
            const uint32_t aq = sb + OFF_AXQ + i * 1024 + lane * 32;
            sts128(aq, h0, l0, 0, 0); sts128(aq + 16, h1, l1, 0, 0);
            sts64(sb + OFF_RSQ + i * 256 + lane * 8, v.y & ~3u, v.w & ~3u);
          }
        }
        fence_async_smem();
        __syncwarp();
        if (el) { sts32(sb + OFF_EP, ep1); mbar_arrive(sb + B_AUX); }
        reset_o(RS_N, 32, RS_D2);
        if (half == 0 && rank == 0 && lane < 12) st128_rlx(&G->oflag[(m128 * 6 + (lane >> 1)) * 32 + 4 * j + 4 * (lane & 1)], 0, 0, 0, 0);
        fence_gpu();
        __syncwarp();
        if (el) { st32_rlx(&G->oset[16 * c + 8 * half], ep1); if (half) mbar_arrive(sb + B_AUXQ); }
        if (!half) {
          const uint4* src = reinterpret_cast<const uint4*>(&G->csq[128 * j]) + lane;
          uint4 v0, v1, v2, v3;
          do { v0 = ld128_rlx(src); v1 = ld128_rlx(src + DM / 4); v2 = ld128_rlx(src + DM / 2); v3 = ld128_rlx(src + 3 * DM / 4); }
          while ((tag_bad(v0, tg) || tag_bad(v1, tg) || tag_bad(v2, tg) || tag_bad(v3, tg)) && ++it < POLL_LIMIT);
          put_colsums(sb + OFF_BXQ, lane, (untag(v0.x) + untag(v1.x)) + (untag(v2.x) + untag(v3.x)), (untag(v0.y) + untag(v1.y)) + (untag(v2.y) + untag(v3.y)),
                      (untag(v0.z) + untag(v1.z)) + (untag(v2.z) + untag(v3.z)), (untag(v0.w) + untag(v1.w)) + (untag(v2.w) + untag(v3.w)));
          fence_async_smem();
          __syncwarp();
          if (el) mbar_arrive(sb + B_AUXQ);
        }
      }
      if (half == 0) {
        for (uint32_t it = 0; __any_sync(~0u, ld32_rlx(&G->oset[m128 * 128 + 8 * (lane & 15)]) != ep1) && it < POLL_LIMIT; it++) {}
        fence_acquire_gpu();
        if (el) mbar_arrive(sb + B_OS);
      }
      if (!half) {
        #pragma unroll 1
        for (int hh = 0; hh < 2; hh++) {
          const uint32_t src = sb + (1 + rank) * R5 + hh * 8192, fa = sb + B_GA + 16 * rank + 8 * hh;
          mbar_wait2(sb + B_UO + 8 * hh, 0, sb + B_GB + 8 * rank, 0);
          if (el) bulk_s2peer(mapa(src, rank ^ 1), src, 8192, mapa(fa, rank ^ 1));
        }
        fetch_o(1);
      }
      else if (f < NFFN_L) {
        mbar_wait(sb + B_UO + 24, 0);
        mbar_wait2(sb + B_UO, 0, sb + B_UO + 8, 0);
        uint32_t t0 = (uint32_t)clock();
        while ((uint32_t)clock() - t0 < (uint32_t)FF_T0) __nanosleep(32);
        t0 -= FF_DT;
        #pragma unroll 1
        for (int i = 0; i < 12; i++) {
          const int e = (FF_ORD >> (4 * i)) & 15;
          const uint32_t dst = sb + 16384 * ((FF_SLOT >> (4 * e)) & 15), fb = sb + B_F + 8 * e;
          if (i >= 2) mbar_wait(sb + B_WC + 8 * ((0x100066553244ull >> (4 * e)) & 15), 0);
          while ((uint32_t)clock() - t0 < (uint32_t)(i < FF_N ? FF_DT : FF_D2)) __nanosleep(32);
          t0 = (uint32_t)clock();
          if (i < 8) { TK(48 + i); }
          if (el) {
            mbar_expect_tx(fb, 16384);
            if (e >= 8) tma_3d_h(dst, &P.wd, 0, 32 * f, 4 * e - 32, fb, ef);
            else { tma_2d_h(dst, &P.wg, 32 * f, 128 * e, fb, ef); tma_2d_h(dst + 8192, &P.wu, 32 * f, 128 * e, fb, ef); }
          }
        }
      }
      __syncwarp();
    }
    if (wp & 1) {
      __syncwarp();
      mbar_wait(sb + B_OUT + 8 * (wp >> 1), 0);
      uint32_t t0 = (uint32_t)clock() + OUT_0;
      #pragma unroll 1
      for (int i = 0; i < 8; i++) {
        while ((int32_t)((uint32_t)clock() - t0) < 0) __nanosleep(20);
        if (el) tma_store_2d(&P.out, 128 * j + 64 * (i & 1), 128 * m128 + 32 * (wp & 2) + 8 * (i & 6), sb + OFF_OUT + (i & 1) * 16384 + (wp & 2) * 4096 + (i & 6) * 1024, ef);
        t0 += OUT_D;
      }
      if (el) { bulk_commit(); bulk_wait_all(); fence_async_global(); mbar_arrive(sb + B_SD); TS(19); }
    }
    __syncwarp();
    cluster_arrive(); cluster_wait();
    return;
  }

  asm volatile("setmaxnreg.inc.sync.aligned.u32 160;");
  cluster_wait();
  const int t = tid & 127, g = lane >> 2;
  const uint32_t sa = (16 * wp + (lane & 15)) * 128 + (((lane >> 4) ^ (lane & 7)) << 4);

  if (wg == 2) {
    float s[2] = {0.f, 0.f}, s2[2] = {0.f, 0.f}, ck[8] = {0.f, 0.f, 0.f, 0.f, 0.f, 0.f, 0.f, 0.f}, cs[8] = {0.f, 0.f, 0.f, 0.f, 0.f, 0.f, 0.f, 0.f};
    const uint32_t ebr = mapa(sb + B_EMPTYKV, lane & 1), tg = (ld32_rlx(&G->epoch) + 1) & 3;
    auto addx = [&](const uint4 v) {
      const uint32_t w[4] = {v.x, v.y, v.z, v.w};
      #pragma unroll
      for (int e = 0; e < 4; e++) { const float a = bf_lo(w[e]), d = bf_hi(w[e]); s[0] += a; s[1] += d; s2[0] = fmaf(a, a, s2[0]); s2[1] = fmaf(d, d, s2[1]); }
    };
    auto addc = [&](const uint4 v, float (&o)[8]) {
      o[0] += bf_lo(v.x); o[1] += bf_hi(v.x); o[2] += bf_lo(v.y); o[3] += bf_hi(v.y); o[4] += bf_lo(v.z); o[5] += bf_hi(v.z); o[6] += bf_lo(v.w); o[7] += bf_hi(v.w);
    };
    {
      const uint32_t ra = (16 * nkv + (t >> 3)) * 128 + (t & 7) * 16;
      const uint32_t ca = 32768 + (m256 >> 2) * 8192 + (t >> 1) * 128 + (((2 * (m256 & 3) + (t & 1)) ^ ((t >> 1) & 7)) << 4);
      int rd = 0;
      mbar_wait(sb + B_S0, 0);
      #pragma unroll 1
      for (int kb = 0; kb < 10; kb++) {
        const uint32_t st = sb + (kb & 3) * KV_STAGE;
        mbar_wait(sb + B_FULLKV + 8 * (kb & 3), (kb >> 2) & 1);
        const uint4 x0 = lds128(st + ra), w0 = lds128(st + ca);
        if (!(XP & 1)) { addx(x0); addc(w0, ck); } else s[0] += __uint_as_float(x0.x ^ w0.x);
        __syncwarp();
        if (lane < 2) mbar_arrive_remote(ebr + 8 * (kb & 3), 1);
        if ((SKM >> kb) & 1) {
          if (rd) {
            mbar_wait(sb + B_G, (rd - 1) & 1);
            const uint32_t a = sb + OFF_G + (t >> 3) * 256 + (t & 7) * 16;
            const uint4 x1 = lds128(a), x2 = lds128(a + 128), w1 = lds128(sb + OFF_G + 4096 + t * 16), w2 = lds128(sb + OFF_G + 6144 + t * 16);
            addx(x1); addx(x2); addc(w1, ck); addc(w2, ck);
            bar_sync(NB_WG2, 128);
          }
          if (wp == 0 && elect_one()) {
            mbar_expect_tx(sb + B_G, 8192);
            if (rd < 3) {
              tma_2d(sb + OFF_G, &P.xs, 640 + 128 * rd, 256 * m256 + 16 * nkv, sb + B_G);
              tma_2d(sb + OFF_G + 4096, &P.ws, (1 + (m256 >> 2)) * DM + 64 * nkv + 16 * (m256 & 3), 640 + 128 * rd, sb + B_G);
            } else tma_2d(sb + OFF_G, &P.qs, 32 * (c & 31), 256 * (c >> 5), sb + B_G);
          }
          rd++;
        }
      }
    }
    TK(82);
    const uint32_t scr = sb + OFF_WR;
    float sx = s[0] + s[1], sq = s2[0] + s2[1];
    #pragma unroll
    for (int o = 1; o < 8; o <<= 1) { sx += __shfl_xor_sync(~0u, sx, o); sq += __shfl_xor_sync(~0u, sq, o); }
    float v = reduce8(ck, lane);
    v += __shfl_xor_sync(~0u, v, 2);
    if (!(lane & 2)) stsf(scr + (wp * 16 + 8 * (lane & 1) + (lane >> 2)) * 4, v);

    bar_sync(NB_ZERO, 160);
    if ((lane & 7) == 0) {
      const float mean = sx * (1.f / DM);
      st64_rlx(&G->stats[256 * m256 + 16 * nkv + (t >> 3)], tagw(mean, tg), tagw(rsqrtf(fmaxf(sq * (1.f / DM) - mean * mean, 0.f) + 1e-5f), tg));
    }
    if (wp == 1 && lane < 16) {
      const uint32_t a = scr + lane * 4;
      st32_rlx(&G->cskv[128 * nkv + 16 * m256 + lane], tagw((ldsf(a) + ldsf(a + 64)) + (ldsf(a + 128) + ldsf(a + 192)), tg));
    }
    __syncwarp();
    bar_arrive(NB_PUB, 192);
    TSW(23);
    const uint4 wv = ld128_keep(P.wr + t * 8);
    #pragma unroll 1
    for (int i = 0; i < 2; i++) {
      mbar_wait(sb + B_G, i ^ 1);
      const uint32_t a = sb + OFF_G + t * 16;
      const uint4 u0 = lds128(a), u1 = lds128(a + 2048), u2 = lds128(a + 4096), u3 = lds128(a + 6144);
      addc(u0, cs); addc(u1, cs); addc(u2, cs); addc(u3, cs);
      bar_sync(NB_WG2, 128);
      if (i == 0 && wp == 0 && elect_one()) { mbar_expect_tx(sb + B_G, 8192); tma_2d(sb + OFF_G, &P.qs, 32 * (c & 31), 256 * (c >> 5) + 128, sb + B_G); }
    }
    float sw = (bf_lo(wv.x) + bf_hi(wv.x)) + (bf_lo(wv.y) + bf_hi(wv.y)) + (bf_lo(wv.z) + bf_hi(wv.z)) + (bf_lo(wv.w) + bf_hi(wv.w));
    #pragma unroll
    for (int o = 16; o; o >>= 1) sw += __shfl_xor_sync(~0u, sw, o);
    if (lane == 0) stsf(sb + OFF_SUMWR + wp * 4, sw);
    if ((t >> 4) == j) {
      const uint32_t a = sb + OFF_WR + (t & 15) * 32;
      sts128(a, wv.x << 16, wv.x & 0xffff0000u, wv.y << 16, wv.y & 0xffff0000u);
      sts128(a + 16, wv.z << 16, wv.z & 0xffff0000u, wv.w << 16, wv.w & 0xffff0000u);
    }
    v = reduce8(cs, lane);
    stsf(sb + OFF_G + (wp * 32 + 8 * (lane & 3) + (lane >> 2)) * 4, v);
    bar_sync(NB_WG2, 128);
    if (wp == 0) {
      const uint32_t a = sb + OFF_G + lane * 4, cq = tagw((ldsf(a) + ldsf(a + 128)) + (ldsf(a + 256) + ldsf(a + 384)), tg);
      st32_rlx(&G->csq[(c >> 5) * DM + 32 * (c & 31) + lane], cq);
      if (lane == 0) mbar_arrive_at(sb + B_W, rank, (cq & P.zero) + 1);
    }
  }

  uint32_t xr[32];
  {
    const bool isq = wg == 2;
    float acc[2][64];
    {
      const uint32_t emptyb = mapa(sb + (isq ? B_EMPTY5 : B_EMPTYKV), t & 1);
      auto correct = [&](uint32_t xa, uint32_t xb) {
        wg_fence();
        wgmma_sa_n128<0, 1, H0, H0>(acc[0], dlo(SB0, 0) + (xa >> 4), dlo(SB0, 0) + (xb >> 4));
        wgmma_sa_n128<0, 1, H0, H0>(acc[1], dlo(SB0, 0) + (xa >> 4) + 64, dlo(SB0, 0) + (xb >> 4));
        wg_commit();
      };
      if (!isq) {
        mbar_wait(sb + B_S0, 0);
        if (wg) mbar_wait(sb + B_FULLKV, 0);
        if (wg == 0) { TSW(2); }
        #pragma unroll 1
        for (int kb = 0; kb < 16; kb++) {
          if (!KT && wg == 0) { TK(kb); }
          const uint32_t da = dlo(SB0, 16) + wg * 1024 + (kb & 3) * (KV_STAGE >> 4), db = dlo(SB0 + 32768, 8192) + (kb & 3) * (KV_STAGE >> 4);
          wg_fence();
          #pragma unroll
          for (int k = 0; k < 4; k++) {
            wgmma_ss_n128<0, 1, H128, H128>(acc[0], da + 2 * k, db + 128 * k, k > 0 || kb != 0);
            wgmma_ss_n128<0, 1, H128, H128>(acc[1], da + 512 + 2 * k, db + 128 * k, k > 0 || kb != 0);
          }
          wg_commit();
          wg_wait<1>();
          if (kb > 0 && t < 2) mbar_arrive_remote(emptyb + 8 * ((kb - 1) & 3), kb > 10 ? 3 : 1);
          if (kb < 15) mbar_wait(sb + B_FULLKV + 8 * ((kb + 1) & 3), ((kb + 1) >> 2) & 1);
          if (kb == 0) mbar_wait(sb + B_FULLKV, 0);
          if (kb == 15 - LAG && wg == 1) bar_sync(NB_LAG, 256);
        }
        bar_arrive(wg ? NB_QGO : NB_LAG, 256);
        mbar_wait(sb + B_AUX, 0);
        correct(OFF_AXK + wg * 2048, OFF_BXK);
        wg_wait<0>();
        if (t < 2) mbar_arrive_remote(emptyb + 24, 3);
        if (wg == 0) { TSW(3); }
        fence_regs(acc[0]); fence_regs(acc[1]);
      const uint32_t stg = sb + OFF_X + (1 - wg) * 24576;
      const uint32_t va = stg + 16384 + (16 * wp + (lane & 15)) * 64 + (((lane >> 4) ^ ((lane >> 1) & 3)) << 4);
      const uint32_t ra = sb + OFF_RS256 + (128 * wg + 16 * wp + g) * 4;
      const float rs[4] = {ldsf(ra), ldsf(ra + 32), ldsf(ra + 256), ldsf(ra + 288)};
      float p[2][16];
      uint32_t vf[16], kf[2][16];
      auto project = [&](const uint32_t (&f)[16], uint32_t db) {
        wg_fence();
        #pragma unroll
        for (int i = 0; i < 2; i++) {
          wgmma_rs_n32<1, H64>(p[i], f[8*i], f[8*i+1], f[8*i+2], f[8*i+3], db, 0);
          wgmma_ra_n32<1, H64>(p[i], f[8*i+4], f[8*i+5], f[8*i+6], f[8*i+7], db + 64);
        }
        wg_commit();
      };
      auto fold = [&](uint32_t (&f)[16], int col, float sc) {
        #pragma unroll
        for (int i = 0; i < 16; i++) {
          const float r = rs[2 * (i >> 3) + (i & 1)] * sc;
          f[i] = pack_bf16(acc[i >> 3][col + 2 * (i & 7)] * r, acc[i >> 3][col + 2 * (i & 7) + 1] * r);
          asm volatile("" : "+r"(f[i]));
        }
      };
      auto put_v = [&](const uint32_t (&f)[16]) {
        #pragma unroll
        for (int k = 0; k < 4; k++) stsm4((va ^ ((k & 1) << 5)) + (k >> 1) * 4096, f[4*k], f[4*k+1], f[4*k+2], f[4*k+3]);
      };
      KK(0);
      fold(vf, 48, 1.f);
      mbar_wait(sb + B_W, 0);
      fold(kf[0], 0, LOG2E);
      #pragma unroll
      for (int i = 0; i < 32; i++) p[i >> 4][i & 15] = acc[i >> 4][i & 15];
      project(kf[0], dlo(SB0 + OFF_WPHIK, 16));
      mbar_wait(sb + B_W, 0);
      KK(1);
      {
        uint32_t v0[16];
        fold(kf[1], 16, LOG2E);
        fold(v0, 32, 1.f);
        if (wg == 1) bar_sync(NB_DN, 256);
        put_v(v0);
      }
      wg_wait<0>();
      fence_regs(p[0]); fence_regs(p[1]);
      if (wg == 1) bar_arrive(NB_WG01, 256);
      KK(2);
      #pragma unroll 1
      for (int h = 0; h < 2; h++) {
        uint32_t ph[4][8];
        float rsum[2][4];
        dual_exp2<PRK & 1>(p[0], ph[0], ph[1]); dual_exp2<(PRK >> 1)>(p[1], ph[2], ph[3]);
        row_sums(rsum, ph, dlo(SB0 + OFF_SEL, 16));
        KK(3 + 6 * h);
        if (wg == 0 && h == 0) { bar_arrive(NB_DN, 256); bar_sync(NB_WG01, 256); }
        if (h == 1) {
          if (wg == 1) bar_sync(NB_DN, 256);
          put_v(vf);
        }
        wg_wait<0>();
        KK(4 + 6 * h);
        fence_regs(rsum[0]); fence_regs(rsum[1]);
        if (!(XP & 8) && __builtin_expect(__any_sync(~0u, !((rsum[0][0] + rsum[0][1]) + (rsum[0][2] + rsum[0][3]) + (rsum[1][0] + rsum[1][1]) + (rsum[1][2] + rsum[1][3]) < EXP_LIM)), 0)) {
          dual_exp2_shifted(p, ph);
          #pragma unroll
          for (int i = 0; i < 8; i++) {
            const uint32_t* f = &ph[i >> 1][i & 1];
            float a = (bf_lo(f[0]) + bf_hi(f[0])) + (bf_lo(f[2]) + bf_hi(f[2])) + (bf_lo(f[4]) + bf_hi(f[4])) + (bf_lo(f[6]) + bf_hi(f[6]));
            a += __shfl_xor_sync(~0u, a, 1);
            rsum[i >> 2][2 * (i & 1) + ((i >> 1) & 1)] = a + __shfl_xor_sync(~0u, a, 2);
          }
        }
        if (h == 0) project(kf[1], dlo(SB0 + OFF_WPHIK1, 16));
        normalize(ph, rsum);
        #pragma unroll
        for (int i = 0; i < 8; i++) {
          const uint32_t* f = &ph[i >> 1][4 * (i & 1)];
          stsm4(((stg + sa) ^ ((i & 3) << 5)) + (i >> 2) * 8192, f[0], f[1], f[2], f[3]);
        }
        KK(5 + 6 * h);
        fence_async_smem();
        KK(6 + 6 * h);
        if (wg != h) { KK(7 + 6 * h); }
        if (wg == h) {
          float kv[20];
          #pragma unroll
          for (int w = 0; w < 2; w++) {
            const uint32_t da = dlo(SB0 + OFF_X, 16) + (h ^ w ^ 1) * 1536, db = dlo(SB0 + OFF_X + 16384, OFF_ONES - OFF_X - 16384) - (h ^ w ^ 1) * (1536 * 65535);
            if (w) bar_sync(NB_ST, 256); else bar_sync(NB_L0 + h, 128);
            wg_fence();
            #pragma unroll
            for (int k = 0; k < 8; k++) {
              if (k == 0 && w == 0) wgmma_sz_n40<1, 1, H128, H64>(kv, da, db);
              else wgmma_sa_n40<1, 1, H128, H64>(kv, da + k * 128, db - k * (64 * 65535));
            }
            wg_commit();
          }
          float4* dst = &G->kvacc[(ha + 2 * h) * KVP + t];
          wg_wait<0>();
          fence_regs(kv);
          KK(7 + 6 * h);
          if (h == 0) bar_arrive(NB_DN, 256); else if (t < 2) { mbar_arrive_at(sb + B_EMPTY5 + 40, t, 2); if (t == 0) mbar_arrive(sb + B_KD); }
          kv[17] = kv[18];
          #pragma unroll
          for (int i = 0; i < 6; i++) red_add_f32x4(dst + 128 * i, kv[3*i], kv[3*i+1], kv[3*i+2], 1.f);
          TSW(29 + h);
        } else bar_arrive(NB_ST, 256);
        wg_wait<0>();
        KK(8 + 6 * h);
        fence_regs(p[0]); fence_regs(p[1]);
      }
      #pragma unroll
      for (int i = 0; i < 32; i++) asm volatile("mov.b32 %0, 0;" : "=r"(xr[i]));
      } else {
        uint32_t so = 0, po = 0, par = 0;
        mbar_wait(sb + B_FULL5, 0);
        bar_sync(NB_QGO, 256);
        TSW(11);
        #pragma unroll 1
        for (int kb = 0; kb < 16 - ML; kb++) {
          if (KT != 2) { TK(16 + kb); }
          const uint32_t da = dlo(SB0, 16) + so * 256, db = dlo(SB0 + 16384, 8192) + so * 256;
          #pragma unroll
          for (int k = 0; k < 4; k++) {
            wg_fence();
            wgmma_ss_n128<0, 1, H128, H128>(acc[0], da + 2 * k, db + 128 * k, k > 0 || kb != 0);
            wgmma_ss_n128<0, 1, H128, H128>(acc[1], da + 512 + 2 * k, db + 128 * k, k > 0 || kb != 0);
            wg_commit();
            if (k == 1 && kb > 0 && t < 2) mbar_arrive_remote(emptyb + po, 2);
            if (k == 3) {
              po = so; so += 8;
              if (so == 40) { so = 0; par ^= 1; }
              mbar_wait(sb + B_FULL5 + so, par);
            }
            if ((QW >> k) & 1) wg_wait<2>(); else wg_wait<1>();
          }
        }
        auto block = [&](const int kb, const int i) {
          wg_fence();
          #pragma unroll
          for (int k = 0; k < 4; k++) wgmma_sa_n128<0, 1, H128, H128>(acc[i], dlo(SB0, 16) + (kb % 5) * 2048 + 512 * i + 2 * k, dlo(SB0 + 16384, 8192) + (kb % 5) * 2048 + 128 * k);
          wg_commit();
        };
        auto hand_over = [&](const int i) {
          const uint32_t ta = sb + (1 + rank) * R5 + sa + i * 8192;
          #pragma unroll
          for (int k = 0; k < 4; k++) {
            const float* a = &acc[i][32 * (k >> 1) + 8 * (k & 1)];
            stsm4(ta ^ (k << 5), pack_bf16(a[0], a[1]), pack_bf16(a[2], a[3]), pack_bf16(a[4], a[5]), pack_bf16(a[6], a[7]));
          }
        };
        mbar_wait2(sb + B_AUXQ, 0, sb + B_OS, 0);
        correct(OFF_AXQ, OFF_BXQ);
        #pragma unroll
        for (int kb = 16 - ML; kb < 16; kb++) {
          if (KT != 2) { TK(16 + kb); }
          block(kb, 0);
          if (kb < 15) mbar_wait(sb + B_FULL5 + 8 * ((kb + 1) % 5), ((kb + 1) / 5) & 1);
          if (kb == 16 - ML) wg_wait<2>(); else if (!H3) wg_wait<1>();
          if (kb == 16 - ML && t < 2) mbar_arrive_remote(emptyb + 8 * ((kb - 1) % 5), 2);
        }
        mbar_wait(sb + B_RC, 0);
        block(16 - ML, 1);
        if (H2) { block(17 - ML, 1); wg_wait<2>(); } else wg_wait<1>();
        fence_regs(acc[0]);
        hand_over(0);
        if (!H2) block(17 - ML, 1);
        fence_async_smem();
        bar_arrive(NB_Q0, 256);
        TSW(1);
        #pragma unroll
        for (int kb = 18 - ML; kb <= 16; kb++) {
          wg_wait<1>();
          if (t < 2) mbar_arrive_remote(emptyb + 8 * ((kb - 2) % 5), 2);
          if (kb < 16) block(kb, 1);
        }
        mbar_wait(sb + B_RC + 8, 0);
        wg_wait<0>();
        if (t < 2) mbar_arrive_remote(emptyb, 2);
        TSW(8);
        fence_regs(acc[1]);
        hand_over(1);
        fence_async_smem();
        bar_arrive(NB_Q0 + 1, 256);
        #pragma unroll
        for (int i = 0; i < 32; i++) { const float* a = &acc[(i >> 3) & 1][16 + 32 * (i >> 4) + 2 * (i & 7)]; xr[i] = pack_bf16(a[0], a[1]); }
        TSW(26);
      }
    }
    float p[2][16];
    #pragma unroll
    for (int i = 0; i < 32; i++) asm volatile("mov.b32 %0, 0;" : "=f"(p[i >> 4][i & 15]));
    auto project_r = [&](int w) {
      wg_fence();
      #pragma unroll
      for (int h = 0; h < 2; h++) {
        wgmma_rs_n32<1, H64>(p[h], xr[8*h], xr[8*h+1], xr[8*h+2], xr[8*h+3], dlo(SB0 + OFF_WPHIQ, 16) + 128 * w, 0);
        wgmma_ra_n32<1, H64>(p[h], xr[8*h+4], xr[8*h+5], xr[8*h+6], xr[8*h+7], dlo(SB0 + OFF_WPHIQ, 16) + 128 * w + 64);
      }
      wg_commit();
    };
    auto capture = [&](const int i) {
      if (!i || CAPL != 2) mbar_wait(sb + (i ? B_R1 : B_R), 0);
      #pragma unroll
      for (int k = 0; k < 4; k++) ldsm4(((sb + (1 + rank) * R5 + wg * 8192 + sa) ^ (k << 5)) + i * 2 * R5, xr[16*i+4*k], xr[16*i+4*k+1], xr[16*i+4*k+2], xr[16*i+4*k+3]);
      const uint32_t one = (((xr[16*i] | xr[16*i+4]) | (xr[16*i+8] | xr[16*i+12])) & P.zero) + 1;
      if (lane == 0) mbar_arrive_at(sb + (i ? B_RX : B_RC + 8 * wg), i ? wg : rank, one);
    };
    const uint32_t rq = sb + OFF_RSQ + (16 * wp + g) * 4 + 256 * (wg & 1), rb = rq + 128 * (wg & 2);
    const float cc[2][2] = {{ldsf(rq) * LOG2E, ldsf(rq + 32) * LOG2E}, {ldsf(rb) * LOG2E, ldsf(rb + 32) * LOG2E}};
    {
      const uint4* src = reinterpret_cast<const uint4*>(&G->kvacc[(4 * j + wg) * KVP + t]);
      uint4 v[12];
      #pragma unroll
      for (int i = 0; i < 12; i++) v[i] = i < 6 || isq ? ld128_rlx(src + 128 * i) : make_uint4(0, 0, 0, 0x41000000u);
      if (isq) {
        project_r(2);
        wg_wait<0>();
        #pragma unroll
        for (int i = 0; i < 16; i++) xr[i] = xr[16 + i];
      } else {
        capture(0);
        if (CAPL == 0) capture(1);
      }
      #pragma unroll 1
      for (uint32_t it = 0; it < POLL_LIMIT; it++) {
        uint32_t bad = 0;
        #pragma unroll
        for (int i = 0; i < 12; i++) bad |= v[i].w ^ 0x41000000u;
        if (!__any_sync(~0u, bad != 0)) break;
        #pragma unroll
        for (int i = 0; i < 12; i++) if (i < 6 || isq) v[i] = ld128_rlx(src + 128 * i);
      }
      mbar_wait(sb + B_KD, 0);
      #pragma unroll
      for (int e = 0; e < 2; e++) {
        if (e == 0 || isq) {
          float f[18];
          #pragma unroll
          for (int i = 0; i < 6; i++) { f[3*i] = __uint_as_float(v[6*e+i].x); f[3*i+1] = __uint_as_float(v[6*e+i].y); f[3*i+2] = __uint_as_float(v[6*e+i].z); }
          const uint32_t ka = sb + OFF_KVZ + (wg + e) * 5120 + wp * 1280 + lane * 16;
          stsm4(ka, pack_bf16(f[0], f[1]), pack_bf16(f[2], f[3]), pack_bf16(f[4], f[5]), pack_bf16(f[6], f[7]));
          stsm4(ka + 512, pack_bf16(f[8], f[9]), pack_bf16(f[10], f[11]), pack_bf16(f[12], f[13]), pack_bf16(f[14], f[15]));
          stsm2(ka + 1024, pack_bf16(f[16], 1.f), pack_bf16(f[17], 1.f));
        }
      }
    }
    fence_async_smem();
    if (wg == 1) bar_arrive(NB_DN, 256);
    if (CAPL == 1 && !isq) capture(1);
    TSW(wg == 0 ? 5 : wg == 1 ? 25 : 6);
    #pragma unroll 1
    for (int e = wg; e < wg + 1 + (wg >> 1); e++) {
      const int half = e >> 1, hh = e & 1, turn = e;
      const uint32_t ao = (1 + rank) * R5 + hh * 8192;
      uint32_t ph[4][8];
      #pragma unroll
      for (int i = 0; i < 32; i++) asm volatile("mov.b32 %0, 0;" : "=r"(ph[i >> 3][i & 7]));
      uint32_t shifted = 0;
      asm volatile("" : "+r"(shifted));
      #pragma unroll 1
      for (;;) {
        if (!(XP & 16) && shifted) dual_exp2_shifted(p, ph);
        uint32_t first = (shifted ^ 1) & !isq;
        asm volatile("" : "+r"(first));
        if (first) {
          if (wg == 0) { TSW(7); }
          bar_sync(NB_Q0 + wg, 256);
          const uint32_t da = dlo(SB0, 16) + (ao >> 4), db = dlo(SB0 + OFF_WPHIQ, 16);
          wg_fence();
          #pragma unroll
          for (int h = 0; h < 2; h++) {
            wgmma_ss_n32<0, 1, H128, H64>(p[h], da + 4 * h, db + 128 * h, 0);
            wgmma_sa_n32<0, 1, H128, H64>(p[h], da + 4 * h + 2, db + 128 * h + 64);
          }
          wg_commit();
          if (CAPL == 2) capture(1);
          wg_wait<0>();
        }
        fence_regs(p[0]); fence_regs(p[1]);
        uint32_t again = shifted;
        asm volatile("" : "+r"(again));
        if (again) break;
        float s2[4] = {0.f, 0.f, 0.f, 0.f};
        #pragma unroll
        for (int i = 0; i < 32; i++) { float& x = p[i >> 4][i & 15]; x *= cc[i >> 4][(i >> 1) & 1]; s2[i & 3] = fmaf(x, x, s2[i & 3]); }
        if (!__any_sync(~0u, !((s2[0] < ARG_LIM2) & (s2[1] < ARG_LIM2) & (s2[2] < ARG_LIM2) & (s2[3] < ARG_LIM2)))) break;
        shifted = 1;
      }
      if (e == 1 || e == 2) bar_sync(NB_TOK + e - 1, 256);
      TK(64 + 4 * turn);
      float ac[4][20];
      auto numer = [&](int h) {
        const uint32_t (*f)[8] = &ph[2 * h];
        const uint32_t db = dlo(SB0 + OFF_KVZ, 128) + (half ? e : h) * 320;
        wg_fence();
        #pragma unroll
        for (int i = 0; i < 2; i++) {
          wgmma_rz_n40<1, dhi(256, 0)>(ac[2*h+i], f[i][0], f[i][1], f[i][2], f[i][3], db + i * 160);
          wgmma_ra_n40<1, dhi(256, 0)>(ac[2*h+i], f[i][4], f[i][5], f[i][6], f[i][7], db + (i * 160 + 80));
        }
        wg_commit();
      };
      const uint32_t oa = (16 * wp + g) * 128 + (((lane & 3) ^ g) << 4);
      auto finish = [&](int h) {
        const float* ap = ac[2 * h]; const float* am = ac[2 * h + 1];
        const float ip0 = rcp(ap[17]), im0 = rcp(am[17]), ip1 = rcp(ap[19]), im1 = rcp(am[19]);
        const float d0 = rcp(fmaf(ap[16], ip0, fmaf(am[16], im0, 1e-6f))), d1 = rcp(fmaf(ap[18], ip1, fmaf(am[18], im1, 1e-6f)));
        const float a0 = ip0 * d0, b0 = im0 * d0, a1 = ip1 * d1, b1 = im1 * d1;
        #pragma unroll
        for (int r = 0; r < 2; r++) {
          const float a = r ? a1 : a0, b = r ? b1 : b0;
          uint32_t w[4];
          #pragma unroll
          for (int k = 0; k < 4; k++) w[k] = pack_bf16(fmaf(ap[4*k+2*r], a, am[4*k+2*r] * b), fmaf(ap[4*k+2*r+1], a, am[4*k+2*r+1] * b));
          const uint32_t off = (oa ^ ((half ? rank : h) << 6)) + r * 1024;
          st128_rlx(reinterpret_cast<uint8_t*>(G->o + (m128 * 16 + (half ? 2 * (j & 6) + 2 * hh + 1 : 2 * j)) * 8192 + (half ? h : hh) * 4096) + off, w[0], w[1], w[2], w[3]);
          if (!half) sts128(sb + ao + off, w[0], w[1], w[2], w[3]);
        }
        if ((half || h) && lane == 0) st32_rlx(&G->oflag[(m128 * 6 + (half ? 2 * e - 2 + h : hh)) * 32 + 4 * j + wp], 1);
      };
      if (!shifted) dual_exp2<true>(p[0], ph[0], ph[1]);
      numer(0);
      if (!shifted) dual_exp2<true>(p[1], ph[2], ph[3]);
      if (turn < 2) bar_arrive(NB_TOK + turn, 256);
      if (wg == 0) bar_sync(NB_DN, 256);
      numer(1);
      wg_wait<1>();
      TK(65 + 4 * turn);
      fence_regs(ac[0]); fence_regs(ac[1]);
      finish(0);
      wg_wait<0>();
      fence_regs(ac[2]); fence_regs(ac[3]);
      #pragma unroll
      for (int i = 0; i < 32; i++) asm volatile("mov.b32 %0, 0;" : "=f"(p[i >> 4][i & 15]));
      if (e == 2) project_r(3);
      finish(1);
      TK(66 + 4 * turn);
      if (!half) fence_async_smem();
      __syncwarp();
      if (lane == 0) mbar_arrive(sb + B_UO + 8 * e);
      wg_wait<0>();
      TK(67 + 4 * turn);
    }
    if (isq) cluster_arrive();
  }

  {
  int lane;
  asm volatile("mov.u32 %0, %%laneid;" : "=r"(lane));
  const int g = lane >> 2, q = lane & 3;
  if (wg < 2) {
    float h[64];
    {
      if (wg == 0) { TK(83); }
      #pragma unroll
      for (int i = 0; i < 32; i++) { h[2*i] = bf_lo(xr[i]); h[2*i+1] = bf_hi(xr[i]); }
      fence_regs(h);
      TK(80 + wg);
      const uint32_t emptyb = mapa(sb + B_EMPTY5, t & 1);
      uint32_t s = 1 + rank, ps = 0;
      mbar_wait2(sb + B_GB + 8 * rank, 0, sb + B_UO + 8 * wg, 0);
      if (wg == 0) { TSW(14); }
      #pragma unroll
      for (int i = 0; i < 16; i++) {
        if (KT == 2 && wg == 1) { TK(i); }
        if (KT != 1 && wg == 0) { TK(32 + i); }
        const uint32_t da = dlo(SB0, 16) + s * 2048 + wg * 512, db = dlo(SB0 + 16384, 8192) + s * 2048;
        wg_fence();
        #pragma unroll
        for (int k = 0; k < 4; k++) wgmma_sa_n128<0, 1, H128, H128>(h, da + k * 2, db + k * 128);
        wg_commit();
        const uint32_t ns = i ? (i + 2) % 6 : 2 - rank;
        const uint32_t nb = i ? i + 1 : 1 - rank, b0 = sb + B_GB + 8 * nb, b1 = sb + B_GA + 16 * nb + 8 * wg;
        const bool here = i == 15 || mbar_test2(b0, 0, b1, 0);
        wg_wait<1>();
        if (!(((2 * REL + 1) >> i) & 1) && i < 14 && t < 2) mbar_arrive_remote(emptyb + 8 * ps, 1);
        if ((REL >> i) & 1) { wg_wait<0>(); if (t < 2) mbar_arrive_remote(emptyb + 8 * s, 1); }
        if (!here) mbar_wait2(b0, 0, b1, 0);
        ps = s; s = ns;
      }
    }
    cluster_arrive();
    float2 wr[16];
    #pragma unroll
    for (int i = 0; i < 16; i++) wr[i] = lds64f(sb + OFF_WR + 32 * i + 8 * q);
    const int r0 = 64 * wg + 16 * wp + g;
    float sum0, sum1, dot0, dot1, sq0, sq1;
    uint32_t redo = 0;
    asm volatile("" : "+r"(redo));
    #pragma unroll 1
    for (;;) {
    if (!(XP & 32) && redo) {
      wg_wait<0>();
      const uint32_t* xp = reinterpret_cast<const uint32_t*>(P.x + (size_t)(128 * m128 + r0) * DM + 128 * j) + q;
      #pragma unroll
      for (int i = 0; i < 32; i++) { const uint32_t v = xp[4 * (i >> 1) + (i & 1) * 4 * DM]; h[2*i] = bf_lo(v); h[2*i+1] = bf_hi(v); }
      #pragma unroll 1
      for (int ks = 0; ks < 64; ks++) {
        const int kb = ks >> 2, kk = 16 * (ks & 3);
        const bf16* op = G->o + (m128 * 16 + kb) * 8192 + r0 * 64 + 2 * q;
        const int o0 = ((kk >> 3) ^ g) << 3;
        const uint32_t* w = reinterpret_cast<const uint32_t*>(P.wo_p + (size_t)(((kb & 1) ? 256 * (kb >> 2) + 32 * (kb & 2) + 32 + 4 * (kk & 32) : 64 * kb + 2 * (kk & 32)) +
                                                                              ((kk & 16) >> 2) + 4 * (g & 6) + (g & 1)) * DM + 128 * j) + q;
        uint32_t b[32], a0, a1, a2, a3, it = 0;
        #pragma unroll
        for (int n = 0; n < 32; n++) b[n] = w[4 * (n >> 1) + (n & 1) * DM];
        do { a0 = ld32_rlx(op + o0); a1 = ld32_rlx(op + 512 + o0); a2 = ld32_rlx(op + (o0 ^ 8)); a3 = ld32_rlx(op + 512 + (o0 ^ 8)); }
        while (max(max(a0, a1), max(a2, a3)) == ~0u && ++it < POLL_LIMIT);
        __syncwarp();
        #pragma unroll
        for (int n = 0; n < 16; n++) mma16816(h[4*n], h[4*n+1], h[4*n+2], h[4*n+3], a0, a1, a2, a3, transpose8(b[2*n]), transpose8(b[2*n+1]));
      }
    }
    wg_wait<0>();
    fence_regs(h);
    if (wg == 0) { TSW(16); }
    sum0 = 0.f, sum1 = 0.f, dot0 = 0.f, dot1 = 0.f, sq0 = 0.f, sq1 = 0.f;
    #pragma unroll
    for (int i = 0; i < 16; i++) {
      sum0 += h[4*i] + h[4*i+1]; sum1 += h[4*i+2] + h[4*i+3];
      sq0 = fmaf(h[4*i], h[4*i], fmaf(h[4*i+1], h[4*i+1], sq0)); sq1 = fmaf(h[4*i+2], h[4*i+2], fmaf(h[4*i+3], h[4*i+3], sq1));
      dot0 = fmaf(h[4*i], wr[i].x, fmaf(h[4*i+1], wr[i].y, dot0)); dot1 = fmaf(h[4*i+2], wr[i].x, fmaf(h[4*i+3], wr[i].y, dot1));
    }
    if (!__any_sync(~0u, !redo & (h[0] != h[0] | h[2] != h[2]))) break;
    redo = 1;
    }
    float4* const rs = &G->rstat[128 * m128 + r0];
    {
      const bool up = q & 2;
      float a = up ? sum1 : sum0, b = up ? sq1 : sq0, d = up ? dot1 : dot0;
      a += __shfl_xor_sync(~0u, up ? sum0 : sum1, 2); b += __shfl_xor_sync(~0u, up ? sq0 : sq1, 2); d += __shfl_xor_sync(~0u, up ? dot0 : dot1, 2);
      a += __shfl_xor_sync(~0u, a, 1); b += __shfl_xor_sync(~0u, b, 1); d += __shfl_xor_sync(~0u, d, 1);
      if ((q & 1) == 0) red_add_f32x4(rs + 4 * q, a, b, d, 1.f);
    }
    if (TRKL == 0) bar_arrive(NB_G2E, 384);
    if (wg == 0) { TSW(24); }
    bar_sync(NB_WG01, 256);
    uint32_t wa[8][4][4];
    const uint32_t wb = sb + 16384 * (((uint32_t)FF_SLOT >> (4 * warp)) & 15) + ((lane & 7) + ((lane >> 4) << 3)) * 64 + ((((lane >> 3) & 1) ^ ((lane >> 1) & 3)) << 4);
    auto getw = [&](int ks) {
      #pragma unroll
      for (int m = 0; m < 4; m++) ldsm4t((wb ^ ((m & 1) << 5)) + (m >> 1) * 8192 + ks * 1024, wa[ks][m][0], wa[ks][m][1], wa[ks][m][2], wa[ks][m][3]);
    };
    if (GPRE && f < NFFN_L) mbar_wait(sb + B_F + 8 * warp, 0);
    if (warp == 7) { TK(60); }
    #pragma unroll
    for (int ks = 0; ks < GPRE; ks++) getw(ks);
    float rstd[2], bm[2];
    uint32_t best;
    {
      const float2 swa = lds64f(sb + OFF_SUMWR), swb = lds64f(sb + OFF_SUMWR + 8);
      const float sw = (swa.x + swa.y) + (swb.x + swb.y);
      uint4 a[2]; uint32_t it = 0, key[2];
      do { a[0] = ld128_rlx(rs); a[1] = ld128_rlx(rs + 8); } while (__any_sync(~0u, (a[0].w & a[1].w) != 0x41000000u) && ++it < POLL_LIMIT);
      #pragma unroll
      for (int i = 0; i < 2; i++) {
        const float mean = __uint_as_float(a[i].x) * (1.f / DM);
        rstd[i] = rsqrtf(fmaxf(__uint_as_float(a[i].y) * (1.f / DM) - mean * mean, 0.f) + 1e-5f);
        bm[i] = -mean * rstd[i];
        const uint32_t rr = __float_as_uint(fmaf(__uint_as_float(a[i].z), rstd[i], sw * bm[i]));
        key[i] = ((rr ^ ((uint32_t)((int32_t)rr >> 31) | 0x80000000u)) & ~2047u) | (2047 - 128 * m128 - r0 - 8 * i);
      }
      asm volatile("redux.sync.max.u32 %0, %1, 0xffffffff;" : "=r"(best) : "r"(max(key[0], key[1])));
    }
    if (TRKL == 2) bar_arrive(NB_G2E, 384);
    if (TRKL == 3 && wg == 0) bar_arrive(NB_G2E, 256);
    if (wg == 0) { TSW(17); }
    const int slot = m128 * 8 + warp, win = ~best & 15;
    if (lane < KR) st32_rlx(&G->key[(KR * j + lane) * 128 + slot], best);
    if ((win & 7) == g) {
      const bool up = win & 8;
      const float ra = up ? rstd[1] : rstd[0], rb = up ? bm[1] : bm[0];
      uint32_t x[16];
      #pragma unroll
      for (int i = 0; i < 16; i++) x[i] = pack_bf16(fmaf(up ? h[4*i+2] : h[4*i], ra, rb), fmaf(up ? h[4*i+3] : h[4*i+1], ra, rb));
      #pragma unroll
      for (int i = 0; i < 4; i++) st128_rlx(&G->cand[slot * 512 + 64 * j + 16 * i + 4 * q], x[4*i], x[4*i+1], x[4*i+2], x[4*i+3]);
    }
    __syncwarp();
    if (TRKL == 1) bar_arrive(NB_G2E, 384);
    if (wg == 0) { TSW(27); }
    {
      const float a0 = 1.f + rstd[0], b0 = bm[0], a1 = 1.f + rstd[1], b1 = bm[1];
      #pragma unroll
      for (int k = 0; k < 8; k++)
        stsm4(((sb + OFF_OUT + wg * 8192 + sa) ^ ((k & 3) << 5)) + (k >> 2) * 16384,
              pack_bf16(fmaf(h[8*k], a0, b0), fmaf(h[8*k+1], a0, b0)),     pack_bf16(fmaf(h[8*k+2], a1, b1), fmaf(h[8*k+3], a1, b1)),
              pack_bf16(fmaf(h[8*k+4], a0, b0), fmaf(h[8*k+5], a0, b0)),   pack_bf16(fmaf(h[8*k+6], a1, b1), fmaf(h[8*k+7], a1, b1)));
      fence_async_smem();
      __syncwarp();
      if (lane == 0) mbar_arrive(sb + B_OUT + 8 * wg);
    }
    if (wg == 0) { TSW(28); }
    {
      if (!GPRE && f < NFFN_L) mbar_wait(sb + B_F + 8 * warp, 0);
      #pragma unroll
      for (int ks = GPRE; ks < GRES; ks++) getw(ks);
      if (wg == 0) { TSW(15); }
      bar_sync(NB_XS, 384);
      uint4 xs[4];
      #pragma unroll
      for (int i = 0; i < 4; i++) xs[i] = lds128(sb + OFF_XSEL + 256 * warp + 64 * i + 16 * q);
      float d[4][4];
      #pragma unroll
      for (int ks = 0; ks < 8; ks++) {
        if (ks >= 1 && GRES + ks - 1 < 8) getw(GRES + ks - 1);
        #pragma unroll
        for (int m = 0; m < 4; m++) {
          if (ks == 0) { d[m][0] = 0.f; d[m][1] = 0.f; d[m][2] = 0.f; d[m][3] = 0.f; }
          mma16816(d[m][0], d[m][1], d[m][2], d[m][3], wa[ks][m][0], wa[ks][m][1], wa[ks][m][2], wa[ks][m][3],
                   (ks & 1) ? xs[ks >> 1].z : xs[ks >> 1].x, (ks & 1) ? xs[ks >> 1].w : xs[ks >> 1].y);
        }
      }
      if (q == 0) {
        #pragma unroll
        for (int m = 0; m < 8; m++) stsf(sb + OFF_GU + (8 * m + g) * 48 + 4 * warp, d[m >> 1][2 * (m & 1)]);
      }
      bar_arrive(NB_ACT, 384);
    }
    {
      const uint32_t ky = __float_as_uint(ldsf(sb + OFF_KEY));
      const int row = 2047 - (ky & 2047) - 128 * m128;
      if ((uint32_t)row < 128u) {
        const int l = tid >> 3, vi = (j & 1) + ((lane >> 2) & 1), e = 3 * vi + q - 4 * (j & 1);
        const float kr = __uint_as_float((ky & ~2047u) ^ ((ky >> 31) ? 0x80000000u : 0xfffff800u));
        const int col = 32 * (l & 3) + 16 * (e & 1) + 4 * (e & 2) + (l >> 2);
        const float sg = rcp(1.f + ex2(-LOG2E * kr));
        const uint32_t base = __float_as_uint(ldsf(sb + OFF_OUT + (col >> 6) * 16384 + row * 128 + ((((col >> 3) ^ row) & 7) << 4) + 2 * (col & 6)));
        const float4* yp = &G->yacc[(q * 3 + vi) * 128 + 32 * (j >> 1) + l];
        uint32_t it = 0;
        uint4 v;
        mbar_wait(sb + B_SD, 0);
        do { v = ld128_rlx(yp); } while (__any_sync(~0u, __uint_as_float(v.w) != (float)(NFFN / 4)) && ++it < POLL_LIMIT);
        float y0 = __uint_as_float(v.x), y1 = __uint_as_float(v.y), y2 = __uint_as_float(v.z);
        #pragma unroll
        for (int o = 1; o < 4; o <<= 1) { y0 += __shfl_xor_sync(~0u, y0, o); y1 += __shfl_xor_sync(~0u, y1, o); y2 += __shfl_xor_sync(~0u, y2, o); }
        if (q < 3 && (uint32_t)e < 4u)
          P.out_p[(size_t)(128 * m128 + row) * DM + 128 * j + col] = __float2bfloat16(fmaf(q == 0 ? y0 : q == 1 ? y1 : y2, sg, (col & 1) ? bf_hi(base) : bf_lo(base)));
      }
      if (c == 0 && tid == 0) st32_rlx(&G->epoch, __float_as_uint(ldsf(sb + OFF_EP)));
      if (warp == 0) { TSW(22); }
      if (wg == 0) { TDUMP(); }
    }
  }
  if (wg == 2) {
    uint32_t wf[16][2][4];
    {
      const uint32_t wb = sb + OFF_S + 16384 * (wp & 1) + ((lane & 7) + ((lane >> 4) << 3)) * 128 + ((((lane >> 3) & 1) ^ (lane & 7)) << 4);
      if (f < NFFN_L) mbar_wait(sb + B_WD + 8 * wp, 0);
      if (wp == 0) { TK(61); }
      #pragma unroll
      for (int i = 0; i < 32; i++) ldsm4t((wb ^ (((i >> 1) & 3) << 5)) + (i >> 3) * 4096 + (i & 1) * 2048, wf[i >> 1][i & 1][0], wf[i >> 1][i & 1][1], wf[i >> 1][i & 1][2], wf[i >> 1][i & 1][3]);
      fence_async_smem();
      __syncwarp();
      if (lane == 0) mbar_arrive(sb + B_WC + 8 * wp);
      if (wp == 0) { TK(62); }
    }
    bar_sync(NB_G2E, TRKL == 3 ? 256 : 384);
    {
      uint32_t cur = 0;
      uint4 v;
      #pragma unroll 1
      for (uint32_t it = 0; it < POLL_LIMIT; it++) {
        const uint4 kx = ld128_rlx(&G->key[(KSEL & (8 * KR - 1)) * 128 + 4 * lane]);
        v = ld128_rlx(&G->cand[((~cur >> 4) & 127) * 512 + 4 * t]);
        uint32_t best;
        asm volatile("redux.sync.max.u32 %0, %1, 0xffffffff;" : "=r"(best) : "r"(max(max(kx.x, kx.y), max(kx.z, kx.w))));
        if (!__any_sync(~0u, min(min(kx.x, kx.y), min(kx.z, kx.w)) == 0 || v.w == ~0u) && best == cur) break;
        cur = best;
      }
      sts128(sb + OFF_XSEL + 16 * t, v.x, v.y, v.z, v.w);
      sts32(sb + OFF_KEY, cur);
      bar_arrive(NB_XS, 384);
      TSW(18);
      bar_sync(NB_ACT, 384);
    }
    float gu[2];
    #pragma unroll
    for (int i = 0; i < 2; i++) {
      const uint4 v0 = lds128(sb + OFF_GU + (32 * i + lane) * 48), v1 = lds128(sb + OFF_GU + (32 * i + lane) * 48 + 16);
      gu[i] = ((__uint_as_float(v0.x) + __uint_as_float(v0.y)) + (__uint_as_float(v0.z) + __uint_as_float(v0.w))) +
              ((__uint_as_float(v1.x) + __uint_as_float(v1.y)) + (__uint_as_float(v1.z) + __uint_as_float(v1.w)));
    }
    const float act = gu[0] * gu[1] * rcp(1.f + ex2(-LOG2E * gu[0]));
    const uint32_t ap = pack_bf16(act, __shfl_down_sync(~0u, act, 1));
    uint32_t bf[4];
    #pragma unroll
    for (int i = 0; i < 4; i++) bf[i] = __shfl_sync(~0u, ap, 2 * q + 8 * i);
    TSW(20);
    float d[16][4];
    #pragma unroll
    for (int k = 0; k < 2; k++)
      #pragma unroll
      for (int i = 0; i < 16; i++) {
        if (k == 0) { d[i][0] = 0.f; d[i][1] = 0.f; d[i][2] = 0.f; d[i][3] = 0.f; }
        mma16816(d[i][0], d[i][1], d[i][2], d[i][3], wf[i][k][0], wf[i][k][1], wf[i][k][2], wf[i][k][3], bf[2*k], bf[2*k+1]);
      }
    float y[9];
    #pragma unroll
    for (int e = 0; e < 8; e++) {
      const int n = 2 * (e & 4) + (e & 1);
      const float lo = (q & 1) ? d[n + 2][e & 2] : d[n][e & 2], hi = (q & 1) ? d[n + 6][e & 2] : d[n + 4][e & 2];
      y[e] = (q & 2) ? hi : lo;
    }
    y[8] = 0.f;
    if (f < NFFN) {
      #pragma unroll
      for (int i = 0; i < 3; i++) red_add_f32x4(&G->yacc[((f & 3) * 3 + i) * 128 + t], y[3*i], y[3*i+1], y[3*i+2], 1.f);
    }
    TSW(21);
  }
  }
  cluster_wait();
}

typedef CUresult (*EncodeFn)(CUtensorMap*, CUtensorMapDataType, cuuint32_t, void*, const cuuint64_t*, const cuuint64_t*,
                             const cuuint32_t*, const cuuint32_t*, CUtensorMapInterleave, CUtensorMapSwizzle,
                             CUtensorMapL2promotion, CUtensorMapFloatOOBfill);

void make_map(EncodeFn enc, CUtensorMap* m, const void* p, int n, const cuuint64_t* dims, const cuuint64_t* str, const cuuint32_t* box,
              CUtensorMapSwizzle sw, CUtensorMapL2promotion promo) {
  cuuint32_t es[5] = {1, 1, 1, 1, 1};
  enc(m, CU_TENSOR_MAP_DATA_TYPE_BFLOAT16, n, const_cast<void*>(p), dims, str, box, es, CU_TENSOR_MAP_INTERLEAVE_NONE, sw, promo,
      CU_TENSOR_MAP_FLOAT_OOB_FILL_NONE);
}
void map2(EncodeFn enc, CUtensorMap* m, const void* p, uint64_t cols, uint64_t rows, uint32_t bc, uint32_t br, CUtensorMapSwizzle sw,
          CUtensorMapL2promotion promo) {
  const cuuint64_t dims[2] = {cols, rows}, str[1] = {cols * 2};
  const cuuint32_t box[2] = {bc, br};
  make_map(enc, m, p, 2, dims, str, box, sw, promo);
}
void map3(EncodeFn enc, CUtensorMap* m, const void* p, uint64_t cols, uint64_t rows, uint32_t br, uint32_t nb) {
  const cuuint64_t dims[3] = {64, rows, cols / 64}, str[2] = {cols * 2, 128};
  const cuuint32_t box[3] = {64, br, nb};
  make_map(enc, m, p, 3, dims, str, box, CU_TENSOR_MAP_SWIZZLE_128B, CU_TENSOR_MAP_L2_PROMOTION_L2_128B);
}

}

extern "C" void kernel_launch(void* const* d_in, const int* in_sizes, int n_in, void* d_out, int out_size) {
  (void)in_sizes; (void)n_in; (void)out_size;
  static EncodeFn enc = nullptr;
  static void* o_ptr = nullptr;
  if (!enc) {
    void* f = nullptr; cudaDriverEntryPointQueryResult qr;
    cudaGetDriverEntryPoint("cuTensorMapEncodeTiled", &f, cudaEnableDefault, &qr);
    enc = (EncodeFn)f;
    cudaGetSymbolAddress(&o_ptr, g_scr);
    cudaFuncSetAttribute(fused_kernel, cudaFuncAttributeMaxDynamicSharedMemorySize, SMEM_BYTES);
  }
  const bf16* x = (const bf16*)d_in[0];
  const bf16* wqkv = (const bf16*)d_in[1];
  const bf16* wphi = (const bf16*)d_in[2];
  const bf16* wo = (const bf16*)d_in[3];
  const bf16* wr = (const bf16*)d_in[5];
  const bf16* wgate = (const bf16*)d_in[6];
  const bf16* wup = (const bf16*)d_in[7];
  const bf16* wdown = (const bf16*)d_in[8];
  Params P;
  const CUtensorMapSwizzle S128 = CU_TENSOR_MAP_SWIZZLE_128B, S64 = CU_TENSOR_MAP_SWIZZLE_64B;
  const CUtensorMapL2promotion L128 = CU_TENSOR_MAP_L2_PROMOTION_L2_128B, L256 = CU_TENSOR_MAP_L2_PROMOTION_L2_256B,
                               L64 = CU_TENSOR_MAP_L2_PROMOTION_L2_64B;
  map2(enc, &P.x128, x, DM, SEQ, 64, 128, S128, L128);
  map2(enc, &P.x64, x, DM, SEQ, 64, 64, S128, L128);
  {
    const cuuint64_t dims[4] = {64, DM, 16, 3}, str[3] = {6 * DM, 128, 2 * DM};
    const cuuint32_t box[4] = {64, 64, 1, 2};
    make_map(enc, &P.wkv, wqkv, 4, dims, str, box, S128, L128);
  }
  map3(enc, &P.wq, wqkv, 3 * DM, DM, 64, 2);
  for (int i = 0; i < 2; i++) {
    const cuuint64_t dims[5] = {DM, (cuuint64_t)(DM - 94 - 64 * i), 4, 4, 2}, str[4] = {2 * DM, 16 * DM, 4 * DM, (cuuint64_t)(128 * DM) << i};
    const cuuint32_t box[5] = {64, 2, 4, 4, 2};
    make_map(enc, &P.wo[i], wo, 5, dims, str, box, S128, L128);
  }
  map3(enc, &P.wd, wdown, DM, FF, 32, 4);
  map2(enc, &P.wg, wgate, FF, DM, 32, 128, S64, L64);
  map2(enc, &P.wu, wup, FF, DM, 32, 128, S64, L64);
  map2(enc, &P.tg, wgate, FF, DM, 8, 16, CU_TENSOR_MAP_SWIZZLE_NONE, L128);
  map2(enc, &P.tu, wup, FF, DM, 8, 16, CU_TENSOR_MAP_SWIZZLE_NONE, L128);
  map2(enc, &P.td, wdown, 128, FF * 8, 8, 16, CU_TENSOR_MAP_SWIZZLE_NONE, L256);
  map2(enc, &P.xs, x, DM, SEQ, 128, 16, CU_TENSOR_MAP_SWIZZLE_NONE, L256);
  map2(enc, &P.ws, wqkv, 3 * DM, DM, 16, 128, CU_TENSOR_MAP_SWIZZLE_NONE, L128);
  map2(enc, &P.qs, wqkv, 3 * DM, DM, 32, 128, CU_TENSOR_MAP_SWIZZLE_NONE, L64);
  map2(enc, &P.out, d_out, DM, SEQ, 64, 16, S128, L128);
  map2(enc, &P.o, o_ptr, 256, SEQ * DM / 256, 256, 16, CU_TENSOR_MAP_SWIZZLE_NONE, L128);
  map2(enc, &P.phi, wphi, 32, 1024, 32, 32, S64, L64);
  P.x = x; P.wqkv = wqkv; P.wo_p = wo; P.wd_p = wdown; P.wg_p = wgate; P.wu_p = wup; P.wr = wr; P.out_p = (bf16*)d_out; P.g = (Scratch*)o_ptr; P.zero = 0;

  cudaLaunchConfig_t cfg = {};
  cfg.gridDim = dim3(128); cfg.blockDim = dim3(512); cfg.dynamicSmemBytes = SMEM_BYTES; cfg.stream = cudaStreamPerThread;
  cudaLaunchAttribute at[1];
  at[0].id = cudaLaunchAttributeClusterDimension; at[0].val.clusterDim.x = 2; at[0].val.clusterDim.y = 1; at[0].val.clusterDim.z = 1;
  cfg.attrs = at; cfg.numAttrs = 1;
  cudaLaunchKernelEx(&cfg, fused_kernel, P);
}
```

```cpp
#include <cuda_runtime.h>
#include <cuda.h>
#include <cuda_bf16.h>
#include <stdint.h>

namespace {

typedef __nv_bfloat16 bf16;

__device__ __forceinline__ uint32_t smem_u32(const void* p){ return (uint32_t)__cvta_generic_to_shared(p); }
__device__ __forceinline__ void mbar_init(uint32_t bar, uint32_t cnt){ asm volatile("mbarrier.init.shared::cta.b64 [%0], %1;"::"r"(bar),"r"(cnt):"memory"); }
__device__ __forceinline__ void mbar_expect_tx(uint32_t bar, uint32_t bytes){ asm volatile("mbarrier.arrive.expect_tx.shared::cta.b64 _, [%0], %1;"::"r"(bar),"r"(bytes):"memory"); }
__device__ __forceinline__ void mbar_arrive(uint32_t bar){ asm volatile("mbarrier.arrive.shared::cta.b64 _, [%0];"::"r"(bar):"memory"); }
__device__ __forceinline__ uint32_t mapa(uint32_t addr, uint32_t cta){ uint32_t r; asm volatile("mapa.shared::cluster.u32 %0, %1, %2;":"=r"(r):"r"(addr),"r"(cta)); return r; }
__device__ __forceinline__ void mbar_arrive_at(uint32_t bar, uint32_t cta, uint32_t cnt){
  asm volatile("{\n.reg .b32 ra;\nmapa.shared::cluster.u32 ra, %0, %1;\nmbarrier.arrive.shared::cluster.b64 _, [ra], %2;\n}\n"::"r"(bar),"r"(cta),"r"(cnt):"memory"); }
__device__ __forceinline__ void mbar_arrive_remote(uint32_t cluster_addr, uint32_t cnt){
  asm volatile("mbarrier.arrive.shared::cluster.b64 _, [%0], %1;"::"r"(cluster_addr),"r"(cnt):"memory"); }
__device__ __forceinline__ void mbar_wait(uint32_t bar, uint32_t parity){
  asm volatile("{\n.reg .pred p;\n.reg .u32 c;\nmov.u32 c, 0;\nLW:\nmbarrier.try_wait.parity.shared::cta.b64 p, [%0], %1;\n@p bra LD;\nadd.u32 c, c, 1;\nsetp.lt.u32 p, c, 2000000;\n@p bra LW;\ntrap;\nLD:\n}\n"::"r"(bar),"r"(parity):"memory"); }
__device__ __forceinline__ void mbar_wait2(uint32_t bar0, uint32_t par0, uint32_t bar1, uint32_t par1){
  asm volatile("{\n.reg .pred p, q;\n.reg .u32 c;\nmov.u32 c, 0;\nLW:\nmbarrier.try_wait.parity.shared::cta.b64 p, [%0], %1;\nmbarrier.try_wait.parity.shared::cta.b64 q, [%2], %3;\nand.pred p, p, q;\n@p bra LD;\nadd.u32 c, c, 1;\nsetp.lt.u32 p, c, 2000000;\n@p bra LW;\ntrap;\nLD:\n}\n"::"r"(bar0),"r"(par0),"r"(bar1),"r"(par1):"memory"); }
__device__ __forceinline__ bool mbar_test2(uint32_t bar0, uint32_t par0, uint32_t bar1, uint32_t par1){
  uint32_t r;
  asm volatile("{\n.reg .pred p, q;\nmbarrier.test_wait.parity.shared::cta.b64 p, [%1], %2;\nmbarrier.test_wait.parity.shared::cta.b64 q, [%3], %4;\nand.pred p, p, q;\nselp.u32 %0, 1, 0, p;\n}\n":"=r"(r):"r"(bar0),"r"(par0),"r"(bar1),"r"(par1):"memory");
  return r; }
__device__ __forceinline__ void tma_2d(uint32_t dst, const CUtensorMap* m, int c0, int c1, uint32_t bar){
  asm volatile("cp.async.bulk.tensor.2d.shared::cluster.global.mbarrier::complete_tx::bytes [%0], [%1, {%3, %4}], [%2];"::"r"(dst),"l"(m),"r"(bar),"r"(c0),"r"(c1):"memory"); }
__device__ __forceinline__ void tma_2d_h(uint32_t dst, const CUtensorMap* m, int c0, int c1, uint32_t bar, uint64_t pol){
  asm volatile("cp.async.bulk.tensor.2d.shared::cluster.global.mbarrier::complete_tx::bytes.L2::cache_hint [%0], [%1, {%3, %4}], [%2], %5;"::"r"(dst),"l"(m),"r"(bar),"r"(c0),"r"(c1),"l"(pol):"memory"); }
__device__ __forceinline__ void tma_2d_mc(uint32_t dst, const CUtensorMap* m, int c0, int c1, uint32_t bar){
  asm volatile("cp.async.bulk.tensor.2d.shared::cluster.global.mbarrier::complete_tx::bytes.multicast::cluster [%0], [%1, {%3, %4}], [%2], %5;"::"r"(dst),"l"(m),"r"(bar),"r"(c0),"r"(c1),"h"((uint16_t)3):"memory"); }
__device__ __forceinline__ void tma_2d_mc_h(uint32_t dst, const CUtensorMap* m, int c0, int c1, uint32_t bar, uint64_t pol){
  asm volatile("cp.async.bulk.tensor.2d.shared::cluster.global.mbarrier::complete_tx::bytes.multicast::cluster.L2::cache_hint [%0], [%1, {%3, %4}], [%2], %5, %6;"::"r"(dst),"l"(m),"r"(bar),"r"(c0),"r"(c1),"h"((uint16_t)3),"l"(pol):"memory"); }
__device__ __forceinline__ void tma_4d(uint32_t dst, const CUtensorMap* m, int c0, int c1, int c2, int c3, uint32_t bar){
  asm volatile("cp.async.bulk.tensor.4d.shared::cluster.global.mbarrier::complete_tx::bytes [%0], [%1, {%3, %4, %5, %6}], [%2];"::"r"(dst),"l"(m),"r"(bar),"r"(c0),"r"(c1),"r"(c2),"r"(c3):"memory"); }
__device__ __forceinline__ uint64_t policy_evict_first(){ uint64_t p; asm volatile("createpolicy.fractional.L2::evict_first.b64 %0, 1.0;":"=l"(p)); return p; }
__device__ __forceinline__ uint64_t policy_evict_normal(){ uint64_t p; asm("createpolicy.fractional.L2::evict_normal.b64 %0, 1.0;":"=l"(p)); return p; }
__device__ __forceinline__ void tma_3d_h(uint32_t dst, const CUtensorMap* m, int c0, int c1, int c2, uint32_t bar, uint64_t pol){
  asm volatile("cp.async.bulk.tensor.3d.shared::cluster.global.mbarrier::complete_tx::bytes.L2::cache_hint [%0], [%1, {%3, %4, %5}], [%2], %6;"::"r"(dst),"l"(m),"r"(bar),"r"(c0),"r"(c1),"r"(c2),"l"(pol):"memory"); }
__device__ __forceinline__ void tma_4d_h(uint32_t dst, const CUtensorMap* m, int c0, int c1, int c2, int c3, uint32_t bar, uint64_t pol){
  asm volatile("cp.async.bulk.tensor.4d.shared::cluster.global.mbarrier::complete_tx::bytes.L2::cache_hint [%0], [%1, {%3, %4, %5, %6}], [%2], %7;"::"r"(dst),"l"(m),"r"(bar),"r"(c0),"r"(c1),"r"(c2),"r"(c3),"l"(pol):"memory"); }
__device__ __forceinline__ void red_add_f32x4(float4* p, float x, float y, float z, float w){ asm volatile("red.relaxed.gpu.global.add.v4.f32 [%0], {%1,%2,%3,%4};"::"l"(p),"f"(x),"f"(y),"f"(z),"f"(w):"memory"); }
__device__ __forceinline__ void tma_5d_h(uint32_t dst, const CUtensorMap* m, int c0, int c1, uint32_t bar, uint64_t pol){
  asm volatile("cp.async.bulk.tensor.5d.shared::cluster.global.mbarrier::complete_tx::bytes.L2::cache_hint [%0], [%1, {%3, %4, 0, 0, 0}], [%2], %5;"::"r"(dst),"l"(m),"r"(bar),"r"(c0),"r"(c1),"l"(pol):"memory"); }
__device__ __forceinline__ void tma_store_2d(const CUtensorMap* m, int c0, int c1, uint32_t src, uint64_t pol){
  asm volatile("cp.async.bulk.tensor.2d.global.shared::cta.bulk_group.L2::cache_hint [%0, {%2, %3}], [%1], %4;"::"l"(m),"r"(src),"r"(c0),"r"(c1),"l"(pol):"memory"); }
__device__ __forceinline__ void bulk_commit(){ asm volatile("cp.async.bulk.commit_group;":::"memory"); }
__device__ __forceinline__ void bulk_wait_all(){ asm volatile("cp.async.bulk.wait_group 0;":::"memory"); }
__device__ __forceinline__ void fence_async_global(){ asm volatile("fence.proxy.async.global;":::"memory"); }
__device__ __forceinline__ bool elect_one(){ uint32_t p; asm volatile("{\n.reg .pred P;\nelect.sync _|P, 0xffffffff;\nselp.b32 %0, 1, 0, P;\n}\n":"=r"(p)); return p; }
__device__ __forceinline__ void bulk_prefetch(const void* p, uint32_t bytes){
  asm volatile("cp.async.bulk.prefetch.L2.global [%0], %1;"::"l"(p),"r"(bytes):"memory"); }
__device__ __forceinline__ void bulk_s2peer(uint32_t dst_cluster, uint32_t src, uint32_t bytes, uint32_t bar_cluster){
  asm volatile("cp.async.bulk.shared::cluster.shared::cta.mbarrier::complete_tx::bytes [%0], [%1], %2, [%3];"::"r"(dst_cluster),"r"(src),"r"(bytes),"r"(bar_cluster):"memory"); }
__device__ __forceinline__ void prefetch_map(const CUtensorMap* m){ asm volatile("prefetch.tensormap [%0];"::"l"(m):"memory"); }
__device__ __forceinline__ void fence_async_smem(){ asm volatile("fence.proxy.async.shared::cta;":::"memory"); }
__device__ __forceinline__ void fence_acquire_gpu(){ asm volatile("fence.acquire.gpu;":::"memory"); }
__device__ __forceinline__ void fence_gpu(){ asm volatile("fence.acq_rel.gpu;":::"memory"); }
__device__ __forceinline__ void wg_fence(){ asm volatile("wgmma.fence.sync.aligned;":::"memory"); }
__device__ __forceinline__ void wg_commit(){ asm volatile("wgmma.commit_group.sync.aligned;":::"memory"); }
template<int N> __device__ __forceinline__ void wg_wait(){ asm volatile("wgmma.wait_group.sync.aligned %0;"::"n"(N):"memory"); }
template<int N> __device__ __forceinline__ void fence_regs(float (&d)[N]){
  #pragma unroll
  for(int i=0;i<N;i++) asm volatile("":"+f"(d[i])::"memory"); }
__device__ __forceinline__ void bar_sync(int id, int n){ asm volatile("bar.sync %0, %1;"::"r"(id),"r"(n):"memory"); }
__device__ __forceinline__ void bar_arrive(int id, int n){ asm volatile("bar.arrive %0, %1;"::"r"(id),"r"(n):"memory"); }
__device__ __forceinline__ void cluster_arrive(){ asm volatile("barrier.cluster.arrive.relaxed.aligned;":::"memory"); }
__device__ __forceinline__ void cluster_wait(){ asm volatile("barrier.cluster.wait.aligned;":::"memory"); }
__host__ __device__ constexpr uint32_t dlo(uint32_t addr, uint32_t lbo){ return (addr >> 4) | ((lbo >> 4) << 16); }
__host__ __device__ constexpr uint32_t dhi(uint32_t sbo, uint32_t sw){ return (sbo >> 4) | (sw << 30); }
constexpr uint32_t H128 = dhi(1024, 1), H64 = dhi(512, 2), H0 = dhi(128, 0);
__device__ __forceinline__ uint32_t pack_bf16(float lo, float hi){ uint32_t r; asm("cvt.rn.bf16x2.f32 %0, %1, %2;":"=r"(r):"f"(hi),"f"(lo)); return r; }
__device__ __forceinline__ float bf_lo(uint32_t v){ return __uint_as_float(v<<16); }
__device__ __forceinline__ float bf_hi(uint32_t v){ return __uint_as_float(v&0xffff0000u); }
__device__ __forceinline__ float ex2(float x){ float r; asm("ex2.approx.ftz.f32 %0, %1;":"=f"(r):"f"(x)); return r; }
__device__ __forceinline__ float rcp(float x){ float r; asm("rcp.approx.ftz.f32 %0, %1;":"=f"(r):"f"(x)); return r; }
__device__ __forceinline__ void stsm4(uint32_t addr, uint32_t a, uint32_t b, uint32_t c, uint32_t d){
  asm volatile("stmatrix.sync.aligned.m8n8.x4.shared.b16 [%0], {%1,%2,%3,%4};"::"r"(addr),"r"(a),"r"(b),"r"(c),"r"(d)); }
__device__ __forceinline__ void stsm2(uint32_t addr, uint32_t a, uint32_t b){
  asm volatile("stmatrix.sync.aligned.m8n8.x2.shared.b16 [%0], {%1,%2};"::"r"(addr),"r"(a),"r"(b)); }
__device__ __forceinline__ void mma16816(float& d0, float& d1, float& d2, float& d3, uint32_t a0, uint32_t a1, uint32_t a2, uint32_t a3, uint32_t b0, uint32_t b1){
  asm volatile("mma.sync.aligned.m16n8k16.row.col.f32.bf16.bf16.f32 {%0,%1,%2,%3}, {%4,%5,%6,%7}, {%8,%9}, {%0,%1,%2,%3};"
               : "+f"(d0), "+f"(d1), "+f"(d2), "+f"(d3) : "r"(a0), "r"(a1), "r"(a2), "r"(a3), "r"(b0), "r"(b1)); }
__device__ __forceinline__ uint32_t transpose8(uint32_t a){ uint32_t r; asm volatile("movmatrix.sync.aligned.m8n8.trans.b16 %0, %1;":"=r"(r):"r"(a)); return r; }
__device__ __forceinline__ void ldsm4(uint32_t addr, uint32_t& a, uint32_t& b, uint32_t& c, uint32_t& d){
  asm volatile("ldmatrix.sync.aligned.m8n8.x4.shared.b16 {%0,%1,%2,%3}, [%4];":"=r"(a),"=r"(b),"=r"(c),"=r"(d):"r"(addr):"memory"); }
__device__ __forceinline__ void ldsm4t(uint32_t addr, uint32_t& a, uint32_t& b, uint32_t& c, uint32_t& d){
  asm volatile("ldmatrix.sync.aligned.m8n8.x4.trans.shared.b16 {%0,%1,%2,%3}, [%4];":"=r"(a),"=r"(b),"=r"(c),"=r"(d):"r"(addr):"memory"); }
__device__ __forceinline__ void sts32(uint32_t a, uint32_t v){ asm volatile("st.shared.b32 [%0], %1;"::"r"(a),"r"(v):"memory"); }
__device__ __forceinline__ void stsf(uint32_t a, float v){ asm volatile("st.shared.f32 [%0], %1;"::"r"(a),"f"(v):"memory"); }
__device__ __forceinline__ void sts64(uint32_t a, uint32_t x, uint32_t y){ asm volatile("st.shared.v2.b32 [%0], {%1,%2};"::"r"(a),"r"(x),"r"(y):"memory"); }
__device__ __forceinline__ void sts128(uint32_t a, uint32_t x, uint32_t y, uint32_t z, uint32_t w){ asm volatile("st.shared.v4.b32 [%0], {%1,%2,%3,%4};"::"r"(a),"r"(x),"r"(y),"r"(z),"r"(w):"memory"); }
__device__ __forceinline__ float ldsf(uint32_t a){ float v; asm volatile("ld.shared.f32 %0, [%1];":"=f"(v):"r"(a):"memory"); return v; }
__device__ __forceinline__ float2 lds64f(uint32_t a){ float2 v; asm volatile("ld.shared.v2.f32 {%0,%1}, [%2];":"=f"(v.x),"=f"(v.y):"r"(a):"memory"); return v; }
__device__ __forceinline__ uint4 lds128(uint32_t a){ uint4 v; asm volatile("ld.shared.v4.u32 {%0,%1,%2,%3}, [%4];":"=r"(v.x),"=r"(v.y),"=r"(v.z),"=r"(v.w):"r"(a):"memory"); return v; }
__device__ __forceinline__ uint4 ld128_keep(const void* p){ uint4 v; asm volatile("ld.global.v4.u32 {%0,%1,%2,%3}, [%4];":"=r"(v.x),"=r"(v.y),"=r"(v.z),"=r"(v.w):"l"(p):"memory"); return v; }
__device__ __forceinline__ uint4 ld128_rlx(const void* p){ uint4 v; asm volatile("ld.relaxed.gpu.global.v4.u32 {%0,%1,%2,%3}, [%4];":"=r"(v.x),"=r"(v.y),"=r"(v.z),"=r"(v.w):"l"(p):"memory"); return v; }
__device__ __forceinline__ uint32_t ld32_rlx(const void* p){ uint32_t v; asm volatile("ld.relaxed.gpu.global.u32 %0, [%1];":"=r"(v):"l"(p):"memory"); return v; }
__device__ __forceinline__ void st128_rlx(void* p, uint32_t x, uint32_t y, uint32_t z, uint32_t w){ asm volatile("st.relaxed.gpu.global.v4.u32 [%0], {%1,%2,%3,%4};"::"l"(p),"r"(x),"r"(y),"r"(z),"r"(w):"memory"); }
__device__ __forceinline__ void st64_rlx(void* p, uint32_t x, uint32_t y){ asm volatile("st.relaxed.gpu.global.v2.u32 [%0], {%1,%2};"::"l"(p),"r"(x),"r"(y):"memory"); }
__device__ __forceinline__ void st32_rlx(void* p, uint32_t x){ asm volatile("st.relaxed.gpu.global.u32 [%0], %1;"::"l"(p),"r"(x):"memory"); }
__device__ __forceinline__ void wait_until(uint32_t t){ while ((int32_t)((uint32_t)clock() - t) < 0) __nanosleep(32); }
__device__ __forceinline__ void flags_wait(uint32_t& missing, const uint32_t* p, uint32_t need){
  asm volatile("{\n.reg .pred p;\n.reg .u32 c, v;\nmov.u32 c, 0;\nLW:\nand.b32 v, %0, %2;\nsetp.eq.u32 p, v, 0;\n@p bra.uni LD;\nld.relaxed.gpu.global.u32 v, [%1];\nsetp.eq.u32 p, v, 0;\n"
               "vote.sync.ballot.b32 %0, p, 0xffffffff;\nadd.u32 c, c, 1;\nsetp.lt.u32 p, c, 4000000;\n@p bra.uni LW;\nLD:\n}\n":"+r"(missing):"l"(p),"r"(need):"memory"); }
__device__ __forceinline__ uint32_t tagw(float x, uint32_t t){ return (__float_as_uint(x) & ~3u) | t; }
__device__ __forceinline__ float untag(uint32_t w){ return __uint_as_float(w & ~3u); }

template<int TA, int TB, uint32_t HA, uint32_t HB> __device__ __forceinline__ void wgmma_ss_n128(float (&d)[64], uint32_t da, uint32_t db, int scale_d){
  asm volatile("{\n.reg .pred p;\n.reg .b64 a, b;\nsetp.ne.b32 p, %70, 0;\nmov.b64 a, {%64, %68};\nmov.b64 b, {%65, %69};\n"
  "wgmma.mma_async.sync.aligned.m64n128k16.f32.bf16.bf16 {%0, %1, %2, %3, %4, %5, %6, %7, %8, %9, %10, %11, %12, %13, %14, %15, %16, %17, %18, %19, %20, %21, %22, %23, %24, %25, %26, %27, %28, %29, %30, %31, %32, %33, %34, %35, %36, %37, %38, %39, %40, %41, %42, %43, %44, %45, %46, %47, %48, %49, %50, %51, %52, %53, %54, %55, %56, %57, %58, %59, %60, %61, %62, %63}, a, b, p, 1, 1, %66, %67;\n}\n"
  : "+f"(d[0]), "+f"(d[1]), "+f"(d[2]), "+f"(d[3]), "+f"(d[4]), "+f"(d[5]), "+f"(d[6]), "+f"(d[7]), "+f"(d[8]), "+f"(d[9]), "+f"(d[10]), "+f"(d[11]), "+f"(d[12]), "+f"(d[13]), "+f"(d[14]), "+f"(d[15]), "+f"(d[16]), "+f"(d[17]), "+f"(d[18]), "+f"(d[19]), "+f"(d[20]), "+f"(d[21]), "+f"(d[22]), "+f"(d[23]), "+f"(d[24]), "+f"(d[25]), "+f"(d[26]), "+f"(d[27]), "+f"(d[28]), "+f"(d[29]), "+f"(d[30]), "+f"(d[31]), "+f"(d[32]), "+f"(d[33]), "+f"(d[34]), "+f"(d[35]), "+f"(d[36]), "+f"(d[37]), "+f"(d[38]), "+f"(d[39]), "+f"(d[40]), "+f"(d[41]), "+f"(d[42]), "+f"(d[43]), "+f"(d[44]), "+f"(d[45]), "+f"(d[46]), "+f"(d[47]), "+f"(d[48]), "+f"(d[49]), "+f"(d[50]), "+f"(d[51]), "+f"(d[52]), "+f"(d[53]), "+f"(d[54]), "+f"(d[55]), "+f"(d[56]), "+f"(d[57]), "+f"(d[58]), "+f"(d[59]), "+f"(d[60]), "+f"(d[61]), "+f"(d[62]), "+f"(d[63])
  : "r"(da), "r"(db), "n"(TA), "n"(TB), "n"(HA), "n"(HB), "r"(scale_d));
}
template<int TA, int TB, uint32_t HA, uint32_t HB> __device__ __forceinline__ void wgmma_sa_n128(float (&d)[64], uint32_t da, uint32_t db){
  asm volatile("{\n.reg .pred p;\n.reg .b64 a, b;\nsetp.ne.b32 p, 1, 0;\nmov.b64 a, {%64, %68};\nmov.b64 b, {%65, %69};\n"
  "wgmma.mma_async.sync.aligned.m64n128k16.f32.bf16.bf16 {%0, %1, %2, %3, %4, %5, %6, %7, %8, %9, %10, %11, %12, %13, %14, %15, %16, %17, %18, %19, %20, %21, %22, %23, %24, %25, %26, %27, %28, %29, %30, %31, %32, %33, %34, %35, %36, %37, %38, %39, %40, %41, %42, %43, %44, %45, %46, %47, %48, %49, %50, %51, %52, %53, %54, %55, %56, %57, %58, %59, %60, %61, %62, %63}, a, b, p, 1, 1, %66, %67;\n}\n"
  : "+f"(d[0]), "+f"(d[1]), "+f"(d[2]), "+f"(d[3]), "+f"(d[4]), "+f"(d[5]), "+f"(d[6]), "+f"(d[7]), "+f"(d[8]), "+f"(d[9]), "+f"(d[10]), "+f"(d[11]), "+f"(d[12]), "+f"(d[13]), "+f"(d[14]), "+f"(d[15]), "+f"(d[16]), "+f"(d[17]), "+f"(d[18]), "+f"(d[19]), "+f"(d[20]), "+f"(d[21]), "+f"(d[22]), "+f"(d[23]), "+f"(d[24]), "+f"(d[25]), "+f"(d[26]), "+f"(d[27]), "+f"(d[28]), "+f"(d[29]), "+f"(d[30]), "+f"(d[31]), "+f"(d[32]), "+f"(d[33]), "+f"(d[34]), "+f"(d[35]), "+f"(d[36]), "+f"(d[37]), "+f"(d[38]), "+f"(d[39]), "+f"(d[40]), "+f"(d[41]), "+f"(d[42]), "+f"(d[43]), "+f"(d[44]), "+f"(d[45]), "+f"(d[46]), "+f"(d[47]), "+f"(d[48]), "+f"(d[49]), "+f"(d[50]), "+f"(d[51]), "+f"(d[52]), "+f"(d[53]), "+f"(d[54]), "+f"(d[55]), "+f"(d[56]), "+f"(d[57]), "+f"(d[58]), "+f"(d[59]), "+f"(d[60]), "+f"(d[61]), "+f"(d[62]), "+f"(d[63])
  : "r"(da), "r"(db), "n"(TA), "n"(TB), "n"(HA), "n"(HB));
}
template<int TA, int TB, uint32_t HA, uint32_t HB> __device__ __forceinline__ void wgmma_sa_n40(float (&d)[20], uint32_t da, uint32_t db){
  asm volatile("{\n.reg .pred p;\n.reg .b64 a, b;\nsetp.ne.b32 p, 1, 0;\nmov.b64 a, {%20, %24};\nmov.b64 b, {%21, %25};\n"
  "wgmma.mma_async.sync.aligned.m64n40k16.f32.bf16.bf16 {%0, %1, %2, %3, %4, %5, %6, %7, %8, %9, %10, %11, %12, %13, %14, %15, %16, %17, %18, %19}, a, b, p, 1, 1, %22, %23;\n}\n"
  : "+f"(d[0]), "+f"(d[1]), "+f"(d[2]), "+f"(d[3]), "+f"(d[4]), "+f"(d[5]), "+f"(d[6]), "+f"(d[7]), "+f"(d[8]), "+f"(d[9]), "+f"(d[10]), "+f"(d[11]), "+f"(d[12]), "+f"(d[13]), "+f"(d[14]), "+f"(d[15]), "+f"(d[16]), "+f"(d[17]), "+f"(d[18]), "+f"(d[19])
  : "r"(da), "r"(db), "n"(TA), "n"(TB), "n"(HA), "n"(HB));
}
template<int TA, int TB, uint32_t HA, uint32_t HB> __device__ __forceinline__ void wgmma_sz_n40(float (&d)[20], uint32_t da, uint32_t db){
  asm volatile("{\n.reg .pred p;\n.reg .b64 a, b;\nsetp.ne.b32 p, 0, 0;\nmov.b64 a, {%20, %24};\nmov.b64 b, {%21, %25};\n"
  "wgmma.mma_async.sync.aligned.m64n40k16.f32.bf16.bf16 {%0, %1, %2, %3, %4, %5, %6, %7, %8, %9, %10, %11, %12, %13, %14, %15, %16, %17, %18, %19}, a, b, p, 1, 1, %22, %23;\n}\n"
  : "=f"(d[0]), "=f"(d[1]), "=f"(d[2]), "=f"(d[3]), "=f"(d[4]), "=f"(d[5]), "=f"(d[6]), "=f"(d[7]), "=f"(d[8]), "=f"(d[9]), "=f"(d[10]), "=f"(d[11]), "=f"(d[12]), "=f"(d[13]), "=f"(d[14]), "=f"(d[15]), "=f"(d[16]), "=f"(d[17]), "=f"(d[18]), "=f"(d[19])
  : "r"(da), "r"(db), "n"(TA), "n"(TB), "n"(HA), "n"(HB));
}
template<int TA, int TB, uint32_t HA, uint32_t HB> __device__ __forceinline__ void wgmma_sa_n32(float (&d)[16], uint32_t da, uint32_t db){
  asm volatile("{\n.reg .pred p;\n.reg .b64 a, b;\nsetp.ne.b32 p, 1, 0;\nmov.b64 a, {%16, %20};\nmov.b64 b, {%17, %21};\n"
  "wgmma.mma_async.sync.aligned.m64n32k16.f32.bf16.bf16 {%0, %1, %2, %3, %4, %5, %6, %7, %8, %9, %10, %11, %12, %13, %14, %15}, a, b, p, 1, 1, %18, %19;\n}\n"
  : "+f"(d[0]), "+f"(d[1]), "+f"(d[2]), "+f"(d[3]), "+f"(d[4]), "+f"(d[5]), "+f"(d[6]), "+f"(d[7]), "+f"(d[8]), "+f"(d[9]), "+f"(d[10]), "+f"(d[11]), "+f"(d[12]), "+f"(d[13]), "+f"(d[14]), "+f"(d[15])
  : "r"(da), "r"(db), "n"(TA), "n"(TB), "n"(HA), "n"(HB));
}
template<int TA, int TB, uint32_t HA, uint32_t HB> __device__ __forceinline__ void wgmma_ss_n32(float (&d)[16], uint32_t da, uint32_t db, int scale_d){
  asm volatile("{\n.reg .pred p;\n.reg .b64 a, b;\nsetp.ne.b32 p, %22, 0;\nmov.b64 a, {%16, %20};\nmov.b64 b, {%17, %21};\n"
  "wgmma.mma_async.sync.aligned.m64n32k16.f32.bf16.bf16 {%0, %1, %2, %3, %4, %5, %6, %7, %8, %9, %10, %11, %12, %13, %14, %15}, a, b, p, 1, 1, %18, %19;\n}\n"
  : "+f"(d[0]), "+f"(d[1]), "+f"(d[2]), "+f"(d[3]), "+f"(d[4]), "+f"(d[5]), "+f"(d[6]), "+f"(d[7]), "+f"(d[8]), "+f"(d[9]), "+f"(d[10]), "+f"(d[11]), "+f"(d[12]), "+f"(d[13]), "+f"(d[14]), "+f"(d[15])
  : "r"(da), "r"(db), "n"(TA), "n"(TB), "n"(HA), "n"(HB), "r"(scale_d));
}
template<int TB, uint32_t HB> __device__ __forceinline__ void wgmma_ra_n32(float (&d)[16], uint32_t a0, uint32_t a1, uint32_t a2, uint32_t a3, uint32_t db){
  asm volatile("{\n.reg .pred p;\n.reg .b64 a, b;\nsetp.ne.b32 p, 1, 0;\nmov.b64 b, {%20, %22};\n"
  "wgmma.mma_async.sync.aligned.m64n32k16.f32.bf16.bf16 {%0, %1, %2, %3, %4, %5, %6, %7, %8, %9, %10, %11, %12, %13, %14, %15}, {%16,%17,%18,%19}, b, p, 1, 1, %21;\n}\n"
  : "+f"(d[0]), "+f"(d[1]), "+f"(d[2]), "+f"(d[3]), "+f"(d[4]), "+f"(d[5]), "+f"(d[6]), "+f"(d[7]), "+f"(d[8]), "+f"(d[9]), "+f"(d[10]), "+f"(d[11]), "+f"(d[12]), "+f"(d[13]), "+f"(d[14]), "+f"(d[15])
  : "r"(a0), "r"(a1), "r"(a2), "r"(a3), "r"(db), "n"(TB), "n"(HB));
}
template<int TB, uint32_t HB> __device__ __forceinline__ void wgmma_rs_n32(float (&d)[16], uint32_t a0, uint32_t a1, uint32_t a2, uint32_t a3, uint32_t db, int scale_d){
  asm volatile("{\n.reg .pred p;\n.reg .b64 a, b;\nsetp.ne.b32 p, %23, 0;\nmov.b64 b, {%20, %22};\n"
  "wgmma.mma_async.sync.aligned.m64n32k16.f32.bf16.bf16 {%0, %1, %2, %3, %4, %5, %6, %7, %8, %9, %10, %11, %12, %13, %14, %15}, {%16,%17,%18,%19}, b, p, 1, 1, %21;\n}\n"
  : "+f"(d[0]), "+f"(d[1]), "+f"(d[2]), "+f"(d[3]), "+f"(d[4]), "+f"(d[5]), "+f"(d[6]), "+f"(d[7]), "+f"(d[8]), "+f"(d[9]), "+f"(d[10]), "+f"(d[11]), "+f"(d[12]), "+f"(d[13]), "+f"(d[14]), "+f"(d[15])
  : "r"(a0), "r"(a1), "r"(a2), "r"(a3), "r"(db), "n"(TB), "n"(HB), "r"(scale_d));
}
template<int TB, uint32_t HB> __device__ __forceinline__ void wgmma_ra_n40(float (&d)[20], uint32_t a0, uint32_t a1, uint32_t a2, uint32_t a3, uint32_t db){
  asm volatile("{\n.reg .pred p;\n.reg .b64 a, b;\nsetp.ne.b32 p, 1, 0;\nmov.b64 b, {%24, %26};\n"
  "wgmma.mma_async.sync.aligned.m64n40k16.f32.bf16.bf16 {%0, %1, %2, %3, %4, %5, %6, %7, %8, %9, %10, %11, %12, %13, %14, %15, %16, %17, %18, %19}, {%20,%21,%22,%23}, b, p, 1, 1, %25;\n}\n"
  : "+f"(d[0]), "+f"(d[1]), "+f"(d[2]), "+f"(d[3]), "+f"(d[4]), "+f"(d[5]), "+f"(d[6]), "+f"(d[7]), "+f"(d[8]), "+f"(d[9]), "+f"(d[10]), "+f"(d[11]), "+f"(d[12]), "+f"(d[13]), "+f"(d[14]), "+f"(d[15]), "+f"(d[16]), "+f"(d[17]), "+f"(d[18]), "+f"(d[19])
  : "r"(a0), "r"(a1), "r"(a2), "r"(a3), "r"(db), "n"(TB), "n"(HB));
}
template<int TB, uint32_t HB> __device__ __forceinline__ void wgmma_rz_n40(float (&d)[20], uint32_t a0, uint32_t a1, uint32_t a2, uint32_t a3, uint32_t db){
  asm volatile("{\n.reg .pred p;\n.reg .b64 a, b;\nsetp.ne.b32 p, 0, 0;\nmov.b64 b, {%24, %26};\n"
  "wgmma.mma_async.sync.aligned.m64n40k16.f32.bf16.bf16 {%0, %1, %2, %3, %4, %5, %6, %7, %8, %9, %10, %11, %12, %13, %14, %15, %16, %17, %18, %19}, {%20,%21,%22,%23}, b, p, 1, 1, %25;\n}\n"
  : "=f"(d[0]), "=f"(d[1]), "=f"(d[2]), "=f"(d[3]), "=f"(d[4]), "=f"(d[5]), "=f"(d[6]), "=f"(d[7]), "=f"(d[8]), "=f"(d[9]), "=f"(d[10]), "=f"(d[11]), "=f"(d[12]), "=f"(d[13]), "=f"(d[14]), "=f"(d[15]), "=f"(d[16]), "=f"(d[17]), "=f"(d[18]), "=f"(d[19])
  : "r"(a0), "r"(a1), "r"(a2), "r"(a3), "r"(db), "n"(TB), "n"(HB));
}
template<int TB, uint32_t HB> __device__ __forceinline__ void wgmma_rz_n8(float (&d)[4], uint32_t a0, uint32_t a1, uint32_t a2, uint32_t a3, uint32_t db){
  asm volatile("{\n.reg .pred p;\n.reg .b64 a, b;\nsetp.ne.b32 p, 0, 0;\nmov.b64 b, {%8, %10};\n"
  "wgmma.mma_async.sync.aligned.m64n8k16.f32.bf16.bf16 {%0, %1, %2, %3}, {%4,%5,%6,%7}, b, p, 1, 1, %9;\n}\n"
  : "=f"(d[0]), "=f"(d[1]), "=f"(d[2]), "=f"(d[3])
  : "r"(a0), "r"(a1), "r"(a2), "r"(a3), "r"(db), "n"(TB), "n"(HB));
}

constexpr int SEQ = 2048, DM = 1024, FF = 3584;
constexpr float LOG2E = 1.4426950408889634f;
constexpr uint32_t POLL_LIMIT = 1u << 22;
constexpr int QW = 0;
constexpr int LAG = 2;
constexpr int ML = 2;
constexpr int REL = 6;
constexpr int SKM = 0x154;
constexpr int RS_N = 22;
constexpr int RS_D1 = 420;
constexpr int RS_D2 = 300;
constexpr int PF_T0 = 5000;
constexpr int PF_DT = 800;
constexpr int FF_N = 5;
constexpr int FF_DT = 500;
constexpr int FF_D2 = 350;
constexpr uint64_t FF_ORD = 0x76543210ba98ull;
constexpr int OUT_D = 400;
constexpr int NFFN = 112;

constexpr uint32_t SB0 = 1024;
constexpr uint32_t KV_STAGE = 49152, R5 = 32768;
constexpr uint32_t OFF_X = 163840, OFF_S = 196608, OFF_WPHI = OFF_S + 20480, OFF_M = 229376, SMEM_BYTES = 232448;
constexpr uint32_t OFF_RS256 = 212992, OFF_ONES = OFF_RS256 + 1024, OFF_WPHIK1 = OFF_ONES + 1024, OFF_KVZ = OFF_S;
constexpr uint32_t OFF_WPHIK = OFF_S, OFF_BXK = OFF_S + 2048, OFF_AXK = OFF_S + 4096, OFF_G = OFF_S + 8192;
constexpr uint32_t OFF_AXQ = OFF_WPHI, OFF_BXQ = OFF_WPHI + 2048, OFF_WPHIQ = OFF_WPHI + 4096;
constexpr uint32_t B_FULLKV = OFF_M  , B_EMPTYKV = OFF_M + 32  ;
constexpr uint32_t B_EMPTY5 = OFF_M + 64  , B_UO = B_EMPTY5 + 48  , B_RC = B_UO + 32  ;
constexpr uint32_t B_OUT = B_RC + 16  , B_SD = B_OUT + 16, B_AUX = B_SD + 8, B_AUXQ = B_AUX + 8, B_RX = B_AUXQ + 8;
constexpr uint32_t B_FULL5 = B_RX + 8  , B_F = B_FULL5 + 40  , B_WD = B_F + 64  ;
constexpr uint32_t B_WC = B_WD + 32  , B_DR = B_WC + 32  , B_W = B_DR + 24, B_OS = B_W + 8, B_R = B_W + 16, B_KD = B_W + 24, B_T = B_W + 32, B_G = B_W + 40, B_END = B_W + 48;
constexpr int NB3 = ((B_END - OFF_M) / 8 + 1) / 3;
constexpr uint32_t B_S0 = OFF_M + 8 + 24 * NB3;
static_assert(B_S0 >= B_END && B_S0 < OFF_M + 600, "barriers");
__host__ __device__ constexpr uint32_t bar_count(int i) {
  const uint32_t b = OFF_M + 8 * i;
  return b < B_EMPTYKV ? 1 : b < B_EMPTY5 ? 12 : b < B_SD ? 4 : b < B_RX || b == B_W ? 2 : b == B_RX ? 8 : 1;
}
constexpr uint32_t B_GB = OFF_M + 2560  , B_GA = B_GB + 128  ;
constexpr uint32_t OFF_SUMWR = OFF_M + 608, OFF_EP = OFF_M + 624, OFF_KEY = OFF_M + 628;
constexpr uint32_t OFF_RSQ = OFF_M + 640, OFF_SEL = OFF_M + 1648, OFF_T = OFF_M + 1792, OFF_WR = OFF_M + 2048;
constexpr uint32_t OFF_XSEL = 2 * R5, OFF_GU = OFF_XSEL + 4096, OFF_OUT = 3 * R5;
constexpr uint64_t FF_SLOT = 0xdcdc3210dcbaull;
constexpr int KVP = 6 * 128;

enum { NB_G2E = 1, NB_XS = 2, NB_WG01 = 3, NB_ACT = 4, NB_Q0 = 5  , NB_ST = 14, NB_LAG = 8, NB_DN = 9, NB_ZERO = 10, NB_PUB = 11, NB_TOK = 10  , NB_L0 = 12  , NB_WG2 = 7, NB_QGO = 15 };

struct Scratch {
  bf16     o[SEQ * DM];
  float4   rstat[SEQ];
  uint32_t key[32 * 128];
  uint32_t cand[128 * 512];
  float4   yacc[4 * 3 * 128];
  float4   kvacc[32 * KVP];
  uint2    stats[SEQ];
  uint32_t cskv[2 * DM];
  uint32_t csq[4 * DM];
  uint32_t oset[128 * 16];
  uint32_t oflag[16 * 6 * 32];
  uint32_t epoch;
};
__device__ __align__(1024) Scratch g_scr;

struct Params {
  const bf16 *x, *wqkv, *wo_p, *wr;
  bf16* out_p;
  Scratch* g;
  uint32_t zero;
  CUtensorMap x128, x64, wkv, wq, wo[2], wd, wg, wu, phi, tg, tu, td, xs, ws, qs, out, o;
};

constexpr float EXP_LIM = 1.1529215e18f, ARG_LIM2 = 3600.f;
__device__ __forceinline__ void dual_exp2(const float (&p)[16], uint32_t (&ep)[8], uint32_t (&em)[8]) {
  #pragma unroll
  for (int k = 0; k < 8; k++) {
    const float a = ex2(p[2*k]), b = ex2(p[2*k+1]);
    const float r = rcp(a * b);
    ep[k] = pack_bf16(a, b); em[k] = pack_bf16(r * b, r * a);
  }
}
__device__ __forceinline__ void dual_exp2_shifted(const float (&pp)[2][16], uint32_t (&ph)[4][8]) {
  #pragma unroll
  for (int h = 0; h < 2; h++) {
    const float* p = pp[h];
    float m[4] = {p[0], p[2], p[0], p[2]};
    #pragma unroll
    for (int i = 0; i < 16; i++) { m[(i >> 1) & 1] = fmaxf(m[(i >> 1) & 1], p[i]); m[2 + ((i >> 1) & 1)] = fminf(m[2 + ((i >> 1) & 1)], p[i]); }
    #pragma unroll
    for (int o = 1; o < 4; o <<= 1) {
      m[0] = fmaxf(m[0], __shfl_xor_sync(~0u, m[0], o)); m[1] = fmaxf(m[1], __shfl_xor_sync(~0u, m[1], o));
      m[2] = fminf(m[2], __shfl_xor_sync(~0u, m[2], o)); m[3] = fminf(m[3], __shfl_xor_sync(~0u, m[3], o));
    }
    #pragma unroll
    for (int k = 0; k < 8; k++) {
      ph[2*h][k] = pack_bf16(ex2(p[2*k] - m[k & 1]), ex2(p[2*k+1] - m[k & 1]));
      ph[2*h+1][k] = pack_bf16(ex2(m[2 + (k & 1)] - p[2*k]), ex2(m[2 + (k & 1)] - p[2*k+1]));
    }
  }
}
__device__ __forceinline__ uint32_t add_bf16x2(uint32_t a, uint32_t b) { uint32_t r; asm("add.rn.bf16x2 %0, %1, %2;" : "=r"(r) : "r"(a), "r"(b)); return r; }
__device__ __forceinline__ void row_sums(float (&s)[2][4], const uint32_t (&ph)[4][8], uint32_t sel) {
  uint32_t u[8];
  #pragma unroll
  for (int i = 0; i < 8; i++) { const uint32_t* f = &ph[i >> 1][i & 1]; u[i] = add_bf16x2(add_bf16x2(f[0], f[2]), add_bf16x2(f[4], f[6])); }
  wg_fence();
  wgmma_rz_n8<0, H0>(s[0], u[0], u[1], u[2], u[3], sel);
  wgmma_rz_n8<0, H0>(s[1], u[4], u[5], u[6], u[7], sel);
  wg_commit();
}
__device__ __forceinline__ uint32_t mul_bf16x2(uint32_t a, uint32_t b) { uint32_t r; asm("mul.rn.bf16x2 %0, %1, %2;" : "=r"(r) : "r"(a), "r"(b)); return r; }
__device__ __forceinline__ void normalize(uint32_t (&ph)[4][8], const float (&s)[2][4]) {
  #pragma unroll
  for (int i = 0; i < 4; i++) {
    const float i0 = rcp(s[i >> 1][i & 1]), i1 = rcp(s[i >> 1][2 + (i & 1)]);
    const uint32_t n0 = pack_bf16(i0, i0), n1 = pack_bf16(i1, i1);
    #pragma unroll
    for (int k = 0; k < 4; k++) { ph[i][2*k] = mul_bf16x2(ph[i][2*k], n0); ph[i][2*k+1] = mul_bf16x2(ph[i][2*k+1], n1); }
  }
}
__device__ __forceinline__ void split_bf16(float a, float b, uint32_t& hi, uint32_t& lo) { hi = pack_bf16(a, b); lo = pack_bf16(a - bf_lo(hi), b - bf_hi(hi)); }
__device__ __forceinline__ void put_colsums(uint32_t base, int lane, float a, float b, float c, float d) {
  uint32_t h0, l0, h1, l1;
  split_bf16(a, b, h0, l0); split_bf16(c, d, h1, l1);
  const uint32_t ad = base + (lane >> 1) * 128 + (lane & 1) * 8;
  sts64(ad, h0, h1); sts64(ad + 16, l0, l1); sts64(ad + 32, h0, h1); sts64(ad + 48, l0, l1);
  sts128(base + (lane >> 1) * 128 + 64 + (lane & 1) * 32, 0, 0, 0, 0); sts128(base + (lane >> 1) * 128 + 80 + (lane & 1) * 32, 0, 0, 0, 0);
}
__device__ __forceinline__ float reduce8(const float (&v)[8], int lane) {
  const bool b4 = lane & 16, b3 = lane & 8, b2 = lane & 4;
  float a[4], b[2];
  #pragma unroll
  for (int i = 0; i < 4; i++) a[i] = (b4 ? v[4 + i] : v[i]) + __shfl_xor_sync(~0u, b4 ? v[i] : v[4 + i], 16);
  #pragma unroll
  for (int i = 0; i < 2; i++) b[i] = (b3 ? a[2 + i] : a[i]) + __shfl_xor_sync(~0u, b3 ? a[i] : a[2 + i], 8);
  return (b2 ? b[1] : b[0]) + __shfl_xor_sync(~0u, b2 ? b[0] : b[1], 4);
}
__device__ __forceinline__ bool tag_bad(uint4 v, uint32_t tg) { return (((v.x ^ tg) | (v.y ^ tg) | (v.z ^ tg) | (v.w ^ tg)) & 3) != 0; }


__global__ void __launch_bounds__(512, 1) fused_kernel(const __grid_constant__ Params P) {
  extern __shared__ __align__(1024) uint8_t smem_raw[];
  const uint32_t sb = smem_u32(smem_raw);
  const int tid = threadIdx.x, lane = tid & 31;
  {
    const int n = 16 * blockIdx.x + (lane & 15);
    const bf16* p = (lane < 16 ? P.x : P.wqkv) + (lane < 16 ? n * DM : (n >> 5) * (3 * DM) + DM + 64 * (n & 31));
    asm volatile("{\n.reg .pred p;\nsetp.lt.u32 p, %1, 32;\n@p prefetch.global.L2 [%0];\n}\n" :: "l"(p), "r"(tid));
  }
  const int cp = blockIdx.x >> 1, rank = blockIdx.x & 1;
  const int cr = cp < 4 ? 32 + 8 * cp : cp - 4 + max((cp * 37 - 1076) >> 8, 0);
  const int c = (cr & 62) + 64 * (cr & 1) + rank;
  const int m256 = c >> 4, nkv = c & 15, m128 = c >> 3, j = c & 7;
  if ((tid >> 7) == 2 && elect_one()) {
    if (tid >= 288) {
      const int w = (tid >> 5) - 9;
      #pragma unroll
      for (int i = 0; i < NB3; i++) mbar_init(sb + B_FULLKV + 8 + 8 * NB3 * w + 8 * i, w == 0 ? bar_count(1 + i) : w == 1 ? bar_count(1 + NB3 + i) : bar_count(1 + 2 * NB3 + i));
    } else {
      prefetch_map(&P.wkv); prefetch_map(&P.x128);
      mbar_init(sb + B_S0, 1); mbar_init(sb + B_FULLKV, 1);
      mbar_expect_tx(sb + B_S0, 32768);
      tma_4d(sb + 32768, &P.wkv, 0, 0, nkv, 1, sb + B_S0);
      tma_2d(sb, &P.x128, 0, 256 * m256, sb + B_S0);
      mbar_expect_tx(sb + B_FULLKV, 16384);
      tma_2d(sb + 16384, &P.x128, 0, 256 * m256 + 128, sb + B_FULLKV);
    }
    asm volatile("fence.mbarrier_init.release.cluster;" ::: "memory");
  }
  const int warp = __shfl_sync(~0u, tid >> 5, 0), wg = warp >> 2, wp = warp & 3;
  const int f = 16 * ((cr + 7) & 7) + 2 * (cr >> 3) + rank;
  const int ha = 4 * (nkv >> 1) + (nkv & 1);
  Scratch* const G = P.g;
  if ((sb & 0x3ffff) != SB0) asm volatile("trap;");
  __syncthreads();
  cluster_arrive();
  if (warp == 8 && elect_one()) {
    mbar_expect_tx(sb + B_FULLKV + 8, KV_STAGE);
    tma_4d(sb + KV_STAGE + 32768, &P.wkv, 0, 64, nkv, 1, sb + B_FULLKV + 8);
    tma_2d(sb + KV_STAGE, &P.x128, 64, 256 * m256, sb + B_FULLKV + 8);
    tma_2d(sb + KV_STAGE + 16384, &P.x128, 64, 256 * m256 + 128, sb + B_FULLKV + 8);
  }
  if (wg == 3) {
    asm volatile("setmaxnreg.dec.sync.aligned.u32 32;");
    cluster_wait();
    const bool el = elect_one();
    const uint64_t ef = policy_evict_first(), en = policy_evict_normal();
    auto fetch_o = [&](const int t0) {
      const int sh = t0 & 1;
      uint32_t missing = ~0u;
      const uint32_t* hint = &G->oflag[(m128 * 6 + ((t0 + 1) & 6) + rank) * 32 + ((4 * (j & 6) + lane) & 31)];
      #pragma unroll 1
      for (int i = 2 - 2 * sh; i < 8; i += 1 + sh) {
        const int blk = sh ? 6 + 2 * t0 + (i >> 1) : i, wrap = t0 == 3 ? 2 : (blk >= 5) + (blk >= 11), s = blk + 1 - 6 * wrap;
        flags_wait(missing, hint, (15u + 240u * sh) << (4 * i));
        if (blk > 5) mbar_wait(sb + B_EMPTY5 + 8 * s, wrap & 1);
        if (el) {
          tma_2d_mc_h(sb + s * R5 + rank * 8192, &P.o, 0, (m128 * 16 + t0 + 2 * (((j & 6) + i) & 7)) * 32 + 16 * rank, sb + B_GA + 16 * blk + 8 * rank, ef);
        }
      }
    };
    if (wp == 0) {
      {
        wait_until((uint32_t)clock() + 300);
        #pragma unroll 1
        for (int kb = 2; kb < 16; kb++) {
          const uint32_t st = sb + (kb & 3) * KV_STAGE, fb = sb + B_FULLKV + 8 * (kb & 3);
          mbar_wait(fb + (B_EMPTYKV - B_FULLKV), ~(kb >> 2) & 1);
          if (el) {
            mbar_expect_tx(fb, KV_STAGE);
            tma_2d_mc(st + rank * 16384, &P.x128, 64 * kb, 256 * m256 + 128 * rank, fb);
            tma_4d_h(st + 32768, &P.wkv, 0, 64 * kb, nkv, 1, fb, ef);
          }
        }
        uint64_t ord = 0xf3120edcba987654ull;
        uint32_t so = 0, par = 1;
        #pragma unroll 1
        for (int i = 0; i < 16; i++) {
          const uint32_t st = sb + so * 4096, fb = sb + B_FULL5 + so;
          const int k0 = (64 * (uint32_t)ord + 128 * (j & 6)) & 960;
          mbar_wait(i < 5 ? sb + B_EMPTYKV + so - (i > 1 ? 8 : 0) : fb + (B_EMPTY5 - B_FULL5), par);
          if (el) {
            mbar_expect_tx(fb, R5);
            tma_2d_mc_h(st + rank * 8192, &P.x64, k0, 128 * m128 + 64 * rank, fb, i >= 11 ? ef : en);
            tma_3d_h(st + 16384, &P.wq, 0, k0, 2 * j, fb, ef);
          }
          ord >>= 4; so += 8;
          if (so == 40) { so = 0; par ^= 1; }
        }
        mbar_wait(sb + B_FULL5 + 8 + 8 * rank, 0);
        if (el) mbar_arrive(sb + B_R);
        #pragma unroll 1
        for (int i = 0; i < 19; i++) {
          const int row = i < 8 ? 128 * (((j & 6) + i) & 7) : 256 * (((j >> 1) + i) & 3) + 32 + 16 * (i & 4);
          mbar_wait(sb + B_EMPTY5 + so, par);
          if (el) {
            if (i < 16) {
              tma_5d_h(sb + so * 4096 + 16384, &P.wo[i >> 3], 128 * j, row, sb + B_GB + 8 * i, ef);
              tma_5d_h(sb + so * 4096 + 24576, &P.wo[i >> 3], 128 * j + 64, row, sb + B_GB + 8 * i, ef);
            } else mbar_arrive(sb + B_DR + 8 * (i - 16));
          }
          so += 8;
          if (so == 48) { so = 0; par ^= 1; }
        }
      }
    } else if (wp == 3) {
      const uint32_t t_start = (uint32_t)clock();
      mbar_wait(sb + B_S0, 0);
      if (el) {
        mbar_expect_tx(sb + B_W, 12288);
        #pragma unroll 1
        for (int i = 0; i < 6; i++) tma_2d(sb + (i == 0 ? OFF_WPHIK : i == 1 ? OFF_WPHIK1 : OFF_WPHIQ + 2048 * (i - 2)), &P.phi, 0, 32 * (i < 2 ? 2 * nkv + i : 4 * j + 2 * (i & 1) + ((i - 2) >> 1)), sb + B_W);
        prefetch_map(&P.x64); prefetch_map(&P.wq); prefetch_map(&P.wo[0]); prefetch_map(&P.wo[1]);
        prefetch_map(&P.o); prefetch_map(&P.wd); prefetch_map(&P.out); prefetch_map(&P.wg); prefetch_map(&P.wu);
      }
      #pragma unroll 1
      for (int i = 0; i < 8; i++) {
        if (lane < 16) st128_rlx(&G->cand[(m128 * 8 + i) * 512 + 64 * j + 4 * lane], ~0u, ~0u, ~0u, ~0u);
      }
      if (lane < 16) st128_rlx(&G->rstat[16 * c + lane], 0, 0, 0, 0);
      if (lane < 12) st128_rlx(&G->yacc[12 * c + lane], 0, 0, 0, 0);
      {
        const uint32_t nt = ld32_rlx(&G->epoch);
        if (lane < 8) { st128_rlx(&G->stats[16 * c + 2 * lane], nt, nt, nt, nt); st128_rlx(&G->csq[32 * c + 4 * lane], nt, nt, nt, nt); }
        if (lane < 4) { st128_rlx(&G->cskv[128 * nkv + 16 * m256 + 4 * lane], nt, nt, nt, nt); st128_rlx(&G->oset[16 * c + 4 * lane], nt, nt, nt, nt); }
      }
      if (lane < 8) st128_rlx(&G->key[(4 * j + (lane >> 1)) * 128 + m128 * 8 + 4 * (lane & 1)], 0, 0, 0, 0);
      if (c < 32) {
        #pragma unroll 1
        for (int i = lane; i < KVP; i += 32) st128_rlx(&G->kvacc[(ha + 2 * m256) * KVP + i], 0, 0, 0, 0);
      }
      fence_gpu();
      bar_arrive(NB_ZERO, 160);
      if (el) {
        #pragma unroll 1
        for (int i = 0; i < 30; i++) {
          wait_until(t_start + PF_T0 + PF_DT * i + 7 * f);
          if (i < 4) { bulk_prefetch(P.wqkv + (size_t)(256 * i + c) * (3 * DM), 2048); bulk_prefetch(P.wqkv + (size_t)(256 * i + 128 + c) * (3 * DM), 2048); }
          else if (i < 6) bulk_prefetch(P.wo_p + (size_t)c * 8192 + (i - 4) * 4096, 8192);
          else if (f < NFFN) {
            if (i < 22) {
              #pragma unroll 1
              for (int e = 0; e < 4; e++) tma_2d(sb + OFF_T, rank ? &P.tu : &P.tg, 32 * (f & ~1), 64 * (i - 6) + 16 * e, sb + B_T);
            } else { tma_2d(sb + OFF_T, &P.td, 0, 256 * f + 32 * (i - 22), sb + B_T); tma_2d(sb + OFF_T, &P.td, 0, 256 * f + 32 * (i - 22) + 16, sb + B_T); }
          }
        }
      }
      __syncwarp();
      mbar_wait2(sb + B_OS, 0, sb + B_RX, 0);
      mbar_wait2(sb + B_EMPTY5 + 24, 0, sb + B_EMPTY5 + 32, 0);
      mbar_wait2(sb + B_EMPTY5 + 40, 0, sb + B_EMPTY5, 1);
      fetch_o(0);
      fetch_o(3);
    } else {
      const int half = wp - 1;
      const uint32_t ep1 = ld32_rlx(&G->epoch) + 1, tg = ep1 & 3;
      {
        uint32_t it = 0;
        sts128(sb + OFF_ONES + half * 512 + lane * 16, 0x3f803f80u, 0x3f803f80u, 0x3f803f80u, 0x3f803f80u);
        if (lane < 9) { const uint32_t v = (lane & 1) ? 0 : 0x3f803f80u; sts128(sb + OFF_SEL + lane * 16, v, v, v, v); }
        auto reset_o = [&](int i0, int i1, uint32_t dt) {
          uint32_t t0 = (uint32_t)clock();
          #pragma unroll 1
          for (int i = i0; i < i1; i++) {
            st128_rlx(G->o + (m128 * 16 + 2 * j + half) * 8192 + 256 * i + 8 * lane, ~0u, ~0u, ~0u, ~0u);
            wait_until(t0 += dt);
          }
        };
        if (el) {
          #pragma unroll 1
          for (int i = 24 * half; i < 24 * half + 24; i++) { mbar_init(sb + B_GB + 8 * i, 1); mbar_expect_tx(sb + B_GB + 8 * i, i < 16 ? 16384 : 8192); }
          asm volatile("fence.mbarrier_init.release.cluster;" ::: "memory");
        }
        mbar_wait(sb + B_S0, 0);
        reset_o(0, RS_N, RS_D1);
        bar_sync(NB_PUB, 192);
        const uint4* src = reinterpret_cast<const uint4*>(&G->stats[256 * m256 + 128 * half]) + lane;
        const uint4* srk = reinterpret_cast<const uint4*>(&G->cskv[128 * nkv]) + lane;
        uint4 v0, v1, vk;
        it = 0;
        do { v0 = ld128_rlx(src); v1 = ld128_rlx(src + 32); vk = ld128_rlx(srk); }
        while ((tag_bad(v0, tg) || tag_bad(v1, tg) || tag_bad(vk, tg)) && ++it < POLL_LIMIT);
        fence_acquire_gpu();
        if (half) put_colsums(sb + OFF_BXK, lane, untag(vk.x), untag(vk.y), untag(vk.z), untag(vk.w));
        #pragma unroll
        for (int i = 0; i < 2; i++) {
          const uint4 v = i ? v1 : v0;
          uint32_t hi, lo;
          split_bf16(-0.5f * untag(v.x), -0.5f * untag(v.z), hi, lo);
          const uint32_t h0 = __byte_perm(hi, hi, 0x1010), h1 = __byte_perm(hi, hi, 0x3232), l0 = __byte_perm(lo, lo, 0x1010), l1 = __byte_perm(lo, lo, 0x3232);
          const uint32_t a = sb + OFF_AXK + half * 2048 + i * 1024 + lane * 32;
          sts128(a, h0, l0, 0, 0); sts128(a + 16, h1, l1, 0, 0);
          sts64(sb + OFF_RS256 + half * 512 + i * 256 + lane * 8, v.y & ~3u, v.w & ~3u);
          if (half == (m128 & 1)) {
            const uint32_t aq = sb + OFF_AXQ + i * 1024 + lane * 32;
            sts128(aq, h0, l0, 0, 0); sts128(aq + 16, h1, l1, 0, 0);
            sts64(sb + OFF_RSQ + i * 256 + lane * 8, v.y & ~3u, v.w & ~3u);
          }
        }
        fence_async_smem();
        __syncwarp();
        if (el) { sts32(sb + OFF_EP, ep1); mbar_arrive(sb + B_AUX); }
        reset_o(RS_N, 32, RS_D2);
        if (half == 0 && rank == 0 && lane < 12) st128_rlx(&G->oflag[(m128 * 6 + (lane >> 1)) * 32 + 4 * j + 4 * (lane & 1)], 0, 0, 0, 0);
        fence_gpu();
        __syncwarp();
        if (el) { st32_rlx(&G->oset[16 * c + 8 * half], ep1); if (half) mbar_arrive(sb + B_AUXQ); }
        if (!half) {
          const uint4* src = reinterpret_cast<const uint4*>(&G->csq[128 * j]) + lane;
          uint4 v0, v1, v2, v3;
          do { v0 = ld128_rlx(src); v1 = ld128_rlx(src + DM / 4); v2 = ld128_rlx(src + DM / 2); v3 = ld128_rlx(src + 3 * DM / 4); }
          while ((tag_bad(v0, tg) || tag_bad(v1, tg) || tag_bad(v2, tg) || tag_bad(v3, tg)) && ++it < POLL_LIMIT);
          put_colsums(sb + OFF_BXQ, lane, (untag(v0.x) + untag(v1.x)) + (untag(v2.x) + untag(v3.x)), (untag(v0.y) + untag(v1.y)) + (untag(v2.y) + untag(v3.y)),
                      (untag(v0.z) + untag(v1.z)) + (untag(v2.z) + untag(v3.z)), (untag(v0.w) + untag(v1.w)) + (untag(v2.w) + untag(v3.w)));
          fence_async_smem();
          __syncwarp();
          if (el) mbar_arrive(sb + B_AUXQ);
        }
      }
      if (half == 0) {
        for (uint32_t it = 0; __any_sync(~0u, ld32_rlx(&G->oset[m128 * 128 + 8 * (lane & 15)]) != ep1) && it < POLL_LIMIT; it++) {}
        fence_acquire_gpu();
        if (el) mbar_arrive(sb + B_OS);
      }
      if (!half) {
        #pragma unroll 1
        for (int hh = 0; hh < 2; hh++) {
          const uint32_t src = sb + (1 + rank) * R5 + hh * 8192, fa = sb + B_GA + 16 * rank + 8 * hh;
          mbar_wait2(sb + B_UO + 8 * hh, 0, sb + B_GB + 8 * rank, 0);
          if (el) bulk_s2peer(mapa(src, rank ^ 1), src, 8192, mapa(fa, rank ^ 1));
        }
        fetch_o(1);
      }
      else if (f < NFFN) {
        mbar_wait(sb + B_UO + 24, 0);
        mbar_wait2(sb + B_UO, 0, sb + B_UO + 8, 0);
        uint32_t t0 = (uint32_t)clock();
        #pragma unroll 1
        for (int i = 0; i < 12; i++) {
          const int e = (FF_ORD >> (4 * i)) & 15;
          const uint32_t dst = sb + 16384 * ((FF_SLOT >> (4 * e)) & 15), fb = sb + B_F + 8 * e;
          if (i >= 2) mbar_wait(sb + B_WC + 8 * ((0x100066553244ull >> (4 * e)) & 15), 0);
          wait_until(t0);
          t0 = (uint32_t)clock() + (i < FF_N ? FF_DT : FF_D2);
          if (el) {
            mbar_expect_tx(fb, 16384);
            if (e >= 8) tma_3d_h(dst, &P.wd, 0, 32 * f, 4 * e - 32, fb, ef);
            else { tma_2d_h(dst, &P.wg, 32 * f, 128 * e, fb, ef); tma_2d_h(dst + 8192, &P.wu, 32 * f, 128 * e, fb, ef); }
          }
        }
      }
      __syncwarp();
    }
    if (wp & 1) {
      __syncwarp();
      mbar_wait(sb + B_OUT + 8 * (wp >> 1), 0);
      uint32_t t0 = (uint32_t)clock();
      #pragma unroll 1
      for (int i = 0; i < 8; i++) {
        wait_until(t0);
        if (el) tma_store_2d(&P.out, 128 * j + 64 * (i & 1), 128 * m128 + 32 * (wp & 2) + 8 * (i & 6), sb + OFF_OUT + (i & 1) * 16384 + (wp & 2) * 4096 + (i & 6) * 1024, ef);
        t0 += OUT_D;
      }
      if (el) { bulk_commit(); bulk_wait_all(); fence_async_global(); mbar_arrive(sb + B_SD); }
    }
    __syncwarp();
    cluster_arrive(); cluster_wait();
    return;
  }

  asm volatile("setmaxnreg.inc.sync.aligned.u32 160;");
  cluster_wait();
  const int t = tid & 127, g = lane >> 2;
  const uint32_t sa = (16 * wp + (lane & 15)) * 128 + (((lane >> 4) ^ (lane & 7)) << 4);

  if (wg == 2) {
    float s[2] = {0.f, 0.f}, s2[2] = {0.f, 0.f}, ck[8] = {0.f, 0.f, 0.f, 0.f, 0.f, 0.f, 0.f, 0.f}, cs[8] = {0.f, 0.f, 0.f, 0.f, 0.f, 0.f, 0.f, 0.f};
    const uint32_t ebr = mapa(sb + B_EMPTYKV, lane & 1), tg = (ld32_rlx(&G->epoch) + 1) & 3;
    auto addx = [&](const uint4 v) {
      const uint32_t w[4] = {v.x, v.y, v.z, v.w};
      #pragma unroll
      for (int e = 0; e < 4; e++) { const float a = bf_lo(w[e]), d = bf_hi(w[e]); s[0] += a; s[1] += d; s2[0] = fmaf(a, a, s2[0]); s2[1] = fmaf(d, d, s2[1]); }
    };
    auto addc = [&](const uint4 v, float (&o)[8]) {
      o[0] += bf_lo(v.x); o[1] += bf_hi(v.x); o[2] += bf_lo(v.y); o[3] += bf_hi(v.y); o[4] += bf_lo(v.z); o[5] += bf_hi(v.z); o[6] += bf_lo(v.w); o[7] += bf_hi(v.w);
    };
    {
      const uint32_t ra = (16 * nkv + (t >> 3)) * 128 + (t & 7) * 16;
      const uint32_t ca = 32768 + (m256 >> 2) * 8192 + (t >> 1) * 128 + (((2 * (m256 & 3) + (t & 1)) ^ ((t >> 1) & 7)) << 4);
      int rd = 0;
      mbar_wait(sb + B_S0, 0);
      #pragma unroll 1
      for (int kb = 0; kb < 10; kb++) {
        const uint32_t st = sb + (kb & 3) * KV_STAGE;
        mbar_wait(sb + B_FULLKV + 8 * (kb & 3), (kb >> 2) & 1);
        const uint4 x0 = lds128(st + ra), w0 = lds128(st + ca);
        addx(x0); addc(w0, ck);
        __syncwarp();
        if (lane < 2) mbar_arrive_remote(ebr + 8 * (kb & 3), 1);
        if ((SKM >> kb) & 1) {
          if (rd) {
            mbar_wait(sb + B_G, (rd - 1) & 1);
            const uint32_t a = sb + OFF_G + (t >> 3) * 256 + (t & 7) * 16;
            const uint4 x1 = lds128(a), x2 = lds128(a + 128), w1 = lds128(sb + OFF_G + 4096 + t * 16), w2 = lds128(sb + OFF_G + 6144 + t * 16);
            addx(x1); addx(x2); addc(w1, ck); addc(w2, ck);
            bar_sync(NB_WG2, 128);
          }
          if (wp == 0 && elect_one()) {
            mbar_expect_tx(sb + B_G, 8192);
            if (rd < 3) {
              tma_2d(sb + OFF_G, &P.xs, 640 + 128 * rd, 256 * m256 + 16 * nkv, sb + B_G);
              tma_2d(sb + OFF_G + 4096, &P.ws, (1 + (m256 >> 2)) * DM + 64 * nkv + 16 * (m256 & 3), 640 + 128 * rd, sb + B_G);
            } else tma_2d(sb + OFF_G, &P.qs, 32 * (c & 31), 256 * (c >> 5), sb + B_G);
          }
          rd++;
        }
      }
    }
    const uint32_t scr = sb + OFF_WR;
    float sx = s[0] + s[1], sq = s2[0] + s2[1];
    #pragma unroll
    for (int o = 1; o < 8; o <<= 1) { sx += __shfl_xor_sync(~0u, sx, o); sq += __shfl_xor_sync(~0u, sq, o); }
    float v = reduce8(ck, lane);
    v += __shfl_xor_sync(~0u, v, 2);
    if (!(lane & 2)) stsf(scr + (wp * 16 + 8 * (lane & 1) + (lane >> 2)) * 4, v);

    bar_sync(NB_ZERO, 160);
    if ((lane & 7) == 0) {
      const float mean = sx * (1.f / DM);
      st64_rlx(&G->stats[256 * m256 + 16 * nkv + (t >> 3)], tagw(mean, tg), tagw(rsqrtf(fmaxf(sq * (1.f / DM) - mean * mean, 0.f) + 1e-5f), tg));
    }
    if (wp == 1 && lane < 16) {
      const uint32_t a = scr + lane * 4;
      st32_rlx(&G->cskv[128 * nkv + 16 * m256 + lane], tagw((ldsf(a) + ldsf(a + 64)) + (ldsf(a + 128) + ldsf(a + 192)), tg));
    }
    __syncwarp();
    bar_arrive(NB_PUB, 192);
    const uint4 wv = ld128_keep(P.wr + t * 8);
    #pragma unroll 1
    for (int i = 0; i < 2; i++) {
      mbar_wait(sb + B_G, i ^ 1);
      const uint32_t a = sb + OFF_G + t * 16;
      const uint4 u0 = lds128(a), u1 = lds128(a + 2048), u2 = lds128(a + 4096), u3 = lds128(a + 6144);
      addc(u0, cs); addc(u1, cs); addc(u2, cs); addc(u3, cs);
      bar_sync(NB_WG2, 128);
      if (i == 0 && wp == 0 && elect_one()) { mbar_expect_tx(sb + B_G, 8192); tma_2d(sb + OFF_G, &P.qs, 32 * (c & 31), 256 * (c >> 5) + 128, sb + B_G); }
    }
    float sw = (bf_lo(wv.x) + bf_hi(wv.x)) + (bf_lo(wv.y) + bf_hi(wv.y)) + (bf_lo(wv.z) + bf_hi(wv.z)) + (bf_lo(wv.w) + bf_hi(wv.w));
    #pragma unroll
    for (int o = 16; o; o >>= 1) sw += __shfl_xor_sync(~0u, sw, o);
    if (lane == 0) stsf(sb + OFF_SUMWR + wp * 4, sw);
    if ((t >> 4) == j) {
      const uint32_t a = sb + OFF_WR + (t & 15) * 32;
      sts128(a, wv.x << 16, wv.x & 0xffff0000u, wv.y << 16, wv.y & 0xffff0000u);
      sts128(a + 16, wv.z << 16, wv.z & 0xffff0000u, wv.w << 16, wv.w & 0xffff0000u);
    }
    v = reduce8(cs, lane);
    stsf(sb + OFF_G + (wp * 32 + 8 * (lane & 3) + (lane >> 2)) * 4, v);
    bar_sync(NB_WG2, 128);
    if (wp == 0) {
      const uint32_t a = sb + OFF_G + lane * 4, cq = tagw((ldsf(a) + ldsf(a + 128)) + (ldsf(a + 256) + ldsf(a + 384)), tg);
      st32_rlx(&G->csq[(c >> 5) * DM + 32 * (c & 31) + lane], cq);
      if (lane == 0) mbar_arrive_at(sb + B_W, rank, (cq & P.zero) + 1);
    }
  }

  uint32_t xr[32];
  {
    const bool isq = wg == 2;
    float acc[2][64];
    {
      const uint32_t emptyb = mapa(sb + (isq ? B_EMPTY5 : B_EMPTYKV), t & 1);
      auto correct = [&](uint32_t xa, uint32_t xb) {
        wg_fence();
        wgmma_sa_n128<0, 1, H0, H0>(acc[0], dlo(SB0, 0) + (xa >> 4), dlo(SB0, 0) + (xb >> 4));
        wgmma_sa_n128<0, 1, H0, H0>(acc[1], dlo(SB0, 0) + (xa >> 4) + 64, dlo(SB0, 0) + (xb >> 4));
        wg_commit();
      };
      if (!isq) {
        mbar_wait(sb + B_S0, 0);
        if (wg) mbar_wait(sb + B_FULLKV, 0);
        #pragma unroll 1
        for (int kb = 0; kb < 16; kb++) {
          const uint32_t da = dlo(SB0, 16) + wg * 1024 + (kb & 3) * (KV_STAGE >> 4), db = dlo(SB0 + 32768, 8192) + (kb & 3) * (KV_STAGE >> 4);
          wg_fence();
          #pragma unroll
          for (int k = 0; k < 4; k++) {
            wgmma_ss_n128<0, 1, H128, H128>(acc[0], da + 2 * k, db + 128 * k, k > 0 || kb != 0);
            wgmma_ss_n128<0, 1, H128, H128>(acc[1], da + 512 + 2 * k, db + 128 * k, k > 0 || kb != 0);
          }
          wg_commit();
          wg_wait<1>();
          if (kb > 0 && t < 2) mbar_arrive_remote(emptyb + 8 * ((kb - 1) & 3), kb > 10 ? 3 : 1);
          if (kb < 15) mbar_wait(sb + B_FULLKV + 8 * ((kb + 1) & 3), ((kb + 1) >> 2) & 1);
          if (kb == 0) mbar_wait(sb + B_FULLKV, 0);
          if (kb == 15 - LAG && wg == 1) bar_sync(NB_LAG, 256);
        }
        bar_arrive(wg ? NB_QGO : NB_LAG, 256);
        mbar_wait(sb + B_AUX, 0);
        correct(OFF_AXK + wg * 2048, OFF_BXK);
        wg_wait<0>();
        if (t < 2) mbar_arrive_remote(emptyb + 24, 3);
        fence_regs(acc[0]); fence_regs(acc[1]);
      const uint32_t stg = sb + OFF_X + (1 - wg) * 24576;
      const uint32_t va = stg + 16384 + (16 * wp + (lane & 15)) * 64 + (((lane >> 4) ^ ((lane >> 1) & 3)) << 4);
      const uint32_t ra = sb + OFF_RS256 + (128 * wg + 16 * wp + g) * 4;
      const float rs[4] = {ldsf(ra), ldsf(ra + 32), ldsf(ra + 256), ldsf(ra + 288)};
      float p[2][16];
      uint32_t vf[16], kf[2][16];
      auto project = [&](const uint32_t (&f)[16], uint32_t db) {
        wg_fence();
        #pragma unroll
        for (int i = 0; i < 2; i++) {
          wgmma_rs_n32<1, H64>(p[i], f[8*i], f[8*i+1], f[8*i+2], f[8*i+3], db, 0);
          wgmma_ra_n32<1, H64>(p[i], f[8*i+4], f[8*i+5], f[8*i+6], f[8*i+7], db + 64);
        }
        wg_commit();
      };
      auto fold = [&](uint32_t (&f)[16], int col, float sc) {
        #pragma unroll
        for (int i = 0; i < 16; i++) {
          const float r = rs[2 * (i >> 3) + (i & 1)] * sc;
          f[i] = pack_bf16(acc[i >> 3][col + 2 * (i & 7)] * r, acc[i >> 3][col + 2 * (i & 7) + 1] * r);
          asm volatile("" : "+r"(f[i]));
        }
      };
      auto put_v = [&](const uint32_t (&f)[16]) {
        #pragma unroll
        for (int k = 0; k < 4; k++) stsm4((va ^ ((k & 1) << 5)) + (k >> 1) * 4096, f[4*k], f[4*k+1], f[4*k+2], f[4*k+3]);
      };
      fold(vf, 48, 1.f);
      mbar_wait(sb + B_W, 0);
      fold(kf[0], 0, LOG2E);
      #pragma unroll
      for (int i = 0; i < 32; i++) p[i >> 4][i & 15] = acc[i >> 4][i & 15];
      project(kf[0], dlo(SB0 + OFF_WPHIK, 16));
      mbar_wait(sb + B_W, 0);
      {
        uint32_t v0[16];
        fold(kf[1], 16, LOG2E);
        fold(v0, 32, 1.f);
        if (wg == 1) bar_sync(NB_DN, 256);
        put_v(v0);
      }
      wg_wait<0>();
      fence_regs(p[0]); fence_regs(p[1]);
      if (wg == 1) bar_arrive(NB_WG01, 256);
      #pragma unroll 1
      for (int h = 0; h < 2; h++) {
        uint32_t ph[4][8];
        float rsum[2][4];
        dual_exp2(p[0], ph[0], ph[1]); dual_exp2(p[1], ph[2], ph[3]);
        row_sums(rsum, ph, dlo(SB0 + OFF_SEL, 16));
        if (wg == 0 && h == 0) { bar_arrive(NB_DN, 256); bar_sync(NB_WG01, 256); }
        if (h == 1) {
          if (wg == 1) bar_sync(NB_DN, 256);
          put_v(vf);
        }
        wg_wait<0>();
        fence_regs(rsum[0]); fence_regs(rsum[1]);
        if (__builtin_expect(__any_sync(~0u, !((rsum[0][0] + rsum[0][1]) + (rsum[0][2] + rsum[0][3]) + (rsum[1][0] + rsum[1][1]) + (rsum[1][2] + rsum[1][3]) < EXP_LIM)), 0)) {
          dual_exp2_shifted(p, ph);
          #pragma unroll
          for (int i = 0; i < 8; i++) {
            const uint32_t* f = &ph[i >> 1][i & 1];
            float a = (bf_lo(f[0]) + bf_hi(f[0])) + (bf_lo(f[2]) + bf_hi(f[2])) + (bf_lo(f[4]) + bf_hi(f[4])) + (bf_lo(f[6]) + bf_hi(f[6]));
            a += __shfl_xor_sync(~0u, a, 1);
            rsum[i >> 2][2 * (i & 1) + ((i >> 1) & 1)] = a + __shfl_xor_sync(~0u, a, 2);
          }
        }
        if (h == 0) project(kf[1], dlo(SB0 + OFF_WPHIK1, 16));
        normalize(ph, rsum);
        #pragma unroll
        for (int i = 0; i < 8; i++) {
          const uint32_t* f = &ph[i >> 1][4 * (i & 1)];
          stsm4(((stg + sa) ^ ((i & 3) << 5)) + (i >> 2) * 8192, f[0], f[1], f[2], f[3]);
        }
        fence_async_smem();
        if (wg == h) {
          float kv[20];
          #pragma unroll
          for (int w = 0; w < 2; w++) {
            const uint32_t da = dlo(SB0 + OFF_X, 16) + (h ^ w ^ 1) * 1536, db = dlo(SB0 + OFF_X + 16384, OFF_ONES - OFF_X - 16384) - (h ^ w ^ 1) * (1536 * 65535);
            if (w) bar_sync(NB_ST, 256); else bar_sync(NB_L0 + h, 128);
            wg_fence();
            #pragma unroll
            for (int k = 0; k < 8; k++) {
              if (k == 0 && w == 0) wgmma_sz_n40<1, 1, H128, H64>(kv, da, db);
              else wgmma_sa_n40<1, 1, H128, H64>(kv, da + k * 128, db - k * (64 * 65535));
            }
            wg_commit();
          }
          float4* dst = &G->kvacc[(ha + 2 * h) * KVP + t];
          wg_wait<0>();
          fence_regs(kv);
          if (h == 0) bar_arrive(NB_DN, 256); else if (t < 2) { mbar_arrive_at(sb + B_EMPTY5 + 40, t, 2); if (t == 0) mbar_arrive(sb + B_KD); }
          kv[17] = kv[18];
          #pragma unroll
          for (int i = 0; i < 6; i++) red_add_f32x4(dst + 128 * i, kv[3*i], kv[3*i+1], kv[3*i+2], 1.f);
        } else bar_arrive(NB_ST, 256);
        wg_wait<0>();
        fence_regs(p[0]); fence_regs(p[1]);
      }
      #pragma unroll
      for (int i = 0; i < 32; i++) asm volatile("mov.b32 %0, 0;" : "=r"(xr[i]));
      } else {
        uint32_t so = 0, po = 0, par = 0;
        mbar_wait(sb + B_FULL5, 0);
        bar_sync(NB_QGO, 256);
        #pragma unroll 1
        for (int kb = 0; kb < 16 - ML; kb++) {
          const uint32_t da = dlo(SB0, 16) + so * 256, db = dlo(SB0 + 16384, 8192) + so * 256;
          #pragma unroll
          for (int k = 0; k < 4; k++) {
            wg_fence();
            wgmma_ss_n128<0, 1, H128, H128>(acc[0], da + 2 * k, db + 128 * k, k > 0 || kb != 0);
            wgmma_ss_n128<0, 1, H128, H128>(acc[1], da + 512 + 2 * k, db + 128 * k, k > 0 || kb != 0);
            wg_commit();
            if (k == 1 && kb > 0 && t < 2) mbar_arrive_remote(emptyb + po, 2);
            if (k == 3) {
              po = so; so += 8;
              if (so == 40) { so = 0; par ^= 1; }
              mbar_wait(sb + B_FULL5 + so, par);
            }
            if ((QW >> k) & 1) wg_wait<2>(); else wg_wait<1>();
          }
        }
        auto block = [&](const int kb, const int i) {
          wg_fence();
          #pragma unroll
          for (int k = 0; k < 4; k++) wgmma_sa_n128<0, 1, H128, H128>(acc[i], dlo(SB0, 16) + (kb % 5) * 2048 + 512 * i + 2 * k, dlo(SB0 + 16384, 8192) + (kb % 5) * 2048 + 128 * k);
          wg_commit();
        };
        auto hand_over = [&](const int i) {
          const uint32_t ta = sb + (1 + rank) * R5 + sa + i * 8192;
          #pragma unroll
          for (int k = 0; k < 4; k++) {
            const float* a = &acc[i][32 * (k >> 1) + 8 * (k & 1)];
            stsm4(ta ^ (k << 5), pack_bf16(a[0], a[1]), pack_bf16(a[2], a[3]), pack_bf16(a[4], a[5]), pack_bf16(a[6], a[7]));
          }
        };
        mbar_wait2(sb + B_AUXQ, 0, sb + B_OS, 0);
        correct(OFF_AXQ, OFF_BXQ);
        #pragma unroll
        for (int kb = 16 - ML; kb < 16; kb++) {
          block(kb, 0);
          if (kb < 15) mbar_wait(sb + B_FULL5 + 8 * ((kb + 1) % 5), ((kb + 1) / 5) & 1);
          if (kb == 16 - ML) { wg_wait<2>(); if (t < 2) mbar_arrive_remote(emptyb + 8 * ((kb - 1) % 5), 2); }
        }
        mbar_wait(sb + B_RC, 0);
        block(16 - ML, 1);
        block(17 - ML, 1);
        wg_wait<2>();
        fence_regs(acc[0]);
        hand_over(0);
        fence_async_smem();
        bar_arrive(NB_Q0, 256);
        #pragma unroll
        for (int kb = 18 - ML; kb <= 16; kb++) {
          wg_wait<1>();
          if (t < 2) mbar_arrive_remote(emptyb + 8 * ((kb - 2) % 5), 2);
          if (kb < 16) block(kb, 1);
        }
        mbar_wait(sb + B_RC + 8, 0);
        wg_wait<0>();
        if (t < 2) mbar_arrive_remote(emptyb, 2);
        fence_regs(acc[1]);
        hand_over(1);
        fence_async_smem();
        bar_arrive(NB_Q0 + 1, 256);
        #pragma unroll
        for (int i = 0; i < 32; i++) { const float* a = &acc[(i >> 3) & 1][16 + 32 * (i >> 4) + 2 * (i & 7)]; xr[i] = pack_bf16(a[0], a[1]); }
      }
    }
    float p[2][16];
    #pragma unroll
    for (int i = 0; i < 32; i++) asm volatile("mov.b32 %0, 0;" : "=f"(p[i >> 4][i & 15]));
    auto project_r = [&](int w) {
      wg_fence();
      #pragma unroll
      for (int h = 0; h < 2; h++) {
        wgmma_rs_n32<1, H64>(p[h], xr[8*h], xr[8*h+1], xr[8*h+2], xr[8*h+3], dlo(SB0 + OFF_WPHIQ, 16) + 128 * w, 0);
        wgmma_ra_n32<1, H64>(p[h], xr[8*h+4], xr[8*h+5], xr[8*h+6], xr[8*h+7], dlo(SB0 + OFF_WPHIQ, 16) + 128 * w + 64);
      }
      wg_commit();
    };
    auto capture = [&](const int i) {
      if (!i) mbar_wait(sb + B_R, 0);
      #pragma unroll
      for (int k = 0; k < 4; k++) ldsm4(((sb + (1 + rank) * R5 + wg * 8192 + sa) ^ (k << 5)) + i * 2 * R5, xr[16*i+4*k], xr[16*i+4*k+1], xr[16*i+4*k+2], xr[16*i+4*k+3]);
      const uint32_t one = (((xr[16*i] | xr[16*i+4]) | (xr[16*i+8] | xr[16*i+12])) & P.zero) + 1;
      if (lane == 0) mbar_arrive_at(sb + (i ? B_RX : B_RC + 8 * wg), i ? wg : rank, one);
    };
    const uint32_t rq = sb + OFF_RSQ + (16 * wp + g) * 4 + 256 * (wg & 1), rb = rq + 128 * (wg & 2);
    const float cc[2][2] = {{ldsf(rq) * LOG2E, ldsf(rq + 32) * LOG2E}, {ldsf(rb) * LOG2E, ldsf(rb + 32) * LOG2E}};
    {
      const uint4* src = reinterpret_cast<const uint4*>(&G->kvacc[(4 * j + wg) * KVP + t]);
      uint4 v[12];
      #pragma unroll
      for (int i = 0; i < 12; i++) v[i] = i < 6 || isq ? ld128_rlx(src + 128 * i) : make_uint4(0, 0, 0, 0x41000000u);
      if (isq) {
        project_r(2);
        wg_wait<0>();
        #pragma unroll
        for (int i = 0; i < 16; i++) xr[i] = xr[16 + i];
      } else {
        capture(0);
      }
      #pragma unroll 1
      for (uint32_t it = 0; it < POLL_LIMIT; it++) {
        uint32_t bad = 0;
        #pragma unroll
        for (int i = 0; i < 12; i++) bad |= v[i].w ^ 0x41000000u;
        if (!__any_sync(~0u, bad != 0)) break;
        #pragma unroll
        for (int i = 0; i < 12; i++) if (i < 6 || isq) v[i] = ld128_rlx(src + 128 * i);
      }
      mbar_wait(sb + B_KD, 0);
      #pragma unroll
      for (int e = 0; e < 2; e++) {
        if (e == 0 || isq) {
          float f[18];
          #pragma unroll
          for (int i = 0; i < 6; i++) { f[3*i] = __uint_as_float(v[6*e+i].x); f[3*i+1] = __uint_as_float(v[6*e+i].y); f[3*i+2] = __uint_as_float(v[6*e+i].z); }
          const uint32_t ka = sb + OFF_KVZ + (wg + e) * 5120 + wp * 1280 + lane * 16;
          stsm4(ka, pack_bf16(f[0], f[1]), pack_bf16(f[2], f[3]), pack_bf16(f[4], f[5]), pack_bf16(f[6], f[7]));
          stsm4(ka + 512, pack_bf16(f[8], f[9]), pack_bf16(f[10], f[11]), pack_bf16(f[12], f[13]), pack_bf16(f[14], f[15]));
          stsm2(ka + 1024, pack_bf16(f[16], 1.f), pack_bf16(f[17], 1.f));
        }
      }
    }
    fence_async_smem();
    if (wg == 1) bar_arrive(NB_DN, 256);
    #pragma unroll 1
    for (int e = wg; e < wg + 1 + (wg >> 1); e++) {
      const int half = e >> 1, hh = e & 1, turn = e;
      const uint32_t ao = (1 + rank) * R5 + hh * 8192;
      uint32_t ph[4][8];
      #pragma unroll
      for (int i = 0; i < 32; i++) asm volatile("mov.b32 %0, 0;" : "=r"(ph[i >> 3][i & 7]));
      uint32_t shifted = 0;
      asm volatile("" : "+r"(shifted));
      #pragma unroll 1
      for (;;) {
        if (shifted) dual_exp2_shifted(p, ph);
        uint32_t first = (shifted ^ 1) & !isq;
        asm volatile("" : "+r"(first));
        if (first) {
          bar_sync(NB_Q0 + wg, 256);
          const uint32_t da = dlo(SB0, 16) + (ao >> 4), db = dlo(SB0 + OFF_WPHIQ, 16);
          wg_fence();
          #pragma unroll
          for (int h = 0; h < 2; h++) {
            wgmma_ss_n32<0, 1, H128, H64>(p[h], da + 4 * h, db + 128 * h, 0);
            wgmma_sa_n32<0, 1, H128, H64>(p[h], da + 4 * h + 2, db + 128 * h + 64);
          }
          wg_commit();
          capture(1);
          wg_wait<0>();
        }
        fence_regs(p[0]); fence_regs(p[1]);
        uint32_t again = shifted;
        asm volatile("" : "+r"(again));
        if (again) break;
        float s2[4] = {0.f, 0.f, 0.f, 0.f};
        #pragma unroll
        for (int i = 0; i < 32; i++) { float& x = p[i >> 4][i & 15]; x *= cc[i >> 4][(i >> 1) & 1]; s2[i & 3] = fmaf(x, x, s2[i & 3]); }
        if (!__any_sync(~0u, !((s2[0] < ARG_LIM2) & (s2[1] < ARG_LIM2) & (s2[2] < ARG_LIM2) & (s2[3] < ARG_LIM2)))) break;
        shifted = 1;
      }
      if (e == 1 || e == 2) bar_sync(NB_TOK + e - 1, 256);
      float ac[4][20];
      auto numer = [&](int h) {
        const uint32_t (*f)[8] = &ph[2 * h];
        const uint32_t db = dlo(SB0 + OFF_KVZ, 128) + (half ? e : h) * 320;
        wg_fence();
        #pragma unroll
        for (int i = 0; i < 2; i++) {
          wgmma_rz_n40<1, dhi(256, 0)>(ac[2*h+i], f[i][0], f[i][1], f[i][2], f[i][3], db + i * 160);
          wgmma_ra_n40<1, dhi(256, 0)>(ac[2*h+i], f[i][4], f[i][5], f[i][6], f[i][7], db + (i * 160 + 80));
        }
        wg_commit();
      };
      const uint32_t oa = (16 * wp + g) * 128 + (((lane & 3) ^ g) << 4);
      auto finish = [&](int h) {
        const float* ap = ac[2 * h]; const float* am = ac[2 * h + 1];
        const float ip0 = rcp(ap[17]), im0 = rcp(am[17]), ip1 = rcp(ap[19]), im1 = rcp(am[19]);
        const float d0 = rcp(fmaf(ap[16], ip0, fmaf(am[16], im0, 1e-6f))), d1 = rcp(fmaf(ap[18], ip1, fmaf(am[18], im1, 1e-6f)));
        const float a0 = ip0 * d0, b0 = im0 * d0, a1 = ip1 * d1, b1 = im1 * d1;
        #pragma unroll
        for (int r = 0; r < 2; r++) {
          const float a = r ? a1 : a0, b = r ? b1 : b0;
          uint32_t w[4];
          #pragma unroll
          for (int k = 0; k < 4; k++) w[k] = pack_bf16(fmaf(ap[4*k+2*r], a, am[4*k+2*r] * b), fmaf(ap[4*k+2*r+1], a, am[4*k+2*r+1] * b));
          const uint32_t off = (oa ^ ((half ? rank : h) << 6)) + r * 1024;
          st128_rlx(reinterpret_cast<uint8_t*>(G->o + (m128 * 16 + (half ? 2 * (j & 6) + 2 * hh + 1 : 2 * j)) * 8192 + (half ? h : hh) * 4096) + off, w[0], w[1], w[2], w[3]);
          if (!half) sts128(sb + ao + off, w[0], w[1], w[2], w[3]);
        }
        if ((half || h) && lane == 0) st32_rlx(&G->oflag[(m128 * 6 + (half ? 2 * e - 2 + h : hh)) * 32 + 4 * j + wp], 1);
      };
      if (!shifted) dual_exp2(p[0], ph[0], ph[1]);
      numer(0);
      if (!shifted) dual_exp2(p[1], ph[2], ph[3]);
      if (turn < 2) bar_arrive(NB_TOK + turn, 256);
      if (wg == 0) bar_sync(NB_DN, 256);
      numer(1);
      wg_wait<1>();
      fence_regs(ac[0]); fence_regs(ac[1]);
      finish(0);
      wg_wait<0>();
      fence_regs(ac[2]); fence_regs(ac[3]);
      #pragma unroll
      for (int i = 0; i < 32; i++) asm volatile("mov.b32 %0, 0;" : "=f"(p[i >> 4][i & 15]));
      if (e == 2) project_r(3);
      finish(1);
      if (!half) fence_async_smem();
      __syncwarp();
      if (lane == 0) mbar_arrive(sb + B_UO + 8 * e);
      wg_wait<0>();
    }
    if (isq) cluster_arrive();
  }

  {
  int lane;
  asm volatile("mov.u32 %0, %%laneid;" : "=r"(lane));
  const int g = lane >> 2, q = lane & 3;
  if (wg < 2) {
    float h[64];
    {
      #pragma unroll
      for (int i = 0; i < 32; i++) { h[2*i] = bf_lo(xr[i]); h[2*i+1] = bf_hi(xr[i]); }
      fence_regs(h);
      const uint32_t emptyb = mapa(sb + B_EMPTY5, t & 1);
      uint32_t s = 1 + rank, ps = 0;
      mbar_wait2(sb + B_GB + 8 * rank, 0, sb + B_UO + 8 * wg, 0);
      #pragma unroll
      for (int i = 0; i < 16; i++) {
        const uint32_t da = dlo(SB0, 16) + s * 2048 + wg * 512, db = dlo(SB0 + 16384, 8192) + s * 2048;
        wg_fence();
        #pragma unroll
        for (int k = 0; k < 4; k++) wgmma_sa_n128<0, 1, H128, H128>(h, da + k * 2, db + k * 128);
        wg_commit();
        const uint32_t ns = i ? (i + 2) % 6 : 2 - rank;
        const uint32_t nb = i ? i + 1 : 1 - rank, b0 = sb + B_GB + 8 * nb, b1 = sb + B_GA + 16 * nb + 8 * wg;
        const bool here = i == 15 || mbar_test2(b0, 0, b1, 0);
        wg_wait<1>();
        if (!(((2 * REL + 1) >> i) & 1) && i < 14 && t < 2) mbar_arrive_remote(emptyb + 8 * ps, 1);
        if ((REL >> i) & 1) { wg_wait<0>(); if (t < 2) mbar_arrive_remote(emptyb + 8 * s, 1); }
        if (!here) mbar_wait2(b0, 0, b1, 0);
        ps = s; s = ns;
      }
    }
    cluster_arrive();
    float2 wr[16];
    #pragma unroll
    for (int i = 0; i < 16; i++) wr[i] = lds64f(sb + OFF_WR + 32 * i + 8 * q);
    const int r0 = 64 * wg + 16 * wp + g;
    float sum0, sum1, dot0, dot1, sq0, sq1;
    uint32_t redo = 0;
    asm volatile("" : "+r"(redo));
    #pragma unroll 1
    for (;;) {
    if (redo) {
      wg_wait<0>();
      const uint32_t* xp = reinterpret_cast<const uint32_t*>(P.x + (size_t)(128 * m128 + r0) * DM + 128 * j) + q;
      #pragma unroll
      for (int i = 0; i < 32; i++) { const uint32_t v = xp[4 * (i >> 1) + (i & 1) * 4 * DM]; h[2*i] = bf_lo(v); h[2*i+1] = bf_hi(v); }
      #pragma unroll 1
      for (int ks = 0; ks < 64; ks++) {
        const int kb = ks >> 2, kk = 16 * (ks & 3);
        const bf16* op = G->o + (m128 * 16 + kb) * 8192 + r0 * 64 + 2 * q;
        const int o0 = ((kk >> 3) ^ g) << 3;
        const uint32_t* w = reinterpret_cast<const uint32_t*>(P.wo_p + (size_t)(((kb & 1) ? 256 * (kb >> 2) + 32 * (kb & 2) + 32 + 4 * (kk & 32) : 64 * kb + 2 * (kk & 32)) +
                                                                              ((kk & 16) >> 2) + 4 * (g & 6) + (g & 1)) * DM + 128 * j) + q;
        uint32_t b[32], a0, a1, a2, a3, it = 0;
        #pragma unroll
        for (int n = 0; n < 32; n++) b[n] = w[4 * (n >> 1) + (n & 1) * DM];
        do { a0 = ld32_rlx(op + o0); a1 = ld32_rlx(op + 512 + o0); a2 = ld32_rlx(op + (o0 ^ 8)); a3 = ld32_rlx(op + 512 + (o0 ^ 8)); }
        while (max(max(a0, a1), max(a2, a3)) == ~0u && ++it < POLL_LIMIT);
        __syncwarp();
        #pragma unroll
        for (int n = 0; n < 16; n++) mma16816(h[4*n], h[4*n+1], h[4*n+2], h[4*n+3], a0, a1, a2, a3, transpose8(b[2*n]), transpose8(b[2*n+1]));
      }
    }
    wg_wait<0>();
    fence_regs(h);
    sum0 = 0.f, sum1 = 0.f, dot0 = 0.f, dot1 = 0.f, sq0 = 0.f, sq1 = 0.f;
    #pragma unroll
    for (int i = 0; i < 16; i++) {
      sum0 += h[4*i] + h[4*i+1]; sum1 += h[4*i+2] + h[4*i+3];
      sq0 = fmaf(h[4*i], h[4*i], fmaf(h[4*i+1], h[4*i+1], sq0)); sq1 = fmaf(h[4*i+2], h[4*i+2], fmaf(h[4*i+3], h[4*i+3], sq1));
      dot0 = fmaf(h[4*i], wr[i].x, fmaf(h[4*i+1], wr[i].y, dot0)); dot1 = fmaf(h[4*i+2], wr[i].x, fmaf(h[4*i+3], wr[i].y, dot1));
    }
    if (!__any_sync(~0u, !redo & (h[0] != h[0] | h[2] != h[2]))) break;
    redo = 1;
    }
    float4* const rs = &G->rstat[128 * m128 + r0];
    {
      const bool up = q & 2;
      float a = up ? sum1 : sum0, b = up ? sq1 : sq0, d = up ? dot1 : dot0;
      a += __shfl_xor_sync(~0u, up ? sum0 : sum1, 2); b += __shfl_xor_sync(~0u, up ? sq0 : sq1, 2); d += __shfl_xor_sync(~0u, up ? dot0 : dot1, 2);
      a += __shfl_xor_sync(~0u, a, 1); b += __shfl_xor_sync(~0u, b, 1); d += __shfl_xor_sync(~0u, d, 1);
      if ((q & 1) == 0) red_add_f32x4(rs + 4 * q, a, b, d, 1.f);
    }
    bar_sync(NB_WG01, 256);
    float rstd[2], bm[2];
    uint32_t best;
    {
      const float2 swa = lds64f(sb + OFF_SUMWR), swb = lds64f(sb + OFF_SUMWR + 8);
      const float sw = (swa.x + swa.y) + (swb.x + swb.y);
      uint4 a[2]; uint32_t it = 0, key[2];
      do { a[0] = ld128_rlx(rs); a[1] = ld128_rlx(rs + 8); } while (__any_sync(~0u, (a[0].w & a[1].w) != 0x41000000u) && ++it < POLL_LIMIT);
      #pragma unroll
      for (int i = 0; i < 2; i++) {
        const float mean = __uint_as_float(a[i].x) * (1.f / DM);
        rstd[i] = rsqrtf(fmaxf(__uint_as_float(a[i].y) * (1.f / DM) - mean * mean, 0.f) + 1e-5f);
        bm[i] = -mean * rstd[i];
        const uint32_t rr = __float_as_uint(fmaf(__uint_as_float(a[i].z), rstd[i], sw * bm[i]));
        key[i] = ((rr ^ ((uint32_t)((int32_t)rr >> 31) | 0x80000000u)) & ~2047u) | (2047 - 128 * m128 - r0 - 8 * i);
      }
      asm volatile("redux.sync.max.u32 %0, %1, 0xffffffff;" : "=r"(best) : "r"(max(key[0], key[1])));
    }
    const int slot = m128 * 8 + warp, win = ~best & 15;
    if (lane < 4) st32_rlx(&G->key[(4 * j + lane) * 128 + slot], best);
    if ((win & 7) == g) {
      const bool up = win & 8;
      const float ra = up ? rstd[1] : rstd[0], rb = up ? bm[1] : bm[0];
      uint32_t x[16];
      #pragma unroll
      for (int i = 0; i < 16; i++) x[i] = pack_bf16(fmaf(up ? h[4*i+2] : h[4*i], ra, rb), fmaf(up ? h[4*i+3] : h[4*i+1], ra, rb));
      #pragma unroll
      for (int i = 0; i < 4; i++) st128_rlx(&G->cand[slot * 512 + 64 * j + 16 * i + 4 * q], x[4*i], x[4*i+1], x[4*i+2], x[4*i+3]);
    }
    __syncwarp();
    bar_arrive(NB_G2E, 384);
    {
      const float a0 = 1.f + rstd[0], b0 = bm[0], a1 = 1.f + rstd[1], b1 = bm[1];
      #pragma unroll
      for (int k = 0; k < 8; k++)
        stsm4(((sb + OFF_OUT + wg * 8192 + sa) ^ ((k & 3) << 5)) + (k >> 2) * 16384,
              pack_bf16(fmaf(h[8*k], a0, b0), fmaf(h[8*k+1], a0, b0)),     pack_bf16(fmaf(h[8*k+2], a1, b1), fmaf(h[8*k+3], a1, b1)),
              pack_bf16(fmaf(h[8*k+4], a0, b0), fmaf(h[8*k+5], a0, b0)),   pack_bf16(fmaf(h[8*k+6], a1, b1), fmaf(h[8*k+7], a1, b1)));
      fence_async_smem();
      __syncwarp();
      if (lane == 0) mbar_arrive(sb + B_OUT + 8 * wg);
    }
    {
      uint32_t wa[8][4][4];
      const uint32_t wb = sb + 16384 * (((uint32_t)FF_SLOT >> (4 * warp)) & 15) + ((lane & 7) + ((lane >> 4) << 3)) * 64 + ((((lane >> 3) & 1) ^ ((lane >> 1) & 3)) << 4);
      if (f < NFFN) mbar_wait(sb + B_F + 8 * warp, 0);
      #pragma unroll
      for (int i = 0; i < 32; i++) ldsm4t((wb ^ ((i & 1) << 5)) + ((i >> 1) & 1) * 8192 + (i >> 2) * 1024, wa[i >> 2][i & 3][0], wa[i >> 2][i & 3][1], wa[i >> 2][i & 3][2], wa[i >> 2][i & 3][3]);
      bar_sync(NB_XS, 384);
      uint4 xs[4];
      #pragma unroll
      for (int i = 0; i < 4; i++) xs[i] = lds128(sb + OFF_XSEL + 256 * warp + 64 * i + 16 * q);
      float d[4][4];
      #pragma unroll
      for (int ks = 0; ks < 8; ks++) {
        #pragma unroll
        for (int m = 0; m < 4; m++) {
          if (ks == 0) { d[m][0] = 0.f; d[m][1] = 0.f; d[m][2] = 0.f; d[m][3] = 0.f; }
          mma16816(d[m][0], d[m][1], d[m][2], d[m][3], wa[ks][m][0], wa[ks][m][1], wa[ks][m][2], wa[ks][m][3],
                   (ks & 1) ? xs[ks >> 1].z : xs[ks >> 1].x, (ks & 1) ? xs[ks >> 1].w : xs[ks >> 1].y);
        }
      }
      if (q == 0) {
        #pragma unroll
        for (int m = 0; m < 8; m++) stsf(sb + OFF_GU + (8 * m + g) * 48 + 4 * warp, d[m >> 1][2 * (m & 1)]);
      }
      bar_arrive(NB_ACT, 384);
    }
    {
      const uint32_t ky = __float_as_uint(ldsf(sb + OFF_KEY));
      const int row = 2047 - (ky & 2047) - 128 * m128;
      if ((uint32_t)row < 128u) {
        const int l = tid >> 3, vi = (j & 1) + ((lane >> 2) & 1), e = 3 * vi + q - 4 * (j & 1);
        const float kr = __uint_as_float((ky & ~2047u) ^ ((ky >> 31) ? 0x80000000u : 0xfffff800u));
        const int col = 32 * (l & 3) + 16 * (e & 1) + 4 * (e & 2) + (l >> 2);
        const float sg = rcp(1.f + ex2(-LOG2E * kr));
        const uint32_t base = __float_as_uint(ldsf(sb + OFF_OUT + (col >> 6) * 16384 + row * 128 + ((((col >> 3) ^ row) & 7) << 4) + 2 * (col & 6)));
        const float4* yp = &G->yacc[(q * 3 + vi) * 128 + 32 * (j >> 1) + l];
        uint32_t it = 0;
        uint4 v;
        mbar_wait(sb + B_SD, 0);
        do { v = ld128_rlx(yp); } while (__any_sync(~0u, __uint_as_float(v.w) != (float)(NFFN / 4)) && ++it < POLL_LIMIT);
        float y0 = __uint_as_float(v.x), y1 = __uint_as_float(v.y), y2 = __uint_as_float(v.z);
        #pragma unroll
        for (int o = 1; o < 4; o <<= 1) { y0 += __shfl_xor_sync(~0u, y0, o); y1 += __shfl_xor_sync(~0u, y1, o); y2 += __shfl_xor_sync(~0u, y2, o); }
        if (q < 3 && (uint32_t)e < 4u)
          P.out_p[(size_t)(128 * m128 + row) * DM + 128 * j + col] = __float2bfloat16(fmaf(q == 0 ? y0 : q == 1 ? y1 : y2, sg, (col & 1) ? bf_hi(base) : bf_lo(base)));
      }
      if (c == 0 && tid == 0) st32_rlx(&G->epoch, __float_as_uint(ldsf(sb + OFF_EP)));
    }
  }
  if (wg == 2) {
    uint32_t wf[16][2][4];
    {
      const uint32_t wb = sb + OFF_S + 16384 * (wp & 1) + ((lane & 7) + ((lane >> 4) << 3)) * 128 + ((((lane >> 3) & 1) ^ (lane & 7)) << 4);
      if (f < NFFN) mbar_wait(sb + B_WD + 8 * wp, 0);
      #pragma unroll
      for (int i = 0; i < 32; i++) ldsm4t((wb ^ (((i >> 1) & 3) << 5)) + (i >> 3) * 4096 + (i & 1) * 2048, wf[i >> 1][i & 1][0], wf[i >> 1][i & 1][1], wf[i >> 1][i & 1][2], wf[i >> 1][i & 1][3]);
      fence_async_smem();
      __syncwarp();
      if (lane == 0) mbar_arrive(sb + B_WC + 8 * wp);
    }
    bar_sync(NB_G2E, 384);
    {
      uint32_t cur = 0;
      uint4 v;
      #pragma unroll 1
      for (uint32_t it = 0; it < POLL_LIMIT; it++) {
        const uint4 kx = ld128_rlx(&G->key[(c & 31) * 128 + 4 * lane]);
        v = ld128_rlx(&G->cand[((~cur >> 4) & 127) * 512 + 4 * t]);
        uint32_t best;
        asm volatile("redux.sync.max.u32 %0, %1, 0xffffffff;" : "=r"(best) : "r"(max(max(kx.x, kx.y), max(kx.z, kx.w))));
        if (!__any_sync(~0u, min(min(kx.x, kx.y), min(kx.z, kx.w)) == 0 || v.w == ~0u) && best == cur) break;
        cur = best;
      }
      sts128(sb + OFF_XSEL + 16 * t, v.x, v.y, v.z, v.w);
      sts32(sb + OFF_KEY, cur);
      bar_arrive(NB_XS, 384);
      bar_sync(NB_ACT, 384);
    }
    float gu[2];
    #pragma unroll
    for (int i = 0; i < 2; i++) {
      const uint4 v0 = lds128(sb + OFF_GU + (32 * i + lane) * 48), v1 = lds128(sb + OFF_GU + (32 * i + lane) * 48 + 16);
      gu[i] = ((__uint_as_float(v0.x) + __uint_as_float(v0.y)) + (__uint_as_float(v0.z) + __uint_as_float(v0.w))) +
              ((__uint_as_float(v1.x) + __uint_as_float(v1.y)) + (__uint_as_float(v1.z) + __uint_as_float(v1.w)));
    }
    const float act = gu[0] * gu[1] * rcp(1.f + ex2(-LOG2E * gu[0]));
    const uint32_t ap = pack_bf16(act, __shfl_down_sync(~0u, act, 1));
    uint32_t bf[4];
    #pragma unroll
    for (int i = 0; i < 4; i++) bf[i] = __shfl_sync(~0u, ap, 2 * q + 8 * i);
    float d[16][4];
    #pragma unroll
    for (int k = 0; k < 2; k++)
      #pragma unroll
      for (int i = 0; i < 16; i++) {
        if (k == 0) { d[i][0] = 0.f; d[i][1] = 0.f; d[i][2] = 0.f; d[i][3] = 0.f; }
        mma16816(d[i][0], d[i][1], d[i][2], d[i][3], wf[i][k][0], wf[i][k][1], wf[i][k][2], wf[i][k][3], bf[2*k], bf[2*k+1]);
      }
    float y[9];
    #pragma unroll
    for (int e = 0; e < 8; e++) {
      const int n = 2 * (e & 4) + (e & 1);
      const float lo = (q & 1) ? d[n + 2][e & 2] : d[n][e & 2], hi = (q & 1) ? d[n + 6][e & 2] : d[n + 4][e & 2];
      y[e] = (q & 2) ? hi : lo;
    }
    y[8] = 0.f;
    if (f < NFFN) {
      #pragma unroll
      for (int i = 0; i < 3; i++) red_add_f32x4(&G->yacc[((f & 3) * 3 + i) * 128 + t], y[3*i], y[3*i+1], y[3*i+2], 1.f);
    }
  }
  }
  cluster_wait();
}

typedef CUresult (*EncodeFn)(CUtensorMap*, CUtensorMapDataType, cuuint32_t, void*, const cuuint64_t*, const cuuint64_t*,
                             const cuuint32_t*, const cuuint32_t*, CUtensorMapInterleave, CUtensorMapSwizzle,
                             CUtensorMapL2promotion, CUtensorMapFloatOOBfill);

void make_map(EncodeFn enc, CUtensorMap* m, const void* p, int n, const cuuint64_t* dims, const cuuint64_t* str, const cuuint32_t* box,
              CUtensorMapSwizzle sw, CUtensorMapL2promotion promo) {
  cuuint32_t es[5] = {1, 1, 1, 1, 1};
  enc(m, CU_TENSOR_MAP_DATA_TYPE_BFLOAT16, n, const_cast<void*>(p), dims, str, box, es, CU_TENSOR_MAP_INTERLEAVE_NONE, sw, promo,
      CU_TENSOR_MAP_FLOAT_OOB_FILL_NONE);
}
void map2(EncodeFn enc, CUtensorMap* m, const void* p, uint64_t cols, uint64_t rows, uint32_t bc, uint32_t br, CUtensorMapSwizzle sw,
          CUtensorMapL2promotion promo) {
  const cuuint64_t dims[2] = {cols, rows}, str[1] = {cols * 2};
  const cuuint32_t box[2] = {bc, br};
  make_map(enc, m, p, 2, dims, str, box, sw, promo);
}
void map3(EncodeFn enc, CUtensorMap* m, const void* p, uint64_t cols, uint64_t rows, uint32_t br, uint32_t nb) {
  const cuuint64_t dims[3] = {64, rows, cols / 64}, str[2] = {cols * 2, 128};
  const cuuint32_t box[3] = {64, br, nb};
  make_map(enc, m, p, 3, dims, str, box, CU_TENSOR_MAP_SWIZZLE_128B, CU_TENSOR_MAP_L2_PROMOTION_L2_128B);
}

}

extern "C" void kernel_launch(void* const* d_in, const int* in_sizes, int n_in, void* d_out, int out_size) {
  (void)in_sizes; (void)n_in; (void)out_size;
  static EncodeFn enc = nullptr;
  static void* o_ptr = nullptr;
  if (!enc) {
    void* f = nullptr; cudaDriverEntryPointQueryResult qr;
    cudaGetDriverEntryPoint("cuTensorMapEncodeTiled", &f, cudaEnableDefault, &qr);
    enc = (EncodeFn)f;
    cudaGetSymbolAddress(&o_ptr, g_scr);
    cudaFuncSetAttribute(fused_kernel, cudaFuncAttributeMaxDynamicSharedMemorySize, SMEM_BYTES);
  }
  const bf16* x = (const bf16*)d_in[0];
  const bf16* wqkv = (const bf16*)d_in[1];
  const bf16* wphi = (const bf16*)d_in[2];
  const bf16* wo = (const bf16*)d_in[3];
  const bf16* wr = (const bf16*)d_in[5];
  const bf16* wgate = (const bf16*)d_in[6];
  const bf16* wup = (const bf16*)d_in[7];
  const bf16* wdown = (const bf16*)d_in[8];
  Params P;
  const CUtensorMapSwizzle S128 = CU_TENSOR_MAP_SWIZZLE_128B, S64 = CU_TENSOR_MAP_SWIZZLE_64B;
  const CUtensorMapL2promotion L128 = CU_TENSOR_MAP_L2_PROMOTION_L2_128B, L256 = CU_TENSOR_MAP_L2_PROMOTION_L2_256B,
                               L64 = CU_TENSOR_MAP_L2_PROMOTION_L2_64B;
  map2(enc, &P.x128, x, DM, SEQ, 64, 128, S128, L128);
  map2(enc, &P.x64, x, DM, SEQ, 64, 64, S128, L128);
  {
    const cuuint64_t dims[4] = {64, DM, 16, 3}, str[3] = {6 * DM, 128, 2 * DM};
    const cuuint32_t box[4] = {64, 64, 1, 2};
    make_map(enc, &P.wkv, wqkv, 4, dims, str, box, S128, L128);
  }
  map3(enc, &P.wq, wqkv, 3 * DM, DM, 64, 2);
  for (int i = 0; i < 2; i++) {
    const cuuint64_t dims[5] = {DM, (cuuint64_t)(DM - 94 - 64 * i), 4, 4, 2}, str[4] = {2 * DM, 16 * DM, 4 * DM, (cuuint64_t)(128 * DM) << i};
    const cuuint32_t box[5] = {64, 2, 4, 4, 2};
    make_map(enc, &P.wo[i], wo, 5, dims, str, box, S128, L128);
  }
  map3(enc, &P.wd, wdown, DM, FF, 32, 4);
  map2(enc, &P.wg, wgate, FF, DM, 32, 128, S64, L64);
  map2(enc, &P.wu, wup, FF, DM, 32, 128, S64, L64);
  map2(enc, &P.tg, wgate, FF, DM, 8, 16, CU_TENSOR_MAP_SWIZZLE_NONE, L128);
  map2(enc, &P.tu, wup, FF, DM, 8, 16, CU_TENSOR_MAP_SWIZZLE_NONE, L128);
  map2(enc, &P.td, wdown, 128, FF * 8, 8, 16, CU_TENSOR_MAP_SWIZZLE_NONE, L256);
  map2(enc, &P.xs, x, DM, SEQ, 128, 16, CU_TENSOR_MAP_SWIZZLE_NONE, L256);
  map2(enc, &P.ws, wqkv, 3 * DM, DM, 16, 128, CU_TENSOR_MAP_SWIZZLE_NONE, L128);
  map2(enc, &P.qs, wqkv, 3 * DM, DM, 32, 128, CU_TENSOR_MAP_SWIZZLE_NONE, L64);
  map2(enc, &P.out, d_out, DM, SEQ, 64, 16, S128, L128);
  map2(enc, &P.o, o_ptr, 256, SEQ * DM / 256, 256, 16, CU_TENSOR_MAP_SWIZZLE_NONE, L128);
  map2(enc, &P.phi, wphi, 32, 1024, 32, 32, S64, L64);
  P.x = x; P.wqkv = wqkv; P.wo_p = wo; P.wr = wr; P.out_p = (bf16*)d_out; P.g = (Scratch*)o_ptr; P.zero = 0;

  cudaLaunchConfig_t cfg = {};
  cfg.gridDim = dim3(128); cfg.blockDim = dim3(512); cfg.dynamicSmemBytes = SMEM_BYTES; cfg.stream = cudaStreamPerThread;
  cudaLaunchAttribute at[1];
  at[0].id = cudaLaunchAttributeClusterDimension; at[0].val.clusterDim.x = 2; at[0].val.clusterDim.y = 1; at[0].val.clusterDim.z = 1;
  cfg.attrs = at; cfg.numAttrs = 1;
  cudaLaunchKernelEx(&cfg, fused_kernel, P);
}
```

```cpp
#include <cuda_runtime.h>
#include <cuda.h>
#include <cuda_bf16.h>
#include <stdint.h>

namespace {

typedef __nv_bfloat16 bf16;

__device__ __forceinline__ uint32_t smem_u32(const void* p){ return (uint32_t)__cvta_generic_to_shared(p); }
__device__ __forceinline__ void mbar_init(uint32_t bar, uint32_t cnt){ asm volatile("mbarrier.init.shared::cta.b64 [%0], %1;"::"r"(bar),"r"(cnt):"memory"); }
__device__ __forceinline__ void mbar_expect_tx(uint32_t bar, uint32_t bytes){ asm volatile("mbarrier.arrive.expect_tx.shared::cta.b64 _, [%0], %1;"::"r"(bar),"r"(bytes):"memory"); }
__device__ __forceinline__ void mbar_arrive(uint32_t bar){ asm volatile("mbarrier.arrive.shared::cta.b64 _, [%0];"::"r"(bar):"memory"); }
__device__ __forceinline__ uint32_t mapa(uint32_t addr, uint32_t cta){ uint32_t r; asm volatile("mapa.shared::cluster.u32 %0, %1, %2;":"=r"(r):"r"(addr),"r"(cta)); return r; }
__device__ __forceinline__ void mbar_arrive_at(uint32_t bar, uint32_t cta, uint32_t cnt){
  asm volatile("{\n.reg .b32 ra;\nmapa.shared::cluster.u32 ra, %0, %1;\nmbarrier.arrive.shared::cluster.b64 _, [ra], %2;\n}\n"::"r"(bar),"r"(cta),"r"(cnt):"memory"); }
__device__ __forceinline__ void mbar_arrive_remote(uint32_t cluster_addr, uint32_t cnt){
  asm volatile("mbarrier.arrive.shared::cluster.b64 _, [%0], %1;"::"r"(cluster_addr),"r"(cnt):"memory"); }
__device__ __forceinline__ void mbar_wait(uint32_t bar, uint32_t parity){
  asm volatile("{\n.reg .pred p;\n.reg .u32 c;\nmov.u32 c, 0;\nLW:\nmbarrier.try_wait.parity.shared::cta.b64 p, [%0], %1;\n@p bra LD;\nadd.u32 c, c, 1;\nsetp.lt.u32 p, c, 2000000;\n@p bra LW;\ntrap;\nLD:\n}\n"::"r"(bar),"r"(parity):"memory"); }
__device__ __forceinline__ void mbar_wait2(uint32_t bar0, uint32_t par0, uint32_t bar1, uint32_t par1){
  asm volatile("{\n.reg .pred p, q;\n.reg .u32 c;\nmov.u32 c, 0;\nLW:\nmbarrier.try_wait.parity.shared::cta.b64 p, [%0], %1;\nmbarrier.try_wait.parity.shared::cta.b64 q, [%2], %3;\nand.pred p, p, q;\n@p bra LD;\nadd.u32 c, c, 1;\nsetp.lt.u32 p, c, 2000000;\n@p bra LW;\ntrap;\nLD:\n}\n"::"r"(bar0),"r"(par0),"r"(bar1),"r"(par1):"memory"); }
__device__ __forceinline__ bool mbar_test2(uint32_t bar0, uint32_t par0, uint32_t bar1, uint32_t par1){
  uint32_t r;
  asm volatile("{\n.reg .pred p, q;\nmbarrier.test_wait.parity.shared::cta.b64 p, [%1], %2;\nmbarrier.test_wait.parity.shared::cta.b64 q, [%3], %4;\nand.pred p, p, q;\nselp.u32 %0, 1, 0, p;\n}\n":"=r"(r):"r"(bar0),"r"(par0),"r"(bar1),"r"(par1):"memory");
  return r; }
__device__ __forceinline__ void tma_2d(uint32_t dst, const CUtensorMap* m, int c0, int c1, uint32_t bar){
  asm volatile("cp.async.bulk.tensor.2d.shared::cluster.global.mbarrier::complete_tx::bytes [%0], [%1, {%3, %4}], [%2];"::"r"(dst),"l"(m),"r"(bar),"r"(c0),"r"(c1):"memory"); }
__device__ __forceinline__ void tma_2d_h(uint32_t dst, const CUtensorMap* m, int c0, int c1, uint32_t bar, uint64_t pol){
  asm volatile("cp.async.bulk.tensor.2d.shared::cluster.global.mbarrier::complete_tx::bytes.L2::cache_hint [%0], [%1, {%3, %4}], [%2], %5;"::"r"(dst),"l"(m),"r"(bar),"r"(c0),"r"(c1),"l"(pol):"memory"); }
__device__ __forceinline__ void tma_2d_mc(uint32_t dst, const CUtensorMap* m, int c0, int c1, uint32_t bar){
  asm volatile("cp.async.bulk.tensor.2d.shared::cluster.global.mbarrier::complete_tx::bytes.multicast::cluster [%0], [%1, {%3, %4}], [%2], %5;"::"r"(dst),"l"(m),"r"(bar),"r"(c0),"r"(c1),"h"((uint16_t)3):"memory"); }
__device__ __forceinline__ void tma_2d_mc_h(uint32_t dst, const CUtensorMap* m, int c0, int c1, uint32_t bar, uint64_t pol){
  asm volatile("cp.async.bulk.tensor.2d.shared::cluster.global.mbarrier::complete_tx::bytes.multicast::cluster.L2::cache_hint [%0], [%1, {%3, %4}], [%2], %5, %6;"::"r"(dst),"l"(m),"r"(bar),"r"(c0),"r"(c1),"h"((uint16_t)3),"l"(pol):"memory"); }
__device__ __forceinline__ void tma_4d(uint32_t dst, const CUtensorMap* m, int c0, int c1, int c2, int c3, uint32_t bar){
  asm volatile("cp.async.bulk.tensor.4d.shared::cluster.global.mbarrier::complete_tx::bytes [%0], [%1, {%3, %4, %5, %6}], [%2];"::"r"(dst),"l"(m),"r"(bar),"r"(c0),"r"(c1),"r"(c2),"r"(c3):"memory"); }
__device__ __forceinline__ uint64_t policy_evict_first(){ uint64_t p; asm volatile("createpolicy.fractional.L2::evict_first.b64 %0, 1.0;":"=l"(p)); return p; }
__device__ __forceinline__ uint64_t policy_evict_normal(){ uint64_t p; asm("createpolicy.fractional.L2::evict_normal.b64 %0, 1.0;":"=l"(p)); return p; }
__device__ __forceinline__ void tma_3d_h(uint32_t dst, const CUtensorMap* m, int c0, int c1, int c2, uint32_t bar, uint64_t pol){
  asm volatile("cp.async.bulk.tensor.3d.shared::cluster.global.mbarrier::complete_tx::bytes.L2::cache_hint [%0], [%1, {%3, %4, %5}], [%2], %6;"::"r"(dst),"l"(m),"r"(bar),"r"(c0),"r"(c1),"r"(c2),"l"(pol):"memory"); }
__device__ __forceinline__ void tma_4d_h(uint32_t dst, const CUtensorMap* m, int c0, int c1, int c2, int c3, uint32_t bar, uint64_t pol){
  asm volatile("cp.async.bulk.tensor.4d.shared::cluster.global.mbarrier::complete_tx::bytes.L2::cache_hint [%0], [%1, {%3, %4, %5, %6}], [%2], %7;"::"r"(dst),"l"(m),"r"(bar),"r"(c0),"r"(c1),"r"(c2),"r"(c3),"l"(pol):"memory"); }
__device__ __forceinline__ void red_add_f32x4(float4* p, float x, float y, float z, float w){ asm volatile("red.relaxed.gpu.global.add.v4.f32 [%0], {%1,%2,%3,%4};"::"l"(p),"f"(x),"f"(y),"f"(z),"f"(w):"memory"); }
__device__ __forceinline__ void tma_5d_h(uint32_t dst, const CUtensorMap* m, int c0, int c1, uint32_t bar, uint64_t pol){
  asm volatile("cp.async.bulk.tensor.5d.shared::cluster.global.mbarrier::complete_tx::bytes.L2::cache_hint [%0], [%1, {%3, %4, 0, 0, 0}], [%2], %5;"::"r"(dst),"l"(m),"r"(bar),"r"(c0),"r"(c1),"l"(pol):"memory"); }
__device__ __forceinline__ void tma_store_2d(const CUtensorMap* m, int c0, int c1, uint32_t src, uint64_t pol){
  asm volatile("cp.async.bulk.tensor.2d.global.shared::cta.bulk_group.L2::cache_hint [%0, {%2, %3}], [%1], %4;"::"l"(m),"r"(src),"r"(c0),"r"(c1),"l"(pol):"memory"); }
__device__ __forceinline__ void bulk_commit(){ asm volatile("cp.async.bulk.commit_group;":::"memory"); }
__device__ __forceinline__ void bulk_wait_all(){ asm volatile("cp.async.bulk.wait_group 0;":::"memory"); }
__device__ __forceinline__ void fence_async_global(){ asm volatile("fence.proxy.async.global;":::"memory"); }
__device__ __forceinline__ bool elect_one(){ uint32_t p; asm volatile("{\n.reg .pred P;\nelect.sync _|P, 0xffffffff;\nselp.b32 %0, 1, 0, P;\n}\n":"=r"(p)); return p; }
__device__ __forceinline__ void bulk_prefetch(const void* p, uint32_t bytes){
  asm volatile("cp.async.bulk.prefetch.L2.global [%0], %1;"::"l"(p),"r"(bytes):"memory"); }
__device__ __forceinline__ void bulk_s2peer(uint32_t dst_cluster, uint32_t src, uint32_t bytes, uint32_t bar_cluster){
  asm volatile("cp.async.bulk.shared::cluster.shared::cta.mbarrier::complete_tx::bytes [%0], [%1], %2, [%3];"::"r"(dst_cluster),"r"(src),"r"(bytes),"r"(bar_cluster):"memory"); }
__device__ __forceinline__ void prefetch_map(const CUtensorMap* m){ asm volatile("prefetch.tensormap [%0];"::"l"(m):"memory"); }
__device__ __forceinline__ void fence_async_smem(){ asm volatile("fence.proxy.async.shared::cta;":::"memory"); }
__device__ __forceinline__ void fence_acquire_gpu(){ asm volatile("fence.acquire.gpu;":::"memory"); }
__device__ __forceinline__ void fence_gpu(){ asm volatile("fence.acq_rel.gpu;":::"memory"); }
__device__ __forceinline__ void wg_fence(){ asm volatile("wgmma.fence.sync.aligned;":::"memory"); }
__device__ __forceinline__ void wg_commit(){ asm volatile("wgmma.commit_group.sync.aligned;":::"memory"); }
template<int N> __device__ __forceinline__ void wg_wait(){ asm volatile("wgmma.wait_group.sync.aligned %0;"::"n"(N):"memory"); }
template<int N> __device__ __forceinline__ void fence_regs(float (&d)[N]){
  #pragma unroll
  for(int i=0;i<N;i++) asm volatile("":"+f"(d[i])::"memory"); }
__device__ __forceinline__ void bar_sync(int id, int n){ asm volatile("bar.sync %0, %1;"::"r"(id),"r"(n):"memory"); }
__device__ __forceinline__ void bar_arrive(int id, int n){ asm volatile("bar.arrive %0, %1;"::"r"(id),"r"(n):"memory"); }
__device__ __forceinline__ void cluster_arrive(){ asm volatile("barrier.cluster.arrive.relaxed.aligned;":::"memory"); }
__device__ __forceinline__ void cluster_wait(){ asm volatile("barrier.cluster.wait.aligned;":::"memory"); }
__host__ __device__ constexpr uint32_t dlo(uint32_t addr, uint32_t lbo){ return (addr >> 4) | ((lbo >> 4) << 16); }
__host__ __device__ constexpr uint32_t dhi(uint32_t sbo, uint32_t sw){ return (sbo >> 4) | (sw << 30); }
constexpr uint32_t H128 = dhi(1024, 1), H64 = dhi(512, 2), H0 = dhi(128, 0);
__device__ __forceinline__ uint32_t pack_bf16(float lo, float hi){ uint32_t r; asm("cvt.rn.bf16x2.f32 %0, %1, %2;":"=r"(r):"f"(hi),"f"(lo)); return r; }
__device__ __forceinline__ float bf_lo(uint32_t v){ return __uint_as_float(v<<16); }
__device__ __forceinline__ float bf_hi(uint32_t v){ return __uint_as_float(v&0xffff0000u); }
__device__ __forceinline__ float ex2(float x){ float r; asm("ex2.approx.ftz.f32 %0, %1;":"=f"(r):"f"(x)); return r; }
__device__ __forceinline__ float rcp(float x){ float r; asm("rcp.approx.ftz.f32 %0, %1;":"=f"(r):"f"(x)); return r; }
__device__ __forceinline__ void stsm4(uint32_t addr, uint32_t a, uint32_t b, uint32_t c, uint32_t d){
  asm volatile("stmatrix.sync.aligned.m8n8.x4.shared.b16 [%0], {%1,%2,%3,%4};"::"r"(addr),"r"(a),"r"(b),"r"(c),"r"(d)); }
__device__ __forceinline__ void stsm2(uint32_t addr, uint32_t a, uint32_t b){
  asm volatile("stmatrix.sync.aligned.m8n8.x2.shared.b16 [%0], {%1,%2};"::"r"(addr),"r"(a),"r"(b)); }
__device__ __forceinline__ void mma16816(float& d0, float& d1, float& d2, float& d3, uint32_t a0, uint32_t a1, uint32_t a2, uint32_t a3, uint32_t b0, uint32_t b1){
  asm volatile("mma.sync.aligned.m16n8k16.row.col.f32.bf16.bf16.f32 {%0,%1,%2,%3}, {%4,%5,%6,%7}, {%8,%9}, {%0,%1,%2,%3};"
               : "+f"(d0), "+f"(d1), "+f"(d2), "+f"(d3) : "r"(a0), "r"(a1), "r"(a2), "r"(a3), "r"(b0), "r"(b1)); }
__device__ __forceinline__ uint32_t transpose8(uint32_t a){ uint32_t r; asm volatile("movmatrix.sync.aligned.m8n8.trans.b16 %0, %1;":"=r"(r):"r"(a)); return r; }
__device__ __forceinline__ void ldsm4(uint32_t addr, uint32_t& a, uint32_t& b, uint32_t& c, uint32_t& d){
  asm volatile("ldmatrix.sync.aligned.m8n8.x4.shared.b16 {%0,%1,%2,%3}, [%4];":"=r"(a),"=r"(b),"=r"(c),"=r"(d):"r"(addr):"memory"); }
__device__ __forceinline__ void ldsm4t(uint32_t addr, uint32_t& a, uint32_t& b, uint32_t& c, uint32_t& d){
  asm volatile("ldmatrix.sync.aligned.m8n8.x4.trans.shared.b16 {%0,%1,%2,%3}, [%4];":"=r"(a),"=r"(b),"=r"(c),"=r"(d):"r"(addr):"memory"); }
__device__ __forceinline__ void sts32(uint32_t a, uint32_t v){ asm volatile("st.shared.b32 [%0], %1;"::"r"(a),"r"(v):"memory"); }
__device__ __forceinline__ void stsf(uint32_t a, float v){ asm volatile("st.shared.f32 [%0], %1;"::"r"(a),"f"(v):"memory"); }
__device__ __forceinline__ void sts64(uint32_t a, uint32_t x, uint32_t y){ asm volatile("st.shared.v2.b32 [%0], {%1,%2};"::"r"(a),"r"(x),"r"(y):"memory"); }
__device__ __forceinline__ void sts128(uint32_t a, uint32_t x, uint32_t y, uint32_t z, uint32_t w){ asm volatile("st.shared.v4.b32 [%0], {%1,%2,%3,%4};"::"r"(a),"r"(x),"r"(y),"r"(z),"r"(w):"memory"); }
__device__ __forceinline__ float ldsf(uint32_t a){ float v; asm volatile("ld.shared.f32 %0, [%1];":"=f"(v):"r"(a):"memory"); return v; }
__device__ __forceinline__ float2 lds64f(uint32_t a){ float2 v; asm volatile("ld.shared.v2.f32 {%0,%1}, [%2];":"=f"(v.x),"=f"(v.y):"r"(a):"memory"); return v; }
__device__ __forceinline__ uint4 lds128(uint32_t a){ uint4 v; asm volatile("ld.shared.v4.u32 {%0,%1,%2,%3}, [%4];":"=r"(v.x),"=r"(v.y),"=r"(v.z),"=r"(v.w):"r"(a):"memory"); return v; }
__device__ __forceinline__ uint4 ld128_keep(const void* p){ uint4 v; asm volatile("ld.global.v4.u32 {%0,%1,%2,%3}, [%4];":"=r"(v.x),"=r"(v.y),"=r"(v.z),"=r"(v.w):"l"(p):"memory"); return v; }
__device__ __forceinline__ uint4 ld128_rlx(const void* p){ uint4 v; asm volatile("ld.relaxed.gpu.global.v4.u32 {%0,%1,%2,%3}, [%4];":"=r"(v.x),"=r"(v.y),"=r"(v.z),"=r"(v.w):"l"(p):"memory"); return v; }
__device__ __forceinline__ uint32_t ld32_rlx(const void* p){ uint32_t v; asm volatile("ld.relaxed.gpu.global.u32 %0, [%1];":"=r"(v):"l"(p):"memory"); return v; }
__device__ __forceinline__ void st128_rlx(void* p, uint32_t x, uint32_t y, uint32_t z, uint32_t w){ asm volatile("st.relaxed.gpu.global.v4.u32 [%0], {%1,%2,%3,%4};"::"l"(p),"r"(x),"r"(y),"r"(z),"r"(w):"memory"); }
__device__ __forceinline__ void st64_rlx(void* p, uint32_t x, uint32_t y){ asm volatile("st.relaxed.gpu.global.v2.u32 [%0], {%1,%2};"::"l"(p),"r"(x),"r"(y):"memory"); }
__device__ __forceinline__ void st32_rlx(void* p, uint32_t x){ asm volatile("st.relaxed.gpu.global.u32 [%0], %1;"::"l"(p),"r"(x):"memory"); }
__device__ __forceinline__ void wait_until(uint32_t t){ while ((int32_t)((uint32_t)clock() - t) < 0) __nanosleep(32); }
__device__ __forceinline__ void flags_wait(uint32_t& missing, const uint32_t* p, uint32_t need){
  asm volatile("{\n.reg .pred p;\n.reg .u32 c, v;\nmov.u32 c, 0;\nLW:\nand.b32 v, %0, %2;\nsetp.eq.u32 p, v, 0;\n@p bra.uni LD;\nld.relaxed.gpu.global.u32 v, [%1];\nsetp.eq.u32 p, v, 0;\n"
               "vote.sync.ballot.b32 %0, p, 0xffffffff;\nadd.u32 c, c, 1;\nsetp.lt.u32 p, c, 4000000;\n@p bra.uni LW;\nLD:\n}\n":"+r"(missing):"l"(p),"r"(need):"memory"); }
__device__ __forceinline__ uint32_t tagw(float x, uint32_t t){ return (__float_as_uint(x) & ~3u) | t; }
__device__ __forceinline__ float untag(uint32_t w){ return __uint_as_float(w & ~3u); }

template<int TA, int TB, uint32_t HA, uint32_t HB> __device__ __forceinline__ void wgmma_ss_n128(float (&d)[64], uint32_t da, uint32_t db, int scale_d){
  asm volatile("{\n.reg .pred p;\n.reg .b64 a, b;\nsetp.ne.b32 p, %70, 0;\nmov.b64 a, {%64, %68};\nmov.b64 b, {%65, %69};\n"
  "wgmma.mma_async.sync.aligned.m64n128k16.f32.bf16.bf16 {%0, %1, %2, %3, %4, %5, %6, %7, %8, %9, %10, %11, %12, %13, %14, %15, %16, %17, %18, %19, %20, %21, %22, %23, %24, %25, %26, %27, %28, %29, %30, %31, %32, %33, %34, %35, %36, %37, %38, %39, %40, %41, %42, %43, %44, %45, %46, %47, %48, %49, %50, %51, %52, %53, %54, %55, %56, %57, %58, %59, %60, %61, %62, %63}, a, b, p, 1, 1, %66, %67;\n}\n"
  : "+f"(d[0]), "+f"(d[1]), "+f"(d[2]), "+f"(d[3]), "+f"(d[4]), "+f"(d[5]), "+f"(d[6]), "+f"(d[7]), "+f"(d[8]), "+f"(d[9]), "+f"(d[10]), "+f"(d[11]), "+f"(d[12]), "+f"(d[13]), "+f"(d[14]), "+f"(d[15]), "+f"(d[16]), "+f"(d[17]), "+f"(d[18]), "+f"(d[19]), "+f"(d[20]), "+f"(d[21]), "+f"(d[22]), "+f"(d[23]), "+f"(d[24]), "+f"(d[25]), "+f"(d[26]), "+f"(d[27]), "+f"(d[28]), "+f"(d[29]), "+f"(d[30]), "+f"(d[31]), "+f"(d[32]), "+f"(d[33]), "+f"(d[34]), "+f"(d[35]), "+f"(d[36]), "+f"(d[37]), "+f"(d[38]), "+f"(d[39]), "+f"(d[40]), "+f"(d[41]), "+f"(d[42]), "+f"(d[43]), "+f"(d[44]), "+f"(d[45]), "+f"(d[46]), "+f"(d[47]), "+f"(d[48]), "+f"(d[49]), "+f"(d[50]), "+f"(d[51]), "+f"(d[52]), "+f"(d[53]), "+f"(d[54]), "+f"(d[55]), "+f"(d[56]), "+f"(d[57]), "+f"(d[58]), "+f"(d[59]), "+f"(d[60]), "+f"(d[61]), "+f"(d[62]), "+f"(d[63])
  : "r"(da), "r"(db), "n"(TA), "n"(TB), "n"(HA), "n"(HB), "r"(scale_d));
}
template<int TA, int TB, uint32_t HA, uint32_t HB> __device__ __forceinline__ void wgmma_sa_n128(float (&d)[64], uint32_t da, uint32_t db){
  asm volatile("{\n.reg .pred p;\n.reg .b64 a, b;\nsetp.ne.b32 p, 1, 0;\nmov.b64 a, {%64, %68};\nmov.b64 b, {%65, %69};\n"
  "wgmma.mma_async.sync.aligned.m64n128k16.f32.bf16.bf16 {%0, %1, %2, %3, %4, %5, %6, %7, %8, %9, %10, %11, %12, %13, %14, %15, %16, %17, %18, %19, %20, %21, %22, %23, %24, %25, %26, %27, %28, %29, %30, %31, %32, %33, %34, %35, %36, %37, %38, %39, %40, %41, %42, %43, %44, %45, %46, %47, %48, %49, %50, %51, %52, %53, %54, %55, %56, %57, %58, %59, %60, %61, %62, %63}, a, b, p, 1, 1, %66, %67;\n}\n"
  : "+f"(d[0]), "+f"(d[1]), "+f"(d[2]), "+f"(d[3]), "+f"(d[4]), "+f"(d[5]), "+f"(d[6]), "+f"(d[7]), "+f"(d[8]), "+f"(d[9]), "+f"(d[10]), "+f"(d[11]), "+f"(d[12]), "+f"(d[13]), "+f"(d[14]), "+f"(d[15]), "+f"(d[16]), "+f"(d[17]), "+f"(d[18]), "+f"(d[19]), "+f"(d[20]), "+f"(d[21]), "+f"(d[22]), "+f"(d[23]), "+f"(d[24]), "+f"(d[25]), "+f"(d[26]), "+f"(d[27]), "+f"(d[28]), "+f"(d[29]), "+f"(d[30]), "+f"(d[31]), "+f"(d[32]), "+f"(d[33]), "+f"(d[34]), "+f"(d[35]), "+f"(d[36]), "+f"(d[37]), "+f"(d[38]), "+f"(d[39]), "+f"(d[40]), "+f"(d[41]), "+f"(d[42]), "+f"(d[43]), "+f"(d[44]), "+f"(d[45]), "+f"(d[46]), "+f"(d[47]), "+f"(d[48]), "+f"(d[49]), "+f"(d[50]), "+f"(d[51]), "+f"(d[52]), "+f"(d[53]), "+f"(d[54]), "+f"(d[55]), "+f"(d[56]), "+f"(d[57]), "+f"(d[58]), "+f"(d[59]), "+f"(d[60]), "+f"(d[61]), "+f"(d[62]), "+f"(d[63])
  : "r"(da), "r"(db), "n"(TA), "n"(TB), "n"(HA), "n"(HB));
}
template<int TA, int TB, uint32_t HA, uint32_t HB> __device__ __forceinline__ void wgmma_sa_n40(float (&d)[20], uint32_t da, uint32_t db){
  asm volatile("{\n.reg .pred p;\n.reg .b64 a, b;\nsetp.ne.b32 p, 1, 0;\nmov.b64 a, {%20, %24};\nmov.b64 b, {%21, %25};\n"
  "wgmma.mma_async.sync.aligned.m64n40k16.f32.bf16.bf16 {%0, %1, %2, %3, %4, %5, %6, %7, %8, %9, %10, %11, %12, %13, %14, %15, %16, %17, %18, %19}, a, b, p, 1, 1, %22, %23;\n}\n"
  : "+f"(d[0]), "+f"(d[1]), "+f"(d[2]), "+f"(d[3]), "+f"(d[4]), "+f"(d[5]), "+f"(d[6]), "+f"(d[7]), "+f"(d[8]), "+f"(d[9]), "+f"(d[10]), "+f"(d[11]), "+f"(d[12]), "+f"(d[13]), "+f"(d[14]), "+f"(d[15]), "+f"(d[16]), "+f"(d[17]), "+f"(d[18]), "+f"(d[19])
  : "r"(da), "r"(db), "n"(TA), "n"(TB), "n"(HA), "n"(HB));
}
template<int TA, int TB, uint32_t HA, uint32_t HB> __device__ __forceinline__ void wgmma_sz_n40(float (&d)[20], uint32_t da, uint32_t db){
  asm volatile("{\n.reg .pred p;\n.reg .b64 a, b;\nsetp.ne.b32 p, 0, 0;\nmov.b64 a, {%20, %24};\nmov.b64 b, {%21, %25};\n"
  "wgmma.mma_async.sync.aligned.m64n40k16.f32.bf16.bf16 {%0, %1, %2, %3, %4, %5, %6, %7, %8, %9, %10, %11, %12, %13, %14, %15, %16, %17, %18, %19}, a, b, p, 1, 1, %22, %23;\n}\n"
  : "=f"(d[0]), "=f"(d[1]), "=f"(d[2]), "=f"(d[3]), "=f"(d[4]), "=f"(d[5]), "=f"(d[6]), "=f"(d[7]), "=f"(d[8]), "=f"(d[9]), "=f"(d[10]), "=f"(d[11]), "=f"(d[12]), "=f"(d[13]), "=f"(d[14]), "=f"(d[15]), "=f"(d[16]), "=f"(d[17]), "=f"(d[18]), "=f"(d[19])
  : "r"(da), "r"(db), "n"(TA), "n"(TB), "n"(HA), "n"(HB));
}
template<int TA, int TB, uint32_t HA, uint32_t HB> __device__ __forceinline__ void wgmma_sa_n32(float (&d)[16], uint32_t da, uint32_t db){
  asm volatile("{\n.reg .pred p;\n.reg .b64 a, b;\nsetp.ne.b32 p, 1, 0;\nmov.b64 a, {%16, %20};\nmov.b64 b, {%17, %21};\n"
  "wgmma.mma_async.sync.aligned.m64n32k16.f32.bf16.bf16 {%0, %1, %2, %3, %4, %5, %6, %7, %8, %9, %10, %11, %12, %13, %14, %15}, a, b, p, 1, 1, %18, %19;\n}\n"
  : "+f"(d[0]), "+f"(d[1]), "+f"(d[2]), "+f"(d[3]), "+f"(d[4]), "+f"(d[5]), "+f"(d[6]), "+f"(d[7]), "+f"(d[8]), "+f"(d[9]), "+f"(d[10]), "+f"(d[11]), "+f"(d[12]), "+f"(d[13]), "+f"(d[14]), "+f"(d[15])
  : "r"(da), "r"(db), "n"(TA), "n"(TB), "n"(HA), "n"(HB));
}
template<int TA, int TB, uint32_t HA, uint32_t HB> __device__ __forceinline__ void wgmma_ss_n32(float (&d)[16], uint32_t da, uint32_t db, int scale_d){
  asm volatile("{\n.reg .pred p;\n.reg .b64 a, b;\nsetp.ne.b32 p, %22, 0;\nmov.b64 a, {%16, %20};\nmov.b64 b, {%17, %21};\n"
  "wgmma.mma_async.sync.aligned.m64n32k16.f32.bf16.bf16 {%0, %1, %2, %3, %4, %5, %6, %7, %8, %9, %10, %11, %12, %13, %14, %15}, a, b, p, 1, 1, %18, %19;\n}\n"
  : "+f"(d[0]), "+f"(d[1]), "+f"(d[2]), "+f"(d[3]), "+f"(d[4]), "+f"(d[5]), "+f"(d[6]), "+f"(d[7]), "+f"(d[8]), "+f"(d[9]), "+f"(d[10]), "+f"(d[11]), "+f"(d[12]), "+f"(d[13]), "+f"(d[14]), "+f"(d[15])
  : "r"(da), "r"(db), "n"(TA), "n"(TB), "n"(HA), "n"(HB), "r"(scale_d));
}
template<int TB, uint32_t HB> __device__ __forceinline__ void wgmma_ra_n32(float (&d)[16], uint32_t a0, uint32_t a1, uint32_t a2, uint32_t a3, uint32_t db){
  asm volatile("{\n.reg .pred p;\n.reg .b64 a, b;\nsetp.ne.b32 p, 1, 0;\nmov.b64 b, {%20, %22};\n"
  "wgmma.mma_async.sync.aligned.m64n32k16.f32.bf16.bf16 {%0, %1, %2, %3, %4, %5, %6, %7, %8, %9, %10, %11, %12, %13, %14, %15}, {%16,%17,%18,%19}, b, p, 1, 1, %21;\n}\n"
  : "+f"(d[0]), "+f"(d[1]), "+f"(d[2]), "+f"(d[3]), "+f"(d[4]), "+f"(d[5]), "+f"(d[6]), "+f"(d[7]), "+f"(d[8]), "+f"(d[9]), "+f"(d[10]), "+f"(d[11]), "+f"(d[12]), "+f"(d[13]), "+f"(d[14]), "+f"(d[15])
  : "r"(a0), "r"(a1), "r"(a2), "r"(a3), "r"(db), "n"(TB), "n"(HB));
}
template<int TB, uint32_t HB> __device__ __forceinline__ void wgmma_rs_n32(float (&d)[16], uint32_t a0, uint32_t a1, uint32_t a2, uint32_t a3, uint32_t db, int scale_d){
  asm volatile("{\n.reg .pred p;\n.reg .b64 a, b;\nsetp.ne.b32 p, %23, 0;\nmov.b64 b, {%20, %22};\n"
  "wgmma.mma_async.sync.aligned.m64n32k16.f32.bf16.bf16 {%0, %1, %2, %3, %4, %5, %6, %7, %8, %9, %10, %11, %12, %13, %14, %15}, {%16,%17,%18,%19}, b, p, 1, 1, %21;\n}\n"
  : "+f"(d[0]), "+f"(d[1]), "+f"(d[2]), "+f"(d[3]), "+f"(d[4]), "+f"(d[5]), "+f"(d[6]), "+f"(d[7]), "+f"(d[8]), "+f"(d[9]), "+f"(d[10]), "+f"(d[11]), "+f"(d[12]), "+f"(d[13]), "+f"(d[14]), "+f"(d[15])
  : "r"(a0), "r"(a1), "r"(a2), "r"(a3), "r"(db), "n"(TB), "n"(HB), "r"(scale_d));
}
template<int TB, uint32_t HB> __device__ __forceinline__ void wgmma_ra_n40(float (&d)[20], uint32_t a0, uint32_t a1, uint32_t a2, uint32_t a3, uint32_t db){
  asm volatile("{\n.reg .pred p;\n.reg .b64 a, b;\nsetp.ne.b32 p, 1, 0;\nmov.b64 b, {%24, %26};\n"
  "wgmma.mma_async.sync.aligned.m64n40k16.f32.bf16.bf16 {%0, %1, %2, %3, %4, %5, %6, %7, %8, %9, %10, %11, %12, %13, %14, %15, %16, %17, %18, %19}, {%20,%21,%22,%23}, b, p, 1, 1, %25;\n}\n"
  : "+f"(d[0]), "+f"(d[1]), "+f"(d[2]), "+f"(d[3]), "+f"(d[4]), "+f"(d[5]), "+f"(d[6]), "+f"(d[7]), "+f"(d[8]), "+f"(d[9]), "+f"(d[10]), "+f"(d[11]), "+f"(d[12]), "+f"(d[13]), "+f"(d[14]), "+f"(d[15]), "+f"(d[16]), "+f"(d[17]), "+f"(d[18]), "+f"(d[19])
  : "r"(a0), "r"(a1), "r"(a2), "r"(a3), "r"(db), "n"(TB), "n"(HB));
}
template<int TB, uint32_t HB> __device__ __forceinline__ void wgmma_rz_n40(float (&d)[20], uint32_t a0, uint32_t a1, uint32_t a2, uint32_t a3, uint32_t db){
  asm volatile("{\n.reg .pred p;\n.reg .b64 a, b;\nsetp.ne.b32 p, 0, 0;\nmov.b64 b, {%24, %26};\n"
  "wgmma.mma_async.sync.aligned.m64n40k16.f32.bf16.bf16 {%0, %1, %2, %3, %4, %5, %6, %7, %8, %9, %10, %11, %12, %13, %14, %15, %16, %17, %18, %19}, {%20,%21,%22,%23}, b, p, 1, 1, %25;\n}\n"
  : "=f"(d[0]), "=f"(d[1]), "=f"(d[2]), "=f"(d[3]), "=f"(d[4]), "=f"(d[5]), "=f"(d[6]), "=f"(d[7]), "=f"(d[8]), "=f"(d[9]), "=f"(d[10]), "=f"(d[11]), "=f"(d[12]), "=f"(d[13]), "=f"(d[14]), "=f"(d[15]), "=f"(d[16]), "=f"(d[17]), "=f"(d[18]), "=f"(d[19])
  : "r"(a0), "r"(a1), "r"(a2), "r"(a3), "r"(db), "n"(TB), "n"(HB));
}
template<int TB, uint32_t HB> __device__ __forceinline__ void wgmma_rz_n8(float (&d)[4], uint32_t a0, uint32_t a1, uint32_t a2, uint32_t a3, uint32_t db){
  asm volatile("{\n.reg .pred p;\n.reg .b64 a, b;\nsetp.ne.b32 p, 0, 0;\nmov.b64 b, {%8, %10};\n"
  "wgmma.mma_async.sync.aligned.m64n8k16.f32.bf16.bf16 {%0, %1, %2, %3}, {%4,%5,%6,%7}, b, p, 1, 1, %9;\n}\n"
  : "=f"(d[0]), "=f"(d[1]), "=f"(d[2]), "=f"(d[3])
  : "r"(a0), "r"(a1), "r"(a2), "r"(a3), "r"(db), "n"(TB), "n"(HB));
}

constexpr int SEQ = 2048, DM = 1024, FF = 3584;
constexpr float LOG2E = 1.4426950408889634f;
constexpr uint32_t POLL_LIMIT = 1u << 22;
constexpr int QW = 0;
constexpr int LAG = 2;
constexpr int ML = 2;
constexpr int REL = 6;
constexpr int SKM = 0x154;
constexpr int RS_N = 22;
constexpr int RS_D1 = 420;
constexpr int RS_D2 = 300;
constexpr int PF_T0 = 5000;
constexpr int PF_DT = 800;
constexpr int FF_N = 5;
constexpr int FF_DT = 500;
constexpr int FF_D2 = 350;
constexpr uint64_t FF_ORD = 0x76543210ba98ull;
constexpr int OUT_D = 400;
constexpr int NFFN = 112;

constexpr uint32_t SB0 = 1024;
constexpr uint32_t KV_STAGE = 49152, R5 = 32768;
constexpr uint32_t OFF_X = 163840, OFF_S = 196608, OFF_WPHI = OFF_S + 20480, OFF_M = 229376, SMEM_BYTES = 232448;
constexpr uint32_t OFF_RS256 = 212992, OFF_ONES = OFF_RS256 + 1024, OFF_WPHIK1 = OFF_ONES + 1024, OFF_KVZ = OFF_S;
constexpr uint32_t OFF_WPHIK = OFF_S, OFF_BXK = OFF_S + 2048, OFF_AXK = OFF_S + 4096, OFF_G = OFF_S + 8192;
constexpr uint32_t OFF_AXQ = OFF_WPHI, OFF_BXQ = OFF_WPHI + 2048, OFF_WPHIQ = OFF_WPHI + 4096;
constexpr uint32_t B_FULLKV = OFF_M  , B_EMPTYKV = OFF_M + 32  ;
constexpr uint32_t B_EMPTY5 = OFF_M + 64  , B_UO = B_EMPTY5 + 48  , B_RC = B_UO + 32  ;
constexpr uint32_t B_OUT = B_RC + 16  , B_SD = B_OUT + 16, B_AUX = B_SD + 8, B_AUXQ = B_AUX + 8, B_RX = B_AUXQ + 8;
constexpr uint32_t B_FULL5 = B_RX + 8  , B_F = B_FULL5 + 40  , B_WD = B_F + 64  ;
constexpr uint32_t B_WC = B_WD + 32  , B_DR = B_WC + 32  , B_W = B_DR + 24, B_OS = B_W + 8, B_R = B_W + 16, B_KD = B_W + 24, B_T = B_W + 32, B_G = B_W + 40, B_END = B_W + 48;
constexpr int NB3 = ((B_END - OFF_M) / 8 + 1) / 3;
constexpr uint32_t B_S0 = OFF_M + 8 + 24 * NB3;
static_assert(B_S0 >= B_END && B_S0 < OFF_M + 600, "barriers");
__host__ __device__ constexpr uint32_t bar_count(int i) {
  const uint32_t b = OFF_M + 8 * i;
  return b < B_EMPTYKV ? 1 : b < B_EMPTY5 ? 12 : b < B_SD ? 4 : b < B_RX || b == B_W ? 2 : b == B_RX ? 8 : 1;
}
constexpr uint32_t B_GB = OFF_M + 2560  , B_GA = B_GB + 128  ;
constexpr uint32_t OFF_SUMWR = OFF_M + 608, OFF_EP = OFF_M + 624, OFF_KEY = OFF_M + 628;
constexpr uint32_t OFF_RSQ = OFF_M + 640, OFF_SEL = OFF_M + 1648, OFF_T = OFF_M + 1792, OFF_WR = OFF_M + 2048;
constexpr uint32_t OFF_XSEL = 2 * R5, OFF_GU = OFF_XSEL + 4096, OFF_OUT = 3 * R5;
constexpr uint64_t FF_SLOT = 0xdcdc3210dcbaull;
constexpr int KVP = 6 * 128;
__device__ __forceinline__ uint32_t kv_count(uint32_t launch, uint32_t n) { return 0x42800000u + (((launch & 3) * 16 + n) << 17); }

enum { NB_G2E = 1, NB_XS = 2, NB_WG01 = 3, NB_ACT = 4, NB_Q0 = 5  , NB_ST = 14, NB_LAG = 8, NB_DN = 9, NB_ZERO = 10, NB_PUB = 11, NB_TOK = 10  , NB_L0 = 12  , NB_WG2 = 7, NB_QGO = 15 };

struct Scratch {
  bf16     o[SEQ * DM];
  float4   rstat[SEQ];
  uint32_t key[32 * 128];
  uint32_t cand[128 * 512];
  float4   yacc[4 * 3 * 128];
  float4   kvacc[32 * KVP];
  uint2    stats[SEQ];
  uint32_t cskv[2 * DM];
  uint32_t csq[4 * DM];
  uint32_t oset[128 * 16];
  uint32_t oflag[16 * 6 * 32];
  uint32_t epoch;
};
__device__ __align__(1024) Scratch g_scr;

struct Params {
  const bf16 *x, *wqkv, *wo_p, *wr;
  bf16* out_p;
  Scratch* g;
  uint32_t zero;
  CUtensorMap x128, x64, wkv, wq, wo[2], wd, wg, wu, phi, tg, tu, td, xs, ws, qs, out, o;
};

constexpr float EXP_LIM = 1.1529215e18f, ARG_LIM2 = 3600.f;
__device__ __forceinline__ void dual_exp2(const float (&p)[16], uint32_t (&ep)[8], uint32_t (&em)[8]) {
  #pragma unroll
  for (int k = 0; k < 8; k++) {
    const float a = ex2(p[2*k]), b = ex2(p[2*k+1]);
    const float r = rcp(a * b);
    ep[k] = pack_bf16(a, b); em[k] = pack_bf16(r * b, r * a);
  }
}
__device__ __forceinline__ void dual_exp2_shifted(const float (&pp)[2][16], uint32_t (&ph)[4][8]) {
  #pragma unroll
  for (int h = 0; h < 2; h++) {
    const float* p = pp[h];
    float m[4] = {p[0], p[2], p[0], p[2]};
    #pragma unroll
    for (int i = 0; i < 16; i++) { m[(i >> 1) & 1] = fmaxf(m[(i >> 1) & 1], p[i]); m[2 + ((i >> 1) & 1)] = fminf(m[2 + ((i >> 1) & 1)], p[i]); }
    #pragma unroll
    for (int o = 1; o < 4; o <<= 1) {
      m[0] = fmaxf(m[0], __shfl_xor_sync(~0u, m[0], o)); m[1] = fmaxf(m[1], __shfl_xor_sync(~0u, m[1], o));
      m[2] = fminf(m[2], __shfl_xor_sync(~0u, m[2], o)); m[3] = fminf(m[3], __shfl_xor_sync(~0u, m[3], o));
    }
    #pragma unroll
    for (int k = 0; k < 8; k++) {
      ph[2*h][k] = pack_bf16(ex2(p[2*k] - m[k & 1]), ex2(p[2*k+1] - m[k & 1]));
      ph[2*h+1][k] = pack_bf16(ex2(m[2 + (k & 1)] - p[2*k]), ex2(m[2 + (k & 1)] - p[2*k+1]));
    }
  }
}
__device__ __forceinline__ uint32_t add_bf16x2(uint32_t a, uint32_t b) { uint32_t r; asm("add.rn.bf16x2 %0, %1, %2;" : "=r"(r) : "r"(a), "r"(b)); return r; }
__device__ __forceinline__ void row_sums(float (&s)[2][4], const uint32_t (&ph)[4][8], uint32_t sel) {
  uint32_t u[8];
  #pragma unroll
  for (int i = 0; i < 8; i++) { const uint32_t* f = &ph[i >> 1][i & 1]; u[i] = add_bf16x2(add_bf16x2(f[0], f[2]), add_bf16x2(f[4], f[6])); }
  wg_fence();
  wgmma_rz_n8<0, H0>(s[0], u[0], u[1], u[2], u[3], sel);
  wgmma_rz_n8<0, H0>(s[1], u[4], u[5], u[6], u[7], sel);
  wg_commit();
}
__device__ __forceinline__ uint32_t mul_bf16x2(uint32_t a, uint32_t b) { uint32_t r; asm("mul.rn.bf16x2 %0, %1, %2;" : "=r"(r) : "r"(a), "r"(b)); return r; }
__device__ __forceinline__ void normalize(uint32_t (&ph)[4][8], const float (&s)[2][4]) {
  #pragma unroll
  for (int i = 0; i < 4; i++) {
    const float i0 = rcp(s[i >> 1][i & 1]), i1 = rcp(s[i >> 1][2 + (i & 1)]);
    const uint32_t n0 = pack_bf16(i0, i0), n1 = pack_bf16(i1, i1);
    #pragma unroll
    for (int k = 0; k < 4; k++) { ph[i][2*k] = mul_bf16x2(ph[i][2*k], n0); ph[i][2*k+1] = mul_bf16x2(ph[i][2*k+1], n1); }
  }
}
__device__ __forceinline__ void split_bf16(float a, float b, uint32_t& hi, uint32_t& lo) { hi = pack_bf16(a, b); lo = pack_bf16(a - bf_lo(hi), b - bf_hi(hi)); }
__device__ __forceinline__ void put_colsums(uint32_t base, int lane, float a, float b, float c, float d) {
  uint32_t h0, l0, h1, l1;
  split_bf16(a, b, h0, l0); split_bf16(c, d, h1, l1);
  const uint32_t ad = base + (lane >> 1) * 128 + (lane & 1) * 8;
  sts64(ad, h0, h1); sts64(ad + 16, l0, l1); sts64(ad + 32, h0, h1); sts64(ad + 48, l0, l1);
  sts128(base + (lane >> 1) * 128 + 64 + (lane & 1) * 32, 0, 0, 0, 0); sts128(base + (lane >> 1) * 128 + 80 + (lane & 1) * 32, 0, 0, 0, 0);
}
__device__ __forceinline__ float reduce8(const float (&v)[8], int lane) {
  const bool b4 = lane & 16, b3 = lane & 8, b2 = lane & 4;
  float a[4], b[2];
  #pragma unroll
  for (int i = 0; i < 4; i++) a[i] = (b4 ? v[4 + i] : v[i]) + __shfl_xor_sync(~0u, b4 ? v[i] : v[4 + i], 16);
  #pragma unroll
  for (int i = 0; i < 2; i++) b[i] = (b3 ? a[2 + i] : a[i]) + __shfl_xor_sync(~0u, b3 ? a[i] : a[2 + i], 8);
  return (b2 ? b[1] : b[0]) + __shfl_xor_sync(~0u, b2 ? b[0] : b[1], 4);
}
__device__ __forceinline__ bool tag_bad(uint4 v, uint32_t tg) { return (((v.x ^ tg) | (v.y ^ tg) | (v.z ^ tg) | (v.w ^ tg)) & 3) != 0; }


__global__ void __launch_bounds__(512, 1) fused_kernel(const __grid_constant__ Params P) {
  extern __shared__ __align__(1024) uint8_t smem_raw[];
  const uint32_t sb = smem_u32(smem_raw);
  const int tid = threadIdx.x, lane = tid & 31;
  {
    const int n = 16 * blockIdx.x + (lane & 15);
    const bf16* p = (lane < 16 ? P.x : P.wqkv) + (lane < 16 ? n * DM : (n >> 5) * (3 * DM) + DM + 64 * (n & 31));
    asm volatile("{\n.reg .pred p;\nsetp.lt.u32 p, %1, 32;\n@p prefetch.global.L2 [%0];\n}\n" :: "l"(p), "r"(tid));
  }
  const int cp = blockIdx.x >> 1, rank = blockIdx.x & 1;
  const int cr = cp < 4 ? 32 + 8 * cp : cp - 4 + max((cp * 37 - 1076) >> 8, 0);
  const int c = (cr & 62) + 64 * (cr & 1) + rank;
  const int m256 = c >> 4, nkv = c & 15, m128 = c >> 3, j = c & 7;
  if ((tid >> 7) == 2 && elect_one()) {
    if (tid >= 288) {
      const int w = (tid >> 5) - 9;
      #pragma unroll
      for (int i = 0; i < NB3; i++) mbar_init(sb + B_FULLKV + 8 + 8 * NB3 * w + 8 * i, w == 0 ? bar_count(1 + i) : w == 1 ? bar_count(1 + NB3 + i) : bar_count(1 + 2 * NB3 + i));
    } else {
      prefetch_map(&P.wkv); prefetch_map(&P.x128);
      mbar_init(sb + B_S0, 1); mbar_init(sb + B_FULLKV, 1);
      mbar_expect_tx(sb + B_S0, 32768);
      tma_4d(sb + 32768, &P.wkv, 0, 0, nkv, 1, sb + B_S0);
      tma_2d(sb, &P.x128, 0, 256 * m256, sb + B_S0);
      mbar_expect_tx(sb + B_FULLKV, 16384);
      tma_2d(sb + 16384, &P.x128, 0, 256 * m256 + 128, sb + B_FULLKV);
    }
    asm volatile("fence.mbarrier_init.release.cluster;" ::: "memory");
  }
  const int warp = __shfl_sync(~0u, tid >> 5, 0), wg = warp >> 2, wp = warp & 3;
  const int f = 16 * ((cr + 7) & 7) + 2 * (cr >> 3) + rank;
  const int ha = 4 * (nkv >> 1) + (nkv & 1);
  Scratch* const G = P.g;
  if ((sb & 0x3ffff) != SB0) asm volatile("trap;");
  __syncthreads();
  cluster_arrive();
  if (warp == 8 && elect_one()) {
    mbar_expect_tx(sb + B_FULLKV + 8, KV_STAGE);
    tma_4d(sb + KV_STAGE + 32768, &P.wkv, 0, 64, nkv, 1, sb + B_FULLKV + 8);
    tma_2d(sb + KV_STAGE, &P.x128, 64, 256 * m256, sb + B_FULLKV + 8);
    tma_2d(sb + KV_STAGE + 16384, &P.x128, 64, 256 * m256 + 128, sb + B_FULLKV + 8);
  }
  if (wg == 3) {
    asm volatile("setmaxnreg.dec.sync.aligned.u32 32;");
    cluster_wait();
    const bool el = elect_one();
    const uint64_t ef = policy_evict_first(), en = policy_evict_normal();
    auto fetch_o = [&](const int t0) {
      const int sh = t0 & 1;
      uint32_t missing = ~0u;
      const uint32_t* hint = &G->oflag[(m128 * 6 + ((t0 + 1) & 6) + rank) * 32 + ((4 * (j & 6) + lane) & 31)];
      #pragma unroll 1
      for (int i = 2 - 2 * sh; i < 8; i += 1 + sh) {
        const int blk = sh ? 6 + 2 * t0 + (i >> 1) : i, wrap = t0 == 3 ? 2 : (blk >= 5) + (blk >= 11), s = blk + 1 - 6 * wrap;
        flags_wait(missing, hint, (15u + 240u * sh) << (4 * i));
        if (blk > 5) mbar_wait(sb + B_EMPTY5 + 8 * s, wrap & 1);
        if (el) {
          tma_2d_mc_h(sb + s * R5 + rank * 8192, &P.o, 0, (m128 * 16 + t0 + 2 * (((j & 6) + i) & 7)) * 32 + 16 * rank, sb + B_GA + 16 * blk + 8 * rank, ef);
        }
      }
    };
    if (wp == 0) {
      {
        wait_until((uint32_t)clock() + 300);
        #pragma unroll 1
        for (int kb = 2; kb < 16; kb++) {
          const uint32_t st = sb + (kb & 3) * KV_STAGE, fb = sb + B_FULLKV + 8 * (kb & 3);
          mbar_wait(fb + (B_EMPTYKV - B_FULLKV), ~(kb >> 2) & 1);
          if (el) {
            mbar_expect_tx(fb, KV_STAGE);
            tma_2d_mc(st + rank * 16384, &P.x128, 64 * kb, 256 * m256 + 128 * rank, fb);
            tma_4d_h(st + 32768, &P.wkv, 0, 64 * kb, nkv, 1, fb, ef);
          }
        }
        uint64_t ord = 0xf3120edcba987654ull;
        uint32_t so = 0, par = 1;
        #pragma unroll 1
        for (int i = 0; i < 16; i++) {
          const uint32_t st = sb + so * 4096, fb = sb + B_FULL5 + so;
          const int k0 = (64 * (uint32_t)ord + 128 * (j & 6)) & 960;
          mbar_wait(i < 5 ? sb + B_EMPTYKV + so - (i > 1 ? 8 : 0) : fb + (B_EMPTY5 - B_FULL5), par);
          if (el) {
            mbar_expect_tx(fb, R5);
            tma_2d_mc_h(st + rank * 8192, &P.x64, k0, 128 * m128 + 64 * rank, fb, i >= 11 ? ef : en);
            tma_3d_h(st + 16384, &P.wq, 0, k0, 2 * j, fb, ef);
          }
          ord >>= 4; so += 8;
          if (so == 40) { so = 0; par ^= 1; }
        }
        mbar_wait(sb + B_FULL5 + 8 + 8 * rank, 0);
        if (el) mbar_arrive(sb + B_R);
        #pragma unroll 1
        for (int i = 0; i < 19; i++) {
          const int row = i < 8 ? 128 * (((j & 6) + i) & 7) : 256 * (((j >> 1) + i) & 3) + 32 + 16 * (i & 4);
          mbar_wait(sb + B_EMPTY5 + so, par);
          if (el) {
            if (i < 16) {
              tma_5d_h(sb + so * 4096 + 16384, &P.wo[i >> 3], 128 * j, row, sb + B_GB + 8 * i, ef);
              tma_5d_h(sb + so * 4096 + 24576, &P.wo[i >> 3], 128 * j + 64, row, sb + B_GB + 8 * i, ef);
            } else mbar_arrive(sb + B_DR + 8 * (i - 16));
          }
          so += 8;
          if (so == 48) { so = 0; par ^= 1; }
        }
      }
    } else if (wp == 3) {
      const uint32_t t_start = (uint32_t)clock();
      mbar_wait(sb + B_S0, 0);
      if (el) {
        mbar_expect_tx(sb + B_W, 12288);
        #pragma unroll 1
        for (int i = 0; i < 6; i++) tma_2d(sb + (i == 0 ? OFF_WPHIK : i == 1 ? OFF_WPHIK1 : OFF_WPHIQ + 2048 * (i - 2)), &P.phi, 0, 32 * (i < 2 ? 2 * nkv + i : 4 * j + 2 * (i & 1) + ((i - 2) >> 1)), sb + B_W);
        prefetch_map(&P.x64); prefetch_map(&P.wq); prefetch_map(&P.wo[0]); prefetch_map(&P.wo[1]);
        prefetch_map(&P.o); prefetch_map(&P.wd); prefetch_map(&P.out); prefetch_map(&P.wg); prefetch_map(&P.wu);
      }
      #pragma unroll 1
      for (int i = 0; i < 8; i++) {
        if (lane < 16) st128_rlx(&G->cand[(m128 * 8 + i) * 512 + 64 * j + 4 * lane], ~0u, ~0u, ~0u, ~0u);
      }
      if (lane < 16) st128_rlx(&G->rstat[16 * c + lane], 0, 0, 0, 0);
      if (lane < 12) st128_rlx(&G->yacc[12 * c + lane], 0, 0, 0, 0);
      const uint32_t nt = ld32_rlx(&G->epoch);
      if (lane < 8) { st128_rlx(&G->stats[16 * c + 2 * lane], nt, nt, nt, nt); st128_rlx(&G->csq[32 * c + 4 * lane], nt, nt, nt, nt); }
      if (lane < 4) { st128_rlx(&G->cskv[128 * nkv + 16 * m256 + 4 * lane], nt, nt, nt, nt); st128_rlx(&G->oset[16 * c + 4 * lane], nt, nt, nt, nt); }
      if (lane < 8) st128_rlx(&G->key[(4 * j + (lane >> 1)) * 128 + m128 * 8 + 4 * (lane & 1)], 0, 0, 0, 0);
      if (c < 32) {
        #pragma unroll 1
        for (int i = lane; i < KVP; i += 32) st128_rlx(&G->kvacc[(ha + 2 * m256) * KVP + i], 0, 0, 0, kv_count(nt + 1, 0));
      }
      fence_gpu();
      bar_arrive(NB_ZERO, 160);
      if (el) {
        #pragma unroll 1
        for (int i = 0; i < 30; i++) {
          wait_until(t_start + PF_T0 + PF_DT * i + 7 * f);
          if (i < 4) { bulk_prefetch(P.wqkv + (size_t)(256 * i + c) * (3 * DM), 2048); bulk_prefetch(P.wqkv + (size_t)(256 * i + 128 + c) * (3 * DM), 2048); }
          else if (i < 6) bulk_prefetch(P.wo_p + (size_t)c * 8192 + (i - 4) * 4096, 8192);
          else if (f < NFFN) {
            if (i < 22) {
              #pragma unroll 1
              for (int e = 0; e < 4; e++) tma_2d(sb + OFF_T, rank ? &P.tu : &P.tg, 32 * (f & ~1), 64 * (i - 6) + 16 * e, sb + B_T);
            } else { tma_2d(sb + OFF_T, &P.td, 0, 256 * f + 32 * (i - 22), sb + B_T); tma_2d(sb + OFF_T, &P.td, 0, 256 * f + 32 * (i - 22) + 16, sb + B_T); }
          }
        }
      }
      __syncwarp();
      mbar_wait2(sb + B_OS, 0, sb + B_RX, 0);
      mbar_wait2(sb + B_EMPTY5 + 24, 0, sb + B_EMPTY5 + 32, 0);
      mbar_wait2(sb + B_EMPTY5 + 40, 0, sb + B_EMPTY5, 1);
      fetch_o(0);
      fetch_o(3);
    } else {
      const int half = wp - 1;
      const uint32_t ep1 = ld32_rlx(&G->epoch) + 1, tg = ep1 & 3;
      {
        uint32_t it = 0;
        sts128(sb + OFF_ONES + half * 512 + lane * 16, 0x3f803f80u, 0x3f803f80u, 0x3f803f80u, 0x3f803f80u);
        if (lane < 9) { const uint32_t v = (lane & 1) ? 0 : 0x3f803f80u; sts128(sb + OFF_SEL + lane * 16, v, v, v, v); }
        auto reset_o = [&](int i0, int i1, uint32_t dt) {
          uint32_t t0 = (uint32_t)clock();
          #pragma unroll 1
          for (int i = i0; i < i1; i++) {
            st128_rlx(G->o + (m128 * 16 + 2 * j + half) * 8192 + 256 * i + 8 * lane, ~0u, ~0u, ~0u, ~0u);
            wait_until(t0 += dt);
          }
        };
        if (el) {
          #pragma unroll 1
          for (int i = 24 * half; i < 24 * half + 24; i++) { mbar_init(sb + B_GB + 8 * i, 1); mbar_expect_tx(sb + B_GB + 8 * i, i < 16 ? 16384 : 8192); }
          asm volatile("fence.mbarrier_init.release.cluster;" ::: "memory");
        }
        mbar_wait(sb + B_S0, 0);
        reset_o(0, RS_N, RS_D1);
        bar_sync(NB_PUB, 192);
        const uint4* src = reinterpret_cast<const uint4*>(&G->stats[256 * m256 + 128 * half]) + lane;
        const uint4* srk = reinterpret_cast<const uint4*>(&G->cskv[128 * nkv]) + lane;
        uint4 v0, v1, vk;
        it = 0;
        do { v0 = ld128_rlx(src); v1 = ld128_rlx(src + 32); vk = ld128_rlx(srk); }
        while ((tag_bad(v0, tg) || tag_bad(v1, tg) || tag_bad(vk, tg)) && ++it < POLL_LIMIT);
        fence_acquire_gpu();
        if (half) put_colsums(sb + OFF_BXK, lane, untag(vk.x), untag(vk.y), untag(vk.z), untag(vk.w));
        #pragma unroll
        for (int i = 0; i < 2; i++) {
          const uint4 v = i ? v1 : v0;
          uint32_t hi, lo;
          split_bf16(-0.5f * untag(v.x), -0.5f * untag(v.z), hi, lo);
          const uint32_t h0 = __byte_perm(hi, hi, 0x1010), h1 = __byte_perm(hi, hi, 0x3232), l0 = __byte_perm(lo, lo, 0x1010), l1 = __byte_perm(lo, lo, 0x3232);
          const uint32_t a = sb + OFF_AXK + half * 2048 + i * 1024 + lane * 32;
          sts128(a, h0, l0, 0, 0); sts128(a + 16, h1, l1, 0, 0);
          sts64(sb + OFF_RS256 + half * 512 + i * 256 + lane * 8, v.y & ~3u, v.w & ~3u);
          if (half == (m128 & 1)) {
            const uint32_t aq = sb + OFF_AXQ + i * 1024 + lane * 32;
            sts128(aq, h0, l0, 0, 0); sts128(aq + 16, h1, l1, 0, 0);
            sts64(sb + OFF_RSQ + i * 256 + lane * 8, v.y & ~3u, v.w & ~3u);
          }
        }
        fence_async_smem();
        __syncwarp();
        if (el) { sts32(sb + OFF_EP, ep1); mbar_arrive(sb + B_AUX); }
        reset_o(RS_N, 32, RS_D2);
        if (half == 0 && rank == 0 && lane < 12) st128_rlx(&G->oflag[(m128 * 6 + (lane >> 1)) * 32 + 4 * j + 4 * (lane & 1)], 0, 0, 0, 0);
        fence_gpu();
        __syncwarp();
        if (el) { st32_rlx(&G->oset[16 * c + 8 * half], ep1); if (half) mbar_arrive(sb + B_AUXQ); }
        if (!half) {
          const uint4* src = reinterpret_cast<const uint4*>(&G->csq[128 * j]) + lane;
          uint4 v0, v1, v2, v3;
          do { v0 = ld128_rlx(src); v1 = ld128_rlx(src + DM / 4); v2 = ld128_rlx(src + DM / 2); v3 = ld128_rlx(src + 3 * DM / 4); }
          while ((tag_bad(v0, tg) || tag_bad(v1, tg) || tag_bad(v2, tg) || tag_bad(v3, tg)) && ++it < POLL_LIMIT);
          put_colsums(sb + OFF_BXQ, lane, (untag(v0.x) + untag(v1.x)) + (untag(v2.x) + untag(v3.x)), (untag(v0.y) + untag(v1.y)) + (untag(v2.y) + untag(v3.y)),
                      (untag(v0.z) + untag(v1.z)) + (untag(v2.z) + untag(v3.z)), (untag(v0.w) + untag(v1.w)) + (untag(v2.w) + untag(v3.w)));
          fence_async_smem();
          __syncwarp();
          if (el) mbar_arrive(sb + B_AUXQ);
        }
      }
      if (half == 0) {
        for (uint32_t it = 0; __any_sync(~0u, ld32_rlx(&G->oset[m128 * 128 + 8 * (lane & 15)]) != ep1) && it < POLL_LIMIT; it++) {}
        fence_acquire_gpu();
        if (el) mbar_arrive(sb + B_OS);
      }
      if (!half) {
        #pragma unroll 1
        for (int hh = 0; hh < 2; hh++) {
          const uint32_t src = sb + (1 + rank) * R5 + hh * 8192, fa = sb + B_GA + 16 * rank + 8 * hh;
          mbar_wait2(sb + B_UO + 8 * hh, 0, sb + B_GB + 8 * rank, 0);
          if (el) bulk_s2peer(mapa(src, rank ^ 1), src, 8192, mapa(fa, rank ^ 1));
        }
        fetch_o(1);
      }
      else if (f < NFFN) {
        mbar_wait(sb + B_UO + 24, 0);
        mbar_wait2(sb + B_UO, 0, sb + B_UO + 8, 0);
        uint32_t t0 = (uint32_t)clock();
        #pragma unroll 1
        for (int i = 0; i < 12; i++) {
          const int e = (FF_ORD >> (4 * i)) & 15;
          const uint32_t dst = sb + 16384 * ((FF_SLOT >> (4 * e)) & 15), fb = sb + B_F + 8 * e;
          if (i >= 2) mbar_wait(sb + B_WC + 8 * ((0x100066553244ull >> (4 * e)) & 15), 0);
          wait_until(t0);
          t0 = (uint32_t)clock() + (i < FF_N ? FF_DT : FF_D2);
          if (el) {
            mbar_expect_tx(fb, 16384);
            if (e >= 8) tma_3d_h(dst, &P.wd, 0, 32 * f, 4 * e - 32, fb, ef);
            else { tma_2d_h(dst, &P.wg, 32 * f, 128 * e, fb, ef); tma_2d_h(dst + 8192, &P.wu, 32 * f, 128 * e, fb, ef); }
          }
        }
      }
      __syncwarp();
    }
    if (wp & 1) {
      __syncwarp();
      mbar_wait(sb + B_OUT + 8 * (wp >> 1), 0);
      uint32_t t0 = (uint32_t)clock();
      #pragma unroll 1
      for (int i = 0; i < 8; i++) {
        wait_until(t0);
        if (el) tma_store_2d(&P.out, 128 * j + 64 * (i & 1), 128 * m128 + 32 * (wp & 2) + 8 * (i & 6), sb + OFF_OUT + (i & 1) * 16384 + (wp & 2) * 4096 + (i & 6) * 1024, ef);
        t0 += OUT_D;
      }
      if (el) { bulk_commit(); bulk_wait_all(); fence_async_global(); mbar_arrive(sb + B_SD); }
    }
    __syncwarp();
    cluster_arrive(); cluster_wait();
    return;
  }

  asm volatile("setmaxnreg.inc.sync.aligned.u32 160;");
  cluster_wait();
  const int t = tid & 127, g = lane >> 2;
  const uint32_t sa = (16 * wp + (lane & 15)) * 128 + (((lane >> 4) ^ (lane & 7)) << 4);

  if (wg == 2) {
    float s[2] = {0.f, 0.f}, s2[2] = {0.f, 0.f}, ck[8] = {0.f, 0.f, 0.f, 0.f, 0.f, 0.f, 0.f, 0.f}, cs[8] = {0.f, 0.f, 0.f, 0.f, 0.f, 0.f, 0.f, 0.f};
    const uint32_t ebr = mapa(sb + B_EMPTYKV, lane & 1), tg = (ld32_rlx(&G->epoch) + 1) & 3;
    auto addx = [&](const uint4 v) {
      const uint32_t w[4] = {v.x, v.y, v.z, v.w};
      #pragma unroll
      for (int e = 0; e < 4; e++) { const float a = bf_lo(w[e]), d = bf_hi(w[e]); s[0] += a; s[1] += d; s2[0] = fmaf(a, a, s2[0]); s2[1] = fmaf(d, d, s2[1]); }
    };
    auto addc = [&](const uint4 v, float (&o)[8]) {
      o[0] += bf_lo(v.x); o[1] += bf_hi(v.x); o[2] += bf_lo(v.y); o[3] += bf_hi(v.y); o[4] += bf_lo(v.z); o[5] += bf_hi(v.z); o[6] += bf_lo(v.w); o[7] += bf_hi(v.w);
    };
    {
      const uint32_t ra = (16 * nkv + (t >> 3)) * 128 + (t & 7) * 16;
      const uint32_t ca = 32768 + (m256 >> 2) * 8192 + (t >> 1) * 128 + (((2 * (m256 & 3) + (t & 1)) ^ ((t >> 1) & 7)) << 4);
      int rd = 0;
      mbar_wait(sb + B_S0, 0);
      #pragma unroll 1
      for (int kb = 0; kb < 10; kb++) {
        const uint32_t st = sb + (kb & 3) * KV_STAGE;
        mbar_wait(sb + B_FULLKV + 8 * (kb & 3), (kb >> 2) & 1);
        const uint4 x0 = lds128(st + ra), w0 = lds128(st + ca);
        addx(x0); addc(w0, ck);
        __syncwarp();
        if (lane < 2) mbar_arrive_remote(ebr + 8 * (kb & 3), 1);
        if ((SKM >> kb) & 1) {
          if (rd) {
            mbar_wait(sb + B_G, (rd - 1) & 1);
            const uint32_t a = sb + OFF_G + (t >> 3) * 256 + (t & 7) * 16;
            const uint4 x1 = lds128(a), x2 = lds128(a + 128), w1 = lds128(sb + OFF_G + 4096 + t * 16), w2 = lds128(sb + OFF_G + 6144 + t * 16);
            addx(x1); addx(x2); addc(w1, ck); addc(w2, ck);
            bar_sync(NB_WG2, 128);
          }
          if (wp == 0 && elect_one()) {
            mbar_expect_tx(sb + B_G, 8192);
            if (rd < 3) {
              tma_2d(sb + OFF_G, &P.xs, 640 + 128 * rd, 256 * m256 + 16 * nkv, sb + B_G);
              tma_2d(sb + OFF_G + 4096, &P.ws, (1 + (m256 >> 2)) * DM + 64 * nkv + 16 * (m256 & 3), 640 + 128 * rd, sb + B_G);
            } else tma_2d(sb + OFF_G, &P.qs, 32 * (c & 31), 256 * (c >> 5), sb + B_G);
          }
          rd++;
        }
      }
    }
    const uint32_t scr = sb + OFF_WR;
    float sx = s[0] + s[1], sq = s2[0] + s2[1];
    #pragma unroll
    for (int o = 1; o < 8; o <<= 1) { sx += __shfl_xor_sync(~0u, sx, o); sq += __shfl_xor_sync(~0u, sq, o); }
    float v = reduce8(ck, lane);
    v += __shfl_xor_sync(~0u, v, 2);
    if (!(lane & 2)) stsf(scr + (wp * 16 + 8 * (lane & 1) + (lane >> 2)) * 4, v);

    bar_sync(NB_ZERO, 160);
    if ((lane & 7) == 0) {
      const float mean = sx * (1.f / DM);
      st64_rlx(&G->stats[256 * m256 + 16 * nkv + (t >> 3)], tagw(mean, tg), tagw(rsqrtf(fmaxf(sq * (1.f / DM) - mean * mean, 0.f) + 1e-5f), tg));
    }
    if (wp == 1 && lane < 16) {
      const uint32_t a = scr + lane * 4;
      st32_rlx(&G->cskv[128 * nkv + 16 * m256 + lane], tagw((ldsf(a) + ldsf(a + 64)) + (ldsf(a + 128) + ldsf(a + 192)), tg));
    }
    __syncwarp();
    bar_arrive(NB_PUB, 192);
    const uint4 wv = ld128_keep(P.wr + t * 8);
    #pragma unroll 1
    for (int i = 0; i < 2; i++) {
      mbar_wait(sb + B_G, i ^ 1);
      const uint32_t a = sb + OFF_G + t * 16;
      const uint4 u0 = lds128(a), u1 = lds128(a + 2048), u2 = lds128(a + 4096), u3 = lds128(a + 6144);
      addc(u0, cs); addc(u1, cs); addc(u2, cs); addc(u3, cs);
      bar_sync(NB_WG2, 128);
      if (i == 0 && wp == 0 && elect_one()) { mbar_expect_tx(sb + B_G, 8192); tma_2d(sb + OFF_G, &P.qs, 32 * (c & 31), 256 * (c >> 5) + 128, sb + B_G); }
    }
    float sw = (bf_lo(wv.x) + bf_hi(wv.x)) + (bf_lo(wv.y) + bf_hi(wv.y)) + (bf_lo(wv.z) + bf_hi(wv.z)) + (bf_lo(wv.w) + bf_hi(wv.w));
    #pragma unroll
    for (int o = 16; o; o >>= 1) sw += __shfl_xor_sync(~0u, sw, o);
    if (lane == 0) stsf(sb + OFF_SUMWR + wp * 4, sw);
    if ((t >> 4) == j) {
      const uint32_t a = sb + OFF_WR + (t & 15) * 32;
      sts128(a, wv.x << 16, wv.x & 0xffff0000u, wv.y << 16, wv.y & 0xffff0000u);
      sts128(a + 16, wv.z << 16, wv.z & 0xffff0000u, wv.w << 16, wv.w & 0xffff0000u);
    }
    v = reduce8(cs, lane);
    stsf(sb + OFF_G + (wp * 32 + 8 * (lane & 3) + (lane >> 2)) * 4, v);
    bar_sync(NB_WG2, 128);
    if (wp == 0) {
      const uint32_t a = sb + OFF_G + lane * 4, cq = tagw((ldsf(a) + ldsf(a + 128)) + (ldsf(a + 256) + ldsf(a + 384)), tg);
      st32_rlx(&G->csq[(c >> 5) * DM + 32 * (c & 31) + lane], cq);
      if (lane == 0) mbar_arrive_at(sb + B_W, rank, (cq & P.zero) + 1);
    }
  }

  uint32_t xr[32];
  {
    const bool isq = wg == 2;
    float acc[2][64];
    {
      const uint32_t emptyb = mapa(sb + (isq ? B_EMPTY5 : B_EMPTYKV), t & 1);
      auto correct = [&](uint32_t xa, uint32_t xb) {
        wg_fence();
        wgmma_sa_n128<0, 1, H0, H0>(acc[0], dlo(SB0, 0) + (xa >> 4), dlo(SB0, 0) + (xb >> 4));
        wgmma_sa_n128<0, 1, H0, H0>(acc[1], dlo(SB0, 0) + (xa >> 4) + 64, dlo(SB0, 0) + (xb >> 4));
        wg_commit();
      };
      if (!isq) {
        mbar_wait(sb + B_S0, 0);
        if (wg) mbar_wait(sb + B_FULLKV, 0);
        #pragma unroll 1
        for (int kb = 0; kb < 16; kb++) {
          const uint32_t da = dlo(SB0, 16) + wg * 1024 + (kb & 3) * (KV_STAGE >> 4), db = dlo(SB0 + 32768, 8192) + (kb & 3) * (KV_STAGE >> 4);
          wg_fence();
          #pragma unroll
          for (int k = 0; k < 4; k++) {
            wgmma_ss_n128<0, 1, H128, H128>(acc[0], da + 2 * k, db + 128 * k, k > 0 || kb != 0);
            wgmma_ss_n128<0, 1, H128, H128>(acc[1], da + 512 + 2 * k, db + 128 * k, k > 0 || kb != 0);
          }
          wg_commit();
          wg_wait<1>();
          if (kb > 0 && t < 2) mbar_arrive_remote(emptyb + 8 * ((kb - 1) & 3), kb > 10 ? 3 : 1);
          if (kb < 15) mbar_wait(sb + B_FULLKV + 8 * ((kb + 1) & 3), ((kb + 1) >> 2) & 1);
          if (kb == 0) mbar_wait(sb + B_FULLKV, 0);
          if (kb == 15 - LAG && wg == 1) bar_sync(NB_LAG, 256);
        }
        bar_arrive(wg ? NB_QGO : NB_LAG, 256);
        mbar_wait(sb + B_AUX, 0);
        correct(OFF_AXK + wg * 2048, OFF_BXK);
        wg_wait<0>();
        if (t < 2) mbar_arrive_remote(emptyb + 24, 3);
        fence_regs(acc[0]); fence_regs(acc[1]);
      const uint32_t stg = sb + OFF_X + (1 - wg) * 24576;
      const uint32_t va = stg + 16384 + (16 * wp + (lane & 15)) * 64 + (((lane >> 4) ^ ((lane >> 1) & 3)) << 4);
      const uint32_t ra = sb + OFF_RS256 + (128 * wg + 16 * wp + g) * 4;
      const float rs[4] = {ldsf(ra), ldsf(ra + 32), ldsf(ra + 256), ldsf(ra + 288)};
      float p[2][16];
      uint32_t vf[16], kf[2][16];
      auto project = [&](const uint32_t (&f)[16], uint32_t db) {
        wg_fence();
        #pragma unroll
        for (int i = 0; i < 2; i++) {
          wgmma_rs_n32<1, H64>(p[i], f[8*i], f[8*i+1], f[8*i+2], f[8*i+3], db, 0);
          wgmma_ra_n32<1, H64>(p[i], f[8*i+4], f[8*i+5], f[8*i+6], f[8*i+7], db + 64);
        }
        wg_commit();
      };
      auto fold = [&](uint32_t (&f)[16], int col, float sc) {
        #pragma unroll
        for (int i = 0; i < 16; i++) {
          const float r = rs[2 * (i >> 3) + (i & 1)] * sc;
          f[i] = pack_bf16(acc[i >> 3][col + 2 * (i & 7)] * r, acc[i >> 3][col + 2 * (i & 7) + 1] * r);
          asm volatile("" : "+r"(f[i]));
        }
      };
      auto put_v = [&](const uint32_t (&f)[16]) {
        #pragma unroll
        for (int k = 0; k < 4; k++) stsm4((va ^ ((k & 1) << 5)) + (k >> 1) * 4096, f[4*k], f[4*k+1], f[4*k+2], f[4*k+3]);
      };
      fold(vf, 48, 1.f);
      mbar_wait(sb + B_W, 0);
      fold(kf[0], 0, LOG2E);
      #pragma unroll
      for (int i = 0; i < 32; i++) p[i >> 4][i & 15] = acc[i >> 4][i & 15];
      project(kf[0], dlo(SB0 + OFF_WPHIK, 16));
      mbar_wait(sb + B_W, 0);
      {
        uint32_t v0[16];
        fold(kf[1], 16, LOG2E);
        fold(v0, 32, 1.f);
        if (wg == 1) bar_sync(NB_DN, 256);
        put_v(v0);
      }
      wg_wait<0>();
      fence_regs(p[0]); fence_regs(p[1]);
      if (wg == 1) bar_arrive(NB_WG01, 256);
      #pragma unroll 1
      for (int h = 0; h < 2; h++) {
        uint32_t ph[4][8];
        float rsum[2][4];
        dual_exp2(p[0], ph[0], ph[1]); dual_exp2(p[1], ph[2], ph[3]);
        row_sums(rsum, ph, dlo(SB0 + OFF_SEL, 16));
        if (wg == 0 && h == 0) { bar_arrive(NB_DN, 256); bar_sync(NB_WG01, 256); }
        if (h == 1) {
          if (wg == 1) bar_sync(NB_DN, 256);
          put_v(vf);
        }
        wg_wait<0>();
        fence_regs(rsum[0]); fence_regs(rsum[1]);
        if (__builtin_expect(__any_sync(~0u, !((rsum[0][0] + rsum[0][1]) + (rsum[0][2] + rsum[0][3]) + (rsum[1][0] + rsum[1][1]) + (rsum[1][2] + rsum[1][3]) < EXP_LIM)), 0)) {
          dual_exp2_shifted(p, ph);
          #pragma unroll
          for (int i = 0; i < 8; i++) {
            const uint32_t* f = &ph[i >> 1][i & 1];
            float a = (bf_lo(f[0]) + bf_hi(f[0])) + (bf_lo(f[2]) + bf_hi(f[2])) + (bf_lo(f[4]) + bf_hi(f[4])) + (bf_lo(f[6]) + bf_hi(f[6]));
            a += __shfl_xor_sync(~0u, a, 1);
            rsum[i >> 2][2 * (i & 1) + ((i >> 1) & 1)] = a + __shfl_xor_sync(~0u, a, 2);
          }
        }
        if (h == 0) project(kf[1], dlo(SB0 + OFF_WPHIK1, 16));
        normalize(ph, rsum);
        #pragma unroll
        for (int i = 0; i < 8; i++) {
          const uint32_t* f = &ph[i >> 1][4 * (i & 1)];
          stsm4(((stg + sa) ^ ((i & 3) << 5)) + (i >> 2) * 8192, f[0], f[1], f[2], f[3]);
        }
        fence_async_smem();
        if (wg == h) {
          float kv[20];
          #pragma unroll
          for (int w = 0; w < 2; w++) {
            const uint32_t da = dlo(SB0 + OFF_X, 16) + (h ^ w ^ 1) * 1536, db = dlo(SB0 + OFF_X + 16384, OFF_ONES - OFF_X - 16384) - (h ^ w ^ 1) * (1536 * 65535);
            if (w) bar_sync(NB_ST, 256); else bar_sync(NB_L0 + h, 128);
            wg_fence();
            #pragma unroll
            for (int k = 0; k < 8; k++) {
              if (k == 0 && w == 0) wgmma_sz_n40<1, 1, H128, H64>(kv, da, db);
              else wgmma_sa_n40<1, 1, H128, H64>(kv, da + k * 128, db - k * (64 * 65535));
            }
            wg_commit();
          }
          float4* dst = &G->kvacc[(ha + 2 * h) * KVP + t];
          wg_wait<0>();
          fence_regs(kv);
          if (h == 0) bar_arrive(NB_DN, 256); else if (t < 2) { mbar_arrive_at(sb + B_EMPTY5 + 40, t, 2); if (t == 0) mbar_arrive(sb + B_KD); }
          kv[17] = kv[18];
          #pragma unroll
          for (int i = 0; i < 6; i++) red_add_f32x4(dst + 128 * i, kv[3*i], kv[3*i+1], kv[3*i+2], 1.f);
        } else bar_arrive(NB_ST, 256);
        wg_wait<0>();
        fence_regs(p[0]); fence_regs(p[1]);
      }
      #pragma unroll
      for (int i = 0; i < 32; i++) asm volatile("mov.b32 %0, 0;" : "=r"(xr[i]));
      } else {
        uint32_t so = 0, po = 0, par = 0;
        mbar_wait(sb + B_FULL5, 0);
        bar_sync(NB_QGO, 256);
        #pragma unroll 1
        for (int kb = 0; kb < 16 - ML; kb++) {
          const uint32_t da = dlo(SB0, 16) + so * 256, db = dlo(SB0 + 16384, 8192) + so * 256;
          #pragma unroll
          for (int k = 0; k < 4; k++) {
            wg_fence();
            wgmma_ss_n128<0, 1, H128, H128>(acc[0], da + 2 * k, db + 128 * k, k > 0 || kb != 0);
            wgmma_ss_n128<0, 1, H128, H128>(acc[1], da + 512 + 2 * k, db + 128 * k, k > 0 || kb != 0);
            wg_commit();
            if (k == 1 && kb > 0 && t < 2) mbar_arrive_remote(emptyb + po, 2);
            if (k == 3) {
              po = so; so += 8;
              if (so == 40) { so = 0; par ^= 1; }
              mbar_wait(sb + B_FULL5 + so, par);
            }
            if ((QW >> k) & 1) wg_wait<2>(); else wg_wait<1>();
          }
        }
        auto block = [&](const int kb, const int i) {
          wg_fence();
          #pragma unroll
          for (int k = 0; k < 4; k++) wgmma_sa_n128<0, 1, H128, H128>(acc[i], dlo(SB0, 16) + (kb % 5) * 2048 + 512 * i + 2 * k, dlo(SB0 + 16384, 8192) + (kb % 5) * 2048 + 128 * k);
          wg_commit();
        };
        auto hand_over = [&](const int i) {
          const uint32_t ta = sb + (1 + rank) * R5 + sa + i * 8192;
          #pragma unroll
          for (int k = 0; k < 4; k++) {
            const float* a = &acc[i][32 * (k >> 1) + 8 * (k & 1)];
            stsm4(ta ^ (k << 5), pack_bf16(a[0], a[1]), pack_bf16(a[2], a[3]), pack_bf16(a[4], a[5]), pack_bf16(a[6], a[7]));
          }
        };
        mbar_wait2(sb + B_AUXQ, 0, sb + B_OS, 0);
        correct(OFF_AXQ, OFF_BXQ);
        #pragma unroll
        for (int kb = 16 - ML; kb < 16; kb++) {
          block(kb, 0);
          if (kb < 15) mbar_wait(sb + B_FULL5 + 8 * ((kb + 1) % 5), ((kb + 1) / 5) & 1);
          if (kb == 16 - ML) { wg_wait<2>(); if (t < 2) mbar_arrive_remote(emptyb + 8 * ((kb - 1) % 5), 2); }
        }
        mbar_wait(sb + B_RC, 0);
        block(16 - ML, 1);
        block(17 - ML, 1);
        wg_wait<2>();
        fence_regs(acc[0]);
        hand_over(0);
        fence_async_smem();
        bar_arrive(NB_Q0, 256);
        #pragma unroll
        for (int kb = 18 - ML; kb <= 16; kb++) {
          wg_wait<1>();
          if (t < 2) mbar_arrive_remote(emptyb + 8 * ((kb - 2) % 5), 2);
          if (kb < 16) block(kb, 1);
        }
        mbar_wait(sb + B_RC + 8, 0);
        wg_wait<0>();
        if (t < 2) mbar_arrive_remote(emptyb, 2);
        fence_regs(acc[1]);
        hand_over(1);
        fence_async_smem();
        bar_arrive(NB_Q0 + 1, 256);
        #pragma unroll
        for (int i = 0; i < 32; i++) { const float* a = &acc[(i >> 3) & 1][16 + 32 * (i >> 4) + 2 * (i & 7)]; xr[i] = pack_bf16(a[0], a[1]); }
      }
    }
    float p[2][16];
    #pragma unroll
    for (int i = 0; i < 32; i++) asm volatile("mov.b32 %0, 0;" : "=f"(p[i >> 4][i & 15]));
    auto project_r = [&](int w) {
      wg_fence();
      #pragma unroll
      for (int h = 0; h < 2; h++) {
        wgmma_rs_n32<1, H64>(p[h], xr[8*h], xr[8*h+1], xr[8*h+2], xr[8*h+3], dlo(SB0 + OFF_WPHIQ, 16) + 128 * w, 0);
        wgmma_ra_n32<1, H64>(p[h], xr[8*h+4], xr[8*h+5], xr[8*h+6], xr[8*h+7], dlo(SB0 + OFF_WPHIQ, 16) + 128 * w + 64);
      }
      wg_commit();
    };
    auto capture = [&](const int i) {
      if (!i) mbar_wait(sb + B_R, 0);
      #pragma unroll
      for (int k = 0; k < 4; k++) ldsm4(((sb + (1 + rank) * R5 + wg * 8192 + sa) ^ (k << 5)) + i * 2 * R5, xr[16*i+4*k], xr[16*i+4*k+1], xr[16*i+4*k+2], xr[16*i+4*k+3]);
      const uint32_t one = (((xr[16*i] | xr[16*i+4]) | (xr[16*i+8] | xr[16*i+12])) & P.zero) + 1;
      if (lane == 0) mbar_arrive_at(sb + (i ? B_RX : B_RC + 8 * wg), i ? wg : rank, one);
    };
    const uint32_t rq = sb + OFF_RSQ + (16 * wp + g) * 4 + 256 * (wg & 1), rb = rq + 128 * (wg & 2);
    const float cc[2][2] = {{ldsf(rq) * LOG2E, ldsf(rq + 32) * LOG2E}, {ldsf(rb) * LOG2E, ldsf(rb + 32) * LOG2E}};
    {
      const uint4* src = reinterpret_cast<const uint4*>(&G->kvacc[(4 * j + wg) * KVP + t]);
      const uint32_t full = kv_count(__float_as_uint(ldsf(sb + OFF_EP)), 8);
      uint4 v[12];
      #pragma unroll
      for (int i = 0; i < 12; i++) v[i] = i < 6 || isq ? ld128_rlx(src + 128 * i) : make_uint4(0, 0, 0, full);
      if (isq) {
        project_r(2);
        wg_wait<0>();
        #pragma unroll
        for (int i = 0; i < 16; i++) xr[i] = xr[16 + i];
      } else {
        capture(0);
      }
      #pragma unroll 1
      for (uint32_t it = 0; it < POLL_LIMIT; it++) {
        uint32_t bad = 0;
        #pragma unroll
        for (int i = 0; i < 12; i++) bad |= v[i].w ^ full;
        if (!__any_sync(~0u, bad != 0)) break;
        #pragma unroll
        for (int i = 0; i < 12; i++) if (i < 6 || isq) v[i] = ld128_rlx(src + 128 * i);
      }
      mbar_wait(sb + B_KD, 0);
      #pragma unroll
      for (int e = 0; e < 2; e++) {
        if (e == 0 || isq) {
          float f[18];
          #pragma unroll
          for (int i = 0; i < 6; i++) { f[3*i] = __uint_as_float(v[6*e+i].x); f[3*i+1] = __uint_as_float(v[6*e+i].y); f[3*i+2] = __uint_as_float(v[6*e+i].z); }
          const uint32_t ka = sb + OFF_KVZ + (wg + e) * 5120 + wp * 1280 + lane * 16;
          stsm4(ka, pack_bf16(f[0], f[1]), pack_bf16(f[2], f[3]), pack_bf16(f[4], f[5]), pack_bf16(f[6], f[7]));
          stsm4(ka + 512, pack_bf16(f[8], f[9]), pack_bf16(f[10], f[11]), pack_bf16(f[12], f[13]), pack_bf16(f[14], f[15]));
          stsm2(ka + 1024, pack_bf16(f[16], 1.f), pack_bf16(f[17], 1.f));
        }
      }
    }
    fence_async_smem();
    if (wg == 1) bar_arrive(NB_DN, 256);
    #pragma unroll 1
    for (int e = wg; e < wg + 1 + (wg >> 1); e++) {
      const int half = e >> 1, hh = e & 1, turn = e;
      const uint32_t ao = (1 + rank) * R5 + hh * 8192;
      uint32_t ph[4][8];
      #pragma unroll
      for (int i = 0; i < 32; i++) asm volatile("mov.b32 %0, 0;" : "=r"(ph[i >> 3][i & 7]));
      uint32_t shifted = 0;
      asm volatile("" : "+r"(shifted));
      #pragma unroll 1
      for (;;) {
        if (shifted) dual_exp2_shifted(p, ph);
        uint32_t first = (shifted ^ 1) & !isq;
        asm volatile("" : "+r"(first));
        if (first) {
          bar_sync(NB_Q0 + wg, 256);
          const uint32_t da = dlo(SB0, 16) + (ao >> 4), db = dlo(SB0 + OFF_WPHIQ, 16);
          wg_fence();
          #pragma unroll
          for (int h = 0; h < 2; h++) {
            wgmma_ss_n32<0, 1, H128, H64>(p[h], da + 4 * h, db + 128 * h, 0);
            wgmma_sa_n32<0, 1, H128, H64>(p[h], da + 4 * h + 2, db + 128 * h + 64);
          }
          wg_commit();
          capture(1);
          wg_wait<0>();
        }
        fence_regs(p[0]); fence_regs(p[1]);
        uint32_t again = shifted;
        asm volatile("" : "+r"(again));
        if (again) break;
        float s2[4] = {0.f, 0.f, 0.f, 0.f};
        #pragma unroll
        for (int i = 0; i < 32; i++) { float& x = p[i >> 4][i & 15]; x *= cc[i >> 4][(i >> 1) & 1]; s2[i & 3] = fmaf(x, x, s2[i & 3]); }
        if (!__any_sync(~0u, !((s2[0] < ARG_LIM2) & (s2[1] < ARG_LIM2) & (s2[2] < ARG_LIM2) & (s2[3] < ARG_LIM2)))) break;
        shifted = 1;
      }
      if (e == 1 || e == 2) bar_sync(NB_TOK + e - 1, 256);
      float ac[4][20];
      auto numer = [&](int h) {
        const uint32_t (*f)[8] = &ph[2 * h];
        const uint32_t db = dlo(SB0 + OFF_KVZ, 128) + (half ? e : h) * 320;
        wg_fence();
        #pragma unroll
        for (int i = 0; i < 2; i++) {
          wgmma_rz_n40<1, dhi(256, 0)>(ac[2*h+i], f[i][0], f[i][1], f[i][2], f[i][3], db + i * 160);
          wgmma_ra_n40<1, dhi(256, 0)>(ac[2*h+i], f[i][4], f[i][5], f[i][6], f[i][7], db + (i * 160 + 80));
        }
        wg_commit();
      };
      const uint32_t oa = (16 * wp + g) * 128 + (((lane & 3) ^ g) << 4);
      auto finish = [&](int h) {
        const float* ap = ac[2 * h]; const float* am = ac[2 * h + 1];
        const float ip0 = rcp(ap[17]), im0 = rcp(am[17]), ip1 = rcp(ap[19]), im1 = rcp(am[19]);
        const float d0 = rcp(fmaf(ap[16], ip0, fmaf(am[16], im0, 1e-6f))), d1 = rcp(fmaf(ap[18], ip1, fmaf(am[18], im1, 1e-6f)));
        const float a0 = ip0 * d0, b0 = im0 * d0, a1 = ip1 * d1, b1 = im1 * d1;
        #pragma unroll
        for (int r = 0; r < 2; r++) {
          const float a = r ? a1 : a0, b = r ? b1 : b0;
          uint32_t w[4];
          #pragma unroll
          for (int k = 0; k < 4; k++) w[k] = pack_bf16(fmaf(ap[4*k+2*r], a, am[4*k+2*r] * b), fmaf(ap[4*k+2*r+1], a, am[4*k+2*r+1] * b));
          const uint32_t off = (oa ^ ((half ? rank : h) << 6)) + r * 1024;
          st128_rlx(reinterpret_cast<uint8_t*>(G->o + (m128 * 16 + (half ? 2 * (j & 6) + 2 * hh + 1 : 2 * j)) * 8192 + (half ? h : hh) * 4096) + off, w[0], w[1], w[2], w[3]);
          if (!half) sts128(sb + ao + off, w[0], w[1], w[2], w[3]);
        }
        if ((half || h) && lane == 0) st32_rlx(&G->oflag[(m128 * 6 + (half ? 2 * e - 2 + h : hh)) * 32 + 4 * j + wp], 1);
      };
      if (!shifted) dual_exp2(p[0], ph[0], ph[1]);
      numer(0);
      if (!shifted) dual_exp2(p[1], ph[2], ph[3]);
      if (turn < 2) bar_arrive(NB_TOK + turn, 256);
      if (wg == 0) bar_sync(NB_DN, 256);
      numer(1);
      wg_wait<1>();
      fence_regs(ac[0]); fence_regs(ac[1]);
      finish(0);
      wg_wait<0>();
      fence_regs(ac[2]); fence_regs(ac[3]);
      #pragma unroll
      for (int i = 0; i < 32; i++) asm volatile("mov.b32 %0, 0;" : "=f"(p[i >> 4][i & 15]));
      if (e == 2) project_r(3);
      finish(1);
      if (!half) fence_async_smem();
      __syncwarp();
      if (lane == 0) mbar_arrive(sb + B_UO + 8 * e);
      wg_wait<0>();
    }
    if (isq) cluster_arrive();
  }

  {
  int lane;
  asm volatile("mov.u32 %0, %%laneid;" : "=r"(lane));
  const int g = lane >> 2, q = lane & 3;
  if (wg < 2) {
    float h[64];
    {
      #pragma unroll
      for (int i = 0; i < 32; i++) { h[2*i] = bf_lo(xr[i]); h[2*i+1] = bf_hi(xr[i]); }
      fence_regs(h);
      const uint32_t emptyb = mapa(sb + B_EMPTY5, t & 1);
      uint32_t s = 1 + rank, ps = 0;
      mbar_wait2(sb + B_GB + 8 * rank, 0, sb + B_UO + 8 * wg, 0);
      #pragma unroll
      for (int i = 0; i < 16; i++) {
        const uint32_t da = dlo(SB0, 16) + s * 2048 + wg * 512, db = dlo(SB0 + 16384, 8192) + s * 2048;
        wg_fence();
        #pragma unroll
        for (int k = 0; k < 4; k++) wgmma_sa_n128<0, 1, H128, H128>(h, da + k * 2, db + k * 128);
        wg_commit();
        const uint32_t ns = i ? (i + 2) % 6 : 2 - rank;
        const uint32_t nb = i ? i + 1 : 1 - rank, b0 = sb + B_GB + 8 * nb, b1 = sb + B_GA + 16 * nb + 8 * wg;
        const bool here = i == 15 || mbar_test2(b0, 0, b1, 0);
        wg_wait<1>();
        if (!(((2 * REL + 1) >> i) & 1) && i < 14 && t < 2) mbar_arrive_remote(emptyb + 8 * ps, 1);
        if ((REL >> i) & 1) { wg_wait<0>(); if (t < 2) mbar_arrive_remote(emptyb + 8 * s, 1); }
        if (!here) mbar_wait2(b0, 0, b1, 0);
        ps = s; s = ns;
      }
    }
    cluster_arrive();
    float2 wr[16];
    #pragma unroll
    for (int i = 0; i < 16; i++) wr[i] = lds64f(sb + OFF_WR + 32 * i + 8 * q);
    const int r0 = 64 * wg + 16 * wp + g;
    float sum0, sum1, dot0, dot1, sq0, sq1;
    uint32_t redo = 0;
    asm volatile("" : "+r"(redo));
    #pragma unroll 1
    for (;;) {
    if (redo) {
      wg_wait<0>();
      const uint32_t* xp = reinterpret_cast<const uint32_t*>(P.x + (size_t)(128 * m128 + r0) * DM + 128 * j) + q;
      #pragma unroll
      for (int i = 0; i < 32; i++) { const uint32_t v = xp[4 * (i >> 1) + (i & 1) * 4 * DM]; h[2*i] = bf_lo(v); h[2*i+1] = bf_hi(v); }
      #pragma unroll 1
      for (int ks = 0; ks < 64; ks++) {
        const int kb = ks >> 2, kk = 16 * (ks & 3);
        const bf16* op = G->o + (m128 * 16 + kb) * 8192 + r0 * 64 + 2 * q;
        const int o0 = ((kk >> 3) ^ g) << 3;
        const uint32_t* w = reinterpret_cast<const uint32_t*>(P.wo_p + (size_t)(((kb & 1) ? 256 * (kb >> 2) + 32 * (kb & 2) + 32 + 4 * (kk & 32) : 64 * kb + 2 * (kk & 32)) +
                                                                              ((kk & 16) >> 2) + 4 * (g & 6) + (g & 1)) * DM + 128 * j) + q;
        uint32_t b[32], a0, a1, a2, a3, it = 0;
        #pragma unroll
        for (int n = 0; n < 32; n++) b[n] = w[4 * (n >> 1) + (n & 1) * DM];
        do { a0 = ld32_rlx(op + o0); a1 = ld32_rlx(op + 512 + o0); a2 = ld32_rlx(op + (o0 ^ 8)); a3 = ld32_rlx(op + 512 + (o0 ^ 8)); }
        while (max(max(a0, a1), max(a2, a3)) == ~0u && ++it < POLL_LIMIT);
        __syncwarp();
        #pragma unroll
        for (int n = 0; n < 16; n++) mma16816(h[4*n], h[4*n+1], h[4*n+2], h[4*n+3], a0, a1, a2, a3, transpose8(b[2*n]), transpose8(b[2*n+1]));
      }
    }
    wg_wait<0>();
    fence_regs(h);
    sum0 = 0.f, sum1 = 0.f, dot0 = 0.f, dot1 = 0.f, sq0 = 0.f, sq1 = 0.f;
    #pragma unroll
    for (int i = 0; i < 16; i++) {
      sum0 += h[4*i] + h[4*i+1]; sum1 += h[4*i+2] + h[4*i+3];
      sq0 = fmaf(h[4*i], h[4*i], fmaf(h[4*i+1], h[4*i+1], sq0)); sq1 = fmaf(h[4*i+2], h[4*i+2], fmaf(h[4*i+3], h[4*i+3], sq1));
      dot0 = fmaf(h[4*i], wr[i].x, fmaf(h[4*i+1], wr[i].y, dot0)); dot1 = fmaf(h[4*i+2], wr[i].x, fmaf(h[4*i+3], wr[i].y, dot1));
    }
    if (!__any_sync(~0u, !redo & (h[0] != h[0] | h[2] != h[2]))) break;
    redo = 1;
    }
    float4* const rs = &G->rstat[128 * m128 + r0];
    {
      const bool up = q & 2;
      float a = up ? sum1 : sum0, b = up ? sq1 : sq0, d = up ? dot1 : dot0;
      a += __shfl_xor_sync(~0u, up ? sum0 : sum1, 2); b += __shfl_xor_sync(~0u, up ? sq0 : sq1, 2); d += __shfl_xor_sync(~0u, up ? dot0 : dot1, 2);
      a += __shfl_xor_sync(~0u, a, 1); b += __shfl_xor_sync(~0u, b, 1); d += __shfl_xor_sync(~0u, d, 1);
      if ((q & 1) == 0) red_add_f32x4(rs + 4 * q, a, b, d, 1.f);
    }
    bar_sync(NB_WG01, 256);
    float rstd[2], bm[2];
    uint32_t best;
    {
      const float2 swa = lds64f(sb + OFF_SUMWR), swb = lds64f(sb + OFF_SUMWR + 8);
      const float sw = (swa.x + swa.y) + (swb.x + swb.y);
      uint4 a[2]; uint32_t it = 0, key[2];
      do { a[0] = ld128_rlx(rs); a[1] = ld128_rlx(rs + 8); } while (__any_sync(~0u, (a[0].w & a[1].w) != 0x41000000u) && ++it < POLL_LIMIT);
      #pragma unroll
      for (int i = 0; i < 2; i++) {
        const float mean = __uint_as_float(a[i].x) * (1.f / DM);
        rstd[i] = rsqrtf(fmaxf(__uint_as_float(a[i].y) * (1.f / DM) - mean * mean, 0.f) + 1e-5f);
        bm[i] = -mean * rstd[i];
        const uint32_t rr = __float_as_uint(fmaf(__uint_as_float(a[i].z), rstd[i], sw * bm[i]));
        key[i] = ((rr ^ ((uint32_t)((int32_t)rr >> 31) | 0x80000000u)) & ~2047u) | (2047 - 128 * m128 - r0 - 8 * i);
      }
      asm volatile("redux.sync.max.u32 %0, %1, 0xffffffff;" : "=r"(best) : "r"(max(key[0], key[1])));
    }
    const int slot = m128 * 8 + warp, win = ~best & 15;
    if (lane < 4) st32_rlx(&G->key[(4 * j + lane) * 128 + slot], best);
    if ((win & 7) == g) {
      const bool up = win & 8;
      const float ra = up ? rstd[1] : rstd[0], rb = up ? bm[1] : bm[0];
      uint32_t x[16];
      #pragma unroll
      for (int i = 0; i < 16; i++) x[i] = pack_bf16(fmaf(up ? h[4*i+2] : h[4*i], ra, rb), fmaf(up ? h[4*i+3] : h[4*i+1], ra, rb));
      #pragma unroll
      for (int i = 0; i < 4; i++) st128_rlx(&G->cand[slot * 512 + 64 * j + 16 * i + 4 * q], x[4*i], x[4*i+1], x[4*i+2], x[4*i+3]);
    }
    __syncwarp();
    bar_arrive(NB_G2E, 384);
    {
      const float a0 = 1.f + rstd[0], b0 = bm[0], a1 = 1.f + rstd[1], b1 = bm[1];
      #pragma unroll
      for (int k = 0; k < 8; k++)
        stsm4(((sb + OFF_OUT + wg * 8192 + sa) ^ ((k & 3) << 5)) + (k >> 2) * 16384,
              pack_bf16(fmaf(h[8*k], a0, b0), fmaf(h[8*k+1], a0, b0)),     pack_bf16(fmaf(h[8*k+2], a1, b1), fmaf(h[8*k+3], a1, b1)),
              pack_bf16(fmaf(h[8*k+4], a0, b0), fmaf(h[8*k+5], a0, b0)),   pack_bf16(fmaf(h[8*k+6], a1, b1), fmaf(h[8*k+7], a1, b1)));
      fence_async_smem();
      __syncwarp();
      if (lane == 0) mbar_arrive(sb + B_OUT + 8 * wg);
    }
    {
      uint32_t wa[8][4][4];
      const uint32_t wb = sb + 16384 * (((uint32_t)FF_SLOT >> (4 * warp)) & 15) + ((lane & 7) + ((lane >> 4) << 3)) * 64 + ((((lane >> 3) & 1) ^ ((lane >> 1) & 3)) << 4);
      if (f < NFFN) mbar_wait(sb + B_F + 8 * warp, 0);
      #pragma unroll
      for (int i = 0; i < 32; i++) ldsm4t((wb ^ ((i & 1) << 5)) + ((i >> 1) & 1) * 8192 + (i >> 2) * 1024, wa[i >> 2][i & 3][0], wa[i >> 2][i & 3][1], wa[i >> 2][i & 3][2], wa[i >> 2][i & 3][3]);
      bar_sync(NB_XS, 384);
      uint4 xs[4];
      #pragma unroll
      for (int i = 0; i < 4; i++) xs[i] = lds128(sb + OFF_XSEL + 256 * warp + 64 * i + 16 * q);
      float d[4][4];
      #pragma unroll
      for (int ks = 0; ks < 8; ks++) {
        #pragma unroll
        for (int m = 0; m < 4; m++) {
          if (ks == 0) { d[m][0] = 0.f; d[m][1] = 0.f; d[m][2] = 0.f; d[m][3] = 0.f; }
          mma16816(d[m][0], d[m][1], d[m][2], d[m][3], wa[ks][m][0], wa[ks][m][1], wa[ks][m][2], wa[ks][m][3],
                   (ks & 1) ? xs[ks >> 1].z : xs[ks >> 1].x, (ks & 1) ? xs[ks >> 1].w : xs[ks >> 1].y);
        }
      }
      if (q == 0) {
        #pragma unroll
        for (int m = 0; m < 8; m++) stsf(sb + OFF_GU + (8 * m + g) * 48 + 4 * warp, d[m >> 1][2 * (m & 1)]);
      }
      bar_arrive(NB_ACT, 384);
    }
    {
      const uint32_t ky = __float_as_uint(ldsf(sb + OFF_KEY));
      const int row = 2047 - (ky & 2047) - 128 * m128;
      if ((uint32_t)row < 128u) {
        const int l = tid >> 3, vi = (j & 1) + ((lane >> 2) & 1), e = 3 * vi + q - 4 * (j & 1);
        const float kr = __uint_as_float((ky & ~2047u) ^ ((ky >> 31) ? 0x80000000u : 0xfffff800u));
        const int col = 32 * (l & 3) + 16 * (e & 1) + 4 * (e & 2) + (l >> 2);
        const float sg = rcp(1.f + ex2(-LOG2E * kr));
        const uint32_t base = __float_as_uint(ldsf(sb + OFF_OUT + (col >> 6) * 16384 + row * 128 + ((((col >> 3) ^ row) & 7) << 4) + 2 * (col & 6)));
        const float4* yp = &G->yacc[(q * 3 + vi) * 128 + 32 * (j >> 1) + l];
        uint32_t it = 0;
        uint4 v;
        mbar_wait(sb + B_SD, 0);
        do { v = ld128_rlx(yp); } while (__any_sync(~0u, __uint_as_float(v.w) != (float)(NFFN / 4)) && ++it < POLL_LIMIT);
        float y0 = __uint_as_float(v.x), y1 = __uint_as_float(v.y), y2 = __uint_as_float(v.z);
        #pragma unroll
        for (int o = 1; o < 4; o <<= 1) { y0 += __shfl_xor_sync(~0u, y0, o); y1 += __shfl_xor_sync(~0u, y1, o); y2 += __shfl_xor_sync(~0u, y2, o); }
        if (q < 3 && (uint32_t)e < 4u)
          P.out_p[(size_t)(128 * m128 + row) * DM + 128 * j + col] = __float2bfloat16(fmaf(q == 0 ? y0 : q == 1 ? y1 : y2, sg, (col & 1) ? bf_hi(base) : bf_lo(base)));
      }
      if (c == 0 && tid == 0) st32_rlx(&G->epoch, __float_as_uint(ldsf(sb + OFF_EP)));
    }
  }
  if (wg == 2) {
    uint32_t wf[16][2][4];
    {
      const uint32_t wb = sb + OFF_S + 16384 * (wp & 1) + ((lane & 7) + ((lane >> 4) << 3)) * 128 + ((((lane >> 3) & 1) ^ (lane & 7)) << 4);
      if (f < NFFN) mbar_wait(sb + B_WD + 8 * wp, 0);
      #pragma unroll
      for (int i = 0; i < 32; i++) ldsm4t((wb ^ (((i >> 1) & 3) << 5)) + (i >> 3) * 4096 + (i & 1) * 2048, wf[i >> 1][i & 1][0], wf[i >> 1][i & 1][1], wf[i >> 1][i & 1][2], wf[i >> 1][i & 1][3]);
      fence_async_smem();
      __syncwarp();
      if (lane == 0) mbar_arrive(sb + B_WC + 8 * wp);
    }
    bar_sync(NB_G2E, 384);
    {
      uint32_t cur = 0;
      uint4 v;
      #pragma unroll 1
      for (uint32_t it = 0; it < POLL_LIMIT; it++) {
        const uint4 kx = ld128_rlx(&G->key[(c & 31) * 128 + 4 * lane]);
        v = ld128_rlx(&G->cand[((~cur >> 4) & 127) * 512 + 4 * t]);
        uint32_t best;
        asm volatile("redux.sync.max.u32 %0, %1, 0xffffffff;" : "=r"(best) : "r"(max(max(kx.x, kx.y), max(kx.z, kx.w))));
        if (!__any_sync(~0u, min(min(kx.x, kx.y), min(kx.z, kx.w)) == 0 || v.w == ~0u) && best == cur) break;
        cur = best;
      }
      sts128(sb + OFF_XSEL + 16 * t, v.x, v.y, v.z, v.w);
      sts32(sb + OFF_KEY, cur);
      bar_arrive(NB_XS, 384);
      bar_sync(NB_ACT, 384);
    }
    float gu[2];
    #pragma unroll
    for (int i = 0; i < 2; i++) {
      const uint4 v0 = lds128(sb + OFF_GU + (32 * i + lane) * 48), v1 = lds128(sb + OFF_GU + (32 * i + lane) * 48 + 16);
      gu[i] = ((__uint_as_float(v0.x) + __uint_as_float(v0.y)) + (__uint_as_float(v0.z) + __uint_as_float(v0.w))) +
              ((__uint_as_float(v1.x) + __uint_as_float(v1.y)) + (__uint_as_float(v1.z) + __uint_as_float(v1.w)));
    }
    const float act = gu[0] * gu[1] * rcp(1.f + ex2(-LOG2E * gu[0]));
    const uint32_t ap = pack_bf16(act, __shfl_down_sync(~0u, act, 1));
    uint32_t bf[4];
    #pragma unroll
    for (int i = 0; i < 4; i++) bf[i] = __shfl_sync(~0u, ap, 2 * q + 8 * i);
    float d[16][4];
    #pragma unroll
    for (int k = 0; k < 2; k++)
      #pragma unroll
      for (int i = 0; i < 16; i++) {
        if (k == 0) { d[i][0] = 0.f; d[i][1] = 0.f; d[i][2] = 0.f; d[i][3] = 0.f; }
        mma16816(d[i][0], d[i][1], d[i][2], d[i][3], wf[i][k][0], wf[i][k][1], wf[i][k][2], wf[i][k][3], bf[2*k], bf[2*k+1]);
      }
    float y[9];
    #pragma unroll
    for (int e = 0; e < 8; e++) {
      const int n = 2 * (e & 4) + (e & 1);
      const float lo = (q & 1) ? d[n + 2][e & 2] : d[n][e & 2], hi = (q & 1) ? d[n + 6][e & 2] : d[n + 4][e & 2];
      y[e] = (q & 2) ? hi : lo;
    }
    y[8] = 0.f;
    if (f < NFFN) {
      #pragma unroll
      for (int i = 0; i < 3; i++) red_add_f32x4(&G->yacc[((f & 3) * 3 + i) * 128 + t], y[3*i], y[3*i+1], y[3*i+2], 1.f);
    }
  }
  }
  cluster_wait();
}

typedef CUresult (*EncodeFn)(CUtensorMap*, CUtensorMapDataType, cuuint32_t, void*, const cuuint64_t*, const cuuint64_t*,
                             const cuuint32_t*, const cuuint32_t*, CUtensorMapInterleave, CUtensorMapSwizzle,
                             CUtensorMapL2promotion, CUtensorMapFloatOOBfill);

void make_map(EncodeFn enc, CUtensorMap* m, const void* p, int n, const cuuint64_t* dims, const cuuint64_t* str, const cuuint32_t* box,
              CUtensorMapSwizzle sw, CUtensorMapL2promotion promo) {
  cuuint32_t es[5] = {1, 1, 1, 1, 1};
  enc(m, CU_TENSOR_MAP_DATA_TYPE_BFLOAT16, n, const_cast<void*>(p), dims, str, box, es, CU_TENSOR_MAP_INTERLEAVE_NONE, sw, promo,
      CU_TENSOR_MAP_FLOAT_OOB_FILL_NONE);
}
void map2(EncodeFn enc, CUtensorMap* m, const void* p, uint64_t cols, uint64_t rows, uint32_t bc, uint32_t br, CUtensorMapSwizzle sw,
          CUtensorMapL2promotion promo) {
  const cuuint64_t dims[2] = {cols, rows}, str[1] = {cols * 2};
  const cuuint32_t box[2] = {bc, br};
  make_map(enc, m, p, 2, dims, str, box, sw, promo);
}
void map3(EncodeFn enc, CUtensorMap* m, const void* p, uint64_t cols, uint64_t rows, uint32_t br, uint32_t nb) {
  const cuuint64_t dims[3] = {64, rows, cols / 64}, str[2] = {cols * 2, 128};
  const cuuint32_t box[3] = {64, br, nb};
  make_map(enc, m, p, 3, dims, str, box, CU_TENSOR_MAP_SWIZZLE_128B, CU_TENSOR_MAP_L2_PROMOTION_L2_128B);
}

}

extern "C" void kernel_launch(void* const* d_in, const int* in_sizes, int n_in, void* d_out, int out_size) {
  (void)in_sizes; (void)n_in; (void)out_size;
  static EncodeFn enc = nullptr;
  static void* o_ptr = nullptr;
  if (!enc) {
    void* f = nullptr; cudaDriverEntryPointQueryResult qr;
    cudaGetDriverEntryPoint("cuTensorMapEncodeTiled", &f, cudaEnableDefault, &qr);
    enc = (EncodeFn)f;
    cudaGetSymbolAddress(&o_ptr, g_scr);
    cudaFuncSetAttribute(fused_kernel, cudaFuncAttributeMaxDynamicSharedMemorySize, SMEM_BYTES);
  }
  const bf16* x = (const bf16*)d_in[0];
  const bf16* wqkv = (const bf16*)d_in[1];
  const bf16* wphi = (const bf16*)d_in[2];
  const bf16* wo = (const bf16*)d_in[3];
  const bf16* wr = (const bf16*)d_in[5];
  const bf16* wgate = (const bf16*)d_in[6];
  const bf16* wup = (const bf16*)d_in[7];
  const bf16* wdown = (const bf16*)d_in[8];
  Params P;
  const CUtensorMapSwizzle S128 = CU_TENSOR_MAP_SWIZZLE_128B, S64 = CU_TENSOR_MAP_SWIZZLE_64B;
  const CUtensorMapL2promotion L128 = CU_TENSOR_MAP_L2_PROMOTION_L2_128B, L256 = CU_TENSOR_MAP_L2_PROMOTION_L2_256B,
                               L64 = CU_TENSOR_MAP_L2_PROMOTION_L2_64B;
  map2(enc, &P.x128, x, DM, SEQ, 64, 128, S128, L128);
  map2(enc, &P.x64, x, DM, SEQ, 64, 64, S128, L128);
  {
    const cuuint64_t dims[4] = {64, DM, 16, 3}, str[3] = {6 * DM, 128, 2 * DM};
    const cuuint32_t box[4] = {64, 64, 1, 2};
    make_map(enc, &P.wkv, wqkv, 4, dims, str, box, S128, L128);
  }
  map3(enc, &P.wq, wqkv, 3 * DM, DM, 64, 2);
  for (int i = 0; i < 2; i++) {
    const cuuint64_t dims[5] = {DM, (cuuint64_t)(DM - 94 - 64 * i), 4, 4, 2}, str[4] = {2 * DM, 16 * DM, 4 * DM, (cuuint64_t)(128 * DM) << i};
    const cuuint32_t box[5] = {64, 2, 4, 4, 2};
    make_map(enc, &P.wo[i], wo, 5, dims, str, box, S128, L128);
  }
  map3(enc, &P.wd, wdown, DM, FF, 32, 4);
  map2(enc, &P.wg, wgate, FF, DM, 32, 128, S64, L64);
  map2(enc, &P.wu, wup, FF, DM, 32, 128, S64, L64);
  map2(enc, &P.tg, wgate, FF, DM, 8, 16, CU_TENSOR_MAP_SWIZZLE_NONE, L128);
  map2(enc, &P.tu, wup, FF, DM, 8, 16, CU_TENSOR_MAP_SWIZZLE_NONE, L128);
  map2(enc, &P.td, wdown, 128, FF * 8, 8, 16, CU_TENSOR_MAP_SWIZZLE_NONE, L256);
  map2(enc, &P.xs, x, DM, SEQ, 128, 16, CU_TENSOR_MAP_SWIZZLE_NONE, L256);
  map2(enc, &P.ws, wqkv, 3 * DM, DM, 16, 128, CU_TENSOR_MAP_SWIZZLE_NONE, L128);
  map2(enc, &P.qs, wqkv, 3 * DM, DM, 32, 128, CU_TENSOR_MAP_SWIZZLE_NONE, L64);
  map2(enc, &P.out, d_out, DM, SEQ, 64, 16, S128, L128);
  map2(enc, &P.o, o_ptr, 256, SEQ * DM / 256, 256, 16, CU_TENSOR_MAP_SWIZZLE_NONE, L128);
  map2(enc, &P.phi, wphi, 32, 1024, 32, 32, S64, L64);
  P.x = x; P.wqkv = wqkv; P.wo_p = wo; P.wr = wr; P.out_p = (bf16*)d_out; P.g = (Scratch*)o_ptr; P.zero = 0;

  cudaLaunchConfig_t cfg = {};
  cfg.gridDim = dim3(128); cfg.blockDim = dim3(512); cfg.dynamicSmemBytes = SMEM_BYTES; cfg.stream = cudaStreamPerThread;
  cudaLaunchAttribute at[1];
  at[0].id = cudaLaunchAttributeClusterDimension; at[0].val.clusterDim.x = 2; at[0].val.clusterDim.y = 1; at[0].val.clusterDim.z = 1;
  cfg.attrs = at; cfg.numAttrs = 1;
  cudaLaunchKernelEx(&cfg, fused_kernel, P);
}
```

```cpp
#include <cuda_runtime.h>
#include <cuda.h>
#include <cuda_bf16.h>
#include <stdint.h>

namespace {

typedef __nv_bfloat16 bf16;

__device__ __forceinline__ uint32_t smem_u32(const void* p){ return (uint32_t)__cvta_generic_to_shared(p); }
__device__ __forceinline__ void mbar_init(uint32_t bar, uint32_t cnt){ asm volatile("mbarrier.init.shared::cta.b64 [%0], %1;"::"r"(bar),"r"(cnt):"memory"); }
__device__ __forceinline__ void mbar_expect_tx(uint32_t bar, uint32_t bytes){ asm volatile("mbarrier.arrive.expect_tx.shared::cta.b64 _, [%0], %1;"::"r"(bar),"r"(bytes):"memory"); }
__device__ __forceinline__ void mbar_arrive(uint32_t bar){ asm volatile("mbarrier.arrive.shared::cta.b64 _, [%0];"::"r"(bar):"memory"); }
__device__ __forceinline__ uint32_t mapa(uint32_t addr, uint32_t cta){ uint32_t r; asm volatile("mapa.shared::cluster.u32 %0, %1, %2;":"=r"(r):"r"(addr),"r"(cta)); return r; }
__device__ __forceinline__ void mbar_arrive_at(uint32_t bar, uint32_t cta, uint32_t cnt){
  asm volatile("{\n.reg .b32 ra;\nmapa.shared::cluster.u32 ra, %0, %1;\nmbarrier.arrive.shared::cluster.b64 _, [ra], %2;\n}\n"::"r"(bar),"r"(cta),"r"(cnt):"memory"); }
__device__ __forceinline__ void mbar_arrive_remote(uint32_t cluster_addr, uint32_t cnt){
  asm volatile("mbarrier.arrive.shared::cluster.b64 _, [%0], %1;"::"r"(cluster_addr),"r"(cnt):"memory"); }
__device__ __forceinline__ void mbar_wait(uint32_t bar, uint32_t parity){
  asm volatile("{\n.reg .pred p;\n.reg .u32 c;\nmov.u32 c, 0;\nLW:\nmbarrier.try_wait.parity.shared::cta.b64 p, [%0], %1;\n@p bra LD;\nadd.u32 c, c, 1;\nsetp.lt.u32 p, c, 2000000;\n@p bra LW;\ntrap;\nLD:\n}\n"::"r"(bar),"r"(parity):"memory"); }
__device__ __forceinline__ void mbar_wait2(uint32_t bar0, uint32_t par0, uint32_t bar1, uint32_t par1){
  asm volatile("{\n.reg .pred p, q;\n.reg .u32 c;\nmov.u32 c, 0;\nLW:\nmbarrier.try_wait.parity.shared::cta.b64 p, [%0], %1;\nmbarrier.try_wait.parity.shared::cta.b64 q, [%2], %3;\nand.pred p, p, q;\n@p bra LD;\nadd.u32 c, c, 1;\nsetp.lt.u32 p, c, 2000000;\n@p bra LW;\ntrap;\nLD:\n}\n"::"r"(bar0),"r"(par0),"r"(bar1),"r"(par1):"memory"); }
__device__ __forceinline__ bool mbar_test2(uint32_t bar0, uint32_t par0, uint32_t bar1, uint32_t par1){
  uint32_t r;
  asm volatile("{\n.reg .pred p, q;\nmbarrier.test_wait.parity.shared::cta.b64 p, [%1], %2;\nmbarrier.test_wait.parity.shared::cta.b64 q, [%3], %4;\nand.pred p, p, q;\nselp.u32 %0, 1, 0, p;\n}\n":"=r"(r):"r"(bar0),"r"(par0),"r"(bar1),"r"(par1):"memory");
  return r; }
__device__ __forceinline__ void tma_2d(uint32_t dst, const CUtensorMap* m, int c0, int c1, uint32_t bar){
  asm volatile("cp.async.bulk.tensor.2d.shared::cluster.global.mbarrier::complete_tx::bytes [%0], [%1, {%3, %4}], [%2];"::"r"(dst),"l"(m),"r"(bar),"r"(c0),"r"(c1):"memory"); }
__device__ __forceinline__ void tma_2d_h(uint32_t dst, const CUtensorMap* m, int c0, int c1, uint32_t bar, uint64_t pol){
  asm volatile("cp.async.bulk.tensor.2d.shared::cluster.global.mbarrier::complete_tx::bytes.L2::cache_hint [%0], [%1, {%3, %4}], [%2], %5;"::"r"(dst),"l"(m),"r"(bar),"r"(c0),"r"(c1),"l"(pol):"memory"); }
__device__ __forceinline__ void tma_2d_mc(uint32_t dst, const CUtensorMap* m, int c0, int c1, uint32_t bar){
  asm volatile("cp.async.bulk.tensor.2d.shared::cluster.global.mbarrier::complete_tx::bytes.multicast::cluster [%0], [%1, {%3, %4}], [%2], %5;"::"r"(dst),"l"(m),"r"(bar),"r"(c0),"r"(c1),"h"((uint16_t)3):"memory"); }
__device__ __forceinline__ void tma_2d_mc_h(uint32_t dst, const CUtensorMap* m, int c0, int c1, uint32_t bar, uint64_t pol){
  asm volatile("cp.async.bulk.tensor.2d.shared::cluster.global.mbarrier::complete_tx::bytes.multicast::cluster.L2::cache_hint [%0], [%1, {%3, %4}], [%2], %5, %6;"::"r"(dst),"l"(m),"r"(bar),"r"(c0),"r"(c1),"h"((uint16_t)3),"l"(pol):"memory"); }
__device__ __forceinline__ void tma_4d(uint32_t dst, const CUtensorMap* m, int c0, int c1, int c2, int c3, uint32_t bar){
  asm volatile("cp.async.bulk.tensor.4d.shared::cluster.global.mbarrier::complete_tx::bytes [%0], [%1, {%3, %4, %5, %6}], [%2];"::"r"(dst),"l"(m),"r"(bar),"r"(c0),"r"(c1),"r"(c2),"r"(c3):"memory"); }
__device__ __forceinline__ uint64_t policy_evict_first(){ uint64_t p; asm volatile("createpolicy.fractional.L2::evict_first.b64 %0, 1.0;":"=l"(p)); return p; }
__device__ __forceinline__ uint64_t policy_evict_normal(){ uint64_t p; asm("createpolicy.fractional.L2::evict_normal.b64 %0, 1.0;":"=l"(p)); return p; }
__device__ __forceinline__ void tma_3d_h(uint32_t dst, const CUtensorMap* m, int c0, int c1, int c2, uint32_t bar, uint64_t pol){
  asm volatile("cp.async.bulk.tensor.3d.shared::cluster.global.mbarrier::complete_tx::bytes.L2::cache_hint [%0], [%1, {%3, %4, %5}], [%2], %6;"::"r"(dst),"l"(m),"r"(bar),"r"(c0),"r"(c1),"r"(c2),"l"(pol):"memory"); }
__device__ __forceinline__ void tma_4d_h(uint32_t dst, const CUtensorMap* m, int c0, int c1, int c2, int c3, uint32_t bar, uint64_t pol){
  asm volatile("cp.async.bulk.tensor.4d.shared::cluster.global.mbarrier::complete_tx::bytes.L2::cache_hint [%0], [%1, {%3, %4, %5, %6}], [%2], %7;"::"r"(dst),"l"(m),"r"(bar),"r"(c0),"r"(c1),"r"(c2),"r"(c3),"l"(pol):"memory"); }
__device__ __forceinline__ void red_add_f32x4(float4* p, float x, float y, float z, float w){ asm volatile("red.relaxed.gpu.global.add.v4.f32 [%0], {%1,%2,%3,%4};"::"l"(p),"f"(x),"f"(y),"f"(z),"f"(w):"memory"); }
__device__ __forceinline__ void tma_5d_h(uint32_t dst, const CUtensorMap* m, int c0, int c1, uint32_t bar, uint64_t pol){
  asm volatile("cp.async.bulk.tensor.5d.shared::cluster.global.mbarrier::complete_tx::bytes.L2::cache_hint [%0], [%1, {%3, %4, 0, 0, 0}], [%2], %5;"::"r"(dst),"l"(m),"r"(bar),"r"(c0),"r"(c1),"l"(pol):"memory"); }
__device__ __forceinline__ void tma_store_2d(const CUtensorMap* m, int c0, int c1, uint32_t src, uint64_t pol){
  asm volatile("cp.async.bulk.tensor.2d.global.shared::cta.bulk_group.L2::cache_hint [%0, {%2, %3}], [%1], %4;"::"l"(m),"r"(src),"r"(c0),"r"(c1),"l"(pol):"memory"); }
__device__ __forceinline__ void bulk_commit(){ asm volatile("cp.async.bulk.commit_group;":::"memory"); }
__device__ __forceinline__ void bulk_wait_all(){ asm volatile("cp.async.bulk.wait_group 0;":::"memory"); }
__device__ __forceinline__ void fence_async_global(){ asm volatile("fence.proxy.async.global;":::"memory"); }
__device__ __forceinline__ bool elect_one(){ uint32_t p; asm volatile("{\n.reg .pred P;\nelect.sync _|P, 0xffffffff;\nselp.b32 %0, 1, 0, P;\n}\n":"=r"(p)); return p; }
__device__ __forceinline__ void bulk_prefetch(const void* p, uint32_t bytes){
  asm volatile("cp.async.bulk.prefetch.L2.global [%0], %1;"::"l"(p),"r"(bytes):"memory"); }
__device__ __forceinline__ void bulk_s2peer(uint32_t dst_cluster, uint32_t src, uint32_t bytes, uint32_t bar_cluster){
  asm volatile("cp.async.bulk.shared::cluster.shared::cta.mbarrier::complete_tx::bytes [%0], [%1], %2, [%3];"::"r"(dst_cluster),"r"(src),"r"(bytes),"r"(bar_cluster):"memory"); }
__device__ __forceinline__ void prefetch_map(const CUtensorMap* m){ asm volatile("prefetch.tensormap [%0];"::"l"(m):"memory"); }
__device__ __forceinline__ void fence_async_smem(){ asm volatile("fence.proxy.async.shared::cta;":::"memory"); }
__device__ __forceinline__ void fence_acquire_gpu(){ asm volatile("fence.acquire.gpu;":::"memory"); }
__device__ __forceinline__ void fence_gpu(){ asm volatile("fence.acq_rel.gpu;":::"memory"); }
__device__ __forceinline__ void wg_fence(){ asm volatile("wgmma.fence.sync.aligned;":::"memory"); }
__device__ __forceinline__ void wg_commit(){ asm volatile("wgmma.commit_group.sync.aligned;":::"memory"); }
template<int N> __device__ __forceinline__ void wg_wait(){ asm volatile("wgmma.wait_group.sync.aligned %0;"::"n"(N):"memory"); }
template<int N> __device__ __forceinline__ void fence_regs(float (&d)[N]){
  #pragma unroll
  for(int i=0;i<N;i++) asm volatile("":"+f"(d[i])::"memory"); }
__device__ __forceinline__ void bar_sync(int id, int n){ asm volatile("bar.sync %0, %1;"::"r"(id),"r"(n):"memory"); }
__device__ __forceinline__ void bar_arrive(int id, int n){ asm volatile("bar.arrive %0, %1;"::"r"(id),"r"(n):"memory"); }
__device__ __forceinline__ void cluster_arrive(){ asm volatile("barrier.cluster.arrive.relaxed.aligned;":::"memory"); }
__device__ __forceinline__ void cluster_wait(){ asm volatile("barrier.cluster.wait.aligned;":::"memory"); }
__host__ __device__ constexpr uint32_t dlo(uint32_t addr, uint32_t lbo){ return (addr >> 4) | ((lbo >> 4) << 16); }
__host__ __device__ constexpr uint32_t dhi(uint32_t sbo, uint32_t sw){ return (sbo >> 4) | (sw << 30); }
constexpr uint32_t H128 = dhi(1024, 1), H64 = dhi(512, 2), H0 = dhi(128, 0);
__device__ __forceinline__ uint32_t pack_bf16(float lo, float hi){ uint32_t r; asm("cvt.rn.bf16x2.f32 %0, %1, %2;":"=r"(r):"f"(hi),"f"(lo)); return r; }
__device__ __forceinline__ float bf_lo(uint32_t v){ return __uint_as_float(v<<16); }
__device__ __forceinline__ float bf_hi(uint32_t v){ return __uint_as_float(v&0xffff0000u); }
__device__ __forceinline__ float ex2(float x){ float r; asm("ex2.approx.ftz.f32 %0, %1;":"=f"(r):"f"(x)); return r; }
__device__ __forceinline__ float rcp(float x){ float r; asm("rcp.approx.ftz.f32 %0, %1;":"=f"(r):"f"(x)); return r; }
__device__ __forceinline__ void stsm4(uint32_t addr, uint32_t a, uint32_t b, uint32_t c, uint32_t d){
  asm volatile("stmatrix.sync.aligned.m8n8.x4.shared.b16 [%0], {%1,%2,%3,%4};"::"r"(addr),"r"(a),"r"(b),"r"(c),"r"(d)); }
__device__ __forceinline__ void stsm2(uint32_t addr, uint32_t a, uint32_t b){
  asm volatile("stmatrix.sync.aligned.m8n8.x2.shared.b16 [%0], {%1,%2};"::"r"(addr),"r"(a),"r"(b)); }
__device__ __forceinline__ void mma16816(float& d0, float& d1, float& d2, float& d3, uint32_t a0, uint32_t a1, uint32_t a2, uint32_t a3, uint32_t b0, uint32_t b1){
  asm volatile("mma.sync.aligned.m16n8k16.row.col.f32.bf16.bf16.f32 {%0,%1,%2,%3}, {%4,%5,%6,%7}, {%8,%9}, {%0,%1,%2,%3};"
               : "+f"(d0), "+f"(d1), "+f"(d2), "+f"(d3) : "r"(a0), "r"(a1), "r"(a2), "r"(a3), "r"(b0), "r"(b1)); }
__device__ __forceinline__ uint32_t transpose8(uint32_t a){ uint32_t r; asm volatile("movmatrix.sync.aligned.m8n8.trans.b16 %0, %1;":"=r"(r):"r"(a)); return r; }
__device__ __forceinline__ void ldsm4(uint32_t addr, uint32_t& a, uint32_t& b, uint32_t& c, uint32_t& d){
  asm volatile("ldmatrix.sync.aligned.m8n8.x4.shared.b16 {%0,%1,%2,%3}, [%4];":"=r"(a),"=r"(b),"=r"(c),"=r"(d):"r"(addr):"memory"); }
__device__ __forceinline__ void ldsm4t(uint32_t addr, uint32_t& a, uint32_t& b, uint32_t& c, uint32_t& d){
  asm volatile("ldmatrix.sync.aligned.m8n8.x4.trans.shared.b16 {%0,%1,%2,%3}, [%4];":"=r"(a),"=r"(b),"=r"(c),"=r"(d):"r"(addr):"memory"); }
__device__ __forceinline__ void sts32(uint32_t a, uint32_t v){ asm volatile("st.shared.b32 [%0], %1;"::"r"(a),"r"(v):"memory"); }
__device__ __forceinline__ void stsf(uint32_t a, float v){ asm volatile("st.shared.f32 [%0], %1;"::"r"(a),"f"(v):"memory"); }
__device__ __forceinline__ void sts64(uint32_t a, uint32_t x, uint32_t y){ asm volatile("st.shared.v2.b32 [%0], {%1,%2};"::"r"(a),"r"(x),"r"(y):"memory"); }
__device__ __forceinline__ void sts128(uint32_t a, uint32_t x, uint32_t y, uint32_t z, uint32_t w){ asm volatile("st.shared.v4.b32 [%0], {%1,%2,%3,%4};"::"r"(a),"r"(x),"r"(y),"r"(z),"r"(w):"memory"); }
__device__ __forceinline__ float ldsf(uint32_t a){ float v; asm volatile("ld.shared.f32 %0, [%1];":"=f"(v):"r"(a):"memory"); return v; }
__device__ __forceinline__ float2 lds64f(uint32_t a){ float2 v; asm volatile("ld.shared.v2.f32 {%0,%1}, [%2];":"=f"(v.x),"=f"(v.y):"r"(a):"memory"); return v; }
__device__ __forceinline__ uint4 lds128(uint32_t a){ uint4 v; asm volatile("ld.shared.v4.u32 {%0,%1,%2,%3}, [%4];":"=r"(v.x),"=r"(v.y),"=r"(v.z),"=r"(v.w):"r"(a):"memory"); return v; }
__device__ __forceinline__ uint4 ld128_keep(const void* p){ uint4 v; asm volatile("ld.global.v4.u32 {%0,%1,%2,%3}, [%4];":"=r"(v.x),"=r"(v.y),"=r"(v.z),"=r"(v.w):"l"(p):"memory"); return v; }
__device__ __forceinline__ uint4 ld128_rlx(const void* p){ uint4 v; asm volatile("ld.relaxed.gpu.global.v4.u32 {%0,%1,%2,%3}, [%4];":"=r"(v.x),"=r"(v.y),"=r"(v.z),"=r"(v.w):"l"(p):"memory"); return v; }
__device__ __forceinline__ uint32_t ld32_rlx(const void* p){ uint32_t v; asm volatile("ld.relaxed.gpu.global.u32 %0, [%1];":"=r"(v):"l"(p):"memory"); return v; }
__device__ __forceinline__ void st128_rlx(void* p, uint32_t x, uint32_t y, uint32_t z, uint32_t w){ asm volatile("st.relaxed.gpu.global.v4.u32 [%0], {%1,%2,%3,%4};"::"l"(p),"r"(x),"r"(y),"r"(z),"r"(w):"memory"); }
__device__ __forceinline__ void st64_rlx(void* p, uint32_t x, uint32_t y){ asm volatile("st.relaxed.gpu.global.v2.u32 [%0], {%1,%2};"::"l"(p),"r"(x),"r"(y):"memory"); }
__device__ __forceinline__ void st32_rlx(void* p, uint32_t x){ asm volatile("st.relaxed.gpu.global.u32 [%0], %1;"::"l"(p),"r"(x):"memory"); }
__device__ __forceinline__ void wait_until(uint32_t t){ while ((int32_t)((uint32_t)clock() - t) < 0) __nanosleep(32); }
__device__ __forceinline__ void flags_wait(uint32_t& missing, const uint32_t* p, uint32_t need){
  asm volatile("{\n.reg .pred p;\n.reg .u32 c, v;\nmov.u32 c, 0;\nLW:\nand.b32 v, %0, %2;\nsetp.eq.u32 p, v, 0;\n@p bra.uni LD;\nld.relaxed.gpu.global.u32 v, [%1];\nsetp.eq.u32 p, v, 0;\n"
               "vote.sync.ballot.b32 %0, p, 0xffffffff;\nadd.u32 c, c, 1;\nsetp.lt.u32 p, c, 4000000;\n@p bra.uni LW;\nLD:\n}\n":"+r"(missing):"l"(p),"r"(need):"memory"); }
__device__ __forceinline__ uint32_t tagw(float x, uint32_t t){ return (__float_as_uint(x) & ~3u) | t; }
__device__ __forceinline__ float untag(uint32_t w){ return __uint_as_float(w & ~3u); }

template<int TA, int TB, uint32_t HA, uint32_t HB> __device__ __forceinline__ void wgmma_ss_n128(float (&d)[64], uint32_t da, uint32_t db, int scale_d){
  asm volatile("{\n.reg .pred p;\n.reg .b64 a, b;\nsetp.ne.b32 p, %70, 0;\nmov.b64 a, {%64, %68};\nmov.b64 b, {%65, %69};\n"
  "wgmma.mma_async.sync.aligned.m64n128k16.f32.bf16.bf16 {%0, %1, %2, %3, %4, %5, %6, %7, %8, %9, %10, %11, %12, %13, %14, %15, %16, %17, %18, %19, %20, %21, %22, %23, %24, %25, %26, %27, %28, %29, %30, %31, %32, %33, %34, %35, %36, %37, %38, %39, %40, %41, %42, %43, %44, %45, %46, %47, %48, %49, %50, %51, %52, %53, %54, %55, %56, %57, %58, %59, %60, %61, %62, %63}, a, b, p, 1, 1, %66, %67;\n}\n"
  : "+f"(d[0]), "+f"(d[1]), "+f"(d[2]), "+f"(d[3]), "+f"(d[4]), "+f"(d[5]), "+f"(d[6]), "+f"(d[7]), "+f"(d[8]), "+f"(d[9]), "+f"(d[10]), "+f"(d[11]), "+f"(d[12]), "+f"(d[13]), "+f"(d[14]), "+f"(d[15]), "+f"(d[16]), "+f"(d[17]), "+f"(d[18]), "+f"(d[19]), "+f"(d[20]), "+f"(d[21]), "+f"(d[22]), "+f"(d[23]), "+f"(d[24]), "+f"(d[25]), "+f"(d[26]), "+f"(d[27]), "+f"(d[28]), "+f"(d[29]), "+f"(d[30]), "+f"(d[31]), "+f"(d[32]), "+f"(d[33]), "+f"(d[34]), "+f"(d[35]), "+f"(d[36]), "+f"(d[37]), "+f"(d[38]), "+f"(d[39]), "+f"(d[40]), "+f"(d[41]), "+f"(d[42]), "+f"(d[43]), "+f"(d[44]), "+f"(d[45]), "+f"(d[46]), "+f"(d[47]), "+f"(d[48]), "+f"(d[49]), "+f"(d[50]), "+f"(d[51]), "+f"(d[52]), "+f"(d[53]), "+f"(d[54]), "+f"(d[55]), "+f"(d[56]), "+f"(d[57]), "+f"(d[58]), "+f"(d[59]), "+f"(d[60]), "+f"(d[61]), "+f"(d[62]), "+f"(d[63])
  : "r"(da), "r"(db), "n"(TA), "n"(TB), "n"(HA), "n"(HB), "r"(scale_d));
}
template<int TA, int TB, uint32_t HA, uint32_t HB> __device__ __forceinline__ void wgmma_sa_n128(float (&d)[64], uint32_t da, uint32_t db){
  asm volatile("{\n.reg .pred p;\n.reg .b64 a, b;\nsetp.ne.b32 p, 1, 0;\nmov.b64 a, {%64, %68};\nmov.b64 b, {%65, %69};\n"
  "wgmma.mma_async.sync.aligned.m64n128k16.f32.bf16.bf16 {%0, %1, %2, %3, %4, %5, %6, %7, %8, %9, %10, %11, %12, %13, %14, %15, %16, %17, %18, %19, %20, %21, %22, %23, %24, %25, %26, %27, %28, %29, %30, %31, %32, %33, %34, %35, %36, %37, %38, %39, %40, %41, %42, %43, %44, %45, %46, %47, %48, %49, %50, %51, %52, %53, %54, %55, %56, %57, %58, %59, %60, %61, %62, %63}, a, b, p, 1, 1, %66, %67;\n}\n"
  : "+f"(d[0]), "+f"(d[1]), "+f"(d[2]), "+f"(d[3]), "+f"(d[4]), "+f"(d[5]), "+f"(d[6]), "+f"(d[7]), "+f"(d[8]), "+f"(d[9]), "+f"(d[10]), "+f"(d[11]), "+f"(d[12]), "+f"(d[13]), "+f"(d[14]), "+f"(d[15]), "+f"(d[16]), "+f"(d[17]), "+f"(d[18]), "+f"(d[19]), "+f"(d[20]), "+f"(d[21]), "+f"(d[22]), "+f"(d[23]), "+f"(d[24]), "+f"(d[25]), "+f"(d[26]), "+f"(d[27]), "+f"(d[28]), "+f"(d[29]), "+f"(d[30]), "+f"(d[31]), "+f"(d[32]), "+f"(d[33]), "+f"(d[34]), "+f"(d[35]), "+f"(d[36]), "+f"(d[37]), "+f"(d[38]), "+f"(d[39]), "+f"(d[40]), "+f"(d[41]), "+f"(d[42]), "+f"(d[43]), "+f"(d[44]), "+f"(d[45]), "+f"(d[46]), "+f"(d[47]), "+f"(d[48]), "+f"(d[49]), "+f"(d[50]), "+f"(d[51]), "+f"(d[52]), "+f"(d[53]), "+f"(d[54]), "+f"(d[55]), "+f"(d[56]), "+f"(d[57]), "+f"(d[58]), "+f"(d[59]), "+f"(d[60]), "+f"(d[61]), "+f"(d[62]), "+f"(d[63])
  : "r"(da), "r"(db), "n"(TA), "n"(TB), "n"(HA), "n"(HB));
}
template<int TA, int TB, uint32_t HA, uint32_t HB> __device__ __forceinline__ void wgmma_sa_n40(float (&d)[20], uint32_t da, uint32_t db){
  asm volatile("{\n.reg .pred p;\n.reg .b64 a, b;\nsetp.ne.b32 p, 1, 0;\nmov.b64 a, {%20, %24};\nmov.b64 b, {%21, %25};\n"
  "wgmma.mma_async.sync.aligned.m64n40k16.f32.bf16.bf16 {%0, %1, %2, %3, %4, %5, %6, %7, %8, %9, %10, %11, %12, %13, %14, %15, %16, %17, %18, %19}, a, b, p, 1, 1, %22, %23;\n}\n"
  : "+f"(d[0]), "+f"(d[1]), "+f"(d[2]), "+f"(d[3]), "+f"(d[4]), "+f"(d[5]), "+f"(d[6]), "+f"(d[7]), "+f"(d[8]), "+f"(d[9]), "+f"(d[10]), "+f"(d[11]), "+f"(d[12]), "+f"(d[13]), "+f"(d[14]), "+f"(d[15]), "+f"(d[16]), "+f"(d[17]), "+f"(d[18]), "+f"(d[19])
  : "r"(da), "r"(db), "n"(TA), "n"(TB), "n"(HA), "n"(HB));
}
template<int TA, int TB, uint32_t HA, uint32_t HB> __device__ __forceinline__ void wgmma_sz_n40(float (&d)[20], uint32_t da, uint32_t db){
  asm volatile("{\n.reg .pred p;\n.reg .b64 a, b;\nsetp.ne.b32 p, 0, 0;\nmov.b64 a, {%20, %24};\nmov.b64 b, {%21, %25};\n"
  "wgmma.mma_async.sync.aligned.m64n40k16.f32.bf16.bf16 {%0, %1, %2, %3, %4, %5, %6, %7, %8, %9, %10, %11, %12, %13, %14, %15, %16, %17, %18, %19}, a, b, p, 1, 1, %22, %23;\n}\n"
  : "=f"(d[0]), "=f"(d[1]), "=f"(d[2]), "=f"(d[3]), "=f"(d[4]), "=f"(d[5]), "=f"(d[6]), "=f"(d[7]), "=f"(d[8]), "=f"(d[9]), "=f"(d[10]), "=f"(d[11]), "=f"(d[12]), "=f"(d[13]), "=f"(d[14]), "=f"(d[15]), "=f"(d[16]), "=f"(d[17]), "=f"(d[18]), "=f"(d[19])
  : "r"(da), "r"(db), "n"(TA), "n"(TB), "n"(HA), "n"(HB));
}
template<int TA, int TB, uint32_t HA, uint32_t HB> __device__ __forceinline__ void wgmma_sa_n32(float (&d)[16], uint32_t da, uint32_t db){
  asm volatile("{\n.reg .pred p;\n.reg .b64 a, b;\nsetp.ne.b32 p, 1, 0;\nmov.b64 a, {%16, %20};\nmov.b64 b, {%17, %21};\n"
  "wgmma.mma_async.sync.aligned.m64n32k16.f32.bf16.bf16 {%0, %1, %2, %3, %4, %5, %6, %7, %8, %9, %10, %11, %12, %13, %14, %15}, a, b, p, 1, 1, %18, %19;\n}\n"
  : "+f"(d[0]), "+f"(d[1]), "+f"(d[2]), "+f"(d[3]), "+f"(d[4]), "+f"(d[5]), "+f"(d[6]), "+f"(d[7]), "+f"(d[8]), "+f"(d[9]), "+f"(d[10]), "+f"(d[11]), "+f"(d[12]), "+f"(d[13]), "+f"(d[14]), "+f"(d[15])
  : "r"(da), "r"(db), "n"(TA), "n"(TB), "n"(HA), "n"(HB));
}
template<int TA, int TB, uint32_t HA, uint32_t HB> __device__ __forceinline__ void wgmma_ss_n32(float (&d)[16], uint32_t da, uint32_t db, int scale_d){
  asm volatile("{\n.reg .pred p;\n.reg .b64 a, b;\nsetp.ne.b32 p, %22, 0;\nmov.b64 a, {%16, %20};\nmov.b64 b, {%17, %21};\n"
  "wgmma.mma_async.sync.aligned.m64n32k16.f32.bf16.bf16 {%0, %1, %2, %3, %4, %5, %6, %7, %8, %9, %10, %11, %12, %13, %14, %15}, a, b, p, 1, 1, %18, %19;\n}\n"
  : "+f"(d[0]), "+f"(d[1]), "+f"(d[2]), "+f"(d[3]), "+f"(d[4]), "+f"(d[5]), "+f"(d[6]), "+f"(d[7]), "+f"(d[8]), "+f"(d[9]), "+f"(d[10]), "+f"(d[11]), "+f"(d[12]), "+f"(d[13]), "+f"(d[14]), "+f"(d[15])
  : "r"(da), "r"(db), "n"(TA), "n"(TB), "n"(HA), "n"(HB), "r"(scale_d));
}
template<int TB, uint32_t HB> __device__ __forceinline__ void wgmma_ra_n32(float (&d)[16], uint32_t a0, uint32_t a1, uint32_t a2, uint32_t a3, uint32_t db){
  asm volatile("{\n.reg .pred p;\n.reg .b64 a, b;\nsetp.ne.b32 p, 1, 0;\nmov.b64 b, {%20, %22};\n"
  "wgmma.mma_async.sync.aligned.m64n32k16.f32.bf16.bf16 {%0, %1, %2, %3, %4, %5, %6, %7, %8, %9, %10, %11, %12, %13, %14, %15}, {%16,%17,%18,%19}, b, p, 1, 1, %21;\n}\n"
  : "+f"(d[0]), "+f"(d[1]), "+f"(d[2]), "+f"(d[3]), "+f"(d[4]), "+f"(d[5]), "+f"(d[6]), "+f"(d[7]), "+f"(d[8]), "+f"(d[9]), "+f"(d[10]), "+f"(d[11]), "+f"(d[12]), "+f"(d[13]), "+f"(d[14]), "+f"(d[15])
  : "r"(a0), "r"(a1), "r"(a2), "r"(a3), "r"(db), "n"(TB), "n"(HB));
}
template<int TB, uint32_t HB> __device__ __forceinline__ void wgmma_rs_n32(float (&d)[16], uint32_t a0, uint32_t a1, uint32_t a2, uint32_t a3, uint32_t db, int scale_d){
  asm volatile("{\n.reg .pred p;\n.reg .b64 a, b;\nsetp.ne.b32 p, %23, 0;\nmov.b64 b, {%20, %22};\n"
  "wgmma.mma_async.sync.aligned.m64n32k16.f32.bf16.bf16 {%0, %1, %2, %3, %4, %5, %6, %7, %8, %9, %10, %11, %12, %13, %14, %15}, {%16,%17,%18,%19}, b, p, 1, 1, %21;\n}\n"
  : "+f"(d[0]), "+f"(d[1]), "+f"(d[2]), "+f"(d[3]), "+f"(d[4]), "+f"(d[5]), "+f"(d[6]), "+f"(d[7]), "+f"(d[8]), "+f"(d[9]), "+f"(d[10]), "+f"(d[11]), "+f"(d[12]), "+f"(d[13]), "+f"(d[14]), "+f"(d[15])
  : "r"(a0), "r"(a1), "r"(a2), "r"(a3), "r"(db), "n"(TB), "n"(HB), "r"(scale_d));
}
template<int TB, uint32_t HB> __device__ __forceinline__ void wgmma_ra_n40(float (&d)[20], uint32_t a0, uint32_t a1, uint32_t a2, uint32_t a3, uint32_t db){
  asm volatile("{\n.reg .pred p;\n.reg .b64 a, b;\nsetp.ne.b32 p, 1, 0;\nmov.b64 b, {%24, %26};\n"
  "wgmma.mma_async.sync.aligned.m64n40k16.f32.bf16.bf16 {%0, %1, %2, %3, %4, %5, %6, %7, %8, %9, %10, %11, %12, %13, %14, %15, %16, %17, %18, %19}, {%20,%21,%22,%23}, b, p, 1, 1, %25;\n}\n"
  : "+f"(d[0]), "+f"(d[1]), "+f"(d[2]), "+f"(d[3]), "+f"(d[4]), "+f"(d[5]), "+f"(d[6]), "+f"(d[7]), "+f"(d[8]), "+f"(d[9]), "+f"(d[10]), "+f"(d[11]), "+f"(d[12]), "+f"(d[13]), "+f"(d[14]), "+f"(d[15]), "+f"(d[16]), "+f"(d[17]), "+f"(d[18]), "+f"(d[19])
  : "r"(a0), "r"(a1), "r"(a2), "r"(a3), "r"(db), "n"(TB), "n"(HB));
}
template<int TB, uint32_t HB> __device__ __forceinline__ void wgmma_rz_n40(float (&d)[20], uint32_t a0, uint32_t a1, uint32_t a2, uint32_t a3, uint32_t db){
  asm volatile("{\n.reg .pred p;\n.reg .b64 a, b;\nsetp.ne.b32 p, 0, 0;\nmov.b64 b, {%24, %26};\n"
  "wgmma.mma_async.sync.aligned.m64n40k16.f32.bf16.bf16 {%0, %1, %2, %3, %4, %5, %6, %7, %8, %9, %10, %11, %12, %13, %14, %15, %16, %17, %18, %19}, {%20,%21,%22,%23}, b, p, 1, 1, %25;\n}\n"
  : "=f"(d[0]), "=f"(d[1]), "=f"(d[2]), "=f"(d[3]), "=f"(d[4]), "=f"(d[5]), "=f"(d[6]), "=f"(d[7]), "=f"(d[8]), "=f"(d[9]), "=f"(d[10]), "=f"(d[11]), "=f"(d[12]), "=f"(d[13]), "=f"(d[14]), "=f"(d[15]), "=f"(d[16]), "=f"(d[17]), "=f"(d[18]), "=f"(d[19])
  : "r"(a0), "r"(a1), "r"(a2), "r"(a3), "r"(db), "n"(TB), "n"(HB));
}
template<int TB, uint32_t HB> __device__ __forceinline__ void wgmma_rz_n8(float (&d)[4], uint32_t a0, uint32_t a1, uint32_t a2, uint32_t a3, uint32_t db){
  asm volatile("{\n.reg .pred p;\n.reg .b64 a, b;\nsetp.ne.b32 p, 0, 0;\nmov.b64 b, {%8, %10};\n"
  "wgmma.mma_async.sync.aligned.m64n8k16.f32.bf16.bf16 {%0, %1, %2, %3}, {%4,%5,%6,%7}, b, p, 1, 1, %9;\n}\n"
  : "=f"(d[0]), "=f"(d[1]), "=f"(d[2]), "=f"(d[3])
  : "r"(a0), "r"(a1), "r"(a2), "r"(a3), "r"(db), "n"(TB), "n"(HB));
}

constexpr int SEQ = 2048, DM = 1024, FF = 3584;
constexpr float LOG2E = 1.4426950408889634f;
constexpr uint32_t POLL_LIMIT = 1u << 22;
constexpr int QW = 0;
constexpr int LAG = 2;
constexpr int ML = 2;
constexpr int REL = 6;
constexpr int SKM = 0x154;
constexpr int RS_N = 22;
constexpr int RS_D1 = 420;
constexpr int RS_D2 = 300;
constexpr int PF_T0 = 5000;
constexpr int PF_DT = 800;
constexpr int FF_N = 5;
constexpr int FF_DT = 500;
constexpr int FF_D2 = 350;
constexpr uint64_t FF_ORD = 0x76543210ba98ull;
constexpr int OUT_D = 400;
constexpr int NFFN = 112;

constexpr uint32_t SB0 = 1024;
constexpr uint32_t KV_STAGE = 49152, R5 = 32768;
constexpr uint32_t OFF_X = 163840, OFF_S = 196608, OFF_WPHI = OFF_S + 20480, OFF_M = 229376, SMEM_BYTES = 232448;
constexpr uint32_t OFF_RS256 = 212992, OFF_ONES = OFF_RS256 + 1024, OFF_WPHIK1 = OFF_ONES + 1024, OFF_KVZ = OFF_S;
constexpr uint32_t OFF_WPHIK = OFF_S, OFF_BXK = OFF_S + 2048, OFF_AXK = OFF_S + 4096, OFF_G = OFF_S + 8192;
constexpr uint32_t OFF_AXQ = OFF_WPHI, OFF_BXQ = OFF_WPHI + 2048, OFF_WPHIQ = OFF_WPHI + 4096;
constexpr uint32_t B_FULLKV = OFF_M  , B_EMPTYKV = OFF_M + 32  ;
constexpr uint32_t B_EMPTY5 = OFF_M + 64  , B_UO = B_EMPTY5 + 48  , B_RC = B_UO + 32  ;
constexpr uint32_t B_OUT = B_RC + 16  , B_SD = B_OUT + 16, B_AUX = B_SD + 8, B_AUXQ = B_AUX + 8, B_RX = B_AUXQ + 8;
constexpr uint32_t B_FULL5 = B_RX + 8  , B_F = B_FULL5 + 40  , B_WD = B_F + 64  ;
constexpr uint32_t B_WC = B_WD + 32  , B_DR = B_WC + 32  , B_W = B_DR + 24, B_OS = B_W + 8, B_R = B_W + 16, B_KD = B_W + 24, B_T = B_W + 32, B_G = B_W + 40, B_END = B_W + 48;
constexpr int NB3 = ((B_END - OFF_M) / 8 + 1) / 3;
constexpr uint32_t B_S0 = OFF_M + 8 + 24 * NB3;
static_assert(B_S0 >= B_END && B_S0 < OFF_M + 576, "barriers");
__host__ __device__ constexpr uint32_t bar_count(int i) {
  const uint32_t b = OFF_M + 8 * i;
  return b < B_EMPTYKV ? 1 : b < B_EMPTY5 ? 12 : b < B_SD ? 4 : b < B_RX || b == B_W ? 2 : b == B_RX ? 8 : 1;
}
constexpr uint32_t B_GB = OFF_M + 2560  , B_GA = B_GB + 128  ;
constexpr uint32_t OFF_BEST = OFF_M + 576, OFF_SUMWR = OFF_M + 608, OFF_EP = OFF_M + 624, OFF_KEY = OFF_M + 628;
constexpr uint32_t OFF_RSQ = OFF_M + 640, OFF_SEL = OFF_M + 1648, OFF_T = OFF_M + 1792, OFF_WR = OFF_M + 2048;
constexpr uint32_t OFF_XSEL = 2 * R5, OFF_GU = OFF_XSEL + 4096, OFF_OUT = 3 * R5;
constexpr uint64_t FF_SLOT = 0xdcdc3210dcbaull;
constexpr int KVP = 6 * 128;
__device__ __forceinline__ uint32_t kv_count(uint32_t launch, uint32_t n) { return 0x42800000u + (((launch & 3) * 16 + n) << 17); }

enum { NB_G2E = 1, NB_XS = 2, NB_WG01 = 3, NB_ACT = 4, NB_Q0 = 5  , NB_ST = 14, NB_LAG = 8, NB_DN = 9, NB_ZERO = 10, NB_PUB = 11, NB_TOK = 10  , NB_L0 = 12  , NB_WG2 = 7, NB_QGO = 15 };

struct Scratch {
  bf16     o[SEQ * DM];
  float4   rstat[SEQ];
  uint32_t key[16 * 128];
  uint32_t cand[16 * 512];
  float4   yacc[4 * 3 * 128];
  float4   kvacc[32 * KVP];
  uint2    stats[SEQ];
  uint32_t cskv[2 * DM];
  uint32_t csq[4 * DM];
  uint32_t oset[128 * 16];
  uint32_t oflag[16 * 6 * 32 * 8];
  uint32_t epoch;
};
__device__ __align__(1024) Scratch g_scr;

struct Params {
  const bf16 *x, *wqkv, *wo_p, *wr;
  bf16* out_p;
  Scratch* g;
  uint32_t zero;
  CUtensorMap x128, x64, wkv, wq, wo[2], wd, wg, wu, phi, tg, tu, td, xs, ws, qs, out, o;
};

constexpr float EXP_LIM = 1.1529215e18f, ARG_LIM2 = 3600.f;
__device__ __forceinline__ void dual_exp2(const float (&p)[16], uint32_t (&ep)[8], uint32_t (&em)[8]) {
  #pragma unroll
  for (int k = 0; k < 8; k++) {
    const float a = ex2(p[2*k]), b = ex2(p[2*k+1]);
    const float r = rcp(a * b);
    ep[k] = pack_bf16(a, b); em[k] = pack_bf16(r * b, r * a);
  }
}
__device__ __forceinline__ void dual_exp2_shifted(const float (&pp)[2][16], uint32_t (&ph)[4][8]) {
  #pragma unroll
  for (int h = 0; h < 2; h++) {
    const float* p = pp[h];
    float m[4] = {p[0], p[2], p[0], p[2]};
    #pragma unroll
    for (int i = 0; i < 16; i++) { m[(i >> 1) & 1] = fmaxf(m[(i >> 1) & 1], p[i]); m[2 + ((i >> 1) & 1)] = fminf(m[2 + ((i >> 1) & 1)], p[i]); }
    #pragma unroll
    for (int o = 1; o < 4; o <<= 1) {
      m[0] = fmaxf(m[0], __shfl_xor_sync(~0u, m[0], o)); m[1] = fmaxf(m[1], __shfl_xor_sync(~0u, m[1], o));
      m[2] = fminf(m[2], __shfl_xor_sync(~0u, m[2], o)); m[3] = fminf(m[3], __shfl_xor_sync(~0u, m[3], o));
    }
    #pragma unroll
    for (int k = 0; k < 8; k++) {
      ph[2*h][k] = pack_bf16(ex2(p[2*k] - m[k & 1]), ex2(p[2*k+1] - m[k & 1]));
      ph[2*h+1][k] = pack_bf16(ex2(m[2 + (k & 1)] - p[2*k]), ex2(m[2 + (k & 1)] - p[2*k+1]));
    }
  }
}
__device__ __forceinline__ uint32_t add_bf16x2(uint32_t a, uint32_t b) { uint32_t r; asm("add.rn.bf16x2 %0, %1, %2;" : "=r"(r) : "r"(a), "r"(b)); return r; }
__device__ __forceinline__ void row_sums(float (&s)[2][4], const uint32_t (&ph)[4][8], uint32_t sel) {
  uint32_t u[8];
  #pragma unroll
  for (int i = 0; i < 8; i++) { const uint32_t* f = &ph[i >> 1][i & 1]; u[i] = add_bf16x2(add_bf16x2(f[0], f[2]), add_bf16x2(f[4], f[6])); }
  wg_fence();
  wgmma_rz_n8<0, H0>(s[0], u[0], u[1], u[2], u[3], sel);
  wgmma_rz_n8<0, H0>(s[1], u[4], u[5], u[6], u[7], sel);
  wg_commit();
}
__device__ __forceinline__ uint32_t mul_bf16x2(uint32_t a, uint32_t b) { uint32_t r; asm("mul.rn.bf16x2 %0, %1, %2;" : "=r"(r) : "r"(a), "r"(b)); return r; }
__device__ __forceinline__ void normalize(uint32_t (&ph)[4][8], const float (&s)[2][4]) {
  #pragma unroll
  for (int i = 0; i < 4; i++) {
    const float i0 = rcp(s[i >> 1][i & 1]), i1 = rcp(s[i >> 1][2 + (i & 1)]);
    const uint32_t n0 = pack_bf16(i0, i0), n1 = pack_bf16(i1, i1);
    #pragma unroll
    for (int k = 0; k < 4; k++) { ph[i][2*k] = mul_bf16x2(ph[i][2*k], n0); ph[i][2*k+1] = mul_bf16x2(ph[i][2*k+1], n1); }
  }
}
__device__ __forceinline__ void split_bf16(float a, float b, uint32_t& hi, uint32_t& lo) { hi = pack_bf16(a, b); lo = pack_bf16(a - bf_lo(hi), b - bf_hi(hi)); }
__device__ __forceinline__ void put_colsums(uint32_t base, int lane, float a, float b, float c, float d) {
  uint32_t h0, l0, h1, l1;
  split_bf16(a, b, h0, l0); split_bf16(c, d, h1, l1);
  const uint32_t ad = base + (lane >> 1) * 128 + (lane & 1) * 8;
  sts64(ad, h0, h1); sts64(ad + 16, l0, l1); sts64(ad + 32, h0, h1); sts64(ad + 48, l0, l1);
  sts128(base + (lane >> 1) * 128 + 64 + (lane & 1) * 32, 0, 0, 0, 0); sts128(base + (lane >> 1) * 128 + 80 + (lane & 1) * 32, 0, 0, 0, 0);
}
__device__ __forceinline__ float reduce8(const float (&v)[8], int lane) {
  const bool b4 = lane & 16, b3 = lane & 8, b2 = lane & 4;
  float a[4], b[2];
  #pragma unroll
  for (int i = 0; i < 4; i++) a[i] = (b4 ? v[4 + i] : v[i]) + __shfl_xor_sync(~0u, b4 ? v[i] : v[4 + i], 16);
  #pragma unroll
  for (int i = 0; i < 2; i++) b[i] = (b3 ? a[2 + i] : a[i]) + __shfl_xor_sync(~0u, b3 ? a[i] : a[2 + i], 8);
  return (b2 ? b[1] : b[0]) + __shfl_xor_sync(~0u, b2 ? b[0] : b[1], 4);
}
__device__ __forceinline__ bool tag_bad(uint4 v, uint32_t tg) { return (((v.x ^ tg) | (v.y ^ tg) | (v.z ^ tg) | (v.w ^ tg)) & 3) != 0; }


__global__ void __launch_bounds__(512, 1) fused_kernel(const __grid_constant__ Params P) {
  extern __shared__ __align__(1024) uint8_t smem_raw[];
  const uint32_t sb = smem_u32(smem_raw);
  const int tid = threadIdx.x, lane = tid & 31;
  {
    const int n = 16 * blockIdx.x + (lane & 15);
    const bf16* p = (lane < 16 ? P.x : P.wqkv) + (lane < 16 ? n * DM : (n >> 5) * (3 * DM) + DM + 64 * (n & 31));
    asm volatile("{\n.reg .pred p;\nsetp.lt.u32 p, %1, 32;\n@p prefetch.global.L2 [%0];\n}\n" :: "l"(p), "r"(tid));
  }
  const int cp = blockIdx.x >> 1, rank = blockIdx.x & 1;
  const int cr = cp < 4 ? 32 + 8 * cp : cp - 4 + max((cp * 37 - 1076) >> 8, 0);
  const int c = (cr & 62) + 64 * (cr & 1) + rank;
  const int m256 = c >> 4, nkv = c & 15, m128 = c >> 3, j = c & 7;
  if ((tid >> 7) == 2 && elect_one()) {
    if (tid >= 288) {
      const int w = (tid >> 5) - 9;
      #pragma unroll
      for (int i = 0; i < NB3; i++) mbar_init(sb + B_FULLKV + 8 + 8 * NB3 * w + 8 * i, w == 0 ? bar_count(1 + i) : w == 1 ? bar_count(1 + NB3 + i) : bar_count(1 + 2 * NB3 + i));
    } else {
      prefetch_map(&P.wkv); prefetch_map(&P.x128);
      mbar_init(sb + B_S0, 1); mbar_init(sb + B_FULLKV, 1);
      mbar_expect_tx(sb + B_S0, 32768);
      tma_4d(sb + 32768, &P.wkv, 0, 0, nkv, 1, sb + B_S0);
      tma_2d(sb, &P.x128, 0, 256 * m256, sb + B_S0);
      mbar_expect_tx(sb + B_FULLKV, 16384);
      tma_2d(sb + 16384, &P.x128, 0, 256 * m256 + 128, sb + B_FULLKV);
    }
    asm volatile("fence.mbarrier_init.release.cluster;" ::: "memory");
  }
  const int warp = __shfl_sync(~0u, tid >> 5, 0), wg = warp >> 2, wp = warp & 3;
  const int f = 16 * ((cr + 7) & 7) + 2 * (cr >> 3) + rank;
  const int ha = 4 * (nkv >> 1) + (nkv & 1);
  Scratch* const G = P.g;
  if ((sb & 0x3ffff) != SB0) asm volatile("trap;");
  __syncthreads();
  cluster_arrive();
  if (warp == 8 && elect_one()) {
    mbar_expect_tx(sb + B_FULLKV + 8, KV_STAGE);
    tma_4d(sb + KV_STAGE + 32768, &P.wkv, 0, 64, nkv, 1, sb + B_FULLKV + 8);
    tma_2d(sb + KV_STAGE, &P.x128, 64, 256 * m256, sb + B_FULLKV + 8);
    tma_2d(sb + KV_STAGE + 16384, &P.x128, 64, 256 * m256 + 128, sb + B_FULLKV + 8);
  }
  if (wg == 3) {
    asm volatile("setmaxnreg.dec.sync.aligned.u32 32;");
    cluster_wait();
    const bool el = elect_one();
    const uint64_t ef = policy_evict_first(), en = policy_evict_normal();
    auto fetch_o = [&](const int t0) {
      const int sh = t0 & 1;
      uint32_t missing = ~0u;
      const uint32_t* hint = &G->oflag[((m128 * 6 + ((t0 + 1) & 6) + rank) * 32 + ((4 * (j & 6) + lane) & 31)) * 8];
      #pragma unroll 1
      for (int i = 2 - 2 * sh; i < 8; i += 1 + sh) {
        const int blk = sh ? 6 + 2 * t0 + (i >> 1) : i, wrap = t0 == 3 ? 2 : (blk >= 5) + (blk >= 11), s = blk + 1 - 6 * wrap;
        flags_wait(missing, hint, (15u + 240u * sh) << (4 * i));
        if (blk > 5) mbar_wait(sb + B_EMPTY5 + 8 * s, wrap & 1);
        if (el) {
          tma_2d_mc_h(sb + s * R5 + rank * 8192, &P.o, 0, (m128 * 16 + t0 + 2 * (((j & 6) + i) & 7)) * 32 + 16 * rank, sb + B_GA + 16 * blk + 8 * rank, ef);
        }
      }
    };
    if (wp == 0) {
      {
        wait_until((uint32_t)clock() + 300);
        #pragma unroll 1
        for (int kb = 2; kb < 16; kb++) {
          const uint32_t st = sb + (kb & 3) * KV_STAGE, fb = sb + B_FULLKV + 8 * (kb & 3);
          mbar_wait(fb + (B_EMPTYKV - B_FULLKV), ~(kb >> 2) & 1);
          if (el) {
            mbar_expect_tx(fb, KV_STAGE);
            tma_2d_mc(st + rank * 16384, &P.x128, 64 * kb, 256 * m256 + 128 * rank, fb);
            tma_4d_h(st + 32768, &P.wkv, 0, 64 * kb, nkv, 1, fb, ef);
          }
        }
        uint64_t ord = 0xf3120edcba987654ull;
        uint32_t so = 0, par = 1;
        #pragma unroll 1
        for (int i = 0; i < 16; i++) {
          const uint32_t st = sb + so * 4096, fb = sb + B_FULL5 + so;
          const int k0 = (64 * (uint32_t)ord + 128 * (j & 6)) & 960;
          mbar_wait(i < 5 ? sb + B_EMPTYKV + so - (i > 1 ? 8 : 0) : fb + (B_EMPTY5 - B_FULL5), par);
          if (el) {
            mbar_expect_tx(fb, R5);
            tma_2d_mc_h(st + rank * 8192, &P.x64, k0, 128 * m128 + 64 * rank, fb, i >= 11 ? ef : en);
            tma_3d_h(st + 16384, &P.wq, 0, k0, 2 * j, fb, ef);
          }
          ord >>= 4; so += 8;
          if (so == 40) { so = 0; par ^= 1; }
        }
        mbar_wait(sb + B_FULL5 + 8 + 8 * rank, 0);
        if (el) mbar_arrive(sb + B_R);
        #pragma unroll 1
        for (int i = 0; i < 19; i++) {
          const int row = i < 8 ? 128 * (((j & 6) + i) & 7) : 256 * (((j >> 1) + i) & 3) + 32 + 16 * (i & 4);
          mbar_wait(sb + B_EMPTY5 + so, par);
          if (el) {
            if (i < 16) {
              tma_5d_h(sb + so * 4096 + 16384, &P.wo[i >> 3], 128 * j, row, sb + B_GB + 8 * i, ef);
              tma_5d_h(sb + so * 4096 + 24576, &P.wo[i >> 3], 128 * j + 64, row, sb + B_GB + 8 * i, ef);
            } else mbar_arrive(sb + B_DR + 8 * (i - 16));
          }
          so += 8;
          if (so == 48) { so = 0; par ^= 1; }
        }
      }
    } else if (wp == 3) {
      const uint32_t t_start = (uint32_t)clock();
      mbar_wait(sb + B_S0, 0);
      if (el) {
        mbar_expect_tx(sb + B_W, 12288);
        #pragma unroll 1
        for (int i = 0; i < 6; i++) tma_2d(sb + (i == 0 ? OFF_WPHIK : i == 1 ? OFF_WPHIK1 : OFF_WPHIQ + 2048 * (i - 2)), &P.phi, 0, 32 * (i < 2 ? 2 * nkv + i : 4 * j + 2 * (i & 1) + ((i - 2) >> 1)), sb + B_W);
        prefetch_map(&P.x64); prefetch_map(&P.wq); prefetch_map(&P.wo[0]); prefetch_map(&P.wo[1]);
        prefetch_map(&P.o); prefetch_map(&P.wd); prefetch_map(&P.out); prefetch_map(&P.wg); prefetch_map(&P.wu);
      }
      if (lane < 16) st128_rlx(&G->cand[m128 * 512 + 64 * j + 4 * lane], ~0u, ~0u, ~0u, ~0u);
      if (lane < 16) st128_rlx(&G->rstat[16 * c + lane], 0, 0, 0, 0);
      if (lane < 12) st128_rlx(&G->yacc[12 * c + lane], 0, 0, 0, 0);
      const uint32_t nt = ld32_rlx(&G->epoch);
      if (lane < 8) { st128_rlx(&G->stats[16 * c + 2 * lane], nt, nt, nt, nt); st128_rlx(&G->csq[32 * c + 4 * lane], nt, nt, nt, nt); }
      if (lane < 4) { st128_rlx(&G->cskv[128 * nkv + 16 * m256 + 4 * lane], nt, nt, nt, nt); st128_rlx(&G->oset[16 * c + 4 * lane], nt, nt, nt, nt); }
      if (lane < 4) st128_rlx(&G->key[(2 * j + (lane >> 1)) * 128 + m128 * 8 + 4 * (lane & 1)], 0, 0, 0, 0);
      if (c < 32) {
        #pragma unroll 1
        for (int i = lane; i < KVP; i += 32) st128_rlx(&G->kvacc[(ha + 2 * m256) * KVP + i], 0, 0, 0, kv_count(nt + 1, 0));
      }
      fence_gpu();
      bar_arrive(NB_ZERO, 160);
      if (el) {
        #pragma unroll 1
        for (int i = 0; i < 30; i++) {
          wait_until(t_start + PF_T0 + PF_DT * i + 7 * f);
          if (i < 4) { bulk_prefetch(P.wqkv + (size_t)(256 * i + c) * (3 * DM), 2048); bulk_prefetch(P.wqkv + (size_t)(256 * i + 128 + c) * (3 * DM), 2048); }
          else if (i < 6) bulk_prefetch(P.wo_p + (size_t)c * 8192 + (i - 4) * 4096, 8192);
          else if (f < NFFN) {
            if (i < 22) {
              #pragma unroll 1
              for (int e = 0; e < 4; e++) tma_2d(sb + OFF_T, rank ? &P.tu : &P.tg, 32 * (f & ~1), 64 * (i - 6) + 16 * e, sb + B_T);
            } else { tma_2d(sb + OFF_T, &P.td, 0, 256 * f + 32 * (i - 22), sb + B_T); tma_2d(sb + OFF_T, &P.td, 0, 256 * f + 32 * (i - 22) + 16, sb + B_T); }
          }
        }
      }
      __syncwarp();
      mbar_wait2(sb + B_OS, 0, sb + B_RX, 0);
      mbar_wait2(sb + B_EMPTY5 + 24, 0, sb + B_EMPTY5 + 32, 0);
      mbar_wait2(sb + B_EMPTY5 + 40, 0, sb + B_EMPTY5, 1);
      fetch_o(0);
      fetch_o(3);
    } else {
      const int half = wp - 1;
      const uint32_t ep1 = ld32_rlx(&G->epoch) + 1, tg = ep1 & 3;
      {
        uint32_t it = 0;
        sts128(sb + OFF_ONES + half * 512 + lane * 16, 0x3f803f80u, 0x3f803f80u, 0x3f803f80u, 0x3f803f80u);
        if (lane < 9) { const uint32_t v = (lane & 1) ? 0 : 0x3f803f80u; sts128(sb + OFF_SEL + lane * 16, v, v, v, v); }
        auto reset_o = [&](int i0, int i1, uint32_t dt) {
          uint32_t t0 = (uint32_t)clock();
          #pragma unroll 1
          for (int i = i0; i < i1; i++) {
            st128_rlx(G->o + (m128 * 16 + 2 * j + half) * 8192 + 256 * i + 8 * lane, ~0u, ~0u, ~0u, ~0u);
            wait_until(t0 += dt);
          }
        };
        if (el) {
          #pragma unroll 1
          for (int i = 24 * half; i < 24 * half + 24; i++) { mbar_init(sb + B_GB + 8 * i, 1); mbar_expect_tx(sb + B_GB + 8 * i, i < 16 ? 16384 : 8192); }
          asm volatile("fence.mbarrier_init.release.cluster;" ::: "memory");
        }
        mbar_wait(sb + B_S0, 0);
        reset_o(0, RS_N, RS_D1);
        bar_sync(NB_PUB, 192);
        const uint4* src = reinterpret_cast<const uint4*>(&G->stats[256 * m256 + 128 * half]) + lane;
        const uint4* srk = reinterpret_cast<const uint4*>(&G->cskv[128 * nkv]) + lane;
        uint4 v0, v1, vk;
        it = 0;
        do { v0 = ld128_rlx(src); v1 = ld128_rlx(src + 32); vk = ld128_rlx(srk); }
        while ((tag_bad(v0, tg) || tag_bad(v1, tg) || tag_bad(vk, tg)) && ++it < POLL_LIMIT);
        fence_acquire_gpu();
        if (half) put_colsums(sb + OFF_BXK, lane, untag(vk.x), untag(vk.y), untag(vk.z), untag(vk.w));
        #pragma unroll
        for (int i = 0; i < 2; i++) {
          const uint4 v = i ? v1 : v0;
          uint32_t hi, lo;
          split_bf16(-0.5f * untag(v.x), -0.5f * untag(v.z), hi, lo);
          const uint32_t h0 = __byte_perm(hi, hi, 0x1010), h1 = __byte_perm(hi, hi, 0x3232), l0 = __byte_perm(lo, lo, 0x1010), l1 = __byte_perm(lo, lo, 0x3232);
          const uint32_t a = sb + OFF_AXK + half * 2048 + i * 1024 + lane * 32;
          sts128(a, h0, l0, 0, 0); sts128(a + 16, h1, l1, 0, 0);
          sts64(sb + OFF_RS256 + half * 512 + i * 256 + lane * 8, v.y & ~3u, v.w & ~3u);
          if (half == (m128 & 1)) {
            const uint32_t aq = sb + OFF_AXQ + i * 1024 + lane * 32;
            sts128(aq, h0, l0, 0, 0); sts128(aq + 16, h1, l1, 0, 0);
            sts64(sb + OFF_RSQ + i * 256 + lane * 8, v.y & ~3u, v.w & ~3u);
          }
        }
        fence_async_smem();
        __syncwarp();
        if (el) { sts32(sb + OFF_EP, ep1); mbar_arrive(sb + B_AUX); }
        reset_o(RS_N, 32, RS_D2);
        if (lane < 24) st128_rlx(&G->oflag[((m128 * 6 + 3 * half + (lane >> 3)) * 32 + 4 * j) * 8 + 4 * (lane & 7)], 0, 0, 0, 0);
        fence_gpu();
        __syncwarp();
        if (el) { st32_rlx(&G->oset[16 * c + 8 * half], ep1); if (half) mbar_arrive(sb + B_AUXQ); }
        if (!half) {
          const uint4* src = reinterpret_cast<const uint4*>(&G->csq[128 * j]) + lane;
          uint4 v0, v1, v2, v3;
          do { v0 = ld128_rlx(src); v1 = ld128_rlx(src + DM / 4); v2 = ld128_rlx(src + DM / 2); v3 = ld128_rlx(src + 3 * DM / 4); }
          while ((tag_bad(v0, tg) || tag_bad(v1, tg) || tag_bad(v2, tg) || tag_bad(v3, tg)) && ++it < POLL_LIMIT);
          put_colsums(sb + OFF_BXQ, lane, (untag(v0.x) + untag(v1.x)) + (untag(v2.x) + untag(v3.x)), (untag(v0.y) + untag(v1.y)) + (untag(v2.y) + untag(v3.y)),
                      (untag(v0.z) + untag(v1.z)) + (untag(v2.z) + untag(v3.z)), (untag(v0.w) + untag(v1.w)) + (untag(v2.w) + untag(v3.w)));
          fence_async_smem();
          __syncwarp();
          if (el) mbar_arrive(sb + B_AUXQ);
        }
      }
      if (half == 0) {
        for (uint32_t it = 0; __any_sync(~0u, ld32_rlx(&G->oset[m128 * 128 + 8 * (lane & 15)]) != ep1) && it < POLL_LIMIT; it++) {}
        fence_acquire_gpu();
        if (el) mbar_arrive(sb + B_OS);
      }
      if (!half) {
        #pragma unroll 1
        for (int hh = 0; hh < 2; hh++) {
          const uint32_t src = sb + (1 + rank) * R5 + hh * 8192, fa = sb + B_GA + 16 * rank + 8 * hh;
          mbar_wait2(sb + B_UO + 8 * hh, 0, sb + B_GB + 8 * rank, 0);
          if (el) bulk_s2peer(mapa(src, rank ^ 1), src, 8192, mapa(fa, rank ^ 1));
        }
        fetch_o(1);
      }
      else if (f < NFFN) {
        mbar_wait(sb + B_UO + 24, 0);
        mbar_wait2(sb + B_UO, 0, sb + B_UO + 8, 0);
        uint32_t t0 = (uint32_t)clock();
        #pragma unroll 1
        for (int i = 0; i < 12; i++) {
          const int e = (FF_ORD >> (4 * i)) & 15;
          const uint32_t dst = sb + 16384 * ((FF_SLOT >> (4 * e)) & 15), fb = sb + B_F + 8 * e;
          if (i >= 2) mbar_wait(sb + B_WC + 8 * ((0x100066553244ull >> (4 * e)) & 15), 0);
          wait_until(t0);
          t0 = (uint32_t)clock() + (i < FF_N ? FF_DT : FF_D2);
          if (el) {
            mbar_expect_tx(fb, 16384);
            if (e >= 8) tma_3d_h(dst, &P.wd, 0, 32 * f, 4 * e - 32, fb, ef);
            else { tma_2d_h(dst, &P.wg, 32 * f, 128 * e, fb, ef); tma_2d_h(dst + 8192, &P.wu, 32 * f, 128 * e, fb, ef); }
          }
        }
      }
      __syncwarp();
    }
    if (wp & 1) {
      __syncwarp();
      mbar_wait(sb + B_OUT + 8 * (wp >> 1), 0);
      uint32_t t0 = (uint32_t)clock();
      #pragma unroll 1
      for (int i = 0; i < 8; i++) {
        wait_until(t0);
        if (el) tma_store_2d(&P.out, 128 * j + 64 * (i & 1), 128 * m128 + 32 * (wp & 2) + 8 * (i & 6), sb + OFF_OUT + (i & 1) * 16384 + (wp & 2) * 4096 + (i & 6) * 1024, ef);
        t0 += OUT_D;
      }
      if (el) { bulk_commit(); bulk_wait_all(); fence_async_global(); mbar_arrive(sb + B_SD); }
    }
    __syncwarp();
    cluster_arrive(); cluster_wait();
    return;
  }

  asm volatile("setmaxnreg.inc.sync.aligned.u32 160;");
  cluster_wait();
  const int t = tid & 127, g = lane >> 2;
  const uint32_t sa = (16 * wp + (lane & 15)) * 128 + (((lane >> 4) ^ (lane & 7)) << 4);

  if (wg == 2) {
    float s[2] = {0.f, 0.f}, s2[2] = {0.f, 0.f}, ck[8] = {0.f, 0.f, 0.f, 0.f, 0.f, 0.f, 0.f, 0.f}, cs[8] = {0.f, 0.f, 0.f, 0.f, 0.f, 0.f, 0.f, 0.f};
    const uint32_t ebr = mapa(sb + B_EMPTYKV, lane & 1), tg = (ld32_rlx(&G->epoch) + 1) & 3;
    auto addx = [&](const uint4 v) {
      const uint32_t w[4] = {v.x, v.y, v.z, v.w};
      #pragma unroll
      for (int e = 0; e < 4; e++) { const float a = bf_lo(w[e]), d = bf_hi(w[e]); s[0] += a; s[1] += d; s2[0] = fmaf(a, a, s2[0]); s2[1] = fmaf(d, d, s2[1]); }
    };
    auto addc = [&](const uint4 v, float (&o)[8]) {
      o[0] += bf_lo(v.x); o[1] += bf_hi(v.x); o[2] += bf_lo(v.y); o[3] += bf_hi(v.y); o[4] += bf_lo(v.z); o[5] += bf_hi(v.z); o[6] += bf_lo(v.w); o[7] += bf_hi(v.w);
    };
    {
      const uint32_t ra = (16 * nkv + (t >> 3)) * 128 + (t & 7) * 16;
      const uint32_t ca = 32768 + (m256 >> 2) * 8192 + (t >> 1) * 128 + (((2 * (m256 & 3) + (t & 1)) ^ ((t >> 1) & 7)) << 4);
      int rd = 0;
      mbar_wait(sb + B_S0, 0);
      #pragma unroll 1
      for (int kb = 0; kb < 10; kb++) {
        const uint32_t st = sb + (kb & 3) * KV_STAGE;
        mbar_wait(sb + B_FULLKV + 8 * (kb & 3), (kb >> 2) & 1);
        const uint4 x0 = lds128(st + ra), w0 = lds128(st + ca);
        addx(x0); addc(w0, ck);
        __syncwarp();
        if (lane < 2) mbar_arrive_remote(ebr + 8 * (kb & 3), 1);
        if ((SKM >> kb) & 1) {
          if (rd) {
            mbar_wait(sb + B_G, (rd - 1) & 1);
            const uint32_t a = sb + OFF_G + (t >> 3) * 256 + (t & 7) * 16;
            const uint4 x1 = lds128(a), x2 = lds128(a + 128), w1 = lds128(sb + OFF_G + 4096 + t * 16), w2 = lds128(sb + OFF_G + 6144 + t * 16);
            addx(x1); addx(x2); addc(w1, ck); addc(w2, ck);
            bar_sync(NB_WG2, 128);
          }
          if (wp == 0 && elect_one()) {
            mbar_expect_tx(sb + B_G, 8192);
            if (rd < 3) {
              tma_2d(sb + OFF_G, &P.xs, 640 + 128 * rd, 256 * m256 + 16 * nkv, sb + B_G);
              tma_2d(sb + OFF_G + 4096, &P.ws, (1 + (m256 >> 2)) * DM + 64 * nkv + 16 * (m256 & 3), 640 + 128 * rd, sb + B_G);
            } else tma_2d(sb + OFF_G, &P.qs, 32 * (c & 31), 256 * (c >> 5), sb + B_G);
          }
          rd++;
        }
      }
    }
    const uint32_t scr = sb + OFF_WR;
    float sx = s[0] + s[1], sq = s2[0] + s2[1];
    #pragma unroll
    for (int o = 1; o < 8; o <<= 1) { sx += __shfl_xor_sync(~0u, sx, o); sq += __shfl_xor_sync(~0u, sq, o); }
    float v = reduce8(ck, lane);
    v += __shfl_xor_sync(~0u, v, 2);
    if (!(lane & 2)) stsf(scr + (wp * 16 + 8 * (lane & 1) + (lane >> 2)) * 4, v);

    bar_sync(NB_ZERO, 160);
    if ((lane & 7) == 0) {
      const float mean = sx * (1.f / DM);
      st64_rlx(&G->stats[256 * m256 + 16 * nkv + (t >> 3)], tagw(mean, tg), tagw(rsqrtf(fmaxf(sq * (1.f / DM) - mean * mean, 0.f) + 1e-5f), tg));
    }
    if (wp == 1 && lane < 16) {
      const uint32_t a = scr + lane * 4;
      st32_rlx(&G->cskv[128 * nkv + 16 * m256 + lane], tagw((ldsf(a) + ldsf(a + 64)) + (ldsf(a + 128) + ldsf(a + 192)), tg));
    }
    __syncwarp();
    bar_arrive(NB_PUB, 192);
    const uint4 wv = ld128_keep(P.wr + t * 8);
    #pragma unroll 1
    for (int i = 0; i < 2; i++) {
      mbar_wait(sb + B_G, i ^ 1);
      const uint32_t a = sb + OFF_G + t * 16;
      const uint4 u0 = lds128(a), u1 = lds128(a + 2048), u2 = lds128(a + 4096), u3 = lds128(a + 6144);
      addc(u0, cs); addc(u1, cs); addc(u2, cs); addc(u3, cs);
      bar_sync(NB_WG2, 128);
      if (i == 0 && wp == 0 && elect_one()) { mbar_expect_tx(sb + B_G, 8192); tma_2d(sb + OFF_G, &P.qs, 32 * (c & 31), 256 * (c >> 5) + 128, sb + B_G); }
    }
    float sw = (bf_lo(wv.x) + bf_hi(wv.x)) + (bf_lo(wv.y) + bf_hi(wv.y)) + (bf_lo(wv.z) + bf_hi(wv.z)) + (bf_lo(wv.w) + bf_hi(wv.w));
    #pragma unroll
    for (int o = 16; o; o >>= 1) sw += __shfl_xor_sync(~0u, sw, o);
    if (lane == 0) stsf(sb + OFF_SUMWR + wp * 4, sw);
    if ((t >> 4) == j) {
      const uint32_t a = sb + OFF_WR + (t & 15) * 32;
      sts128(a, wv.x << 16, wv.x & 0xffff0000u, wv.y << 16, wv.y & 0xffff0000u);
      sts128(a + 16, wv.z << 16, wv.z & 0xffff0000u, wv.w << 16, wv.w & 0xffff0000u);
    }
    v = reduce8(cs, lane);
    stsf(sb + OFF_G + (wp * 32 + 8 * (lane & 3) + (lane >> 2)) * 4, v);
    bar_sync(NB_WG2, 128);
    if (wp == 0) {
      const uint32_t a = sb + OFF_G + lane * 4, cq = tagw((ldsf(a) + ldsf(a + 128)) + (ldsf(a + 256) + ldsf(a + 384)), tg);
      st32_rlx(&G->csq[(c >> 5) * DM + 32 * (c & 31) + lane], cq);
      if (lane == 0) mbar_arrive_at(sb + B_W, rank, (cq & P.zero) + 1);
    }
  }

  uint32_t xr[32];
  {
    const bool isq = wg == 2;
    float acc[2][64];
    {
      const uint32_t emptyb = mapa(sb + (isq ? B_EMPTY5 : B_EMPTYKV), t & 1);
      auto correct = [&](uint32_t xa, uint32_t xb) {
        wg_fence();
        wgmma_sa_n128<0, 1, H0, H0>(acc[0], dlo(SB0, 0) + (xa >> 4), dlo(SB0, 0) + (xb >> 4));
        wgmma_sa_n128<0, 1, H0, H0>(acc[1], dlo(SB0, 0) + (xa >> 4) + 64, dlo(SB0, 0) + (xb >> 4));
        wg_commit();
      };
      if (!isq) {
        mbar_wait(sb + B_S0, 0);
        if (wg) mbar_wait(sb + B_FULLKV, 0);
        #pragma unroll 1
        for (int kb = 0; kb < 16; kb++) {
          const uint32_t da = dlo(SB0, 16) + wg * 1024 + (kb & 3) * (KV_STAGE >> 4), db = dlo(SB0 + 32768, 8192) + (kb & 3) * (KV_STAGE >> 4);
          wg_fence();
          #pragma unroll
          for (int k = 0; k < 4; k++) {
            wgmma_ss_n128<0, 1, H128, H128>(acc[0], da + 2 * k, db + 128 * k, k > 0 || kb != 0);
            wgmma_ss_n128<0, 1, H128, H128>(acc[1], da + 512 + 2 * k, db + 128 * k, k > 0 || kb != 0);
          }
          wg_commit();
          wg_wait<1>();
          if (kb > 0 && t < 2) mbar_arrive_remote(emptyb + 8 * ((kb - 1) & 3), kb > 10 ? 3 : 1);
          if (kb < 15) mbar_wait(sb + B_FULLKV + 8 * ((kb + 1) & 3), ((kb + 1) >> 2) & 1);
          if (kb == 0) mbar_wait(sb + B_FULLKV, 0);
          if (kb == 15 - LAG && wg == 1) bar_sync(NB_LAG, 256);
        }
        bar_arrive(wg ? NB_QGO : NB_LAG, 256);
        mbar_wait(sb + B_AUX, 0);
        correct(OFF_AXK + wg * 2048, OFF_BXK);
        wg_wait<0>();
        if (t < 2) mbar_arrive_remote(emptyb + 24, 3);
        fence_regs(acc[0]); fence_regs(acc[1]);
      const uint32_t stg = sb + OFF_X + (1 - wg) * 24576;
      const uint32_t va = stg + 16384 + (16 * wp + (lane & 15)) * 64 + (((lane >> 4) ^ ((lane >> 1) & 3)) << 4);
      const uint32_t ra = sb + OFF_RS256 + (128 * wg + 16 * wp + g) * 4;
      const float rs[4] = {ldsf(ra), ldsf(ra + 32), ldsf(ra + 256), ldsf(ra + 288)};
      float p[2][16];
      uint32_t vf[16], kf[2][16];
      auto project = [&](const uint32_t (&f)[16], uint32_t db) {
        wg_fence();
        #pragma unroll
        for (int i = 0; i < 2; i++) {
          wgmma_rs_n32<1, H64>(p[i], f[8*i], f[8*i+1], f[8*i+2], f[8*i+3], db, 0);
          wgmma_ra_n32<1, H64>(p[i], f[8*i+4], f[8*i+5], f[8*i+6], f[8*i+7], db + 64);
        }
        wg_commit();
      };
      auto fold = [&](uint32_t (&f)[16], int col, float sc) {
        #pragma unroll
        for (int i = 0; i < 16; i++) {
          const float r = rs[2 * (i >> 3) + (i & 1)] * sc;
          f[i] = pack_bf16(acc[i >> 3][col + 2 * (i & 7)] * r, acc[i >> 3][col + 2 * (i & 7) + 1] * r);
          asm volatile("" : "+r"(f[i]));
        }
      };
      auto put_v = [&](const uint32_t (&f)[16]) {
        #pragma unroll
        for (int k = 0; k < 4; k++) stsm4((va ^ ((k & 1) << 5)) + (k >> 1) * 4096, f[4*k], f[4*k+1], f[4*k+2], f[4*k+3]);
      };
      fold(vf, 48, 1.f);
      mbar_wait(sb + B_W, 0);
      fold(kf[0], 0, LOG2E);
      #pragma unroll
      for (int i = 0; i < 32; i++) p[i >> 4][i & 15] = acc[i >> 4][i & 15];
      project(kf[0], dlo(SB0 + OFF_WPHIK, 16));
      mbar_wait(sb + B_W, 0);
      {
        uint32_t v0[16];
        fold(kf[1], 16, LOG2E);
        fold(v0, 32, 1.f);
        if (wg == 1) bar_sync(NB_DN, 256);
        put_v(v0);
      }
      wg_wait<0>();
      fence_regs(p[0]); fence_regs(p[1]);
      if (wg == 1) bar_arrive(NB_WG01, 256);
      #pragma unroll 1
      for (int h = 0; h < 2; h++) {
        uint32_t ph[4][8];
        float rsum[2][4];
        dual_exp2(p[0], ph[0], ph[1]); dual_exp2(p[1], ph[2], ph[3]);
        row_sums(rsum, ph, dlo(SB0 + OFF_SEL, 16));
        if (wg == 0 && h == 0) { bar_arrive(NB_DN, 256); bar_sync(NB_WG01, 256); }
        if (h == 1) {
          if (wg == 1) bar_sync(NB_DN, 256);
          put_v(vf);
        }
        wg_wait<0>();
        fence_regs(rsum[0]); fence_regs(rsum[1]);
        if (__builtin_expect(__any_sync(~0u, !((rsum[0][0] + rsum[0][1]) + (rsum[0][2] + rsum[0][3]) + (rsum[1][0] + rsum[1][1]) + (rsum[1][2] + rsum[1][3]) < EXP_LIM)), 0)) {
          dual_exp2_shifted(p, ph);
          #pragma unroll
          for (int i = 0; i < 8; i++) {
            const uint32_t* f = &ph[i >> 1][i & 1];
            float a = (bf_lo(f[0]) + bf_hi(f[0])) + (bf_lo(f[2]) + bf_hi(f[2])) + (bf_lo(f[4]) + bf_hi(f[4])) + (bf_lo(f[6]) + bf_hi(f[6]));
            a += __shfl_xor_sync(~0u, a, 1);
            rsum[i >> 2][2 * (i & 1) + ((i >> 1) & 1)] = a + __shfl_xor_sync(~0u, a, 2);
          }
        }
        if (h == 0) project(kf[1], dlo(SB0 + OFF_WPHIK1, 16));
        normalize(ph, rsum);
        #pragma unroll
        for (int i = 0; i < 8; i++) {
          const uint32_t* f = &ph[i >> 1][4 * (i & 1)];
          stsm4(((stg + sa) ^ ((i & 3) << 5)) + (i >> 2) * 8192, f[0], f[1], f[2], f[3]);
        }
        fence_async_smem();
        if (wg == h) {
          float kv[20];
          #pragma unroll
          for (int w = 0; w < 2; w++) {
            const uint32_t da = dlo(SB0 + OFF_X, 16) + (h ^ w ^ 1) * 1536, db = dlo(SB0 + OFF_X + 16384, OFF_ONES - OFF_X - 16384) - (h ^ w ^ 1) * (1536 * 65535);
            if (w) bar_sync(NB_ST, 256); else bar_sync(NB_L0 + h, 128);
            wg_fence();
            #pragma unroll
            for (int k = 0; k < 8; k++) {
              if (k == 0 && w == 0) wgmma_sz_n40<1, 1, H128, H64>(kv, da, db);
              else wgmma_sa_n40<1, 1, H128, H64>(kv, da + k * 128, db - k * (64 * 65535));
            }
            wg_commit();
          }
          float4* dst = &G->kvacc[(ha + 2 * h) * KVP + t];
          wg_wait<0>();
          fence_regs(kv);
          if (h == 0) bar_arrive(NB_DN, 256); else if (t < 2) { mbar_arrive_at(sb + B_EMPTY5 + 40, t, 2); if (t == 0) mbar_arrive(sb + B_KD); }
          kv[17] = kv[18];
          #pragma unroll
          for (int i = 0; i < 6; i++) red_add_f32x4(dst + 128 * i, kv[3*i], kv[3*i+1], kv[3*i+2], 1.f);
        } else bar_arrive(NB_ST, 256);
        wg_wait<0>();
        fence_regs(p[0]); fence_regs(p[1]);
      }
      #pragma unroll
      for (int i = 0; i < 32; i++) asm volatile("mov.b32 %0, 0;" : "=r"(xr[i]));
      } else {
        uint32_t so = 0, po = 0, par = 0;
        mbar_wait(sb + B_FULL5, 0);
        bar_sync(NB_QGO, 256);
        #pragma unroll 1
        for (int kb = 0; kb < 16 - ML; kb++) {
          const uint32_t da = dlo(SB0, 16) + so * 256, db = dlo(SB0 + 16384, 8192) + so * 256;
          #pragma unroll
          for (int k = 0; k < 4; k++) {
            wg_fence();
            wgmma_ss_n128<0, 1, H128, H128>(acc[0], da + 2 * k, db + 128 * k, k > 0 || kb != 0);
            wgmma_ss_n128<0, 1, H128, H128>(acc[1], da + 512 + 2 * k, db + 128 * k, k > 0 || kb != 0);
            wg_commit();
            if (k == 1 && kb > 0 && t < 2) mbar_arrive_remote(emptyb + po, 2);
            if (k == 3) {
              po = so; so += 8;
              if (so == 40) { so = 0; par ^= 1; }
              mbar_wait(sb + B_FULL5 + so, par);
            }
            if ((QW >> k) & 1) wg_wait<2>(); else wg_wait<1>();
          }
        }
        auto block = [&](const int kb, const int i) {
          wg_fence();
          #pragma unroll
          for (int k = 0; k < 4; k++) wgmma_sa_n128<0, 1, H128, H128>(acc[i], dlo(SB0, 16) + (kb % 5) * 2048 + 512 * i + 2 * k, dlo(SB0 + 16384, 8192) + (kb % 5) * 2048 + 128 * k);
          wg_commit();
        };
        auto hand_over = [&](const int i) {
          const uint32_t ta = sb + (1 + rank) * R5 + sa + i * 8192;
          #pragma unroll
          for (int k = 0; k < 4; k++) {
            const float* a = &acc[i][32 * (k >> 1) + 8 * (k & 1)];
            stsm4(ta ^ (k << 5), pack_bf16(a[0], a[1]), pack_bf16(a[2], a[3]), pack_bf16(a[4], a[5]), pack_bf16(a[6], a[7]));
          }
        };
        mbar_wait2(sb + B_AUXQ, 0, sb + B_OS, 0);
        correct(OFF_AXQ, OFF_BXQ);
        #pragma unroll
        for (int kb = 16 - ML; kb < 16; kb++) {
          block(kb, 0);
          if (kb < 15) mbar_wait(sb + B_FULL5 + 8 * ((kb + 1) % 5), ((kb + 1) / 5) & 1);
          if (kb == 16 - ML) { wg_wait<2>(); if (t < 2) mbar_arrive_remote(emptyb + 8 * ((kb - 1) % 5), 2); }
        }
        mbar_wait(sb + B_RC, 0);
        block(16 - ML, 1);
        block(17 - ML, 1);
        wg_wait<2>();
        fence_regs(acc[0]);
        hand_over(0);
        fence_async_smem();
        bar_arrive(NB_Q0, 256);
        #pragma unroll
        for (int kb = 18 - ML; kb <= 16; kb++) {
          wg_wait<1>();
          if (t < 2) mbar_arrive_remote(emptyb + 8 * ((kb - 2) % 5), 2);
          if (kb < 16) block(kb, 1);
        }
        mbar_wait(sb + B_RC + 8, 0);
        wg_wait<0>();
        if (t < 2) mbar_arrive_remote(emptyb, 2);
        fence_regs(acc[1]);
        hand_over(1);
        fence_async_smem();
        bar_arrive(NB_Q0 + 1, 256);
        #pragma unroll
        for (int i = 0; i < 32; i++) { const float* a = &acc[(i >> 3) & 1][16 + 32 * (i >> 4) + 2 * (i & 7)]; xr[i] = pack_bf16(a[0], a[1]); }
      }
    }
    float p[2][16];
    #pragma unroll
    for (int i = 0; i < 32; i++) asm volatile("mov.b32 %0, 0;" : "=f"(p[i >> 4][i & 15]));
    auto project_r = [&](int w) {
      wg_fence();
      #pragma unroll
      for (int h = 0; h < 2; h++) {
        wgmma_rs_n32<1, H64>(p[h], xr[8*h], xr[8*h+1], xr[8*h+2], xr[8*h+3], dlo(SB0 + OFF_WPHIQ, 16) + 128 * w, 0);
        wgmma_ra_n32<1, H64>(p[h], xr[8*h+4], xr[8*h+5], xr[8*h+6], xr[8*h+7], dlo(SB0 + OFF_WPHIQ, 16) + 128 * w + 64);
      }
      wg_commit();
    };
    auto capture = [&](const int i) {
      if (!i) mbar_wait(sb + B_R, 0);
      #pragma unroll
      for (int k = 0; k < 4; k++) ldsm4(((sb + (1 + rank) * R5 + wg * 8192 + sa) ^ (k << 5)) + i * 2 * R5, xr[16*i+4*k], xr[16*i+4*k+1], xr[16*i+4*k+2], xr[16*i+4*k+3]);
      const uint32_t one = (((xr[16*i] | xr[16*i+4]) | (xr[16*i+8] | xr[16*i+12])) & P.zero) + 1;
      if (lane == 0) mbar_arrive_at(sb + (i ? B_RX : B_RC + 8 * wg), i ? wg : rank, one);
    };
    const uint32_t rq = sb + OFF_RSQ + (16 * wp + g) * 4 + 256 * (wg & 1), rb = rq + 128 * (wg & 2);
    const float cc[2][2] = {{ldsf(rq) * LOG2E, ldsf(rq + 32) * LOG2E}, {ldsf(rb) * LOG2E, ldsf(rb + 32) * LOG2E}};
    {
      const uint4* src = reinterpret_cast<const uint4*>(&G->kvacc[(4 * j + wg) * KVP + t]);
      const uint32_t full = kv_count(__float_as_uint(ldsf(sb + OFF_EP)), 8);
      uint4 v[12];
      #pragma unroll
      for (int i = 0; i < 12; i++) v[i] = i < 6 || isq ? ld128_rlx(src + 128 * i) : make_uint4(0, 0, 0, full);
      if (isq) {
        project_r(2);
        wg_wait<0>();
        #pragma unroll
        for (int i = 0; i < 16; i++) xr[i] = xr[16 + i];
      } else {
        capture(0);
      }
      #pragma unroll 1
      for (uint32_t it = 0; it < POLL_LIMIT; it++) {
        uint32_t bad = 0;
        #pragma unroll
        for (int i = 0; i < 12; i++) bad |= v[i].w ^ full;
        if (!__any_sync(~0u, bad != 0)) break;
        #pragma unroll
        for (int i = 0; i < 12; i++) if (i < 6 || isq) v[i] = ld128_rlx(src + 128 * i);
      }
      mbar_wait(sb + B_KD, 0);
      #pragma unroll
      for (int e = 0; e < 2; e++) {
        if (e == 0 || isq) {
          float f[18];
          #pragma unroll
          for (int i = 0; i < 6; i++) { f[3*i] = __uint_as_float(v[6*e+i].x); f[3*i+1] = __uint_as_float(v[6*e+i].y); f[3*i+2] = __uint_as_float(v[6*e+i].z); }
          const uint32_t ka = sb + OFF_KVZ + (wg + e) * 5120 + wp * 1280 + lane * 16;
          stsm4(ka, pack_bf16(f[0], f[1]), pack_bf16(f[2], f[3]), pack_bf16(f[4], f[5]), pack_bf16(f[6], f[7]));
          stsm4(ka + 512, pack_bf16(f[8], f[9]), pack_bf16(f[10], f[11]), pack_bf16(f[12], f[13]), pack_bf16(f[14], f[15]));
          stsm2(ka + 1024, pack_bf16(f[16], 1.f), pack_bf16(f[17], 1.f));
        }
      }
    }
    fence_async_smem();
    if (wg == 1) bar_arrive(NB_DN, 256);
    #pragma unroll 1
    for (int e = wg; e < wg + 1 + (wg >> 1); e++) {
      const int half = e >> 1, hh = e & 1, turn = e;
      const uint32_t ao = (1 + rank) * R5 + hh * 8192;
      uint32_t ph[4][8];
      #pragma unroll
      for (int i = 0; i < 32; i++) asm volatile("mov.b32 %0, 0;" : "=r"(ph[i >> 3][i & 7]));
      uint32_t shifted = 0;
      asm volatile("" : "+r"(shifted));
      #pragma unroll 1
      for (;;) {
        if (shifted) dual_exp2_shifted(p, ph);
        uint32_t first = (shifted ^ 1) & !isq;
        asm volatile("" : "+r"(first));
        if (first) {
          bar_sync(NB_Q0 + wg, 256);
          const uint32_t da = dlo(SB0, 16) + (ao >> 4), db = dlo(SB0 + OFF_WPHIQ, 16);
          wg_fence();
          #pragma unroll
          for (int h = 0; h < 2; h++) {
            wgmma_ss_n32<0, 1, H128, H64>(p[h], da + 4 * h, db + 128 * h, 0);
            wgmma_sa_n32<0, 1, H128, H64>(p[h], da + 4 * h + 2, db + 128 * h + 64);
          }
          wg_commit();
          capture(1);
          wg_wait<0>();
        }
        fence_regs(p[0]); fence_regs(p[1]);
        uint32_t again = shifted;
        asm volatile("" : "+r"(again));
        if (again) break;
        float s2[4] = {0.f, 0.f, 0.f, 0.f};
        #pragma unroll
        for (int i = 0; i < 32; i++) { float& x = p[i >> 4][i & 15]; x *= cc[i >> 4][(i >> 1) & 1]; s2[i & 3] = fmaf(x, x, s2[i & 3]); }
        if (!__any_sync(~0u, !((s2[0] < ARG_LIM2) & (s2[1] < ARG_LIM2) & (s2[2] < ARG_LIM2) & (s2[3] < ARG_LIM2)))) break;
        shifted = 1;
      }
      if (e == 1 || e == 2) bar_sync(NB_TOK + e - 1, 256);
      float ac[4][20];
      auto numer = [&](int h) {
        const uint32_t (*f)[8] = &ph[2 * h];
        const uint32_t db = dlo(SB0 + OFF_KVZ, 128) + (half ? e : h) * 320;
        wg_fence();
        #pragma unroll
        for (int i = 0; i < 2; i++) {
          wgmma_rz_n40<1, dhi(256, 0)>(ac[2*h+i], f[i][0], f[i][1], f[i][2], f[i][3], db + i * 160);
          wgmma_ra_n40<1, dhi(256, 0)>(ac[2*h+i], f[i][4], f[i][5], f[i][6], f[i][7], db + (i * 160 + 80));
        }
        wg_commit();
      };
      const uint32_t oa = (16 * wp + g) * 128 + (((lane & 3) ^ g) << 4);
      auto finish = [&](int h) {
        const float* ap = ac[2 * h]; const float* am = ac[2 * h + 1];
        const float ip0 = rcp(ap[17]), im0 = rcp(am[17]), ip1 = rcp(ap[19]), im1 = rcp(am[19]);
        const float d0 = rcp(fmaf(ap[16], ip0, fmaf(am[16], im0, 1e-6f))), d1 = rcp(fmaf(ap[18], ip1, fmaf(am[18], im1, 1e-6f)));
        const float a0 = ip0 * d0, b0 = im0 * d0, a1 = ip1 * d1, b1 = im1 * d1;
        #pragma unroll
        for (int r = 0; r < 2; r++) {
          const float a = r ? a1 : a0, b = r ? b1 : b0;
          uint32_t w[4];
          #pragma unroll
          for (int k = 0; k < 4; k++) w[k] = pack_bf16(fmaf(ap[4*k+2*r], a, am[4*k+2*r] * b), fmaf(ap[4*k+2*r+1], a, am[4*k+2*r+1] * b));
          const uint32_t off = (oa ^ ((half ? rank : h) << 6)) + r * 1024;
          st128_rlx(reinterpret_cast<uint8_t*>(G->o + (m128 * 16 + (half ? 2 * (j & 6) + 2 * hh + 1 : 2 * j)) * 8192 + (half ? h : hh) * 4096) + off, w[0], w[1], w[2], w[3]);
          if (!half) sts128(sb + ao + off, w[0], w[1], w[2], w[3]);
        }
        if ((half || h) && lane < 8) st32_rlx(&G->oflag[((m128 * 6 + (half ? 2 * e - 2 + h : hh)) * 32 + 4 * j + wp) * 8 + lane], 1);
      };
      if (!shifted) dual_exp2(p[0], ph[0], ph[1]);
      numer(0);
      if (!shifted) dual_exp2(p[1], ph[2], ph[3]);
      if (turn < 2) bar_arrive(NB_TOK + turn, 256);
      if (wg == 0) bar_sync(NB_DN, 256);
      numer(1);
      wg_wait<1>();
      fence_regs(ac[0]); fence_regs(ac[1]);
      finish(0);
      wg_wait<0>();
      fence_regs(ac[2]); fence_regs(ac[3]);
      #pragma unroll
      for (int i = 0; i < 32; i++) asm volatile("mov.b32 %0, 0;" : "=f"(p[i >> 4][i & 15]));
      if (e == 2) project_r(3);
      finish(1);
      if (!half) fence_async_smem();
      __syncwarp();
      if (lane == 0) mbar_arrive(sb + B_UO + 8 * e);
      wg_wait<0>();
    }
    if (isq) cluster_arrive();
  }

  {
  int lane;
  asm volatile("mov.u32 %0, %%laneid;" : "=r"(lane));
  const int g = lane >> 2, q = lane & 3;
  if (wg < 2) {
    float h[64];
    {
      #pragma unroll
      for (int i = 0; i < 32; i++) { h[2*i] = bf_lo(xr[i]); h[2*i+1] = bf_hi(xr[i]); }
      fence_regs(h);
      const uint32_t emptyb = mapa(sb + B_EMPTY5, t & 1);
      uint32_t s = 1 + rank, ps = 0;
      mbar_wait2(sb + B_GB + 8 * rank, 0, sb + B_UO + 8 * wg, 0);
      #pragma unroll
      for (int i = 0; i < 16; i++) {
        const uint32_t da = dlo(SB0, 16) + s * 2048 + wg * 512, db = dlo(SB0 + 16384, 8192) + s * 2048;
        wg_fence();
        #pragma unroll
        for (int k = 0; k < 4; k++) wgmma_sa_n128<0, 1, H128, H128>(h, da + k * 2, db + k * 128);
        wg_commit();
        const uint32_t ns = i ? (i + 2) % 6 : 2 - rank;
        const uint32_t nb = i ? i + 1 : 1 - rank, b0 = sb + B_GB + 8 * nb, b1 = sb + B_GA + 16 * nb + 8 * wg;
        const bool here = i == 15 || mbar_test2(b0, 0, b1, 0);
        wg_wait<1>();
        if (!(((2 * REL + 1) >> i) & 1) && i < 14 && t < 2) mbar_arrive_remote(emptyb + 8 * ps, 1);
        if ((REL >> i) & 1) { wg_wait<0>(); if (t < 2) mbar_arrive_remote(emptyb + 8 * s, 1); }
        if (!here) mbar_wait2(b0, 0, b1, 0);
        ps = s; s = ns;
      }
    }
    cluster_arrive();
    float2 wr[16];
    #pragma unroll
    for (int i = 0; i < 16; i++) wr[i] = lds64f(sb + OFF_WR + 32 * i + 8 * q);
    const int r0 = 64 * wg + 16 * wp + g;
    float sum0, sum1, dot0, dot1, sq0, sq1;
    uint32_t redo = 0;
    asm volatile("" : "+r"(redo));
    #pragma unroll 1
    for (;;) {
    if (redo) {
      wg_wait<0>();
      const uint32_t* xp = reinterpret_cast<const uint32_t*>(P.x + (size_t)(128 * m128 + r0) * DM + 128 * j) + q;
      #pragma unroll
      for (int i = 0; i < 32; i++) { const uint32_t v = xp[4 * (i >> 1) + (i & 1) * 4 * DM]; h[2*i] = bf_lo(v); h[2*i+1] = bf_hi(v); }
      #pragma unroll 1
      for (int ks = 0; ks < 64; ks++) {
        const int kb = ks >> 2, kk = 16 * (ks & 3);
        const bf16* op = G->o + (m128 * 16 + kb) * 8192 + r0 * 64 + 2 * q;
        const int o0 = ((kk >> 3) ^ g) << 3;
        const uint32_t* w = reinterpret_cast<const uint32_t*>(P.wo_p + (size_t)(((kb & 1) ? 256 * (kb >> 2) + 32 * (kb & 2) + 32 + 4 * (kk & 32) : 64 * kb + 2 * (kk & 32)) +
                                                                              ((kk & 16) >> 2) + 4 * (g & 6) + (g & 1)) * DM + 128 * j) + q;
        uint32_t b[32], a0, a1, a2, a3, it = 0;
        #pragma unroll
        for (int n = 0; n < 32; n++) b[n] = w[4 * (n >> 1) + (n & 1) * DM];
        do { a0 = ld32_rlx(op + o0); a1 = ld32_rlx(op + 512 + o0); a2 = ld32_rlx(op + (o0 ^ 8)); a3 = ld32_rlx(op + 512 + (o0 ^ 8)); }
        while (max(max(a0, a1), max(a2, a3)) == ~0u && ++it < POLL_LIMIT);
        __syncwarp();
        #pragma unroll
        for (int n = 0; n < 16; n++) mma16816(h[4*n], h[4*n+1], h[4*n+2], h[4*n+3], a0, a1, a2, a3, transpose8(b[2*n]), transpose8(b[2*n+1]));
      }
    }
    wg_wait<0>();
    fence_regs(h);
    sum0 = 0.f, sum1 = 0.f, dot0 = 0.f, dot1 = 0.f, sq0 = 0.f, sq1 = 0.f;
    #pragma unroll
    for (int i = 0; i < 16; i++) {
      sum0 += h[4*i] + h[4*i+1]; sum1 += h[4*i+2] + h[4*i+3];
      sq0 = fmaf(h[4*i], h[4*i], fmaf(h[4*i+1], h[4*i+1], sq0)); sq1 = fmaf(h[4*i+2], h[4*i+2], fmaf(h[4*i+3], h[4*i+3], sq1));
      dot0 = fmaf(h[4*i], wr[i].x, fmaf(h[4*i+1], wr[i].y, dot0)); dot1 = fmaf(h[4*i+2], wr[i].x, fmaf(h[4*i+3], wr[i].y, dot1));
    }
    if (!__any_sync(~0u, !redo & (h[0] != h[0] | h[2] != h[2]))) break;
    redo = 1;
    }
    float4* const rs = &G->rstat[128 * m128 + r0];
    {
      const bool up = q & 2;
      float a = up ? sum1 : sum0, b = up ? sq1 : sq0, d = up ? dot1 : dot0;
      a += __shfl_xor_sync(~0u, up ? sum0 : sum1, 2); b += __shfl_xor_sync(~0u, up ? sq0 : sq1, 2); d += __shfl_xor_sync(~0u, up ? dot0 : dot1, 2);
      a += __shfl_xor_sync(~0u, a, 1); b += __shfl_xor_sync(~0u, b, 1); d += __shfl_xor_sync(~0u, d, 1);
      if ((q & 1) == 0) red_add_f32x4(rs + 4 * q, a, b, d, 1.f);
    }
    float rstd[2], bm[2];
    uint32_t best, it = 0;
    {
      const float2 swa = lds64f(sb + OFF_SUMWR), swb = lds64f(sb + OFF_SUMWR + 8);
      const float sw = (swa.x + swa.y) + (swb.x + swb.y);
      uint4 a[2]; uint32_t key[2];
      do { a[0] = ld128_rlx(rs); a[1] = ld128_rlx(rs + 8); } while (__any_sync(~0u, (a[0].w & a[1].w) != 0x41000000u) && ++it < POLL_LIMIT);
      #pragma unroll
      for (int i = 0; i < 2; i++) {
        const float mean = __uint_as_float(a[i].x) * (1.f / DM);
        rstd[i] = rsqrtf(fmaxf(__uint_as_float(a[i].y) * (1.f / DM) - mean * mean, 0.f) + 1e-5f);
        bm[i] = -mean * rstd[i];
        const uint32_t rr = __float_as_uint(fmaf(__uint_as_float(a[i].z), rstd[i], sw * bm[i]));
        key[i] = ((rr ^ ((uint32_t)((int32_t)rr >> 31) | 0x80000000u)) & ~2047u) | (2047 - 128 * m128 - r0 - 8 * i);
      }
      asm volatile("redux.sync.max.u32 %0, %1, 0xffffffff;" : "=r"(best) : "r"(max(key[0], key[1])));
    }
    sts32(sb + OFF_BEST + 4 * warp, best);
    bar_sync(NB_WG01, 256);
    {
      const uint4 b0 = lds128(sb + OFF_BEST), b1 = lds128(sb + OFF_BEST + 16);
      best = max(max(max(b0.x, b0.y), max(b0.z, b0.w)), max(max(b1.x, b1.y), max(b1.z, b1.w)));
    }
    const int win = ~best & 127;
    if (warp == ((win >> 4) ^ 1) && (lane < 4 || it == 0)) st128_rlx(&G->key[((2 * j + (lane >> 1)) & 15) * 128 + 8 * m128 + 4 * (lane & 1)], best, best, best, best);
    if ((win & 0x77) == r0) {
      const bool up = win & 8;
      const float ra = up ? rstd[1] : rstd[0], rb = up ? bm[1] : bm[0];
      uint32_t x[16];
      #pragma unroll
      for (int i = 0; i < 16; i++) x[i] = pack_bf16(fmaf(up ? h[4*i+2] : h[4*i], ra, rb), fmaf(up ? h[4*i+3] : h[4*i+1], ra, rb));
      #pragma unroll
      for (int i = 0; i < 4; i++) st128_rlx(&G->cand[m128 * 512 + 64 * j + 16 * i + 4 * q], x[4*i], x[4*i+1], x[4*i+2], x[4*i+3]);
    }
    __syncwarp();
    bar_arrive(NB_G2E, 384);
    {
      const float a0 = 1.f + rstd[0], b0 = bm[0], a1 = 1.f + rstd[1], b1 = bm[1];
      #pragma unroll
      for (int k = 0; k < 8; k++)
        stsm4(((sb + OFF_OUT + wg * 8192 + sa) ^ ((k & 3) << 5)) + (k >> 2) * 16384,
              pack_bf16(fmaf(h[8*k], a0, b0), fmaf(h[8*k+1], a0, b0)),     pack_bf16(fmaf(h[8*k+2], a1, b1), fmaf(h[8*k+3], a1, b1)),
              pack_bf16(fmaf(h[8*k+4], a0, b0), fmaf(h[8*k+5], a0, b0)),   pack_bf16(fmaf(h[8*k+6], a1, b1), fmaf(h[8*k+7], a1, b1)));
      fence_async_smem();
      __syncwarp();
      if (lane == 0) mbar_arrive(sb + B_OUT + 8 * wg);
    }
    {
      uint32_t wa[8][4][4];
      const uint32_t wb = sb + 16384 * (((uint32_t)FF_SLOT >> (4 * warp)) & 15) + ((lane & 7) + ((lane >> 4) << 3)) * 64 + ((((lane >> 3) & 1) ^ ((lane >> 1) & 3)) << 4);
      if (f < NFFN) mbar_wait(sb + B_F + 8 * warp, 0);
      #pragma unroll
      for (int i = 0; i < 32; i++) ldsm4t((wb ^ ((i & 1) << 5)) + ((i >> 1) & 1) * 8192 + (i >> 2) * 1024, wa[i >> 2][i & 3][0], wa[i >> 2][i & 3][1], wa[i >> 2][i & 3][2], wa[i >> 2][i & 3][3]);
      bar_sync(NB_XS, 384);
      uint4 xs[4];
      #pragma unroll
      for (int i = 0; i < 4; i++) xs[i] = lds128(sb + OFF_XSEL + 256 * warp + 64 * i + 16 * q);
      float d[4][4];
      #pragma unroll
      for (int ks = 0; ks < 8; ks++) {
        #pragma unroll
        for (int m = 0; m < 4; m++) {
          if (ks == 0) { d[m][0] = 0.f; d[m][1] = 0.f; d[m][2] = 0.f; d[m][3] = 0.f; }
          mma16816(d[m][0], d[m][1], d[m][2], d[m][3], wa[ks][m][0], wa[ks][m][1], wa[ks][m][2], wa[ks][m][3],
                   (ks & 1) ? xs[ks >> 1].z : xs[ks >> 1].x, (ks & 1) ? xs[ks >> 1].w : xs[ks >> 1].y);
        }
      }
      if (q == 0) {
        #pragma unroll
        for (int m = 0; m < 8; m++) stsf(sb + OFF_GU + (8 * m + g) * 48 + 4 * warp, d[m >> 1][2 * (m & 1)]);
      }
      bar_arrive(NB_ACT, 384);
    }
    {
      const uint32_t ky = __float_as_uint(ldsf(sb + OFF_KEY));
      const int row = 2047 - (ky & 2047) - 128 * m128;
      if ((uint32_t)row < 128u) {
        const int l = tid >> 3, vi = (j & 1) + ((lane >> 2) & 1), e = 3 * vi + q - 4 * (j & 1);
        const float kr = __uint_as_float((ky & ~2047u) ^ ((ky >> 31) ? 0x80000000u : 0xfffff800u));
        const int col = 32 * (l & 3) + 16 * (e & 1) + 4 * (e & 2) + (l >> 2);
        const float sg = rcp(1.f + ex2(-LOG2E * kr));
        const uint32_t base = __float_as_uint(ldsf(sb + OFF_OUT + (col >> 6) * 16384 + row * 128 + ((((col >> 3) ^ row) & 7) << 4) + 2 * (col & 6)));
        const float4* yp = &G->yacc[(q * 3 + vi) * 128 + 32 * (j >> 1) + l];
        uint32_t it = 0;
        uint4 v;
        mbar_wait(sb + B_SD, 0);
        do { v = ld128_rlx(yp); } while (__any_sync(~0u, __uint_as_float(v.w) != (float)(NFFN / 4)) && ++it < POLL_LIMIT);
        float y0 = __uint_as_float(v.x), y1 = __uint_as_float(v.y), y2 = __uint_as_float(v.z);
        #pragma unroll
        for (int o = 1; o < 4; o <<= 1) { y0 += __shfl_xor_sync(~0u, y0, o); y1 += __shfl_xor_sync(~0u, y1, o); y2 += __shfl_xor_sync(~0u, y2, o); }
        if (q < 3 && (uint32_t)e < 4u)
          P.out_p[(size_t)(128 * m128 + row) * DM + 128 * j + col] = __float2bfloat16(fmaf(q == 0 ? y0 : q == 1 ? y1 : y2, sg, (col & 1) ? bf_hi(base) : bf_lo(base)));
      }
      if (c == 0 && tid == 0) st32_rlx(&G->epoch, __float_as_uint(ldsf(sb + OFF_EP)));
    }
  }
  if (wg == 2) {
    uint32_t wf[16][2][4];
    {
      const uint32_t wb = sb + OFF_S + 16384 * (wp & 1) + ((lane & 7) + ((lane >> 4) << 3)) * 128 + ((((lane >> 3) & 1) ^ (lane & 7)) << 4);
      if (f < NFFN) mbar_wait(sb + B_WD + 8 * wp, 0);
      #pragma unroll
      for (int i = 0; i < 32; i++) ldsm4t((wb ^ (((i >> 1) & 3) << 5)) + (i >> 3) * 4096 + (i & 1) * 2048, wf[i >> 1][i & 1][0], wf[i >> 1][i & 1][1], wf[i >> 1][i & 1][2], wf[i >> 1][i & 1][3]);
      fence_async_smem();
      __syncwarp();
      if (lane == 0) mbar_arrive(sb + B_WC + 8 * wp);
    }
    bar_sync(NB_G2E, 384);
    {
      uint32_t cur = 0;
      uint4 v;
      #pragma unroll 1
      for (uint32_t it = 0; it < POLL_LIMIT; it++) {
        const uint32_t kx = ld32_rlx(&G->key[(c & 15) * 128 + 8 * (lane & 15)]);
        v = ld128_rlx(&G->cand[((~cur >> 7) & 15) * 512 + 4 * t]);
        uint32_t best;
        asm volatile("redux.sync.max.u32 %0, %1, 0xffffffff;" : "=r"(best) : "r"(kx));
        if (!__any_sync(~0u, kx == 0 || v.w == ~0u) && best == cur) break;
        cur = best;
      }
      sts128(sb + OFF_XSEL + 16 * t, v.x, v.y, v.z, v.w);
      sts32(sb + OFF_KEY, cur);
      bar_arrive(NB_XS, 384);
      bar_sync(NB_ACT, 384);
    }
    float gu[2];
    #pragma unroll
    for (int i = 0; i < 2; i++) {
      const uint4 v0 = lds128(sb + OFF_GU + (32 * i + lane) * 48), v1 = lds128(sb + OFF_GU + (32 * i + lane) * 48 + 16);
      gu[i] = ((__uint_as_float(v0.x) + __uint_as_float(v0.y)) + (__uint_as_float(v0.z) + __uint_as_float(v0.w))) +
              ((__uint_as_float(v1.x) + __uint_as_float(v1.y)) + (__uint_as_float(v1.z) + __uint_as_float(v1.w)));
    }
    const float act = gu[0] * gu[1] * rcp(1.f + ex2(-LOG2E * gu[0]));
    const uint32_t ap = pack_bf16(act, __shfl_down_sync(~0u, act, 1));
    uint32_t bf[4];
    #pragma unroll
    for (int i = 0; i < 4; i++) bf[i] = __shfl_sync(~0u, ap, 2 * q + 8 * i);
    float d[16][4];
    #pragma unroll
    for (int k = 0; k < 2; k++)
      #pragma unroll
      for (int i = 0; i < 16; i++) {
        if (k == 0) { d[i][0] = 0.f; d[i][1] = 0.f; d[i][2] = 0.f; d[i][3] = 0.f; }
        mma16816(d[i][0], d[i][1], d[i][2], d[i][3], wf[i][k][0], wf[i][k][1], wf[i][k][2], wf[i][k][3], bf[2*k], bf[2*k+1]);
      }
    float y[9];
    #pragma unroll
    for (int e = 0; e < 8; e++) {
      const int n = 2 * (e & 4) + (e & 1);
      const float lo = (q & 1) ? d[n + 2][e & 2] : d[n][e & 2], hi = (q & 1) ? d[n + 6][e & 2] : d[n + 4][e & 2];
      y[e] = (q & 2) ? hi : lo;
    }
    y[8] = 0.f;
    if (f < NFFN) {
      #pragma unroll
      for (int i = 0; i < 3; i++) red_add_f32x4(&G->yacc[((f & 3) * 3 + i) * 128 + t], y[3*i], y[3*i+1], y[3*i+2], 1.f);
    }
  }
  }
  cluster_wait();
}

typedef CUresult (*EncodeFn)(CUtensorMap*, CUtensorMapDataType, cuuint32_t, void*, const cuuint64_t*, const cuuint64_t*,
                             const cuuint32_t*, const cuuint32_t*, CUtensorMapInterleave, CUtensorMapSwizzle,
                             CUtensorMapL2promotion, CUtensorMapFloatOOBfill);

void make_map(EncodeFn enc, CUtensorMap* m, const void* p, int n, const cuuint64_t* dims, const cuuint64_t* str, const cuuint32_t* box,
              CUtensorMapSwizzle sw, CUtensorMapL2promotion promo) {
  cuuint32_t es[5] = {1, 1, 1, 1, 1};
  enc(m, CU_TENSOR_MAP_DATA_TYPE_BFLOAT16, n, const_cast<void*>(p), dims, str, box, es, CU_TENSOR_MAP_INTERLEAVE_NONE, sw, promo,
      CU_TENSOR_MAP_FLOAT_OOB_FILL_NONE);
}
void map2(EncodeFn enc, CUtensorMap* m, const void* p, uint64_t cols, uint64_t rows, uint32_t bc, uint32_t br, CUtensorMapSwizzle sw,
          CUtensorMapL2promotion promo) {
  const cuuint64_t dims[2] = {cols, rows}, str[1] = {cols * 2};
  const cuuint32_t box[2] = {bc, br};
  make_map(enc, m, p, 2, dims, str, box, sw, promo);
}
void map3(EncodeFn enc, CUtensorMap* m, const void* p, uint64_t cols, uint64_t rows, uint32_t br, uint32_t nb) {
  const cuuint64_t dims[3] = {64, rows, cols / 64}, str[2] = {cols * 2, 128};
  const cuuint32_t box[3] = {64, br, nb};
  make_map(enc, m, p, 3, dims, str, box, CU_TENSOR_MAP_SWIZZLE_128B, CU_TENSOR_MAP_L2_PROMOTION_L2_128B);
}

}

extern "C" void kernel_launch(void* const* d_in, const int* in_sizes, int n_in, void* d_out, int out_size) {
  (void)in_sizes; (void)n_in; (void)out_size;
  static EncodeFn enc = nullptr;
  static void* o_ptr = nullptr;
  if (!enc) {
    void* f = nullptr; cudaDriverEntryPointQueryResult qr;
    cudaGetDriverEntryPoint("cuTensorMapEncodeTiled", &f, cudaEnableDefault, &qr);
    enc = (EncodeFn)f;
    cudaGetSymbolAddress(&o_ptr, g_scr);
    cudaFuncSetAttribute(fused_kernel, cudaFuncAttributeMaxDynamicSharedMemorySize, SMEM_BYTES);
  }
  const bf16* x = (const bf16*)d_in[0];
  const bf16* wqkv = (const bf16*)d_in[1];
  const bf16* wphi = (const bf16*)d_in[2];
  const bf16* wo = (const bf16*)d_in[3];
  const bf16* wr = (const bf16*)d_in[5];
  const bf16* wgate = (const bf16*)d_in[6];
  const bf16* wup = (const bf16*)d_in[7];
  const bf16* wdown = (const bf16*)d_in[8];
  Params P;
  const CUtensorMapSwizzle S128 = CU_TENSOR_MAP_SWIZZLE_128B, S64 = CU_TENSOR_MAP_SWIZZLE_64B;
  const CUtensorMapL2promotion L128 = CU_TENSOR_MAP_L2_PROMOTION_L2_128B, L256 = CU_TENSOR_MAP_L2_PROMOTION_L2_256B,
                               L64 = CU_TENSOR_MAP_L2_PROMOTION_L2_64B;
  map2(enc, &P.x128, x, DM, SEQ, 64, 128, S128, L128);
  map2(enc, &P.x64, x, DM, SEQ, 64, 64, S128, L128);
  {
    const cuuint64_t dims[4] = {64, DM, 16, 3}, str[3] = {6 * DM, 128, 2 * DM};
    const cuuint32_t box[4] = {64, 64, 1, 2};
    make_map(enc, &P.wkv, wqkv, 4, dims, str, box, S128, L128);
  }
  map3(enc, &P.wq, wqkv, 3 * DM, DM, 64, 2);
  for (int i = 0; i < 2; i++) {
    const cuuint64_t dims[5] = {DM, (cuuint64_t)(DM - 94 - 64 * i), 4, 4, 2}, str[4] = {2 * DM, 16 * DM, 4 * DM, (cuuint64_t)(128 * DM) << i};
    const cuuint32_t box[5] = {64, 2, 4, 4, 2};
    make_map(enc, &P.wo[i], wo, 5, dims, str, box, S128, L128);
  }
  map3(enc, &P.wd, wdown, DM, FF, 32, 4);
  map2(enc, &P.wg, wgate, FF, DM, 32, 128, S64, L64);
  map2(enc, &P.wu, wup, FF, DM, 32, 128, S64, L64);
  map2(enc, &P.tg, wgate, FF, DM, 8, 16, CU_TENSOR_MAP_SWIZZLE_NONE, L128);
  map2(enc, &P.tu, wup, FF, DM, 8, 16, CU_TENSOR_MAP_SWIZZLE_NONE, L128);
  map2(enc, &P.td, wdown, 128, FF * 8, 8, 16, CU_TENSOR_MAP_SWIZZLE_NONE, L256);
  map2(enc, &P.xs, x, DM, SEQ, 128, 16, CU_TENSOR_MAP_SWIZZLE_NONE, L256);
  map2(enc, &P.ws, wqkv, 3 * DM, DM, 16, 128, CU_TENSOR_MAP_SWIZZLE_NONE, L128);
  map2(enc, &P.qs, wqkv, 3 * DM, DM, 32, 128, CU_TENSOR_MAP_SWIZZLE_NONE, L64);
  map2(enc, &P.out, d_out, DM, SEQ, 64, 16, S128, L128);
  map2(enc, &P.o, o_ptr, 256, SEQ * DM / 256, 256, 16, CU_TENSOR_MAP_SWIZZLE_NONE, L128);
  map2(enc, &P.phi, wphi, 32, 1024, 32, 32, S64, L64);
  P.x = x; P.wqkv = wqkv; P.wo_p = wo; P.wr = wr; P.out_p = (bf16*)d_out; P.g = (Scratch*)o_ptr; P.zero = 0;

  cudaLaunchConfig_t cfg = {};
  cfg.gridDim = dim3(128); cfg.blockDim = dim3(512); cfg.dynamicSmemBytes = SMEM_BYTES; cfg.stream = cudaStreamPerThread;
  cudaLaunchAttribute at[1];
  at[0].id = cudaLaunchAttributeClusterDimension; at[0].val.clusterDim.x = 2; at[0].val.clusterDim.y = 1; at[0].val.clusterDim.z = 1;
  cfg.attrs = at; cfg.numAttrs = 1;
  cudaLaunchKernelEx(&cfg, fused_kernel, P);
}
```

```cpp
#include <cuda_runtime.h>
#include <cuda.h>
#include <cuda_bf16.h>
#include <stdint.h>

namespace {

typedef __nv_bfloat16 bf16;

__device__ __forceinline__ uint32_t smem_u32(const void* p){ return (uint32_t)__cvta_generic_to_shared(p); }
__device__ __forceinline__ void mbar_init(uint32_t bar, uint32_t cnt){ asm volatile("mbarrier.init.shared::cta.b64 [%0], %1;"::"r"(bar),"r"(cnt):"memory"); }
__device__ __forceinline__ void mbar_expect_tx(uint32_t bar, uint32_t bytes){ asm volatile("mbarrier.arrive.expect_tx.shared::cta.b64 _, [%0], %1;"::"r"(bar),"r"(bytes):"memory"); }
__device__ __forceinline__ void mbar_arrive(uint32_t bar){ asm volatile("mbarrier.arrive.shared::cta.b64 _, [%0];"::"r"(bar):"memory"); }
__device__ __forceinline__ uint32_t mapa(uint32_t addr, uint32_t cta){ uint32_t r; asm volatile("mapa.shared::cluster.u32 %0, %1, %2;":"=r"(r):"r"(addr),"r"(cta)); return r; }
__device__ __forceinline__ void mbar_arrive_at(uint32_t bar, uint32_t cta, uint32_t cnt){
  asm volatile("{\n.reg .b32 ra;\nmapa.shared::cluster.u32 ra, %0, %1;\nmbarrier.arrive.shared::cluster.b64 _, [ra], %2;\n}\n"::"r"(bar),"r"(cta),"r"(cnt):"memory"); }
__device__ __forceinline__ void mbar_arrive_remote(uint32_t cluster_addr, uint32_t cnt){
  asm volatile("mbarrier.arrive.shared::cluster.b64 _, [%0], %1;"::"r"(cluster_addr),"r"(cnt):"memory"); }
__device__ __forceinline__ void mbar_wait(uint32_t bar, uint32_t parity){
  asm volatile("{\n.reg .pred p;\n.reg .u32 c;\nmov.u32 c, 0;\nLW:\nmbarrier.try_wait.parity.shared::cta.b64 p, [%0], %1;\n@p bra LD;\nadd.u32 c, c, 1;\nsetp.lt.u32 p, c, 2000000;\n@p bra LW;\ntrap;\nLD:\n}\n"::"r"(bar),"r"(parity):"memory"); }
__device__ __forceinline__ void mbar_wait2(uint32_t bar0, uint32_t par0, uint32_t bar1, uint32_t par1){
  asm volatile("{\n.reg .pred p, q;\n.reg .u32 c;\nmov.u32 c, 0;\nLW:\nmbarrier.try_wait.parity.shared::cta.b64 p, [%0], %1;\nmbarrier.try_wait.parity.shared::cta.b64 q, [%2], %3;\nand.pred p, p, q;\n@p bra LD;\nadd.u32 c, c, 1;\nsetp.lt.u32 p, c, 2000000;\n@p bra LW;\ntrap;\nLD:\n}\n"::"r"(bar0),"r"(par0),"r"(bar1),"r"(par1):"memory"); }
__device__ __forceinline__ bool mbar_test2(uint32_t bar0, uint32_t par0, uint32_t bar1, uint32_t par1){
  uint32_t r;
  asm volatile("{\n.reg .pred p, q;\nmbarrier.test_wait.parity.shared::cta.b64 p, [%1], %2;\nmbarrier.test_wait.parity.shared::cta.b64 q, [%3], %4;\nand.pred p, p, q;\nselp.u32 %0, 1, 0, p;\n}\n":"=r"(r):"r"(bar0),"r"(par0),"r"(bar1),"r"(par1):"memory");
  return r; }
__device__ __forceinline__ void tma_2d(uint32_t dst, const CUtensorMap* m, int c0, int c1, uint32_t bar){
  asm volatile("cp.async.bulk.tensor.2d.shared::cluster.global.mbarrier::complete_tx::bytes [%0], [%1, {%3, %4}], [%2];"::"r"(dst),"l"(m),"r"(bar),"r"(c0),"r"(c1):"memory"); }
__device__ __forceinline__ void tma_2d_h(uint32_t dst, const CUtensorMap* m, int c0, int c1, uint32_t bar, uint64_t pol){
  asm volatile("cp.async.bulk.tensor.2d.shared::cluster.global.mbarrier::complete_tx::bytes.L2::cache_hint [%0], [%1, {%3, %4}], [%2], %5;"::"r"(dst),"l"(m),"r"(bar),"r"(c0),"r"(c1),"l"(pol):"memory"); }
__device__ __forceinline__ void tma_2d_mc(uint32_t dst, const CUtensorMap* m, int c0, int c1, uint32_t bar){
  asm volatile("cp.async.bulk.tensor.2d.shared::cluster.global.mbarrier::complete_tx::bytes.multicast::cluster [%0], [%1, {%3, %4}], [%2], %5;"::"r"(dst),"l"(m),"r"(bar),"r"(c0),"r"(c1),"h"((uint16_t)3):"memory"); }
__device__ __forceinline__ void tma_2d_mc_h(uint32_t dst, const CUtensorMap* m, int c0, int c1, uint32_t bar, uint64_t pol){
  asm volatile("cp.async.bulk.tensor.2d.shared::cluster.global.mbarrier::complete_tx::bytes.multicast::cluster.L2::cache_hint [%0], [%1, {%3, %4}], [%2], %5, %6;"::"r"(dst),"l"(m),"r"(bar),"r"(c0),"r"(c1),"h"((uint16_t)3),"l"(pol):"memory"); }
__device__ __forceinline__ void tma_4d(uint32_t dst, const CUtensorMap* m, int c0, int c1, int c2, int c3, uint32_t bar){
  asm volatile("cp.async.bulk.tensor.4d.shared::cluster.global.mbarrier::complete_tx::bytes [%0], [%1, {%3, %4, %5, %6}], [%2];"::"r"(dst),"l"(m),"r"(bar),"r"(c0),"r"(c1),"r"(c2),"r"(c3):"memory"); }
__device__ __forceinline__ uint64_t policy_evict_first(){ uint64_t p; asm volatile("createpolicy.fractional.L2::evict_first.b64 %0, 1.0;":"=l"(p)); return p; }
__device__ __forceinline__ uint64_t policy_evict_normal(){ uint64_t p; asm("createpolicy.fractional.L2::evict_normal.b64 %0, 1.0;":"=l"(p)); return p; }
__device__ __forceinline__ void tma_3d_h(uint32_t dst, const CUtensorMap* m, int c0, int c1, int c2, uint32_t bar, uint64_t pol){
  asm volatile("cp.async.bulk.tensor.3d.shared::cluster.global.mbarrier::complete_tx::bytes.L2::cache_hint [%0], [%1, {%3, %4, %5}], [%2], %6;"::"r"(dst),"l"(m),"r"(bar),"r"(c0),"r"(c1),"r"(c2),"l"(pol):"memory"); }
__device__ __forceinline__ void tma_4d_h(uint32_t dst, const CUtensorMap* m, int c0, int c1, int c2, int c3, uint32_t bar, uint64_t pol){
  asm volatile("cp.async.bulk.tensor.4d.shared::cluster.global.mbarrier::complete_tx::bytes.L2::cache_hint [%0], [%1, {%3, %4, %5, %6}], [%2], %7;"::"r"(dst),"l"(m),"r"(bar),"r"(c0),"r"(c1),"r"(c2),"r"(c3),"l"(pol):"memory"); }
__device__ __forceinline__ void red_add_f32x4(float4* p, float x, float y, float z, float w){ asm volatile("red.relaxed.gpu.global.add.v4.f32 [%0], {%1,%2,%3,%4};"::"l"(p),"f"(x),"f"(y),"f"(z),"f"(w):"memory"); }
__device__ __forceinline__ void tma_5d_h(uint32_t dst, const CUtensorMap* m, int c0, int c1, uint32_t bar, uint64_t pol){
  asm volatile("cp.async.bulk.tensor.5d.shared::cluster.global.mbarrier::complete_tx::bytes.L2::cache_hint [%0], [%1, {%3, %4, 0, 0, 0}], [%2], %5;"::"r"(dst),"l"(m),"r"(bar),"r"(c0),"r"(c1),"l"(pol):"memory"); }
__device__ __forceinline__ void tma_store_2d(const CUtensorMap* m, int c0, int c1, uint32_t src, uint64_t pol){
  asm volatile("cp.async.bulk.tensor.2d.global.shared::cta.bulk_group.L2::cache_hint [%0, {%2, %3}], [%1], %4;"::"l"(m),"r"(src),"r"(c0),"r"(c1),"l"(pol):"memory"); }
__device__ __forceinline__ void bulk_commit(){ asm volatile("cp.async.bulk.commit_group;":::"memory"); }
__device__ __forceinline__ void bulk_wait_all(){ asm volatile("cp.async.bulk.wait_group 0;":::"memory"); }
__device__ __forceinline__ void fence_async_global(){ asm volatile("fence.proxy.async.global;":::"memory"); }
__device__ __forceinline__ bool elect_one(){ uint32_t p; asm volatile("{\n.reg .pred P;\nelect.sync _|P, 0xffffffff;\nselp.b32 %0, 1, 0, P;\n}\n":"=r"(p)); return p; }
__device__ __forceinline__ void bulk_prefetch(const void* p, uint32_t bytes){
  asm volatile("cp.async.bulk.prefetch.L2.global [%0], %1;"::"l"(p),"r"(bytes):"memory"); }
__device__ __forceinline__ void bulk_s2peer(uint32_t dst_cluster, uint32_t src, uint32_t bytes, uint32_t bar_cluster){
  asm volatile("cp.async.bulk.shared::cluster.shared::cta.mbarrier::complete_tx::bytes [%0], [%1], %2, [%3];"::"r"(dst_cluster),"r"(src),"r"(bytes),"r"(bar_cluster):"memory"); }
__device__ __forceinline__ void prefetch_map(const CUtensorMap* m){ asm volatile("prefetch.tensormap [%0];"::"l"(m):"memory"); }
__device__ __forceinline__ void fence_async_smem(){ asm volatile("fence.proxy.async.shared::cta;":::"memory"); }
__device__ __forceinline__ void fence_acquire_gpu(){ asm volatile("fence.acquire.gpu;":::"memory"); }
__device__ __forceinline__ void fence_gpu(){ asm volatile("fence.acq_rel.gpu;":::"memory"); }
__device__ __forceinline__ void wg_fence(){ asm volatile("wgmma.fence.sync.aligned;":::"memory"); }
__device__ __forceinline__ void wg_commit(){ asm volatile("wgmma.commit_group.sync.aligned;":::"memory"); }
template<int N> __device__ __forceinline__ void wg_wait(){ asm volatile("wgmma.wait_group.sync.aligned %0;"::"n"(N):"memory"); }
template<int N> __device__ __forceinline__ void fence_regs(float (&d)[N]){
  #pragma unroll
  for(int i=0;i<N;i++) asm volatile("":"+f"(d[i])::"memory"); }
__device__ __forceinline__ void bar_sync(int id, int n){ asm volatile("bar.sync %0, %1;"::"r"(id),"r"(n):"memory"); }
__device__ __forceinline__ void bar_arrive(int id, int n){ asm volatile("bar.arrive %0, %1;"::"r"(id),"r"(n):"memory"); }
__device__ __forceinline__ void cluster_arrive(){ asm volatile("barrier.cluster.arrive.relaxed.aligned;":::"memory"); }
__device__ __forceinline__ void cluster_wait(){ asm volatile("barrier.cluster.wait.aligned;":::"memory"); }
__host__ __device__ constexpr uint32_t dlo(uint32_t addr, uint32_t lbo){ return (addr >> 4) | ((lbo >> 4) << 16); }
__host__ __device__ constexpr uint32_t dhi(uint32_t sbo, uint32_t sw){ return (sbo >> 4) | (sw << 30); }
constexpr uint32_t H128 = dhi(1024, 1), H64 = dhi(512, 2), H0 = dhi(128, 0);
__device__ __forceinline__ uint32_t pack_bf16(float lo, float hi){ uint32_t r; asm("cvt.rn.bf16x2.f32 %0, %1, %2;":"=r"(r):"f"(hi),"f"(lo)); return r; }
__device__ __forceinline__ float bf_lo(uint32_t v){ return __uint_as_float(v<<16); }
__device__ __forceinline__ float bf_hi(uint32_t v){ return __uint_as_float(v&0xffff0000u); }
__device__ __forceinline__ float ex2(float x){ float r; asm("ex2.approx.ftz.f32 %0, %1;":"=f"(r):"f"(x)); return r; }
__device__ __forceinline__ float rcp(float x){ float r; asm("rcp.approx.ftz.f32 %0, %1;":"=f"(r):"f"(x)); return r; }
__device__ __forceinline__ void stsm4(uint32_t addr, uint32_t a, uint32_t b, uint32_t c, uint32_t d){
  asm volatile("stmatrix.sync.aligned.m8n8.x4.shared.b16 [%0], {%1,%2,%3,%4};"::"r"(addr),"r"(a),"r"(b),"r"(c),"r"(d)); }
__device__ __forceinline__ void stsm2(uint32_t addr, uint32_t a, uint32_t b){
  asm volatile("stmatrix.sync.aligned.m8n8.x2.shared.b16 [%0], {%1,%2};"::"r"(addr),"r"(a),"r"(b)); }
__device__ __forceinline__ void mma16816(float& d0, float& d1, float& d2, float& d3, uint32_t a0, uint32_t a1, uint32_t a2, uint32_t a3, uint32_t b0, uint32_t b1){
  asm volatile("mma.sync.aligned.m16n8k16.row.col.f32.bf16.bf16.f32 {%0,%1,%2,%3}, {%4,%5,%6,%7}, {%8,%9}, {%0,%1,%2,%3};"
               : "+f"(d0), "+f"(d1), "+f"(d2), "+f"(d3) : "r"(a0), "r"(a1), "r"(a2), "r"(a3), "r"(b0), "r"(b1)); }
__device__ __forceinline__ uint32_t transpose8(uint32_t a){ uint32_t r; asm volatile("movmatrix.sync.aligned.m8n8.trans.b16 %0, %1;":"=r"(r):"r"(a)); return r; }
__device__ __forceinline__ void ldsm4(uint32_t addr, uint32_t& a, uint32_t& b, uint32_t& c, uint32_t& d){
  asm volatile("ldmatrix.sync.aligned.m8n8.x4.shared.b16 {%0,%1,%2,%3}, [%4];":"=r"(a),"=r"(b),"=r"(c),"=r"(d):"r"(addr):"memory"); }
__device__ __forceinline__ void ldsm4t(uint32_t addr, uint32_t& a, uint32_t& b, uint32_t& c, uint32_t& d){
  asm volatile("ldmatrix.sync.aligned.m8n8.x4.trans.shared.b16 {%0,%1,%2,%3}, [%4];":"=r"(a),"=r"(b),"=r"(c),"=r"(d):"r"(addr):"memory"); }
__device__ __forceinline__ void sts32(uint32_t a, uint32_t v){ asm volatile("st.shared.b32 [%0], %1;"::"r"(a),"r"(v):"memory"); }
__device__ __forceinline__ void stsf(uint32_t a, float v){ asm volatile("st.shared.f32 [%0], %1;"::"r"(a),"f"(v):"memory"); }
__device__ __forceinline__ void sts64(uint32_t a, uint32_t x, uint32_t y){ asm volatile("st.shared.v2.b32 [%0], {%1,%2};"::"r"(a),"r"(x),"r"(y):"memory"); }
__device__ __forceinline__ void sts128(uint32_t a, uint32_t x, uint32_t y, uint32_t z, uint32_t w){ asm volatile("st.shared.v4.b32 [%0], {%1,%2,%3,%4};"::"r"(a),"r"(x),"r"(y),"r"(z),"r"(w):"memory"); }
__device__ __forceinline__ float ldsf(uint32_t a){ float v; asm volatile("ld.shared.f32 %0, [%1];":"=f"(v):"r"(a):"memory"); return v; }
__device__ __forceinline__ float2 lds64f(uint32_t a){ float2 v; asm volatile("ld.shared.v2.f32 {%0,%1}, [%2];":"=f"(v.x),"=f"(v.y):"r"(a):"memory"); return v; }
__device__ __forceinline__ uint4 lds128(uint32_t a){ uint4 v; asm volatile("ld.shared.v4.u32 {%0,%1,%2,%3}, [%4];":"=r"(v.x),"=r"(v.y),"=r"(v.z),"=r"(v.w):"r"(a):"memory"); return v; }
__device__ __forceinline__ uint4 ld128_keep(const void* p){ uint4 v; asm volatile("ld.global.v4.u32 {%0,%1,%2,%3}, [%4];":"=r"(v.x),"=r"(v.y),"=r"(v.z),"=r"(v.w):"l"(p):"memory"); return v; }
__device__ __forceinline__ uint4 ld128_rlx(const void* p){ uint4 v; asm volatile("ld.relaxed.gpu.global.v4.u32 {%0,%1,%2,%3}, [%4];":"=r"(v.x),"=r"(v.y),"=r"(v.z),"=r"(v.w):"l"(p):"memory"); return v; }
__device__ __forceinline__ uint32_t ld32_rlx(const void* p){ uint32_t v; asm volatile("ld.relaxed.gpu.global.u32 %0, [%1];":"=r"(v):"l"(p):"memory"); return v; }
__device__ __forceinline__ void st128_rlx(void* p, uint32_t x, uint32_t y, uint32_t z, uint32_t w){ asm volatile("st.relaxed.gpu.global.v4.u32 [%0], {%1,%2,%3,%4};"::"l"(p),"r"(x),"r"(y),"r"(z),"r"(w):"memory"); }
__device__ __forceinline__ void st64_rlx(void* p, uint32_t x, uint32_t y){ asm volatile("st.relaxed.gpu.global.v2.u32 [%0], {%1,%2};"::"l"(p),"r"(x),"r"(y):"memory"); }
__device__ __forceinline__ void st32_rlx(void* p, uint32_t x){ asm volatile("st.relaxed.gpu.global.u32 [%0], %1;"::"l"(p),"r"(x):"memory"); }
__device__ __forceinline__ void wait_until(uint32_t t){ while ((int32_t)((uint32_t)clock() - t) < 0) __nanosleep(32); }
__device__ __forceinline__ void flags_wait(uint32_t& missing, const uint32_t* p, uint32_t need){
  asm volatile("{\n.reg .pred p;\n.reg .u32 c, v;\nmov.u32 c, 0;\nLW:\nand.b32 v, %0, %2;\nsetp.eq.u32 p, v, 0;\n@p bra.uni LD;\nld.relaxed.gpu.global.u32 v, [%1];\nsetp.eq.u32 p, v, 0;\n"
               "vote.sync.ballot.b32 %0, p, 0xffffffff;\nadd.u32 c, c, 1;\nsetp.lt.u32 p, c, 4000000;\n@p bra.uni LW;\nLD:\n}\n":"+r"(missing):"l"(p),"r"(need):"memory"); }
__device__ __forceinline__ uint32_t tagw(float x, uint32_t t){ return (__float_as_uint(x) & ~3u) | t; }
__device__ __forceinline__ float untag(uint32_t w){ return __uint_as_float(w & ~3u); }

template<int TA, int TB, uint32_t HA, uint32_t HB> __device__ __forceinline__ void wgmma_ss_n128(float (&d)[64], uint32_t da, uint32_t db, int scale_d){
  asm volatile("{\n.reg .pred p;\n.reg .b64 a, b;\nsetp.ne.b32 p, %70, 0;\nmov.b64 a, {%64, %68};\nmov.b64 b, {%65, %69};\n"
  "wgmma.mma_async.sync.aligned.m64n128k16.f32.bf16.bf16 {%0, %1, %2, %3, %4, %5, %6, %7, %8, %9, %10, %11, %12, %13, %14, %15, %16, %17, %18, %19, %20, %21, %22, %23, %24, %25, %26, %27, %28, %29, %30, %31, %32, %33, %34, %35, %36, %37, %38, %39, %40, %41, %42, %43, %44, %45, %46, %47, %48, %49, %50, %51, %52, %53, %54, %55, %56, %57, %58, %59, %60, %61, %62, %63}, a, b, p, 1, 1, %66, %67;\n}\n"
  : "+f"(d[0]), "+f"(d[1]), "+f"(d[2]), "+f"(d[3]), "+f"(d[4]), "+f"(d[5]), "+f"(d[6]), "+f"(d[7]), "+f"(d[8]), "+f"(d[9]), "+f"(d[10]), "+f"(d[11]), "+f"(d[12]), "+f"(d[13]), "+f"(d[14]), "+f"(d[15]), "+f"(d[16]), "+f"(d[17]), "+f"(d[18]), "+f"(d[19]), "+f"(d[20]), "+f"(d[21]), "+f"(d[22]), "+f"(d[23]), "+f"(d[24]), "+f"(d[25]), "+f"(d[26]), "+f"(d[27]), "+f"(d[28]), "+f"(d[29]), "+f"(d[30]), "+f"(d[31]), "+f"(d[32]), "+f"(d[33]), "+f"(d[34]), "+f"(d[35]), "+f"(d[36]), "+f"(d[37]), "+f"(d[38]), "+f"(d[39]), "+f"(d[40]), "+f"(d[41]), "+f"(d[42]), "+f"(d[43]), "+f"(d[44]), "+f"(d[45]), "+f"(d[46]), "+f"(d[47]), "+f"(d[48]), "+f"(d[49]), "+f"(d[50]), "+f"(d[51]), "+f"(d[52]), "+f"(d[53]), "+f"(d[54]), "+f"(d[55]), "+f"(d[56]), "+f"(d[57]), "+f"(d[58]), "+f"(d[59]), "+f"(d[60]), "+f"(d[61]), "+f"(d[62]), "+f"(d[63])
  : "r"(da), "r"(db), "n"(TA), "n"(TB), "n"(HA), "n"(HB), "r"(scale_d));
}
template<int TA, int TB, uint32_t HA, uint32_t HB> __device__ __forceinline__ void wgmma_sa_n128(float (&d)[64], uint32_t da, uint32_t db){
  asm volatile("{\n.reg .pred p;\n.reg .b64 a, b;\nsetp.ne.b32 p, 1, 0;\nmov.b64 a, {%64, %68};\nmov.b64 b, {%65, %69};\n"
  "wgmma.mma_async.sync.aligned.m64n128k16.f32.bf16.bf16 {%0, %1, %2, %3, %4, %5, %6, %7, %8, %9, %10, %11, %12, %13, %14, %15, %16, %17, %18, %19, %20, %21, %22, %23, %24, %25, %26, %27, %28, %29, %30, %31, %32, %33, %34, %35, %36, %37, %38, %39, %40, %41, %42, %43, %44, %45, %46, %47, %48, %49, %50, %51, %52, %53, %54, %55, %56, %57, %58, %59, %60, %61, %62, %63}, a, b, p, 1, 1, %66, %67;\n}\n"
  : "+f"(d[0]), "+f"(d[1]), "+f"(d[2]), "+f"(d[3]), "+f"(d[4]), "+f"(d[5]), "+f"(d[6]), "+f"(d[7]), "+f"(d[8]), "+f"(d[9]), "+f"(d[10]), "+f"(d[11]), "+f"(d[12]), "+f"(d[13]), "+f"(d[14]), "+f"(d[15]), "+f"(d[16]), "+f"(d[17]), "+f"(d[18]), "+f"(d[19]), "+f"(d[20]), "+f"(d[21]), "+f"(d[22]), "+f"(d[23]), "+f"(d[24]), "+f"(d[25]), "+f"(d[26]), "+f"(d[27]), "+f"(d[28]), "+f"(d[29]), "+f"(d[30]), "+f"(d[31]), "+f"(d[32]), "+f"(d[33]), "+f"(d[34]), "+f"(d[35]), "+f"(d[36]), "+f"(d[37]), "+f"(d[38]), "+f"(d[39]), "+f"(d[40]), "+f"(d[41]), "+f"(d[42]), "+f"(d[43]), "+f"(d[44]), "+f"(d[45]), "+f"(d[46]), "+f"(d[47]), "+f"(d[48]), "+f"(d[49]), "+f"(d[50]), "+f"(d[51]), "+f"(d[52]), "+f"(d[53]), "+f"(d[54]), "+f"(d[55]), "+f"(d[56]), "+f"(d[57]), "+f"(d[58]), "+f"(d[59]), "+f"(d[60]), "+f"(d[61]), "+f"(d[62]), "+f"(d[63])
  : "r"(da), "r"(db), "n"(TA), "n"(TB), "n"(HA), "n"(HB));
}
template<int TA, int TB, uint32_t HA, uint32_t HB> __device__ __forceinline__ void wgmma_sa_n40(float (&d)[20], uint32_t da, uint32_t db){
  asm volatile("{\n.reg .pred p;\n.reg .b64 a, b;\nsetp.ne.b32 p, 1, 0;\nmov.b64 a, {%20, %24};\nmov.b64 b, {%21, %25};\n"
  "wgmma.mma_async.sync.aligned.m64n40k16.f32.bf16.bf16 {%0, %1, %2, %3, %4, %5, %6, %7, %8, %9, %10, %11, %12, %13, %14, %15, %16, %17, %18, %19}, a, b, p, 1, 1, %22, %23;\n}\n"
  : "+f"(d[0]), "+f"(d[1]), "+f"(d[2]), "+f"(d[3]), "+f"(d[4]), "+f"(d[5]), "+f"(d[6]), "+f"(d[7]), "+f"(d[8]), "+f"(d[9]), "+f"(d[10]), "+f"(d[11]), "+f"(d[12]), "+f"(d[13]), "+f"(d[14]), "+f"(d[15]), "+f"(d[16]), "+f"(d[17]), "+f"(d[18]), "+f"(d[19])
  : "r"(da), "r"(db), "n"(TA), "n"(TB), "n"(HA), "n"(HB));
}
template<int TA, int TB, uint32_t HA, uint32_t HB> __device__ __forceinline__ void wgmma_sz_n40(float (&d)[20], uint32_t da, uint32_t db){
  asm volatile("{\n.reg .pred p;\n.reg .b64 a, b;\nsetp.ne.b32 p, 0, 0;\nmov.b64 a, {%20, %24};\nmov.b64 b, {%21, %25};\n"
  "wgmma.mma_async.sync.aligned.m64n40k16.f32.bf16.bf16 {%0, %1, %2, %3, %4, %5, %6, %7, %8, %9, %10, %11, %12, %13, %14, %15, %16, %17, %18, %19}, a, b, p, 1, 1, %22, %23;\n}\n"
  : "=f"(d[0]), "=f"(d[1]), "=f"(d[2]), "=f"(d[3]), "=f"(d[4]), "=f"(d[5]), "=f"(d[6]), "=f"(d[7]), "=f"(d[8]), "=f"(d[9]), "=f"(d[10]), "=f"(d[11]), "=f"(d[12]), "=f"(d[13]), "=f"(d[14]), "=f"(d[15]), "=f"(d[16]), "=f"(d[17]), "=f"(d[18]), "=f"(d[19])
  : "r"(da), "r"(db), "n"(TA), "n"(TB), "n"(HA), "n"(HB));
}
template<int TA, int TB, uint32_t HA, uint32_t HB> __device__ __forceinline__ void wgmma_sa_n32(float (&d)[16], uint32_t da, uint32_t db){
  asm volatile("{\n.reg .pred p;\n.reg .b64 a, b;\nsetp.ne.b32 p, 1, 0;\nmov.b64 a, {%16, %20};\nmov.b64 b, {%17, %21};\n"
  "wgmma.mma_async.sync.aligned.m64n32k16.f32.bf16.bf16 {%0, %1, %2, %3, %4, %5, %6, %7, %8, %9, %10, %11, %12, %13, %14, %15}, a, b, p, 1, 1, %18, %19;\n}\n"
  : "+f"(d[0]), "+f"(d[1]), "+f"(d[2]), "+f"(d[3]), "+f"(d[4]), "+f"(d[5]), "+f"(d[6]), "+f"(d[7]), "+f"(d[8]), "+f"(d[9]), "+f"(d[10]), "+f"(d[11]), "+f"(d[12]), "+f"(d[13]), "+f"(d[14]), "+f"(d[15])
  : "r"(da), "r"(db), "n"(TA), "n"(TB), "n"(HA), "n"(HB));
}
template<int TA, int TB, uint32_t HA, uint32_t HB> __device__ __forceinline__ void wgmma_ss_n32(float (&d)[16], uint32_t da, uint32_t db, int scale_d){
  asm volatile("{\n.reg .pred p;\n.reg .b64 a, b;\nsetp.ne.b32 p, %22, 0;\nmov.b64 a, {%16, %20};\nmov.b64 b, {%17, %21};\n"
  "wgmma.mma_async.sync.aligned.m64n32k16.f32.bf16.bf16 {%0, %1, %2, %3, %4, %5, %6, %7, %8, %9, %10, %11, %12, %13, %14, %15}, a, b, p, 1, 1, %18, %19;\n}\n"
  : "+f"(d[0]), "+f"(d[1]), "+f"(d[2]), "+f"(d[3]), "+f"(d[4]), "+f"(d[5]), "+f"(d[6]), "+f"(d[7]), "+f"(d[8]), "+f"(d[9]), "+f"(d[10]), "+f"(d[11]), "+f"(d[12]), "+f"(d[13]), "+f"(d[14]), "+f"(d[15])
  : "r"(da), "r"(db), "n"(TA), "n"(TB), "n"(HA), "n"(HB), "r"(scale_d));
}
template<int TB, uint32_t HB> __device__ __forceinline__ void wgmma_ra_n32(float (&d)[16], uint32_t a0, uint32_t a1, uint32_t a2, uint32_t a3, uint32_t db){
  asm volatile("{\n.reg .pred p;\n.reg .b64 a, b;\nsetp.ne.b32 p, 1, 0;\nmov.b64 b, {%20, %22};\n"
  "wgmma.mma_async.sync.aligned.m64n32k16.f32.bf16.bf16 {%0, %1, %2, %3, %4, %5, %6, %7, %8, %9, %10, %11, %12, %13, %14, %15}, {%16,%17,%18,%19}, b, p, 1, 1, %21;\n}\n"
  : "+f"(d[0]), "+f"(d[1]), "+f"(d[2]), "+f"(d[3]), "+f"(d[4]), "+f"(d[5]), "+f"(d[6]), "+f"(d[7]), "+f"(d[8]), "+f"(d[9]), "+f"(d[10]), "+f"(d[11]), "+f"(d[12]), "+f"(d[13]), "+f"(d[14]), "+f"(d[15])
  : "r"(a0), "r"(a1), "r"(a2), "r"(a3), "r"(db), "n"(TB), "n"(HB));
}
template<int TB, uint32_t HB> __device__ __forceinline__ void wgmma_rs_n32(float (&d)[16], uint32_t a0, uint32_t a1, uint32_t a2, uint32_t a3, uint32_t db, int scale_d){
  asm volatile("{\n.reg .pred p;\n.reg .b64 a, b;\nsetp.ne.b32 p, %23, 0;\nmov.b64 b, {%20, %22};\n"
  "wgmma.mma_async.sync.aligned.m64n32k16.f32.bf16.bf16 {%0, %1, %2, %3, %4, %5, %6, %7, %8, %9, %10, %11, %12, %13, %14, %15}, {%16,%17,%18,%19}, b, p, 1, 1, %21;\n}\n"
  : "+f"(d[0]), "+f"(d[1]), "+f"(d[2]), "+f"(d[3]), "+f"(d[4]), "+f"(d[5]), "+f"(d[6]), "+f"(d[7]), "+f"(d[8]), "+f"(d[9]), "+f"(d[10]), "+f"(d[11]), "+f"(d[12]), "+f"(d[13]), "+f"(d[14]), "+f"(d[15])
  : "r"(a0), "r"(a1), "r"(a2), "r"(a3), "r"(db), "n"(TB), "n"(HB), "r"(scale_d));
}
template<int TB, uint32_t HB> __device__ __forceinline__ void wgmma_ra_n40(float (&d)[20], uint32_t a0, uint32_t a1, uint32_t a2, uint32_t a3, uint32_t db){
  asm volatile("{\n.reg .pred p;\n.reg .b64 a, b;\nsetp.ne.b32 p, 1, 0;\nmov.b64 b, {%24, %26};\n"
  "wgmma.mma_async.sync.aligned.m64n40k16.f32.bf16.bf16 {%0, %1, %2, %3, %4, %5, %6, %7, %8, %9, %10, %11, %12, %13, %14, %15, %16, %17, %18, %19}, {%20,%21,%22,%23}, b, p, 1, 1, %25;\n}\n"
  : "+f"(d[0]), "+f"(d[1]), "+f"(d[2]), "+f"(d[3]), "+f"(d[4]), "+f"(d[5]), "+f"(d[6]), "+f"(d[7]), "+f"(d[8]), "+f"(d[9]), "+f"(d[10]), "+f"(d[11]), "+f"(d[12]), "+f"(d[13]), "+f"(d[14]), "+f"(d[15]), "+f"(d[16]), "+f"(d[17]), "+f"(d[18]), "+f"(d[19])
  : "r"(a0), "r"(a1), "r"(a2), "r"(a3), "r"(db), "n"(TB), "n"(HB));
}
template<int TB, uint32_t HB> __device__ __forceinline__ void wgmma_rz_n40(float (&d)[20], uint32_t a0, uint32_t a1, uint32_t a2, uint32_t a3, uint32_t db){
  asm volatile("{\n.reg .pred p;\n.reg .b64 a, b;\nsetp.ne.b32 p, 0, 0;\nmov.b64 b, {%24, %26};\n"
  "wgmma.mma_async.sync.aligned.m64n40k16.f32.bf16.bf16 {%0, %1, %2, %3, %4, %5, %6, %7, %8, %9, %10, %11, %12, %13, %14, %15, %16, %17, %18, %19}, {%20,%21,%22,%23}, b, p, 1, 1, %25;\n}\n"
  : "=f"(d[0]), "=f"(d[1]), "=f"(d[2]), "=f"(d[3]), "=f"(d[4]), "=f"(d[5]), "=f"(d[6]), "=f"(d[7]), "=f"(d[8]), "=f"(d[9]), "=f"(d[10]), "=f"(d[11]), "=f"(d[12]), "=f"(d[13]), "=f"(d[14]), "=f"(d[15]), "=f"(d[16]), "=f"(d[17]), "=f"(d[18]), "=f"(d[19])
  : "r"(a0), "r"(a1), "r"(a2), "r"(a3), "r"(db), "n"(TB), "n"(HB));
}
template<int TB, uint32_t HB> __device__ __forceinline__ void wgmma_rz_n8(float (&d)[4], uint32_t a0, uint32_t a1, uint32_t a2, uint32_t a3, uint32_t db){
  asm volatile("{\n.reg .pred p;\n.reg .b64 a, b;\nsetp.ne.b32 p, 0, 0;\nmov.b64 b, {%8, %10};\n"
  "wgmma.mma_async.sync.aligned.m64n8k16.f32.bf16.bf16 {%0, %1, %2, %3}, {%4,%5,%6,%7}, b, p, 1, 1, %9;\n}\n"
  : "=f"(d[0]), "=f"(d[1]), "=f"(d[2]), "=f"(d[3])
  : "r"(a0), "r"(a1), "r"(a2), "r"(a3), "r"(db), "n"(TB), "n"(HB));
}

constexpr int SEQ = 2048, DM = 1024, FF = 3584;
constexpr float LOG2E = 1.4426950408889634f;
constexpr uint32_t POLL_LIMIT = 1u << 22;
constexpr int QW = 0;
constexpr int LAG = 2;
constexpr int ML = 2;
constexpr int REL = 6;
constexpr int SKM = 0x154;
constexpr int RS_N = 22;
constexpr int RS_D1 = 420;
constexpr int RS_D2 = 300;
constexpr int PF_T0 = 5000;
constexpr int PF_DT = 800;
constexpr int FF_N = 5;
constexpr int FF_DT = 500;
constexpr int FF_D2 = 350;
constexpr uint64_t FF_ORD = 0x76543210ba98ull;
constexpr int OUT_D = 400;
constexpr int NFFN = 112;

constexpr uint32_t SB0 = 1024;
constexpr uint32_t KV_STAGE = 49152, R5 = 32768;
constexpr uint32_t OFF_X = 163840, OFF_S = 196608, OFF_WPHI = OFF_S + 20480, OFF_M = 229376, SMEM_BYTES = 232448;
constexpr uint32_t OFF_RS256 = 212992, OFF_ONES = OFF_RS256 + 1024, OFF_WPHIK1 = OFF_ONES + 1024, OFF_KVZ = OFF_S;
constexpr uint32_t OFF_WPHIK = OFF_S, OFF_BXK = OFF_S + 2048, OFF_AXK = OFF_S + 4096, OFF_G = OFF_S + 8192;
constexpr uint32_t OFF_AXQ = OFF_WPHI, OFF_BXQ = OFF_WPHI + 2048, OFF_WPHIQ = OFF_WPHI + 4096;
constexpr uint32_t B_FULLKV = OFF_M  , B_EMPTYKV = OFF_M + 32  ;
constexpr uint32_t B_EMPTY5 = OFF_M + 64  , B_UO = B_EMPTY5 + 48  , B_RC = B_UO + 32  ;
constexpr uint32_t B_OUT = B_RC + 16  , B_SD = B_OUT + 16, B_AUX = B_SD + 8, B_AUXQ = B_AUX + 8, B_RX = B_AUXQ + 8;
constexpr uint32_t B_FULL5 = B_RX + 8  , B_F = B_FULL5 + 40  , B_WD = B_F + 64  ;
constexpr uint32_t B_WC = B_WD + 32  , B_DR = B_WC + 32  , B_W = B_DR + 24, B_OS = B_W + 8, B_R = B_W + 16, B_KD = B_W + 24, B_T = B_W + 32, B_G = B_W + 40, B_END = B_W + 48;
constexpr int NB3 = ((B_END - OFF_M) / 8 + 1) / 3;
constexpr uint32_t B_S0 = OFF_M + 8 + 24 * NB3;
static_assert(B_S0 >= B_END && B_S0 < OFF_M + 576, "barriers");
__host__ __device__ constexpr uint32_t bar_count(int i) {
  const uint32_t b = OFF_M + 8 * i;
  return b < B_EMPTYKV ? 1 : b < B_EMPTY5 ? 12 : b < B_SD ? 4 : b < B_RX || b == B_W ? 2 : b == B_RX ? 8 : 1;
}
constexpr uint32_t B_GB = OFF_M + 2560  , B_GA = B_GB + 128  ;
constexpr uint32_t OFF_BEST = OFF_M + 576, OFF_SUMWR = OFF_M + 608, OFF_EP = OFF_M + 624, OFF_KEY = OFF_M + 628;
constexpr uint32_t OFF_RSQ = OFF_M + 640, OFF_SEL = OFF_M + 1648, OFF_T = OFF_M + 1792, OFF_WR = OFF_M + 2048;
constexpr uint32_t OFF_XSEL = 2 * R5, OFF_GU = OFF_XSEL + 4096, OFF_OUT = 3 * R5;
constexpr uint64_t FF_SLOT = 0xdcdc3210dcbaull;
constexpr int KVP = 6 * 128;
__device__ __forceinline__ uint32_t kv_count(uint32_t launch, uint32_t n) { return 0x42800000u + (((launch & 3) * 16 + n) << 17); }

enum { NB_G2E = 1, NB_XS = 2, NB_WG01 = 3, NB_ACT = 4, NB_Q0 = 5  , NB_ST = 14, NB_LAG = 8, NB_DN = 9, NB_ZERO = 10, NB_PUB = 11, NB_TOK = 10  , NB_L0 = 12  , NB_WG2 = 7, NB_QGO = 15 };

struct Scratch {
  bf16     o[SEQ * DM];
  float4   rstat[SEQ];
  uint32_t key[16 * 128];
  uint32_t cand[16 * 512];
  float4   yacc[4 * 3 * 128];
  float4   kvacc[32 * KVP];
  uint2    stats[SEQ];
  uint32_t cskv[2 * DM];
  uint32_t csq[4 * DM];
  uint32_t oset[128 * 16];
  uint32_t oflag[16 * 6 * 32 * 8];
  uint32_t epoch;
};
__device__ __align__(1024) Scratch g_scr;

struct Params {
  const bf16 *x, *wqkv, *wo_p, *wr;
  bf16* out_p;
  Scratch* g;
  uint32_t zero;
  CUtensorMap x128, x64, wkv, wq, wo[2], wd, wg, wu, phi, tg, tu, td, xs, ws, qs, out, o;
};

constexpr float EXP_LIM = 1.1529215e18f, ARG_LIM2 = 3600.f;
__device__ __forceinline__ void dual_exp2(const float (&p)[16], uint32_t (&ep)[8], uint32_t (&em)[8]) {
  #pragma unroll
  for (int k = 0; k < 8; k++) {
    const float a = ex2(p[2*k]), b = ex2(p[2*k+1]);
    const float r = rcp(a * b);
    ep[k] = pack_bf16(a, b); em[k] = pack_bf16(r * b, r * a);
  }
}
__device__ __forceinline__ void dual_exp2_shifted(const float (&pp)[2][16], uint32_t (&ph)[4][8]) {
  #pragma unroll
  for (int h = 0; h < 2; h++) {
    const float* p = pp[h];
    float m[4] = {p[0], p[2], p[0], p[2]};
    #pragma unroll
    for (int i = 0; i < 16; i++) { m[(i >> 1) & 1] = fmaxf(m[(i >> 1) & 1], p[i]); m[2 + ((i >> 1) & 1)] = fminf(m[2 + ((i >> 1) & 1)], p[i]); }
    #pragma unroll
    for (int o = 1; o < 4; o <<= 1) {
      m[0] = fmaxf(m[0], __shfl_xor_sync(~0u, m[0], o)); m[1] = fmaxf(m[1], __shfl_xor_sync(~0u, m[1], o));
      m[2] = fminf(m[2], __shfl_xor_sync(~0u, m[2], o)); m[3] = fminf(m[3], __shfl_xor_sync(~0u, m[3], o));
    }
    #pragma unroll
    for (int k = 0; k < 8; k++) {
      ph[2*h][k] = pack_bf16(ex2(p[2*k] - m[k & 1]), ex2(p[2*k+1] - m[k & 1]));
      ph[2*h+1][k] = pack_bf16(ex2(m[2 + (k & 1)] - p[2*k]), ex2(m[2 + (k & 1)] - p[2*k+1]));
    }
  }
}
__device__ __forceinline__ uint32_t add_bf16x2(uint32_t a, uint32_t b) { uint32_t r; asm("add.rn.bf16x2 %0, %1, %2;" : "=r"(r) : "r"(a), "r"(b)); return r; }
__device__ __forceinline__ void row_sums(float (&s)[2][4], const uint32_t (&ph)[4][8], uint32_t sel) {
  uint32_t u[8];
  #pragma unroll
  for (int i = 0; i < 8; i++) { const uint32_t* f = &ph[i >> 1][i & 1]; u[i] = add_bf16x2(add_bf16x2(f[0], f[2]), add_bf16x2(f[4], f[6])); }
  wg_fence();
  wgmma_rz_n8<0, H0>(s[0], u[0], u[1], u[2], u[3], sel);
  wgmma_rz_n8<0, H0>(s[1], u[4], u[5], u[6], u[7], sel);
  wg_commit();
}
__device__ __forceinline__ uint32_t mul_bf16x2(uint32_t a, uint32_t b) { uint32_t r; asm("mul.rn.bf16x2 %0, %1, %2;" : "=r"(r) : "r"(a), "r"(b)); return r; }
__device__ __forceinline__ void normalize(uint32_t (&ph)[4][8], const float (&s)[2][4]) {
  #pragma unroll
  for (int i = 0; i < 4; i++) {
    const float i0 = rcp(s[i >> 1][i & 1]), i1 = rcp(s[i >> 1][2 + (i & 1)]);
    const uint32_t n0 = pack_bf16(i0, i0), n1 = pack_bf16(i1, i1);
    #pragma unroll
    for (int k = 0; k < 4; k++) { ph[i][2*k] = mul_bf16x2(ph[i][2*k], n0); ph[i][2*k+1] = mul_bf16x2(ph[i][2*k+1], n1); }
  }
}
__device__ __forceinline__ void split_bf16(float a, float b, uint32_t& hi, uint32_t& lo) { hi = pack_bf16(a, b); lo = pack_bf16(a - bf_lo(hi), b - bf_hi(hi)); }
__device__ __forceinline__ void put_colsums(uint32_t base, int lane, float a, float b, float c, float d) {
  uint32_t h0, l0, h1, l1;
  split_bf16(a, b, h0, l0); split_bf16(c, d, h1, l1);
  const uint32_t ad = base + (lane >> 1) * 128 + (lane & 1) * 8;
  sts64(ad, h0, h1); sts64(ad + 16, l0, l1); sts64(ad + 32, h0, h1); sts64(ad + 48, l0, l1);
  sts128(base + (lane >> 1) * 128 + 64 + (lane & 1) * 32, 0, 0, 0, 0); sts128(base + (lane >> 1) * 128 + 80 + (lane & 1) * 32, 0, 0, 0, 0);
}
__device__ __forceinline__ float reduce8(const float (&v)[8], int lane) {
  const bool b4 = lane & 16, b3 = lane & 8, b2 = lane & 4;
  float a[4], b[2];
  #pragma unroll
  for (int i = 0; i < 4; i++) a[i] = (b4 ? v[4 + i] : v[i]) + __shfl_xor_sync(~0u, b4 ? v[i] : v[4 + i], 16);
  #pragma unroll
  for (int i = 0; i < 2; i++) b[i] = (b3 ? a[2 + i] : a[i]) + __shfl_xor_sync(~0u, b3 ? a[i] : a[2 + i], 8);
  return (b2 ? b[1] : b[0]) + __shfl_xor_sync(~0u, b2 ? b[0] : b[1], 4);
}
__device__ __forceinline__ bool tag_bad(uint4 v, uint32_t tg) { return (((v.x ^ tg) | (v.y ^ tg) | (v.z ^ tg) | (v.w ^ tg)) & 3) != 0; }


__global__ void __launch_bounds__(512, 1) fused_kernel(const __grid_constant__ Params P) {
  extern __shared__ __align__(1024) uint8_t smem_raw[];
  const uint32_t sb = smem_u32(smem_raw);
  const int tid = threadIdx.x, lane = tid & 31;
  {
    const int n = 16 * blockIdx.x + (lane & 15);
    const bf16* p = (lane < 16 ? P.x : P.wqkv) + (lane < 16 ? n * DM : (n >> 5) * (3 * DM) + DM + 64 * (n & 31));
    asm volatile("{\n.reg .pred p;\nsetp.lt.u32 p, %1, 32;\n@p prefetch.global.L2 [%0];\n}\n" :: "l"(p), "r"(tid));
  }
  const int cp = blockIdx.x >> 1, rank = blockIdx.x & 1;
  const int cr = cp < 4 ? 32 + 8 * cp : cp - 4 + max((cp * 37 - 1076) >> 8, 0);
  const int c = (cr & 62) + 64 * (cr & 1) + rank;
  const int m256 = c >> 4, nkv = c & 15, m128 = c >> 3, j = c & 7;
  if ((tid >> 7) == 2 && elect_one()) {
    if (tid >= 288) {
      const int w = (tid >> 5) - 9;
      #pragma unroll
      for (int i = 0; i < NB3; i++) mbar_init(sb + B_FULLKV + 8 + 8 * NB3 * w + 8 * i, w == 0 ? bar_count(1 + i) : w == 1 ? bar_count(1 + NB3 + i) : bar_count(1 + 2 * NB3 + i));
    } else {
      prefetch_map(&P.wkv); prefetch_map(&P.x128);
      mbar_init(sb + B_S0, 1); mbar_init(sb + B_FULLKV, 1);
      mbar_expect_tx(sb + B_S0, 32768);
      tma_4d(sb + 32768, &P.wkv, 0, 0, nkv, 1, sb + B_S0);
      tma_2d(sb, &P.x128, 0, 256 * m256, sb + B_S0);
      mbar_expect_tx(sb + B_FULLKV, 16384);
      tma_2d(sb + 16384, &P.x128, 0, 256 * m256 + 128, sb + B_FULLKV);
    }
    asm volatile("fence.mbarrier_init.release.cluster;" ::: "memory");
  }
  const int warp = __shfl_sync(~0u, tid >> 5, 0), wg = warp >> 2, wp = warp & 3;
  const int f = 16 * ((cr + 7) & 7) + 2 * (cr >> 3) + rank;
  const int ha = 4 * (nkv >> 1) + (nkv & 1);
  Scratch* const G = P.g;
  if ((sb & 0x3ffff) != SB0) asm volatile("trap;");
  __syncthreads();
  cluster_arrive();
  if (warp == 8 && elect_one()) {
    mbar_expect_tx(sb + B_FULLKV + 8, KV_STAGE);
    tma_4d(sb + KV_STAGE + 32768, &P.wkv, 0, 64, nkv, 1, sb + B_FULLKV + 8);
    tma_2d(sb + KV_STAGE, &P.x128, 64, 256 * m256, sb + B_FULLKV + 8);
    tma_2d(sb + KV_STAGE + 16384, &P.x128, 64, 256 * m256 + 128, sb + B_FULLKV + 8);
  }
  if (wg == 3) {
    asm volatile("setmaxnreg.dec.sync.aligned.u32 32;");
    cluster_wait();
    const bool el = elect_one();
    const uint64_t ef = policy_evict_first(), en = policy_evict_normal();
    auto fetch_o = [&](const int t0) {
      const int sh = t0 & 1;
      uint32_t missing = ~0u;
      const uint32_t* hint = &G->oflag[((m128 * 6 + ((t0 + 1) & 6) + rank) * 32 + ((4 * (j & 6) + lane) & 31)) * 8];
      #pragma unroll 1
      for (int i = 2 - 2 * sh; i < 8; i += 1 + sh) {
        const int blk = sh ? 6 + 2 * t0 + (i >> 1) : i, wrap = t0 == 3 ? 2 : (blk >= 5) + (blk >= 11), s = blk + 1 - 6 * wrap;
        flags_wait(missing, hint, (15u + 240u * sh) << (4 * i));
        if (blk > 5) mbar_wait(sb + B_EMPTY5 + 8 * s, wrap & 1);
        if (el) {
          tma_2d_mc_h(sb + s * R5 + rank * 8192, &P.o, 0, (m128 * 16 + t0 + 2 * (((j & 6) + i) & 7)) * 32 + 16 * rank, sb + B_GA + 16 * blk + 8 * rank, ef);
        }
      }
    };
    if (wp == 0) {
      {
        wait_until((uint32_t)clock() + 300);
        #pragma unroll 1
        for (int kb = 2; kb < 16; kb++) {
          const uint32_t st = sb + (kb & 3) * KV_STAGE, fb = sb + B_FULLKV + 8 * (kb & 3);
          mbar_wait(fb + (B_EMPTYKV - B_FULLKV), ~(kb >> 2) & 1);
          if (el) {
            mbar_expect_tx(fb, KV_STAGE);
            tma_2d_mc(st + rank * 16384, &P.x128, 64 * kb, 256 * m256 + 128 * rank, fb);
            tma_4d_h(st + 32768, &P.wkv, 0, 64 * kb, nkv, 1, fb, ef);
          }
        }
        uint64_t ord = 0xf3120edcba987654ull;
        uint32_t so = 0, par = 1;
        #pragma unroll 1
        for (int i = 0; i < 16; i++) {
          const uint32_t st = sb + so * 4096, fb = sb + B_FULL5 + so;
          const int k0 = (64 * (uint32_t)ord + 128 * (j & 6)) & 960;
          mbar_wait(i < 5 ? sb + B_EMPTYKV + so - (i > 1 ? 8 : 0) : fb + (B_EMPTY5 - B_FULL5), par);
          if (el) {
            mbar_expect_tx(fb, R5);
            tma_2d_mc_h(st + rank * 8192, &P.x64, k0, 128 * m128 + 64 * rank, fb, i >= 11 ? ef : en);
            tma_3d_h(st + 16384, &P.wq, 0, k0, 2 * j, fb, ef);
          }
          ord >>= 4; so += 8;
          if (so == 40) { so = 0; par ^= 1; }
        }
        mbar_wait(sb + B_FULL5 + 8 + 8 * rank, 0);
        if (el) mbar_arrive(sb + B_R);
        #pragma unroll 1
        for (int i = 0; i < 19; i++) {
          const int row = i < 8 ? 128 * (((j & 6) + i) & 7) : 256 * (((j >> 1) + i) & 3) + 32 + 16 * (i & 4);
          mbar_wait(sb + B_EMPTY5 + so, par);
          if (el) {
            if (i < 16) {
              tma_5d_h(sb + so * 4096 + 16384, &P.wo[i >> 3], 128 * j, row, sb + B_GB + 8 * i, ef);
              tma_5d_h(sb + so * 4096 + 24576, &P.wo[i >> 3], 128 * j + 64, row, sb + B_GB + 8 * i, ef);
            } else mbar_arrive(sb + B_DR + 8 * (i - 16));
          }
          so += 8;
          if (so == 48) { so = 0; par ^= 1; }
        }
      }
    } else if (wp == 3) {
      const uint32_t t_start = (uint32_t)clock();
      mbar_wait(sb + B_S0, 0);
      if (el) {
        mbar_expect_tx(sb + B_W, 12288);
        #pragma unroll 1
        for (int i = 0; i < 6; i++) tma_2d(sb + (i == 0 ? OFF_WPHIK : i == 1 ? OFF_WPHIK1 : OFF_WPHIQ + 2048 * (i - 2)), &P.phi, 0, 32 * (i < 2 ? 2 * nkv + i : 4 * j + 2 * (i & 1) + ((i - 2) >> 1)), sb + B_W);
        prefetch_map(&P.x64); prefetch_map(&P.wq); prefetch_map(&P.wo[0]); prefetch_map(&P.wo[1]);
        prefetch_map(&P.o); prefetch_map(&P.wd); prefetch_map(&P.out); prefetch_map(&P.wg); prefetch_map(&P.wu);
      }
      if (lane < 16) st128_rlx(&G->cand[m128 * 512 + 64 * j + 4 * lane], ~0u, ~0u, ~0u, ~0u);
      if (lane < 16) st128_rlx(&G->rstat[16 * c + lane], 0, 0, 0, 0);
      if (lane < 12) st128_rlx(&G->yacc[12 * c + lane], 0, 0, 0, 0);
      const uint32_t nt = ld32_rlx(&G->epoch);
      if (lane < 8) { st128_rlx(&G->stats[16 * c + 2 * lane], nt, nt, nt, nt); st128_rlx(&G->csq[32 * c + 4 * lane], nt, nt, nt, nt); }
      if (lane < 4) { st128_rlx(&G->cskv[128 * nkv + 16 * m256 + 4 * lane], nt, nt, nt, nt); st128_rlx(&G->oset[16 * c + 4 * lane], nt, nt, nt, nt); }
      if (lane < 4) st128_rlx(&G->key[(2 * j + (lane >> 1)) * 128 + m128 * 8 + 4 * (lane & 1)], 0, 0, 0, 0);
      if (c < 32) {
        #pragma unroll 1
        for (int i = lane; i < KVP; i += 32) st128_rlx(&G->kvacc[(ha + 2 * m256) * KVP + i], 0, 0, 0, kv_count(nt + 1, 0));
      }
      fence_gpu();
      bar_arrive(NB_ZERO, 160);
      if (el) {
        #pragma unroll 1
        for (int i = 0; i < 30; i++) {
          wait_until(t_start + PF_T0 + PF_DT * i + 7 * f);
          if (i < 4) { bulk_prefetch(P.wqkv + (size_t)(256 * i + c) * (3 * DM), 2048); bulk_prefetch(P.wqkv + (size_t)(256 * i + 128 + c) * (3 * DM), 2048); }
          else if (i < 6) bulk_prefetch(P.wo_p + (size_t)c * 8192 + (i - 4) * 4096, 8192);
          else if (f < NFFN) {
            if (i < 22) {
              #pragma unroll 1
              for (int e = 0; e < 4; e++) tma_2d(sb + OFF_T, rank ? &P.tu : &P.tg, 32 * (f & ~1), 64 * (i - 6) + 16 * e, sb + B_T);
            } else { tma_2d(sb + OFF_T, &P.td, 0, 256 * f + 32 * (i - 22), sb + B_T); tma_2d(sb + OFF_T, &P.td, 0, 256 * f + 32 * (i - 22) + 16, sb + B_T); }
          }
        }
      }
      __syncwarp();
      mbar_wait2(sb + B_OS, 0, sb + B_RX, 0);
      mbar_wait2(sb + B_EMPTY5 + 24, 0, sb + B_EMPTY5 + 32, 0);
      mbar_wait2(sb + B_EMPTY5 + 40, 0, sb + B_EMPTY5, 1);
      fetch_o(0);
      fetch_o(3);
    } else {
      const int half = wp - 1;
      const uint32_t ep1 = ld32_rlx(&G->epoch) + 1, tg = ep1 & 3;
      {
        uint32_t it = 0;
        sts128(sb + OFF_ONES + half * 512 + lane * 16, 0x3f803f80u, 0x3f803f80u, 0x3f803f80u, 0x3f803f80u);
        if (lane < 9) { const uint32_t v = (lane & 1) ? 0 : 0x3f803f80u; sts128(sb + OFF_SEL + lane * 16, v, v, v, v); }
        auto reset_o = [&](int i0, int i1, uint32_t dt) {
          uint32_t t0 = (uint32_t)clock();
          #pragma unroll 1
          for (int i = i0; i < i1; i++) {
            st128_rlx(G->o + (m128 * 16 + 2 * j + half) * 8192 + 256 * i + 8 * lane, ~0u, ~0u, ~0u, ~0u);
            wait_until(t0 += dt);
          }
        };
        if (el) {
          #pragma unroll 1
          for (int i = 24 * half; i < 24 * half + 24; i++) { mbar_init(sb + B_GB + 8 * i, 1); mbar_expect_tx(sb + B_GB + 8 * i, i < 16 ? 16384 : 8192); }
          asm volatile("fence.mbarrier_init.release.cluster;" ::: "memory");
        }
        mbar_wait(sb + B_S0, 0);
        reset_o(0, RS_N, RS_D1);
        bar_sync(NB_PUB, 192);
        const uint4* src = reinterpret_cast<const uint4*>(&G->stats[256 * m256 + 128 * half]) + lane;
        const uint4* srk = reinterpret_cast<const uint4*>(&G->cskv[128 * nkv]) + lane;
        uint4 v0, v1, vk;
        it = 0;
        do { v0 = ld128_rlx(src); v1 = ld128_rlx(src + 32); vk = ld128_rlx(srk); }
        while ((tag_bad(v0, tg) || tag_bad(v1, tg) || tag_bad(vk, tg)) && ++it < POLL_LIMIT);
        fence_acquire_gpu();
        if (half) put_colsums(sb + OFF_BXK, lane, untag(vk.x), untag(vk.y), untag(vk.z), untag(vk.w));
        #pragma unroll
        for (int i = 0; i < 2; i++) {
          const uint4 v = i ? v1 : v0;
          uint32_t hi, lo;
          split_bf16(-0.5f * untag(v.x), -0.5f * untag(v.z), hi, lo);
          const uint32_t h0 = __byte_perm(hi, hi, 0x1010), h1 = __byte_perm(hi, hi, 0x3232), l0 = __byte_perm(lo, lo, 0x1010), l1 = __byte_perm(lo, lo, 0x3232);
          const uint32_t a = sb + OFF_AXK + half * 2048 + i * 1024 + lane * 32;
          sts128(a, h0, l0, 0, 0); sts128(a + 16, h1, l1, 0, 0);
          sts64(sb + OFF_RS256 + half * 512 + i * 256 + lane * 8, v.y & ~3u, v.w & ~3u);
          if (half == (m128 & 1)) {
            const uint32_t aq = sb + OFF_AXQ + i * 1024 + lane * 32;
            sts128(aq, h0, l0, 0, 0); sts128(aq + 16, h1, l1, 0, 0);
            sts64(sb + OFF_RSQ + i * 256 + lane * 8, v.y & ~3u, v.w & ~3u);
          }
        }
        fence_async_smem();
        __syncwarp();
        if (el) { sts32(sb + OFF_EP, ep1); mbar_arrive(sb + B_AUX); }
        reset_o(RS_N, 32, RS_D2);
        if (lane < 24) st128_rlx(&G->oflag[((m128 * 6 + 3 * half + (lane >> 3)) * 32 + 4 * j) * 8 + 4 * (lane & 7)], 0, 0, 0, 0);
        fence_gpu();
        __syncwarp();
        if (el) { st32_rlx(&G->oset[16 * c + 8 * half], ep1); if (half) mbar_arrive(sb + B_AUXQ); }
        if (!half) {
          const uint4* src = reinterpret_cast<const uint4*>(&G->csq[128 * j]) + lane;
          uint4 v0, v1, v2, v3;
          do { v0 = ld128_rlx(src); v1 = ld128_rlx(src + DM / 4); v2 = ld128_rlx(src + DM / 2); v3 = ld128_rlx(src + 3 * DM / 4); }
          while ((tag_bad(v0, tg) || tag_bad(v1, tg) || tag_bad(v2, tg) || tag_bad(v3, tg)) && ++it < POLL_LIMIT);
          put_colsums(sb + OFF_BXQ, lane, (untag(v0.x) + untag(v1.x)) + (untag(v2.x) + untag(v3.x)), (untag(v0.y) + untag(v1.y)) + (untag(v2.y) + untag(v3.y)),
                      (untag(v0.z) + untag(v1.z)) + (untag(v2.z) + untag(v3.z)), (untag(v0.w) + untag(v1.w)) + (untag(v2.w) + untag(v3.w)));
          fence_async_smem();
          __syncwarp();
          if (el) mbar_arrive(sb + B_AUXQ);
        }
      }
      if (half == 0) {
        for (uint32_t it = 0; __any_sync(~0u, ld32_rlx(&G->oset[m128 * 128 + 8 * (lane & 15)]) != ep1) && it < POLL_LIMIT; it++) {}
        fence_acquire_gpu();
        if (el) mbar_arrive(sb + B_OS);
      }
      if (!half) {
        #pragma unroll 1
        for (int hh = 0; hh < 2; hh++) {
          const uint32_t src = sb + (1 + rank) * R5 + hh * 8192, fa = sb + B_GA + 16 * rank + 8 * hh;
          mbar_wait2(sb + B_UO + 8 * hh, 0, sb + B_GB + 8 * rank, 0);
          if (el) bulk_s2peer(mapa(src, rank ^ 1), src, 8192, mapa(fa, rank ^ 1));
        }
        fetch_o(1);
      }
      else if (f < NFFN) {
        mbar_wait(sb + B_UO + 24, 0);
        mbar_wait2(sb + B_UO, 0, sb + B_UO + 8, 0);
        uint32_t t0 = (uint32_t)clock();
        #pragma unroll 1
        for (int i = 0; i < 12; i++) {
          const int e = (FF_ORD >> (4 * i)) & 15;
          const uint32_t dst = sb + 16384 * ((FF_SLOT >> (4 * e)) & 15), fb = sb + B_F + 8 * e;
          if (i >= 2) mbar_wait(sb + B_WC + 8 * ((0x100066553244ull >> (4 * e)) & 15), 0);
          wait_until(t0);
          t0 = (uint32_t)clock() + (i < FF_N ? FF_DT : FF_D2);
          if (el) {
            mbar_expect_tx(fb, 16384);
            if (e >= 8) tma_3d_h(dst, &P.wd, 0, 32 * f, 4 * e - 32, fb, ef);
            else { tma_2d_h(dst, &P.wg, 32 * f, 128 * e, fb, ef); tma_2d_h(dst + 8192, &P.wu, 32 * f, 128 * e, fb, ef); }
          }
        }
      }
      __syncwarp();
    }
    if (wp & 1) {
      __syncwarp();
      mbar_wait(sb + B_OUT + 8 * (wp >> 1), 0);
      uint32_t t0 = (uint32_t)clock();
      #pragma unroll 1
      for (int i = 0; i < 8; i++) {
        wait_until(t0);
        if (el) tma_store_2d(&P.out, 128 * j + 64 * (i & 1), 128 * m128 + 32 * (wp & 2) + 8 * (i & 6), sb + OFF_OUT + (i & 1) * 16384 + (wp & 2) * 4096 + (i & 6) * 1024, ef);
        t0 += OUT_D;
      }
      if (el) { bulk_commit(); bulk_wait_all(); fence_async_global(); mbar_arrive(sb + B_SD); }
    }
    __syncwarp();
    cluster_arrive(); cluster_wait();
    return;
  }

  asm volatile("setmaxnreg.inc.sync.aligned.u32 160;");
  cluster_wait();
  const int t = tid & 127, g = lane >> 2;
  const uint32_t sa = (16 * wp + (lane & 15)) * 128 + (((lane >> 4) ^ (lane & 7)) << 4);

  if (wg == 2) {
    float s[2] = {0.f, 0.f}, s2[2] = {0.f, 0.f}, ck[8] = {0.f, 0.f, 0.f, 0.f, 0.f, 0.f, 0.f, 0.f}, cs[8] = {0.f, 0.f, 0.f, 0.f, 0.f, 0.f, 0.f, 0.f};
    const uint32_t ebr = mapa(sb + B_EMPTYKV, lane & 1), tg = (ld32_rlx(&G->epoch) + 1) & 3;
    auto addx = [&](const uint4 v) {
      const uint32_t w[4] = {v.x, v.y, v.z, v.w};
      #pragma unroll
      for (int e = 0; e < 4; e++) { const float a = bf_lo(w[e]), d = bf_hi(w[e]); s[0] += a; s[1] += d; s2[0] = fmaf(a, a, s2[0]); s2[1] = fmaf(d, d, s2[1]); }
    };
    auto addc = [&](const uint4 v, float (&o)[8]) {
      o[0] += bf_lo(v.x); o[1] += bf_hi(v.x); o[2] += bf_lo(v.y); o[3] += bf_hi(v.y); o[4] += bf_lo(v.z); o[5] += bf_hi(v.z); o[6] += bf_lo(v.w); o[7] += bf_hi(v.w);
    };
    {
      const uint32_t ra = (16 * nkv + (t >> 3)) * 128 + (t & 7) * 16;
      const uint32_t ca = 32768 + (m256 >> 2) * 8192 + (t >> 1) * 128 + (((2 * (m256 & 3) + (t & 1)) ^ ((t >> 1) & 7)) << 4);
      int rd = 0;
      mbar_wait(sb + B_S0, 0);
      #pragma unroll 1
      for (int kb = 0; kb < 10; kb++) {
        const uint32_t st = sb + (kb & 3) * KV_STAGE;
        mbar_wait(sb + B_FULLKV + 8 * (kb & 3), (kb >> 2) & 1);
        const uint4 x0 = lds128(st + ra), w0 = lds128(st + ca);
        addx(x0); addc(w0, ck);
        __syncwarp();
        if (lane < 2) mbar_arrive_remote(ebr + 8 * (kb & 3), 1);
        if ((SKM >> kb) & 1) {
          if (rd) {
            mbar_wait(sb + B_G, (rd - 1) & 1);
            const uint32_t a = sb + OFF_G + (t >> 3) * 256 + (t & 7) * 16;
            const uint4 x1 = lds128(a), x2 = lds128(a + 128), w1 = lds128(sb + OFF_G + 4096 + t * 16), w2 = lds128(sb + OFF_G + 6144 + t * 16);
            addx(x1); addx(x2); addc(w1, ck); addc(w2, ck);
            bar_sync(NB_WG2, 128);
          }
          if (wp == 0 && elect_one()) {
            mbar_expect_tx(sb + B_G, 8192);
            if (rd < 3) {
              tma_2d(sb + OFF_G, &P.xs, 640 + 128 * rd, 256 * m256 + 16 * nkv, sb + B_G);
              tma_2d(sb + OFF_G + 4096, &P.ws, (1 + (m256 >> 2)) * DM + 64 * nkv + 16 * (m256 & 3), 640 + 128 * rd, sb + B_G);
            } else tma_2d(sb + OFF_G, &P.qs, 32 * (c & 31), 256 * (c >> 5), sb + B_G);
          }
          rd++;
        }
      }
    }
    const uint32_t scr = sb + OFF_WR;
    float sx = s[0] + s[1], sq = s2[0] + s2[1];
    #pragma unroll
    for (int o = 1; o < 8; o <<= 1) { sx += __shfl_xor_sync(~0u, sx, o); sq += __shfl_xor_sync(~0u, sq, o); }
    float v = reduce8(ck, lane);
    v += __shfl_xor_sync(~0u, v, 2);
    if (!(lane & 2)) stsf(scr + (wp * 16 + 8 * (lane & 1) + (lane >> 2)) * 4, v);

    bar_sync(NB_ZERO, 160);
    if ((lane & 7) == 0) {
      const float mean = sx * (1.f / DM);
      st64_rlx(&G->stats[256 * m256 + 16 * nkv + (t >> 3)], tagw(mean, tg), tagw(rsqrtf(fmaxf(sq * (1.f / DM) - mean * mean, 0.f) + 1e-5f), tg));
    }
    if (wp == 1 && lane < 16) {
      const uint32_t a = scr + lane * 4;
      st32_rlx(&G->cskv[128 * nkv + 16 * m256 + lane], tagw((ldsf(a) + ldsf(a + 64)) + (ldsf(a + 128) + ldsf(a + 192)), tg));
    }
    __syncwarp();
    bar_arrive(NB_PUB, 192);
    const uint4 wv = ld128_keep(P.wr + t * 8);
    #pragma unroll 1
    for (int i = 0; i < 2; i++) {
      mbar_wait(sb + B_G, i ^ 1);
      const uint32_t a = sb + OFF_G + t * 16;
      const uint4 u0 = lds128(a), u1 = lds128(a + 2048), u2 = lds128(a + 4096), u3 = lds128(a + 6144);
      addc(u0, cs); addc(u1, cs); addc(u2, cs); addc(u3, cs);
      bar_sync(NB_WG2, 128);
      if (i == 0 && wp == 0 && elect_one()) { mbar_expect_tx(sb + B_G, 8192); tma_2d(sb + OFF_G, &P.qs, 32 * (c & 31), 256 * (c >> 5) + 128, sb + B_G); }
    }
    float sw = (bf_lo(wv.x) + bf_hi(wv.x)) + (bf_lo(wv.y) + bf_hi(wv.y)) + (bf_lo(wv.z) + bf_hi(wv.z)) + (bf_lo(wv.w) + bf_hi(wv.w));
    #pragma unroll
    for (int o = 16; o; o >>= 1) sw += __shfl_xor_sync(~0u, sw, o);
    if (lane == 0) stsf(sb + OFF_SUMWR + wp * 4, sw);
    if ((t >> 4) == j) {
      const uint32_t a = sb + OFF_WR + (t & 15) * 32;
      sts128(a, wv.x << 16, wv.x & 0xffff0000u, wv.y << 16, wv.y & 0xffff0000u);
      sts128(a + 16, wv.z << 16, wv.z & 0xffff0000u, wv.w << 16, wv.w & 0xffff0000u);
    }
    v = reduce8(cs, lane);
    stsf(sb + OFF_G + (wp * 32 + 8 * (lane & 3) + (lane >> 2)) * 4, v);
    bar_sync(NB_WG2, 128);
    if (wp == 0) {
      const uint32_t a = sb + OFF_G + lane * 4, cq = tagw((ldsf(a) + ldsf(a + 128)) + (ldsf(a + 256) + ldsf(a + 384)), tg);
      st32_rlx(&G->csq[(c >> 5) * DM + 32 * (c & 31) + lane], cq);
      if (lane == 0) mbar_arrive_at(sb + B_W, rank, (cq & P.zero) + 1);
    }
  }

  uint32_t xr[32];
  {
    const bool isq = wg == 2;
    float acc[2][64];
    {
      const uint32_t emptyb = mapa(sb + (isq ? B_EMPTY5 : B_EMPTYKV), t & 1);
      auto correct = [&](uint32_t xa, uint32_t xb) {
        wg_fence();
        wgmma_sa_n128<0, 1, H0, H0>(acc[0], dlo(SB0, 0) + (xa >> 4), dlo(SB0, 0) + (xb >> 4));
        wgmma_sa_n128<0, 1, H0, H0>(acc[1], dlo(SB0, 0) + (xa >> 4) + 64, dlo(SB0, 0) + (xb >> 4));
        wg_commit();
      };
      if (!isq) {
        mbar_wait(sb + B_S0, 0);
        if (wg) mbar_wait(sb + B_FULLKV, 0);
        #pragma unroll 1
        for (int kb = 0; kb < 16; kb++) {
          const uint32_t da = dlo(SB0, 16) + wg * 1024 + (kb & 3) * (KV_STAGE >> 4), db = dlo(SB0 + 32768, 8192) + (kb & 3) * (KV_STAGE >> 4);
          wg_fence();
          #pragma unroll
          for (int k = 0; k < 4; k++) {
            wgmma_ss_n128<0, 1, H128, H128>(acc[0], da + 2 * k, db + 128 * k, k > 0 || kb != 0);
            wgmma_ss_n128<0, 1, H128, H128>(acc[1], da + 512 + 2 * k, db + 128 * k, k > 0 || kb != 0);
          }
          wg_commit();
          wg_wait<1>();
          if (kb > 0 && t < 2) mbar_arrive_remote(emptyb + 8 * ((kb - 1) & 3), kb > 10 ? 3 : 1);
          if (kb < 15) mbar_wait(sb + B_FULLKV + 8 * ((kb + 1) & 3), ((kb + 1) >> 2) & 1);
          if (kb == 0) mbar_wait(sb + B_FULLKV, 0);
          if (kb == 15 - LAG && wg == 1) bar_sync(NB_LAG, 256);
        }
        bar_arrive(wg ? NB_QGO : NB_LAG, 256);
        mbar_wait(sb + B_AUX, 0);
        correct(OFF_AXK + wg * 2048, OFF_BXK);
        wg_wait<0>();
        if (t < 2) mbar_arrive_remote(emptyb + 24, 3);
        fence_regs(acc[0]); fence_regs(acc[1]);
      const uint32_t stg = sb + OFF_X + (1 - wg) * 24576;
      const uint32_t va = stg + 16384 + (16 * wp + (lane & 15)) * 64 + (((lane >> 4) ^ ((lane >> 1) & 3)) << 4);
      const uint32_t ra = sb + OFF_RS256 + (128 * wg + 16 * wp + g) * 4;
      const float rs[4] = {ldsf(ra), ldsf(ra + 32), ldsf(ra + 256), ldsf(ra + 288)};
      float p[2][16];
      uint32_t vf[16], kf[2][16];
      auto project = [&](const uint32_t (&f)[16], uint32_t db) {
        wg_fence();
        #pragma unroll
        for (int i = 0; i < 2; i++) {
          wgmma_rs_n32<1, H64>(p[i], f[8*i], f[8*i+1], f[8*i+2], f[8*i+3], db, 0);
          wgmma_ra_n32<1, H64>(p[i], f[8*i+4], f[8*i+5], f[8*i+6], f[8*i+7], db + 64);
        }
        wg_commit();
      };
      auto fold = [&](uint32_t (&f)[16], int col, float sc) {
        #pragma unroll
        for (int i = 0; i < 16; i++) {
          const float r = rs[2 * (i >> 3) + (i & 1)] * sc;
          f[i] = pack_bf16(acc[i >> 3][col + 2 * (i & 7)] * r, acc[i >> 3][col + 2 * (i & 7) + 1] * r);
          asm volatile("" : "+r"(f[i]));
        }
      };
      auto put_v = [&](const uint32_t (&f)[16]) {
        #pragma unroll
        for (int k = 0; k < 4; k++) stsm4((va ^ ((k & 1) << 5)) + (k >> 1) * 4096, f[4*k], f[4*k+1], f[4*k+2], f[4*k+3]);
      };
      fold(vf, 48, 1.f);
      mbar_wait(sb + B_W, 0);
      fold(kf[0], 0, LOG2E);
      #pragma unroll
      for (int i = 0; i < 32; i++) p[i >> 4][i & 15] = acc[i >> 4][i & 15];
      project(kf[0], dlo(SB0 + OFF_WPHIK, 16));
      mbar_wait(sb + B_W, 0);
      {
        uint32_t v0[16];
        fold(kf[1], 16, LOG2E);
        fold(v0, 32, 1.f);
        if (wg == 1) bar_sync(NB_DN, 256);
        put_v(v0);
      }
      wg_wait<0>();
      fence_regs(p[0]); fence_regs(p[1]);
      if (wg == 1) bar_arrive(NB_WG01, 256);
      #pragma unroll 1
      for (int h = 0; h < 2; h++) {
        uint32_t ph[4][8];
        float rsum[2][4];
        dual_exp2(p[0], ph[0], ph[1]); dual_exp2(p[1], ph[2], ph[3]);
        row_sums(rsum, ph, dlo(SB0 + OFF_SEL, 16));
        if (wg == 0 && h == 0) { bar_arrive(NB_DN, 256); bar_sync(NB_WG01, 256); }
        if (h == 1) {
          if (wg == 1) bar_sync(NB_DN, 256);
          put_v(vf);
        }
        wg_wait<0>();
        fence_regs(rsum[0]); fence_regs(rsum[1]);
        if (__builtin_expect(__any_sync(~0u, !((rsum[0][0] + rsum[0][1]) + (rsum[0][2] + rsum[0][3]) + (rsum[1][0] + rsum[1][1]) + (rsum[1][2] + rsum[1][3]) < EXP_LIM)), 0)) {
          dual_exp2_shifted(p, ph);
          #pragma unroll
          for (int i = 0; i < 8; i++) {
            const uint32_t* f = &ph[i >> 1][i & 1];
            float a = (bf_lo(f[0]) + bf_hi(f[0])) + (bf_lo(f[2]) + bf_hi(f[2])) + (bf_lo(f[4]) + bf_hi(f[4])) + (bf_lo(f[6]) + bf_hi(f[6]));
            a += __shfl_xor_sync(~0u, a, 1);
            rsum[i >> 2][2 * (i & 1) + ((i >> 1) & 1)] = a + __shfl_xor_sync(~0u, a, 2);
          }
        }
        if (h == 0) project(kf[1], dlo(SB0 + OFF_WPHIK1, 16));
        normalize(ph, rsum);
        #pragma unroll
        for (int i = 0; i < 8; i++) {
          const uint32_t* f = &ph[i >> 1][4 * (i & 1)];
          stsm4(((stg + sa) ^ ((i & 3) << 5)) + (i >> 2) * 8192, f[0], f[1], f[2], f[3]);
        }
        fence_async_smem();
        if (wg == h) {
          float kv[20];
          #pragma unroll
          for (int w = 0; w < 2; w++) {
            const uint32_t da = dlo(SB0 + OFF_X, 16) + (h ^ w ^ 1) * 1536, db = dlo(SB0 + OFF_X + 16384, OFF_ONES - OFF_X - 16384) - (h ^ w ^ 1) * (1536 * 65535);
            if (w) bar_sync(NB_ST, 256); else bar_sync(NB_L0 + h, 128);
            wg_fence();
            #pragma unroll
            for (int k = 0; k < 8; k++) {
              if (k == 0 && w == 0) wgmma_sz_n40<1, 1, H128, H64>(kv, da, db);
              else wgmma_sa_n40<1, 1, H128, H64>(kv, da + k * 128, db - k * (64 * 65535));
            }
            wg_commit();
          }
          float4* dst = &G->kvacc[(ha + 2 * h) * KVP + t];
          wg_wait<0>();
          fence_regs(kv);
          if (h == 0) bar_arrive(NB_DN, 256); else if (t < 2) { mbar_arrive_at(sb + B_EMPTY5 + 40, t, 2); if (t == 0) mbar_arrive(sb + B_KD); }
          kv[17] = kv[18];
          #pragma unroll
          for (int i = 0; i < 6; i++) red_add_f32x4(dst + 128 * i, kv[3*i], kv[3*i+1], kv[3*i+2], 1.f);
        } else bar_arrive(NB_ST, 256);
        wg_wait<0>();
        fence_regs(p[0]); fence_regs(p[1]);
      }
      #pragma unroll
      for (int i = 0; i < 32; i++) asm volatile("mov.b32 %0, 0;" : "=r"(xr[i]));
      } else {
        uint32_t so = 0, po = 0, par = 0;
        mbar_wait(sb + B_FULL5, 0);
        bar_sync(NB_QGO, 256);
        #pragma unroll 1
        for (int kb = 0; kb < 16 - ML; kb++) {
          const uint32_t da = dlo(SB0, 16) + so * 256, db = dlo(SB0 + 16384, 8192) + so * 256;
          #pragma unroll
          for (int k = 0; k < 4; k++) {
            wg_fence();
            wgmma_ss_n128<0, 1, H128, H128>(acc[0], da + 2 * k, db + 128 * k, k > 0 || kb != 0);
            wgmma_ss_n128<0, 1, H128, H128>(acc[1], da + 512 + 2 * k, db + 128 * k, k > 0 || kb != 0);
            wg_commit();
            if (k == 1 && kb > 0 && t < 2) mbar_arrive_remote(emptyb + po, 2);
            if (k == 3) {
              po = so; so += 8;
              if (so == 40) { so = 0; par ^= 1; }
              mbar_wait(sb + B_FULL5 + so, par);
            }
            if ((QW >> k) & 1) wg_wait<2>(); else wg_wait<1>();
          }
        }
        auto block = [&](const int kb, const int i) {
          wg_fence();
          #pragma unroll
          for (int k = 0; k < 4; k++) wgmma_sa_n128<0, 1, H128, H128>(acc[i], dlo(SB0, 16) + (kb % 5) * 2048 + 512 * i + 2 * k, dlo(SB0 + 16384, 8192) + (kb % 5) * 2048 + 128 * k);
          wg_commit();
        };
        auto hand_over = [&](const int i) {
          const uint32_t ta = sb + (1 + rank) * R5 + sa + i * 8192;
          #pragma unroll
          for (int k = 0; k < 4; k++) {
            const float* a = &acc[i][32 * (k >> 1) + 8 * (k & 1)];
            stsm4(ta ^ (k << 5), pack_bf16(a[0], a[1]), pack_bf16(a[2], a[3]), pack_bf16(a[4], a[5]), pack_bf16(a[6], a[7]));
          }
        };
        mbar_wait2(sb + B_AUXQ, 0, sb + B_OS, 0);
        correct(OFF_AXQ, OFF_BXQ);
        #pragma unroll
        for (int kb = 16 - ML; kb < 16; kb++) {
          block(kb, 0);
          if (kb < 15) mbar_wait(sb + B_FULL5 + 8 * ((kb + 1) % 5), ((kb + 1) / 5) & 1);
          if (kb == 16 - ML) { wg_wait<2>(); if (t < 2) mbar_arrive_remote(emptyb + 8 * ((kb - 1) % 5), 2); }
        }
        mbar_wait(sb + B_RC, 0);
        block(16 - ML, 1);
        block(17 - ML, 1);
        wg_wait<2>();
        fence_regs(acc[0]);
        hand_over(0);
        fence_async_smem();
        bar_arrive(NB_Q0, 256);
        #pragma unroll
        for (int kb = 18 - ML; kb <= 16; kb++) {
          wg_wait<1>();
          if (t < 2) mbar_arrive_remote(emptyb + 8 * ((kb - 2) % 5), 2);
          if (kb < 16) block(kb, 1);
        }
        mbar_wait(sb + B_RC + 8, 0);
        wg_wait<0>();
        if (t < 2) mbar_arrive_remote(emptyb, 2);
        fence_regs(acc[1]);
        hand_over(1);
        fence_async_smem();
        bar_arrive(NB_Q0 + 1, 256);
        #pragma unroll
        for (int i = 0; i < 32; i++) { const float* a = &acc[(i >> 3) & 1][16 + 32 * (i >> 4) + 2 * (i & 7)]; xr[i] = pack_bf16(a[0], a[1]); }
      }
    }
    float p[2][16];
    #pragma unroll
    for (int i = 0; i < 32; i++) asm volatile("mov.b32 %0, 0;" : "=f"(p[i >> 4][i & 15]));
    auto project_r = [&](int w) {
      wg_fence();
      #pragma unroll
      for (int h = 0; h < 2; h++) {
        wgmma_rs_n32<1, H64>(p[h], xr[8*h], xr[8*h+1], xr[8*h+2], xr[8*h+3], dlo(SB0 + OFF_WPHIQ, 16) + 128 * w, 0);
        wgmma_ra_n32<1, H64>(p[h], xr[8*h+4], xr[8*h+5], xr[8*h+6], xr[8*h+7], dlo(SB0 + OFF_WPHIQ, 16) + 128 * w + 64);
      }
      wg_commit();
    };
    auto capture = [&](const int i) {
      if (!i) mbar_wait(sb + B_R, 0);
      #pragma unroll
      for (int k = 0; k < 4; k++) ldsm4(((sb + (1 + rank) * R5 + wg * 8192 + sa) ^ (k << 5)) + i * 2 * R5, xr[16*i+4*k], xr[16*i+4*k+1], xr[16*i+4*k+2], xr[16*i+4*k+3]);
      const uint32_t one = (((xr[16*i] | xr[16*i+4]) | (xr[16*i+8] | xr[16*i+12])) & P.zero) + 1;
      if (lane == 0) mbar_arrive_at(sb + (i ? B_RX : B_RC + 8 * wg), i ? wg : rank, one);
    };
    const uint32_t rq = sb + OFF_RSQ + (16 * wp + g) * 4 + 256 * (wg & 1), rb = rq + 128 * (wg & 2);
    const float cc[2][2] = {{ldsf(rq) * LOG2E, ldsf(rq + 32) * LOG2E}, {ldsf(rb) * LOG2E, ldsf(rb + 32) * LOG2E}};
    {
      const uint4* src = reinterpret_cast<const uint4*>(&G->kvacc[(4 * j + wg) * KVP + t]);
      const uint32_t full = kv_count(__float_as_uint(ldsf(sb + OFF_EP)), 8);
      uint4 v[12];
      #pragma unroll
      for (int i = 0; i < 12; i++) v[i] = i < 6 || isq ? ld128_rlx(src + 128 * i) : make_uint4(0, 0, 0, full);
      if (isq) {
        project_r(2);
        wg_wait<0>();
        #pragma unroll
        for (int i = 0; i < 16; i++) xr[i] = xr[16 + i];
      } else {
        capture(0);
      }
      #pragma unroll 1
      for (uint32_t it = 0; it < POLL_LIMIT; it++) {
        uint32_t bad = 0;
        #pragma unroll
        for (int i = 0; i < 12; i++) bad |= v[i].w ^ full;
        if (!__any_sync(~0u, bad != 0)) break;
        #pragma unroll
        for (int i = 0; i < 12; i++) if (i < 6 || isq) v[i] = ld128_rlx(src + 128 * i);
      }
      mbar_wait(sb + B_KD, 0);
      #pragma unroll
      for (int e = 0; e < 2; e++) {
        if (e == 0 || isq) {
          float f[18];
          #pragma unroll
          for (int i = 0; i < 6; i++) { f[3*i] = __uint_as_float(v[6*e+i].x); f[3*i+1] = __uint_as_float(v[6*e+i].y); f[3*i+2] = __uint_as_float(v[6*e+i].z); }
          const uint32_t ka = sb + OFF_KVZ + (wg + e) * 5120 + wp * 1280 + lane * 16;
          stsm4(ka, pack_bf16(f[0], f[1]), pack_bf16(f[2], f[3]), pack_bf16(f[4], f[5]), pack_bf16(f[6], f[7]));
          stsm4(ka + 512, pack_bf16(f[8], f[9]), pack_bf16(f[10], f[11]), pack_bf16(f[12], f[13]), pack_bf16(f[14], f[15]));
          stsm2(ka + 1024, pack_bf16(f[16], 1.f), pack_bf16(f[17], 1.f));
        }
      }
    }
    fence_async_smem();
    if (wg == 1) bar_arrive(NB_DN, 256);
    #pragma unroll 1
    for (int e = wg; e < wg + 1 + (wg >> 1); e++) {
      const int half = e >> 1, hh = e & 1, turn = e;
      const uint32_t ao = (1 + rank) * R5 + hh * 8192;
      uint32_t ph[4][8];
      #pragma unroll
      for (int i = 0; i < 32; i++) asm volatile("mov.b32 %0, 0;" : "=r"(ph[i >> 3][i & 7]));
      uint32_t shifted = 0;
      asm volatile("" : "+r"(shifted));
      #pragma unroll 1
      for (;;) {
        if (shifted) dual_exp2_shifted(p, ph);
        uint32_t first = (shifted ^ 1) & !isq;
        asm volatile("" : "+r"(first));
        if (first) {
          bar_sync(NB_Q0 + wg, 256);
          const uint32_t da = dlo(SB0, 16) + (ao >> 4), db = dlo(SB0 + OFF_WPHIQ, 16);
          wg_fence();
          #pragma unroll
          for (int h = 0; h < 2; h++) {
            wgmma_ss_n32<0, 1, H128, H64>(p[h], da + 4 * h, db + 128 * h, 0);
            wgmma_sa_n32<0, 1, H128, H64>(p[h], da + 4 * h + 2, db + 128 * h + 64);
          }
          wg_commit();
          capture(1);
          wg_wait<0>();
        }
        fence_regs(p[0]); fence_regs(p[1]);
        uint32_t again = shifted;
        asm volatile("" : "+r"(again));
        if (again) break;
        float s2[4] = {0.f, 0.f, 0.f, 0.f};
        #pragma unroll
        for (int i = 0; i < 32; i++) { float& x = p[i >> 4][i & 15]; x *= cc[i >> 4][(i >> 1) & 1]; s2[i & 3] = fmaf(x, x, s2[i & 3]); }
        if (!__any_sync(~0u, !((s2[0] < ARG_LIM2) & (s2[1] < ARG_LIM2) & (s2[2] < ARG_LIM2) & (s2[3] < ARG_LIM2)))) break;
        shifted = 1;
      }
      if (e == 1 || e == 2) bar_sync(NB_TOK + e - 1, 256);
      float ac[4][20];
      auto numer = [&](int h) {
        const uint32_t (*f)[8] = &ph[2 * h];
        const uint32_t db = dlo(SB0 + OFF_KVZ, 128) + (half ? e : h) * 320;
        wg_fence();
        #pragma unroll
        for (int i = 0; i < 2; i++) {
          wgmma_rz_n40<1, dhi(256, 0)>(ac[2*h+i], f[i][0], f[i][1], f[i][2], f[i][3], db + i * 160);
          wgmma_ra_n40<1, dhi(256, 0)>(ac[2*h+i], f[i][4], f[i][5], f[i][6], f[i][7], db + (i * 160 + 80));
        }
        wg_commit();
      };
      const uint32_t oa = (16 * wp + g) * 128 + (((lane & 3) ^ g) << 4);
      auto finish = [&](int h) {
        const float* ap = ac[2 * h]; const float* am = ac[2 * h + 1];
        const float ip0 = rcp(ap[17]), im0 = rcp(am[17]), ip1 = rcp(ap[19]), im1 = rcp(am[19]);
        const float d0 = rcp(fmaf(ap[16], ip0, fmaf(am[16], im0, 1e-6f))), d1 = rcp(fmaf(ap[18], ip1, fmaf(am[18], im1, 1e-6f)));
        const float a0 = ip0 * d0, b0 = im0 * d0, a1 = ip1 * d1, b1 = im1 * d1;
        #pragma unroll
        for (int r = 0; r < 2; r++) {
          const float a = r ? a1 : a0, b = r ? b1 : b0;
          uint32_t w[4];
          #pragma unroll
          for (int k = 0; k < 4; k++) w[k] = pack_bf16(fmaf(ap[4*k+2*r], a, am[4*k+2*r] * b), fmaf(ap[4*k+2*r+1], a, am[4*k+2*r+1] * b));
          const uint32_t off = (oa ^ ((half ? rank : h) << 6)) + r * 1024;
          st128_rlx(reinterpret_cast<uint8_t*>(G->o + (m128 * 16 + (half ? 2 * (j & 6) + 2 * hh + 1 : 2 * j)) * 8192 + (half ? h : hh) * 4096) + off, w[0], w[1], w[2], w[3]);
          if (!half) sts128(sb + ao + off, w[0], w[1], w[2], w[3]);
        }
        if ((half || h) && lane < 8) st32_rlx(&G->oflag[((m128 * 6 + (half ? 2 * e - 2 + h : hh)) * 32 + 4 * j + wp) * 8 + lane], 1);
      };
      if (!shifted) dual_exp2(p[0], ph[0], ph[1]);
      numer(0);
      if (!shifted) dual_exp2(p[1], ph[2], ph[3]);
      if (turn < 2) bar_arrive(NB_TOK + turn, 256);
      if (wg == 0) bar_sync(NB_DN, 256);
      numer(1);
      wg_wait<1>();
      fence_regs(ac[0]); fence_regs(ac[1]);
      finish(0);
      wg_wait<0>();
      fence_regs(ac[2]); fence_regs(ac[3]);
      #pragma unroll
      for (int i = 0; i < 32; i++) asm volatile("mov.b32 %0, 0;" : "=f"(p[i >> 4][i & 15]));
      if (e == 2) project_r(3);
      finish(1);
      if (!half) fence_async_smem();
      __syncwarp();
      if (lane == 0) mbar_arrive(sb + B_UO + 8 * e);
      wg_wait<0>();
    }
    if (isq) cluster_arrive();
  }

  {
  int lane;
  asm volatile("mov.u32 %0, %%laneid;" : "=r"(lane));
  const int g = lane >> 2, q = lane & 3;
  if (wg < 2) {
    float h[64];
    {
      #pragma unroll
      for (int i = 0; i < 32; i++) { h[2*i] = bf_lo(xr[i]); h[2*i+1] = bf_hi(xr[i]); }
      fence_regs(h);
      const uint32_t emptyb = mapa(sb + B_EMPTY5, t & 1);
      uint32_t s = 1 + rank, ps = 0;
      mbar_wait2(sb + B_GB + 8 * rank, 0, sb + B_UO + 8 * wg, 0);
      #pragma unroll
      for (int i = 0; i < 16; i++) {
        const uint32_t da = dlo(SB0, 16) + s * 2048 + wg * 512, db = dlo(SB0 + 16384, 8192) + s * 2048;
        wg_fence();
        #pragma unroll
        for (int k = 0; k < 4; k++) wgmma_sa_n128<0, 1, H128, H128>(h, da + k * 2, db + k * 128);
        wg_commit();
        const uint32_t ns = i ? (i + 2) % 6 : 2 - rank;
        const uint32_t nb = i ? i + 1 : 1 - rank, b0 = sb + B_GB + 8 * nb, b1 = sb + B_GA + 16 * nb + 8 * wg;
        const bool here = i == 15 || mbar_test2(b0, 0, b1, 0);
        wg_wait<1>();
        if (!(((2 * REL + 1) >> i) & 1) && i < 14 && t < 2) mbar_arrive_remote(emptyb + 8 * ps, 1);
        if ((REL >> i) & 1) { wg_wait<0>(); if (t < 2) mbar_arrive_remote(emptyb + 8 * s, 1); }
        if (!here) mbar_wait2(b0, 0, b1, 0);
        ps = s; s = ns;
      }
    }
    cluster_arrive();
    float2 wr[16];
    #pragma unroll
    for (int i = 0; i < 16; i++) wr[i] = lds64f(sb + OFF_WR + 32 * i + 8 * q);
    const int r0 = 64 * wg + 16 * wp + g;
    float sum0, sum1, dot0, dot1, sq0, sq1;
    uint32_t redo = 0;
    asm volatile("" : "+r"(redo));
    #pragma unroll 1
    for (;;) {
    if (redo) {
      wg_wait<0>();
      const uint32_t* xp = reinterpret_cast<const uint32_t*>(P.x + (size_t)(128 * m128 + r0) * DM + 128 * j) + q;
      #pragma unroll
      for (int i = 0; i < 32; i++) { const uint32_t v = xp[4 * (i >> 1) + (i & 1) * 4 * DM]; h[2*i] = bf_lo(v); h[2*i+1] = bf_hi(v); }
      #pragma unroll 1
      for (int ks = 0; ks < 64; ks++) {
        const int kb = ks >> 2, kk = 16 * (ks & 3);
        const bf16* op = G->o + (m128 * 16 + kb) * 8192 + r0 * 64 + 2 * q;
        const int o0 = ((kk >> 3) ^ g) << 3;
        const uint32_t* w = reinterpret_cast<const uint32_t*>(P.wo_p + (size_t)(((kb & 1) ? 256 * (kb >> 2) + 32 * (kb & 2) + 32 + 4 * (kk & 32) : 64 * kb + 2 * (kk & 32)) +
                                                                              ((kk & 16) >> 2) + 4 * (g & 6) + (g & 1)) * DM + 128 * j) + q;
        uint32_t b[32], a0, a1, a2, a3, it = 0;
        #pragma unroll
        for (int n = 0; n < 32; n++) b[n] = w[4 * (n >> 1) + (n & 1) * DM];
        do { a0 = ld32_rlx(op + o0); a1 = ld32_rlx(op + 512 + o0); a2 = ld32_rlx(op + (o0 ^ 8)); a3 = ld32_rlx(op + 512 + (o0 ^ 8)); }
        while (max(max(a0, a1), max(a2, a3)) == ~0u && ++it < POLL_LIMIT);
        __syncwarp();
        #pragma unroll
        for (int n = 0; n < 16; n++) mma16816(h[4*n], h[4*n+1], h[4*n+2], h[4*n+3], a0, a1, a2, a3, transpose8(b[2*n]), transpose8(b[2*n+1]));
      }
    }
    wg_wait<0>();
    fence_regs(h);
    sum0 = 0.f, sum1 = 0.f, dot0 = 0.f, dot1 = 0.f, sq0 = 0.f, sq1 = 0.f;
    #pragma unroll
    for (int i = 0; i < 16; i++) {
      sum0 += h[4*i] + h[4*i+1]; sum1 += h[4*i+2] + h[4*i+3];
      sq0 = fmaf(h[4*i], h[4*i], fmaf(h[4*i+1], h[4*i+1], sq0)); sq1 = fmaf(h[4*i+2], h[4*i+2], fmaf(h[4*i+3], h[4*i+3], sq1));
      dot0 = fmaf(h[4*i], wr[i].x, fmaf(h[4*i+1], wr[i].y, dot0)); dot1 = fmaf(h[4*i+2], wr[i].x, fmaf(h[4*i+3], wr[i].y, dot1));
    }
    if (!__any_sync(~0u, !redo & (h[0] != h[0] | h[2] != h[2]))) break;
    redo = 1;
    }
    float4* const rs = &G->rstat[128 * m128 + r0];
    {
      const bool up = q & 2;
      float a = up ? sum1 : sum0, b = up ? sq1 : sq0, d = up ? dot1 : dot0;
      a += __shfl_xor_sync(~0u, up ? sum0 : sum1, 2); b += __shfl_xor_sync(~0u, up ? sq0 : sq1, 2); d += __shfl_xor_sync(~0u, up ? dot0 : dot1, 2);
      a += __shfl_xor_sync(~0u, a, 1); b += __shfl_xor_sync(~0u, b, 1); d += __shfl_xor_sync(~0u, d, 1);
      if ((q & 1) == 0) red_add_f32x4(rs + 4 * q, a, b, d, 1.f);
    }
    float rstd[2], bm[2];
    uint32_t best, it = 0;
    {
      const float2 swa = lds64f(sb + OFF_SUMWR), swb = lds64f(sb + OFF_SUMWR + 8);
      const float sw = (swa.x + swa.y) + (swb.x + swb.y);
      uint4 a[2]; uint32_t key[2];
      do { a[0] = ld128_rlx(rs); a[1] = ld128_rlx(rs + 8); } while (__any_sync(~0u, (a[0].w & a[1].w) != 0x41000000u) && ++it < POLL_LIMIT);
      #pragma unroll
      for (int i = 0; i < 2; i++) {
        const float mean = __uint_as_float(a[i].x) * (1.f / DM);
        rstd[i] = rsqrtf(fmaxf(__uint_as_float(a[i].y) * (1.f / DM) - mean * mean, 0.f) + 1e-5f);
        bm[i] = -mean * rstd[i];
        const uint32_t rr = __float_as_uint(fmaf(__uint_as_float(a[i].z), rstd[i], sw * bm[i]));
        key[i] = ((rr ^ ((uint32_t)((int32_t)rr >> 31) | 0x80000000u)) & ~2047u) | (2047 - 128 * m128 - r0 - 8 * i);
      }
      asm volatile("redux.sync.max.u32 %0, %1, 0xffffffff;" : "=r"(best) : "r"(max(key[0], key[1])));
    }
    sts32(sb + OFF_BEST + 4 * warp, best);
    bar_sync(NB_WG01, 256);
    {
      const uint4 b0 = lds128(sb + OFF_BEST), b1 = lds128(sb + OFF_BEST + 16);
      best = max(max(max(b0.x, b0.y), max(b0.z, b0.w)), max(max(b1.x, b1.y), max(b1.z, b1.w)));
    }
    const int win = ~best & 127;
    if (warp == ((win >> 4) ^ 1) && (lane < 4 || it == 0)) st128_rlx(&G->key[((2 * j + (lane >> 1)) & 15) * 128 + 8 * m128 + 4 * (lane & 1)], best, best, best, best);
    if ((win & 0x77) == r0) {
      const bool up = win & 8;
      const float ra = up ? rstd[1] : rstd[0], rb = up ? bm[1] : bm[0];
      uint32_t x[16];
      #pragma unroll
      for (int i = 0; i < 16; i++) x[i] = pack_bf16(fmaf(up ? h[4*i+2] : h[4*i], ra, rb), fmaf(up ? h[4*i+3] : h[4*i+1], ra, rb));
      #pragma unroll
      for (int i = 0; i < 4; i++) st128_rlx(&G->cand[m128 * 512 + 64 * j + 16 * i + 4 * q], x[4*i], x[4*i+1], x[4*i+2], x[4*i+3]);
    }
    __syncwarp();
    bar_arrive(NB_G2E, 384);
    {
      const float a0 = 1.f + rstd[0], b0 = bm[0], a1 = 1.f + rstd[1], b1 = bm[1];
      #pragma unroll
      for (int k = 0; k < 8; k++)
        stsm4(((sb + OFF_OUT + wg * 8192 + sa) ^ ((k & 3) << 5)) + (k >> 2) * 16384,
              pack_bf16(fmaf(h[8*k], a0, b0), fmaf(h[8*k+1], a0, b0)),     pack_bf16(fmaf(h[8*k+2], a1, b1), fmaf(h[8*k+3], a1, b1)),
              pack_bf16(fmaf(h[8*k+4], a0, b0), fmaf(h[8*k+5], a0, b0)),   pack_bf16(fmaf(h[8*k+6], a1, b1), fmaf(h[8*k+7], a1, b1)));
      fence_async_smem();
      __syncwarp();
      if (lane == 0) mbar_arrive(sb + B_OUT + 8 * wg);
    }
    {
      uint32_t wa[8][4][4];
      const uint32_t wb = sb + 16384 * (((uint32_t)FF_SLOT >> (4 * warp)) & 15) + ((lane & 7) + ((lane >> 4) << 3)) * 64 + ((((lane >> 3) & 1) ^ ((lane >> 1) & 3)) << 4);
      if (f < NFFN) mbar_wait(sb + B_F + 8 * warp, 0);
      #pragma unroll
      for (int i = 0; i < 32; i++) ldsm4t((wb ^ ((i & 1) << 5)) + ((i >> 1) & 1) * 8192 + (i >> 2) * 1024, wa[i >> 2][i & 3][0], wa[i >> 2][i & 3][1], wa[i >> 2][i & 3][2], wa[i >> 2][i & 3][3]);
      bar_sync(NB_XS, 384);
      uint4 xs[4];
      #pragma unroll
      for (int i = 0; i < 4; i++) xs[i] = lds128(sb + OFF_XSEL + 256 * warp + 64 * i + 16 * q);
      float d[4][4];
      #pragma unroll
      for (int ks = 0; ks < 8; ks++) {
        #pragma unroll
        for (int m = 0; m < 4; m++) {
          if (ks == 0) { d[m][0] = 0.f; d[m][1] = 0.f; d[m][2] = 0.f; d[m][3] = 0.f; }
          mma16816(d[m][0], d[m][1], d[m][2], d[m][3], wa[ks][m][0], wa[ks][m][1], wa[ks][m][2], wa[ks][m][3],
                   (ks & 1) ? xs[ks >> 1].z : xs[ks >> 1].x, (ks & 1) ? xs[ks >> 1].w : xs[ks >> 1].y);
        }
      }
      if (q == 0) {
        #pragma unroll
        for (int m = 0; m < 8; m++) stsf(sb + OFF_GU + (8 * m + g) * 48 + 4 * warp, d[m >> 1][2 * (m & 1)]);
      }
      bar_arrive(NB_ACT, 384);
    }
    {
      const uint32_t ky = __float_as_uint(ldsf(sb + OFF_KEY));
      const int row = 2047 - (ky & 2047) - 128 * m128;
      if ((uint32_t)row < 128u) {
        const int vi = (j & 1) + wg, e = 3 * vi + q - 4 * (j & 1);
        const float kr = __uint_as_float((ky & ~2047u) ^ ((ky >> 31) ? 0x80000000u : 0xfffff800u));
        const int col = 32 * wp + 16 * (e & 1) + 4 * (e & 2) + g;
        const float sg = rcp(1.f + ex2(-LOG2E * kr));
        const uint32_t base = __float_as_uint(ldsf(sb + OFF_OUT + (col >> 6) * 16384 + row * 128 + ((((col >> 3) ^ row) & 7) << 4) + 2 * (col & 6)));
        const float4* yp = &G->yacc[(q * 3 + vi) * 128 + 32 * (j >> 1) + 8 * wp + g];
        uint32_t it = 0;
        uint4 v;
        mbar_wait(sb + B_SD, 0);
        do { v = ld128_rlx(yp); } while (__any_sync(~0u, __uint_as_float(v.w) != (float)(NFFN / 4)) && ++it < POLL_LIMIT);
        float y0 = __uint_as_float(v.x), y1 = __uint_as_float(v.y), y2 = __uint_as_float(v.z);
        #pragma unroll
        for (int o = 1; o < 4; o <<= 1) { y0 += __shfl_xor_sync(~0u, y0, o); y1 += __shfl_xor_sync(~0u, y1, o); y2 += __shfl_xor_sync(~0u, y2, o); }
        if (q < 3 && (uint32_t)e < 4u)
          P.out_p[(size_t)(128 * m128 + row) * DM + 128 * j + col] = __float2bfloat16(fmaf(q == 0 ? y0 : q == 1 ? y1 : y2, sg, (col & 1) ? bf_hi(base) : bf_lo(base)));
      }
      if (c == 0 && tid == 0) st32_rlx(&G->epoch, __float_as_uint(ldsf(sb + OFF_EP)));
    }
  }
  if (wg == 2) {
    uint32_t wf[16][2][4];
    {
      const uint32_t wb = sb + OFF_S + 16384 * (wp & 1) + ((lane & 7) + ((lane >> 4) << 3)) * 128 + ((((lane >> 3) & 1) ^ (lane & 7)) << 4);
      if (f < NFFN) mbar_wait(sb + B_WD + 8 * wp, 0);
      #pragma unroll
      for (int i = 0; i < 32; i++) ldsm4t((wb ^ (((i >> 1) & 3) << 5)) + (i >> 3) * 4096 + (i & 1) * 2048, wf[i >> 1][i & 1][0], wf[i >> 1][i & 1][1], wf[i >> 1][i & 1][2], wf[i >> 1][i & 1][3]);
      fence_async_smem();
      __syncwarp();
      if (lane == 0) mbar_arrive(sb + B_WC + 8 * wp);
    }
    bar_sync(NB_G2E, 384);
    {
      uint32_t cur = 0;
      uint4 v;
      #pragma unroll 1
      for (uint32_t it = 0; it < POLL_LIMIT; it++) {
        const uint32_t kx = ld32_rlx(&G->key[(c & 15) * 128 + 8 * (lane & 15)]);
        v = ld128_rlx(&G->cand[((~cur >> 7) & 15) * 512 + 4 * t]);
        uint32_t best;
        asm volatile("redux.sync.max.u32 %0, %1, 0xffffffff;" : "=r"(best) : "r"(kx));
        if (!__any_sync(~0u, kx == 0 || v.w == ~0u) && best == cur) break;
        cur = best;
      }
      sts128(sb + OFF_XSEL + 16 * t, v.x, v.y, v.z, v.w);
      sts32(sb + OFF_KEY, cur);
      bar_arrive(NB_XS, 384);
      bar_sync(NB_ACT, 384);
    }
    float gu[2];
    #pragma unroll
    for (int i = 0; i < 2; i++) {
      const uint4 v0 = lds128(sb + OFF_GU + (32 * i + lane) * 48), v1 = lds128(sb + OFF_GU + (32 * i + lane) * 48 + 16);
      gu[i] = ((__uint_as_float(v0.x) + __uint_as_float(v0.y)) + (__uint_as_float(v0.z) + __uint_as_float(v0.w))) +
              ((__uint_as_float(v1.x) + __uint_as_float(v1.y)) + (__uint_as_float(v1.z) + __uint_as_float(v1.w)));
    }
    const float act = gu[0] * gu[1] * rcp(1.f + ex2(-LOG2E * gu[0]));
    const uint32_t ap = pack_bf16(act, __shfl_down_sync(~0u, act, 1));
    uint32_t bf[4];
    #pragma unroll
    for (int i = 0; i < 4; i++) bf[i] = __shfl_sync(~0u, ap, 2 * q + 8 * i);
    float d[16][4];
    #pragma unroll
    for (int k = 0; k < 2; k++)
      #pragma unroll
      for (int i = 0; i < 16; i++) {
        if (k == 0) { d[i][0] = 0.f; d[i][1] = 0.f; d[i][2] = 0.f; d[i][3] = 0.f; }
        mma16816(d[i][0], d[i][1], d[i][2], d[i][3], wf[i][k][0], wf[i][k][1], wf[i][k][2], wf[i][k][3], bf[2*k], bf[2*k+1]);
      }
    float y[9];
    #pragma unroll
    for (int e = 0; e < 8; e++) {
      const int n = 2 * (e & 4) + (e & 1);
      const float lo = (q & 1) ? d[n + 2][e & 2] : d[n][e & 2], hi = (q & 1) ? d[n + 6][e & 2] : d[n + 4][e & 2];
      y[e] = (q & 2) ? hi : lo;
    }
    y[8] = 0.f;
    if (f < NFFN) {
      #pragma unroll
      for (int i = 0; i < 3; i++) red_add_f32x4(&G->yacc[((f & 3) * 3 + i) * 128 + 32 * wp + 8 * q + g], y[3*i], y[3*i+1], y[3*i+2], 1.f);
    }
  }
  }
  cluster_wait();
}

typedef CUresult (*EncodeFn)(CUtensorMap*, CUtensorMapDataType, cuuint32_t, void*, const cuuint64_t*, const cuuint64_t*,
                             const cuuint32_t*, const cuuint32_t*, CUtensorMapInterleave, CUtensorMapSwizzle,
                             CUtensorMapL2promotion, CUtensorMapFloatOOBfill);

void make_map(EncodeFn enc, CUtensorMap* m, const void* p, int n, const cuuint64_t* dims, const cuuint64_t* str, const cuuint32_t* box,
              CUtensorMapSwizzle sw, CUtensorMapL2promotion promo) {
  cuuint32_t es[5] = {1, 1, 1, 1, 1};
  enc(m, CU_TENSOR_MAP_DATA_TYPE_BFLOAT16, n, const_cast<void*>(p), dims, str, box, es, CU_TENSOR_MAP_INTERLEAVE_NONE, sw, promo,
      CU_TENSOR_MAP_FLOAT_OOB_FILL_NONE);
}
void map2(EncodeFn enc, CUtensorMap* m, const void* p, uint64_t cols, uint64_t rows, uint32_t bc, uint32_t br, CUtensorMapSwizzle sw,
          CUtensorMapL2promotion promo) {
  const cuuint64_t dims[2] = {cols, rows}, str[1] = {cols * 2};
  const cuuint32_t box[2] = {bc, br};
  make_map(enc, m, p, 2, dims, str, box, sw, promo);
}
void map3(EncodeFn enc, CUtensorMap* m, const void* p, uint64_t cols, uint64_t rows, uint32_t br, uint32_t nb) {
  const cuuint64_t dims[3] = {64, rows, cols / 64}, str[2] = {cols * 2, 128};
  const cuuint32_t box[3] = {64, br, nb};
  make_map(enc, m, p, 3, dims, str, box, CU_TENSOR_MAP_SWIZZLE_128B, CU_TENSOR_MAP_L2_PROMOTION_L2_128B);
}

}

extern "C" void kernel_launch(void* const* d_in, const int* in_sizes, int n_in, void* d_out, int out_size) {
  (void)in_sizes; (void)n_in; (void)out_size;
  static EncodeFn enc = nullptr;
  static void* o_ptr = nullptr;
  if (!enc) {
    void* f = nullptr; cudaDriverEntryPointQueryResult qr;
    cudaGetDriverEntryPoint("cuTensorMapEncodeTiled", &f, cudaEnableDefault, &qr);
    enc = (EncodeFn)f;
    cudaGetSymbolAddress(&o_ptr, g_scr);
    cudaFuncSetAttribute(fused_kernel, cudaFuncAttributeMaxDynamicSharedMemorySize, SMEM_BYTES);
  }
  const bf16* x = (const bf16*)d_in[0];
  const bf16* wqkv = (const bf16*)d_in[1];
  const bf16* wphi = (const bf16*)d_in[2];
  const bf16* wo = (const bf16*)d_in[3];
  const bf16* wr = (const bf16*)d_in[5];
  const bf16* wgate = (const bf16*)d_in[6];
  const bf16* wup = (const bf16*)d_in[7];
  const bf16* wdown = (const bf16*)d_in[8];
  Params P;
  const CUtensorMapSwizzle S128 = CU_TENSOR_MAP_SWIZZLE_128B, S64 = CU_TENSOR_MAP_SWIZZLE_64B;
  const CUtensorMapL2promotion L128 = CU_TENSOR_MAP_L2_PROMOTION_L2_128B, L256 = CU_TENSOR_MAP_L2_PROMOTION_L2_256B,
                               L64 = CU_TENSOR_MAP_L2_PROMOTION_L2_64B;
  map2(enc, &P.x128, x, DM, SEQ, 64, 128, S128, L128);
  map2(enc, &P.x64, x, DM, SEQ, 64, 64, S128, L128);
  {
    const cuuint64_t dims[4] = {64, DM, 16, 3}, str[3] = {6 * DM, 128, 2 * DM};
    const cuuint32_t box[4] = {64, 64, 1, 2};
    make_map(enc, &P.wkv, wqkv, 4, dims, str, box, S128, L128);
  }
  map3(enc, &P.wq, wqkv, 3 * DM, DM, 64, 2);
  for (int i = 0; i < 2; i++) {
    const cuuint64_t dims[5] = {DM, (cuuint64_t)(DM - 94 - 64 * i), 4, 4, 2}, str[4] = {2 * DM, 16 * DM, 4 * DM, (cuuint64_t)(128 * DM) << i};
    const cuuint32_t box[5] = {64, 2, 4, 4, 2};
    make_map(enc, &P.wo[i], wo, 5, dims, str, box, S128, L128);
  }
  map3(enc, &P.wd, wdown, DM, FF, 32, 4);
  map2(enc, &P.wg, wgate, FF, DM, 32, 128, S64, L64);
  map2(enc, &P.wu, wup, FF, DM, 32, 128, S64, L64);
  map2(enc, &P.tg, wgate, FF, DM, 8, 16, CU_TENSOR_MAP_SWIZZLE_NONE, L128);
  map2(enc, &P.tu, wup, FF, DM, 8, 16, CU_TENSOR_MAP_SWIZZLE_NONE, L128);
  map2(enc, &P.td, wdown, 128, FF * 8, 8, 16, CU_TENSOR_MAP_SWIZZLE_NONE, L256);
  map2(enc, &P.xs, x, DM, SEQ, 128, 16, CU_TENSOR_MAP_SWIZZLE_NONE, L256);
  map2(enc, &P.ws, wqkv, 3 * DM, DM, 16, 128, CU_TENSOR_MAP_SWIZZLE_NONE, L128);
  map2(enc, &P.qs, wqkv, 3 * DM, DM, 32, 128, CU_TENSOR_MAP_SWIZZLE_NONE, L64);
  map2(enc, &P.out, d_out, DM, SEQ, 64, 16, S128, L128);
  map2(enc, &P.o, o_ptr, 256, SEQ * DM / 256, 256, 16, CU_TENSOR_MAP_SWIZZLE_NONE, L128);
  map2(enc, &P.phi, wphi, 32, 1024, 32, 32, S64, L64);
  P.x = x; P.wqkv = wqkv; P.wo_p = wo; P.wr = wr; P.out_p = (bf16*)d_out; P.g = (Scratch*)o_ptr; P.zero = 0;

  cudaLaunchConfig_t cfg = {};
  cfg.gridDim = dim3(128); cfg.blockDim = dim3(512); cfg.dynamicSmemBytes = SMEM_BYTES; cfg.stream = cudaStreamPerThread;
  cudaLaunchAttribute at[1];
  at[0].id = cudaLaunchAttributeClusterDimension; at[0].val.clusterDim.x = 2; at[0].val.clusterDim.y = 1; at[0].val.clusterDim.z = 1;
  cfg.attrs = at; cfg.numAttrs = 1;
  cudaLaunchKernelEx(&cfg, fused_kernel, P);
}
```

```cpp
#include <cuda_runtime.h>
#include <cuda.h>
#include <cuda_bf16.h>
#include <stdint.h>

namespace {

typedef __nv_bfloat16 bf16;

__device__ __forceinline__ uint32_t smem_u32(const void* p){ return (uint32_t)__cvta_generic_to_shared(p); }
__device__ __forceinline__ void mbar_init(uint32_t bar, uint32_t cnt){ asm volatile("mbarrier.init.shared::cta.b64 [%0], %1;"::"r"(bar),"r"(cnt):"memory"); }
__device__ __forceinline__ void mbar_expect_tx(uint32_t bar, uint32_t bytes){ asm volatile("mbarrier.arrive.expect_tx.shared::cta.b64 _, [%0], %1;"::"r"(bar),"r"(bytes):"memory"); }
__device__ __forceinline__ void mbar_arrive(uint32_t bar){ asm volatile("mbarrier.arrive.shared::cta.b64 _, [%0];"::"r"(bar):"memory"); }
__device__ __forceinline__ uint32_t mapa(uint32_t addr, uint32_t cta){ uint32_t r; asm volatile("mapa.shared::cluster.u32 %0, %1, %2;":"=r"(r):"r"(addr),"r"(cta)); return r; }
__device__ __forceinline__ void mbar_arrive_at(uint32_t bar, uint32_t cta, uint32_t cnt){
  asm volatile("{\n.reg .b32 ra;\nmapa.shared::cluster.u32 ra, %0, %1;\nmbarrier.arrive.shared::cluster.b64 _, [ra], %2;\n}\n"::"r"(bar),"r"(cta),"r"(cnt):"memory"); }
__device__ __forceinline__ void mbar_arrive_remote(uint32_t cluster_addr, uint32_t cnt){
  asm volatile("mbarrier.arrive.shared::cluster.b64 _, [%0], %1;"::"r"(cluster_addr),"r"(cnt):"memory"); }
__device__ __forceinline__ void mbar_wait(uint32_t bar, uint32_t parity){
  asm volatile("{\n.reg .pred p;\n.reg .u32 c;\nmov.u32 c, 0;\nLW:\nmbarrier.try_wait.parity.shared::cta.b64 p, [%0], %1;\n@p bra LD;\nadd.u32 c, c, 1;\nsetp.lt.u32 p, c, 2000000;\n@p bra LW;\ntrap;\nLD:\n}\n"::"r"(bar),"r"(parity):"memory"); }
__device__ __forceinline__ void mbar_wait2(uint32_t bar0, uint32_t par0, uint32_t bar1, uint32_t par1){
  asm volatile("{\n.reg .pred p, q;\n.reg .u32 c;\nmov.u32 c, 0;\nLW:\nmbarrier.try_wait.parity.shared::cta.b64 p, [%0], %1;\nmbarrier.try_wait.parity.shared::cta.b64 q, [%2], %3;\nand.pred p, p, q;\n@p bra LD;\nadd.u32 c, c, 1;\nsetp.lt.u32 p, c, 2000000;\n@p bra LW;\ntrap;\nLD:\n}\n"::"r"(bar0),"r"(par0),"r"(bar1),"r"(par1):"memory"); }
__device__ __forceinline__ void mbar_wait2u(uint32_t bar0, uint32_t bar1){
  asm volatile("{\n.reg .pred p, q;\nLW:\nmbarrier.try_wait.parity.shared::cta.b64 p, [%0], 0;\nmbarrier.try_wait.parity.shared::cta.b64 q, [%1], 0;\nand.pred p, p, q;\n@!p bra LW;\n}\n"::"r"(bar0),"r"(bar1):"memory"); }
__device__ __forceinline__ bool mbar_test2(uint32_t bar0, uint32_t par0, uint32_t bar1, uint32_t par1){
  uint32_t r;
  asm volatile("{\n.reg .pred p, q;\nmbarrier.test_wait.parity.shared::cta.b64 p, [%1], %2;\nmbarrier.test_wait.parity.shared::cta.b64 q, [%3], %4;\nand.pred p, p, q;\nselp.u32 %0, 1, 0, p;\n}\n":"=r"(r):"r"(bar0),"r"(par0),"r"(bar1),"r"(par1):"memory");
  return r; }
__device__ __forceinline__ void tma_2d(uint32_t dst, const CUtensorMap* m, int c0, int c1, uint32_t bar){
  asm volatile("cp.async.bulk.tensor.2d.shared::cluster.global.mbarrier::complete_tx::bytes [%0], [%1, {%3, %4}], [%2];"::"r"(dst),"l"(m),"r"(bar),"r"(c0),"r"(c1):"memory"); }
__device__ __forceinline__ void tma_2d_h(uint32_t dst, const CUtensorMap* m, int c0, int c1, uint32_t bar, uint64_t pol){
  asm volatile("cp.async.bulk.tensor.2d.shared::cluster.global.mbarrier::complete_tx::bytes.L2::cache_hint [%0], [%1, {%3, %4}], [%2], %5;"::"r"(dst),"l"(m),"r"(bar),"r"(c0),"r"(c1),"l"(pol):"memory"); }
__device__ __forceinline__ void tma_2d_mc(uint32_t dst, const CUtensorMap* m, int c0, int c1, uint32_t bar){
  asm volatile("cp.async.bulk.tensor.2d.shared::cluster.global.mbarrier::complete_tx::bytes.multicast::cluster [%0], [%1, {%3, %4}], [%2], %5;"::"r"(dst),"l"(m),"r"(bar),"r"(c0),"r"(c1),"h"((uint16_t)3):"memory"); }
__device__ __forceinline__ void tma_2d_mc_h(uint32_t dst, const CUtensorMap* m, int c0, int c1, uint32_t bar, uint64_t pol){
  asm volatile("cp.async.bulk.tensor.2d.shared::cluster.global.mbarrier::complete_tx::bytes.multicast::cluster.L2::cache_hint [%0], [%1, {%3, %4}], [%2], %5, %6;"::"r"(dst),"l"(m),"r"(bar),"r"(c0),"r"(c1),"h"((uint16_t)3),"l"(pol):"memory"); }
__device__ __forceinline__ void tma_4d(uint32_t dst, const CUtensorMap* m, int c0, int c1, int c2, int c3, uint32_t bar){
  asm volatile("cp.async.bulk.tensor.4d.shared::cluster.global.mbarrier::complete_tx::bytes [%0], [%1, {%3, %4, %5, %6}], [%2];"::"r"(dst),"l"(m),"r"(bar),"r"(c0),"r"(c1),"r"(c2),"r"(c3):"memory"); }
__device__ __forceinline__ uint64_t policy_evict_first(){ uint64_t p; asm volatile("createpolicy.fractional.L2::evict_first.b64 %0, 1.0;":"=l"(p)); return p; }
__device__ __forceinline__ uint64_t policy_evict_normal(){ uint64_t p; asm("createpolicy.fractional.L2::evict_normal.b64 %0, 1.0;":"=l"(p)); return p; }
__device__ __forceinline__ void tma_3d_h(uint32_t dst, const CUtensorMap* m, int c0, int c1, int c2, uint32_t bar, uint64_t pol){
  asm volatile("cp.async.bulk.tensor.3d.shared::cluster.global.mbarrier::complete_tx::bytes.L2::cache_hint [%0], [%1, {%3, %4, %5}], [%2], %6;"::"r"(dst),"l"(m),"r"(bar),"r"(c0),"r"(c1),"r"(c2),"l"(pol):"memory"); }
__device__ __forceinline__ void tma_4d_h(uint32_t dst, const CUtensorMap* m, int c0, int c1, int c2, int c3, uint32_t bar, uint64_t pol){
  asm volatile("cp.async.bulk.tensor.4d.shared::cluster.global.mbarrier::complete_tx::bytes.L2::cache_hint [%0], [%1, {%3, %4, %5, %6}], [%2], %7;"::"r"(dst),"l"(m),"r"(bar),"r"(c0),"r"(c1),"r"(c2),"r"(c3),"l"(pol):"memory"); }
__device__ __forceinline__ void red_add_f32x4(float4* p, float x, float y, float z, float w){ asm volatile("red.relaxed.gpu.global.add.v4.f32 [%0], {%1,%2,%3,%4};"::"l"(p),"f"(x),"f"(y),"f"(z),"f"(w):"memory"); }
__device__ __forceinline__ void tma_5d_h(uint32_t dst, const CUtensorMap* m, int c0, int c1, uint32_t bar, uint64_t pol){
  asm volatile("cp.async.bulk.tensor.5d.shared::cluster.global.mbarrier::complete_tx::bytes.L2::cache_hint [%0], [%1, {%3, %4, 0, 0, 0}], [%2], %5;"::"r"(dst),"l"(m),"r"(bar),"r"(c0),"r"(c1),"l"(pol):"memory"); }
__device__ __forceinline__ void tma_store_2d(const CUtensorMap* m, int c0, int c1, uint32_t src, uint64_t pol){
  asm volatile("cp.async.bulk.tensor.2d.global.shared::cta.bulk_group.L2::cache_hint [%0, {%2, %3}], [%1], %4;"::"l"(m),"r"(src),"r"(c0),"r"(c1),"l"(pol):"memory"); }
__device__ __forceinline__ void bulk_commit(){ asm volatile("cp.async.bulk.commit_group;":::"memory"); }
__device__ __forceinline__ void bulk_wait_all(){ asm volatile("cp.async.bulk.wait_group 0;":::"memory"); }
__device__ __forceinline__ void fence_async_global(){ asm volatile("fence.proxy.async.global;":::"memory"); }
__device__ __forceinline__ bool elect_one(){ uint32_t p; asm volatile("{\n.reg .pred P;\nelect.sync _|P, 0xffffffff;\nselp.b32 %0, 1, 0, P;\n}\n":"=r"(p)); return p; }
__device__ __forceinline__ void bulk_prefetch(const void* p, uint32_t bytes){
  asm volatile("cp.async.bulk.prefetch.L2.global [%0], %1;"::"l"(p),"r"(bytes):"memory"); }
__device__ __forceinline__ void bulk_s2peer(uint32_t dst_cluster, uint32_t src, uint32_t bytes, uint32_t bar_cluster){
  asm volatile("cp.async.bulk.shared::cluster.shared::cta.mbarrier::complete_tx::bytes [%0], [%1], %2, [%3];"::"r"(dst_cluster),"r"(src),"r"(bytes),"r"(bar_cluster):"memory"); }
__device__ __forceinline__ void prefetch_map(const CUtensorMap* m){ asm volatile("prefetch.tensormap [%0];"::"l"(m):"memory"); }
__device__ __forceinline__ void fence_async_smem(){ asm volatile("fence.proxy.async.shared::cta;":::"memory"); }
__device__ __forceinline__ void fence_acquire_gpu(){ asm volatile("fence.acquire.gpu;":::"memory"); }
__device__ __forceinline__ void fence_gpu(){ asm volatile("fence.acq_rel.gpu;":::"memory"); }
__device__ __forceinline__ void wg_fence(){ asm volatile("wgmma.fence.sync.aligned;":::"memory"); }
__device__ __forceinline__ void wg_commit(){ asm volatile("wgmma.commit_group.sync.aligned;":::"memory"); }
template<int N> __device__ __forceinline__ void wg_wait(){ asm volatile("wgmma.wait_group.sync.aligned %0;"::"n"(N):"memory"); }
template<int N> __device__ __forceinline__ void fence_regs(float (&d)[N]){
  #pragma unroll
  for(int i=0;i<N;i++) asm volatile("":"+f"(d[i])::"memory"); }
__device__ __forceinline__ void bar_sync(int id, int n){ asm volatile("bar.sync %0, %1;"::"r"(id),"r"(n):"memory"); }
__device__ __forceinline__ void bar_arrive(int id, int n){ asm volatile("bar.arrive %0, %1;"::"r"(id),"r"(n):"memory"); }
__device__ __forceinline__ void cluster_arrive(){ asm volatile("barrier.cluster.arrive.relaxed.aligned;":::"memory"); }
__device__ __forceinline__ void cluster_wait(){ asm volatile("barrier.cluster.wait.aligned;":::"memory"); }
__host__ __device__ constexpr uint32_t dlo(uint32_t addr, uint32_t lbo){ return (addr >> 4) | ((lbo >> 4) << 16); }
__host__ __device__ constexpr uint32_t dhi(uint32_t sbo, uint32_t sw){ return (sbo >> 4) | (sw << 30); }
constexpr uint32_t H128 = dhi(1024, 1), H64 = dhi(512, 2), H0 = dhi(128, 0);
__device__ __forceinline__ uint32_t pack_bf16(float lo, float hi){ uint32_t r; asm("cvt.rn.bf16x2.f32 %0, %1, %2;":"=r"(r):"f"(hi),"f"(lo)); return r; }
__device__ __forceinline__ float bf_lo(uint32_t v){ return __uint_as_float(v<<16); }
__device__ __forceinline__ float bf_hi(uint32_t v){ return __uint_as_float(v&0xffff0000u); }
__device__ __forceinline__ float ex2(float x){ float r; asm("ex2.approx.ftz.f32 %0, %1;":"=f"(r):"f"(x)); return r; }
__device__ __forceinline__ float rcp(float x){ float r; asm("rcp.approx.ftz.f32 %0, %1;":"=f"(r):"f"(x)); return r; }
__device__ __forceinline__ void stsm4(uint32_t addr, uint32_t a, uint32_t b, uint32_t c, uint32_t d){
  asm volatile("stmatrix.sync.aligned.m8n8.x4.shared.b16 [%0], {%1,%2,%3,%4};"::"r"(addr),"r"(a),"r"(b),"r"(c),"r"(d)); }
__device__ __forceinline__ void stsm2(uint32_t addr, uint32_t a, uint32_t b){
  asm volatile("stmatrix.sync.aligned.m8n8.x2.shared.b16 [%0], {%1,%2};"::"r"(addr),"r"(a),"r"(b)); }
__device__ __forceinline__ void mma16816(float& d0, float& d1, float& d2, float& d3, uint32_t a0, uint32_t a1, uint32_t a2, uint32_t a3, uint32_t b0, uint32_t b1){
  asm volatile("mma.sync.aligned.m16n8k16.row.col.f32.bf16.bf16.f32 {%0,%1,%2,%3}, {%4,%5,%6,%7}, {%8,%9}, {%0,%1,%2,%3};"
               : "+f"(d0), "+f"(d1), "+f"(d2), "+f"(d3) : "r"(a0), "r"(a1), "r"(a2), "r"(a3), "r"(b0), "r"(b1)); }
__device__ __forceinline__ uint32_t transpose8(uint32_t a){ uint32_t r; asm volatile("movmatrix.sync.aligned.m8n8.trans.b16 %0, %1;":"=r"(r):"r"(a)); return r; }
__device__ __forceinline__ void ldsm4(uint32_t addr, uint32_t& a, uint32_t& b, uint32_t& c, uint32_t& d){
  asm volatile("ldmatrix.sync.aligned.m8n8.x4.shared.b16 {%0,%1,%2,%3}, [%4];":"=r"(a),"=r"(b),"=r"(c),"=r"(d):"r"(addr):"memory"); }
__device__ __forceinline__ void ldsm4t(uint32_t addr, uint32_t& a, uint32_t& b, uint32_t& c, uint32_t& d){
  asm volatile("ldmatrix.sync.aligned.m8n8.x4.trans.shared.b16 {%0,%1,%2,%3}, [%4];":"=r"(a),"=r"(b),"=r"(c),"=r"(d):"r"(addr):"memory"); }
__device__ __forceinline__ void sts32(uint32_t a, uint32_t v){ asm volatile("st.shared.b32 [%0], %1;"::"r"(a),"r"(v):"memory"); }
__device__ __forceinline__ void stsf(uint32_t a, float v){ asm volatile("st.shared.f32 [%0], %1;"::"r"(a),"f"(v):"memory"); }
__device__ __forceinline__ void sts64(uint32_t a, uint32_t x, uint32_t y){ asm volatile("st.shared.v2.b32 [%0], {%1,%2};"::"r"(a),"r"(x),"r"(y):"memory"); }
__device__ __forceinline__ void sts128(uint32_t a, uint32_t x, uint32_t y, uint32_t z, uint32_t w){ asm volatile("st.shared.v4.b32 [%0], {%1,%2,%3,%4};"::"r"(a),"r"(x),"r"(y),"r"(z),"r"(w):"memory"); }
__device__ __forceinline__ float ldsf(uint32_t a){ float v; asm volatile("ld.shared.f32 %0, [%1];":"=f"(v):"r"(a):"memory"); return v; }
__device__ __forceinline__ float2 lds64f(uint32_t a){ float2 v; asm volatile("ld.shared.v2.f32 {%0,%1}, [%2];":"=f"(v.x),"=f"(v.y):"r"(a):"memory"); return v; }
__device__ __forceinline__ uint4 lds128(uint32_t a){ uint4 v; asm volatile("ld.shared.v4.u32 {%0,%1,%2,%3}, [%4];":"=r"(v.x),"=r"(v.y),"=r"(v.z),"=r"(v.w):"r"(a):"memory"); return v; }
__device__ __forceinline__ uint4 ld128_keep(const void* p){ uint4 v; asm volatile("ld.global.v4.u32 {%0,%1,%2,%3}, [%4];":"=r"(v.x),"=r"(v.y),"=r"(v.z),"=r"(v.w):"l"(p):"memory"); return v; }
__device__ __forceinline__ uint4 ld128_rlx(const void* p){ uint4 v; asm volatile("ld.relaxed.gpu.global.v4.u32 {%0,%1,%2,%3}, [%4];":"=r"(v.x),"=r"(v.y),"=r"(v.z),"=r"(v.w):"l"(p):"memory"); return v; }
__device__ __forceinline__ uint32_t ld32_rlx(const void* p){ uint32_t v; asm volatile("ld.relaxed.gpu.global.u32 %0, [%1];":"=r"(v):"l"(p):"memory"); return v; }
__device__ __forceinline__ void st128_rlx(void* p, uint32_t x, uint32_t y, uint32_t z, uint32_t w){ asm volatile("st.relaxed.gpu.global.v4.u32 [%0], {%1,%2,%3,%4};"::"l"(p),"r"(x),"r"(y),"r"(z),"r"(w):"memory"); }
__device__ __forceinline__ void st64_rlx(void* p, uint32_t x, uint32_t y){ asm volatile("st.relaxed.gpu.global.v2.u32 [%0], {%1,%2};"::"l"(p),"r"(x),"r"(y):"memory"); }
__device__ __forceinline__ void st32_rlx(void* p, uint32_t x){ asm volatile("st.relaxed.gpu.global.u32 [%0], %1;"::"l"(p),"r"(x):"memory"); }
__device__ __forceinline__ void wait_until(uint32_t t){ while ((int32_t)((uint32_t)clock() - t) < 0) __nanosleep(32); }
__device__ __forceinline__ void flags_wait(uint32_t& missing, const uint32_t* p, uint32_t need){
  asm volatile("{\n.reg .pred p;\n.reg .u32 c, v;\nmov.u32 c, 0;\nLW:\nand.b32 v, %0, %2;\nsetp.eq.u32 p, v, 0;\n@p bra.uni LD;\nld.relaxed.gpu.global.u32 v, [%1];\nsetp.eq.u32 p, v, 0;\n"
               "vote.sync.ballot.b32 %0, p, 0xffffffff;\nadd.u32 c, c, 1;\nsetp.lt.u32 p, c, 4000000;\n@p bra.uni LW;\nLD:\n}\n":"+r"(missing):"l"(p),"r"(need):"memory"); }
__device__ __forceinline__ uint32_t tagw(float x, uint32_t t){ return (__float_as_uint(x) & ~3u) | t; }
__device__ __forceinline__ float untag(uint32_t w){ return __uint_as_float(w & ~3u); }

template<int TA, int TB, uint32_t HA, uint32_t HB> __device__ __forceinline__ void wgmma_ss_n128(float (&d)[64], uint32_t da, uint32_t db, int scale_d){
  asm volatile("{\n.reg .pred p;\n.reg .b64 a, b;\nsetp.ne.b32 p, %70, 0;\nmov.b64 a, {%64, %68};\nmov.b64 b, {%65, %69};\n"
  "wgmma.mma_async.sync.aligned.m64n128k16.f32.bf16.bf16 {%0, %1, %2, %3, %4, %5, %6, %7, %8, %9, %10, %11, %12, %13, %14, %15, %16, %17, %18, %19, %20, %21, %22, %23, %24, %25, %26, %27, %28, %29, %30, %31, %32, %33, %34, %35, %36, %37, %38, %39, %40, %41, %42, %43, %44, %45, %46, %47, %48, %49, %50, %51, %52, %53, %54, %55, %56, %57, %58, %59, %60, %61, %62, %63}, a, b, p, 1, 1, %66, %67;\n}\n"
  : "+f"(d[0]), "+f"(d[1]), "+f"(d[2]), "+f"(d[3]), "+f"(d[4]), "+f"(d[5]), "+f"(d[6]), "+f"(d[7]), "+f"(d[8]), "+f"(d[9]), "+f"(d[10]), "+f"(d[11]), "+f"(d[12]), "+f"(d[13]), "+f"(d[14]), "+f"(d[15]), "+f"(d[16]), "+f"(d[17]), "+f"(d[18]), "+f"(d[19]), "+f"(d[20]), "+f"(d[21]), "+f"(d[22]), "+f"(d[23]), "+f"(d[24]), "+f"(d[25]), "+f"(d[26]), "+f"(d[27]), "+f"(d[28]), "+f"(d[29]), "+f"(d[30]), "+f"(d[31]), "+f"(d[32]), "+f"(d[33]), "+f"(d[34]), "+f"(d[35]), "+f"(d[36]), "+f"(d[37]), "+f"(d[38]), "+f"(d[39]), "+f"(d[40]), "+f"(d[41]), "+f"(d[42]), "+f"(d[43]), "+f"(d[44]), "+f"(d[45]), "+f"(d[46]), "+f"(d[47]), "+f"(d[48]), "+f"(d[49]), "+f"(d[50]), "+f"(d[51]), "+f"(d[52]), "+f"(d[53]), "+f"(d[54]), "+f"(d[55]), "+f"(d[56]), "+f"(d[57]), "+f"(d[58]), "+f"(d[59]), "+f"(d[60]), "+f"(d[61]), "+f"(d[62]), "+f"(d[63])
  : "r"(da), "r"(db), "n"(TA), "n"(TB), "n"(HA), "n"(HB), "r"(scale_d));
}
template<int TA, int TB, uint32_t HA, uint32_t HB> __device__ __forceinline__ void wgmma_sa_n128(float (&d)[64], uint32_t da, uint32_t db){
  asm volatile("{\n.reg .pred p;\n.reg .b64 a, b;\nsetp.ne.b32 p, 1, 0;\nmov.b64 a, {%64, %68};\nmov.b64 b, {%65, %69};\n"
  "wgmma.mma_async.sync.aligned.m64n128k16.f32.bf16.bf16 {%0, %1, %2, %3, %4, %5, %6, %7, %8, %9, %10, %11, %12, %13, %14, %15, %16, %17, %18, %19, %20, %21, %22, %23, %24, %25, %26, %27, %28, %29, %30, %31, %32, %33, %34, %35, %36, %37, %38, %39, %40, %41, %42, %43, %44, %45, %46, %47, %48, %49, %50, %51, %52, %53, %54, %55, %56, %57, %58, %59, %60, %61, %62, %63}, a, b, p, 1, 1, %66, %67;\n}\n"
  : "+f"(d[0]), "+f"(d[1]), "+f"(d[2]), "+f"(d[3]), "+f"(d[4]), "+f"(d[5]), "+f"(d[6]), "+f"(d[7]), "+f"(d[8]), "+f"(d[9]), "+f"(d[10]), "+f"(d[11]), "+f"(d[12]), "+f"(d[13]), "+f"(d[14]), "+f"(d[15]), "+f"(d[16]), "+f"(d[17]), "+f"(d[18]), "+f"(d[19]), "+f"(d[20]), "+f"(d[21]), "+f"(d[22]), "+f"(d[23]), "+f"(d[24]), "+f"(d[25]), "+f"(d[26]), "+f"(d[27]), "+f"(d[28]), "+f"(d[29]), "+f"(d[30]), "+f"(d[31]), "+f"(d[32]), "+f"(d[33]), "+f"(d[34]), "+f"(d[35]), "+f"(d[36]), "+f"(d[37]), "+f"(d[38]), "+f"(d[39]), "+f"(d[40]), "+f"(d[41]), "+f"(d[42]), "+f"(d[43]), "+f"(d[44]), "+f"(d[45]), "+f"(d[46]), "+f"(d[47]), "+f"(d[48]), "+f"(d[49]), "+f"(d[50]), "+f"(d[51]), "+f"(d[52]), "+f"(d[53]), "+f"(d[54]), "+f"(d[55]), "+f"(d[56]), "+f"(d[57]), "+f"(d[58]), "+f"(d[59]), "+f"(d[60]), "+f"(d[61]), "+f"(d[62]), "+f"(d[63])
  : "r"(da), "r"(db), "n"(TA), "n"(TB), "n"(HA), "n"(HB));
}
template<int TA, int TB, uint32_t HA, uint32_t HB> __device__ __forceinline__ void wgmma_sa_n40(float (&d)[20], uint32_t da, uint32_t db){
  asm volatile("{\n.reg .pred p;\n.reg .b64 a, b;\nsetp.ne.b32 p, 1, 0;\nmov.b64 a, {%20, %24};\nmov.b64 b, {%21, %25};\n"
  "wgmma.mma_async.sync.aligned.m64n40k16.f32.bf16.bf16 {%0, %1, %2, %3, %4, %5, %6, %7, %8, %9, %10, %11, %12, %13, %14, %15, %16, %17, %18, %19}, a, b, p, 1, 1, %22, %23;\n}\n"
  : "+f"(d[0]), "+f"(d[1]), "+f"(d[2]), "+f"(d[3]), "+f"(d[4]), "+f"(d[5]), "+f"(d[6]), "+f"(d[7]), "+f"(d[8]), "+f"(d[9]), "+f"(d[10]), "+f"(d[11]), "+f"(d[12]), "+f"(d[13]), "+f"(d[14]), "+f"(d[15]), "+f"(d[16]), "+f"(d[17]), "+f"(d[18]), "+f"(d[19])
  : "r"(da), "r"(db), "n"(TA), "n"(TB), "n"(HA), "n"(HB));
}
template<int TA, int TB, uint32_t HA, uint32_t HB> __device__ __forceinline__ void wgmma_sz_n40(float (&d)[20], uint32_t da, uint32_t db){
  asm volatile("{\n.reg .pred p;\n.reg .b64 a, b;\nsetp.ne.b32 p, 0, 0;\nmov.b64 a, {%20, %24};\nmov.b64 b, {%21, %25};\n"
  "wgmma.mma_async.sync.aligned.m64n40k16.f32.bf16.bf16 {%0, %1, %2, %3, %4, %5, %6, %7, %8, %9, %10, %11, %12, %13, %14, %15, %16, %17, %18, %19}, a, b, p, 1, 1, %22, %23;\n}\n"
  : "=f"(d[0]), "=f"(d[1]), "=f"(d[2]), "=f"(d[3]), "=f"(d[4]), "=f"(d[5]), "=f"(d[6]), "=f"(d[7]), "=f"(d[8]), "=f"(d[9]), "=f"(d[10]), "=f"(d[11]), "=f"(d[12]), "=f"(d[13]), "=f"(d[14]), "=f"(d[15]), "=f"(d[16]), "=f"(d[17]), "=f"(d[18]), "=f"(d[19])
  : "r"(da), "r"(db), "n"(TA), "n"(TB), "n"(HA), "n"(HB));
}
template<int TA, int TB, uint32_t HA, uint32_t HB> __device__ __forceinline__ void wgmma_sa_n32(float (&d)[16], uint32_t da, uint32_t db){
  asm volatile("{\n.reg .pred p;\n.reg .b64 a, b;\nsetp.ne.b32 p, 1, 0;\nmov.b64 a, {%16, %20};\nmov.b64 b, {%17, %21};\n"
  "wgmma.mma_async.sync.aligned.m64n32k16.f32.bf16.bf16 {%0, %1, %2, %3, %4, %5, %6, %7, %8, %9, %10, %11, %12, %13, %14, %15}, a, b, p, 1, 1, %18, %19;\n}\n"
  : "+f"(d[0]), "+f"(d[1]), "+f"(d[2]), "+f"(d[3]), "+f"(d[4]), "+f"(d[5]), "+f"(d[6]), "+f"(d[7]), "+f"(d[8]), "+f"(d[9]), "+f"(d[10]), "+f"(d[11]), "+f"(d[12]), "+f"(d[13]), "+f"(d[14]), "+f"(d[15])
  : "r"(da), "r"(db), "n"(TA), "n"(TB), "n"(HA), "n"(HB));
}
template<int TA, int TB, uint32_t HA, uint32_t HB> __device__ __forceinline__ void wgmma_ss_n32(float (&d)[16], uint32_t da, uint32_t db, int scale_d){
  asm volatile("{\n.reg .pred p;\n.reg .b64 a, b;\nsetp.ne.b32 p, %22, 0;\nmov.b64 a, {%16, %20};\nmov.b64 b, {%17, %21};\n"
  "wgmma.mma_async.sync.aligned.m64n32k16.f32.bf16.bf16 {%0, %1, %2, %3, %4, %5, %6, %7, %8, %9, %10, %11, %12, %13, %14, %15}, a, b, p, 1, 1, %18, %19;\n}\n"
  : "+f"(d[0]), "+f"(d[1]), "+f"(d[2]), "+f"(d[3]), "+f"(d[4]), "+f"(d[5]), "+f"(d[6]), "+f"(d[7]), "+f"(d[8]), "+f"(d[9]), "+f"(d[10]), "+f"(d[11]), "+f"(d[12]), "+f"(d[13]), "+f"(d[14]), "+f"(d[15])
  : "r"(da), "r"(db), "n"(TA), "n"(TB), "n"(HA), "n"(HB), "r"(scale_d));
}
template<int TB, uint32_t HB> __device__ __forceinline__ void wgmma_ra_n32(float (&d)[16], uint32_t a0, uint32_t a1, uint32_t a2, uint32_t a3, uint32_t db){
  asm volatile("{\n.reg .pred p;\n.reg .b64 a, b;\nsetp.ne.b32 p, 1, 0;\nmov.b64 b, {%20, %22};\n"
  "wgmma.mma_async.sync.aligned.m64n32k16.f32.bf16.bf16 {%0, %1, %2, %3, %4, %5, %6, %7, %8, %9, %10, %11, %12, %13, %14, %15}, {%16,%17,%18,%19}, b, p, 1, 1, %21;\n}\n"
  : "+f"(d[0]), "+f"(d[1]), "+f"(d[2]), "+f"(d[3]), "+f"(d[4]), "+f"(d[5]), "+f"(d[6]), "+f"(d[7]), "+f"(d[8]), "+f"(d[9]), "+f"(d[10]), "+f"(d[11]), "+f"(d[12]), "+f"(d[13]), "+f"(d[14]), "+f"(d[15])
  : "r"(a0), "r"(a1), "r"(a2), "r"(a3), "r"(db), "n"(TB), "n"(HB));
}
template<int TB, uint32_t HB> __device__ __forceinline__ void wgmma_rs_n32(float (&d)[16], uint32_t a0, uint32_t a1, uint32_t a2, uint32_t a3, uint32_t db, int scale_d){
  asm volatile("{\n.reg .pred p;\n.reg .b64 a, b;\nsetp.ne.b32 p, %23, 0;\nmov.b64 b, {%20, %22};\n"
  "wgmma.mma_async.sync.aligned.m64n32k16.f32.bf16.bf16 {%0, %1, %2, %3, %4, %5, %6, %7, %8, %9, %10, %11, %12, %13, %14, %15}, {%16,%17,%18,%19}, b, p, 1, 1, %21;\n}\n"
  : "+f"(d[0]), "+f"(d[1]), "+f"(d[2]), "+f"(d[3]), "+f"(d[4]), "+f"(d[5]), "+f"(d[6]), "+f"(d[7]), "+f"(d[8]), "+f"(d[9]), "+f"(d[10]), "+f"(d[11]), "+f"(d[12]), "+f"(d[13]), "+f"(d[14]), "+f"(d[15])
  : "r"(a0), "r"(a1), "r"(a2), "r"(a3), "r"(db), "n"(TB), "n"(HB), "r"(scale_d));
}
template<int TB, uint32_t HB> __device__ __forceinline__ void wgmma_ra_n40(float (&d)[20], uint32_t a0, uint32_t a1, uint32_t a2, uint32_t a3, uint32_t db){
  asm volatile("{\n.reg .pred p;\n.reg .b64 a, b;\nsetp.ne.b32 p, 1, 0;\nmov.b64 b, {%24, %26};\n"
  "wgmma.mma_async.sync.aligned.m64n40k16.f32.bf16.bf16 {%0, %1, %2, %3, %4, %5, %6, %7, %8, %9, %10, %11, %12, %13, %14, %15, %16, %17, %18, %19}, {%20,%21,%22,%23}, b, p, 1, 1, %25;\n}\n"
  : "+f"(d[0]), "+f"(d[1]), "+f"(d[2]), "+f"(d[3]), "+f"(d[4]), "+f"(d[5]), "+f"(d[6]), "+f"(d[7]), "+f"(d[8]), "+f"(d[9]), "+f"(d[10]), "+f"(d[11]), "+f"(d[12]), "+f"(d[13]), "+f"(d[14]), "+f"(d[15]), "+f"(d[16]), "+f"(d[17]), "+f"(d[18]), "+f"(d[19])
  : "r"(a0), "r"(a1), "r"(a2), "r"(a3), "r"(db), "n"(TB), "n"(HB));
}
template<int TB, uint32_t HB> __device__ __forceinline__ void wgmma_rz_n40(float (&d)[20], uint32_t a0, uint32_t a1, uint32_t a2, uint32_t a3, uint32_t db){
  asm volatile("{\n.reg .pred p;\n.reg .b64 a, b;\nsetp.ne.b32 p, 0, 0;\nmov.b64 b, {%24, %26};\n"
  "wgmma.mma_async.sync.aligned.m64n40k16.f32.bf16.bf16 {%0, %1, %2, %3, %4, %5, %6, %7, %8, %9, %10, %11, %12, %13, %14, %15, %16, %17, %18, %19}, {%20,%21,%22,%23}, b, p, 1, 1, %25;\n}\n"
  : "=f"(d[0]), "=f"(d[1]), "=f"(d[2]), "=f"(d[3]), "=f"(d[4]), "=f"(d[5]), "=f"(d[6]), "=f"(d[7]), "=f"(d[8]), "=f"(d[9]), "=f"(d[10]), "=f"(d[11]), "=f"(d[12]), "=f"(d[13]), "=f"(d[14]), "=f"(d[15]), "=f"(d[16]), "=f"(d[17]), "=f"(d[18]), "=f"(d[19])
  : "r"(a0), "r"(a1), "r"(a2), "r"(a3), "r"(db), "n"(TB), "n"(HB));
}
template<int TB, uint32_t HB> __device__ __forceinline__ void wgmma_rz_n8(float (&d)[4], uint32_t a0, uint32_t a1, uint32_t a2, uint32_t a3, uint32_t db){
  asm volatile("{\n.reg .pred p;\n.reg .b64 a, b;\nsetp.ne.b32 p, 0, 0;\nmov.b64 b, {%8, %10};\n"
  "wgmma.mma_async.sync.aligned.m64n8k16.f32.bf16.bf16 {%0, %1, %2, %3}, {%4,%5,%6,%7}, b, p, 1, 1, %9;\n}\n"
  : "=f"(d[0]), "=f"(d[1]), "=f"(d[2]), "=f"(d[3])
  : "r"(a0), "r"(a1), "r"(a2), "r"(a3), "r"(db), "n"(TB), "n"(HB));
}

constexpr int SEQ = 2048, DM = 1024, FF = 3584;
constexpr float LOG2E = 1.4426950408889634f;
constexpr uint32_t POLL_LIMIT = 1u << 22;
constexpr int QW = 0;
constexpr int LAG = 2;
constexpr int ML = 2;
constexpr int REL = 6;
constexpr int SKM = 0x154;
constexpr int RS_N = 22;
constexpr int RS_D1 = 420;
constexpr int RS_D2 = 300;
constexpr int PF_T0 = 5000;
constexpr int PF_DT = 800;
constexpr int FF_N = 5;
constexpr int FF_DT = 500;
constexpr int FF_D2 = 350;
constexpr uint64_t FF_ORD = 0x76543210ba98ull;
constexpr int G2P = 4;
constexpr int XC = 0;
constexpr int OUT_D = 400;
constexpr int NFFN = 112;

constexpr uint32_t SB0 = 1024;
constexpr uint32_t KV_STAGE = 49152, R5 = 32768;
constexpr uint32_t OFF_X = 163840, OFF_S = 196608, OFF_WPHI = OFF_S + 20480, OFF_M = 229376, SMEM_BYTES = 232448;
constexpr uint32_t OFF_RS256 = 212992, OFF_ONES = OFF_RS256 + 1024, OFF_WPHIK1 = OFF_ONES + 1024, OFF_KVZ = OFF_S;
constexpr uint32_t OFF_WPHIK = OFF_S, OFF_BXK = OFF_S + 2048, OFF_AXK = OFF_S + 4096, OFF_G = OFF_S + 8192;
constexpr uint32_t OFF_AXQ = OFF_WPHI, OFF_BXQ = OFF_WPHI + 2048, OFF_WPHIQ = OFF_WPHI + 4096;
constexpr uint32_t B_FULLKV = OFF_M  , B_EMPTYKV = OFF_M + 32  ;
constexpr uint32_t B_EMPTY5 = OFF_M + 64  , B_UO = B_EMPTY5 + 48  , B_RC = B_UO + 32  ;
constexpr uint32_t B_OUT = B_RC + 16  , B_SD = B_OUT + 16, B_AUX = B_SD + 8, B_AUXQ = B_AUX + 8, B_RX = B_AUXQ + 8;
constexpr uint32_t B_FULL5 = B_RX + 8  , B_F = B_FULL5 + 40  , B_WD = B_F + 64  ;
constexpr uint32_t B_WC = B_WD + 32  , B_DR = B_WC + 32  , B_W = B_DR + 24, B_OS = B_W + 8, B_R = B_W + 16, B_KD = B_W + 24, B_T = B_W + 32, B_G = B_W + 40, B_END = B_W + 48;
constexpr int NB3 = ((B_END - OFF_M) / 8 + 1) / 3;
constexpr uint32_t B_S0 = OFF_M + 8 + 24 * NB3;
static_assert(B_S0 >= B_END && B_S0 < OFF_M + 576, "barriers");
__host__ __device__ constexpr uint32_t bar_count(int i) {
  const uint32_t b = OFF_M + 8 * i;
  return b < B_EMPTYKV ? 1 : b < B_EMPTY5 ? 12 : b < B_SD ? 4 : b < B_RX || b == B_W ? 2 : b == B_RX ? 8 : 1;
}
constexpr uint32_t B_GB = OFF_M + 2560  , B_GA = B_GB + 128  ;
constexpr uint32_t OFF_BEST = OFF_M + 576, OFF_SUMWR = OFF_M + 608, OFF_EP = OFF_M + 624, OFF_KEY = OFF_M + 628;
constexpr uint32_t OFF_RSQ = OFF_M + 640, OFF_SEL = OFF_M + 1648, OFF_T = OFF_M + 1792, OFF_WR = OFF_M + 2048;
constexpr uint32_t OFF_XSEL = 2 * R5, OFF_GU = OFF_XSEL + 4096, OFF_OUT = 3 * R5;
constexpr uint64_t FF_SLOT = 0xdcdc3210dcbaull;
constexpr int KVP = 6 * 128;
__device__ __forceinline__ uint32_t kv_count(uint32_t launch, uint32_t n) { return 0x42800000u + (((launch & 3) * 16 + n) << 17); }

enum { NB_G2E = 1, NB_XS = 2, NB_WG01 = 3, NB_ACT = 4, NB_Q0 = 5  , NB_ST = 14, NB_LAG = 8, NB_DN = 9, NB_ZERO = 10, NB_PUB = 11, NB_TOK = 10  , NB_L0 = 12  , NB_WG2 = 7, NB_QGO = 15 };

struct Scratch {
  bf16     o[SEQ * DM];
  float4   rstat[SEQ];
  uint32_t key[16 * 128];
  uint32_t cand[16 * 512];
  float4   yacc[4 * 3 * 128];
  float4   kvacc[32 * KVP];
  uint2    stats[SEQ];
  uint32_t cskv[2 * DM];
  uint32_t csq[4 * DM];
  uint32_t oset[128 * 16];
  uint32_t oflag[16 * 6 * 32 * 8];
  uint32_t epoch;
};
__device__ __align__(1024) Scratch g_scr;

struct Params {
  const bf16 *x, *wqkv, *wo_p, *wr;
  bf16* out_p;
  Scratch* g;
  uint32_t zero;
  CUtensorMap x128, x64, wkv, wq, wo[2], wd, wg, wu, phi, tg, tu, td, xs, ws, qs, out, o;
};

constexpr float EXP_LIM = 1.1529215e18f, ARG_LIM2 = 3600.f;
__device__ __forceinline__ void dual_exp2(const float (&p)[16], uint32_t (&ep)[8], uint32_t (&em)[8]) {
  #pragma unroll
  for (int k = 0; k < 8; k++) {
    const float a = ex2(p[2*k]), b = ex2(p[2*k+1]);
    const float r = rcp(a * b);
    ep[k] = pack_bf16(a, b); em[k] = pack_bf16(r * b, r * a);
  }
}
template<bool SUMS> __device__ __forceinline__ void dual_exp2_shifted(float (&p)[2][16], uint32_t (&ph)[4][8], float (&s)[2][4]) {
  #pragma unroll 1
  for (int r = 0; r < 4; r++) {
    float m[2] = {p[0][0], p[0][2]}, a[2] = {0.f, 0.f};
    #pragma unroll
    for (int i = 0; i < 16; i++) m[(i >> 1) & 1] = fmaxf(m[(i >> 1) & 1], p[0][i]);
    #pragma unroll
    for (int o = 1; o < 4; o <<= 1) { m[0] = fmaxf(m[0], __shfl_xor_sync(~0u, m[0], o)); m[1] = fmaxf(m[1], __shfl_xor_sync(~0u, m[1], o)); }
    #pragma unroll
    for (int k = 0; k < 8; k++) {
      const float e0 = ex2(p[0][2*k] - m[k & 1]), e1 = ex2(p[0][2*k+1] - m[k & 1]);
      ph[0][k] = ph[2][k]; ph[2][k] = ph[1][k]; ph[1][k] = ph[3][k]; ph[3][k] = pack_bf16(e0, e1);
      a[k & 1] += e0 + e1;
    }
    #pragma unroll
    for (int i = 0; i < 16; i++) { const float x = p[0][i]; p[0][i] = p[1][i]; p[1][i] = -x; }
    if (SUMS) {
      #pragma unroll
      for (int i = 0; i < 2; i++) {
        a[i] += __shfl_xor_sync(~0u, a[i], 1);
        s[0][2*i] = s[1][2*i]; s[1][2*i] = s[0][2*i+1]; s[0][2*i+1] = s[1][2*i+1]; s[1][2*i+1] = a[i] + __shfl_xor_sync(~0u, a[i], 2);
      }
    }
  }
}
__device__ __forceinline__ uint32_t add_bf16x2(uint32_t a, uint32_t b) { uint32_t r; asm("add.rn.bf16x2 %0, %1, %2;" : "=r"(r) : "r"(a), "r"(b)); return r; }
__device__ __forceinline__ void row_sums(float (&s)[2][4], const uint32_t (&ph)[4][8], uint32_t sel) {
  uint32_t u[8];
  #pragma unroll
  for (int i = 0; i < 8; i++) { const uint32_t* f = &ph[i >> 1][i & 1]; u[i] = add_bf16x2(add_bf16x2(f[0], f[2]), add_bf16x2(f[4], f[6])); }
  wg_fence();
  wgmma_rz_n8<0, H0>(s[0], u[0], u[1], u[2], u[3], sel);
  wgmma_rz_n8<0, H0>(s[1], u[4], u[5], u[6], u[7], sel);
  wg_commit();
}
__device__ __forceinline__ uint32_t mul_bf16x2(uint32_t a, uint32_t b) { uint32_t r; asm("mul.rn.bf16x2 %0, %1, %2;" : "=r"(r) : "r"(a), "r"(b)); return r; }
__device__ __forceinline__ void normalize(uint32_t (&ph)[4][8], const float (&s)[2][4]) {
  #pragma unroll
  for (int i = 0; i < 4; i++) {
    const float i0 = rcp(s[i >> 1][i & 1]), i1 = rcp(s[i >> 1][2 + (i & 1)]);
    const uint32_t n0 = pack_bf16(i0, i0), n1 = pack_bf16(i1, i1);
    #pragma unroll
    for (int k = 0; k < 4; k++) { ph[i][2*k] = mul_bf16x2(ph[i][2*k], n0); ph[i][2*k+1] = mul_bf16x2(ph[i][2*k+1], n1); }
  }
}
__device__ __forceinline__ void split_bf16(float a, float b, uint32_t& hi, uint32_t& lo) { hi = pack_bf16(a, b); lo = pack_bf16(a - bf_lo(hi), b - bf_hi(hi)); }
__device__ __forceinline__ void put_colsums(uint32_t base, int lane, float a, float b, float c, float d) {
  uint32_t h0, l0, h1, l1;
  split_bf16(a, b, h0, l0); split_bf16(c, d, h1, l1);
  const uint32_t ad = base + (lane >> 1) * 128 + (lane & 1) * 8;
  sts64(ad, h0, h1); sts64(ad + 16, l0, l1); sts64(ad + 32, h0, h1); sts64(ad + 48, l0, l1);
  sts128(base + (lane >> 1) * 128 + 64 + (lane & 1) * 32, 0, 0, 0, 0); sts128(base + (lane >> 1) * 128 + 80 + (lane & 1) * 32, 0, 0, 0, 0);
}
__device__ __forceinline__ float reduce8(const float (&v)[8], int lane) {
  const bool b4 = lane & 16, b3 = lane & 8, b2 = lane & 4;
  float a[4], b[2];
  #pragma unroll
  for (int i = 0; i < 4; i++) a[i] = (b4 ? v[4 + i] : v[i]) + __shfl_xor_sync(~0u, b4 ? v[i] : v[4 + i], 16);
  #pragma unroll
  for (int i = 0; i < 2; i++) b[i] = (b3 ? a[2 + i] : a[i]) + __shfl_xor_sync(~0u, b3 ? a[i] : a[2 + i], 8);
  return (b2 ? b[1] : b[0]) + __shfl_xor_sync(~0u, b2 ? b[0] : b[1], 4);
}
__device__ __forceinline__ bool tag_bad(uint4 v, uint32_t tg) { return (((v.x ^ tg) | (v.y ^ tg) | (v.z ^ tg) | (v.w ^ tg)) & 3) != 0; }


__global__ void __launch_bounds__(512, 1) __cluster_dims__(2, 1, 1) fused_kernel(const __grid_constant__ Params P) {
  extern __shared__ __align__(1024) uint8_t smem_raw[];
  const uint32_t sb = smem_u32(smem_raw);
  const int tid = threadIdx.x, lane = tid & 31;
  {
    const int n = 16 * blockIdx.x + (lane & 15);
    const bf16* p = (lane < 16 ? P.x : P.wqkv) + (lane < 16 ? n * DM : (n >> 5) * (3 * DM) + DM + 64 * (n & 31));
    asm volatile("{\n.reg .pred p;\nsetp.lt.u32 p, %1, 32;\n@p prefetch.global.L2 [%0];\n}\n" :: "l"(p), "r"(tid));
  }
  const int cp = blockIdx.x >> 1, rank = blockIdx.x & 1;
  const int cr = cp < 4 ? 32 + 8 * cp : cp - 4 + max((cp * 37 - 1076) >> 8, 0);
  const int c = (cr & 62) + 64 * (cr & 1) + rank;
  const int m256 = c >> 4, nkv = c & 15, m128 = c >> 3, j = c & 7;
  if ((tid >> 7) == 2 && elect_one()) {
    if (tid >= 288) {
      const int w = (tid >> 5) - 9;
      #pragma unroll
      for (int i = 0; i < NB3; i++) mbar_init(sb + B_FULLKV + 8 + 8 * NB3 * w + 8 * i, w == 0 ? bar_count(1 + i) : w == 1 ? bar_count(1 + NB3 + i) : bar_count(1 + 2 * NB3 + i));
    } else {
      prefetch_map(&P.wkv); prefetch_map(&P.x128);
      mbar_init(sb + B_S0, 1); mbar_init(sb + B_FULLKV, 1);
      mbar_expect_tx(sb + B_S0, 32768);
      tma_4d(sb + 32768, &P.wkv, 0, 0, nkv, 1, sb + B_S0);
      tma_2d(sb, &P.x128, 0, 256 * m256, sb + B_S0);
      mbar_expect_tx(sb + B_FULLKV, 16384);
      tma_2d(sb + 16384, &P.x128, 0, 256 * m256 + 128, sb + B_FULLKV);
    }
    asm volatile("fence.mbarrier_init.release.cluster;" ::: "memory");
  }
  const int warp = __shfl_sync(~0u, tid >> 5, 0), wg = warp >> 2, wp = warp & 3;
  const int f = 16 * ((cr + 7) & 7) + 2 * (cr >> 3) + rank;
  const int ha = 4 * (nkv >> 1) + (nkv & 1);
  Scratch* const G = P.g;
  if ((sb & 0x3ffff) != SB0) asm volatile("trap;");
  __syncthreads();
  cluster_arrive();
  if (warp == 8 && elect_one()) {
    mbar_expect_tx(sb + B_FULLKV + 8, KV_STAGE);
    tma_4d(sb + KV_STAGE + 32768, &P.wkv, 0, 64, nkv, 1, sb + B_FULLKV + 8);
    tma_2d(sb + KV_STAGE, &P.x128, 64, 256 * m256, sb + B_FULLKV + 8);
    tma_2d(sb + KV_STAGE + 16384, &P.x128, 64, 256 * m256 + 128, sb + B_FULLKV + 8);
  }
  if (wg == 3) {
    asm volatile("setmaxnreg.dec.sync.aligned.u32 32;");
    cluster_wait();
    const bool el = elect_one();
    const uint64_t ef = policy_evict_first(), en = policy_evict_normal();
    auto fetch_o = [&](const int t0, const int sh) {
      uint32_t missing = ~0u;
      const uint32_t* hint = &G->oflag[((m128 * 6 + ((t0 + 1) & 6) + rank) * 32 + ((4 * (j & 6) + lane) & 31)) * 8];
      #pragma unroll 1
      for (int i = 2 - 2 * sh; i < 8; i += 1 + sh) {
        const int blk = sh ? 6 + 2 * t0 + (i >> 1) : i, wrap = sh ? 1 + (blk >= 11) : blk >= 5, s = blk + 1 - 6 * wrap;
        flags_wait(missing, hint, (15u + 240u * sh) << (4 * i));
        if (sh || blk > 5) mbar_wait(sb + B_EMPTY5 + 8 * s, wrap & 1);
        if (el) {
          tma_2d_mc_h(sb + s * R5 + rank * 8192, &P.o, 0, (m128 * 16 + t0 + 2 * (((j & 6) + i) & 7)) * 32 + 16 * rank, sb + B_GA + 16 * blk + 8 * rank, ef);
        }
      }
    };
    if (wp == 0) {
      {
        wait_until((uint32_t)clock() + 300);
        #pragma unroll 1
        for (int kb = 2; kb < 16; kb++) {
          const uint32_t st = sb + (kb & 3) * KV_STAGE, fb = sb + B_FULLKV + 8 * (kb & 3);
          mbar_wait(fb + (B_EMPTYKV - B_FULLKV), ~(kb >> 2) & 1);
          if (el) {
            mbar_expect_tx(fb, KV_STAGE);
            tma_2d_mc(st + rank * 16384, &P.x128, 64 * kb, 256 * m256 + 128 * rank, fb);
            tma_4d_h(st + 32768, &P.wkv, 0, 64 * kb, nkv, 1, fb, ef);
          }
        }
        uint64_t ord = 0xf3120edcba987654ull;
        uint32_t so = 0, par = 1;
        #pragma unroll 1
        for (int i = 0; i < 16; i++) {
          const uint32_t st = sb + so * 4096, fb = sb + B_FULL5 + so;
          const int k0 = (64 * (uint32_t)ord + 128 * (j & 6)) & 960;
          mbar_wait(i < 5 ? sb + B_EMPTYKV + so - (i > 1 ? 8 : 0) : fb + (B_EMPTY5 - B_FULL5), par);
          if (el) {
            mbar_expect_tx(fb, R5);
            tma_2d_mc_h(st + rank * 8192, &P.x64, k0, 128 * m128 + 64 * rank, fb, i >= 11 ? ef : en);
            tma_3d_h(st + 16384, &P.wq, 0, k0, 2 * j, fb, ef);
          }
          ord >>= 4; so += 8;
          if (so == 40) { so = 0; par ^= 1; }
        }
        mbar_wait(sb + B_FULL5 + 8 + 8 * rank, 0);
        if (el) mbar_arrive(sb + B_R);
        #pragma unroll 1
        for (int i = 0; i < 19; i++) {
          const int row = i < 8 ? 128 * (((j & 6) + i) & 7) : 256 * (((j >> 1) + i) & 3) + 32 + 16 * (i & 4);
          mbar_wait(sb + B_EMPTY5 + so, par);
          if (el) {
            if (i < 16) {
              tma_5d_h(sb + so * 4096 + 16384, &P.wo[i >> 3], 128 * j, row, sb + B_GB + 8 * i, ef);
              tma_5d_h(sb + so * 4096 + 24576, &P.wo[i >> 3], 128 * j + 64, row, sb + B_GB + 8 * i, ef);
            } else mbar_arrive(sb + B_DR + 8 * (i - 16));
          }
          so += 8;
          if (so == 48) { so = 0; par ^= 1; }
        }
      }
    } else if (wp == 3) {
      const uint32_t t_start = (uint32_t)clock();
      mbar_wait(sb + B_S0, 0);
      if (el) {
        mbar_expect_tx(sb + B_W, 12288);
        #pragma unroll 1
        for (int i = 0; i < 6; i++) tma_2d(sb + (i == 0 ? OFF_WPHIK : i == 1 ? OFF_WPHIK1 : OFF_WPHIQ + 2048 * (i - 2)), &P.phi, 0, 32 * (i < 2 ? 2 * nkv + i : 4 * j + 2 * (i & 1) + ((i - 2) >> 1)), sb + B_W);
        prefetch_map(&P.x64); prefetch_map(&P.wq); prefetch_map(&P.wo[0]); prefetch_map(&P.wo[1]);
        prefetch_map(&P.o); prefetch_map(&P.wd); prefetch_map(&P.out); prefetch_map(&P.wg); prefetch_map(&P.wu);
      }
      if (lane < 16) st128_rlx(&G->cand[m128 * 512 + 64 * j + 4 * lane], ~0u, ~0u, ~0u, ~0u);
      if (lane < 16) st128_rlx(&G->rstat[16 * c + lane], 0, 0, 0, 0);
      if (lane < 12) st128_rlx(&G->yacc[12 * c + lane], 0, 0, 0, 0);
      const uint32_t nt = ld32_rlx(&G->epoch);
      if (lane < 8) { st128_rlx(&G->stats[16 * c + 2 * lane], nt, nt, nt, nt); st128_rlx(&G->csq[32 * c + 4 * lane], nt, nt, nt, nt); }
      if (lane < 4) { st128_rlx(&G->cskv[128 * nkv + 16 * m256 + 4 * lane], nt, nt, nt, nt); st128_rlx(&G->oset[16 * c + 4 * lane], nt, nt, nt, nt); }
      if (lane < 4) st128_rlx(&G->key[(2 * j + (lane >> 1)) * 128 + m128 * 8 + 4 * (lane & 1)], 0, 0, 0, 0);
      if (c < 32) {
        #pragma unroll 1
        for (int i = lane; i < KVP; i += 32) st128_rlx(&G->kvacc[(ha + 2 * m256) * KVP + i], 0, 0, 0, kv_count(nt + 1, 0));
      }
      fence_gpu();
      bar_arrive(NB_ZERO, 160);
      if (el) {
        #pragma unroll 1
        for (int i = 0; i < 30; i++) {
          wait_until(t_start + PF_T0 + PF_DT * i + 7 * f);
          if (i < 4) { bulk_prefetch(P.wqkv + (size_t)(256 * i + c) * (3 * DM), 2048); bulk_prefetch(P.wqkv + (size_t)(256 * i + 128 + c) * (3 * DM), 2048); }
          else if (i < 6) bulk_prefetch(P.wo_p + (size_t)c * 8192 + (i - 4) * 4096, 8192);
          else if (f < NFFN) {
            if (i < 22) {
              #pragma unroll 1
              for (int e = 0; e < 4; e++) tma_2d(sb + OFF_T, rank ? &P.tu : &P.tg, 32 * (f & ~1), 64 * (i - 6) + 16 * e, sb + B_T);
            } else { tma_2d(sb + OFF_T, &P.td, 0, 256 * f + 32 * (i - 22), sb + B_T); tma_2d(sb + OFF_T, &P.td, 0, 256 * f + 32 * (i - 22) + 16, sb + B_T); }
          }
        }
      }
      __syncwarp();
      mbar_wait2(sb + B_OS, 0, sb + B_RX, 0);
      mbar_wait2(sb + B_EMPTY5 + 24, 0, sb + B_EMPTY5 + 32, 0);
      mbar_wait2(sb + B_EMPTY5 + 40, 0, sb + B_EMPTY5, 1);
      fetch_o(0, 0);
    } else {
      const int half = wp - 1;
      const uint32_t ep1 = ld32_rlx(&G->epoch) + 1, tg = ep1 & 3;
      {
        uint32_t it = 0;
        sts128(sb + OFF_ONES + half * 512 + lane * 16, 0x3f803f80u, 0x3f803f80u, 0x3f803f80u, 0x3f803f80u);
        if (lane < 9) { const uint32_t v = (lane & 1) ? 0 : 0x3f803f80u; sts128(sb + OFF_SEL + lane * 16, v, v, v, v); }
        auto reset_o = [&](int i0, int i1, uint32_t dt) {
          uint32_t t0 = (uint32_t)clock();
          #pragma unroll 1
          for (int i = i0; i < i1; i++) {
            st128_rlx(G->o + (m128 * 16 + 2 * j + half) * 8192 + 256 * i + 8 * lane, ~0u, ~0u, ~0u, ~0u);
            wait_until(t0 += dt);
          }
        };
        if (el) {
          #pragma unroll 1
          for (int i = 24 * half; i < 24 * half + 24; i++) { mbar_init(sb + B_GB + 8 * i, 1); mbar_expect_tx(sb + B_GB + 8 * i, i < 16 ? 16384 : 8192); }
          asm volatile("fence.mbarrier_init.release.cluster;" ::: "memory");
        }
        mbar_wait(sb + B_S0, 0);
        reset_o(0, RS_N, RS_D1);
        bar_sync(NB_PUB, 192);
        const uint4* src = reinterpret_cast<const uint4*>(&G->stats[256 * m256 + 128 * half]) + lane;
        const uint4* srk = reinterpret_cast<const uint4*>(&G->cskv[128 * nkv]) + lane;
        uint4 v0, v1, vk;
        it = 0;
        do { v0 = ld128_rlx(src); v1 = ld128_rlx(src + 32); vk = ld128_rlx(srk); }
        while ((tag_bad(v0, tg) || tag_bad(v1, tg) || tag_bad(vk, tg)) && ++it < POLL_LIMIT);
        fence_acquire_gpu();
        if (half) put_colsums(sb + OFF_BXK, lane, untag(vk.x), untag(vk.y), untag(vk.z), untag(vk.w));
        #pragma unroll 1
        for (int i = 0; i < 2; i++) {
          const uint4 v = i ? v1 : v0;
          uint32_t hi, lo;
          split_bf16(-0.5f * untag(v.x), -0.5f * untag(v.z), hi, lo);
          const uint32_t h0 = __byte_perm(hi, hi, 0x1010), h1 = __byte_perm(hi, hi, 0x3232), l0 = __byte_perm(lo, lo, 0x1010), l1 = __byte_perm(lo, lo, 0x3232);
          const uint32_t a = sb + OFF_AXK + half * 2048 + i * 1024 + lane * 32;
          sts128(a, h0, l0, 0, 0); sts128(a + 16, h1, l1, 0, 0);
          sts64(sb + OFF_RS256 + half * 512 + i * 256 + lane * 8, v.y & ~3u, v.w & ~3u);
          if (half == (m128 & 1)) {
            const uint32_t aq = sb + OFF_AXQ + i * 1024 + lane * 32;
            sts128(aq, h0, l0, 0, 0); sts128(aq + 16, h1, l1, 0, 0);
            sts64(sb + OFF_RSQ + i * 256 + lane * 8, v.y & ~3u, v.w & ~3u);
          }
        }
        fence_async_smem();
        __syncwarp();
        if (el) { sts32(sb + OFF_EP, ep1); mbar_arrive(sb + B_AUX); }
        reset_o(RS_N, 32, RS_D2);
        if (lane < 24) st128_rlx(&G->oflag[((m128 * 6 + 3 * half + (lane >> 3)) * 32 + 4 * j) * 8 + 4 * (lane & 7)], 0, 0, 0, 0);
        fence_gpu();
        __syncwarp();
        if (el) { st32_rlx(&G->oset[16 * c + 8 * half], ep1); if (half) mbar_arrive(sb + B_AUXQ); }
        if (!half) {
          const uint4* src = reinterpret_cast<const uint4*>(&G->csq[128 * j]) + lane;
          uint4 v0, v1, v2, v3;
          do { v0 = ld128_rlx(src); v1 = ld128_rlx(src + DM / 4); v2 = ld128_rlx(src + DM / 2); v3 = ld128_rlx(src + 3 * DM / 4); }
          while ((tag_bad(v0, tg) || tag_bad(v1, tg) || tag_bad(v2, tg) || tag_bad(v3, tg)) && ++it < POLL_LIMIT);
          put_colsums(sb + OFF_BXQ, lane, (untag(v0.x) + untag(v1.x)) + (untag(v2.x) + untag(v3.x)), (untag(v0.y) + untag(v1.y)) + (untag(v2.y) + untag(v3.y)),
                      (untag(v0.z) + untag(v1.z)) + (untag(v2.z) + untag(v3.z)), (untag(v0.w) + untag(v1.w)) + (untag(v2.w) + untag(v3.w)));
          fence_async_smem();
          __syncwarp();
          if (el) mbar_arrive(sb + B_AUXQ);
        }
      }
      if (half == 0) {
        for (uint32_t it = 0; __any_sync(~0u, ld32_rlx(&G->oset[m128 * 128 + 8 * (lane & 15)]) != ep1) && it < POLL_LIMIT; it++) {}
        fence_acquire_gpu();
        if (el) mbar_arrive(sb + B_OS);
      }
      if (!half) {
        #pragma unroll 1
        for (int hh = 0; hh < 2; hh++) {
          const uint32_t src = sb + (1 + rank) * R5 + hh * 8192, fa = sb + B_GA + 16 * rank + 8 * hh;
          mbar_wait2(sb + B_UO + 8 * hh, 0, sb + B_GB + 8 * rank, 0);
          if (el) bulk_s2peer(mapa(src, rank ^ 1), src, 8192, mapa(fa, rank ^ 1));
        }
      }
      else if (f < NFFN) {
        mbar_wait(sb + B_UO + 24, 0);
        mbar_wait2(sb + B_UO, 0, sb + B_UO + 8, 0);
        uint32_t t0 = (uint32_t)clock();
        #pragma unroll 1
        for (int i = 0; i < 12; i++) {
          const int e = (FF_ORD >> (4 * i)) & 15;
          const uint32_t dst = sb + 16384 * ((FF_SLOT >> (4 * e)) & 15), fb = sb + B_F + 8 * e;
          if (i >= 2) mbar_wait(sb + B_WC + 8 * ((0x100066553244ull >> (4 * e)) & 15), 0);
          wait_until(t0);
          t0 = (uint32_t)clock() + (i < FF_N ? FF_DT : FF_D2);
          if (el) {
            mbar_expect_tx(fb, 16384);
            if (e >= 8) tma_3d_h(dst, &P.wd, 0, 32 * f, 4 * e - 32, fb, ef);
            else { tma_2d_h(dst, &P.wg, 32 * f, 128 * e, fb, ef); tma_2d_h(dst + 8192, &P.wu, 32 * f, 128 * e, fb, ef); }
          }
        }
      }
      __syncwarp();
    }
    if (wp & 1) {
      __syncwarp();
      fetch_o(wp, 1);
      mbar_wait(sb + B_OUT + 8 * (wp >> 1), 0);
      uint32_t t0 = (uint32_t)clock();
      #pragma unroll 1
      for (int i = 0; i < 8; i++) {
        wait_until(t0);
        if (el) tma_store_2d(&P.out, 128 * j + 64 * (i & 1), 128 * m128 + 32 * (wp & 2) + 8 * (i & 6), sb + OFF_OUT + (i & 1) * 16384 + (wp & 2) * 4096 + (i & 6) * 1024, ef);
        t0 += OUT_D;
      }
      if (el) { bulk_commit(); bulk_wait_all(); fence_async_global(); mbar_arrive(sb + B_SD); }
    }
    __syncwarp();
    cluster_arrive(); cluster_wait();
    return;
  }

  asm volatile("setmaxnreg.inc.sync.aligned.u32 160;");
  cluster_wait();
  const int t = tid & 127, g = lane >> 2;
  const uint32_t sa = (16 * wp + (lane & 15)) * 128 + (((lane >> 4) ^ (lane & 7)) << 4);

  if (wg == 2) {
    float s[2] = {0.f, 0.f}, s2[2] = {0.f, 0.f}, ck[8] = {0.f, 0.f, 0.f, 0.f, 0.f, 0.f, 0.f, 0.f}, cs[8] = {0.f, 0.f, 0.f, 0.f, 0.f, 0.f, 0.f, 0.f};
    const uint32_t ebr = mapa(sb + B_EMPTYKV, lane & 1), tg = (ld32_rlx(&G->epoch) + 1) & 3;
    auto addx = [&](const uint4 v) {
      const uint32_t w[4] = {v.x, v.y, v.z, v.w};
      #pragma unroll
      for (int e = 0; e < 4; e++) { const float a = bf_lo(w[e]), d = bf_hi(w[e]); s[0] += a; s[1] += d; s2[0] = fmaf(a, a, s2[0]); s2[1] = fmaf(d, d, s2[1]); }
    };
    auto addc = [&](const uint4 v, float (&o)[8]) {
      o[0] += bf_lo(v.x); o[1] += bf_hi(v.x); o[2] += bf_lo(v.y); o[3] += bf_hi(v.y); o[4] += bf_lo(v.z); o[5] += bf_hi(v.z); o[6] += bf_lo(v.w); o[7] += bf_hi(v.w);
    };
    {
      const uint32_t ra = (16 * nkv + (t >> 3)) * 128 + (t & 7) * 16;
      const uint32_t ca = 32768 + (m256 >> 2) * 8192 + (t >> 1) * 128 + (((2 * (m256 & 3) + (t & 1)) ^ ((t >> 1) & 7)) << 4);
      int rd = 0;
      mbar_wait(sb + B_S0, 0);
      #pragma unroll 1
      for (int kb = 0; kb < 10; kb++) {
        const uint32_t st = sb + (kb & 3) * KV_STAGE;
        mbar_wait(sb + B_FULLKV + 8 * (kb & 3), (kb >> 2) & 1);
        const uint4 x0 = lds128(st + ra), w0 = lds128(st + ca);
        addx(x0); addc(w0, ck);
        __syncwarp();
        if (lane < 2) mbar_arrive_remote(ebr + 8 * (kb & 3), 1);
        if ((SKM >> kb) & 1) {
          if (rd) {
            mbar_wait(sb + B_G, (rd - 1) & 1);
            #pragma unroll 1
            for (int i = 0; i < 2; i++) { addx(lds128(sb + OFF_G + (t >> 3) * 256 + (t & 7) * 16 + 128 * i)); addc(lds128(sb + OFF_G + 4096 + t * 16 + 2048 * i), ck); }
            bar_sync(NB_WG2, 128);
          }
          if (wp == 0 && elect_one()) {
            mbar_expect_tx(sb + B_G, 8192);
            if (rd < 3) {
              tma_2d(sb + OFF_G, &P.xs, 640 + 128 * rd, 256 * m256 + 16 * nkv, sb + B_G);
              tma_2d(sb + OFF_G + 4096, &P.ws, (1 + (m256 >> 2)) * DM + 64 * nkv + 16 * (m256 & 3), 640 + 128 * rd, sb + B_G);
            } else tma_2d(sb + OFF_G, &P.qs, 32 * (c & 31), 256 * (c >> 5), sb + B_G);
          }
          rd++;
        }
      }
    }
    const uint32_t scr = sb + OFF_WR;
    float sx = s[0] + s[1], sq = s2[0] + s2[1];
    #pragma unroll
    for (int o = 1; o < 8; o <<= 1) { sx += __shfl_xor_sync(~0u, sx, o); sq += __shfl_xor_sync(~0u, sq, o); }
    float v = reduce8(ck, lane);
    v += __shfl_xor_sync(~0u, v, 2);
    if (!(lane & 2)) stsf(scr + (wp * 16 + 8 * (lane & 1) + (lane >> 2)) * 4, v);

    bar_sync(NB_ZERO, 160);
    if ((lane & 7) == 0) {
      const float mean = sx * (1.f / DM);
      st64_rlx(&G->stats[256 * m256 + 16 * nkv + (t >> 3)], tagw(mean, tg), tagw(rsqrtf(fmaxf(sq * (1.f / DM) - mean * mean, 0.f) + 1e-5f), tg));
    }
    if (wp == 1 && lane < 16) {
      const uint32_t a = scr + lane * 4;
      st32_rlx(&G->cskv[128 * nkv + 16 * m256 + lane], tagw((ldsf(a) + ldsf(a + 64)) + (ldsf(a + 128) + ldsf(a + 192)), tg));
    }
    __syncwarp();
    bar_arrive(NB_PUB, 192);
    const uint4 wv = ld128_keep(P.wr + t * 8);
    #pragma unroll 1
    for (int i = 0; i < 2; i++) {
      mbar_wait(sb + B_G, i ^ 1);
      #pragma unroll 1
      for (int e = 0; e < 4; e++) addc(lds128(sb + OFF_G + t * 16 + 2048 * e), cs);
      bar_sync(NB_WG2, 128);
      if (i == 0 && wp == 0 && elect_one()) { mbar_expect_tx(sb + B_G, 8192); tma_2d(sb + OFF_G, &P.qs, 32 * (c & 31), 256 * (c >> 5) + 128, sb + B_G); }
    }
    float sw = (bf_lo(wv.x) + bf_hi(wv.x)) + (bf_lo(wv.y) + bf_hi(wv.y)) + (bf_lo(wv.z) + bf_hi(wv.z)) + (bf_lo(wv.w) + bf_hi(wv.w));
    #pragma unroll
    for (int o = 16; o; o >>= 1) sw += __shfl_xor_sync(~0u, sw, o);
    if (lane == 0) stsf(sb + OFF_SUMWR + wp * 4, sw);
    if ((t >> 4) == j) {
      const uint32_t a = sb + OFF_WR + (t & 15) * 32;
      sts128(a, wv.x << 16, wv.x & 0xffff0000u, wv.y << 16, wv.y & 0xffff0000u);
      sts128(a + 16, wv.z << 16, wv.z & 0xffff0000u, wv.w << 16, wv.w & 0xffff0000u);
    }
    v = reduce8(cs, lane);
    stsf(sb + OFF_G + (wp * 32 + 8 * (lane & 3) + (lane >> 2)) * 4, v);
    bar_sync(NB_WG2, 128);
    if (wp == 0) {
      const uint32_t a = sb + OFF_G + lane * 4, cq = tagw((ldsf(a) + ldsf(a + 128)) + (ldsf(a + 256) + ldsf(a + 384)), tg);
      st32_rlx(&G->csq[(c >> 5) * DM + 32 * (c & 31) + lane], cq);
      if (lane == 0) mbar_arrive_at(sb + B_W, rank, (cq & P.zero) + 1);
    }
  }

  uint32_t xr[32];
  {
    const bool isq = wg == 2;
    float acc[2][64];
    {
      const uint32_t emptyb = mapa(sb + (isq ? B_EMPTY5 : B_EMPTYKV), t & 1);
      auto correct = [&](uint32_t xa, uint32_t xb) {
        wg_fence();
        wgmma_sa_n128<0, 1, H0, H0>(acc[0], dlo(SB0, 0) + (xa >> 4), dlo(SB0, 0) + (xb >> 4));
        wgmma_sa_n128<0, 1, H0, H0>(acc[1], dlo(SB0, 0) + (xa >> 4) + 64, dlo(SB0, 0) + (xb >> 4));
        wg_commit();
      };
      if (!isq) {
        mbar_wait(sb + B_S0, 0);
        if (wg) mbar_wait(sb + B_FULLKV, 0);
        #pragma unroll 1
        for (int kb = 0; kb < 16; kb++) {
          const uint32_t da = dlo(SB0, 16) + wg * 1024 + (kb & 3) * (KV_STAGE >> 4), db = dlo(SB0 + 32768, 8192) + (kb & 3) * (KV_STAGE >> 4);
          wg_fence();
          #pragma unroll
          for (int k = 0; k < 4; k++) {
            wgmma_ss_n128<0, 1, H128, H128>(acc[0], da + 2 * k, db + 128 * k, k > 0 || kb != 0);
            wgmma_ss_n128<0, 1, H128, H128>(acc[1], da + 512 + 2 * k, db + 128 * k, k > 0 || kb != 0);
          }
          wg_commit();
          wg_wait<1>();
          if (kb > 0 && t < 2) mbar_arrive_remote(emptyb + 8 * ((kb - 1) & 3), kb > 10 ? 3 : 1);
          if (kb < 15) mbar_wait(sb + B_FULLKV + 8 * ((kb + 1) & 3), ((kb + 1) >> 2) & 1);
          if (kb == 0) mbar_wait(sb + B_FULLKV, 0);
          if (kb == 15 - LAG && wg == 1) bar_sync(NB_LAG, 256);
        }
        bar_arrive(wg ? NB_QGO : NB_LAG, 256);
        mbar_wait(sb + B_AUX, 0);
        correct(OFF_AXK + wg * 2048, OFF_BXK);
        wg_wait<0>();
        if (t < 2) mbar_arrive_remote(emptyb + 24, 3);
        fence_regs(acc[0]); fence_regs(acc[1]);
      const uint32_t stg = sb + OFF_X + (1 - wg) * 24576;
      const uint32_t va = stg + 16384 + (16 * wp + (lane & 15)) * 64 + (((lane >> 4) ^ ((lane >> 1) & 3)) << 4);
      const uint32_t ra = sb + OFF_RS256 + (128 * wg + 16 * wp + g) * 4;
      const float rs[4] = {ldsf(ra), ldsf(ra + 32), ldsf(ra + 256), ldsf(ra + 288)};
      float p[2][16];
      uint32_t vf[16], kf[2][16];
      auto project = [&](const uint32_t (&f)[16], uint32_t db) {
        wg_fence();
        #pragma unroll
        for (int i = 0; i < 2; i++) {
          wgmma_rs_n32<1, H64>(p[i], f[8*i], f[8*i+1], f[8*i+2], f[8*i+3], db, 0);
          wgmma_ra_n32<1, H64>(p[i], f[8*i+4], f[8*i+5], f[8*i+6], f[8*i+7], db + 64);
        }
        wg_commit();
      };
      auto fold = [&](uint32_t (&f)[16], int col, float sc) {
        #pragma unroll
        for (int i = 0; i < 16; i++) {
          const float r = rs[2 * (i >> 3) + (i & 1)] * sc;
          f[i] = pack_bf16(acc[i >> 3][col + 2 * (i & 7)] * r, acc[i >> 3][col + 2 * (i & 7) + 1] * r);
          asm volatile("" : "+r"(f[i]));
        }
      };
      auto put_v = [&](const uint32_t (&f)[16]) {
        #pragma unroll
        for (int k = 0; k < 4; k++) stsm4((va ^ ((k & 1) << 5)) + (k >> 1) * 4096, f[4*k], f[4*k+1], f[4*k+2], f[4*k+3]);
      };
      fold(vf, 48, 1.f);
      mbar_wait(sb + B_W, 0);
      fold(kf[0], 0, LOG2E);
      #pragma unroll
      for (int i = 0; i < 32; i++) p[i >> 4][i & 15] = acc[i >> 4][i & 15];
      project(kf[0], dlo(SB0 + OFF_WPHIK, 16));
      mbar_wait(sb + B_W, 0);
      {
        uint32_t v0[16];
        fold(kf[1], 16, LOG2E);
        fold(v0, 32, 1.f);
        if (wg == 1) bar_sync(NB_DN, 256);
        put_v(v0);
      }
      wg_wait<0>();
      fence_regs(p[0]); fence_regs(p[1]);
      if (wg == 1) bar_arrive(NB_WG01, 256);
      #pragma unroll 1
      for (int h = 0; h < 2; h++) {
        uint32_t ph[4][8];
        float rsum[2][4];
        dual_exp2(p[0], ph[0], ph[1]); dual_exp2(p[1], ph[2], ph[3]);
        row_sums(rsum, ph, dlo(SB0 + OFF_SEL, 16));
        if (wg == 0 && h == 0) { bar_arrive(NB_DN, 256); bar_sync(NB_WG01, 256); }
        if (h == 1) {
          if (wg == 1) bar_sync(NB_DN, 256);
          put_v(vf);
        }
        wg_wait<0>();
        fence_regs(rsum[0]); fence_regs(rsum[1]);
        if (!XC && __builtin_expect(__any_sync(~0u, !((rsum[0][0] + rsum[0][1]) + (rsum[0][2] + rsum[0][3]) + (rsum[1][0] + rsum[1][1]) + (rsum[1][2] + rsum[1][3]) < EXP_LIM)), 0)) {
          dual_exp2_shifted<true>(p, ph, rsum);
        }
        if (h == 0) project(kf[1], dlo(SB0 + OFF_WPHIK1, 16));
        normalize(ph, rsum);
        #pragma unroll
        for (int i = 0; i < 8; i++) {
          const uint32_t* f = &ph[i >> 1][4 * (i & 1)];
          stsm4(((stg + sa) ^ ((i & 3) << 5)) + (i >> 2) * 8192, f[0], f[1], f[2], f[3]);
        }
        fence_async_smem();
        if (wg == h) {
          float kv[20];
          #pragma unroll
          for (int w = 0; w < 2; w++) {
            const uint32_t da = dlo(SB0 + OFF_X, 16) + (h ^ w ^ 1) * 1536, db = dlo(SB0 + OFF_X + 16384, OFF_ONES - OFF_X - 16384) - (h ^ w ^ 1) * (1536 * 65535);
            if (w) bar_sync(NB_ST, 256); else bar_sync(NB_L0 + h, 128);
            wg_fence();
            #pragma unroll
            for (int k = 0; k < 8; k++) {
              if (k == 0 && w == 0) wgmma_sz_n40<1, 1, H128, H64>(kv, da, db);
              else wgmma_sa_n40<1, 1, H128, H64>(kv, da + k * 128, db - k * (64 * 65535));
            }
            wg_commit();
          }
          float4* dst = &G->kvacc[(ha + 2 * h) * KVP + t];
          wg_wait<0>();
          fence_regs(kv);
          if (h == 0) bar_arrive(NB_DN, 256); else if (t < 2) { mbar_arrive_at(sb + B_EMPTY5 + 40, t, 2); if (t == 0) mbar_arrive(sb + B_KD); }
          kv[17] = kv[18];
          #pragma unroll
          for (int i = 0; i < 6; i++) red_add_f32x4(dst + 128 * i, kv[3*i], kv[3*i+1], kv[3*i+2], 1.f);
        } else bar_arrive(NB_ST, 256);
        wg_wait<0>();
        fence_regs(p[0]); fence_regs(p[1]);
      }
      #pragma unroll
      for (int i = 0; i < 32; i++) asm volatile("mov.b32 %0, 0;" : "=r"(xr[i]));
      } else {
        uint32_t so = 0, po = 0, par = 0;
        mbar_wait(sb + B_FULL5, 0);
        bar_sync(NB_QGO, 256);
        #pragma unroll 1
        for (int kb = 0; kb < 16 - ML; kb++) {
          const uint32_t da = dlo(SB0, 16) + so * 256, db = dlo(SB0 + 16384, 8192) + so * 256;
          #pragma unroll
          for (int k = 0; k < 4; k++) {
            wg_fence();
            wgmma_ss_n128<0, 1, H128, H128>(acc[0], da + 2 * k, db + 128 * k, k > 0 || kb != 0);
            wgmma_ss_n128<0, 1, H128, H128>(acc[1], da + 512 + 2 * k, db + 128 * k, k > 0 || kb != 0);
            wg_commit();
            if (k == 1 && kb > 0 && t < 2) mbar_arrive_remote(emptyb + po, 2);
            if (k == 3) {
              po = so; so += 8;
              if (so == 40) { so = 0; par ^= 1; }
              mbar_wait(sb + B_FULL5 + so, par);
            }
            if ((QW >> k) & 1) wg_wait<2>(); else wg_wait<1>();
          }
        }
        auto block = [&](const int kb, const int i) {
          wg_fence();
          #pragma unroll
          for (int k = 0; k < 4; k++) wgmma_sa_n128<0, 1, H128, H128>(acc[i], dlo(SB0, 16) + (kb % 5) * 2048 + 512 * i + 2 * k, dlo(SB0 + 16384, 8192) + (kb % 5) * 2048 + 128 * k);
          wg_commit();
        };
        auto hand_over = [&](const int i) {
          const uint32_t ta = sb + (1 + rank) * R5 + sa + i * 8192;
          #pragma unroll
          for (int k = 0; k < 4; k++) {
            const float* a = &acc[i][32 * (k >> 1) + 8 * (k & 1)];
            stsm4(ta ^ (k << 5), pack_bf16(a[0], a[1]), pack_bf16(a[2], a[3]), pack_bf16(a[4], a[5]), pack_bf16(a[6], a[7]));
          }
        };
        mbar_wait2(sb + B_AUXQ, 0, sb + B_OS, 0);
        correct(OFF_AXQ, OFF_BXQ);
        #pragma unroll
        for (int kb = 16 - ML; kb < 16; kb++) {
          block(kb, 0);
          if (kb < 15) mbar_wait(sb + B_FULL5 + 8 * ((kb + 1) % 5), ((kb + 1) / 5) & 1);
          if (kb == 16 - ML) { wg_wait<2>(); if (t < 2) mbar_arrive_remote(emptyb + 8 * ((kb - 1) % 5), 2); }
        }
        mbar_wait(sb + B_RC, 0);
        block(16 - ML, 1);
        block(17 - ML, 1);
        wg_wait<2>();
        fence_regs(acc[0]);
        hand_over(0);
        fence_async_smem();
        bar_arrive(NB_Q0, 256);
        #pragma unroll
        for (int kb = 18 - ML; kb <= 16; kb++) {
          wg_wait<1>();
          if (t < 2) mbar_arrive_remote(emptyb + 8 * ((kb - 2) % 5), 2);
          if (kb < 16) block(kb, 1);
        }
        mbar_wait(sb + B_RC + 8, 0);
        wg_wait<0>();
        if (t < 2) mbar_arrive_remote(emptyb, 2);
        fence_regs(acc[1]);
        hand_over(1);
        fence_async_smem();
        bar_arrive(NB_Q0 + 1, 256);
        #pragma unroll
        for (int i = 0; i < 32; i++) { const float* a = &acc[(i >> 3) & 1][16 + 32 * (i >> 4) + 2 * (i & 7)]; xr[i] = pack_bf16(a[0], a[1]); }
      }
    }
    float p[2][16];
    #pragma unroll
    for (int i = 0; i < 32; i++) asm volatile("mov.b32 %0, 0;" : "=f"(p[i >> 4][i & 15]));
    auto project_r = [&](int w) {
      wg_fence();
      #pragma unroll
      for (int h = 0; h < 2; h++) {
        wgmma_rs_n32<1, H64>(p[h], xr[8*h], xr[8*h+1], xr[8*h+2], xr[8*h+3], dlo(SB0 + OFF_WPHIQ, 16) + 128 * w, 0);
        wgmma_ra_n32<1, H64>(p[h], xr[8*h+4], xr[8*h+5], xr[8*h+6], xr[8*h+7], dlo(SB0 + OFF_WPHIQ, 16) + 128 * w + 64);
      }
      wg_commit();
    };
    auto capture = [&](const int i) {
      if (!i) mbar_wait(sb + B_R, 0);
      #pragma unroll
      for (int k = 0; k < 4; k++) ldsm4(((sb + (1 + rank) * R5 + wg * 8192 + sa) ^ (k << 5)) + i * 2 * R5, xr[16*i+4*k], xr[16*i+4*k+1], xr[16*i+4*k+2], xr[16*i+4*k+3]);
      const uint32_t one = (((xr[16*i] | xr[16*i+4]) | (xr[16*i+8] | xr[16*i+12])) & P.zero) + 1;
      if (lane == 0) mbar_arrive_at(sb + (i ? B_RX : B_RC + 8 * wg), i ? wg : rank, one);
    };
    const uint32_t rq = sb + OFF_RSQ + (16 * wp + g) * 4 + 256 * (wg & 1), rb = rq + 128 * (wg & 2);
    const float cc[2][2] = {{ldsf(rq) * LOG2E, ldsf(rq + 32) * LOG2E}, {ldsf(rb) * LOG2E, ldsf(rb + 32) * LOG2E}};
    {
      const uint4* src = reinterpret_cast<const uint4*>(&G->kvacc[(4 * j + wg) * KVP + t]);
      const uint32_t full = kv_count(__float_as_uint(ldsf(sb + OFF_EP)), 8);
      uint4 v[12];
      #pragma unroll
      for (int i = 0; i < 12; i++) v[i] = i < 6 || isq ? ld128_rlx(src + 128 * i) : make_uint4(0, 0, 0, full);
      if (isq) {
        project_r(2);
        wg_wait<0>();
        #pragma unroll
        for (int i = 0; i < 16; i++) xr[i] = xr[16 + i];
      } else {
        capture(0);
      }
      #pragma unroll 1
      for (uint32_t it = 0; it < POLL_LIMIT; it++) {
        uint32_t bad = 0;
        #pragma unroll
        for (int i = 0; i < 12; i++) bad |= v[i].w ^ full;
        if (!__any_sync(~0u, bad != 0)) break;
        #pragma unroll
        for (int i = 0; i < 12; i++) if (i < 6 || isq) v[i] = ld128_rlx(src + 128 * i);
      }
      mbar_wait(sb + B_KD, 0);
      #pragma unroll
      for (int e = 0; e < 2; e++) {
        if (e == 0 || isq) {
          float f[18];
          #pragma unroll
          for (int i = 0; i < 6; i++) { f[3*i] = __uint_as_float(v[6*e+i].x); f[3*i+1] = __uint_as_float(v[6*e+i].y); f[3*i+2] = __uint_as_float(v[6*e+i].z); }
          const uint32_t ka = sb + OFF_KVZ + (wg + e) * 5120 + wp * 1280 + lane * 16;
          stsm4(ka, pack_bf16(f[0], f[1]), pack_bf16(f[2], f[3]), pack_bf16(f[4], f[5]), pack_bf16(f[6], f[7]));
          stsm4(ka + 512, pack_bf16(f[8], f[9]), pack_bf16(f[10], f[11]), pack_bf16(f[12], f[13]), pack_bf16(f[14], f[15]));
          stsm2(ka + 1024, pack_bf16(f[16], 1.f), pack_bf16(f[17], 1.f));
        }
      }
    }
    fence_async_smem();
    if (wg == 1) bar_arrive(NB_DN, 256);
    #pragma unroll 1
    for (int e = wg; e < wg + 1 + (wg >> 1); e++) {
      const int half = e >> 1, hh = e & 1, turn = e;
      const uint32_t ao = (1 + rank) * R5 + hh * 8192;
      uint32_t ph[4][8];
      #pragma unroll
      for (int i = 0; i < 32; i++) asm volatile("mov.b32 %0, 0;" : "=r"(ph[i >> 3][i & 7]));
      uint32_t shifted = 0;
      asm volatile("" : "+r"(shifted));
      #pragma unroll 1
      for (;;) {
        if (!XC && shifted) { float unused[2][4]; dual_exp2_shifted<false>(p, ph, unused); }
        uint32_t first = (shifted ^ 1) & !isq;
        asm volatile("" : "+r"(first));
        if (first) {
          bar_sync(NB_Q0 + wg, 256);
          const uint32_t da = dlo(SB0, 16) + (ao >> 4), db = dlo(SB0 + OFF_WPHIQ, 16);
          wg_fence();
          #pragma unroll
          for (int h = 0; h < 2; h++) {
            wgmma_ss_n32<0, 1, H128, H64>(p[h], da + 4 * h, db + 128 * h, 0);
            wgmma_sa_n32<0, 1, H128, H64>(p[h], da + 4 * h + 2, db + 128 * h + 64);
          }
          wg_commit();
          capture(1);
          wg_wait<0>();
        }
        fence_regs(p[0]); fence_regs(p[1]);
        uint32_t again = shifted;
        asm volatile("" : "+r"(again));
        if (again) break;
        float s2[4] = {0.f, 0.f, 0.f, 0.f};
        #pragma unroll
        for (int i = 0; i < 32; i++) { float& x = p[i >> 4][i & 15]; x *= cc[i >> 4][(i >> 1) & 1]; s2[i & 3] = fmaf(x, x, s2[i & 3]); }
        if (!__any_sync(~0u, !((s2[0] < ARG_LIM2) & (s2[1] < ARG_LIM2) & (s2[2] < ARG_LIM2) & (s2[3] < ARG_LIM2)))) break;
        shifted = 1;
      }
      if (e == 1 || e == 2) bar_sync(NB_TOK + e - 1, 256);
      float ac[4][20];
      auto numer = [&](int h) {
        const uint32_t (*f)[8] = &ph[2 * h];
        const uint32_t db = dlo(SB0 + OFF_KVZ, 128) + (half ? e : h) * 320;
        wg_fence();
        #pragma unroll
        for (int i = 0; i < 2; i++) {
          wgmma_rz_n40<1, dhi(256, 0)>(ac[2*h+i], f[i][0], f[i][1], f[i][2], f[i][3], db + i * 160);
          wgmma_ra_n40<1, dhi(256, 0)>(ac[2*h+i], f[i][4], f[i][5], f[i][6], f[i][7], db + (i * 160 + 80));
        }
        wg_commit();
      };
      const uint32_t oa = (16 * wp + g) * 128 + (((lane & 3) ^ g) << 4);
      auto finish = [&](int h) {
        const float* ap = ac[2 * h]; const float* am = ac[2 * h + 1];
        const float ip0 = rcp(ap[17]), im0 = rcp(am[17]), ip1 = rcp(ap[19]), im1 = rcp(am[19]);
        const float d0 = rcp(fmaf(ap[16], ip0, fmaf(am[16], im0, 1e-6f))), d1 = rcp(fmaf(ap[18], ip1, fmaf(am[18], im1, 1e-6f)));
        const float a0 = ip0 * d0, b0 = im0 * d0, a1 = ip1 * d1, b1 = im1 * d1;
        #pragma unroll
        for (int r = 0; r < 2; r++) {
          const float a = r ? a1 : a0, b = r ? b1 : b0;
          uint32_t w[4];
          #pragma unroll
          for (int k = 0; k < 4; k++) w[k] = pack_bf16(fmaf(ap[4*k+2*r], a, am[4*k+2*r] * b), fmaf(ap[4*k+2*r+1], a, am[4*k+2*r+1] * b));
          const uint32_t off = (oa ^ ((half ? rank : h) << 6)) + r * 1024;
          st128_rlx(reinterpret_cast<uint8_t*>(G->o + (m128 * 16 + (half ? 2 * (j & 6) + 2 * hh + 1 : 2 * j)) * 8192 + (half ? h : hh) * 4096) + off, w[0], w[1], w[2], w[3]);
          if (!half) sts128(sb + ao + off, w[0], w[1], w[2], w[3]);
        }
        if ((half || h) && lane < 8) st32_rlx(&G->oflag[((m128 * 6 + (half ? 2 * e - 2 + h : hh)) * 32 + 4 * j + wp) * 8 + lane], 1);
      };
      if (!shifted) dual_exp2(p[0], ph[0], ph[1]);
      numer(0);
      if (!shifted) dual_exp2(p[1], ph[2], ph[3]);
      if (turn < 2) bar_arrive(NB_TOK + turn, 256);
      if (wg == 0) bar_sync(NB_DN, 256);
      numer(1);
      wg_wait<1>();
      fence_regs(ac[0]); fence_regs(ac[1]);
      finish(0);
      wg_wait<0>();
      fence_regs(ac[2]); fence_regs(ac[3]);
      #pragma unroll
      for (int i = 0; i < 32; i++) asm volatile("mov.b32 %0, 0;" : "=f"(p[i >> 4][i & 15]));
      if (e == 2) project_r(3);
      finish(1);
      if (!half) fence_async_smem();
      __syncwarp();
      if (lane == 0) mbar_arrive(sb + B_UO + 8 * e);
      wg_wait<0>();
    }
    if (isq) cluster_arrive();
  }

  {
  int lane;
  asm volatile("mov.u32 %0, %%laneid;" : "=r"(lane));
  const int g = lane >> 2, q = lane & 3;
  if (wg < 2) {
    float h[64];
    {
      #pragma unroll
      for (int i = 0; i < 32; i++) { h[2*i] = bf_lo(xr[i]); h[2*i+1] = bf_hi(xr[i]); }
      fence_regs(h);
      const uint32_t emptyb = mapa(sb + B_EMPTY5, t & 1);
      uint32_t s = 1 + rank, ps = 0;
      mbar_wait2(sb + B_GB + 8 * rank, 0, sb + B_UO + 8 * wg, 0);
      #pragma unroll
      for (int i = 0; i < G2P; i++) {
        const uint32_t da = dlo(SB0, 16) + s * 2048 + wg * 512, db = dlo(SB0 + 16384, 8192) + s * 2048;
        wg_fence();
        #pragma unroll
        for (int k = 0; k < 4; k++) wgmma_sa_n128<0, 1, H128, H128>(h, da + k * 2, db + k * 128);
        wg_commit();
        const uint32_t ns = i ? (i + 2) % 6 : 2 - rank;
        const uint32_t nb = i ? i + 1 : 1 - rank, b0 = sb + B_GB + 8 * nb, b1 = sb + B_GA + 16 * nb + 8 * wg;
        const bool here = i == 15 || mbar_test2(b0, 0, b1, 0);
        wg_wait<1>();
        if (!(((2 * REL + 1) >> i) & 1) && i < 14 && t < 2) mbar_arrive_remote(emptyb + 8 * ps, 1);
        if ((REL >> i) & 1) { wg_wait<0>(); if (t < 2) mbar_arrive_remote(emptyb + 8 * s, 1); }
        if (!here) mbar_wait2u(b0, b1);
        ps = s; s = ns;
      }
      #pragma unroll 1
      for (int i = G2P; i < 16; i++) {
        const uint32_t da = dlo(SB0, 16) + s * 2048 + wg * 512, db = dlo(SB0 + 16384, 8192) + s * 2048;
        wg_fence();
        #pragma unroll
        for (int k = 0; k < 4; k++) wgmma_sa_n128<0, 1, H128, H128>(h, da + k * 2, db + k * 128);
        wg_commit();
        const uint32_t nb = min(i + 1, 15), b0 = sb + B_GB + 8 * nb, b1 = sb + B_GA + 16 * nb + 8 * wg;
        const bool here = mbar_test2(b0, 0, b1, 0);
        wg_wait<1>();
        if (t < 2) mbar_arrive_remote(emptyb + 8 * ps, 1);
        if (!here) mbar_wait2u(b0, b1);
        ps = s; s = s == 5 ? 0 : s + 1;
      }
    }
    cluster_arrive();
    float2 wr[16];
    #pragma unroll
    for (int i = 0; i < 16; i++) wr[i] = lds64f(sb + OFF_WR + 32 * i + 8 * q);
    const int r0 = 64 * wg + 16 * wp + g;
    float sum0, sum1, dot0, dot1, sq0, sq1;
    uint32_t redo = 0;
    asm volatile("" : "+r"(redo));
    #pragma unroll 1
    for (;;) {
    if (!XC && redo) {
      wg_wait<0>();
      #pragma unroll 1
      for (int n4 = 0; n4 < 4; n4++) {
        const uint32_t* xp = reinterpret_cast<const uint32_t*>(P.x + (size_t)(128 * m128 + r0) * DM + 128 * j) + 16 * n4 + q;
        #pragma unroll
        for (int i = 0; i < 48; i++) h[i] = h[i + 16];
        #pragma unroll
        for (int i = 0; i < 8; i++) { const uint32_t v = xp[4 * (i >> 1) + (i & 1) * 4 * DM]; h[48+2*i] = bf_lo(v); h[49+2*i] = bf_hi(v); }
        #pragma unroll 1
        for (int ks = 0; ks < 64; ks++) {
          const int kb = ks >> 2, kk = 16 * (ks & 3);
          const bf16* op = G->o + (m128 * 16 + kb) * 8192 + r0 * 64 + 2 * q + (((kk >> 3) ^ g) << 3);
          const uint32_t* w = reinterpret_cast<const uint32_t*>(P.wo_p) + 64 * j + 16 * n4 + q +
              (((kb & 1) ? 256 * (kb >> 2) + 32 * (kb & 2) + 32 + 4 * (kk & 32) : 64 * kb + 2 * (kk & 32)) + ((kk & 16) >> 2) + 4 * (g & 6) + (g & 1)) * (DM / 2);
          uint32_t b[8], a0, a1, a2, a3, it = 0;
          #pragma unroll
          for (int n = 0; n < 8; n++) b[n] = w[4 * (n >> 1) + (n & 1) * DM];
          const bf16* o2 = op + 8 - 16 * (g & 1);
          do { a0 = ld32_rlx(op); a1 = ld32_rlx(op + 512); a2 = ld32_rlx(o2); a3 = ld32_rlx(o2 + 512); }
          while (__any_sync(~0u, max(max(a0, a1), max(a2, a3)) == ~0u) && ++it < POLL_LIMIT);
          #pragma unroll
          for (int n = 0; n < 4; n++) mma16816(h[48+4*n], h[49+4*n], h[50+4*n], h[51+4*n], a0, a1, a2, a3, transpose8(b[2*n]), transpose8(b[2*n+1]));
        }
      }
    }
    wg_wait<0>();
    fence_regs(h);
    sum0 = 0.f, sum1 = 0.f, dot0 = 0.f, dot1 = 0.f, sq0 = 0.f, sq1 = 0.f;
    #pragma unroll
    for (int i = 0; i < 16; i++) {
      sum0 += h[4*i] + h[4*i+1]; sum1 += h[4*i+2] + h[4*i+3];
      sq0 = fmaf(h[4*i], h[4*i], fmaf(h[4*i+1], h[4*i+1], sq0)); sq1 = fmaf(h[4*i+2], h[4*i+2], fmaf(h[4*i+3], h[4*i+3], sq1));
      dot0 = fmaf(h[4*i], wr[i].x, fmaf(h[4*i+1], wr[i].y, dot0)); dot1 = fmaf(h[4*i+2], wr[i].x, fmaf(h[4*i+3], wr[i].y, dot1));
    }
    if (!__any_sync(~0u, !redo & (h[0] != h[0] | h[2] != h[2]))) break;
    redo = 1;
    }
    float4* const rs = &G->rstat[128 * m128 + r0];
    {
      const bool up = q & 2;
      float a = up ? sum1 : sum0, b = up ? sq1 : sq0, d = up ? dot1 : dot0;
      a += __shfl_xor_sync(~0u, up ? sum0 : sum1, 2); b += __shfl_xor_sync(~0u, up ? sq0 : sq1, 2); d += __shfl_xor_sync(~0u, up ? dot0 : dot1, 2);
      a += __shfl_xor_sync(~0u, a, 1); b += __shfl_xor_sync(~0u, b, 1); d += __shfl_xor_sync(~0u, d, 1);
      if ((q & 1) == 0) red_add_f32x4(rs + 4 * q, a, b, d, 1.f);
    }
    float rstd[2], bm[2];
    uint32_t best, it = 0;
    {
      const float2 swa = lds64f(sb + OFF_SUMWR), swb = lds64f(sb + OFF_SUMWR + 8);
      const float sw = (swa.x + swa.y) + (swb.x + swb.y);
      uint4 a[2]; uint32_t key[2];
      do { a[0] = ld128_rlx(rs); a[1] = ld128_rlx(rs + 8); } while (__any_sync(~0u, (a[0].w & a[1].w) != 0x41000000u) && ++it < POLL_LIMIT);
      #pragma unroll
      for (int i = 0; i < 2; i++) {
        const float mean = __uint_as_float(a[i].x) * (1.f / DM);
        rstd[i] = rsqrtf(fmaxf(__uint_as_float(a[i].y) * (1.f / DM) - mean * mean, 0.f) + 1e-5f);
        bm[i] = -mean * rstd[i];
        const uint32_t rr = __float_as_uint(fmaf(__uint_as_float(a[i].z), rstd[i], sw * bm[i]));
        key[i] = ((rr ^ ((uint32_t)((int32_t)rr >> 31) | 0x80000000u)) & ~2047u) | (2047 - 128 * m128 - r0 - 8 * i);
      }
      asm volatile("redux.sync.max.u32 %0, %1, 0xffffffff;" : "=r"(best) : "r"(max(key[0], key[1])));
    }
    sts32(sb + OFF_BEST + 4 * warp, best);
    bar_sync(NB_WG01, 256);
    {
      const uint4 b0 = lds128(sb + OFF_BEST), b1 = lds128(sb + OFF_BEST + 16);
      best = max(max(max(b0.x, b0.y), max(b0.z, b0.w)), max(max(b1.x, b1.y), max(b1.z, b1.w)));
    }
    const int win = ~best & 127;
    if (warp == ((win >> 4) ^ 1) && (lane < 4 || it == 0)) st128_rlx(&G->key[((2 * j + (lane >> 1)) & 15) * 128 + 8 * m128 + 4 * (lane & 1)], best, best, best, best);
    if ((win & 0x77) == r0) {
      const bool up = win & 8;
      const float ra = up ? rstd[1] : rstd[0], rb = up ? bm[1] : bm[0];
      uint32_t x[16];
      #pragma unroll
      for (int i = 0; i < 16; i++) x[i] = pack_bf16(fmaf(up ? h[4*i+2] : h[4*i], ra, rb), fmaf(up ? h[4*i+3] : h[4*i+1], ra, rb));
      #pragma unroll
      for (int i = 0; i < 4; i++) st128_rlx(&G->cand[m128 * 512 + 64 * j + 16 * i + 4 * q], x[4*i], x[4*i+1], x[4*i+2], x[4*i+3]);
    }
    __syncwarp();
    bar_arrive(NB_G2E, 384);
    {
      const float a0 = 1.f + rstd[0], b0 = bm[0], a1 = 1.f + rstd[1], b1 = bm[1];
      #pragma unroll
      for (int k = 0; k < 8; k++)
        stsm4(((sb + OFF_OUT + wg * 8192 + sa) ^ ((k & 3) << 5)) + (k >> 2) * 16384,
              pack_bf16(fmaf(h[8*k], a0, b0), fmaf(h[8*k+1], a0, b0)),     pack_bf16(fmaf(h[8*k+2], a1, b1), fmaf(h[8*k+3], a1, b1)),
              pack_bf16(fmaf(h[8*k+4], a0, b0), fmaf(h[8*k+5], a0, b0)),   pack_bf16(fmaf(h[8*k+6], a1, b1), fmaf(h[8*k+7], a1, b1)));
      fence_async_smem();
      __syncwarp();
      if (lane == 0) mbar_arrive(sb + B_OUT + 8 * wg);
    }
    {
      uint32_t wa[8][4][4];
      const uint32_t wb = sb + 16384 * (((uint32_t)FF_SLOT >> (4 * warp)) & 15) + ((lane & 7) + ((lane >> 4) << 3)) * 64 + ((((lane >> 3) & 1) ^ ((lane >> 1) & 3)) << 4);
      if (f < NFFN) mbar_wait(sb + B_F + 8 * warp, 0);
      #pragma unroll
      for (int i = 0; i < 32; i++) ldsm4t((wb ^ ((i & 1) << 5)) + ((i >> 1) & 1) * 8192 + (i >> 2) * 1024, wa[i >> 2][i & 3][0], wa[i >> 2][i & 3][1], wa[i >> 2][i & 3][2], wa[i >> 2][i & 3][3]);
      bar_sync(NB_XS, 384);
      uint4 xs[4];
      #pragma unroll
      for (int i = 0; i < 4; i++) xs[i] = lds128(sb + OFF_XSEL + 256 * warp + 64 * i + 16 * q);
      float d[4][4];
      #pragma unroll
      for (int ks = 0; ks < 8; ks++) {
        #pragma unroll
        for (int m = 0; m < 4; m++) {
          if (ks == 0) { d[m][0] = 0.f; d[m][1] = 0.f; d[m][2] = 0.f; d[m][3] = 0.f; }
          mma16816(d[m][0], d[m][1], d[m][2], d[m][3], wa[ks][m][0], wa[ks][m][1], wa[ks][m][2], wa[ks][m][3],
                   (ks & 1) ? xs[ks >> 1].z : xs[ks >> 1].x, (ks & 1) ? xs[ks >> 1].w : xs[ks >> 1].y);
        }
      }
      #pragma unroll
      for (int m = 0; m < 8; m++) stsf(sb + OFF_GU + (8 * m + g) * 48 + 4 * warp, d[m >> 1][2 * (m & 1)]);
      bar_arrive(NB_ACT, 384);
    }
    {
      const uint32_t ky = __float_as_uint(ldsf(sb + OFF_KEY));
      const int row = 2047 - (ky & 2047) - 128 * m128;
      if ((uint32_t)row < 128u) {
        const int vi = (j & 1) + wg, e = 3 * vi + q - 4 * (j & 1);
        const float kr = __uint_as_float((ky & ~2047u) ^ ((ky >> 31) ? 0x80000000u : 0xfffff800u));
        const int col = 32 * wp + 16 * (e & 1) + 4 * (e & 2) + g;
        const float sg = rcp(1.f + ex2(-LOG2E * kr));
        const uint32_t base = __float_as_uint(ldsf(sb + OFF_OUT + (col >> 6) * 16384 + row * 128 + ((((col >> 3) ^ row) & 7) << 4) + 2 * (col & 6)));
        const float4* yp = &G->yacc[(q * 3 + vi) * 128 + 32 * (j >> 1) + 8 * wp + g];
        uint32_t it = 0;
        uint4 v;
        mbar_wait(sb + B_SD, 0);
        do { v = ld128_rlx(yp); } while (__any_sync(~0u, __uint_as_float(v.w) != (float)(NFFN / 4)) && ++it < POLL_LIMIT);
        float y0 = __uint_as_float(v.x), y1 = __uint_as_float(v.y), y2 = __uint_as_float(v.z);
        #pragma unroll
        for (int o = 1; o < 4; o <<= 1) { y0 += __shfl_xor_sync(~0u, y0, o); y1 += __shfl_xor_sync(~0u, y1, o); y2 += __shfl_xor_sync(~0u, y2, o); }
        if (q < 3 && (uint32_t)e < 4u)
          P.out_p[(size_t)(128 * m128 + row) * DM + 128 * j + col] = __float2bfloat16(fmaf(q == 0 ? y0 : q == 1 ? y1 : y2, sg, (col & 1) ? bf_hi(base) : bf_lo(base)));
      }
      if (c == 0 && tid == 0) st32_rlx(&G->epoch, __float_as_uint(ldsf(sb + OFF_EP)));
    }
  }
  if (wg == 2) {
    uint32_t wf[16][2][4];
    {
      const uint32_t wb = sb + OFF_S + 16384 * (wp & 1) + ((lane & 7) + ((lane >> 4) << 3)) * 128 + ((((lane >> 3) & 1) ^ (lane & 7)) << 4);
      if (f < NFFN) mbar_wait(sb + B_WD + 8 * wp, 0);
      #pragma unroll
      for (int i = 0; i < 32; i++) ldsm4t((wb ^ (((i >> 1) & 3) << 5)) + (i >> 3) * 4096 + (i & 1) * 2048, wf[i >> 1][i & 1][0], wf[i >> 1][i & 1][1], wf[i >> 1][i & 1][2], wf[i >> 1][i & 1][3]);
      fence_async_smem();
      __syncwarp();
      if (lane == 0) mbar_arrive(sb + B_WC + 8 * wp);
    }
    bar_sync(NB_G2E, 384);
    {
      uint32_t cur = 0;
      uint4 v;
      #pragma unroll 1
      for (uint32_t it = 0; it < POLL_LIMIT; it++) {
        const uint32_t kx = ld32_rlx(&G->key[(c & 15) * 128 + 8 * (lane & 15)]);
        v = ld128_rlx(&G->cand[((~cur >> 7) & 15) * 512 + 4 * t]);
        uint32_t best;
        asm volatile("redux.sync.max.u32 %0, %1, 0xffffffff;" : "=r"(best) : "r"(kx));
        if (!__any_sync(~0u, kx == 0 || v.w == ~0u) && best == cur) break;
        cur = best;
      }
      sts128(sb + OFF_XSEL + 16 * t, v.x, v.y, v.z, v.w);
      sts32(sb + OFF_KEY, cur);
      bar_arrive(NB_XS, 384);
    }
    float4* yd = &G->yacc[(f & 3) * 384 + 32 * wp + 8 * q + g];
    asm volatile("" : "+l"(yd));
    if (f >= NFFN) { bar_arrive(NB_ACT, 384); cluster_wait(); return; }
    bar_sync(NB_ACT, 384);
    float gu[2];
    #pragma unroll
    for (int i = 0; i < 2; i++) {
      const uint4 v0 = lds128(sb + OFF_GU + (32 * i + lane) * 48), v1 = lds128(sb + OFF_GU + (32 * i + lane) * 48 + 16);
      gu[i] = ((__uint_as_float(v0.x) + __uint_as_float(v0.y)) + (__uint_as_float(v0.z) + __uint_as_float(v0.w))) +
              ((__uint_as_float(v1.x) + __uint_as_float(v1.y)) + (__uint_as_float(v1.z) + __uint_as_float(v1.w)));
    }
    const float act = gu[0] * gu[1] * rcp(1.f + ex2(-LOG2E * gu[0]));
    const uint32_t ap = pack_bf16(act, __shfl_down_sync(~0u, act, 1));
    uint32_t bf[4];
    #pragma unroll
    for (int i = 0; i < 4; i++) bf[i] = __shfl_sync(~0u, ap, 2 * q + 8 * i);
    float d[16][4];
    #pragma unroll
    for (int k = 0; k < 2; k++)
      #pragma unroll
      for (int i = 0; i < 16; i++) {
        if (k == 0) { d[i][0] = 0.f; d[i][1] = 0.f; d[i][2] = 0.f; d[i][3] = 0.f; }
        mma16816(d[i][0], d[i][1], d[i][2], d[i][3], wf[i][k][0], wf[i][k][1], wf[i][k][2], wf[i][k][3], bf[2*k], bf[2*k+1]);
      }
    float y[9];
    #pragma unroll
    for (int e = 0; e < 8; e++) {
      const int n = 2 * (e & 4) + (e & 1);
      const float lo = (q & 1) ? d[n + 2][e & 2] : d[n][e & 2], hi = (q & 1) ? d[n + 6][e & 2] : d[n + 4][e & 2];
      y[e] = (q & 2) ? hi : lo;
    }
    y[8] = 0.f;
    #pragma unroll
    for (int i = 0; i < 3; i++) red_add_f32x4(yd + 128 * i, y[3*i], y[3*i+1], y[3*i+2], 1.f);
  }
  }
  cluster_wait();
}

typedef CUresult (*EncodeFn)(CUtensorMap*, CUtensorMapDataType, cuuint32_t, void*, const cuuint64_t*, const cuuint64_t*,
                             const cuuint32_t*, const cuuint32_t*, CUtensorMapInterleave, CUtensorMapSwizzle,
                             CUtensorMapL2promotion, CUtensorMapFloatOOBfill);

void make_map(EncodeFn enc, CUtensorMap* m, const void* p, int n, const cuuint64_t* dims, const cuuint64_t* str, const cuuint32_t* box,
              CUtensorMapSwizzle sw, CUtensorMapL2promotion promo) {
  cuuint32_t es[5] = {1, 1, 1, 1, 1};
  enc(m, CU_TENSOR_MAP_DATA_TYPE_BFLOAT16, n, const_cast<void*>(p), dims, str, box, es, CU_TENSOR_MAP_INTERLEAVE_NONE, sw, promo,
      CU_TENSOR_MAP_FLOAT_OOB_FILL_NONE);
}
void map2(EncodeFn enc, CUtensorMap* m, const void* p, uint64_t cols, uint64_t rows, uint32_t bc, uint32_t br, CUtensorMapSwizzle sw,
          CUtensorMapL2promotion promo) {
  const cuuint64_t dims[2] = {cols, rows}, str[1] = {cols * 2};
  const cuuint32_t box[2] = {bc, br};
  make_map(enc, m, p, 2, dims, str, box, sw, promo);
}
void map3(EncodeFn enc, CUtensorMap* m, const void* p, uint64_t cols, uint64_t rows, uint32_t br, uint32_t nb) {
  const cuuint64_t dims[3] = {64, rows, cols / 64}, str[2] = {cols * 2, 128};
  const cuuint32_t box[3] = {64, br, nb};
  make_map(enc, m, p, 3, dims, str, box, CU_TENSOR_MAP_SWIZZLE_128B, CU_TENSOR_MAP_L2_PROMOTION_L2_128B);
}

}

extern "C" void kernel_launch(void* const* d_in, const int* in_sizes, int n_in, void* d_out, int out_size) {
  (void)in_sizes; (void)n_in; (void)out_size;
  static EncodeFn enc = nullptr;
  static void* o_ptr = nullptr;
  if (!enc) {
    void* f = nullptr; cudaDriverEntryPointQueryResult qr;
    cudaGetDriverEntryPoint("cuTensorMapEncodeTiled", &f, cudaEnableDefault, &qr);
    enc = (EncodeFn)f;
    cudaGetSymbolAddress(&o_ptr, g_scr);
    cudaFuncSetAttribute(fused_kernel, cudaFuncAttributeMaxDynamicSharedMemorySize, SMEM_BYTES);
  }
  const bf16* x = (const bf16*)d_in[0];
  const bf16* wqkv = (const bf16*)d_in[1];
  const bf16* wphi = (const bf16*)d_in[2];
  const bf16* wo = (const bf16*)d_in[3];
  const bf16* wr = (const bf16*)d_in[5];
  const bf16* wgate = (const bf16*)d_in[6];
  const bf16* wup = (const bf16*)d_in[7];
  const bf16* wdown = (const bf16*)d_in[8];
  Params P;
  const CUtensorMapSwizzle S128 = CU_TENSOR_MAP_SWIZZLE_128B, S64 = CU_TENSOR_MAP_SWIZZLE_64B;
  const CUtensorMapL2promotion L128 = CU_TENSOR_MAP_L2_PROMOTION_L2_128B, L256 = CU_TENSOR_MAP_L2_PROMOTION_L2_256B,
                               L64 = CU_TENSOR_MAP_L2_PROMOTION_L2_64B;
  map2(enc, &P.x128, x, DM, SEQ, 64, 128, S128, L128);
  map2(enc, &P.x64, x, DM, SEQ, 64, 64, S128, L128);
  {
    const cuuint64_t dims[4] = {64, DM, 16, 3}, str[3] = {6 * DM, 128, 2 * DM};
    const cuuint32_t box[4] = {64, 64, 1, 2};
    make_map(enc, &P.wkv, wqkv, 4, dims, str, box, S128, L128);
  }
  map3(enc, &P.wq, wqkv, 3 * DM, DM, 64, 2);
  for (int i = 0; i < 2; i++) {
    const cuuint64_t dims[5] = {DM, (cuuint64_t)(DM - 94 - 64 * i), 4, 4, 2}, str[4] = {2 * DM, 16 * DM, 4 * DM, (cuuint64_t)(128 * DM) << i};
    const cuuint32_t box[5] = {64, 2, 4, 4, 2};
    make_map(enc, &P.wo[i], wo, 5, dims, str, box, S128, L128);
  }
  map3(enc, &P.wd, wdown, DM, FF, 32, 4);
  map2(enc, &P.wg, wgate, FF, DM, 32, 128, S64, L64);
  map2(enc, &P.wu, wup, FF, DM, 32, 128, S64, L64);
  map2(enc, &P.tg, wgate, FF, DM, 8, 16, CU_TENSOR_MAP_SWIZZLE_NONE, L128);
  map2(enc, &P.tu, wup, FF, DM, 8, 16, CU_TENSOR_MAP_SWIZZLE_NONE, L128);
  map2(enc, &P.td, wdown, 128, FF * 8, 8, 16, CU_TENSOR_MAP_SWIZZLE_NONE, L256);
  map2(enc, &P.xs, x, DM, SEQ, 128, 16, CU_TENSOR_MAP_SWIZZLE_NONE, L256);
  map2(enc, &P.ws, wqkv, 3 * DM, DM, 16, 128, CU_TENSOR_MAP_SWIZZLE_NONE, L128);
  map2(enc, &P.qs, wqkv, 3 * DM, DM, 32, 128, CU_TENSOR_MAP_SWIZZLE_NONE, L64);
  map2(enc, &P.out, d_out, DM, SEQ, 64, 16, S128, L128);
  map2(enc, &P.o, o_ptr, 256, SEQ * DM / 256, 256, 16, CU_TENSOR_MAP_SWIZZLE_NONE, L128);
  map2(enc, &P.phi, wphi, 32, 1024, 32, 32, S64, L64);
  P.x = x; P.wqkv = wqkv; P.wo_p = wo; P.wr = wr; P.out_p = (bf16*)d_out; P.g = (Scratch*)o_ptr; P.zero = 0;

  fused_kernel<<<128, 512, SMEM_BYTES, cudaStreamPerThread>>>(P);
}
```

```cpp
#include <cuda_runtime.h>
#include <cuda.h>
#include <cuda_bf16.h>
#include <stdint.h>

namespace {

typedef __nv_bfloat16 bf16;

__device__ __forceinline__ uint32_t smem_u32(const void* p){ return (uint32_t)__cvta_generic_to_shared(p); }
__device__ __forceinline__ void mbar_init(uint32_t bar, uint32_t cnt){ asm volatile("mbarrier.init.shared::cta.b64 [%0], %1;"::"r"(bar),"r"(cnt):"memory"); }
__device__ __forceinline__ void mbar_expect_tx(uint32_t bar, uint32_t bytes){ asm volatile("mbarrier.arrive.expect_tx.shared::cta.b64 _, [%0], %1;"::"r"(bar),"r"(bytes):"memory"); }
__device__ __forceinline__ void mbar_arrive(uint32_t bar){ asm volatile("mbarrier.arrive.shared::cta.b64 _, [%0];"::"r"(bar):"memory"); }
__device__ __forceinline__ uint32_t mapa(uint32_t addr, uint32_t cta){ uint32_t r; asm volatile("mapa.shared::cluster.u32 %0, %1, %2;":"=r"(r):"r"(addr),"r"(cta)); return r; }
__device__ __forceinline__ void mbar_arrive_at(uint32_t bar, uint32_t cta, uint32_t cnt){
  asm volatile("{\n.reg .b32 ra;\nmapa.shared::cluster.u32 ra, %0, %1;\nmbarrier.arrive.shared::cluster.b64 _, [ra], %2;\n}\n"::"r"(bar),"r"(cta),"r"(cnt):"memory"); }
__device__ __forceinline__ void mbar_arrive_remote(uint32_t cluster_addr, uint32_t cnt){
  asm volatile("mbarrier.arrive.shared::cluster.b64 _, [%0], %1;"::"r"(cluster_addr),"r"(cnt):"memory"); }
__device__ __forceinline__ void mbar_wait(uint32_t bar, uint32_t parity){
  asm volatile("{\n.reg .pred p;\n.reg .u32 c;\nmov.u32 c, 0;\nLW:\nmbarrier.try_wait.parity.shared::cta.b64 p, [%0], %1;\n@p bra LD;\nadd.u32 c, c, 1;\nsetp.lt.u32 p, c, 2000000;\n@p bra LW;\ntrap;\nLD:\n}\n"::"r"(bar),"r"(parity):"memory"); }
__device__ __forceinline__ void mbar_wait2(uint32_t bar0, uint32_t par0, uint32_t bar1, uint32_t par1){
  asm volatile("{\n.reg .pred p, q;\n.reg .u32 c;\nmov.u32 c, 0;\nLW:\nmbarrier.try_wait.parity.shared::cta.b64 p, [%0], %1;\nmbarrier.try_wait.parity.shared::cta.b64 q, [%2], %3;\nand.pred p, p, q;\n@p bra LD;\nadd.u32 c, c, 1;\nsetp.lt.u32 p, c, 2000000;\n@p bra LW;\ntrap;\nLD:\n}\n"::"r"(bar0),"r"(par0),"r"(bar1),"r"(par1):"memory"); }
__device__ __forceinline__ void mbar_wait2u(uint32_t bar0, uint32_t bar1){
  asm volatile("{\n.reg .pred p, q;\nLW:\nmbarrier.try_wait.parity.shared::cta.b64 p, [%0], 0;\nmbarrier.try_wait.parity.shared::cta.b64 q, [%1], 0;\nand.pred p, p, q;\n@!p bra LW;\n}\n"::"r"(bar0),"r"(bar1):"memory"); }
__device__ __forceinline__ bool mbar_test2(uint32_t bar0, uint32_t par0, uint32_t bar1, uint32_t par1){
  uint32_t r;
  asm volatile("{\n.reg .pred p, q;\nmbarrier.test_wait.parity.shared::cta.b64 p, [%1], %2;\nmbarrier.test_wait.parity.shared::cta.b64 q, [%3], %4;\nand.pred p, p, q;\nselp.u32 %0, 1, 0, p;\n}\n":"=r"(r):"r"(bar0),"r"(par0),"r"(bar1),"r"(par1):"memory");
  return r; }
__device__ __forceinline__ void tma_2d(uint32_t dst, const CUtensorMap* m, int c0, int c1, uint32_t bar){
  asm volatile("cp.async.bulk.tensor.2d.shared::cluster.global.mbarrier::complete_tx::bytes [%0], [%1, {%3, %4}], [%2];"::"r"(dst),"l"(m),"r"(bar),"r"(c0),"r"(c1):"memory"); }
__device__ __forceinline__ void tma_2d_h(uint32_t dst, const CUtensorMap* m, int c0, int c1, uint32_t bar, uint64_t pol){
  asm volatile("cp.async.bulk.tensor.2d.shared::cluster.global.mbarrier::complete_tx::bytes.L2::cache_hint [%0], [%1, {%3, %4}], [%2], %5;"::"r"(dst),"l"(m),"r"(bar),"r"(c0),"r"(c1),"l"(pol):"memory"); }
__device__ __forceinline__ void tma_2d_mc(uint32_t dst, const CUtensorMap* m, int c0, int c1, uint32_t bar){
  asm volatile("cp.async.bulk.tensor.2d.shared::cluster.global.mbarrier::complete_tx::bytes.multicast::cluster [%0], [%1, {%3, %4}], [%2], %5;"::"r"(dst),"l"(m),"r"(bar),"r"(c0),"r"(c1),"h"((uint16_t)3):"memory"); }
__device__ __forceinline__ void tma_2d_mc_h(uint32_t dst, const CUtensorMap* m, int c0, int c1, uint32_t bar, uint64_t pol){
  asm volatile("cp.async.bulk.tensor.2d.shared::cluster.global.mbarrier::complete_tx::bytes.multicast::cluster.L2::cache_hint [%0], [%1, {%3, %4}], [%2], %5, %6;"::"r"(dst),"l"(m),"r"(bar),"r"(c0),"r"(c1),"h"((uint16_t)3),"l"(pol):"memory"); }
__device__ __forceinline__ void tma_4d(uint32_t dst, const CUtensorMap* m, int c0, int c1, int c2, int c3, uint32_t bar){
  asm volatile("cp.async.bulk.tensor.4d.shared::cluster.global.mbarrier::complete_tx::bytes [%0], [%1, {%3, %4, %5, %6}], [%2];"::"r"(dst),"l"(m),"r"(bar),"r"(c0),"r"(c1),"r"(c2),"r"(c3):"memory"); }
__device__ __forceinline__ uint64_t policy_evict_first(){ uint64_t p; asm volatile("createpolicy.fractional.L2::evict_first.b64 %0, 1.0;":"=l"(p)); return p; }
__device__ __forceinline__ uint64_t policy_evict_normal(){ uint64_t p; asm("createpolicy.fractional.L2::evict_normal.b64 %0, 1.0;":"=l"(p)); return p; }
__device__ __forceinline__ void tma_3d_h(uint32_t dst, const CUtensorMap* m, int c0, int c1, int c2, uint32_t bar, uint64_t pol){
  asm volatile("cp.async.bulk.tensor.3d.shared::cluster.global.mbarrier::complete_tx::bytes.L2::cache_hint [%0], [%1, {%3, %4, %5}], [%2], %6;"::"r"(dst),"l"(m),"r"(bar),"r"(c0),"r"(c1),"r"(c2),"l"(pol):"memory"); }
__device__ __forceinline__ void tma_4d_h(uint32_t dst, const CUtensorMap* m, int c0, int c1, int c2, int c3, uint32_t bar, uint64_t pol){
  asm volatile("cp.async.bulk.tensor.4d.shared::cluster.global.mbarrier::complete_tx::bytes.L2::cache_hint [%0], [%1, {%3, %4, %5, %6}], [%2], %7;"::"r"(dst),"l"(m),"r"(bar),"r"(c0),"r"(c1),"r"(c2),"r"(c3),"l"(pol):"memory"); }
__device__ __forceinline__ void red_add_f32x4(float4* p, float x, float y, float z, float w){ asm volatile("red.relaxed.gpu.global.add.v4.f32 [%0], {%1,%2,%3,%4};"::"l"(p),"f"(x),"f"(y),"f"(z),"f"(w):"memory"); }
__device__ __forceinline__ void tma_5d_h(uint32_t dst, const CUtensorMap* m, int c0, int c1, uint32_t bar, uint64_t pol){
  asm volatile("cp.async.bulk.tensor.5d.shared::cluster.global.mbarrier::complete_tx::bytes.L2::cache_hint [%0], [%1, {%3, %4, 0, 0, 0}], [%2], %5;"::"r"(dst),"l"(m),"r"(bar),"r"(c0),"r"(c1),"l"(pol):"memory"); }
__device__ __forceinline__ void tma_store_2d(const CUtensorMap* m, int c0, int c1, uint32_t src, uint64_t pol){
  asm volatile("cp.async.bulk.tensor.2d.global.shared::cta.bulk_group.L2::cache_hint [%0, {%2, %3}], [%1], %4;"::"l"(m),"r"(src),"r"(c0),"r"(c1),"l"(pol):"memory"); }
__device__ __forceinline__ void bulk_commit(){ asm volatile("cp.async.bulk.commit_group;":::"memory"); }
__device__ __forceinline__ void bulk_wait_all(){ asm volatile("cp.async.bulk.wait_group 0;":::"memory"); }
__device__ __forceinline__ void fence_async_global(){ asm volatile("fence.proxy.async.global;":::"memory"); }
__device__ __forceinline__ bool elect_one(){ uint32_t p; asm volatile("{\n.reg .pred P;\nelect.sync _|P, 0xffffffff;\nselp.b32 %0, 1, 0, P;\n}\n":"=r"(p)); return p; }
__device__ __forceinline__ void bulk_prefetch(const void* p, uint32_t bytes){
  asm volatile("cp.async.bulk.prefetch.L2.global [%0], %1;"::"l"(p),"r"(bytes):"memory"); }
__device__ __forceinline__ void bulk_s2peer(uint32_t dst_cluster, uint32_t src, uint32_t bytes, uint32_t bar_cluster){
  asm volatile("cp.async.bulk.shared::cluster.shared::cta.mbarrier::complete_tx::bytes [%0], [%1], %2, [%3];"::"r"(dst_cluster),"r"(src),"r"(bytes),"r"(bar_cluster):"memory"); }
__device__ __forceinline__ void prefetch_map(const CUtensorMap* m){ asm volatile("prefetch.tensormap [%0];"::"l"(m):"memory"); }
__device__ __forceinline__ void fence_async_smem(){ asm volatile("fence.proxy.async.shared::cta;":::"memory"); }
__device__ __forceinline__ void fence_acquire_gpu(){ asm volatile("fence.acquire.gpu;":::"memory"); }
__device__ __forceinline__ void fence_gpu(){ asm volatile("fence.acq_rel.gpu;":::"memory"); }
__device__ __forceinline__ void wg_fence(){ asm volatile("wgmma.fence.sync.aligned;":::"memory"); }
__device__ __forceinline__ void wg_commit(){ asm volatile("wgmma.commit_group.sync.aligned;":::"memory"); }
template<int N> __device__ __forceinline__ void wg_wait(){ asm volatile("wgmma.wait_group.sync.aligned %0;"::"n"(N):"memory"); }
template<int N> __device__ __forceinline__ void fence_regs(float (&d)[N]){
  #pragma unroll
  for(int i=0;i<N;i++) asm volatile("":"+f"(d[i])::"memory"); }
__device__ __forceinline__ void bar_sync(int id, int n){ asm volatile("bar.sync %0, %1;"::"r"(id),"r"(n):"memory"); }
__device__ __forceinline__ void bar_arrive(int id, int n){ asm volatile("bar.arrive %0, %1;"::"r"(id),"r"(n):"memory"); }
__device__ __forceinline__ void cluster_arrive(){ asm volatile("barrier.cluster.arrive.relaxed.aligned;":::"memory"); }
__device__ __forceinline__ void cluster_wait(){ asm volatile("barrier.cluster.wait.aligned;":::"memory"); }
__host__ __device__ constexpr uint32_t dlo(uint32_t addr, uint32_t lbo){ return (addr >> 4) | ((lbo >> 4) << 16); }
__host__ __device__ constexpr uint32_t dhi(uint32_t sbo, uint32_t sw){ return (sbo >> 4) | (sw << 30); }
constexpr uint32_t H128 = dhi(1024, 1), H64 = dhi(512, 2), H0 = dhi(128, 0);
__device__ __forceinline__ uint32_t pack_bf16(float lo, float hi){ uint32_t r; asm("cvt.rn.bf16x2.f32 %0, %1, %2;":"=r"(r):"f"(hi),"f"(lo)); return r; }
__device__ __forceinline__ float bf_lo(uint32_t v){ return __uint_as_float(v<<16); }
__device__ __forceinline__ float bf_hi(uint32_t v){ return __uint_as_float(v&0xffff0000u); }
__device__ __forceinline__ float ex2(float x){ float r; asm("ex2.approx.ftz.f32 %0, %1;":"=f"(r):"f"(x)); return r; }
__device__ __forceinline__ float rcp(float x){ float r; asm("rcp.approx.ftz.f32 %0, %1;":"=f"(r):"f"(x)); return r; }
__device__ __forceinline__ void stsm4(uint32_t addr, uint32_t a, uint32_t b, uint32_t c, uint32_t d){
  asm volatile("stmatrix.sync.aligned.m8n8.x4.shared.b16 [%0], {%1,%2,%3,%4};"::"r"(addr),"r"(a),"r"(b),"r"(c),"r"(d)); }
__device__ __forceinline__ void stsm2(uint32_t addr, uint32_t a, uint32_t b){
  asm volatile("stmatrix.sync.aligned.m8n8.x2.shared.b16 [%0], {%1,%2};"::"r"(addr),"r"(a),"r"(b)); }
__device__ __forceinline__ void mma16816(float& d0, float& d1, float& d2, float& d3, uint32_t a0, uint32_t a1, uint32_t a2, uint32_t a3, uint32_t b0, uint32_t b1){
  asm volatile("mma.sync.aligned.m16n8k16.row.col.f32.bf16.bf16.f32 {%0,%1,%2,%3}, {%4,%5,%6,%7}, {%8,%9}, {%0,%1,%2,%3};"
               : "+f"(d0), "+f"(d1), "+f"(d2), "+f"(d3) : "r"(a0), "r"(a1), "r"(a2), "r"(a3), "r"(b0), "r"(b1)); }
__device__ __forceinline__ uint32_t transpose8(uint32_t a){ uint32_t r; asm volatile("movmatrix.sync.aligned.m8n8.trans.b16 %0, %1;":"=r"(r):"r"(a)); return r; }
__device__ __forceinline__ void ldsm4(uint32_t addr, uint32_t& a, uint32_t& b, uint32_t& c, uint32_t& d){
  asm volatile("ldmatrix.sync.aligned.m8n8.x4.shared.b16 {%0,%1,%2,%3}, [%4];":"=r"(a),"=r"(b),"=r"(c),"=r"(d):"r"(addr):"memory"); }
__device__ __forceinline__ void ldsm4t(uint32_t addr, uint32_t& a, uint32_t& b, uint32_t& c, uint32_t& d){
  asm volatile("ldmatrix.sync.aligned.m8n8.x4.trans.shared.b16 {%0,%1,%2,%3}, [%4];":"=r"(a),"=r"(b),"=r"(c),"=r"(d):"r"(addr):"memory"); }
__device__ __forceinline__ void sts32(uint32_t a, uint32_t v){ asm volatile("st.shared.b32 [%0], %1;"::"r"(a),"r"(v):"memory"); }
__device__ __forceinline__ void stsf(uint32_t a, float v){ asm volatile("st.shared.f32 [%0], %1;"::"r"(a),"f"(v):"memory"); }
__device__ __forceinline__ void sts64(uint32_t a, uint32_t x, uint32_t y){ asm volatile("st.shared.v2.b32 [%0], {%1,%2};"::"r"(a),"r"(x),"r"(y):"memory"); }
__device__ __forceinline__ void sts128(uint32_t a, uint32_t x, uint32_t y, uint32_t z, uint32_t w){ asm volatile("st.shared.v4.b32 [%0], {%1,%2,%3,%4};"::"r"(a),"r"(x),"r"(y),"r"(z),"r"(w):"memory"); }
__device__ __forceinline__ float ldsf(uint32_t a){ float v; asm volatile("ld.shared.f32 %0, [%1];":"=f"(v):"r"(a):"memory"); return v; }
__device__ __forceinline__ float2 lds64f(uint32_t a){ float2 v; asm volatile("ld.shared.v2.f32 {%0,%1}, [%2];":"=f"(v.x),"=f"(v.y):"r"(a):"memory"); return v; }
__device__ __forceinline__ uint4 lds128(uint32_t a){ uint4 v; asm volatile("ld.shared.v4.u32 {%0,%1,%2,%3}, [%4];":"=r"(v.x),"=r"(v.y),"=r"(v.z),"=r"(v.w):"r"(a):"memory"); return v; }
__device__ __forceinline__ uint4 ld128_keep(const void* p){ uint4 v; asm volatile("ld.global.v4.u32 {%0,%1,%2,%3}, [%4];":"=r"(v.x),"=r"(v.y),"=r"(v.z),"=r"(v.w):"l"(p):"memory"); return v; }
__device__ __forceinline__ uint4 ld128_rlx(const void* p){ uint4 v; asm volatile("ld.relaxed.gpu.global.v4.u32 {%0,%1,%2,%3}, [%4];":"=r"(v.x),"=r"(v.y),"=r"(v.z),"=r"(v.w):"l"(p):"memory"); return v; }
__device__ __forceinline__ uint32_t ld32_rlx(const void* p){ uint32_t v; asm volatile("ld.relaxed.gpu.global.u32 %0, [%1];":"=r"(v):"l"(p):"memory"); return v; }
__device__ __forceinline__ void st128_rlx(void* p, uint32_t x, uint32_t y, uint32_t z, uint32_t w){ asm volatile("st.relaxed.gpu.global.v4.u32 [%0], {%1,%2,%3,%4};"::"l"(p),"r"(x),"r"(y),"r"(z),"r"(w):"memory"); }
__device__ __forceinline__ void st64_rlx(void* p, uint32_t x, uint32_t y){ asm volatile("st.relaxed.gpu.global.v2.u32 [%0], {%1,%2};"::"l"(p),"r"(x),"r"(y):"memory"); }
__device__ __forceinline__ void st32_rlx(void* p, uint32_t x){ asm volatile("st.relaxed.gpu.global.u32 [%0], %1;"::"l"(p),"r"(x):"memory"); }
__device__ __forceinline__ void wait_until(uint32_t t){ while ((int32_t)((uint32_t)clock() - t) < 0) __nanosleep(32); }
__device__ __forceinline__ void flags_wait(uint32_t& missing, const uint32_t* p, uint32_t need){
  asm volatile("{\n.reg .pred p;\n.reg .u32 c, v;\nmov.u32 c, 0;\nLW:\nand.b32 v, %0, %2;\nsetp.eq.u32 p, v, 0;\n@p bra.uni LD;\nld.relaxed.gpu.global.u32 v, [%1];\nsetp.eq.u32 p, v, 0;\n"
               "vote.sync.ballot.b32 %0, p, 0xffffffff;\nadd.u32 c, c, 1;\nsetp.lt.u32 p, c, 4000000;\n@p bra.uni LW;\nLD:\n}\n":"+r"(missing):"l"(p),"r"(need):"memory"); }
__device__ __forceinline__ uint32_t tagw(float x, uint32_t t){ return (__float_as_uint(x) & ~3u) | t; }
__device__ __forceinline__ float untag(uint32_t w){ return __uint_as_float(w & ~3u); }

template<int TA, int TB, uint32_t HA, uint32_t HB> __device__ __forceinline__ void wgmma_ss_n128(float (&d)[64], uint32_t da, uint32_t db, int scale_d){
  asm volatile("{\n.reg .pred p;\n.reg .b64 a, b;\nsetp.ne.b32 p, %70, 0;\nmov.b64 a, {%64, %68};\nmov.b64 b, {%65, %69};\n"
  "wgmma.mma_async.sync.aligned.m64n128k16.f32.bf16.bf16 {%0, %1, %2, %3, %4, %5, %6, %7, %8, %9, %10, %11, %12, %13, %14, %15, %16, %17, %18, %19, %20, %21, %22, %23, %24, %25, %26, %27, %28, %29, %30, %31, %32, %33, %34, %35, %36, %37, %38, %39, %40, %41, %42, %43, %44, %45, %46, %47, %48, %49, %50, %51, %52, %53, %54, %55, %56, %57, %58, %59, %60, %61, %62, %63}, a, b, p, 1, 1, %66, %67;\n}\n"
  : "+f"(d[0]), "+f"(d[1]), "+f"(d[2]), "+f"(d[3]), "+f"(d[4]), "+f"(d[5]), "+f"(d[6]), "+f"(d[7]), "+f"(d[8]), "+f"(d[9]), "+f"(d[10]), "+f"(d[11]), "+f"(d[12]), "+f"(d[13]), "+f"(d[14]), "+f"(d[15]), "+f"(d[16]), "+f"(d[17]), "+f"(d[18]), "+f"(d[19]), "+f"(d[20]), "+f"(d[21]), "+f"(d[22]), "+f"(d[23]), "+f"(d[24]), "+f"(d[25]), "+f"(d[26]), "+f"(d[27]), "+f"(d[28]), "+f"(d[29]), "+f"(d[30]), "+f"(d[31]), "+f"(d[32]), "+f"(d[33]), "+f"(d[34]), "+f"(d[35]), "+f"(d[36]), "+f"(d[37]), "+f"(d[38]), "+f"(d[39]), "+f"(d[40]), "+f"(d[41]), "+f"(d[42]), "+f"(d[43]), "+f"(d[44]), "+f"(d[45]), "+f"(d[46]), "+f"(d[47]), "+f"(d[48]), "+f"(d[49]), "+f"(d[50]), "+f"(d[51]), "+f"(d[52]), "+f"(d[53]), "+f"(d[54]), "+f"(d[55]), "+f"(d[56]), "+f"(d[57]), "+f"(d[58]), "+f"(d[59]), "+f"(d[60]), "+f"(d[61]), "+f"(d[62]), "+f"(d[63])
  : "r"(da), "r"(db), "n"(TA), "n"(TB), "n"(HA), "n"(HB), "r"(scale_d));
}
template<int TA, int TB, uint32_t HA, uint32_t HB> __device__ __forceinline__ void wgmma_sa_n128(float (&d)[64], uint32_t da, uint32_t db){
  asm volatile("{\n.reg .pred p;\n.reg .b64 a, b;\nsetp.ne.b32 p, 1, 0;\nmov.b64 a, {%64, %68};\nmov.b64 b, {%65, %69};\n"
  "wgmma.mma_async.sync.aligned.m64n128k16.f32.bf16.bf16 {%0, %1, %2, %3, %4, %5, %6, %7, %8, %9, %10, %11, %12, %13, %14, %15, %16, %17, %18, %19, %20, %21, %22, %23, %24, %25, %26, %27, %28, %29, %30, %31, %32, %33, %34, %35, %36, %37, %38, %39, %40, %41, %42, %43, %44, %45, %46, %47, %48, %49, %50, %51, %52, %53, %54, %55, %56, %57, %58, %59, %60, %61, %62, %63}, a, b, p, 1, 1, %66, %67;\n}\n"
  : "+f"(d[0]), "+f"(d[1]), "+f"(d[2]), "+f"(d[3]), "+f"(d[4]), "+f"(d[5]), "+f"(d[6]), "+f"(d[7]), "+f"(d[8]), "+f"(d[9]), "+f"(d[10]), "+f"(d[11]), "+f"(d[12]), "+f"(d[13]), "+f"(d[14]), "+f"(d[15]), "+f"(d[16]), "+f"(d[17]), "+f"(d[18]), "+f"(d[19]), "+f"(d[20]), "+f"(d[21]), "+f"(d[22]), "+f"(d[23]), "+f"(d[24]), "+f"(d[25]), "+f"(d[26]), "+f"(d[27]), "+f"(d[28]), "+f"(d[29]), "+f"(d[30]), "+f"(d[31]), "+f"(d[32]), "+f"(d[33]), "+f"(d[34]), "+f"(d[35]), "+f"(d[36]), "+f"(d[37]), "+f"(d[38]), "+f"(d[39]), "+f"(d[40]), "+f"(d[41]), "+f"(d[42]), "+f"(d[43]), "+f"(d[44]), "+f"(d[45]), "+f"(d[46]), "+f"(d[47]), "+f"(d[48]), "+f"(d[49]), "+f"(d[50]), "+f"(d[51]), "+f"(d[52]), "+f"(d[53]), "+f"(d[54]), "+f"(d[55]), "+f"(d[56]), "+f"(d[57]), "+f"(d[58]), "+f"(d[59]), "+f"(d[60]), "+f"(d[61]), "+f"(d[62]), "+f"(d[63])
  : "r"(da), "r"(db), "n"(TA), "n"(TB), "n"(HA), "n"(HB));
}
template<int TA, int TB, uint32_t HA, uint32_t HB> __device__ __forceinline__ void wgmma_sa_n40(float (&d)[20], uint32_t da, uint32_t db){
  asm volatile("{\n.reg .pred p;\n.reg .b64 a, b;\nsetp.ne.b32 p, 1, 0;\nmov.b64 a, {%20, %24};\nmov.b64 b, {%21, %25};\n"
  "wgmma.mma_async.sync.aligned.m64n40k16.f32.bf16.bf16 {%0, %1, %2, %3, %4, %5, %6, %7, %8, %9, %10, %11, %12, %13, %14, %15, %16, %17, %18, %19}, a, b, p, 1, 1, %22, %23;\n}\n"
  : "+f"(d[0]), "+f"(d[1]), "+f"(d[2]), "+f"(d[3]), "+f"(d[4]), "+f"(d[5]), "+f"(d[6]), "+f"(d[7]), "+f"(d[8]), "+f"(d[9]), "+f"(d[10]), "+f"(d[11]), "+f"(d[12]), "+f"(d[13]), "+f"(d[14]), "+f"(d[15]), "+f"(d[16]), "+f"(d[17]), "+f"(d[18]), "+f"(d[19])
  : "r"(da), "r"(db), "n"(TA), "n"(TB), "n"(HA), "n"(HB));
}
template<int TA, int TB, uint32_t HA, uint32_t HB> __device__ __forceinline__ void wgmma_sz_n40(float (&d)[20], uint32_t da, uint32_t db){
  asm volatile("{\n.reg .pred p;\n.reg .b64 a, b;\nsetp.ne.b32 p, 0, 0;\nmov.b64 a, {%20, %24};\nmov.b64 b, {%21, %25};\n"
  "wgmma.mma_async.sync.aligned.m64n40k16.f32.bf16.bf16 {%0, %1, %2, %3, %4, %5, %6, %7, %8, %9, %10, %11, %12, %13, %14, %15, %16, %17, %18, %19}, a, b, p, 1, 1, %22, %23;\n}\n"
  : "=f"(d[0]), "=f"(d[1]), "=f"(d[2]), "=f"(d[3]), "=f"(d[4]), "=f"(d[5]), "=f"(d[6]), "=f"(d[7]), "=f"(d[8]), "=f"(d[9]), "=f"(d[10]), "=f"(d[11]), "=f"(d[12]), "=f"(d[13]), "=f"(d[14]), "=f"(d[15]), "=f"(d[16]), "=f"(d[17]), "=f"(d[18]), "=f"(d[19])
  : "r"(da), "r"(db), "n"(TA), "n"(TB), "n"(HA), "n"(HB));
}
template<int TA, int TB, uint32_t HA, uint32_t HB> __device__ __forceinline__ void wgmma_sa_n32(float (&d)[16], uint32_t da, uint32_t db){
  asm volatile("{\n.reg .pred p;\n.reg .b64 a, b;\nsetp.ne.b32 p, 1, 0;\nmov.b64 a, {%16, %20};\nmov.b64 b, {%17, %21};\n"
  "wgmma.mma_async.sync.aligned.m64n32k16.f32.bf16.bf16 {%0, %1, %2, %3, %4, %5, %6, %7, %8, %9, %10, %11, %12, %13, %14, %15}, a, b, p, 1, 1, %18, %19;\n}\n"
  : "+f"(d[0]), "+f"(d[1]), "+f"(d[2]), "+f"(d[3]), "+f"(d[4]), "+f"(d[5]), "+f"(d[6]), "+f"(d[7]), "+f"(d[8]), "+f"(d[9]), "+f"(d[10]), "+f"(d[11]), "+f"(d[12]), "+f"(d[13]), "+f"(d[14]), "+f"(d[15])
  : "r"(da), "r"(db), "n"(TA), "n"(TB), "n"(HA), "n"(HB));
}
template<int TA, int TB, uint32_t HA, uint32_t HB> __device__ __forceinline__ void wgmma_ss_n32(float (&d)[16], uint32_t da, uint32_t db, int scale_d){
  asm volatile("{\n.reg .pred p;\n.reg .b64 a, b;\nsetp.ne.b32 p, %22, 0;\nmov.b64 a, {%16, %20};\nmov.b64 b, {%17, %21};\n"
  "wgmma.mma_async.sync.aligned.m64n32k16.f32.bf16.bf16 {%0, %1, %2, %3, %4, %5, %6, %7, %8, %9, %10, %11, %12, %13, %14, %15}, a, b, p, 1, 1, %18, %19;\n}\n"
  : "+f"(d[0]), "+f"(d[1]), "+f"(d[2]), "+f"(d[3]), "+f"(d[4]), "+f"(d[5]), "+f"(d[6]), "+f"(d[7]), "+f"(d[8]), "+f"(d[9]), "+f"(d[10]), "+f"(d[11]), "+f"(d[12]), "+f"(d[13]), "+f"(d[14]), "+f"(d[15])
  : "r"(da), "r"(db), "n"(TA), "n"(TB), "n"(HA), "n"(HB), "r"(scale_d));
}
template<int TB, uint32_t HB> __device__ __forceinline__ void wgmma_ra_n32(float (&d)[16], uint32_t a0, uint32_t a1, uint32_t a2, uint32_t a3, uint32_t db){
  asm volatile("{\n.reg .pred p;\n.reg .b64 a, b;\nsetp.ne.b32 p, 1, 0;\nmov.b64 b, {%20, %22};\n"
  "wgmma.mma_async.sync.aligned.m64n32k16.f32.bf16.bf16 {%0, %1, %2, %3, %4, %5, %6, %7, %8, %9, %10, %11, %12, %13, %14, %15}, {%16,%17,%18,%19}, b, p, 1, 1, %21;\n}\n"
  : "+f"(d[0]), "+f"(d[1]), "+f"(d[2]), "+f"(d[3]), "+f"(d[4]), "+f"(d[5]), "+f"(d[6]), "+f"(d[7]), "+f"(d[8]), "+f"(d[9]), "+f"(d[10]), "+f"(d[11]), "+f"(d[12]), "+f"(d[13]), "+f"(d[14]), "+f"(d[15])
  : "r"(a0), "r"(a1), "r"(a2), "r"(a3), "r"(db), "n"(TB), "n"(HB));
}
template<int TB, uint32_t HB> __device__ __forceinline__ void wgmma_rs_n32(float (&d)[16], uint32_t a0, uint32_t a1, uint32_t a2, uint32_t a3, uint32_t db, int scale_d){
  asm volatile("{\n.reg .pred p;\n.reg .b64 a, b;\nsetp.ne.b32 p, %23, 0;\nmov.b64 b, {%20, %22};\n"
  "wgmma.mma_async.sync.aligned.m64n32k16.f32.bf16.bf16 {%0, %1, %2, %3, %4, %5, %6, %7, %8, %9, %10, %11, %12, %13, %14, %15}, {%16,%17,%18,%19}, b, p, 1, 1, %21;\n}\n"
  : "+f"(d[0]), "+f"(d[1]), "+f"(d[2]), "+f"(d[3]), "+f"(d[4]), "+f"(d[5]), "+f"(d[6]), "+f"(d[7]), "+f"(d[8]), "+f"(d[9]), "+f"(d[10]), "+f"(d[11]), "+f"(d[12]), "+f"(d[13]), "+f"(d[14]), "+f"(d[15])
  : "r"(a0), "r"(a1), "r"(a2), "r"(a3), "r"(db), "n"(TB), "n"(HB), "r"(scale_d));
}
template<int TB, uint32_t HB> __device__ __forceinline__ void wgmma_ra_n40(float (&d)[20], uint32_t a0, uint32_t a1, uint32_t a2, uint32_t a3, uint32_t db){
  asm volatile("{\n.reg .pred p;\n.reg .b64 a, b;\nsetp.ne.b32 p, 1, 0;\nmov.b64 b, {%24, %26};\n"
  "wgmma.mma_async.sync.aligned.m64n40k16.f32.bf16.bf16 {%0, %1, %2, %3, %4, %5, %6, %7, %8, %9, %10, %11, %12, %13, %14, %15, %16, %17, %18, %19}, {%20,%21,%22,%23}, b, p, 1, 1, %25;\n}\n"
  : "+f"(d[0]), "+f"(d[1]), "+f"(d[2]), "+f"(d[3]), "+f"(d[4]), "+f"(d[5]), "+f"(d[6]), "+f"(d[7]), "+f"(d[8]), "+f"(d[9]), "+f"(d[10]), "+f"(d[11]), "+f"(d[12]), "+f"(d[13]), "+f"(d[14]), "+f"(d[15]), "+f"(d[16]), "+f"(d[17]), "+f"(d[18]), "+f"(d[19])
  : "r"(a0), "r"(a1), "r"(a2), "r"(a3), "r"(db), "n"(TB), "n"(HB));
}
template<int TB, uint32_t HB> __device__ __forceinline__ void wgmma_rz_n40(float (&d)[20], uint32_t a0, uint32_t a1, uint32_t a2, uint32_t a3, uint32_t db){
  asm volatile("{\n.reg .pred p;\n.reg .b64 a, b;\nsetp.ne.b32 p, 0, 0;\nmov.b64 b, {%24, %26};\n"
  "wgmma.mma_async.sync.aligned.m64n40k16.f32.bf16.bf16 {%0, %1, %2, %3, %4, %5, %6, %7, %8, %9, %10, %11, %12, %13, %14, %15, %16, %17, %18, %19}, {%20,%21,%22,%23}, b, p, 1, 1, %25;\n}\n"
  : "=f"(d[0]), "=f"(d[1]), "=f"(d[2]), "=f"(d[3]), "=f"(d[4]), "=f"(d[5]), "=f"(d[6]), "=f"(d[7]), "=f"(d[8]), "=f"(d[9]), "=f"(d[10]), "=f"(d[11]), "=f"(d[12]), "=f"(d[13]), "=f"(d[14]), "=f"(d[15]), "=f"(d[16]), "=f"(d[17]), "=f"(d[18]), "=f"(d[19])
  : "r"(a0), "r"(a1), "r"(a2), "r"(a3), "r"(db), "n"(TB), "n"(HB));
}
template<int TB, uint32_t HB> __device__ __forceinline__ void wgmma_rz_n8(float (&d)[4], uint32_t a0, uint32_t a1, uint32_t a2, uint32_t a3, uint32_t db){
  asm volatile("{\n.reg .pred p;\n.reg .b64 a, b;\nsetp.ne.b32 p, 0, 0;\nmov.b64 b, {%8, %10};\n"
  "wgmma.mma_async.sync.aligned.m64n8k16.f32.bf16.bf16 {%0, %1, %2, %3}, {%4,%5,%6,%7}, b, p, 1, 1, %9;\n}\n"
  : "=f"(d[0]), "=f"(d[1]), "=f"(d[2]), "=f"(d[3])
  : "r"(a0), "r"(a1), "r"(a2), "r"(a3), "r"(db), "n"(TB), "n"(HB));
}

constexpr int SEQ = 2048, DM = 1024, FF = 3584;
constexpr float LOG2E = 1.4426950408889634f;
constexpr uint32_t POLL_LIMIT = 1u << 22;
constexpr int QW = 0;
constexpr int LAG = 2;
constexpr int ML = 2;
constexpr int REL = 6;
constexpr int SKM = 0x154;
constexpr int RS_N = 26;
constexpr int RS_D1 = 350;
constexpr int RS_D2 = 300;
constexpr int PF_T0 = 4200;
constexpr int PF_DT = 855;
constexpr int FF_N = 4;
constexpr int FF_DT = 650;
constexpr int FF_D2 = 350;
constexpr uint64_t FF_ORD = 0x76543210ba98ull;
constexpr int G2P = 4;
constexpr int XC = 0;
constexpr int OUT_D = 400;
constexpr int NFFN = 112;

constexpr uint32_t SB0 = 1024;
constexpr uint32_t KV_STAGE = 49152, R5 = 32768;
constexpr uint32_t OFF_X = 163840, OFF_S = 196608, OFF_WPHI = OFF_S + 20480, OFF_M = 229376, SMEM_BYTES = 232448;
constexpr uint32_t OFF_RS256 = 212992, OFF_ONES = OFF_RS256 + 1024, OFF_WPHIK1 = OFF_ONES + 1024, OFF_KVZ = OFF_S;
constexpr uint32_t OFF_WPHIK = OFF_S, OFF_BXK = OFF_S + 2048, OFF_AXK = OFF_S + 4096, OFF_G = OFF_S + 8192;
constexpr uint32_t OFF_AXQ = OFF_WPHI, OFF_BXQ = OFF_WPHI + 2048, OFF_WPHIQ = OFF_WPHI + 4096;
constexpr uint32_t B_FULLKV = OFF_M  , B_EMPTYKV = OFF_M + 32  ;
constexpr uint32_t B_EMPTY5 = OFF_M + 64  , B_UO = B_EMPTY5 + 48  , B_RC = B_UO + 32  ;
constexpr uint32_t B_OUT = B_RC + 16  , B_SD = B_OUT + 16, B_AUX = B_SD + 8, B_AUXQ = B_AUX + 8, B_RX = B_AUXQ + 8;
constexpr uint32_t B_FULL5 = B_RX + 8  , B_F = B_FULL5 + 40  , B_WD = B_F + 64  ;
constexpr uint32_t B_WC = B_WD + 32  , B_DR = B_WC + 32  , B_W = B_DR + 24, B_OS = B_W + 8, B_R = B_W + 16, B_KD = B_W + 24, B_T = B_W + 32, B_G = B_W + 40, B_END = B_W + 48;
constexpr int NB3 = ((B_END - OFF_M) / 8 + 1) / 3;
constexpr uint32_t B_S0 = OFF_M + 8 + 24 * NB3;
static_assert(B_S0 >= B_END && B_S0 < OFF_M + 576, "barriers");
__host__ __device__ constexpr uint32_t bar_count(int i) {
  const uint32_t b = OFF_M + 8 * i;
  return b < B_EMPTYKV ? 1 : b < B_EMPTY5 ? 12 : b < B_SD ? 4 : b < B_RX || b == B_W ? 2 : b == B_RX ? 8 : 1;
}
constexpr uint32_t B_GB = OFF_M + 2560  , B_GA = B_GB + 128  ;
constexpr uint32_t OFF_BEST = OFF_M + 576, OFF_SUMWR = OFF_M + 608, OFF_EP = OFF_M + 624, OFF_KEY = OFF_M + 628;
constexpr uint32_t OFF_RSQ = OFF_M + 640, OFF_SEL = OFF_M + 1648, OFF_T = OFF_M + 1792, OFF_WR = OFF_M + 2048;
constexpr uint32_t OFF_XSEL = 2 * R5, OFF_GU = OFF_XSEL + 4096, OFF_OUT = 3 * R5;
constexpr uint64_t FF_SLOT = 0xdcdc3210dcbaull;
constexpr int KVP = 6 * 128;
__device__ __forceinline__ uint32_t kv_count(uint32_t launch, uint32_t n) { return 0x42800000u + (((launch & 3) * 16 + n) << 17); }

enum { NB_G2E = 1, NB_XS = 2, NB_WG01 = 3, NB_ACT = 4, NB_Q0 = 5  , NB_ST = 14, NB_LAG = 8, NB_DN = 9, NB_ZERO = 10, NB_PUB = 11, NB_TOK = 10  , NB_L0 = 12  , NB_WG2 = 7, NB_QGO = 15 };

struct Scratch {
  bf16     o[SEQ * DM];
  float4   rstat[SEQ];
  uint32_t key[16 * 128];
  uint32_t cand[16 * 512];
  float4   yacc[4 * 3 * 128];
  float4   kvacc[32 * KVP];
  uint2    stats[SEQ];
  uint32_t cskv[2 * DM];
  uint32_t csq[4 * DM];
  uint32_t oset[128 * 16];
  uint32_t oflag[16 * 6 * 32 * 8];
  uint32_t epoch;
};
__device__ __align__(1024) Scratch g_scr;

struct Params {
  const bf16 *x, *wqkv, *wo_p, *wr;
  bf16* out_p;
  Scratch* g;
  uint32_t zero;
  CUtensorMap x128, x64, wkv, wq, wo[2], wd, wg, wu, phi, tg, tu, td, xs, ws, qs, out, o;
};

constexpr float EXP_LIM = 1.1529215e18f, ARG_LIM2 = 3600.f;
__device__ __forceinline__ void dual_exp2(const float (&p)[16], uint32_t (&ep)[8], uint32_t (&em)[8]) {
  #pragma unroll
  for (int k = 0; k < 8; k++) {
    const float a = ex2(p[2*k]), b = ex2(p[2*k+1]);
    const float r = rcp(a * b);
    ep[k] = pack_bf16(a, b); em[k] = pack_bf16(r * b, r * a);
  }
}
template<bool SUMS> __device__ __forceinline__ void dual_exp2_shifted(float (&p)[2][16], uint32_t (&ph)[4][8], float (&s)[2][4]) {
  #pragma unroll 1
  for (int r = 0; r < 4; r++) {
    float m[2] = {p[0][0], p[0][2]}, a[2] = {0.f, 0.f};
    #pragma unroll
    for (int i = 0; i < 16; i++) m[(i >> 1) & 1] = fmaxf(m[(i >> 1) & 1], p[0][i]);
    #pragma unroll
    for (int o = 1; o < 4; o <<= 1) { m[0] = fmaxf(m[0], __shfl_xor_sync(~0u, m[0], o)); m[1] = fmaxf(m[1], __shfl_xor_sync(~0u, m[1], o)); }
    #pragma unroll
    for (int k = 0; k < 8; k++) {
      const float e0 = ex2(p[0][2*k] - m[k & 1]), e1 = ex2(p[0][2*k+1] - m[k & 1]);
      ph[0][k] = ph[2][k]; ph[2][k] = ph[1][k]; ph[1][k] = ph[3][k]; ph[3][k] = pack_bf16(e0, e1);
      a[k & 1] += e0 + e1;
    }
    #pragma unroll
    for (int i = 0; i < 16; i++) { const float x = p[0][i]; p[0][i] = p[1][i]; p[1][i] = -x; }
    if (SUMS) {
      #pragma unroll
      for (int i = 0; i < 2; i++) {
        a[i] += __shfl_xor_sync(~0u, a[i], 1);
        s[0][2*i] = s[1][2*i]; s[1][2*i] = s[0][2*i+1]; s[0][2*i+1] = s[1][2*i+1]; s[1][2*i+1] = a[i] + __shfl_xor_sync(~0u, a[i], 2);
      }
    }
  }
}
__device__ __forceinline__ uint32_t add_bf16x2(uint32_t a, uint32_t b) { uint32_t r; asm("add.rn.bf16x2 %0, %1, %2;" : "=r"(r) : "r"(a), "r"(b)); return r; }
__device__ __forceinline__ void row_sums(float (&s)[2][4], const uint32_t (&ph)[4][8], uint32_t sel) {
  uint32_t u[8];
  #pragma unroll
  for (int i = 0; i < 8; i++) { const uint32_t* f = &ph[i >> 1][i & 1]; u[i] = add_bf16x2(add_bf16x2(f[0], f[2]), add_bf16x2(f[4], f[6])); }
  wg_fence();
  wgmma_rz_n8<0, H0>(s[0], u[0], u[1], u[2], u[3], sel);
  wgmma_rz_n8<0, H0>(s[1], u[4], u[5], u[6], u[7], sel);
  wg_commit();
}
__device__ __forceinline__ uint32_t mul_bf16x2(uint32_t a, uint32_t b) { uint32_t r; asm("mul.rn.bf16x2 %0, %1, %2;" : "=r"(r) : "r"(a), "r"(b)); return r; }
__device__ __forceinline__ void normalize(uint32_t (&ph)[4][8], const float (&s)[2][4]) {
  #pragma unroll
  for (int i = 0; i < 4; i++) {
    const float i0 = rcp(s[i >> 1][i & 1]), i1 = rcp(s[i >> 1][2 + (i & 1)]);
    const uint32_t n0 = pack_bf16(i0, i0), n1 = pack_bf16(i1, i1);
    #pragma unroll
    for (int k = 0; k < 4; k++) { ph[i][2*k] = mul_bf16x2(ph[i][2*k], n0); ph[i][2*k+1] = mul_bf16x2(ph[i][2*k+1], n1); }
  }
}
__device__ __forceinline__ void split_bf16(float a, float b, uint32_t& hi, uint32_t& lo) { hi = pack_bf16(a, b); lo = pack_bf16(a - bf_lo(hi), b - bf_hi(hi)); }
__device__ __forceinline__ void put_colsums(uint32_t base, int lane, float a, float b, float c, float d) {
  uint32_t h0, l0, h1, l1;
  split_bf16(a, b, h0, l0); split_bf16(c, d, h1, l1);
  const uint32_t ad = base + (lane >> 1) * 128 + (lane & 1) * 8;
  sts64(ad, h0, h1); sts64(ad + 16, l0, l1); sts64(ad + 32, h0, h1); sts64(ad + 48, l0, l1);
  sts128(base + (lane >> 1) * 128 + 64 + (lane & 1) * 32, 0, 0, 0, 0); sts128(base + (lane >> 1) * 128 + 80 + (lane & 1) * 32, 0, 0, 0, 0);
}
__device__ __forceinline__ float reduce8(const float (&v)[8], int lane) {
  const bool b4 = lane & 16, b3 = lane & 8, b2 = lane & 4;
  float a[4], b[2];
  #pragma unroll
  for (int i = 0; i < 4; i++) a[i] = (b4 ? v[4 + i] : v[i]) + __shfl_xor_sync(~0u, b4 ? v[i] : v[4 + i], 16);
  #pragma unroll
  for (int i = 0; i < 2; i++) b[i] = (b3 ? a[2 + i] : a[i]) + __shfl_xor_sync(~0u, b3 ? a[i] : a[2 + i], 8);
  return (b2 ? b[1] : b[0]) + __shfl_xor_sync(~0u, b2 ? b[0] : b[1], 4);
}
__device__ __forceinline__ bool tag_bad(uint4 v, uint32_t tg) { return (((v.x ^ tg) | (v.y ^ tg) | (v.z ^ tg) | (v.w ^ tg)) & 3) != 0; }


__global__ void __launch_bounds__(512, 1) __cluster_dims__(2, 1, 1) fused_kernel(const __grid_constant__ Params P) {
  extern __shared__ __align__(1024) uint8_t smem_raw[];
  const uint32_t sb = smem_u32(smem_raw);
  const int tid = threadIdx.x, lane = tid & 31;
  {
    const int n = 16 * blockIdx.x + (lane & 15);
    const bf16* p = (lane < 16 ? P.x : P.wqkv) + (lane < 16 ? n * DM : (n >> 5) * (3 * DM) + DM + 64 * (n & 31));
    asm volatile("{\n.reg .pred p;\nsetp.lt.u32 p, %1, 32;\n@p prefetch.global.L2 [%0];\n}\n" :: "l"(p), "r"(tid));
  }
  const int cp = blockIdx.x >> 1, rank = blockIdx.x & 1;
  const int cr = cp < 4 ? 32 + 8 * cp : cp - 4 + max((cp * 37 - 1076) >> 8, 0);
  const int c = (cr & 62) + 64 * (cr & 1) + rank;
  const int m256 = c >> 4, nkv = c & 15, m128 = c >> 3, j = c & 7;
  if ((tid >> 7) == 2 && elect_one()) {
    if (tid >= 288) {
      const int w = (tid >> 5) - 9;
      #pragma unroll
      for (int i = 0; i < NB3; i++) mbar_init(sb + B_FULLKV + 8 + 8 * NB3 * w + 8 * i, w == 0 ? bar_count(1 + i) : w == 1 ? bar_count(1 + NB3 + i) : bar_count(1 + 2 * NB3 + i));
    } else {
      prefetch_map(&P.wkv); prefetch_map(&P.x128);
      mbar_init(sb + B_S0, 1); mbar_init(sb + B_FULLKV, 1);
      mbar_expect_tx(sb + B_S0, 32768);
      tma_4d(sb + 32768, &P.wkv, 0, 0, nkv, 1, sb + B_S0);
      tma_2d(sb, &P.x128, 0, 256 * m256, sb + B_S0);
      mbar_expect_tx(sb + B_FULLKV, 16384);
      tma_2d(sb + 16384, &P.x128, 0, 256 * m256 + 128, sb + B_FULLKV);
    }
    asm volatile("fence.mbarrier_init.release.cluster;" ::: "memory");
  }
  const int warp = __shfl_sync(~0u, tid >> 5, 0), wg = warp >> 2, wp = warp & 3;
  const int f = 16 * ((cr + 7) & 7) + 2 * (cr >> 3) + rank;
  const int ha = 4 * (nkv >> 1) + (nkv & 1);
  Scratch* const G = P.g;
  if ((sb & 0x3ffff) != SB0) asm volatile("trap;");
  __syncthreads();
  cluster_arrive();
  if (warp == 8 && elect_one()) {
    mbar_expect_tx(sb + B_FULLKV + 8, KV_STAGE);
    tma_4d(sb + KV_STAGE + 32768, &P.wkv, 0, 64, nkv, 1, sb + B_FULLKV + 8);
    tma_2d(sb + KV_STAGE, &P.x128, 64, 256 * m256, sb + B_FULLKV + 8);
    tma_2d(sb + KV_STAGE + 16384, &P.x128, 64, 256 * m256 + 128, sb + B_FULLKV + 8);
  }
  if (wg == 3) {
    asm volatile("setmaxnreg.dec.sync.aligned.u32 32;");
    cluster_wait();
    const bool el = elect_one();
    const uint64_t ef = policy_evict_first(), en = policy_evict_normal();
    auto fetch_o = [&](const int t0, const int sh) {
      uint32_t missing = ~0u;
      const uint32_t* hint = &G->oflag[((m128 * 6 + ((t0 + 1) & 6) + rank) * 32 + ((4 * (j & 6) + lane) & 31)) * 8];
      #pragma unroll 1
      for (int i = 2 - 2 * sh; i < 8; i += 1 + sh) {
        const int blk = sh ? 6 + 2 * t0 + (i >> 1) : i, wrap = sh ? 1 + (blk >= 11) : blk >= 5, s = blk + 1 - 6 * wrap;
        flags_wait(missing, hint, (15u + 240u * sh) << (4 * i));
        if (sh || blk > 5) mbar_wait(sb + B_EMPTY5 + 8 * s, wrap & 1);
        if (el) {
          tma_2d_mc_h(sb + s * R5 + rank * 8192, &P.o, 0, (m128 * 16 + t0 + 2 * (((j & 6) + i) & 7)) * 32 + 16 * rank, sb + B_GA + 16 * blk + 8 * rank, ef);
        }
      }
    };
    if (wp == 0) {
      {
        wait_until((uint32_t)clock() + 300);
        #pragma unroll 1
        for (int kb = 2; kb < 16; kb++) {
          const uint32_t st = sb + (kb & 3) * KV_STAGE, fb = sb + B_FULLKV + 8 * (kb & 3);
          mbar_wait(fb + (B_EMPTYKV - B_FULLKV), ~(kb >> 2) & 1);
          if (el) {
            mbar_expect_tx(fb, KV_STAGE);
            tma_2d_mc(st + rank * 16384, &P.x128, 64 * kb, 256 * m256 + 128 * rank, fb);
            tma_4d_h(st + 32768, &P.wkv, 0, 64 * kb, nkv, 1, fb, ef);
          }
        }
        uint64_t ord = 0xf3120edcba987654ull;
        uint32_t so = 0, par = 1;
        #pragma unroll 1
        for (int i = 0; i < 16; i++) {
          const uint32_t st = sb + so * 4096, fb = sb + B_FULL5 + so;
          const int k0 = (64 * (uint32_t)ord + 128 * (j & 6)) & 960;
          mbar_wait(i < 5 ? sb + B_EMPTYKV + so - (i > 1 ? 8 : 0) : fb + (B_EMPTY5 - B_FULL5), par);
          if (el) {
            mbar_expect_tx(fb, R5);
            tma_2d_mc_h(st + rank * 8192, &P.x64, k0, 128 * m128 + 64 * rank, fb, i >= 11 ? ef : en);
            tma_3d_h(st + 16384, &P.wq, 0, k0, 2 * j, fb, ef);
          }
          ord >>= 4; so += 8;
          if (so == 40) { so = 0; par ^= 1; }
        }
        mbar_wait(sb + B_FULL5 + 8 + 8 * rank, 0);
        if (el) mbar_arrive(sb + B_R);
        #pragma unroll 1
        for (int i = 0; i < 19; i++) {
          const int row = i < 8 ? 128 * (((j & 6) + i) & 7) : 256 * (((j >> 1) + i) & 3) + 32 + 16 * (i & 4);
          mbar_wait(sb + B_EMPTY5 + so, par);
          if (el) {
            if (i < 16) {
              tma_5d_h(sb + so * 4096 + 16384, &P.wo[i >> 3], 128 * j, row, sb + B_GB + 8 * i, ef);
              tma_5d_h(sb + so * 4096 + 24576, &P.wo[i >> 3], 128 * j + 64, row, sb + B_GB + 8 * i, ef);
            } else mbar_arrive(sb + B_DR + 8 * (i - 16));
          }
          so += 8;
          if (so == 48) { so = 0; par ^= 1; }
        }
      }
    } else if (wp == 3) {
      const uint32_t t_start = (uint32_t)clock();
      mbar_wait(sb + B_S0, 0);
      if (el) {
        mbar_expect_tx(sb + B_W, 12288);
        #pragma unroll 1
        for (int i = 0; i < 6; i++) tma_2d(sb + (i == 0 ? OFF_WPHIK : i == 1 ? OFF_WPHIK1 : OFF_WPHIQ + 2048 * (i - 2)), &P.phi, 0, 32 * (i < 2 ? 2 * nkv + i : 4 * j + 2 * (i & 1) + ((i - 2) >> 1)), sb + B_W);
        prefetch_map(&P.x64); prefetch_map(&P.wq); prefetch_map(&P.wo[0]); prefetch_map(&P.wo[1]);
        prefetch_map(&P.o); prefetch_map(&P.wd); prefetch_map(&P.out); prefetch_map(&P.wg); prefetch_map(&P.wu);
      }
      if (lane < 16) st128_rlx(&G->cand[m128 * 512 + 64 * j + 4 * lane], ~0u, ~0u, ~0u, ~0u);
      if (lane < 16) st128_rlx(&G->rstat[16 * c + lane], 0, 0, 0, 0);
      if (lane < 12) st128_rlx(&G->yacc[12 * c + lane], 0, 0, 0, 0);
      const uint32_t nt = ld32_rlx(&G->epoch);
      if (lane < 8) { st128_rlx(&G->stats[16 * c + 2 * lane], nt, nt, nt, nt); st128_rlx(&G->csq[32 * c + 4 * lane], nt, nt, nt, nt); }
      if (lane < 4) { st128_rlx(&G->cskv[128 * nkv + 16 * m256 + 4 * lane], nt, nt, nt, nt); st128_rlx(&G->oset[16 * c + 4 * lane], nt, nt, nt, nt); }
      if (lane < 4) st128_rlx(&G->key[(2 * j + (lane >> 1)) * 128 + m128 * 8 + 4 * (lane & 1)], 0, 0, 0, 0);
      if (c < 32) {
        #pragma unroll 1
        for (int i = lane; i < KVP; i += 32) st128_rlx(&G->kvacc[(ha + 2 * m256) * KVP + i], 0, 0, 0, kv_count(nt + 1, 0));
      }
      fence_gpu();
      bar_arrive(NB_ZERO, 160);
      if (el) {
        #pragma unroll 1
        for (int i = 0; i < 30; i++) {
          wait_until(t_start + PF_T0 + PF_DT * i + 7 * f);
          if (i < 4) { bulk_prefetch(P.wqkv + (size_t)(256 * i + c) * (3 * DM), 2048); bulk_prefetch(P.wqkv + (size_t)(256 * i + 128 + c) * (3 * DM), 2048); }
          else if (i < 6) bulk_prefetch(P.wo_p + (size_t)c * 8192 + (i - 4) * 4096, 8192);
          else if (f < NFFN) {
            if (i < 22) {
              #pragma unroll 1
              for (int e = 0; e < 4; e++) tma_2d(sb + OFF_T, rank ? &P.tu : &P.tg, 32 * (f & ~1), 64 * (i - 6) + 16 * e, sb + B_T);
            } else { tma_2d(sb + OFF_T, &P.td, 0, 256 * f + 32 * (i - 22), sb + B_T); tma_2d(sb + OFF_T, &P.td, 0, 256 * f + 32 * (i - 22) + 16, sb + B_T); }
          }
        }
      }
      __syncwarp();
      mbar_wait2(sb + B_OS, 0, sb + B_RX, 0);
      mbar_wait2(sb + B_EMPTY5 + 24, 0, sb + B_EMPTY5 + 32, 0);
      mbar_wait2(sb + B_EMPTY5 + 40, 0, sb + B_EMPTY5, 1);
      fetch_o(0, 0);
    } else {
      const int half = wp - 1;
      const uint32_t ep1 = ld32_rlx(&G->epoch) + 1, tg = ep1 & 3;
      {
        uint32_t it = 0;
        sts128(sb + OFF_ONES + half * 512 + lane * 16, 0x3f803f80u, 0x3f803f80u, 0x3f803f80u, 0x3f803f80u);
        if (lane < 9) { const uint32_t v = (lane & 1) ? 0 : 0x3f803f80u; sts128(sb + OFF_SEL + lane * 16, v, v, v, v); }
        auto reset_o = [&](int i0, int i1, uint32_t dt) {
          uint32_t t0 = (uint32_t)clock();
          #pragma unroll 1
          for (int i = i0; i < i1; i++) {
            st128_rlx(G->o + (m128 * 16 + 2 * j + half) * 8192 + 256 * i + 8 * lane, ~0u, ~0u, ~0u, ~0u);
            wait_until(t0 += dt);
          }
        };
        if (el) {
          #pragma unroll 1
          for (int i = 24 * half; i < 24 * half + 24; i++) { mbar_init(sb + B_GB + 8 * i, 1); mbar_expect_tx(sb + B_GB + 8 * i, i < 16 ? 16384 : 8192); }
          asm volatile("fence.mbarrier_init.release.cluster;" ::: "memory");
        }
        mbar_wait(sb + B_S0, 0);
        reset_o(0, RS_N, RS_D1);
        bar_sync(NB_PUB, 192);
        const uint4* src = reinterpret_cast<const uint4*>(&G->stats[256 * m256 + 128 * half]) + lane;
        const uint4* srk = reinterpret_cast<const uint4*>(&G->cskv[128 * nkv]) + lane;
        uint4 v0, v1, vk;
        it = 0;
        do { v0 = ld128_rlx(src); v1 = ld128_rlx(src + 32); vk = ld128_rlx(srk); }
        while ((tag_bad(v0, tg) || tag_bad(v1, tg) || tag_bad(vk, tg)) && ++it < POLL_LIMIT);
        fence_acquire_gpu();
        if (half) put_colsums(sb + OFF_BXK, lane, untag(vk.x), untag(vk.y), untag(vk.z), untag(vk.w));
        #pragma unroll 1
        for (int i = 0; i < 2; i++) {
          const uint4 v = i ? v1 : v0;
          uint32_t hi, lo;
          split_bf16(-0.5f * untag(v.x), -0.5f * untag(v.z), hi, lo);
          const uint32_t h0 = __byte_perm(hi, hi, 0x1010), h1 = __byte_perm(hi, hi, 0x3232), l0 = __byte_perm(lo, lo, 0x1010), l1 = __byte_perm(lo, lo, 0x3232);
          const uint32_t a = sb + OFF_AXK + half * 2048 + i * 1024 + lane * 32;
          sts128(a, h0, l0, 0, 0); sts128(a + 16, h1, l1, 0, 0);
          sts64(sb + OFF_RS256 + half * 512 + i * 256 + lane * 8, v.y & ~3u, v.w & ~3u);
          if (half == (m128 & 1)) {
            const uint32_t aq = sb + OFF_AXQ + i * 1024 + lane * 32;
            sts128(aq, h0, l0, 0, 0); sts128(aq + 16, h1, l1, 0, 0);
            sts64(sb + OFF_RSQ + i * 256 + lane * 8, v.y & ~3u, v.w & ~3u);
          }
        }
        fence_async_smem();
        __syncwarp();
        if (el) { sts32(sb + OFF_EP, ep1); mbar_arrive(sb + B_AUX); }
        reset_o(RS_N, 32, RS_D2);
        if (lane < 24) st128_rlx(&G->oflag[((m128 * 6 + 3 * half + (lane >> 3)) * 32 + 4 * j) * 8 + 4 * (lane & 7)], 0, 0, 0, 0);
        fence_gpu();
        __syncwarp();
        if (el) { st32_rlx(&G->oset[16 * c + 8 * half], ep1); if (half) mbar_arrive(sb + B_AUXQ); }
        if (!half) {
          const uint4* src = reinterpret_cast<const uint4*>(&G->csq[128 * j]) + lane;
          uint4 v0, v1, v2, v3;
          do { v0 = ld128_rlx(src); v1 = ld128_rlx(src + DM / 4); v2 = ld128_rlx(src + DM / 2); v3 = ld128_rlx(src + 3 * DM / 4); }
          while ((tag_bad(v0, tg) || tag_bad(v1, tg) || tag_bad(v2, tg) || tag_bad(v3, tg)) && ++it < POLL_LIMIT);
          put_colsums(sb + OFF_BXQ, lane, (untag(v0.x) + untag(v1.x)) + (untag(v2.x) + untag(v3.x)), (untag(v0.y) + untag(v1.y)) + (untag(v2.y) + untag(v3.y)),
                      (untag(v0.z) + untag(v1.z)) + (untag(v2.z) + untag(v3.z)), (untag(v0.w) + untag(v1.w)) + (untag(v2.w) + untag(v3.w)));
          fence_async_smem();
          __syncwarp();
          if (el) mbar_arrive(sb + B_AUXQ);
        }
      }
      if (half == 0) {
        for (uint32_t it = 0; __any_sync(~0u, ld32_rlx(&G->oset[m128 * 128 + 8 * (lane & 15)]) != ep1) && it < POLL_LIMIT; it++) {}
        fence_acquire_gpu();
        if (el) mbar_arrive(sb + B_OS);
      }
      if (!half) {
        #pragma unroll 1
        for (int hh = 0; hh < 2; hh++) {
          const uint32_t src = sb + (1 + rank) * R5 + hh * 8192, fa = sb + B_GA + 16 * rank + 8 * hh;
          mbar_wait2(sb + B_UO + 8 * hh, 0, sb + B_GB + 8 * rank, 0);
          if (el) bulk_s2peer(mapa(src, rank ^ 1), src, 8192, mapa(fa, rank ^ 1));
        }
      }
      else if (f < NFFN) {
        mbar_wait(sb + B_UO + 24, 0);
        mbar_wait2(sb + B_UO, 0, sb + B_UO + 8, 0);
        uint32_t t0 = (uint32_t)clock();
        #pragma unroll 1
        for (int i = 0; i < 12; i++) {
          const int e = (FF_ORD >> (4 * i)) & 15;
          const uint32_t dst = sb + 16384 * ((FF_SLOT >> (4 * e)) & 15), fb = sb + B_F + 8 * e;
          if (i >= 2) mbar_wait(sb + B_WC + 8 * ((0x100066553244ull >> (4 * e)) & 15), 0);
          wait_until(t0);
          t0 = (uint32_t)clock() + (i < FF_N ? FF_DT : FF_D2);
          if (el) {
            mbar_expect_tx(fb, 16384);
            if (e >= 8) tma_3d_h(dst, &P.wd, 0, 32 * f, 4 * e - 32, fb, ef);
            else { tma_2d_h(dst, &P.wg, 32 * f, 128 * e, fb, ef); tma_2d_h(dst + 8192, &P.wu, 32 * f, 128 * e, fb, ef); }
          }
        }
      }
      __syncwarp();
    }
    if (wp & 1) {
      __syncwarp();
      fetch_o(wp, 1);
      mbar_wait(sb + B_OUT + 8 * (wp >> 1), 0);
      uint32_t t0 = (uint32_t)clock();
      #pragma unroll 1
      for (int i = 0; i < 8; i++) {
        wait_until(t0);
        if (el) tma_store_2d(&P.out, 128 * j + 64 * (i & 1), 128 * m128 + 32 * (wp & 2) + 8 * (i & 6), sb + OFF_OUT + (i & 1) * 16384 + (wp & 2) * 4096 + (i & 6) * 1024, ef);
        t0 += OUT_D;
      }
      if (el) { bulk_commit(); bulk_wait_all(); fence_async_global(); mbar_arrive(sb + B_SD); }
    }
    __syncwarp();
    cluster_arrive(); cluster_wait();
    return;
  }

  asm volatile("setmaxnreg.inc.sync.aligned.u32 160;");
  cluster_wait();
  const int t = tid & 127, g = lane >> 2;
  const uint32_t sa = (16 * wp + (lane & 15)) * 128 + (((lane >> 4) ^ (lane & 7)) << 4);

  if (wg == 2) {
    float s[2] = {0.f, 0.f}, s2[2] = {0.f, 0.f}, ck[8] = {0.f, 0.f, 0.f, 0.f, 0.f, 0.f, 0.f, 0.f}, cs[8] = {0.f, 0.f, 0.f, 0.f, 0.f, 0.f, 0.f, 0.f};
    const uint32_t ebr = mapa(sb + B_EMPTYKV, lane & 1), tg = (ld32_rlx(&G->epoch) + 1) & 3;
    auto addx = [&](const uint4 v) {
      const uint32_t w[4] = {v.x, v.y, v.z, v.w};
      #pragma unroll
      for (int e = 0; e < 4; e++) { const float a = bf_lo(w[e]), d = bf_hi(w[e]); s[0] += a; s[1] += d; s2[0] = fmaf(a, a, s2[0]); s2[1] = fmaf(d, d, s2[1]); }
    };
    auto addc = [&](const uint4 v, float (&o)[8]) {
      o[0] += bf_lo(v.x); o[1] += bf_hi(v.x); o[2] += bf_lo(v.y); o[3] += bf_hi(v.y); o[4] += bf_lo(v.z); o[5] += bf_hi(v.z); o[6] += bf_lo(v.w); o[7] += bf_hi(v.w);
    };
    {
      const uint32_t ra = (16 * nkv + (t >> 3)) * 128 + (t & 7) * 16;
      const uint32_t ca = 32768 + (m256 >> 2) * 8192 + (t >> 1) * 128 + (((2 * (m256 & 3) + (t & 1)) ^ ((t >> 1) & 7)) << 4);
      int rd = 0;
      mbar_wait(sb + B_S0, 0);
      #pragma unroll 1
      for (int kb = 0; kb < 10; kb++) {
        const uint32_t st = sb + (kb & 3) * KV_STAGE;
        mbar_wait(sb + B_FULLKV + 8 * (kb & 3), (kb >> 2) & 1);
        const uint4 x0 = lds128(st + ra), w0 = lds128(st + ca);
        addx(x0); addc(w0, ck);
        __syncwarp();
        if (lane < 2) mbar_arrive_remote(ebr + 8 * (kb & 3), 1);
        if ((SKM >> kb) & 1) {
          if (rd) {
            mbar_wait(sb + B_G, (rd - 1) & 1);
            #pragma unroll 1
            for (int i = 0; i < 2; i++) { addx(lds128(sb + OFF_G + (t >> 3) * 256 + (t & 7) * 16 + 128 * i)); addc(lds128(sb + OFF_G + 4096 + t * 16 + 2048 * i), ck); }
            bar_sync(NB_WG2, 128);
          }
          if (wp == 0 && elect_one()) {
            mbar_expect_tx(sb + B_G, 8192);
            if (rd < 3) {
              tma_2d(sb + OFF_G, &P.xs, 640 + 128 * rd, 256 * m256 + 16 * nkv, sb + B_G);
              tma_2d(sb + OFF_G + 4096, &P.ws, (1 + (m256 >> 2)) * DM + 64 * nkv + 16 * (m256 & 3), 640 + 128 * rd, sb + B_G);
            } else tma_2d(sb + OFF_G, &P.qs, 32 * (c & 31), 256 * (c >> 5), sb + B_G);
          }
          rd++;
        }
      }
    }
    const uint32_t scr = sb + OFF_WR;
    float sx = s[0] + s[1], sq = s2[0] + s2[1];
    #pragma unroll
    for (int o = 1; o < 8; o <<= 1) { sx += __shfl_xor_sync(~0u, sx, o); sq += __shfl_xor_sync(~0u, sq, o); }
    float v = reduce8(ck, lane);
    v += __shfl_xor_sync(~0u, v, 2);
    if (!(lane & 2)) stsf(scr + (wp * 16 + 8 * (lane & 1) + (lane >> 2)) * 4, v);

    bar_sync(NB_ZERO, 160);
    if ((lane & 7) == 0) {
      const float mean = sx * (1.f / DM);
      st64_rlx(&G->stats[256 * m256 + 16 * nkv + (t >> 3)], tagw(mean, tg), tagw(rsqrtf(fmaxf(sq * (1.f / DM) - mean * mean, 0.f) + 1e-5f), tg));
    }
    if (wp == 1 && lane < 16) {
      const uint32_t a = scr + lane * 4;
      st32_rlx(&G->cskv[128 * nkv + 16 * m256 + lane], tagw((ldsf(a) + ldsf(a + 64)) + (ldsf(a + 128) + ldsf(a + 192)), tg));
    }
    __syncwarp();
    bar_arrive(NB_PUB, 192);
    const uint4 wv = ld128_keep(P.wr + t * 8);
    #pragma unroll 1
    for (int i = 0; i < 2; i++) {
      mbar_wait(sb + B_G, i ^ 1);
      #pragma unroll 1
      for (int e = 0; e < 4; e++) addc(lds128(sb + OFF_G + t * 16 + 2048 * e), cs);
      bar_sync(NB_WG2, 128);
      if (i == 0 && wp == 0 && elect_one()) { mbar_expect_tx(sb + B_G, 8192); tma_2d(sb + OFF_G, &P.qs, 32 * (c & 31), 256 * (c >> 5) + 128, sb + B_G); }
    }
    float sw = (bf_lo(wv.x) + bf_hi(wv.x)) + (bf_lo(wv.y) + bf_hi(wv.y)) + (bf_lo(wv.z) + bf_hi(wv.z)) + (bf_lo(wv.w) + bf_hi(wv.w));
    #pragma unroll
    for (int o = 16; o; o >>= 1) sw += __shfl_xor_sync(~0u, sw, o);
    if (lane == 0) stsf(sb + OFF_SUMWR + wp * 4, sw);
    if ((t >> 4) == j) {
      const uint32_t a = sb + OFF_WR + (t & 15) * 32;
      sts128(a, wv.x << 16, wv.x & 0xffff0000u, wv.y << 16, wv.y & 0xffff0000u);
      sts128(a + 16, wv.z << 16, wv.z & 0xffff0000u, wv.w << 16, wv.w & 0xffff0000u);
    }
    v = reduce8(cs, lane);
    stsf(sb + OFF_G + (wp * 32 + 8 * (lane & 3) + (lane >> 2)) * 4, v);
    bar_sync(NB_WG2, 128);
    if (wp == 0) {
      const uint32_t a = sb + OFF_G + lane * 4, cq = tagw((ldsf(a) + ldsf(a + 128)) + (ldsf(a + 256) + ldsf(a + 384)), tg);
      st32_rlx(&G->csq[(c >> 5) * DM + 32 * (c & 31) + lane], cq);
      if (lane == 0) mbar_arrive_at(sb + B_W, rank, (cq & P.zero) + 1);
    }
  }

  uint32_t xr[32];
  {
    const bool isq = wg == 2;
    float acc[2][64];
    {
      const uint32_t emptyb = mapa(sb + (isq ? B_EMPTY5 : B_EMPTYKV), t & 1);
      auto correct = [&](uint32_t xa, uint32_t xb) {
        wg_fence();
        wgmma_sa_n128<0, 1, H0, H0>(acc[0], dlo(SB0, 0) + (xa >> 4), dlo(SB0, 0) + (xb >> 4));
        wgmma_sa_n128<0, 1, H0, H0>(acc[1], dlo(SB0, 0) + (xa >> 4) + 64, dlo(SB0, 0) + (xb >> 4));
        wg_commit();
      };
      if (!isq) {
        mbar_wait(sb + B_S0, 0);
        if (wg) mbar_wait(sb + B_FULLKV, 0);
        #pragma unroll 1
        for (int kb = 0; kb < 16; kb++) {
          const uint32_t da = dlo(SB0, 16) + wg * 1024 + (kb & 3) * (KV_STAGE >> 4), db = dlo(SB0 + 32768, 8192) + (kb & 3) * (KV_STAGE >> 4);
          wg_fence();
          #pragma unroll
          for (int k = 0; k < 4; k++) {
            wgmma_ss_n128<0, 1, H128, H128>(acc[0], da + 2 * k, db + 128 * k, k > 0 || kb != 0);
            wgmma_ss_n128<0, 1, H128, H128>(acc[1], da + 512 + 2 * k, db + 128 * k, k > 0 || kb != 0);
          }
          wg_commit();
          wg_wait<1>();
          if (kb > 0 && t < 2) mbar_arrive_remote(emptyb + 8 * ((kb - 1) & 3), kb > 10 ? 3 : 1);
          if (kb < 15) mbar_wait(sb + B_FULLKV + 8 * ((kb + 1) & 3), ((kb + 1) >> 2) & 1);
          if (kb == 0) mbar_wait(sb + B_FULLKV, 0);
          if (kb == 15 - LAG && wg == 1) bar_sync(NB_LAG, 256);
        }
        bar_arrive(wg ? NB_QGO : NB_LAG, 256);
        mbar_wait(sb + B_AUX, 0);
        correct(OFF_AXK + wg * 2048, OFF_BXK);
        wg_wait<0>();
        if (t < 2) mbar_arrive_remote(emptyb + 24, 3);
        fence_regs(acc[0]); fence_regs(acc[1]);
      const uint32_t stg = sb + OFF_X + (1 - wg) * 24576;
      const uint32_t va = stg + 16384 + (16 * wp + (lane & 15)) * 64 + (((lane >> 4) ^ ((lane >> 1) & 3)) << 4);
      const uint32_t ra = sb + OFF_RS256 + (128 * wg + 16 * wp + g) * 4;
      const float rs[4] = {ldsf(ra), ldsf(ra + 32), ldsf(ra + 256), ldsf(ra + 288)};
      float p[2][16];
      uint32_t vf[16], kf[2][16];
      auto project = [&](const uint32_t (&f)[16], uint32_t db) {
        wg_fence();
        #pragma unroll
        for (int i = 0; i < 2; i++) {
          wgmma_rs_n32<1, H64>(p[i], f[8*i], f[8*i+1], f[8*i+2], f[8*i+3], db, 0);
          wgmma_ra_n32<1, H64>(p[i], f[8*i+4], f[8*i+5], f[8*i+6], f[8*i+7], db + 64);
        }
        wg_commit();
      };
      auto fold = [&](uint32_t (&f)[16], int col, float sc) {
        #pragma unroll
        for (int i = 0; i < 16; i++) {
          const float r = rs[2 * (i >> 3) + (i & 1)] * sc;
          f[i] = pack_bf16(acc[i >> 3][col + 2 * (i & 7)] * r, acc[i >> 3][col + 2 * (i & 7) + 1] * r);
          asm volatile("" : "+r"(f[i]));
        }
      };
      auto put_v = [&](const uint32_t (&f)[16]) {
        #pragma unroll
        for (int k = 0; k < 4; k++) stsm4((va ^ ((k & 1) << 5)) + (k >> 1) * 4096, f[4*k], f[4*k+1], f[4*k+2], f[4*k+3]);
      };
      fold(vf, 48, 1.f);
      mbar_wait(sb + B_W, 0);
      fold(kf[0], 0, LOG2E);
      #pragma unroll
      for (int i = 0; i < 32; i++) p[i >> 4][i & 15] = acc[i >> 4][i & 15];
      project(kf[0], dlo(SB0 + OFF_WPHIK, 16));
      mbar_wait(sb + B_W, 0);
      {
        uint32_t v0[16];
        fold(kf[1], 16, LOG2E);
        fold(v0, 32, 1.f);
        if (wg == 1) bar_sync(NB_DN, 256);
        put_v(v0);
      }
      wg_wait<0>();
      fence_regs(p[0]); fence_regs(p[1]);
      if (wg == 1) bar_arrive(NB_WG01, 256);
      #pragma unroll 1
      for (int h = 0; h < 2; h++) {
        uint32_t ph[4][8];
        float rsum[2][4];
        dual_exp2(p[0], ph[0], ph[1]); dual_exp2(p[1], ph[2], ph[3]);
        row_sums(rsum, ph, dlo(SB0 + OFF_SEL, 16));
        if (wg == 0 && h == 0) { bar_arrive(NB_DN, 256); bar_sync(NB_WG01, 256); }
        if (h == 1) {
          if (wg == 1) bar_sync(NB_DN, 256);
          put_v(vf);
        }
        wg_wait<0>();
        fence_regs(rsum[0]); fence_regs(rsum[1]);
        if (!XC && __builtin_expect(__any_sync(~0u, !((rsum[0][0] + rsum[0][1]) + (rsum[0][2] + rsum[0][3]) + (rsum[1][0] + rsum[1][1]) + (rsum[1][2] + rsum[1][3]) < EXP_LIM)), 0)) {
          dual_exp2_shifted<true>(p, ph, rsum);
        }
        if (h == 0) project(kf[1], dlo(SB0 + OFF_WPHIK1, 16));
        normalize(ph, rsum);
        #pragma unroll
        for (int i = 0; i < 8; i++) {
          const uint32_t* f = &ph[i >> 1][4 * (i & 1)];
          stsm4(((stg + sa) ^ ((i & 3) << 5)) + (i >> 2) * 8192, f[0], f[1], f[2], f[3]);
        }
        fence_async_smem();
        if (wg == h) {
          float kv[20];
          #pragma unroll
          for (int w = 0; w < 2; w++) {
            const uint32_t da = dlo(SB0 + OFF_X, 16) + (h ^ w ^ 1) * 1536, db = dlo(SB0 + OFF_X + 16384, OFF_ONES - OFF_X - 16384) - (h ^ w ^ 1) * (1536 * 65535);
            if (w) bar_sync(NB_ST, 256); else bar_sync(NB_L0 + h, 128);
            wg_fence();
            #pragma unroll
            for (int k = 0; k < 8; k++) {
              if (k == 0 && w == 0) wgmma_sz_n40<1, 1, H128, H64>(kv, da, db);
              else wgmma_sa_n40<1, 1, H128, H64>(kv, da + k * 128, db - k * (64 * 65535));
            }
            wg_commit();
          }
          float4* dst = &G->kvacc[(ha + 2 * h) * KVP + t];
          wg_wait<0>();
          fence_regs(kv);
          if (h == 0) bar_arrive(NB_DN, 256); else if (t < 2) { mbar_arrive_at(sb + B_EMPTY5 + 40, t, 2); if (t == 0) mbar_arrive(sb + B_KD); }
          kv[17] = kv[18];
          #pragma unroll
          for (int i = 0; i < 6; i++) red_add_f32x4(dst + 128 * i, kv[3*i], kv[3*i+1], kv[3*i+2], 1.f);
        } else bar_arrive(NB_ST, 256);
        wg_wait<0>();
        fence_regs(p[0]); fence_regs(p[1]);
      }
      #pragma unroll
      for (int i = 0; i < 32; i++) asm volatile("mov.b32 %0, 0;" : "=r"(xr[i]));
      } else {
        uint32_t so = 0, po = 0, par = 0;
        mbar_wait(sb + B_FULL5, 0);
        bar_sync(NB_QGO, 256);
        #pragma unroll 1
        for (int kb = 0; kb < 16 - ML; kb++) {
          const uint32_t da = dlo(SB0, 16) + so * 256, db = dlo(SB0 + 16384, 8192) + so * 256;
          #pragma unroll
          for (int k = 0; k < 4; k++) {
            wg_fence();
            wgmma_ss_n128<0, 1, H128, H128>(acc[0], da + 2 * k, db + 128 * k, k > 0 || kb != 0);
            wgmma_ss_n128<0, 1, H128, H128>(acc[1], da + 512 + 2 * k, db + 128 * k, k > 0 || kb != 0);
            wg_commit();
            if (k == 1 && kb > 0 && t < 2) mbar_arrive_remote(emptyb + po, 2);
            if (k == 3) {
              po = so; so += 8;
              if (so == 40) { so = 0; par ^= 1; }
              mbar_wait(sb + B_FULL5 + so, par);
            }
            if ((QW >> k) & 1) wg_wait<2>(); else wg_wait<1>();
          }
        }
        auto block = [&](const int kb, const int i) {
          wg_fence();
          #pragma unroll
          for (int k = 0; k < 4; k++) wgmma_sa_n128<0, 1, H128, H128>(acc[i], dlo(SB0, 16) + (kb % 5) * 2048 + 512 * i + 2 * k, dlo(SB0 + 16384, 8192) + (kb % 5) * 2048 + 128 * k);
          wg_commit();
        };
        auto hand_over = [&](const int i) {
          const uint32_t ta = sb + (1 + rank) * R5 + sa + i * 8192;
          #pragma unroll
          for (int k = 0; k < 4; k++) {
            const float* a = &acc[i][32 * (k >> 1) + 8 * (k & 1)];
            stsm4(ta ^ (k << 5), pack_bf16(a[0], a[1]), pack_bf16(a[2], a[3]), pack_bf16(a[4], a[5]), pack_bf16(a[6], a[7]));
          }
        };
        mbar_wait2(sb + B_AUXQ, 0, sb + B_OS, 0);
        correct(OFF_AXQ, OFF_BXQ);
        #pragma unroll
        for (int kb = 16 - ML; kb < 16; kb++) {
          block(kb, 0);
          if (kb < 15) mbar_wait(sb + B_FULL5 + 8 * ((kb + 1) % 5), ((kb + 1) / 5) & 1);
          if (kb == 16 - ML) { wg_wait<2>(); if (t < 2) mbar_arrive_remote(emptyb + 8 * ((kb - 1) % 5), 2); }
        }
        mbar_wait(sb + B_RC, 0);
        block(16 - ML, 1);
        block(17 - ML, 1);
        wg_wait<2>();
        fence_regs(acc[0]);
        hand_over(0);
        fence_async_smem();
        bar_arrive(NB_Q0, 256);
        #pragma unroll
        for (int kb = 18 - ML; kb <= 16; kb++) {
          wg_wait<1>();
          if (t < 2) mbar_arrive_remote(emptyb + 8 * ((kb - 2) % 5), 2);
          if (kb < 16) block(kb, 1);
        }
        mbar_wait(sb + B_RC + 8, 0);
        wg_wait<0>();
        if (t < 2) mbar_arrive_remote(emptyb, 2);
        fence_regs(acc[1]);
        hand_over(1);
        fence_async_smem();
        bar_arrive(NB_Q0 + 1, 256);
        #pragma unroll
        for (int i = 0; i < 32; i++) { const float* a = &acc[(i >> 3) & 1][16 + 32 * (i >> 4) + 2 * (i & 7)]; xr[i] = pack_bf16(a[0], a[1]); }
      }
    }
    float p[2][16];
    #pragma unroll
    for (int i = 0; i < 32; i++) asm volatile("mov.b32 %0, 0;" : "=f"(p[i >> 4][i & 15]));
    auto project_r = [&](int w) {
      wg_fence();
      #pragma unroll
      for (int h = 0; h < 2; h++) {
        wgmma_rs_n32<1, H64>(p[h], xr[8*h], xr[8*h+1], xr[8*h+2], xr[8*h+3], dlo(SB0 + OFF_WPHIQ, 16) + 128 * w, 0);
        wgmma_ra_n32<1, H64>(p[h], xr[8*h+4], xr[8*h+5], xr[8*h+6], xr[8*h+7], dlo(SB0 + OFF_WPHIQ, 16) + 128 * w + 64);
      }
      wg_commit();
    };
    auto capture = [&](const int i) {
      if (!i) mbar_wait(sb + B_R, 0);
      #pragma unroll
      for (int k = 0; k < 4; k++) ldsm4(((sb + (1 + rank) * R5 + wg * 8192 + sa) ^ (k << 5)) + i * 2 * R5, xr[16*i+4*k], xr[16*i+4*k+1], xr[16*i+4*k+2], xr[16*i+4*k+3]);
      const uint32_t one = (((xr[16*i] | xr[16*i+4]) | (xr[16*i+8] | xr[16*i+12])) & P.zero) + 1;
      if (lane == 0) mbar_arrive_at(sb + (i ? B_RX : B_RC + 8 * wg), i ? wg : rank, one);
    };
    const uint32_t rq = sb + OFF_RSQ + (16 * wp + g) * 4 + 256 * (wg & 1), rb = rq + 128 * (wg & 2);
    const float cc[2][2] = {{ldsf(rq) * LOG2E, ldsf(rq + 32) * LOG2E}, {ldsf(rb) * LOG2E, ldsf(rb + 32) * LOG2E}};
    {
      const uint4* src = reinterpret_cast<const uint4*>(&G->kvacc[(4 * j + wg) * KVP + t]);
      const uint32_t full = kv_count(__float_as_uint(ldsf(sb + OFF_EP)), 8);
      uint4 v[12];
      #pragma unroll
      for (int i = 0; i < 12; i++) v[i] = i < 6 || isq ? ld128_rlx(src + 128 * i) : make_uint4(0, 0, 0, full);
      if (isq) {
        project_r(2);
        wg_wait<0>();
        #pragma unroll
        for (int i = 0; i < 16; i++) xr[i] = xr[16 + i];
      } else {
        capture(0);
      }
      #pragma unroll 1
      for (uint32_t it = 0; it < POLL_LIMIT; it++) {
        uint32_t bad = 0;
        #pragma unroll
        for (int i = 0; i < 12; i++) bad |= v[i].w ^ full;
        if (!__any_sync(~0u, bad != 0)) break;
        #pragma unroll
        for (int i = 0; i < 12; i++) if (i < 6 || isq) v[i] = ld128_rlx(src + 128 * i);
      }
      mbar_wait(sb + B_KD, 0);
      #pragma unroll
      for (int e = 0; e < 2; e++) {
        if (e == 0 || isq) {
          float f[18];
          #pragma unroll
          for (int i = 0; i < 6; i++) { f[3*i] = __uint_as_float(v[6*e+i].x); f[3*i+1] = __uint_as_float(v[6*e+i].y); f[3*i+2] = __uint_as_float(v[6*e+i].z); }
          const uint32_t ka = sb + OFF_KVZ + (wg + e) * 5120 + wp * 1280 + lane * 16;
          stsm4(ka, pack_bf16(f[0], f[1]), pack_bf16(f[2], f[3]), pack_bf16(f[4], f[5]), pack_bf16(f[6], f[7]));
          stsm4(ka + 512, pack_bf16(f[8], f[9]), pack_bf16(f[10], f[11]), pack_bf16(f[12], f[13]), pack_bf16(f[14], f[15]));
          stsm2(ka + 1024, pack_bf16(f[16], 1.f), pack_bf16(f[17], 1.f));
        }
      }
    }
    fence_async_smem();
    if (wg == 1) bar_arrive(NB_DN, 256);
    #pragma unroll 1
    for (int e = wg; e < wg + 1 + (wg >> 1); e++) {
      const int half = e >> 1, hh = e & 1, turn = e;
      const uint32_t ao = (1 + rank) * R5 + hh * 8192;
      uint32_t ph[4][8];
      #pragma unroll
      for (int i = 0; i < 32; i++) asm volatile("mov.b32 %0, 0;" : "=r"(ph[i >> 3][i & 7]));
      uint32_t shifted = 0;
      asm volatile("" : "+r"(shifted));
      #pragma unroll 1
      for (;;) {
        if (!XC && shifted) { float unused[2][4]; dual_exp2_shifted<false>(p, ph, unused); }
        uint32_t first = (shifted ^ 1) & !isq;
        asm volatile("" : "+r"(first));
        if (first) {
          bar_sync(NB_Q0 + wg, 256);
          const uint32_t da = dlo(SB0, 16) + (ao >> 4), db = dlo(SB0 + OFF_WPHIQ, 16);
          wg_fence();
          #pragma unroll
          for (int h = 0; h < 2; h++) {
            wgmma_ss_n32<0, 1, H128, H64>(p[h], da + 4 * h, db + 128 * h, 0);
            wgmma_sa_n32<0, 1, H128, H64>(p[h], da + 4 * h + 2, db + 128 * h + 64);
          }
          wg_commit();
          capture(1);
          wg_wait<0>();
        }
        fence_regs(p[0]); fence_regs(p[1]);
        uint32_t again = shifted;
        asm volatile("" : "+r"(again));
        if (again) break;
        float s2[4] = {0.f, 0.f, 0.f, 0.f};
        #pragma unroll
        for (int i = 0; i < 32; i++) { float& x = p[i >> 4][i & 15]; x *= cc[i >> 4][(i >> 1) & 1]; s2[i & 3] = fmaf(x, x, s2[i & 3]); }
        if (!__any_sync(~0u, !((s2[0] < ARG_LIM2) & (s2[1] < ARG_LIM2) & (s2[2] < ARG_LIM2) & (s2[3] < ARG_LIM2)))) break;
        shifted = 1;
      }
      if (e == 1 || e == 2) bar_sync(NB_TOK + e - 1, 256);
      float ac[4][20];
      auto numer = [&](int h) {
        const uint32_t (*f)[8] = &ph[2 * h];
        const uint32_t db = dlo(SB0 + OFF_KVZ, 128) + (half ? e : h) * 320;
        wg_fence();
        #pragma unroll
        for (int i = 0; i < 2; i++) {
          wgmma_rz_n40<1, dhi(256, 0)>(ac[2*h+i], f[i][0], f[i][1], f[i][2], f[i][3], db + i * 160);
          wgmma_ra_n40<1, dhi(256, 0)>(ac[2*h+i], f[i][4], f[i][5], f[i][6], f[i][7], db + (i * 160 + 80));
        }
        wg_commit();
      };
      const uint32_t oa = (16 * wp + g) * 128 + (((lane & 3) ^ g) << 4);
      auto finish = [&](int h) {
        const float* ap = ac[2 * h]; const float* am = ac[2 * h + 1];
        const float ip0 = rcp(ap[17]), im0 = rcp(am[17]), ip1 = rcp(ap[19]), im1 = rcp(am[19]);
        const float d0 = rcp(fmaf(ap[16], ip0, fmaf(am[16], im0, 1e-6f))), d1 = rcp(fmaf(ap[18], ip1, fmaf(am[18], im1, 1e-6f)));
        const float a0 = ip0 * d0, b0 = im0 * d0, a1 = ip1 * d1, b1 = im1 * d1;
        #pragma unroll
        for (int r = 0; r < 2; r++) {
          const float a = r ? a1 : a0, b = r ? b1 : b0;
          uint32_t w[4];
          #pragma unroll
          for (int k = 0; k < 4; k++) w[k] = pack_bf16(fmaf(ap[4*k+2*r], a, am[4*k+2*r] * b), fmaf(ap[4*k+2*r+1], a, am[4*k+2*r+1] * b));
          const uint32_t off = (oa ^ ((half ? rank : h) << 6)) + r * 1024;
          st128_rlx(reinterpret_cast<uint8_t*>(G->o + (m128 * 16 + (half ? 2 * (j & 6) + 2 * hh + 1 : 2 * j)) * 8192 + (half ? h : hh) * 4096) + off, w[0], w[1], w[2], w[3]);
          if (!half) sts128(sb + ao + off, w[0], w[1], w[2], w[3]);
        }
        if ((half || h) && lane < 8) st32_rlx(&G->oflag[((m128 * 6 + (half ? 2 * e - 2 + h : hh)) * 32 + 4 * j + wp) * 8 + lane], 1);
      };
      if (!shifted) dual_exp2(p[0], ph[0], ph[1]);
      numer(0);
      if (!shifted) dual_exp2(p[1], ph[2], ph[3]);
      if (turn < 2) bar_arrive(NB_TOK + turn, 256);
      if (wg == 0) bar_sync(NB_DN, 256);
      numer(1);
      wg_wait<1>();
      fence_regs(ac[0]); fence_regs(ac[1]);
      finish(0);
      wg_wait<0>();
      fence_regs(ac[2]); fence_regs(ac[3]);
      #pragma unroll
      for (int i = 0; i < 32; i++) asm volatile("mov.b32 %0, 0;" : "=f"(p[i >> 4][i & 15]));
      if (e == 2) project_r(3);
      finish(1);
      if (!half) fence_async_smem();
      __syncwarp();
      if (lane == 0) mbar_arrive(sb + B_UO + 8 * e);
      wg_wait<0>();
    }
    if (isq) cluster_arrive();
  }

  {
  int lane;
  asm volatile("mov.u32 %0, %%laneid;" : "=r"(lane));
  const int g = lane >> 2, q = lane & 3;
  if (wg < 2) {
    float h[64];
    {
      #pragma unroll
      for (int i = 0; i < 32; i++) { h[2*i] = bf_lo(xr[i]); h[2*i+1] = bf_hi(xr[i]); }
      fence_regs(h);
      const uint32_t emptyb = mapa(sb + B_EMPTY5, t & 1);
      uint32_t s = 1 + rank, ps = 0;
      mbar_wait2(sb + B_GB + 8 * rank, 0, sb + B_UO + 8 * wg, 0);
      #pragma unroll
      for (int i = 0; i < G2P; i++) {
        const uint32_t da = dlo(SB0, 16) + s * 2048 + wg * 512, db = dlo(SB0 + 16384, 8192) + s * 2048;
        wg_fence();
        #pragma unroll
        for (int k = 0; k < 4; k++) wgmma_sa_n128<0, 1, H128, H128>(h, da + k * 2, db + k * 128);
        wg_commit();
        const uint32_t ns = i ? (i + 2) % 6 : 2 - rank;
        const uint32_t nb = i ? i + 1 : 1 - rank, b0 = sb + B_GB + 8 * nb, b1 = sb + B_GA + 16 * nb + 8 * wg;
        const bool here = i == 15 || mbar_test2(b0, 0, b1, 0);
        wg_wait<1>();
        if (!(((2 * REL + 1) >> i) & 1) && i < 14 && t < 2) mbar_arrive_remote(emptyb + 8 * ps, 1);
        if ((REL >> i) & 1) { wg_wait<0>(); if (t < 2) mbar_arrive_remote(emptyb + 8 * s, 1); }
        if (!here) mbar_wait2u(b0, b1);
        ps = s; s = ns;
      }
      #pragma unroll 1
      for (int i = G2P; i < 16; i++) {
        const uint32_t da = dlo(SB0, 16) + s * 2048 + wg * 512, db = dlo(SB0 + 16384, 8192) + s * 2048;
        wg_fence();
        #pragma unroll
        for (int k = 0; k < 4; k++) wgmma_sa_n128<0, 1, H128, H128>(h, da + k * 2, db + k * 128);
        wg_commit();
        const uint32_t nb = min(i + 1, 15), b0 = sb + B_GB + 8 * nb, b1 = sb + B_GA + 16 * nb + 8 * wg;
        const bool here = mbar_test2(b0, 0, b1, 0);
        wg_wait<1>();
        if (t < 2) mbar_arrive_remote(emptyb + 8 * ps, 1);
        if (!here) mbar_wait2u(b0, b1);
        ps = s; s = s == 5 ? 0 : s + 1;
      }
    }
    cluster_arrive();
    float2 wr[16];
    #pragma unroll
    for (int i = 0; i < 16; i++) wr[i] = lds64f(sb + OFF_WR + 32 * i + 8 * q);
    const int r0 = 64 * wg + 16 * wp + g;
    float sum0, sum1, dot0, dot1, sq0, sq1;
    uint32_t redo = 0;
    asm volatile("" : "+r"(redo));
    #pragma unroll 1
    for (;;) {
    if (!XC && redo) {
      wg_wait<0>();
      #pragma unroll 1
      for (int n4 = 0; n4 < 4; n4++) {
        const uint32_t* xp = reinterpret_cast<const uint32_t*>(P.x + (size_t)(128 * m128 + r0) * DM + 128 * j) + 16 * n4 + q;
        #pragma unroll
        for (int i = 0; i < 48; i++) h[i] = h[i + 16];
        #pragma unroll
        for (int i = 0; i < 8; i++) { const uint32_t v = xp[4 * (i >> 1) + (i & 1) * 4 * DM]; h[48+2*i] = bf_lo(v); h[49+2*i] = bf_hi(v); }
        #pragma unroll 1
        for (int ks = 0; ks < 64; ks++) {
          const int kb = ks >> 2, kk = 16 * (ks & 3);
          const bf16* op = G->o + (m128 * 16 + kb) * 8192 + r0 * 64 + 2 * q + (((kk >> 3) ^ g) << 3);
          const uint32_t* w = reinterpret_cast<const uint32_t*>(P.wo_p) + 64 * j + 16 * n4 + q +
              (((kb & 1) ? 256 * (kb >> 2) + 32 * (kb & 2) + 32 + 4 * (kk & 32) : 64 * kb + 2 * (kk & 32)) + ((kk & 16) >> 2) + 4 * (g & 6) + (g & 1)) * (DM / 2);
          uint32_t b[8], a0, a1, a2, a3, it = 0;
          #pragma unroll
          for (int n = 0; n < 8; n++) b[n] = w[4 * (n >> 1) + (n & 1) * DM];
          const bf16* o2 = op + 8 - 16 * (g & 1);
          do { a0 = ld32_rlx(op); a1 = ld32_rlx(op + 512); a2 = ld32_rlx(o2); a3 = ld32_rlx(o2 + 512); }
          while (__any_sync(~0u, max(max(a0, a1), max(a2, a3)) == ~0u) && ++it < POLL_LIMIT);
          #pragma unroll
          for (int n = 0; n < 4; n++) mma16816(h[48+4*n], h[49+4*n], h[50+4*n], h[51+4*n], a0, a1, a2, a3, transpose8(b[2*n]), transpose8(b[2*n+1]));
        }
      }
    }
    wg_wait<0>();
    fence_regs(h);
    sum0 = 0.f, sum1 = 0.f, dot0 = 0.f, dot1 = 0.f, sq0 = 0.f, sq1 = 0.f;
    #pragma unroll
    for (int i = 0; i < 16; i++) {
      sum0 += h[4*i] + h[4*i+1]; sum1 += h[4*i+2] + h[4*i+3];
      sq0 = fmaf(h[4*i], h[4*i], fmaf(h[4*i+1], h[4*i+1], sq0)); sq1 = fmaf(h[4*i+2], h[4*i+2], fmaf(h[4*i+3], h[4*i+3], sq1));
      dot0 = fmaf(h[4*i], wr[i].x, fmaf(h[4*i+1], wr[i].y, dot0)); dot1 = fmaf(h[4*i+2], wr[i].x, fmaf(h[4*i+3], wr[i].y, dot1));
    }
    if (!__any_sync(~0u, !redo & (h[0] != h[0] | h[2] != h[2]))) break;
    redo = 1;
    }
    float4* const rs = &G->rstat[128 * m128 + r0];
    {
      const bool up = q & 2;
      float a = up ? sum1 : sum0, b = up ? sq1 : sq0, d = up ? dot1 : dot0;
      a += __shfl_xor_sync(~0u, up ? sum0 : sum1, 2); b += __shfl_xor_sync(~0u, up ? sq0 : sq1, 2); d += __shfl_xor_sync(~0u, up ? dot0 : dot1, 2);
      a += __shfl_xor_sync(~0u, a, 1); b += __shfl_xor_sync(~0u, b, 1); d += __shfl_xor_sync(~0u, d, 1);
      if ((q & 1) == 0) red_add_f32x4(rs + 4 * q, a, b, d, 1.f);
    }
    float rstd[2], bm[2];
    uint32_t best, it = 0;
    {
      const float2 swa = lds64f(sb + OFF_SUMWR), swb = lds64f(sb + OFF_SUMWR + 8);
      const float sw = (swa.x + swa.y) + (swb.x + swb.y);
      uint4 a[2]; uint32_t key[2];
      do { a[0] = ld128_rlx(rs); a[1] = ld128_rlx(rs + 8); } while (__any_sync(~0u, (a[0].w & a[1].w) != 0x41000000u) && ++it < POLL_LIMIT);
      #pragma unroll
      for (int i = 0; i < 2; i++) {
        const float mean = __uint_as_float(a[i].x) * (1.f / DM);
        rstd[i] = rsqrtf(fmaxf(__uint_as_float(a[i].y) * (1.f / DM) - mean * mean, 0.f) + 1e-5f);
        bm[i] = -mean * rstd[i];
        const uint32_t rr = __float_as_uint(fmaf(__uint_as_float(a[i].z), rstd[i], sw * bm[i]));
        key[i] = ((rr ^ ((uint32_t)((int32_t)rr >> 31) | 0x80000000u)) & ~2047u) | (2047 - 128 * m128 - r0 - 8 * i);
      }
      asm volatile("redux.sync.max.u32 %0, %1, 0xffffffff;" : "=r"(best) : "r"(max(key[0], key[1])));
    }
    sts32(sb + OFF_BEST + 4 * warp, best);
    bar_sync(NB_WG01, 256);
    {
      const uint4 b0 = lds128(sb + OFF_BEST), b1 = lds128(sb + OFF_BEST + 16);
      best = max(max(max(b0.x, b0.y), max(b0.z, b0.w)), max(max(b1.x, b1.y), max(b1.z, b1.w)));
    }
    const int win = ~best & 127;
    if (warp == ((win >> 4) ^ 1) && (lane < 4 || it == 0)) st128_rlx(&G->key[((2 * j + (lane >> 1)) & 15) * 128 + 8 * m128 + 4 * (lane & 1)], best, best, best, best);
    if ((win & 0x77) == r0) {
      const bool up = win & 8;
      const float ra = up ? rstd[1] : rstd[0], rb = up ? bm[1] : bm[0];
      uint32_t x[16];
      #pragma unroll
      for (int i = 0; i < 16; i++) x[i] = pack_bf16(fmaf(up ? h[4*i+2] : h[4*i], ra, rb), fmaf(up ? h[4*i+3] : h[4*i+1], ra, rb));
      #pragma unroll
      for (int i = 0; i < 4; i++) st128_rlx(&G->cand[m128 * 512 + 64 * j + 16 * i + 4 * q], x[4*i], x[4*i+1], x[4*i+2], x[4*i+3]);
    }
    __syncwarp();
    bar_arrive(NB_G2E, 384);
    {
      const float a0 = 1.f + rstd[0], b0 = bm[0], a1 = 1.f + rstd[1], b1 = bm[1];
      #pragma unroll
      for (int k = 0; k < 8; k++)
        stsm4(((sb + OFF_OUT + wg * 8192 + sa) ^ ((k & 3) << 5)) + (k >> 2) * 16384,
              pack_bf16(fmaf(h[8*k], a0, b0), fmaf(h[8*k+1], a0, b0)),     pack_bf16(fmaf(h[8*k+2], a1, b1), fmaf(h[8*k+3], a1, b1)),
              pack_bf16(fmaf(h[8*k+4], a0, b0), fmaf(h[8*k+5], a0, b0)),   pack_bf16(fmaf(h[8*k+6], a1, b1), fmaf(h[8*k+7], a1, b1)));
      fence_async_smem();
      __syncwarp();
      if (lane == 0) mbar_arrive(sb + B_OUT + 8 * wg);
    }
    {
      uint32_t wa[8][4][4];
      const uint32_t wb = sb + 16384 * (((uint32_t)FF_SLOT >> (4 * warp)) & 15) + ((lane & 7) + ((lane >> 4) << 3)) * 64 + ((((lane >> 3) & 1) ^ ((lane >> 1) & 3)) << 4);
      if (f < NFFN) mbar_wait(sb + B_F + 8 * warp, 0);
      #pragma unroll
      for (int i = 0; i < 32; i++) ldsm4t((wb ^ ((i & 1) << 5)) + ((i >> 1) & 1) * 8192 + (i >> 2) * 1024, wa[i >> 2][i & 3][0], wa[i >> 2][i & 3][1], wa[i >> 2][i & 3][2], wa[i >> 2][i & 3][3]);
      bar_sync(NB_XS, 384);
      uint4 xs[4];
      #pragma unroll
      for (int i = 0; i < 4; i++) xs[i] = lds128(sb + OFF_XSEL + 256 * warp + 64 * i + 16 * q);
      float d[4][4];
      #pragma unroll
      for (int ks = 0; ks < 8; ks++) {
        #pragma unroll
        for (int m = 0; m < 4; m++) {
          if (ks == 0) { d[m][0] = 0.f; d[m][1] = 0.f; d[m][2] = 0.f; d[m][3] = 0.f; }
          mma16816(d[m][0], d[m][1], d[m][2], d[m][3], wa[ks][m][0], wa[ks][m][1], wa[ks][m][2], wa[ks][m][3],
                   (ks & 1) ? xs[ks >> 1].z : xs[ks >> 1].x, (ks & 1) ? xs[ks >> 1].w : xs[ks >> 1].y);
        }
      }
      #pragma unroll
      for (int m = 0; m < 8; m++) stsf(sb + OFF_GU + (8 * m + g) * 48 + 4 * warp, d[m >> 1][2 * (m & 1)]);
      bar_arrive(NB_ACT, 384);
    }
    {
      const uint32_t ky = __float_as_uint(ldsf(sb + OFF_KEY));
      const int row = 2047 - (ky & 2047) - 128 * m128;
      if ((uint32_t)row < 128u) {
        const int vi = (j & 1) + wg, e = 3 * vi + q - 4 * (j & 1);
        const float kr = __uint_as_float((ky & ~2047u) ^ ((ky >> 31) ? 0x80000000u : 0xfffff800u));
        const int col = 32 * wp + 16 * (e & 1) + 4 * (e & 2) + g;
        const float sg = rcp(1.f + ex2(-LOG2E * kr));
        const uint32_t base = __float_as_uint(ldsf(sb + OFF_OUT + (col >> 6) * 16384 + row * 128 + ((((col >> 3) ^ row) & 7) << 4) + 2 * (col & 6)));
        const float4* yp = &G->yacc[(q * 3 + vi) * 128 + 32 * (j >> 1) + 8 * wp + g];
        uint32_t it = 0;
        uint4 v;
        mbar_wait(sb + B_SD, 0);
        do { v = ld128_rlx(yp); } while (__any_sync(~0u, __uint_as_float(v.w) != (float)(NFFN / 4)) && ++it < POLL_LIMIT);
        float y0 = __uint_as_float(v.x), y1 = __uint_as_float(v.y), y2 = __uint_as_float(v.z);
        #pragma unroll
        for (int o = 1; o < 4; o <<= 1) { y0 += __shfl_xor_sync(~0u, y0, o); y1 += __shfl_xor_sync(~0u, y1, o); y2 += __shfl_xor_sync(~0u, y2, o); }
        if (q < 3 && (uint32_t)e < 4u)
          P.out_p[(size_t)(128 * m128 + row) * DM + 128 * j + col] = __float2bfloat16(fmaf(q == 0 ? y0 : q == 1 ? y1 : y2, sg, (col & 1) ? bf_hi(base) : bf_lo(base)));
      }
      if (c == 0 && tid == 0) st32_rlx(&G->epoch, __float_as_uint(ldsf(sb + OFF_EP)));
    }
  }
  if (wg == 2) {
    uint32_t wf[16][2][4];
    {
      const uint32_t wb = sb + OFF_S + 16384 * (wp & 1) + ((lane & 7) + ((lane >> 4) << 3)) * 128 + ((((lane >> 3) & 1) ^ (lane & 7)) << 4);
      if (f < NFFN) mbar_wait(sb + B_WD + 8 * wp, 0);
      #pragma unroll
      for (int i = 0; i < 32; i++) ldsm4t((wb ^ (((i >> 1) & 3) << 5)) + (i >> 3) * 4096 + (i & 1) * 2048, wf[i >> 1][i & 1][0], wf[i >> 1][i & 1][1], wf[i >> 1][i & 1][2], wf[i >> 1][i & 1][3]);
      fence_async_smem();
      __syncwarp();
      if (lane == 0) mbar_arrive(sb + B_WC + 8 * wp);
    }
    bar_sync(NB_G2E, 384);
    {
      uint32_t cur = 0;
      uint4 v;
      #pragma unroll 1
      for (uint32_t it = 0; it < POLL_LIMIT; it++) {
        const uint32_t kx = ld32_rlx(&G->key[(c & 15) * 128 + 8 * (lane & 15)]);
        v = ld128_rlx(&G->cand[((~cur >> 7) & 15) * 512 + 4 * t]);
        uint32_t best;
        asm volatile("redux.sync.max.u32 %0, %1, 0xffffffff;" : "=r"(best) : "r"(kx));
        if (!__any_sync(~0u, kx == 0 || v.w == ~0u) && best == cur) break;
        cur = best;
      }
      sts128(sb + OFF_XSEL + 16 * t, v.x, v.y, v.z, v.w);
      sts32(sb + OFF_KEY, cur);
      bar_arrive(NB_XS, 384);
    }
    float4* yd = &G->yacc[(f & 3) * 384 + 32 * wp + 8 * q + g];
    asm volatile("" : "+l"(yd));
    if (f >= NFFN) { bar_arrive(NB_ACT, 384); cluster_wait(); return; }
    bar_sync(NB_ACT, 384);
    float gu[2];
    #pragma unroll
    for (int i = 0; i < 2; i++) {
      const uint4 v0 = lds128(sb + OFF_GU + (32 * i + lane) * 48), v1 = lds128(sb + OFF_GU + (32 * i + lane) * 48 + 16);
      gu[i] = ((__uint_as_float(v0.x) + __uint_as_float(v0.y)) + (__uint_as_float(v0.z) + __uint_as_float(v0.w))) +
              ((__uint_as_float(v1.x) + __uint_as_float(v1.y)) + (__uint_as_float(v1.z) + __uint_as_float(v1.w)));
    }
    const float act = gu[0] * gu[1] * rcp(1.f + ex2(-LOG2E * gu[0]));
    const uint32_t ap = pack_bf16(act, __shfl_down_sync(~0u, act, 1));
    uint32_t bf[4];
    #pragma unroll
    for (int i = 0; i < 4; i++) bf[i] = __shfl_sync(~0u, ap, 2 * q + 8 * i);
    float d[16][4];
    #pragma unroll
    for (int k = 0; k < 2; k++)
      #pragma unroll
      for (int i = 0; i < 16; i++) {
        if (k == 0) { d[i][0] = 0.f; d[i][1] = 0.f; d[i][2] = 0.f; d[i][3] = 0.f; }
        mma16816(d[i][0], d[i][1], d[i][2], d[i][3], wf[i][k][0], wf[i][k][1], wf[i][k][2], wf[i][k][3], bf[2*k], bf[2*k+1]);
      }
    float y[9];
    #pragma unroll
    for (int e = 0; e < 8; e++) {
      const int n = 2 * (e & 4) + (e & 1);
      const float lo = (q & 1) ? d[n + 2][e & 2] : d[n][e & 2], hi = (q & 1) ? d[n + 6][e & 2] : d[n + 4][e & 2];
      y[e] = (q & 2) ? hi : lo;
    }
    y[8] = 0.f;
    #pragma unroll
    for (int i = 0; i < 3; i++) red_add_f32x4(yd + 128 * i, y[3*i], y[3*i+1], y[3*i+2], 1.f);
  }
  }
  cluster_wait();
}

typedef CUresult (*EncodeFn)(CUtensorMap*, CUtensorMapDataType, cuuint32_t, void*, const cuuint64_t*, const cuuint64_t*,
                             const cuuint32_t*, const cuuint32_t*, CUtensorMapInterleave, CUtensorMapSwizzle,
                             CUtensorMapL2promotion, CUtensorMapFloatOOBfill);

void make_map(EncodeFn enc, CUtensorMap* m, const void* p, int n, const cuuint64_t* dims, const cuuint64_t* str, const cuuint32_t* box,
              CUtensorMapSwizzle sw, CUtensorMapL2promotion promo) {
  cuuint32_t es[5] = {1, 1, 1, 1, 1};
  enc(m, CU_TENSOR_MAP_DATA_TYPE_BFLOAT16, n, const_cast<void*>(p), dims, str, box, es, CU_TENSOR_MAP_INTERLEAVE_NONE, sw, promo,
      CU_TENSOR_MAP_FLOAT_OOB_FILL_NONE);
}
void map2(EncodeFn enc, CUtensorMap* m, const void* p, uint64_t cols, uint64_t rows, uint32_t bc, uint32_t br, CUtensorMapSwizzle sw,
          CUtensorMapL2promotion promo) {
  const cuuint64_t dims[2] = {cols, rows}, str[1] = {cols * 2};
  const cuuint32_t box[2] = {bc, br};
  make_map(enc, m, p, 2, dims, str, box, sw, promo);
}
void map3(EncodeFn enc, CUtensorMap* m, const void* p, uint64_t cols, uint64_t rows, uint32_t br, uint32_t nb) {
  const cuuint64_t dims[3] = {64, rows, cols / 64}, str[2] = {cols * 2, 128};
  const cuuint32_t box[3] = {64, br, nb};
  make_map(enc, m, p, 3, dims, str, box, CU_TENSOR_MAP_SWIZZLE_128B, CU_TENSOR_MAP_L2_PROMOTION_L2_128B);
}

}

extern "C" void kernel_launch(void* const* d_in, const int* in_sizes, int n_in, void* d_out, int out_size) {
  (void)in_sizes; (void)n_in; (void)out_size;
  static EncodeFn enc = nullptr;
  static void* o_ptr = nullptr;
  if (!enc) {
    void* f = nullptr; cudaDriverEntryPointQueryResult qr;
    cudaGetDriverEntryPoint("cuTensorMapEncodeTiled", &f, cudaEnableDefault, &qr);
    enc = (EncodeFn)f;
    cudaGetSymbolAddress(&o_ptr, g_scr);
    cudaFuncSetAttribute(fused_kernel, cudaFuncAttributeMaxDynamicSharedMemorySize, SMEM_BYTES);
  }
  const bf16* x = (const bf16*)d_in[0];
  const bf16* wqkv = (const bf16*)d_in[1];
  const bf16* wphi = (const bf16*)d_in[2];
  const bf16* wo = (const bf16*)d_in[3];
  const bf16* wr = (const bf16*)d_in[5];
  const bf16* wgate = (const bf16*)d_in[6];
  const bf16* wup = (const bf16*)d_in[7];
  const bf16* wdown = (const bf16*)d_in[8];
  Params P;
  const CUtensorMapSwizzle S128 = CU_TENSOR_MAP_SWIZZLE_128B, S64 = CU_TENSOR_MAP_SWIZZLE_64B;
  const CUtensorMapL2promotion L128 = CU_TENSOR_MAP_L2_PROMOTION_L2_128B, L256 = CU_TENSOR_MAP_L2_PROMOTION_L2_256B,
                               L64 = CU_TENSOR_MAP_L2_PROMOTION_L2_64B;
  map2(enc, &P.x128, x, DM, SEQ, 64, 128, S128, L128);
  map2(enc, &P.x64, x, DM, SEQ, 64, 64, S128, L128);
  {
    const cuuint64_t dims[4] = {64, DM, 16, 3}, str[3] = {6 * DM, 128, 2 * DM};
    const cuuint32_t box[4] = {64, 64, 1, 2};
    make_map(enc, &P.wkv, wqkv, 4, dims, str, box, S128, L128);
  }
  map3(enc, &P.wq, wqkv, 3 * DM, DM, 64, 2);
  for (int i = 0; i < 2; i++) {
    const cuuint64_t dims[5] = {DM, (cuuint64_t)(DM - 94 - 64 * i), 4, 4, 2}, str[4] = {2 * DM, 16 * DM, 4 * DM, (cuuint64_t)(128 * DM) << i};
    const cuuint32_t box[5] = {64, 2, 4, 4, 2};
    make_map(enc, &P.wo[i], wo, 5, dims, str, box, S128, L128);
  }
  map3(enc, &P.wd, wdown, DM, FF, 32, 4);
  map2(enc, &P.wg, wgate, FF, DM, 32, 128, S64, L64);
  map2(enc, &P.wu, wup, FF, DM, 32, 128, S64, L64);
  map2(enc, &P.tg, wgate, FF, DM, 8, 16, CU_TENSOR_MAP_SWIZZLE_NONE, L128);
  map2(enc, &P.tu, wup, FF, DM, 8, 16, CU_TENSOR_MAP_SWIZZLE_NONE, L128);
  map2(enc, &P.td, wdown, 128, FF * 8, 8, 16, CU_TENSOR_MAP_SWIZZLE_NONE, L256);
  map2(enc, &P.xs, x, DM, SEQ, 128, 16, CU_TENSOR_MAP_SWIZZLE_NONE, L256);
  map2(enc, &P.ws, wqkv, 3 * DM, DM, 16, 128, CU_TENSOR_MAP_SWIZZLE_NONE, L128);
  map2(enc, &P.qs, wqkv, 3 * DM, DM, 32, 128, CU_TENSOR_MAP_SWIZZLE_NONE, L64);
  map2(enc, &P.out, d_out, DM, SEQ, 64, 16, S128, L128);
  map2(enc, &P.o, o_ptr, 256, SEQ * DM / 256, 256, 16, CU_TENSOR_MAP_SWIZZLE_NONE, L128);
  map2(enc, &P.phi, wphi, 32, 1024, 32, 32, S64, L64);
  P.x = x; P.wqkv = wqkv; P.wo_p = wo; P.wr = wr; P.out_p = (bf16*)d_out; P.g = (Scratch*)o_ptr; P.zero = 0;

  fused_kernel<<<128, 512, SMEM_BYTES, cudaStreamPerThread>>>(P);
}
```

```cpp
#include <cuda_runtime.h>
#include <cuda.h>
#include <cuda_bf16.h>
#include <stdint.h>

namespace {

typedef __nv_bfloat16 bf16;

__device__ __forceinline__ uint32_t smem_u32(const void* p){ return (uint32_t)__cvta_generic_to_shared(p); }
__device__ __forceinline__ void mbar_init(uint32_t bar, uint32_t cnt){ asm volatile("mbarrier.init.shared::cta.b64 [%0], %1;"::"r"(bar),"r"(cnt):"memory"); }
__device__ __forceinline__ void mbar_expect_tx(uint32_t bar, uint32_t bytes){ asm volatile("mbarrier.arrive.expect_tx.shared::cta.b64 _, [%0], %1;"::"r"(bar),"r"(bytes):"memory"); }
__device__ __forceinline__ void mbar_arrive(uint32_t bar){ asm volatile("mbarrier.arrive.shared::cta.b64 _, [%0];"::"r"(bar):"memory"); }
__device__ __forceinline__ uint32_t mapa(uint32_t addr, uint32_t cta){ uint32_t r; asm volatile("mapa.shared::cluster.u32 %0, %1, %2;":"=r"(r):"r"(addr),"r"(cta)); return r; }
__device__ __forceinline__ void mbar_arrive_at(uint32_t bar, uint32_t cta, uint32_t cnt){
  asm volatile("{\n.reg .b32 ra;\nmapa.shared::cluster.u32 ra, %0, %1;\nmbarrier.arrive.shared::cluster.b64 _, [ra], %2;\n}\n"::"r"(bar),"r"(cta),"r"(cnt):"memory"); }
__device__ __forceinline__ void mbar_arrive_remote(uint32_t cluster_addr, uint32_t cnt){
  asm volatile("mbarrier.arrive.shared::cluster.b64 _, [%0], %1;"::"r"(cluster_addr),"r"(cnt):"memory"); }
__device__ __forceinline__ void mbar_wait(uint32_t bar, uint32_t parity){
  asm volatile("{\n.reg .pred p;\n.reg .u32 c;\nmov.u32 c, 0;\nLW:\nmbarrier.try_wait.parity.shared::cta.b64 p, [%0], %1;\n@p bra LD;\nadd.u32 c, c, 1;\nsetp.lt.u32 p, c, 2000000;\n@p bra LW;\ntrap;\nLD:\n}\n"::"r"(bar),"r"(parity):"memory"); }
__device__ __forceinline__ void mbar_wait2(uint32_t bar0, uint32_t par0, uint32_t bar1, uint32_t par1){
  asm volatile("{\n.reg .pred p, q;\n.reg .u32 c;\nmov.u32 c, 0;\nLW:\nmbarrier.try_wait.parity.shared::cta.b64 p, [%0], %1;\nmbarrier.try_wait.parity.shared::cta.b64 q, [%2], %3;\nand.pred p, p, q;\n@p bra LD;\nadd.u32 c, c, 1;\nsetp.lt.u32 p, c, 2000000;\n@p bra LW;\ntrap;\nLD:\n}\n"::"r"(bar0),"r"(par0),"r"(bar1),"r"(par1):"memory"); }
__device__ __forceinline__ void mbar_wait2u(uint32_t bar0, uint32_t bar1){
  asm volatile("{\n.reg .pred p, q;\nLW:\nmbarrier.try_wait.parity.shared::cta.b64 p, [%0], 0;\nmbarrier.try_wait.parity.shared::cta.b64 q, [%1], 0;\nand.pred p, p, q;\n@!p bra LW;\n}\n"::"r"(bar0),"r"(bar1):"memory"); }
__device__ __forceinline__ bool mbar_test2(uint32_t bar0, uint32_t par0, uint32_t bar1, uint32_t par1){
  uint32_t r;
  asm volatile("{\n.reg .pred p, q;\nmbarrier.test_wait.parity.shared::cta.b64 p, [%1], %2;\nmbarrier.test_wait.parity.shared::cta.b64 q, [%3], %4;\nand.pred p, p, q;\nselp.u32 %0, 1, 0, p;\n}\n":"=r"(r):"r"(bar0),"r"(par0),"r"(bar1),"r"(par1):"memory");
  return r; }
__device__ __forceinline__ void tma_2d(uint32_t dst, const CUtensorMap* m, int c0, int c1, uint32_t bar){
  asm volatile("cp.async.bulk.tensor.2d.shared::cluster.global.mbarrier::complete_tx::bytes [%0], [%1, {%3, %4}], [%2];"::"r"(dst),"l"(m),"r"(bar),"r"(c0),"r"(c1):"memory"); }
__device__ __forceinline__ void tma_2d_h(uint32_t dst, const CUtensorMap* m, int c0, int c1, uint32_t bar, uint64_t pol){
  asm volatile("cp.async.bulk.tensor.2d.shared::cluster.global.mbarrier::complete_tx::bytes.L2::cache_hint [%0], [%1, {%3, %4}], [%2], %5;"::"r"(dst),"l"(m),"r"(bar),"r"(c0),"r"(c1),"l"(pol):"memory"); }
__device__ __forceinline__ void tma_2d_mc(uint32_t dst, const CUtensorMap* m, int c0, int c1, uint32_t bar){
  asm volatile("cp.async.bulk.tensor.2d.shared::cluster.global.mbarrier::complete_tx::bytes.multicast::cluster [%0], [%1, {%3, %4}], [%2], %5;"::"r"(dst),"l"(m),"r"(bar),"r"(c0),"r"(c1),"h"((uint16_t)3):"memory"); }
__device__ __forceinline__ void tma_2d_mc_h(uint32_t dst, const CUtensorMap* m, int c0, int c1, uint32_t bar, uint64_t pol){
  asm volatile("cp.async.bulk.tensor.2d.shared::cluster.global.mbarrier::complete_tx::bytes.multicast::cluster.L2::cache_hint [%0], [%1, {%3, %4}], [%2], %5, %6;"::"r"(dst),"l"(m),"r"(bar),"r"(c0),"r"(c1),"h"((uint16_t)3),"l"(pol):"memory"); }
__device__ __forceinline__ void tma_4d(uint32_t dst, const CUtensorMap* m, int c0, int c1, int c2, int c3, uint32_t bar){
  asm volatile("cp.async.bulk.tensor.4d.shared::cluster.global.mbarrier::complete_tx::bytes [%0], [%1, {%3, %4, %5, %6}], [%2];"::"r"(dst),"l"(m),"r"(bar),"r"(c0),"r"(c1),"r"(c2),"r"(c3):"memory"); }
__device__ __forceinline__ uint64_t policy_evict_first(){ uint64_t p; asm volatile("createpolicy.fractional.L2::evict_first.b64 %0, 1.0;":"=l"(p)); return p; }
__device__ __forceinline__ uint64_t policy_evict_normal(){ uint64_t p; asm("createpolicy.fractional.L2::evict_normal.b64 %0, 1.0;":"=l"(p)); return p; }
__device__ __forceinline__ void tma_3d_h(uint32_t dst, const CUtensorMap* m, int c0, int c1, int c2, uint32_t bar, uint64_t pol){
  asm volatile("cp.async.bulk.tensor.3d.shared::cluster.global.mbarrier::complete_tx::bytes.L2::cache_hint [%0], [%1, {%3, %4, %5}], [%2], %6;"::"r"(dst),"l"(m),"r"(bar),"r"(c0),"r"(c1),"r"(c2),"l"(pol):"memory"); }
__device__ __forceinline__ void tma_4d_h(uint32_t dst, const CUtensorMap* m, int c0, int c1, int c2, int c3, uint32_t bar, uint64_t pol){
  asm volatile("cp.async.bulk.tensor.4d.shared::cluster.global.mbarrier::complete_tx::bytes.L2::cache_hint [%0], [%1, {%3, %4, %5, %6}], [%2], %7;"::"r"(dst),"l"(m),"r"(bar),"r"(c0),"r"(c1),"r"(c2),"r"(c3),"l"(pol):"memory"); }
__device__ __forceinline__ void red_add_f32x4(float4* p, float x, float y, float z, float w){ asm volatile("red.relaxed.gpu.global.add.v4.f32 [%0], {%1,%2,%3,%4};"::"l"(p),"f"(x),"f"(y),"f"(z),"f"(w):"memory"); }
__device__ __forceinline__ void tma_5d_h(uint32_t dst, const CUtensorMap* m, int c0, int c1, uint32_t bar, uint64_t pol){
  asm volatile("cp.async.bulk.tensor.5d.shared::cluster.global.mbarrier::complete_tx::bytes.L2::cache_hint [%0], [%1, {%3, %4, 0, 0, 0}], [%2], %5;"::"r"(dst),"l"(m),"r"(bar),"r"(c0),"r"(c1),"l"(pol):"memory"); }
__device__ __forceinline__ void tma_store_2d(const CUtensorMap* m, int c0, int c1, uint32_t src, uint64_t pol){
  asm volatile("cp.async.bulk.tensor.2d.global.shared::cta.bulk_group.L2::cache_hint [%0, {%2, %3}], [%1], %4;"::"l"(m),"r"(src),"r"(c0),"r"(c1),"l"(pol):"memory"); }
__device__ __forceinline__ void bulk_commit(){ asm volatile("cp.async.bulk.commit_group;":::"memory"); }
__device__ __forceinline__ void bulk_wait_all(){ asm volatile("cp.async.bulk.wait_group 0;":::"memory"); }
__device__ __forceinline__ void fence_async_global(){ asm volatile("fence.proxy.async.global;":::"memory"); }
__device__ __forceinline__ bool elect_one(){ uint32_t p; asm volatile("{\n.reg .pred P;\nelect.sync _|P, 0xffffffff;\nselp.b32 %0, 1, 0, P;\n}\n":"=r"(p)); return p; }
__device__ __forceinline__ void bulk_prefetch(const void* p, uint32_t bytes){
  asm volatile("cp.async.bulk.prefetch.L2.global [%0], %1;"::"l"(p),"r"(bytes):"memory"); }
__device__ __forceinline__ void bulk_s2peer(uint32_t dst_cluster, uint32_t src, uint32_t bytes, uint32_t bar_cluster){
  asm volatile("cp.async.bulk.shared::cluster.shared::cta.mbarrier::complete_tx::bytes [%0], [%1], %2, [%3];"::"r"(dst_cluster),"r"(src),"r"(bytes),"r"(bar_cluster):"memory"); }
__device__ __forceinline__ void prefetch_map(const CUtensorMap* m){ asm volatile("prefetch.tensormap [%0];"::"l"(m):"memory"); }
__device__ __forceinline__ void fence_async_smem(){ asm volatile("fence.proxy.async.shared::cta;":::"memory"); }
__device__ __forceinline__ void fence_acquire_gpu(){ asm volatile("fence.acquire.gpu;":::"memory"); }
__device__ __forceinline__ void fence_gpu(){ asm volatile("fence.acq_rel.gpu;":::"memory"); }
__device__ __forceinline__ void wg_fence(){ asm volatile("wgmma.fence.sync.aligned;":::"memory"); }
__device__ __forceinline__ void wg_commit(){ asm volatile("wgmma.commit_group.sync.aligned;":::"memory"); }
template<int N> __device__ __forceinline__ void wg_wait(){ asm volatile("wgmma.wait_group.sync.aligned %0;"::"n"(N):"memory"); }
template<int N> __device__ __forceinline__ void fence_regs(float (&d)[N]){
  #pragma unroll
  for(int i=0;i<N;i++) asm volatile("":"+f"(d[i])::"memory"); }
__device__ __forceinline__ void bar_sync(int id, int n){ asm volatile("bar.sync %0, %1;"::"r"(id),"r"(n):"memory"); }
__device__ __forceinline__ void bar_arrive(int id, int n){ asm volatile("bar.arrive %0, %1;"::"r"(id),"r"(n):"memory"); }
__device__ __forceinline__ void cluster_arrive(){ asm volatile("barrier.cluster.arrive.relaxed.aligned;":::"memory"); }
__device__ __forceinline__ void cluster_wait(){ asm volatile("barrier.cluster.wait.aligned;":::"memory"); }
__host__ __device__ constexpr uint32_t dlo(uint32_t addr, uint32_t lbo){ return (addr >> 4) | ((lbo >> 4) << 16); }
__host__ __device__ constexpr uint32_t dhi(uint32_t sbo, uint32_t sw){ return (sbo >> 4) | (sw << 30); }
constexpr uint32_t H128 = dhi(1024, 1), H64 = dhi(512, 2), H0 = dhi(128, 0);
__device__ __forceinline__ uint32_t pack_bf16(float lo, float hi){ uint32_t r; asm("cvt.rn.bf16x2.f32 %0, %1, %2;":"=r"(r):"f"(hi),"f"(lo)); return r; }
__device__ __forceinline__ float bf_lo(uint32_t v){ return __uint_as_float(v<<16); }
__device__ __forceinline__ float bf_hi(uint32_t v){ return __uint_as_float(v&0xffff0000u); }
__device__ __forceinline__ float ex2(float x){ float r; asm("ex2.approx.ftz.f32 %0, %1;":"=f"(r):"f"(x)); return r; }
__device__ __forceinline__ float rcp(float x){ float r; asm("rcp.approx.ftz.f32 %0, %1;":"=f"(r):"f"(x)); return r; }
__device__ __forceinline__ void stsm4(uint32_t addr, uint32_t a, uint32_t b, uint32_t c, uint32_t d){
  asm volatile("stmatrix.sync.aligned.m8n8.x4.shared.b16 [%0], {%1,%2,%3,%4};"::"r"(addr),"r"(a),"r"(b),"r"(c),"r"(d)); }
__device__ __forceinline__ void stsm2(uint32_t addr, uint32_t a, uint32_t b){
  asm volatile("stmatrix.sync.aligned.m8n8.x2.shared.b16 [%0], {%1,%2};"::"r"(addr),"r"(a),"r"(b)); }
__device__ __forceinline__ void mma16816(float& d0, float& d1, float& d2, float& d3, uint32_t a0, uint32_t a1, uint32_t a2, uint32_t a3, uint32_t b0, uint32_t b1){
  asm volatile("mma.sync.aligned.m16n8k16.row.col.f32.bf16.bf16.f32 {%0,%1,%2,%3}, {%4,%5,%6,%7}, {%8,%9}, {%0,%1,%2,%3};"
               : "+f"(d0), "+f"(d1), "+f"(d2), "+f"(d3) : "r"(a0), "r"(a1), "r"(a2), "r"(a3), "r"(b0), "r"(b1)); }
__device__ __forceinline__ uint32_t transpose8(uint32_t a){ uint32_t r; asm volatile("movmatrix.sync.aligned.m8n8.trans.b16 %0, %1;":"=r"(r):"r"(a)); return r; }
__device__ __forceinline__ void ldsm4(uint32_t addr, uint32_t& a, uint32_t& b, uint32_t& c, uint32_t& d){
  asm volatile("ldmatrix.sync.aligned.m8n8.x4.shared.b16 {%0,%1,%2,%3}, [%4];":"=r"(a),"=r"(b),"=r"(c),"=r"(d):"r"(addr):"memory"); }
__device__ __forceinline__ void ldsm4t(uint32_t addr, uint32_t& a, uint32_t& b, uint32_t& c, uint32_t& d){
  asm volatile("ldmatrix.sync.aligned.m8n8.x4.trans.shared.b16 {%0,%1,%2,%3}, [%4];":"=r"(a),"=r"(b),"=r"(c),"=r"(d):"r"(addr):"memory"); }
__device__ __forceinline__ void sts32(uint32_t a, uint32_t v){ asm volatile("st.shared.b32 [%0], %1;"::"r"(a),"r"(v):"memory"); }
__device__ __forceinline__ void stsf(uint32_t a, float v){ asm volatile("st.shared.f32 [%0], %1;"::"r"(a),"f"(v):"memory"); }
__device__ __forceinline__ void sts64(uint32_t a, uint32_t x, uint32_t y){ asm volatile("st.shared.v2.b32 [%0], {%1,%2};"::"r"(a),"r"(x),"r"(y):"memory"); }
__device__ __forceinline__ void sts128(uint32_t a, uint32_t x, uint32_t y, uint32_t z, uint32_t w){ asm volatile("st.shared.v4.b32 [%0], {%1,%2,%3,%4};"::"r"(a),"r"(x),"r"(y),"r"(z),"r"(w):"memory"); }
__device__ __forceinline__ float ldsf(uint32_t a){ float v; asm volatile("ld.shared.f32 %0, [%1];":"=f"(v):"r"(a):"memory"); return v; }
__device__ __forceinline__ float2 lds64f(uint32_t a){ float2 v; asm volatile("ld.shared.v2.f32 {%0,%1}, [%2];":"=f"(v.x),"=f"(v.y):"r"(a):"memory"); return v; }
__device__ __forceinline__ uint4 lds128(uint32_t a){ uint4 v; asm volatile("ld.shared.v4.u32 {%0,%1,%2,%3}, [%4];":"=r"(v.x),"=r"(v.y),"=r"(v.z),"=r"(v.w):"r"(a):"memory"); return v; }
__device__ __forceinline__ uint4 ld128_keep(const void* p){ uint4 v; asm volatile("ld.global.v4.u32 {%0,%1,%2,%3}, [%4];":"=r"(v.x),"=r"(v.y),"=r"(v.z),"=r"(v.w):"l"(p):"memory"); return v; }
__device__ __forceinline__ uint4 ld128_rlx(const void* p){ uint4 v; asm volatile("ld.relaxed.gpu.global.v4.u32 {%0,%1,%2,%3}, [%4];":"=r"(v.x),"=r"(v.y),"=r"(v.z),"=r"(v.w):"l"(p):"memory"); return v; }
__device__ __forceinline__ uint32_t ld32_rlx(const void* p){ uint32_t v; asm volatile("ld.relaxed.gpu.global.u32 %0, [%1];":"=r"(v):"l"(p):"memory"); return v; }
__device__ __forceinline__ void st128_rlx(void* p, uint32_t x, uint32_t y, uint32_t z, uint32_t w){ asm volatile("st.relaxed.gpu.global.v4.u32 [%0], {%1,%2,%3,%4};"::"l"(p),"r"(x),"r"(y),"r"(z),"r"(w):"memory"); }
__device__ __forceinline__ void st64_rlx(void* p, uint32_t x, uint32_t y){ asm volatile("st.relaxed.gpu.global.v2.u32 [%0], {%1,%2};"::"l"(p),"r"(x),"r"(y):"memory"); }
__device__ __forceinline__ void st32_rlx(void* p, uint32_t x){ asm volatile("st.relaxed.gpu.global.u32 [%0], %1;"::"l"(p),"r"(x):"memory"); }
__device__ __forceinline__ void wait_until(uint32_t t){ while ((int32_t)((uint32_t)clock() - t) < 0) __nanosleep(32); }
__device__ __forceinline__ void flags_wait(uint32_t& missing, const uint32_t* p, uint32_t need){
  asm volatile("{\n.reg .pred p;\n.reg .u32 c, v;\nmov.u32 c, 0;\nLW:\nand.b32 v, %0, %2;\nsetp.eq.u32 p, v, 0;\n@p bra.uni LD;\nld.relaxed.gpu.global.u32 v, [%1];\nsetp.eq.u32 p, v, 0;\n"
               "vote.sync.ballot.b32 %0, p, 0xffffffff;\nadd.u32 c, c, 1;\nsetp.lt.u32 p, c, 4000000;\n@p bra.uni LW;\nLD:\n}\n":"+r"(missing):"l"(p),"r"(need):"memory"); }
__device__ __forceinline__ uint32_t tagw(float x, uint32_t t){ return (__float_as_uint(x) & ~3u) | t; }
__device__ __forceinline__ float untag(uint32_t w){ return __uint_as_float(w & ~3u); }

template<int TA, int TB, uint32_t HA, uint32_t HB> __device__ __forceinline__ void wgmma_ss_n128(float (&d)[64], uint32_t da, uint32_t db, int scale_d){
  asm volatile("{\n.reg .pred p;\n.reg .b64 a, b;\nsetp.ne.b32 p, %70, 0;\nmov.b64 a, {%64, %68};\nmov.b64 b, {%65, %69};\n"
  "wgmma.mma_async.sync.aligned.m64n128k16.f32.bf16.bf16 {%0, %1, %2, %3, %4, %5, %6, %7, %8, %9, %10, %11, %12, %13, %14, %15, %16, %17, %18, %19, %20, %21, %22, %23, %24, %25, %26, %27, %28, %29, %30, %31, %32, %33, %34, %35, %36, %37, %38, %39, %40, %41, %42, %43, %44, %45, %46, %47, %48, %49, %50, %51, %52, %53, %54, %55, %56, %57, %58, %59, %60, %61, %62, %63}, a, b, p, 1, 1, %66, %67;\n}\n"
  : "+f"(d[0]), "+f"(d[1]), "+f"(d[2]), "+f"(d[3]), "+f"(d[4]), "+f"(d[5]), "+f"(d[6]), "+f"(d[7]), "+f"(d[8]), "+f"(d[9]), "+f"(d[10]), "+f"(d[11]), "+f"(d[12]), "+f"(d[13]), "+f"(d[14]), "+f"(d[15]), "+f"(d[16]), "+f"(d[17]), "+f"(d[18]), "+f"(d[19]), "+f"(d[20]), "+f"(d[21]), "+f"(d[22]), "+f"(d[23]), "+f"(d[24]), "+f"(d[25]), "+f"(d[26]), "+f"(d[27]), "+f"(d[28]), "+f"(d[29]), "+f"(d[30]), "+f"(d[31]), "+f"(d[32]), "+f"(d[33]), "+f"(d[34]), "+f"(d[35]), "+f"(d[36]), "+f"(d[37]), "+f"(d[38]), "+f"(d[39]), "+f"(d[40]), "+f"(d[41]), "+f"(d[42]), "+f"(d[43]), "+f"(d[44]), "+f"(d[45]), "+f"(d[46]), "+f"(d[47]), "+f"(d[48]), "+f"(d[49]), "+f"(d[50]), "+f"(d[51]), "+f"(d[52]), "+f"(d[53]), "+f"(d[54]), "+f"(d[55]), "+f"(d[56]), "+f"(d[57]), "+f"(d[58]), "+f"(d[59]), "+f"(d[60]), "+f"(d[61]), "+f"(d[62]), "+f"(d[63])
  : "r"(da), "r"(db), "n"(TA), "n"(TB), "n"(HA), "n"(HB), "r"(scale_d));
}
template<int TA, int TB, uint32_t HA, uint32_t HB> __device__ __forceinline__ void wgmma_sa_n128(float (&d)[64], uint32_t da, uint32_t db){
  asm volatile("{\n.reg .pred p;\n.reg .b64 a, b;\nsetp.ne.b32 p, 1, 0;\nmov.b64 a, {%64, %68};\nmov.b64 b, {%65, %69};\n"
  "wgmma.mma_async.sync.aligned.m64n128k16.f32.bf16.bf16 {%0, %1, %2, %3, %4, %5, %6, %7, %8, %9, %10, %11, %12, %13, %14, %15, %16, %17, %18, %19, %20, %21, %22, %23, %24, %25, %26, %27, %28, %29, %30, %31, %32, %33, %34, %35, %36, %37, %38, %39, %40, %41, %42, %43, %44, %45, %46, %47, %48, %49, %50, %51, %52, %53, %54, %55, %56, %57, %58, %59, %60, %61, %62, %63}, a, b, p, 1, 1, %66, %67;\n}\n"
  : "+f"(d[0]), "+f"(d[1]), "+f"(d[2]), "+f"(d[3]), "+f"(d[4]), "+f"(d[5]), "+f"(d[6]), "+f"(d[7]), "+f"(d[8]), "+f"(d[9]), "+f"(d[10]), "+f"(d[11]), "+f"(d[12]), "+f"(d[13]), "+f"(d[14]), "+f"(d[15]), "+f"(d[16]), "+f"(d[17]), "+f"(d[18]), "+f"(d[19]), "+f"(d[20]), "+f"(d[21]), "+f"(d[22]), "+f"(d[23]), "+f"(d[24]), "+f"(d[25]), "+f"(d[26]), "+f"(d[27]), "+f"(d[28]), "+f"(d[29]), "+f"(d[30]), "+f"(d[31]), "+f"(d[32]), "+f"(d[33]), "+f"(d[34]), "+f"(d[35]), "+f"(d[36]), "+f"(d[37]), "+f"(d[38]), "+f"(d[39]), "+f"(d[40]), "+f"(d[41]), "+f"(d[42]), "+f"(d[43]), "+f"(d[44]), "+f"(d[45]), "+f"(d[46]), "+f"(d[47]), "+f"(d[48]), "+f"(d[49]), "+f"(d[50]), "+f"(d[51]), "+f"(d[52]), "+f"(d[53]), "+f"(d[54]), "+f"(d[55]), "+f"(d[56]), "+f"(d[57]), "+f"(d[58]), "+f"(d[59]), "+f"(d[60]), "+f"(d[61]), "+f"(d[62]), "+f"(d[63])
  : "r"(da), "r"(db), "n"(TA), "n"(TB), "n"(HA), "n"(HB));
}
template<int TA, int TB, uint32_t HA, uint32_t HB> __device__ __forceinline__ void wgmma_sa_n40(float (&d)[20], uint32_t da, uint32_t db){
  asm volatile("{\n.reg .pred p;\n.reg .b64 a, b;\nsetp.ne.b32 p, 1, 0;\nmov.b64 a, {%20, %24};\nmov.b64 b, {%21, %25};\n"
  "wgmma.mma_async.sync.aligned.m64n40k16.f32.bf16.bf16 {%0, %1, %2, %3, %4, %5, %6, %7, %8, %9, %10, %11, %12, %13, %14, %15, %16, %17, %18, %19}, a, b, p, 1, 1, %22, %23;\n}\n"
  : "+f"(d[0]), "+f"(d[1]), "+f"(d[2]), "+f"(d[3]), "+f"(d[4]), "+f"(d[5]), "+f"(d[6]), "+f"(d[7]), "+f"(d[8]), "+f"(d[9]), "+f"(d[10]), "+f"(d[11]), "+f"(d[12]), "+f"(d[13]), "+f"(d[14]), "+f"(d[15]), "+f"(d[16]), "+f"(d[17]), "+f"(d[18]), "+f"(d[19])
  : "r"(da), "r"(db), "n"(TA), "n"(TB), "n"(HA), "n"(HB));
}
template<int TA, int TB, uint32_t HA, uint32_t HB> __device__ __forceinline__ void wgmma_sz_n40(float (&d)[20], uint32_t da, uint32_t db){
  asm volatile("{\n.reg .pred p;\n.reg .b64 a, b;\nsetp.ne.b32 p, 0, 0;\nmov.b64 a, {%20, %24};\nmov.b64 b, {%21, %25};\n"
  "wgmma.mma_async.sync.aligned.m64n40k16.f32.bf16.bf16 {%0, %1, %2, %3, %4, %5, %6, %7, %8, %9, %10, %11, %12, %13, %14, %15, %16, %17, %18, %19}, a, b, p, 1, 1, %22, %23;\n}\n"
  : "=f"(d[0]), "=f"(d[1]), "=f"(d[2]), "=f"(d[3]), "=f"(d[4]), "=f"(d[5]), "=f"(d[6]), "=f"(d[7]), "=f"(d[8]), "=f"(d[9]), "=f"(d[10]), "=f"(d[11]), "=f"(d[12]), "=f"(d[13]), "=f"(d[14]), "=f"(d[15]), "=f"(d[16]), "=f"(d[17]), "=f"(d[18]), "=f"(d[19])
  : "r"(da), "r"(db), "n"(TA), "n"(TB), "n"(HA), "n"(HB));
}
template<int TA, int TB, uint32_t HA, uint32_t HB> __device__ __forceinline__ void wgmma_sa_n32(float (&d)[16], uint32_t da, uint32_t db){
  asm volatile("{\n.reg .pred p;\n.reg .b64 a, b;\nsetp.ne.b32 p, 1, 0;\nmov.b64 a, {%16, %20};\nmov.b64 b, {%17, %21};\n"
  "wgmma.mma_async.sync.aligned.m64n32k16.f32.bf16.bf16 {%0, %1, %2, %3, %4, %5, %6, %7, %8, %9, %10, %11, %12, %13, %14, %15}, a, b, p, 1, 1, %18, %19;\n}\n"
  : "+f"(d[0]), "+f"(d[1]), "+f"(d[2]), "+f"(d[3]), "+f"(d[4]), "+f"(d[5]), "+f"(d[6]), "+f"(d[7]), "+f"(d[8]), "+f"(d[9]), "+f"(d[10]), "+f"(d[11]), "+f"(d[12]), "+f"(d[13]), "+f"(d[14]), "+f"(d[15])
  : "r"(da), "r"(db), "n"(TA), "n"(TB), "n"(HA), "n"(HB));
}
template<int TA, int TB, uint32_t HA, uint32_t HB> __device__ __forceinline__ void wgmma_ss_n32(float (&d)[16], uint32_t da, uint32_t db, int scale_d){
  asm volatile("{\n.reg .pred p;\n.reg .b64 a, b;\nsetp.ne.b32 p, %22, 0;\nmov.b64 a, {%16, %20};\nmov.b64 b, {%17, %21};\n"
  "wgmma.mma_async.sync.aligned.m64n32k16.f32.bf16.bf16 {%0, %1, %2, %3, %4, %5, %6, %7, %8, %9, %10, %11, %12, %13, %14, %15}, a, b, p, 1, 1, %18, %19;\n}\n"
  : "+f"(d[0]), "+f"(d[1]), "+f"(d[2]), "+f"(d[3]), "+f"(d[4]), "+f"(d[5]), "+f"(d[6]), "+f"(d[7]), "+f"(d[8]), "+f"(d[9]), "+f"(d[10]), "+f"(d[11]), "+f"(d[12]), "+f"(d[13]), "+f"(d[14]), "+f"(d[15])
  : "r"(da), "r"(db), "n"(TA), "n"(TB), "n"(HA), "n"(HB), "r"(scale_d));
}
template<int TB, uint32_t HB> __device__ __forceinline__ void wgmma_ra_n32(float (&d)[16], uint32_t a0, uint32_t a1, uint32_t a2, uint32_t a3, uint32_t db){
  asm volatile("{\n.reg .pred p;\n.reg .b64 a, b;\nsetp.ne.b32 p, 1, 0;\nmov.b64 b, {%20, %22};\n"
  "wgmma.mma_async.sync.aligned.m64n32k16.f32.bf16.bf16 {%0, %1, %2, %3, %4, %5, %6, %7, %8, %9, %10, %11, %12, %13, %14, %15}, {%16,%17,%18,%19}, b, p, 1, 1, %21;\n}\n"
  : "+f"(d[0]), "+f"(d[1]), "+f"(d[2]), "+f"(d[3]), "+f"(d[4]), "+f"(d[5]), "+f"(d[6]), "+f"(d[7]), "+f"(d[8]), "+f"(d[9]), "+f"(d[10]), "+f"(d[11]), "+f"(d[12]), "+f"(d[13]), "+f"(d[14]), "+f"(d[15])
  : "r"(a0), "r"(a1), "r"(a2), "r"(a3), "r"(db), "n"(TB), "n"(HB));
}
template<int TB, uint32_t HB> __device__ __forceinline__ void wgmma_rs_n32(float (&d)[16], uint32_t a0, uint32_t a1, uint32_t a2, uint32_t a3, uint32_t db, int scale_d){
  asm volatile("{\n.reg .pred p;\n.reg .b64 a, b;\nsetp.ne.b32 p, %23, 0;\nmov.b64 b, {%20, %22};\n"
  "wgmma.mma_async.sync.aligned.m64n32k16.f32.bf16.bf16 {%0, %1, %2, %3, %4, %5, %6, %7, %8, %9, %10, %11, %12, %13, %14, %15}, {%16,%17,%18,%19}, b, p, 1, 1, %21;\n}\n"
  : "+f"(d[0]), "+f"(d[1]), "+f"(d[2]), "+f"(d[3]), "+f"(d[4]), "+f"(d[5]), "+f"(d[6]), "+f"(d[7]), "+f"(d[8]), "+f"(d[9]), "+f"(d[10]), "+f"(d[11]), "+f"(d[12]), "+f"(d[13]), "+f"(d[14]), "+f"(d[15])
  : "r"(a0), "r"(a1), "r"(a2), "r"(a3), "r"(db), "n"(TB), "n"(HB), "r"(scale_d));
}
template<int TB, uint32_t HB> __device__ __forceinline__ void wgmma_ra_n40(float (&d)[20], uint32_t a0, uint32_t a1, uint32_t a2, uint32_t a3, uint32_t db){
  asm volatile("{\n.reg .pred p;\n.reg .b64 a, b;\nsetp.ne.b32 p, 1, 0;\nmov.b64 b, {%24, %26};\n"
  "wgmma.mma_async.sync.aligned.m64n40k16.f32.bf16.bf16 {%0, %1, %2, %3, %4, %5, %6, %7, %8, %9, %10, %11, %12, %13, %14, %15, %16, %17, %18, %19}, {%20,%21,%22,%23}, b, p, 1, 1, %25;\n}\n"
  : "+f"(d[0]), "+f"(d[1]), "+f"(d[2]), "+f"(d[3]), "+f"(d[4]), "+f"(d[5]), "+f"(d[6]), "+f"(d[7]), "+f"(d[8]), "+f"(d[9]), "+f"(d[10]), "+f"(d[11]), "+f"(d[12]), "+f"(d[13]), "+f"(d[14]), "+f"(d[15]), "+f"(d[16]), "+f"(d[17]), "+f"(d[18]), "+f"(d[19])
  : "r"(a0), "r"(a1), "r"(a2), "r"(a3), "r"(db), "n"(TB), "n"(HB));
}
template<int TB, uint32_t HB> __device__ __forceinline__ void wgmma_rz_n40(float (&d)[20], uint32_t a0, uint32_t a1, uint32_t a2, uint32_t a3, uint32_t db){
  asm volatile("{\n.reg .pred p;\n.reg .b64 a, b;\nsetp.ne.b32 p, 0, 0;\nmov.b64 b, {%24, %26};\n"
  "wgmma.mma_async.sync.aligned.m64n40k16.f32.bf16.bf16 {%0, %1, %2, %3, %4, %5, %6, %7, %8, %9, %10, %11, %12, %13, %14, %15, %16, %17, %18, %19}, {%20,%21,%22,%23}, b, p, 1, 1, %25;\n}\n"
  : "=f"(d[0]), "=f"(d[1]), "=f"(d[2]), "=f"(d[3]), "=f"(d[4]), "=f"(d[5]), "=f"(d[6]), "=f"(d[7]), "=f"(d[8]), "=f"(d[9]), "=f"(d[10]), "=f"(d[11]), "=f"(d[12]), "=f"(d[13]), "=f"(d[14]), "=f"(d[15]), "=f"(d[16]), "=f"(d[17]), "=f"(d[18]), "=f"(d[19])
  : "r"(a0), "r"(a1), "r"(a2), "r"(a3), "r"(db), "n"(TB), "n"(HB));
}
template<int TB, uint32_t HB> __device__ __forceinline__ void wgmma_rz_n8(float (&d)[4], uint32_t a0, uint32_t a1, uint32_t a2, uint32_t a3, uint32_t db){
  asm volatile("{\n.reg .pred p;\n.reg .b64 a, b;\nsetp.ne.b32 p, 0, 0;\nmov.b64 b, {%8, %10};\n"
  "wgmma.mma_async.sync.aligned.m64n8k16.f32.bf16.bf16 {%0, %1, %2, %3}, {%4,%5,%6,%7}, b, p, 1, 1, %9;\n}\n"
  : "=f"(d[0]), "=f"(d[1]), "=f"(d[2]), "=f"(d[3])
  : "r"(a0), "r"(a1), "r"(a2), "r"(a3), "r"(db), "n"(TB), "n"(HB));
}

constexpr int SEQ = 2048, DM = 1024, FF = 3584;
constexpr float LOG2E = 1.4426950408889634f;
constexpr uint32_t POLL_LIMIT = 1u << 22;
constexpr int QW = 0;
constexpr int LAG = 2;
constexpr int ML = 2;
constexpr int REL = 6;
constexpr int SKM = 0x154;
constexpr int RS_N = 26;
constexpr int RS_D1 = 350;
constexpr int RS_D2 = 300;
constexpr int PF_T0 = 4200;
constexpr int PF_DT = 855;
constexpr int FF_N = 4;
constexpr int FF_DT = 650;
constexpr int FF_D2 = 350;
constexpr uint64_t FF_ORD = 0x76543210ba98ull;
constexpr int G2P = 4;
constexpr int XC = 0;
constexpr int FI = 0;
constexpr int OUT_D = 400;
constexpr int NFFN = 112;

constexpr uint32_t SB0 = 1024;
constexpr uint32_t KV_STAGE = 49152, R5 = 32768;
constexpr uint32_t OFF_X = 163840, OFF_S = 196608, OFF_WPHI = OFF_S + 20480, OFF_M = 229376, SMEM_BYTES = 232448;
constexpr uint32_t OFF_RS256 = 212992, OFF_ONES = OFF_RS256 + 1024, OFF_WPHIK1 = OFF_ONES + 1024, OFF_KVZ = OFF_S;
constexpr uint32_t OFF_WPHIK = OFF_S, OFF_BXK = OFF_S + 2048, OFF_AXK = OFF_S + 4096, OFF_G = OFF_S + 8192;
constexpr uint32_t OFF_AXQ = OFF_WPHI, OFF_BXQ = OFF_WPHI + 2048, OFF_WPHIQ = OFF_WPHI + 4096;
constexpr uint32_t B_FULLKV = OFF_M  , B_EMPTYKV = OFF_M + 32  ;
constexpr uint32_t B_EMPTY5 = OFF_M + 64  , B_UO = B_EMPTY5 + 48  , B_RC = B_UO + 32  ;
constexpr uint32_t B_OUT = B_RC + 16  , B_SD = B_OUT + 16, B_AUX = B_SD + 8, B_AUXQ = B_AUX + 8, B_RX = B_AUXQ + 8;
constexpr uint32_t B_FULL5 = B_RX + 8  , B_F = B_FULL5 + 40  , B_WD = B_F + 64  ;
constexpr uint32_t B_WC = B_WD + 32  , B_DR = B_WC + 32  , B_W = B_DR + 24, B_OS = B_W + 8, B_R = B_W + 16, B_KD = B_W + 24, B_T = B_W + 32, B_G = B_W + 40, B_END = B_W + 48;
constexpr int NB3 = ((B_END - OFF_M) / 8 + 1) / 3;
constexpr uint32_t B_S0 = OFF_M + 8 + 24 * NB3;
static_assert(B_S0 >= B_END && B_S0 < OFF_M + 576, "barriers");
__host__ __device__ constexpr uint32_t bar_count(int i) {
  const uint32_t b = OFF_M + 8 * i;
  return b < B_EMPTYKV ? 1 : b < B_EMPTY5 ? 12 : b < B_SD ? 4 : b < B_RX || b == B_W ? 2 : b == B_RX ? 8 : 1;
}
constexpr uint32_t B_GB = OFF_M + 2560  , B_GA = B_GB + 128  ;
constexpr uint32_t OFF_BEST = OFF_M + 576, OFF_SUMWR = OFF_M + 608, OFF_EP = OFF_M + 624, OFF_KEY = OFF_M + 628;
constexpr uint32_t OFF_RSQ = OFF_M + 640, OFF_SEL = OFF_M + 1648, OFF_T = OFF_M + 1792, OFF_WR = OFF_M + 2048;
constexpr uint32_t OFF_XSEL = 2 * R5, OFF_GU = OFF_XSEL + 4096, OFF_OUT = 3 * R5;
constexpr uint64_t FF_SLOT = 0xdcdc3210dcbaull;
constexpr int KVP = 6 * 128;
__device__ __forceinline__ uint32_t kv_count(uint32_t launch, uint32_t n) { return 0x42800000u + (((launch & 3) * 16 + n) << 17); }

enum { NB_G2E = 1, NB_XS = 2, NB_WG01 = 3, NB_ACT = 4, NB_Q0 = 5  , NB_ST = 14, NB_LAG = 8, NB_DN = 9, NB_ZERO = 10, NB_PUB = 11, NB_TOK = 10  , NB_L0 = 12  , NB_WG2 = 7, NB_QGO = 15 };

struct Scratch {
  bf16     o[SEQ * DM];
  float4   rstat[SEQ];
  uint32_t key[16 * 128];
  uint32_t cand[16 * 512];
  float4   yacc[4 * 3 * 128];
  float4   kvacc[32 * KVP];
  uint2    stats[SEQ];
  uint32_t cskv[2 * DM];
  uint32_t csq[4 * DM];
  uint32_t oset[128 * 16];
  uint32_t oflag[16 * 6 * 32 * 8];
  uint32_t epoch;
};
__device__ __align__(1024) Scratch g_scr;

struct Params {
  const bf16 *x, *wqkv, *wo_p, *wr;
  bf16* out_p;
  Scratch* g;
  uint32_t zero;
  CUtensorMap x128, x64, wkv, wq, wo[2], wd, wg, wu, phi, tg, tu, td, xs, ws, qs, out, o;
};

constexpr float EXP_LIM = 1.1529215e18f, ARG_LIM2 = 3600.f;
__device__ __forceinline__ void dual_exp2(const float (&p)[16], uint32_t (&ep)[8], uint32_t (&em)[8]) {
  #pragma unroll
  for (int k = 0; k < 8; k++) {
    const float a = ex2(p[2*k]), b = ex2(p[2*k+1]);
    const float r = rcp(a * b);
    ep[k] = pack_bf16(a, b); em[k] = pack_bf16(r * b, r * a);
  }
}
template<bool SUMS> __device__ __forceinline__ void dual_exp2_shifted(float (&p)[2][16], uint32_t (&ph)[4][8], float (&s)[2][4]) {
  #pragma unroll 1
  for (int r = 0; r < 4; r++) {
    float m[2] = {p[0][0], p[0][2]}, a[2] = {0.f, 0.f};
    #pragma unroll
    for (int i = 0; i < 16; i++) m[(i >> 1) & 1] = fmaxf(m[(i >> 1) & 1], p[0][i]);
    #pragma unroll
    for (int o = 1; o < 4; o <<= 1) { m[0] = fmaxf(m[0], __shfl_xor_sync(~0u, m[0], o)); m[1] = fmaxf(m[1], __shfl_xor_sync(~0u, m[1], o)); }
    #pragma unroll
    for (int k = 0; k < 8; k++) {
      const float e0 = ex2(p[0][2*k] - m[k & 1]), e1 = ex2(p[0][2*k+1] - m[k & 1]);
      ph[0][k] = ph[2][k]; ph[2][k] = ph[1][k]; ph[1][k] = ph[3][k]; ph[3][k] = pack_bf16(e0, e1);
      a[k & 1] += e0 + e1;
    }
    #pragma unroll
    for (int i = 0; i < 16; i++) { const float x = p[0][i]; p[0][i] = p[1][i]; p[1][i] = -x; }
    if (SUMS) {
      #pragma unroll
      for (int i = 0; i < 2; i++) {
        a[i] += __shfl_xor_sync(~0u, a[i], 1);
        s[0][2*i] = s[1][2*i]; s[1][2*i] = s[0][2*i+1]; s[0][2*i+1] = s[1][2*i+1]; s[1][2*i+1] = a[i] + __shfl_xor_sync(~0u, a[i], 2);
      }
    }
  }
}
__device__ __forceinline__ uint32_t add_bf16x2(uint32_t a, uint32_t b) { uint32_t r; asm("add.rn.bf16x2 %0, %1, %2;" : "=r"(r) : "r"(a), "r"(b)); return r; }
__device__ __forceinline__ void row_sums(float (&s)[2][4], const uint32_t (&ph)[4][8], uint32_t sel) {
  uint32_t u[8];
  #pragma unroll
  for (int i = 0; i < 8; i++) { const uint32_t* f = &ph[i >> 1][i & 1]; u[i] = add_bf16x2(add_bf16x2(f[0], f[2]), add_bf16x2(f[4], f[6])); }
  wg_fence();
  wgmma_rz_n8<0, H0>(s[0], u[0], u[1], u[2], u[3], sel);
  wgmma_rz_n8<0, H0>(s[1], u[4], u[5], u[6], u[7], sel);
  wg_commit();
}
__device__ __forceinline__ uint32_t mul_bf16x2(uint32_t a, uint32_t b) { uint32_t r; asm("mul.rn.bf16x2 %0, %1, %2;" : "=r"(r) : "r"(a), "r"(b)); return r; }
__device__ __forceinline__ void normalize(uint32_t (&ph)[4][8], const float (&s)[2][4]) {
  #pragma unroll
  for (int i = 0; i < 4; i++) {
    const float i0 = rcp(s[i >> 1][i & 1]), i1 = rcp(s[i >> 1][2 + (i & 1)]);
    const uint32_t n0 = pack_bf16(i0, i0), n1 = pack_bf16(i1, i1);
    #pragma unroll
    for (int k = 0; k < 4; k++) { ph[i][2*k] = mul_bf16x2(ph[i][2*k], n0); ph[i][2*k+1] = mul_bf16x2(ph[i][2*k+1], n1); }
  }
}
__device__ __forceinline__ void split_bf16(float a, float b, uint32_t& hi, uint32_t& lo) { hi = pack_bf16(a, b); lo = pack_bf16(a - bf_lo(hi), b - bf_hi(hi)); }
__device__ __forceinline__ void put_colsums(uint32_t base, int lane, float a, float b, float c, float d) {
  uint32_t h0, l0, h1, l1;
  split_bf16(a, b, h0, l0); split_bf16(c, d, h1, l1);
  const uint32_t ad = base + (lane >> 1) * 128 + (lane & 1) * 8;
  sts64(ad, h0, h1); sts64(ad + 16, l0, l1); sts64(ad + 32, h0, h1); sts64(ad + 48, l0, l1);
  sts128(base + (lane >> 1) * 128 + 64 + (lane & 1) * 32, 0, 0, 0, 0); sts128(base + (lane >> 1) * 128 + 80 + (lane & 1) * 32, 0, 0, 0, 0);
}
__device__ __forceinline__ float reduce8(const float (&v)[8], int lane) {
  const bool b4 = lane & 16, b3 = lane & 8, b2 = lane & 4;
  float a[4], b[2];
  #pragma unroll
  for (int i = 0; i < 4; i++) a[i] = (b4 ? v[4 + i] : v[i]) + __shfl_xor_sync(~0u, b4 ? v[i] : v[4 + i], 16);
  #pragma unroll
  for (int i = 0; i < 2; i++) b[i] = (b3 ? a[2 + i] : a[i]) + __shfl_xor_sync(~0u, b3 ? a[i] : a[2 + i], 8);
  return (b2 ? b[1] : b[0]) + __shfl_xor_sync(~0u, b2 ? b[0] : b[1], 4);
}
__device__ __forceinline__ bool tag_bad(uint4 v, uint32_t tg) { return (((v.x ^ tg) | (v.y ^ tg) | (v.z ^ tg) | (v.w ^ tg)) & 3) != 0; }


__global__ void __launch_bounds__(512, 1) __cluster_dims__(2, 1, 1) fused_kernel(const __grid_constant__ Params P) {
  extern __shared__ __align__(1024) uint8_t smem_raw[];
  const uint32_t sb = smem_u32(smem_raw);
  const int tid = threadIdx.x, lane = tid & 31;
  {
    const int n = 16 * blockIdx.x + (lane & 15);
    const bf16* p = (lane < 16 ? P.x : P.wqkv) + (lane < 16 ? n * DM : (n >> 5) * (3 * DM) + DM + 64 * (n & 31));
    asm volatile("{\n.reg .pred p;\nsetp.lt.u32 p, %1, 32;\n@p prefetch.global.L2 [%0];\n}\n" :: "l"(p), "r"(tid));
  }
  const int cp = blockIdx.x >> 1, rank = blockIdx.x & 1;
  const int cr = cp < 4 ? 32 + 8 * cp : cp - 4 + max((cp * 37 - 1076) >> 8, 0);
  const int c = (cr & 62) + 64 * (cr & 1) + rank;
  const int m256 = c >> 4, nkv = c & 15, m128 = c >> 3, j = c & 7;
  if ((tid >> 7) == 2 && elect_one()) {
    if (tid >= 288) {
      const int w = (tid >> 5) - 9;
      #pragma unroll
      for (int i = 0; i < NB3; i++) mbar_init(sb + B_FULLKV + 8 + 8 * NB3 * w + 8 * i, w == 0 ? bar_count(1 + i) : w == 1 ? bar_count(1 + NB3 + i) : bar_count(1 + 2 * NB3 + i));
    } else {
      prefetch_map(&P.wkv); prefetch_map(&P.x128);
      mbar_init(sb + B_S0, 1); mbar_init(sb + B_FULLKV, 1);
      mbar_expect_tx(sb + B_S0, 32768);
      tma_4d(sb + 32768, &P.wkv, 0, 0, nkv, 1, sb + B_S0);
      tma_2d(sb, &P.x128, 0, 256 * m256, sb + B_S0);
      mbar_expect_tx(sb + B_FULLKV, 16384);
      tma_2d(sb + 16384, &P.x128, 0, 256 * m256 + 128, sb + B_FULLKV);
    }
    asm volatile("fence.mbarrier_init.release.cluster;" ::: "memory");
  }
  const int warp = __shfl_sync(~0u, tid >> 5, 0), wg = warp >> 2, wp = warp & 3;
  const int f = 16 * ((cr + 7) & 7) + 2 * (cr >> 3) + rank;
  const int ha = 4 * (nkv >> 1) + (nkv & 1);
  Scratch* const G = P.g;
  if ((sb & 0x3ffff) != SB0) asm volatile("trap;");
  __syncthreads();
  cluster_arrive();
  if (warp == 8 && elect_one()) {
    mbar_expect_tx(sb + B_FULLKV + 8, KV_STAGE);
    tma_4d(sb + KV_STAGE + 32768, &P.wkv, 0, 64, nkv, 1, sb + B_FULLKV + 8);
    tma_2d(sb + KV_STAGE, &P.x128, 64, 256 * m256, sb + B_FULLKV + 8);
    tma_2d(sb + KV_STAGE + 16384, &P.x128, 64, 256 * m256 + 128, sb + B_FULLKV + 8);
  }
  if (wg == 3) {
    asm volatile("setmaxnreg.dec.sync.aligned.u32 32;");
    cluster_wait();
    const bool el = elect_one();
    const uint64_t ef = policy_evict_first(), en = policy_evict_normal();
    auto fetch_o = [&](const int t0, const int sh) {
      uint32_t missing = ~0u;
      const uint32_t* hint = &G->oflag[((m128 * 6 + ((t0 + 1) & 6) + rank) * 32 + ((4 * (j & 6) + lane) & 31)) * 8];
      #pragma unroll 1
      for (int i = 2 - 2 * sh; i < 8; i += 1 + sh) {
        const int blk = sh ? 6 + 2 * t0 + (i >> 1) : i, wrap = sh ? 1 + (blk >= 11) : blk >= 5, s = blk + 1 - 6 * wrap;
        flags_wait(missing, hint, (15u + 240u * sh) << (4 * i));
        if (sh || blk > 5) mbar_wait(sb + B_EMPTY5 + 8 * s, wrap & 1);
        if (el) {
          tma_2d_mc_h(sb + s * R5 + rank * 8192, &P.o, 0, (m128 * 16 + t0 + 2 * (((j & 6) + i) & 7)) * 32 + 16 * rank, sb + B_GA + 16 * blk + 8 * rank, ef);
        }
      }
    };
    if (wp == 0) {
      {
        wait_until((uint32_t)clock() + 300);
        #pragma unroll 1
        for (int kb = 2; kb < 16; kb++) {
          const uint32_t st = sb + (kb & 3) * KV_STAGE, fb = sb + B_FULLKV + 8 * (kb & 3);
          mbar_wait(fb + (B_EMPTYKV - B_FULLKV), ~(kb >> 2) & 1);
          if (el) {
            mbar_expect_tx(fb, KV_STAGE);
            tma_2d_mc(st + rank * 16384, &P.x128, 64 * kb, 256 * m256 + 128 * rank, fb);
            tma_4d_h(st + 32768, &P.wkv, 0, 64 * kb, nkv, 1, fb, ef);
          }
        }
        uint64_t ord = 0xf3120edcba987654ull;
        uint32_t so = 0, par = 1;
        #pragma unroll 1
        for (int i = 0; i < 16; i++) {
          const uint32_t st = sb + so * 4096, fb = sb + B_FULL5 + so;
          const int k0 = (64 * (uint32_t)ord + 128 * (j & 6)) & 960;
          mbar_wait(i < 5 ? sb + B_EMPTYKV + so - (i > 1 ? 8 : 0) : fb + (B_EMPTY5 - B_FULL5), par);
          if (el) {
            mbar_expect_tx(fb, R5);
            tma_2d_mc_h(st + rank * 8192, &P.x64, k0, 128 * m128 + 64 * rank, fb, i >= 11 ? ef : en);
            tma_3d_h(st + 16384, &P.wq, 0, k0, 2 * j, fb, ef);
          }
          ord >>= 4; so += 8;
          if (so == 40) { so = 0; par ^= 1; }
        }
        mbar_wait(sb + B_FULL5 + 8 + 8 * rank, 0);
        if (el) mbar_arrive(sb + B_R);
        #pragma unroll 1
        for (int i = 0; i < 19; i++) {
          const int row = i < 8 ? 128 * (((j & 6) + i) & 7) : 256 * (((j >> 1) + i) & 3) + 32 + 16 * (i & 4);
          mbar_wait(sb + B_EMPTY5 + so, par);
          if (el) {
            if (i < 16) {
              tma_5d_h(sb + so * 4096 + 16384, &P.wo[i >> 3], 128 * j, row, sb + B_GB + 8 * i, ef);
              tma_5d_h(sb + so * 4096 + 24576, &P.wo[i >> 3], 128 * j + 64, row, sb + B_GB + 8 * i, ef);
            } else mbar_arrive(sb + B_DR + 8 * (i - 16));
          }
          so += 8;
          if (so == 48) { so = 0; par ^= 1; }
        }
      }
    } else if (wp == 3) {
      const uint32_t t_start = (uint32_t)clock();
      mbar_wait(sb + B_S0, 0);
      if (el) {
        mbar_expect_tx(sb + B_W, 12288);
        #pragma unroll 1
        for (int i = 0; i < 6; i++) tma_2d(sb + (i == 0 ? OFF_WPHIK : i == 1 ? OFF_WPHIK1 : OFF_WPHIQ + 2048 * (i - 2)), &P.phi, 0, 32 * (i < 2 ? 2 * nkv + i : 4 * j + 2 * (i & 1) + ((i - 2) >> 1)), sb + B_W);
        prefetch_map(&P.x64); prefetch_map(&P.wq); prefetch_map(&P.wo[0]); prefetch_map(&P.wo[1]);
        prefetch_map(&P.o); prefetch_map(&P.wd); prefetch_map(&P.out); prefetch_map(&P.wg); prefetch_map(&P.wu);
      }
      if (lane < 16) st128_rlx(&G->cand[m128 * 512 + 64 * j + 4 * lane], ~0u, ~0u, ~0u, ~0u);
      if (lane < 16) st128_rlx(&G->rstat[16 * c + lane], 0, 0, 0, 0);
      if (lane < 12) st128_rlx(&G->yacc[12 * c + lane], 0, 0, 0, 0);
      const uint32_t nt = ld32_rlx(&G->epoch);
      if (lane < 8) { st128_rlx(&G->stats[16 * c + 2 * lane], nt, nt, nt, nt); st128_rlx(&G->csq[32 * c + 4 * lane], nt, nt, nt, nt); }
      if (lane < 4) { st128_rlx(&G->cskv[128 * nkv + 16 * m256 + 4 * lane], nt, nt, nt, nt); st128_rlx(&G->oset[16 * c + 4 * lane], nt, nt, nt, nt); }
      if (lane < 4) st128_rlx(&G->key[(2 * j + (lane >> 1)) * 128 + m128 * 8 + 4 * (lane & 1)], 0, 0, 0, 0);
      #pragma unroll 1
      for (int i = 0; i < 6; i++) {
        st128_rlx(&G->kvacc[(ha + 2 * (m256 & 1)) * KVP + 192 * (m256 >> 1) + 32 * i + lane], 0, 0, 0, kv_count(nt + 1, 0));
      }
      #pragma unroll 1
      for (int i = 0; i < 30; i++) {
        if (i == FI) { fence_gpu(); bar_arrive(NB_ZERO, 160); }
        wait_until(t_start + PF_T0 + PF_DT * i + 7 * f);
        if (el) {
          if (i < 4) { bulk_prefetch(P.wqkv + (size_t)(256 * i + c) * (3 * DM), 2048); bulk_prefetch(P.wqkv + (size_t)(256 * i + 128 + c) * (3 * DM), 2048); }
          else if (i < 6) bulk_prefetch(P.wo_p + (size_t)c * 8192 + (i - 4) * 4096, 8192);
          else if (f < NFFN) {
            if (i < 22) {
              #pragma unroll 1
              for (int e = 0; e < 4; e++) tma_2d(sb + OFF_T, rank ? &P.tu : &P.tg, 32 * (f & ~1), 64 * (i - 6) + 16 * e, sb + B_T);
            } else { tma_2d(sb + OFF_T, &P.td, 0, 256 * f + 32 * (i - 22), sb + B_T); tma_2d(sb + OFF_T, &P.td, 0, 256 * f + 32 * (i - 22) + 16, sb + B_T); }
          }
        }
      }
      __syncwarp();
      mbar_wait2(sb + B_OS, 0, sb + B_RX, 0);
      mbar_wait2(sb + B_EMPTY5 + 24, 0, sb + B_EMPTY5 + 32, 0);
      mbar_wait2(sb + B_EMPTY5 + 40, 0, sb + B_EMPTY5, 1);
      fetch_o(0, 0);
    } else {
      const int half = wp - 1;
      const uint32_t ep1 = ld32_rlx(&G->epoch) + 1, tg = ep1 & 3;
      {
        uint32_t it = 0;
        sts128(sb + OFF_ONES + half * 512 + lane * 16, 0x3f803f80u, 0x3f803f80u, 0x3f803f80u, 0x3f803f80u);
        if (lane < 9) { const uint32_t v = (lane & 1) ? 0 : 0x3f803f80u; sts128(sb + OFF_SEL + lane * 16, v, v, v, v); }
        auto reset_o = [&](int i0, int i1, uint32_t dt) {
          uint32_t t0 = (uint32_t)clock();
          #pragma unroll 1
          for (int i = i0; i < i1; i++) {
            st128_rlx(G->o + (m128 * 16 + 2 * j + half) * 8192 + 256 * i + 8 * lane, ~0u, ~0u, ~0u, ~0u);
            wait_until(t0 += dt);
          }
        };
        if (el) {
          #pragma unroll 1
          for (int i = 24 * half; i < 24 * half + 24; i++) { mbar_init(sb + B_GB + 8 * i, 1); mbar_expect_tx(sb + B_GB + 8 * i, i < 16 ? 16384 : 8192); }
          asm volatile("fence.mbarrier_init.release.cluster;" ::: "memory");
        }
        mbar_wait(sb + B_S0, 0);
        reset_o(0, RS_N, RS_D1);
        bar_sync(NB_PUB, 192);
        const uint4* src = reinterpret_cast<const uint4*>(&G->stats[256 * m256 + 128 * half]) + lane;
        const uint4* srk = reinterpret_cast<const uint4*>(&G->cskv[128 * nkv]) + lane;
        uint4 v0, v1, vk;
        it = 0;
        do { v0 = ld128_rlx(src); v1 = ld128_rlx(src + 32); vk = ld128_rlx(srk); }
        while ((tag_bad(v0, tg) || tag_bad(v1, tg) || tag_bad(vk, tg)) && ++it < POLL_LIMIT);
        fence_acquire_gpu();
        if (half) put_colsums(sb + OFF_BXK, lane, untag(vk.x), untag(vk.y), untag(vk.z), untag(vk.w));
        #pragma unroll 1
        for (int i = 0; i < 2; i++) {
          const uint4 v = i ? v1 : v0;
          uint32_t hi, lo;
          split_bf16(-0.5f * untag(v.x), -0.5f * untag(v.z), hi, lo);
          const uint32_t h0 = __byte_perm(hi, hi, 0x1010), h1 = __byte_perm(hi, hi, 0x3232), l0 = __byte_perm(lo, lo, 0x1010), l1 = __byte_perm(lo, lo, 0x3232);
          const uint32_t a = sb + OFF_AXK + half * 2048 + i * 1024 + lane * 32;
          sts128(a, h0, l0, 0, 0); sts128(a + 16, h1, l1, 0, 0);
          sts64(sb + OFF_RS256 + half * 512 + i * 256 + lane * 8, v.y & ~3u, v.w & ~3u);
          if (half == (m128 & 1)) {
            const uint32_t aq = sb + OFF_AXQ + i * 1024 + lane * 32;
            sts128(aq, h0, l0, 0, 0); sts128(aq + 16, h1, l1, 0, 0);
            sts64(sb + OFF_RSQ + i * 256 + lane * 8, v.y & ~3u, v.w & ~3u);
          }
        }
        fence_async_smem();
        __syncwarp();
        if (el) { sts32(sb + OFF_EP, ep1); mbar_arrive(sb + B_AUX); }
        reset_o(RS_N, 32, RS_D2);
        if (lane < 24) st128_rlx(&G->oflag[((m128 * 6 + 3 * half + (lane >> 3)) * 32 + 4 * j) * 8 + 4 * (lane & 7)], 0, 0, 0, 0);
        fence_gpu();
        __syncwarp();
        if (el) { st32_rlx(&G->oset[16 * c + 8 * half], ep1); if (half) mbar_arrive(sb + B_AUXQ); }
        if (!half) {
          const uint4* src = reinterpret_cast<const uint4*>(&G->csq[128 * j]) + lane;
          uint4 v0, v1, v2, v3;
          do { v0 = ld128_rlx(src); v1 = ld128_rlx(src + DM / 4); v2 = ld128_rlx(src + DM / 2); v3 = ld128_rlx(src + 3 * DM / 4); }
          while ((tag_bad(v0, tg) || tag_bad(v1, tg) || tag_bad(v2, tg) || tag_bad(v3, tg)) && ++it < POLL_LIMIT);
          put_colsums(sb + OFF_BXQ, lane, (untag(v0.x) + untag(v1.x)) + (untag(v2.x) + untag(v3.x)), (untag(v0.y) + untag(v1.y)) + (untag(v2.y) + untag(v3.y)),
                      (untag(v0.z) + untag(v1.z)) + (untag(v2.z) + untag(v3.z)), (untag(v0.w) + untag(v1.w)) + (untag(v2.w) + untag(v3.w)));
          fence_async_smem();
          __syncwarp();
          if (el) mbar_arrive(sb + B_AUXQ);
        }
      }
      if (half == 0) {
        for (uint32_t it = 0; __any_sync(~0u, ld32_rlx(&G->oset[m128 * 128 + 8 * (lane & 15)]) != ep1) && it < POLL_LIMIT; it++) {}
        fence_acquire_gpu();
        if (el) mbar_arrive(sb + B_OS);
      }
      if (!half) {
        #pragma unroll 1
        for (int hh = 0; hh < 2; hh++) {
          const uint32_t src = sb + (1 + rank) * R5 + hh * 8192, fa = sb + B_GA + 16 * rank + 8 * hh;
          mbar_wait2(sb + B_UO + 8 * hh, 0, sb + B_GB + 8 * rank, 0);
          if (el) bulk_s2peer(mapa(src, rank ^ 1), src, 8192, mapa(fa, rank ^ 1));
        }
      }
      else if (f < NFFN) {
        mbar_wait(sb + B_UO + 24, 0);
        mbar_wait2(sb + B_UO, 0, sb + B_UO + 8, 0);
        uint32_t t0 = (uint32_t)clock();
        #pragma unroll 1
        for (int i = 0; i < 12; i++) {
          const int e = (FF_ORD >> (4 * i)) & 15;
          const uint32_t dst = sb + 16384 * ((FF_SLOT >> (4 * e)) & 15), fb = sb + B_F + 8 * e;
          if (i >= 2) mbar_wait(sb + B_WC + 8 * ((0x100066553244ull >> (4 * e)) & 15), 0);
          wait_until(t0);
          t0 = (uint32_t)clock() + (i < FF_N ? FF_DT : FF_D2);
          if (el) {
            mbar_expect_tx(fb, 16384);
            if (e >= 8) tma_3d_h(dst, &P.wd, 0, 32 * f, 4 * e - 32, fb, ef);
            else { tma_2d_h(dst, &P.wg, 32 * f, 128 * e, fb, ef); tma_2d_h(dst + 8192, &P.wu, 32 * f, 128 * e, fb, ef); }
          }
        }
      }
      __syncwarp();
    }
    if (wp & 1) {
      __syncwarp();
      fetch_o(wp, 1);
      mbar_wait(sb + B_OUT + 8 * (wp >> 1), 0);
      uint32_t t0 = (uint32_t)clock();
      #pragma unroll 1
      for (int i = 0; i < 8; i++) {
        wait_until(t0);
        if (el) tma_store_2d(&P.out, 128 * j + 64 * (i & 1), 128 * m128 + 32 * (wp & 2) + 8 * (i & 6), sb + OFF_OUT + (i & 1) * 16384 + (wp & 2) * 4096 + (i & 6) * 1024, ef);
        t0 += OUT_D;
      }
      if (el) { bulk_commit(); bulk_wait_all(); fence_async_global(); mbar_arrive(sb + B_SD); }
    }
    __syncwarp();
    cluster_arrive(); cluster_wait();
    return;
  }

  asm volatile("setmaxnreg.inc.sync.aligned.u32 160;");
  cluster_wait();
  const int t = tid & 127, g = lane >> 2;
  const uint32_t sa = (16 * wp + (lane & 15)) * 128 + (((lane >> 4) ^ (lane & 7)) << 4);

  if (wg == 2) {
    float s[2] = {0.f, 0.f}, s2[2] = {0.f, 0.f}, ck[8] = {0.f, 0.f, 0.f, 0.f, 0.f, 0.f, 0.f, 0.f}, cs[8] = {0.f, 0.f, 0.f, 0.f, 0.f, 0.f, 0.f, 0.f};
    const uint32_t ebr = mapa(sb + B_EMPTYKV, lane & 1), tg = (ld32_rlx(&G->epoch) + 1) & 3;
    auto addx = [&](const uint4 v) {
      const uint32_t w[4] = {v.x, v.y, v.z, v.w};
      #pragma unroll
      for (int e = 0; e < 4; e++) { const float a = bf_lo(w[e]), d = bf_hi(w[e]); s[0] += a; s[1] += d; s2[0] = fmaf(a, a, s2[0]); s2[1] = fmaf(d, d, s2[1]); }
    };
    auto addc = [&](const uint4 v, float (&o)[8]) {
      o[0] += bf_lo(v.x); o[1] += bf_hi(v.x); o[2] += bf_lo(v.y); o[3] += bf_hi(v.y); o[4] += bf_lo(v.z); o[5] += bf_hi(v.z); o[6] += bf_lo(v.w); o[7] += bf_hi(v.w);
    };
    {
      const uint32_t ra = (16 * nkv + (t >> 3)) * 128 + (t & 7) * 16;
      const uint32_t ca = 32768 + (m256 >> 2) * 8192 + (t >> 1) * 128 + (((2 * (m256 & 3) + (t & 1)) ^ ((t >> 1) & 7)) << 4);
      int rd = 0;
      mbar_wait(sb + B_S0, 0);
      #pragma unroll 1
      for (int kb = 0; kb < 10; kb++) {
        const uint32_t st = sb + (kb & 3) * KV_STAGE;
        mbar_wait(sb + B_FULLKV + 8 * (kb & 3), (kb >> 2) & 1);
        const uint4 x0 = lds128(st + ra), w0 = lds128(st + ca);
        addx(x0); addc(w0, ck);
        __syncwarp();
        if (lane < 2) mbar_arrive_remote(ebr + 8 * (kb & 3), 1);
        if ((SKM >> kb) & 1) {
          if (rd) {
            mbar_wait(sb + B_G, (rd - 1) & 1);
            #pragma unroll 1
            for (int i = 0; i < 2; i++) { addx(lds128(sb + OFF_G + (t >> 3) * 256 + (t & 7) * 16 + 128 * i)); addc(lds128(sb + OFF_G + 4096 + t * 16 + 2048 * i), ck); }
            bar_sync(NB_WG2, 128);
          }
          if (wp == 0 && elect_one()) {
            mbar_expect_tx(sb + B_G, 8192);
            if (rd < 3) {
              tma_2d(sb + OFF_G, &P.xs, 640 + 128 * rd, 256 * m256 + 16 * nkv, sb + B_G);
              tma_2d(sb + OFF_G + 4096, &P.ws, (1 + (m256 >> 2)) * DM + 64 * nkv + 16 * (m256 & 3), 640 + 128 * rd, sb + B_G);
            } else tma_2d(sb + OFF_G, &P.qs, 32 * (c & 31), 256 * (c >> 5), sb + B_G);
          }
          rd++;
        }
      }
    }
    const uint32_t scr = sb + OFF_WR;
    float sx = s[0] + s[1], sq = s2[0] + s2[1];
    #pragma unroll
    for (int o = 1; o < 8; o <<= 1) { sx += __shfl_xor_sync(~0u, sx, o); sq += __shfl_xor_sync(~0u, sq, o); }
    float v = reduce8(ck, lane);
    v += __shfl_xor_sync(~0u, v, 2);
    if (!(lane & 2)) stsf(scr + (wp * 16 + 8 * (lane & 1) + (lane >> 2)) * 4, v);

    bar_sync(NB_ZERO, 160);
    if ((lane & 7) == 0) {
      const float mean = sx * (1.f / DM);
      st64_rlx(&G->stats[256 * m256 + 16 * nkv + (t >> 3)], tagw(mean, tg), tagw(rsqrtf(fmaxf(sq * (1.f / DM) - mean * mean, 0.f) + 1e-5f), tg));
    }
    if (wp == 1 && lane < 16) {
      const uint32_t a = scr + lane * 4;
      st32_rlx(&G->cskv[128 * nkv + 16 * m256 + lane], tagw((ldsf(a) + ldsf(a + 64)) + (ldsf(a + 128) + ldsf(a + 192)), tg));
    }
    __syncwarp();
    bar_arrive(NB_PUB, 192);
    const uint4 wv = ld128_keep(P.wr + t * 8);
    #pragma unroll 1
    for (int i = 0; i < 2; i++) {
      mbar_wait(sb + B_G, i ^ 1);
      #pragma unroll 1
      for (int e = 0; e < 4; e++) addc(lds128(sb + OFF_G + t * 16 + 2048 * e), cs);
      bar_sync(NB_WG2, 128);
      if (i == 0 && wp == 0 && elect_one()) { mbar_expect_tx(sb + B_G, 8192); tma_2d(sb + OFF_G, &P.qs, 32 * (c & 31), 256 * (c >> 5) + 128, sb + B_G); }
    }
    float sw = (bf_lo(wv.x) + bf_hi(wv.x)) + (bf_lo(wv.y) + bf_hi(wv.y)) + (bf_lo(wv.z) + bf_hi(wv.z)) + (bf_lo(wv.w) + bf_hi(wv.w));
    #pragma unroll
    for (int o = 16; o; o >>= 1) sw += __shfl_xor_sync(~0u, sw, o);
    if (lane == 0) stsf(sb + OFF_SUMWR + wp * 4, sw);
    if ((t >> 4) == j) {
      const uint32_t a = sb + OFF_WR + (t & 15) * 32;
      sts128(a, wv.x << 16, wv.x & 0xffff0000u, wv.y << 16, wv.y & 0xffff0000u);
      sts128(a + 16, wv.z << 16, wv.z & 0xffff0000u, wv.w << 16, wv.w & 0xffff0000u);
    }
    v = reduce8(cs, lane);
    stsf(sb + OFF_G + (wp * 32 + 8 * (lane & 3) + (lane >> 2)) * 4, v);
    bar_sync(NB_WG2, 128);
    if (wp == 0) {
      const uint32_t a = sb + OFF_G + lane * 4, cq = tagw((ldsf(a) + ldsf(a + 128)) + (ldsf(a + 256) + ldsf(a + 384)), tg);
      st32_rlx(&G->csq[(c >> 5) * DM + 32 * (c & 31) + lane], cq);
      if (lane == 0) mbar_arrive_at(sb + B_W, rank, (cq & P.zero) + 1);
    }
  }

  uint32_t xr[32];
  {
    const bool isq = wg == 2;
    float acc[2][64];
    {
      const uint32_t emptyb = mapa(sb + (isq ? B_EMPTY5 : B_EMPTYKV), t & 1);
      auto correct = [&](uint32_t xa, uint32_t xb) {
        wg_fence();
        wgmma_sa_n128<0, 1, H0, H0>(acc[0], dlo(SB0, 0) + (xa >> 4), dlo(SB0, 0) + (xb >> 4));
        wgmma_sa_n128<0, 1, H0, H0>(acc[1], dlo(SB0, 0) + (xa >> 4) + 64, dlo(SB0, 0) + (xb >> 4));
        wg_commit();
      };
      if (!isq) {
        mbar_wait(sb + B_S0, 0);
        if (wg) mbar_wait(sb + B_FULLKV, 0);
        #pragma unroll 1
        for (int kb = 0; kb < 16; kb++) {
          const uint32_t da = dlo(SB0, 16) + wg * 1024 + (kb & 3) * (KV_STAGE >> 4), db = dlo(SB0 + 32768, 8192) + (kb & 3) * (KV_STAGE >> 4);
          wg_fence();
          #pragma unroll
          for (int k = 0; k < 4; k++) {
            wgmma_ss_n128<0, 1, H128, H128>(acc[0], da + 2 * k, db + 128 * k, k > 0 || kb != 0);
            wgmma_ss_n128<0, 1, H128, H128>(acc[1], da + 512 + 2 * k, db + 128 * k, k > 0 || kb != 0);
          }
          wg_commit();
          wg_wait<1>();
          if (kb > 0 && t < 2) mbar_arrive_remote(emptyb + 8 * ((kb - 1) & 3), kb > 10 ? 3 : 1);
          if (kb < 15) mbar_wait(sb + B_FULLKV + 8 * ((kb + 1) & 3), ((kb + 1) >> 2) & 1);
          if (kb == 0) mbar_wait(sb + B_FULLKV, 0);
          if (kb == 15 - LAG && wg == 1) bar_sync(NB_LAG, 256);
        }
        bar_arrive(wg ? NB_QGO : NB_LAG, 256);
        mbar_wait(sb + B_AUX, 0);
        correct(OFF_AXK + wg * 2048, OFF_BXK);
        wg_wait<0>();
        if (t < 2) mbar_arrive_remote(emptyb + 24, 3);
        fence_regs(acc[0]); fence_regs(acc[1]);
      const uint32_t stg = sb + OFF_X + (1 - wg) * 24576;
      const uint32_t va = stg + 16384 + (16 * wp + (lane & 15)) * 64 + (((lane >> 4) ^ ((lane >> 1) & 3)) << 4);
      const uint32_t ra = sb + OFF_RS256 + (128 * wg + 16 * wp + g) * 4;
      const float rs[4] = {ldsf(ra), ldsf(ra + 32), ldsf(ra + 256), ldsf(ra + 288)};
      float p[2][16];
      uint32_t vf[16], kf[2][16];
      auto project = [&](const uint32_t (&f)[16], uint32_t db) {
        wg_fence();
        #pragma unroll
        for (int i = 0; i < 2; i++) {
          wgmma_rs_n32<1, H64>(p[i], f[8*i], f[8*i+1], f[8*i+2], f[8*i+3], db, 0);
          wgmma_ra_n32<1, H64>(p[i], f[8*i+4], f[8*i+5], f[8*i+6], f[8*i+7], db + 64);
        }
        wg_commit();
      };
      auto fold = [&](uint32_t (&f)[16], int col, float sc) {
        #pragma unroll
        for (int i = 0; i < 16; i++) {
          const float r = rs[2 * (i >> 3) + (i & 1)] * sc;
          f[i] = pack_bf16(acc[i >> 3][col + 2 * (i & 7)] * r, acc[i >> 3][col + 2 * (i & 7) + 1] * r);
          asm volatile("" : "+r"(f[i]));
        }
      };
      auto put_v = [&](const uint32_t (&f)[16]) {
        #pragma unroll
        for (int k = 0; k < 4; k++) stsm4((va ^ ((k & 1) << 5)) + (k >> 1) * 4096, f[4*k], f[4*k+1], f[4*k+2], f[4*k+3]);
      };
      fold(vf, 48, 1.f);
      mbar_wait(sb + B_W, 0);
      fold(kf[0], 0, LOG2E);
      #pragma unroll
      for (int i = 0; i < 32; i++) p[i >> 4][i & 15] = acc[i >> 4][i & 15];
      project(kf[0], dlo(SB0 + OFF_WPHIK, 16));
      mbar_wait(sb + B_W, 0);
      {
        uint32_t v0[16];
        fold(kf[1], 16, LOG2E);
        fold(v0, 32, 1.f);
        if (wg == 1) bar_sync(NB_DN, 256);
        put_v(v0);
      }
      wg_wait<0>();
      fence_regs(p[0]); fence_regs(p[1]);
      if (wg == 1) bar_arrive(NB_WG01, 256);
      #pragma unroll 1
      for (int h = 0; h < 2; h++) {
        uint32_t ph[4][8];
        float rsum[2][4];
        dual_exp2(p[0], ph[0], ph[1]); dual_exp2(p[1], ph[2], ph[3]);
        row_sums(rsum, ph, dlo(SB0 + OFF_SEL, 16));
        if (wg == 0 && h == 0) { bar_arrive(NB_DN, 256); bar_sync(NB_WG01, 256); }
        if (h == 1) {
          if (wg == 1) bar_sync(NB_DN, 256);
          put_v(vf);
        }
        wg_wait<0>();
        fence_regs(rsum[0]); fence_regs(rsum[1]);
        if (!XC && __builtin_expect(__any_sync(~0u, !((rsum[0][0] + rsum[0][1]) + (rsum[0][2] + rsum[0][3]) + (rsum[1][0] + rsum[1][1]) + (rsum[1][2] + rsum[1][3]) < EXP_LIM)), 0)) {
          dual_exp2_shifted<true>(p, ph, rsum);
        }
        if (h == 0) project(kf[1], dlo(SB0 + OFF_WPHIK1, 16));
        normalize(ph, rsum);
        #pragma unroll
        for (int i = 0; i < 8; i++) {
          const uint32_t* f = &ph[i >> 1][4 * (i & 1)];
          stsm4(((stg + sa) ^ ((i & 3) << 5)) + (i >> 2) * 8192, f[0], f[1], f[2], f[3]);
        }
        fence_async_smem();
        if (wg == h) {
          float kv[20];
          #pragma unroll
          for (int w = 0; w < 2; w++) {
            const uint32_t da = dlo(SB0 + OFF_X, 16) + (h ^ w ^ 1) * 1536, db = dlo(SB0 + OFF_X + 16384, OFF_ONES - OFF_X - 16384) - (h ^ w ^ 1) * (1536 * 65535);
            if (w) bar_sync(NB_ST, 256); else bar_sync(NB_L0 + h, 128);
            wg_fence();
            #pragma unroll
            for (int k = 0; k < 8; k++) {
              if (k == 0 && w == 0) wgmma_sz_n40<1, 1, H128, H64>(kv, da, db);
              else wgmma_sa_n40<1, 1, H128, H64>(kv, da + k * 128, db - k * (64 * 65535));
            }
            wg_commit();
          }
          float4* dst = &G->kvacc[(ha + 2 * h) * KVP + t];
          wg_wait<0>();
          fence_regs(kv);
          if (h == 0) bar_arrive(NB_DN, 256); else if (t < 2) { mbar_arrive_at(sb + B_EMPTY5 + 40, t, 2); if (t == 0) mbar_arrive(sb + B_KD); }
          kv[17] = kv[18];
          #pragma unroll
          for (int i = 0; i < 6; i++) red_add_f32x4(dst + 128 * i, kv[3*i], kv[3*i+1], kv[3*i+2], 1.f);
        } else bar_arrive(NB_ST, 256);
        wg_wait<0>();
        fence_regs(p[0]); fence_regs(p[1]);
      }
      #pragma unroll
      for (int i = 0; i < 32; i++) asm volatile("mov.b32 %0, 0;" : "=r"(xr[i]));
      } else {
        uint32_t so = 0, po = 0, par = 0;
        mbar_wait(sb + B_FULL5, 0);
        bar_sync(NB_QGO, 256);
        #pragma unroll 1
        for (int kb = 0; kb < 16 - ML; kb++) {
          const uint32_t da = dlo(SB0, 16) + so * 256, db = dlo(SB0 + 16384, 8192) + so * 256;
          #pragma unroll
          for (int k = 0; k < 4; k++) {
            wg_fence();
            wgmma_ss_n128<0, 1, H128, H128>(acc[0], da + 2 * k, db + 128 * k, k > 0 || kb != 0);
            wgmma_ss_n128<0, 1, H128, H128>(acc[1], da + 512 + 2 * k, db + 128 * k, k > 0 || kb != 0);
            wg_commit();
            if (k == 1 && kb > 0 && t < 2) mbar_arrive_remote(emptyb + po, 2);
            if (k == 3) {
              po = so; so += 8;
              if (so == 40) { so = 0; par ^= 1; }
              mbar_wait(sb + B_FULL5 + so, par);
            }
            if ((QW >> k) & 1) wg_wait<2>(); else wg_wait<1>();
          }
        }
        auto block = [&](const int kb, const int i) {
          wg_fence();
          #pragma unroll
          for (int k = 0; k < 4; k++) wgmma_sa_n128<0, 1, H128, H128>(acc[i], dlo(SB0, 16) + (kb % 5) * 2048 + 512 * i + 2 * k, dlo(SB0 + 16384, 8192) + (kb % 5) * 2048 + 128 * k);
          wg_commit();
        };
        auto hand_over = [&](const int i) {
          const uint32_t ta = sb + (1 + rank) * R5 + sa + i * 8192;
          #pragma unroll
          for (int k = 0; k < 4; k++) {
            const float* a = &acc[i][32 * (k >> 1) + 8 * (k & 1)];
            stsm4(ta ^ (k << 5), pack_bf16(a[0], a[1]), pack_bf16(a[2], a[3]), pack_bf16(a[4], a[5]), pack_bf16(a[6], a[7]));
          }
        };
        mbar_wait2(sb + B_AUXQ, 0, sb + B_OS, 0);
        correct(OFF_AXQ, OFF_BXQ);
        #pragma unroll
        for (int kb = 16 - ML; kb < 16; kb++) {
          block(kb, 0);
          if (kb < 15) mbar_wait(sb + B_FULL5 + 8 * ((kb + 1) % 5), ((kb + 1) / 5) & 1);
          if (kb == 16 - ML) { wg_wait<2>(); if (t < 2) mbar_arrive_remote(emptyb + 8 * ((kb - 1) % 5), 2); }
        }
        mbar_wait(sb + B_RC, 0);
        block(16 - ML, 1);
        block(17 - ML, 1);
        wg_wait<2>();
        fence_regs(acc[0]);
        hand_over(0);
        fence_async_smem();
        bar_arrive(NB_Q0, 256);
        #pragma unroll
        for (int kb = 18 - ML; kb <= 16; kb++) {
          wg_wait<1>();
          if (t < 2) mbar_arrive_remote(emptyb + 8 * ((kb - 2) % 5), 2);
          if (kb < 16) block(kb, 1);
        }
        mbar_wait(sb + B_RC + 8, 0);
        wg_wait<0>();
        if (t < 2) mbar_arrive_remote(emptyb, 2);
        fence_regs(acc[1]);
        hand_over(1);
        fence_async_smem();
        bar_arrive(NB_Q0 + 1, 256);
        #pragma unroll
        for (int i = 0; i < 32; i++) { const float* a = &acc[(i >> 3) & 1][16 + 32 * (i >> 4) + 2 * (i & 7)]; xr[i] = pack_bf16(a[0], a[1]); }
      }
    }
    float p[2][16];
    #pragma unroll
    for (int i = 0; i < 32; i++) asm volatile("mov.b32 %0, 0;" : "=f"(p[i >> 4][i & 15]));
    auto project_r = [&](int w) {
      wg_fence();
      #pragma unroll
      for (int h = 0; h < 2; h++) {
        wgmma_rs_n32<1, H64>(p[h], xr[8*h], xr[8*h+1], xr[8*h+2], xr[8*h+3], dlo(SB0 + OFF_WPHIQ, 16) + 128 * w, 0);
        wgmma_ra_n32<1, H64>(p[h], xr[8*h+4], xr[8*h+5], xr[8*h+6], xr[8*h+7], dlo(SB0 + OFF_WPHIQ, 16) + 128 * w + 64);
      }
      wg_commit();
    };
    auto capture = [&](const int i) {
      if (!i) mbar_wait(sb + B_R, 0);
      #pragma unroll
      for (int k = 0; k < 4; k++) ldsm4(((sb + (1 + rank) * R5 + wg * 8192 + sa) ^ (k << 5)) + i * 2 * R5, xr[16*i+4*k], xr[16*i+4*k+1], xr[16*i+4*k+2], xr[16*i+4*k+3]);
      const uint32_t one = (((xr[16*i] | xr[16*i+4]) | (xr[16*i+8] | xr[16*i+12])) & P.zero) + 1;
      if (lane == 0) mbar_arrive_at(sb + (i ? B_RX : B_RC + 8 * wg), i ? wg : rank, one);
    };
    float cc[2][2];
    auto get_scales = [&]() {
      const uint32_t rq = sb + OFF_RSQ + (16 * wp + g) * 4 + 256 * (wg & 1), rb = rq + 128 * (wg & 2);
      cc[0][0] = ldsf(rq) * LOG2E; cc[0][1] = ldsf(rq + 32) * LOG2E; cc[1][0] = ldsf(rb) * LOG2E; cc[1][1] = ldsf(rb + 32) * LOG2E;
    };
    get_scales();
    {
      const uint4* src = reinterpret_cast<const uint4*>(&G->kvacc[(4 * j + wg) * KVP + t]);
      const uint32_t full = kv_count(__float_as_uint(ldsf(sb + OFF_EP)), 8);
      uint4 v[12];
      #pragma unroll
      for (int i = 0; i < 12; i++) v[i] = i < 6 || isq ? ld128_rlx(src + 128 * i) : make_uint4(0, 0, 0, full);
      if (isq) {
        project_r(2);
        wg_wait<0>();
        #pragma unroll
        for (int i = 0; i < 16; i++) xr[i] = xr[16 + i];
      } else {
        capture(0);
      }
      #pragma unroll 1
      for (uint32_t it = 0; it < POLL_LIMIT; it++) {
        uint32_t bad = 0;
        #pragma unroll
        for (int i = 0; i < 12; i++) bad |= v[i].w ^ full;
        if (!__any_sync(~0u, bad != 0)) break;
        #pragma unroll
        for (int i = 0; i < 12; i++) if (i < 6 || isq) v[i] = ld128_rlx(src + 128 * i);
      }
      mbar_wait(sb + B_KD, 0);
      #pragma unroll
      for (int e = 0; e < 2; e++) {
        if (e == 0 || isq) {
          float f[18];
          #pragma unroll
          for (int i = 0; i < 6; i++) { f[3*i] = __uint_as_float(v[6*e+i].x); f[3*i+1] = __uint_as_float(v[6*e+i].y); f[3*i+2] = __uint_as_float(v[6*e+i].z); }
          const uint32_t ka = sb + OFF_KVZ + (wg + e) * 5120 + wp * 1280 + lane * 16;
          stsm4(ka, pack_bf16(f[0], f[1]), pack_bf16(f[2], f[3]), pack_bf16(f[4], f[5]), pack_bf16(f[6], f[7]));
          stsm4(ka + 512, pack_bf16(f[8], f[9]), pack_bf16(f[10], f[11]), pack_bf16(f[12], f[13]), pack_bf16(f[14], f[15]));
          stsm2(ka + 1024, pack_bf16(f[16], 1.f), pack_bf16(f[17], 1.f));
        }
      }
    }
    fence_async_smem();
    if (wg == 1) bar_arrive(NB_DN, 256);
    #pragma unroll 1
    for (int e = wg;; e++) {
      const int half = e >> 1, hh = e & 1, turn = e;
      const uint32_t ao = (1 + rank) * R5 + hh * 8192;
      uint32_t ph[4][8];
      #pragma unroll
      for (int i = 0; i < 32; i++) asm volatile("mov.b32 %0, 0;" : "=r"(ph[i >> 3][i & 7]));
      uint32_t shifted = 0;
      asm volatile("" : "+r"(shifted));
      #pragma unroll 1
      for (;;) {
        if (!XC && shifted) { float unused[2][4]; dual_exp2_shifted<false>(p, ph, unused); }
        uint32_t first = (shifted ^ 1) & !isq;
        asm volatile("" : "+r"(first));
        if (first) {
          bar_sync(NB_Q0 + wg, 256);
          const uint32_t da = dlo(SB0, 16) + (ao >> 4), db = dlo(SB0 + OFF_WPHIQ, 16);
          wg_fence();
          #pragma unroll
          for (int h = 0; h < 2; h++) {
            wgmma_ss_n32<0, 1, H128, H64>(p[h], da + 4 * h, db + 128 * h, 0);
            wgmma_sa_n32<0, 1, H128, H64>(p[h], da + 4 * h + 2, db + 128 * h + 64);
          }
          wg_commit();
          capture(1);
          wg_wait<0>();
        }
        fence_regs(p[0]); fence_regs(p[1]);
        uint32_t again = shifted;
        asm volatile("" : "+r"(again));
        if (again) break;
        float s2[4] = {0.f, 0.f, 0.f, 0.f};
        #pragma unroll
        for (int i = 0; i < 32; i++) { float& x = p[i >> 4][i & 15]; x *= cc[i >> 4][(i >> 1) & 1]; s2[i & 3] = fmaf(x, x, s2[i & 3]); }
        if (!__any_sync(~0u, !((s2[0] < ARG_LIM2) & (s2[1] < ARG_LIM2) & (s2[2] < ARG_LIM2) & (s2[3] < ARG_LIM2)))) break;
        shifted = 1;
      }
      if (e == 1 || e == 2) bar_sync(NB_TOK + e - 1, 256);
      float ac[4][20];
      auto numer = [&](int h) {
        const uint32_t (*f)[8] = &ph[2 * h];
        const uint32_t db = dlo(SB0 + OFF_KVZ, 128) + (half ? e : h) * 320;
        wg_fence();
        #pragma unroll
        for (int i = 0; i < 2; i++) {
          wgmma_rz_n40<1, dhi(256, 0)>(ac[2*h+i], f[i][0], f[i][1], f[i][2], f[i][3], db + i * 160);
          wgmma_ra_n40<1, dhi(256, 0)>(ac[2*h+i], f[i][4], f[i][5], f[i][6], f[i][7], db + (i * 160 + 80));
        }
        wg_commit();
      };
      const uint32_t oa = (16 * wp + g) * 128 + (((lane & 3) ^ g) << 4);
      auto finish = [&](int h) {
        const float* ap = ac[2 * h]; const float* am = ac[2 * h + 1];
        const float ip0 = rcp(ap[17]), im0 = rcp(am[17]), ip1 = rcp(ap[19]), im1 = rcp(am[19]);
        const float d0 = rcp(fmaf(ap[16], ip0, fmaf(am[16], im0, 1e-6f))), d1 = rcp(fmaf(ap[18], ip1, fmaf(am[18], im1, 1e-6f)));
        const float a0 = ip0 * d0, b0 = im0 * d0, a1 = ip1 * d1, b1 = im1 * d1;
        #pragma unroll
        for (int r = 0; r < 2; r++) {
          const float a = r ? a1 : a0, b = r ? b1 : b0;
          uint32_t w[4];
          #pragma unroll
          for (int k = 0; k < 4; k++) w[k] = pack_bf16(fmaf(ap[4*k+2*r], a, am[4*k+2*r] * b), fmaf(ap[4*k+2*r+1], a, am[4*k+2*r+1] * b));
          const uint32_t off = (oa ^ ((half ? rank : h) << 6)) + r * 1024;
          st128_rlx(reinterpret_cast<uint8_t*>(G->o + (m128 * 16 + (half ? 2 * (j & 6) + 2 * hh + 1 : 2 * j)) * 8192 + (half ? h : hh) * 4096) + off, w[0], w[1], w[2], w[3]);
          if (!half) sts128(sb + ao + off, w[0], w[1], w[2], w[3]);
        }
        if ((half || h) && lane < 8) st32_rlx(&G->oflag[((m128 * 6 + (half ? 2 * e - 2 + h : hh)) * 32 + 4 * j + wp) * 8 + lane], 1);
      };
      if (!shifted) dual_exp2(p[0], ph[0], ph[1]);
      numer(0);
      if (!shifted) dual_exp2(p[1], ph[2], ph[3]);
      if (turn < 2) bar_arrive(NB_TOK + turn, 256);
      if (wg == 0) bar_sync(NB_DN, 256);
      numer(1);
      wg_wait<1>();
      fence_regs(ac[0]); fence_regs(ac[1]);
      finish(0);
      wg_wait<0>();
      fence_regs(ac[2]); fence_regs(ac[3]);
      #pragma unroll
      for (int i = 0; i < 32; i++) asm volatile("mov.b32 %0, 0;" : "=f"(p[i >> 4][i & 15]));
      if (e == 2) project_r(3);
      finish(1);
      if (!half) fence_async_smem();
      __syncwarp();
      if (lane == 0) mbar_arrive(sb + B_UO + 8 * e);
      wg_wait<0>();
      if (e != 2) break;
      get_scales();
    }
    if (isq) cluster_arrive();
  }

  {
  int lane;
  asm volatile("mov.u32 %0, %%laneid;" : "=r"(lane));
  const int g = lane >> 2, q = lane & 3;
  if (wg < 2) {
    float h[64];
    {
      #pragma unroll
      for (int i = 0; i < 32; i++) { h[2*i] = bf_lo(xr[i]); h[2*i+1] = bf_hi(xr[i]); }
      fence_regs(h);
      const uint32_t emptyb = mapa(sb + B_EMPTY5, t & 1);
      uint32_t s = 1 + rank, ps = 0;
      mbar_wait2(sb + B_GB + 8 * rank, 0, sb + B_UO + 8 * wg, 0);
      #pragma unroll
      for (int i = 0; i < G2P; i++) {
        const uint32_t da = dlo(SB0, 16) + s * 2048 + wg * 512, db = dlo(SB0 + 16384, 8192) + s * 2048;
        wg_fence();
        #pragma unroll
        for (int k = 0; k < 4; k++) wgmma_sa_n128<0, 1, H128, H128>(h, da + k * 2, db + k * 128);
        wg_commit();
        const uint32_t ns = i ? (i + 2) % 6 : 2 - rank;
        const uint32_t nb = i ? i + 1 : 1 - rank, b0 = sb + B_GB + 8 * nb, b1 = sb + B_GA + 16 * nb + 8 * wg;
        const bool here = i == 15 || mbar_test2(b0, 0, b1, 0);
        wg_wait<1>();
        if (!(((2 * REL + 1) >> i) & 1) && i < 14 && t < 2) mbar_arrive_remote(emptyb + 8 * ps, 1);
        if ((REL >> i) & 1) { wg_wait<0>(); if (t < 2) mbar_arrive_remote(emptyb + 8 * s, 1); }
        if (!here) mbar_wait2u(b0, b1);
        ps = s; s = ns;
      }
      #pragma unroll 1
      for (int i = G2P; i < 16; i++) {
        const uint32_t da = dlo(SB0, 16) + s * 2048 + wg * 512, db = dlo(SB0 + 16384, 8192) + s * 2048;
        wg_fence();
        #pragma unroll
        for (int k = 0; k < 4; k++) wgmma_sa_n128<0, 1, H128, H128>(h, da + k * 2, db + k * 128);
        wg_commit();
        const uint32_t nb = min(i + 1, 15), b0 = sb + B_GB + 8 * nb, b1 = sb + B_GA + 16 * nb + 8 * wg;
        const bool here = mbar_test2(b0, 0, b1, 0);
        wg_wait<1>();
        if (t < 2) mbar_arrive_remote(emptyb + 8 * ps, 1);
        if (!here) mbar_wait2u(b0, b1);
        ps = s; s = s == 5 ? 0 : s + 1;
      }
    }
    cluster_arrive();
    float2 wr[16];
    #pragma unroll
    for (int i = 0; i < 16; i++) wr[i] = lds64f(sb + OFF_WR + 32 * i + 8 * q);
    const int r0 = 64 * wg + 16 * wp + g;
    float sum0, sum1, dot0, dot1, sq0, sq1;
    uint32_t redo = 0;
    asm volatile("" : "+r"(redo));
    #pragma unroll 1
    for (;;) {
    if (!XC && redo) {
      wg_wait<0>();
      #pragma unroll 1
      for (int n4 = 0; n4 < 4; n4++) {
        const uint32_t* xp = reinterpret_cast<const uint32_t*>(P.x + (size_t)(128 * m128 + r0) * DM + 128 * j) + 16 * n4 + q;
        #pragma unroll
        for (int i = 0; i < 48; i++) h[i] = h[i + 16];
        #pragma unroll
        for (int i = 0; i < 8; i++) { const uint32_t v = xp[4 * (i >> 1) + (i & 1) * 4 * DM]; h[48+2*i] = bf_lo(v); h[49+2*i] = bf_hi(v); }
        #pragma unroll 1
        for (int ks = 0; ks < 64; ks++) {
          const int kb = ks >> 2, kk = 16 * (ks & 3);
          const bf16* op = G->o + (m128 * 16 + kb) * 8192 + r0 * 64 + 2 * q + (((kk >> 3) ^ g) << 3);
          const uint32_t* w = reinterpret_cast<const uint32_t*>(P.wo_p) + 64 * j + 16 * n4 + q +
              (((kb & 1) ? 256 * (kb >> 2) + 32 * (kb & 2) + 32 + 4 * (kk & 32) : 64 * kb + 2 * (kk & 32)) + ((kk & 16) >> 2) + 4 * (g & 6) + (g & 1)) * (DM / 2);
          uint32_t b[8], a0, a1, a2, a3, it = 0;
          #pragma unroll
          for (int n = 0; n < 8; n++) b[n] = w[4 * (n >> 1) + (n & 1) * DM];
          const bf16* o2 = op + 8 - 16 * (g & 1);
          do { a0 = ld32_rlx(op); a1 = ld32_rlx(op + 512); a2 = ld32_rlx(o2); a3 = ld32_rlx(o2 + 512); }
          while (__any_sync(~0u, max(max(a0, a1), max(a2, a3)) == ~0u) && ++it < POLL_LIMIT);
          #pragma unroll
          for (int n = 0; n < 4; n++) mma16816(h[48+4*n], h[49+4*n], h[50+4*n], h[51+4*n], a0, a1, a2, a3, transpose8(b[2*n]), transpose8(b[2*n+1]));
        }
      }
    }
    wg_wait<0>();
    fence_regs(h);
    sum0 = 0.f, sum1 = 0.f, dot0 = 0.f, dot1 = 0.f, sq0 = 0.f, sq1 = 0.f;
    #pragma unroll
    for (int i = 0; i < 16; i++) {
      sum0 += h[4*i] + h[4*i+1]; sum1 += h[4*i+2] + h[4*i+3];
      sq0 = fmaf(h[4*i], h[4*i], fmaf(h[4*i+1], h[4*i+1], sq0)); sq1 = fmaf(h[4*i+2], h[4*i+2], fmaf(h[4*i+3], h[4*i+3], sq1));
      dot0 = fmaf(h[4*i], wr[i].x, fmaf(h[4*i+1], wr[i].y, dot0)); dot1 = fmaf(h[4*i+2], wr[i].x, fmaf(h[4*i+3], wr[i].y, dot1));
    }
    if (!__any_sync(~0u, !redo & (h[0] != h[0] | h[2] != h[2]))) break;
    redo = 1;
    }
    float4* const rs = &G->rstat[128 * m128 + r0];
    {
      const bool up = q & 2;
      float a = up ? sum1 : sum0, b = up ? sq1 : sq0, d = up ? dot1 : dot0;
      a += __shfl_xor_sync(~0u, up ? sum0 : sum1, 2); b += __shfl_xor_sync(~0u, up ? sq0 : sq1, 2); d += __shfl_xor_sync(~0u, up ? dot0 : dot1, 2);
      a += __shfl_xor_sync(~0u, a, 1); b += __shfl_xor_sync(~0u, b, 1); d += __shfl_xor_sync(~0u, d, 1);
      if ((q & 1) == 0) red_add_f32x4(rs + 4 * q, a, b, d, 1.f);
    }
    float rstd[2], bm[2];
    uint32_t best, it = 0;
    {
      const float2 swa = lds64f(sb + OFF_SUMWR), swb = lds64f(sb + OFF_SUMWR + 8);
      const float sw = (swa.x + swa.y) + (swb.x + swb.y);
      uint4 a[2]; uint32_t key[2];
      do { a[0] = ld128_rlx(rs); a[1] = ld128_rlx(rs + 8); } while (__any_sync(~0u, (a[0].w & a[1].w) != 0x41000000u) && ++it < POLL_LIMIT);
      #pragma unroll
      for (int i = 0; i < 2; i++) {
        const float mean = __uint_as_float(a[i].x) * (1.f / DM);
        rstd[i] = rsqrtf(fmaxf(__uint_as_float(a[i].y) * (1.f / DM) - mean * mean, 0.f) + 1e-5f);
        bm[i] = -mean * rstd[i];
        const uint32_t rr = __float_as_uint(fmaf(__uint_as_float(a[i].z), rstd[i], sw * bm[i]));
        key[i] = ((rr ^ ((uint32_t)((int32_t)rr >> 31) | 0x80000000u)) & ~2047u) | (2047 - 128 * m128 - r0 - 8 * i);
      }
      asm volatile("redux.sync.max.u32 %0, %1, 0xffffffff;" : "=r"(best) : "r"(max(key[0], key[1])));
    }
    sts32(sb + OFF_BEST + 4 * warp, best);
    bar_sync(NB_WG01, 256);
    {
      const uint4 b0 = lds128(sb + OFF_BEST), b1 = lds128(sb + OFF_BEST + 16);
      best = max(max(max(b0.x, b0.y), max(b0.z, b0.w)), max(max(b1.x, b1.y), max(b1.z, b1.w)));
    }
    const int win = ~best & 127;
    if (warp == ((win >> 4) ^ 1) && (lane < 4 || it == 0)) st128_rlx(&G->key[((2 * j + (lane >> 1)) & 15) * 128 + 8 * m128 + 4 * (lane & 1)], best, best, best, best);
    if ((win & 0x77) == r0) {
      const bool up = win & 8;
      const float ra = up ? rstd[1] : rstd[0], rb = up ? bm[1] : bm[0];
      uint32_t x[16];
      #pragma unroll
      for (int i = 0; i < 16; i++) x[i] = pack_bf16(fmaf(up ? h[4*i+2] : h[4*i], ra, rb), fmaf(up ? h[4*i+3] : h[4*i+1], ra, rb));
      #pragma unroll
      for (int i = 0; i < 4; i++) st128_rlx(&G->cand[m128 * 512 + 64 * j + 16 * i + 4 * q], x[4*i], x[4*i+1], x[4*i+2], x[4*i+3]);
    }
    __syncwarp();
    bar_arrive(NB_G2E, 384);
    {
      const float a0 = 1.f + rstd[0], b0 = bm[0], a1 = 1.f + rstd[1], b1 = bm[1];
      #pragma unroll
      for (int k = 0; k < 8; k++)
        stsm4(((sb + OFF_OUT + wg * 8192 + sa) ^ ((k & 3) << 5)) + (k >> 2) * 16384,
              pack_bf16(fmaf(h[8*k], a0, b0), fmaf(h[8*k+1], a0, b0)),     pack_bf16(fmaf(h[8*k+2], a1, b1), fmaf(h[8*k+3], a1, b1)),
              pack_bf16(fmaf(h[8*k+4], a0, b0), fmaf(h[8*k+5], a0, b0)),   pack_bf16(fmaf(h[8*k+6], a1, b1), fmaf(h[8*k+7], a1, b1)));
      fence_async_smem();
      __syncwarp();
      if (lane == 0) mbar_arrive(sb + B_OUT + 8 * wg);
    }
    {
      uint32_t wa[8][4][4];
      const uint32_t wb = sb + 16384 * (((uint32_t)FF_SLOT >> (4 * warp)) & 15) + ((lane & 7) + ((lane >> 4) << 3)) * 64 + ((((lane >> 3) & 1) ^ ((lane >> 1) & 3)) << 4);
      if (f < NFFN) mbar_wait(sb + B_F + 8 * warp, 0);
      #pragma unroll
      for (int i = 0; i < 32; i++) ldsm4t((wb ^ ((i & 1) << 5)) + ((i >> 1) & 1) * 8192 + (i >> 2) * 1024, wa[i >> 2][i & 3][0], wa[i >> 2][i & 3][1], wa[i >> 2][i & 3][2], wa[i >> 2][i & 3][3]);
      bar_sync(NB_XS, 384);
      uint4 xs[4];
      #pragma unroll
      for (int i = 0; i < 4; i++) xs[i] = lds128(sb + OFF_XSEL + 256 * warp + 64 * i + 16 * q);
      float d[4][4];
      #pragma unroll
      for (int ks = 0; ks < 8; ks++) {
        #pragma unroll
        for (int m = 0; m < 4; m++) {
          if (ks == 0) { d[m][0] = 0.f; d[m][1] = 0.f; d[m][2] = 0.f; d[m][3] = 0.f; }
          mma16816(d[m][0], d[m][1], d[m][2], d[m][3], wa[ks][m][0], wa[ks][m][1], wa[ks][m][2], wa[ks][m][3],
                   (ks & 1) ? xs[ks >> 1].z : xs[ks >> 1].x, (ks & 1) ? xs[ks >> 1].w : xs[ks >> 1].y);
        }
      }
      #pragma unroll
      for (int m = 0; m < 8; m++) stsf(sb + OFF_GU + (8 * m + g) * 48 + 4 * warp, d[m >> 1][2 * (m & 1)]);
      bar_arrive(NB_ACT, 384);
    }
    {
      const uint32_t ky = __float_as_uint(ldsf(sb + OFF_KEY));
      const int row = 2047 - (ky & 2047) - 128 * m128;
      if ((uint32_t)row < 128u) {
        const int vi = (j & 1) + wg, e = 3 * vi + q - 4 * (j & 1);
        const float kr = __uint_as_float((ky & ~2047u) ^ ((ky >> 31) ? 0x80000000u : 0xfffff800u));
        const int col = 32 * wp + 16 * (e & 1) + 4 * (e & 2) + g;
        const float sg = rcp(1.f + ex2(-LOG2E * kr));
        const uint32_t base = __float_as_uint(ldsf(sb + OFF_OUT + (col >> 6) * 16384 + row * 128 + ((((col >> 3) ^ row) & 7) << 4) + 2 * (col & 6)));
        const float4* yp = &G->yacc[(q * 3 + vi) * 128 + 32 * (j >> 1) + 8 * wp + g];
        uint32_t it = 0;
        uint4 v;
        mbar_wait(sb + B_SD, 0);
        do { v = ld128_rlx(yp); } while (__any_sync(~0u, __uint_as_float(v.w) != (float)(NFFN / 4)) && ++it < POLL_LIMIT);
        float y0 = __uint_as_float(v.x), y1 = __uint_as_float(v.y), y2 = __uint_as_float(v.z);
        #pragma unroll
        for (int o = 1; o < 4; o <<= 1) { y0 += __shfl_xor_sync(~0u, y0, o); y1 += __shfl_xor_sync(~0u, y1, o); y2 += __shfl_xor_sync(~0u, y2, o); }
        if (q < 3 && (uint32_t)e < 4u)
          P.out_p[(size_t)(128 * m128 + row) * DM + 128 * j + col] = __float2bfloat16(fmaf(q == 0 ? y0 : q == 1 ? y1 : y2, sg, (col & 1) ? bf_hi(base) : bf_lo(base)));
      }
      if (c == 0 && tid == 0) st32_rlx(&G->epoch, __float_as_uint(ldsf(sb + OFF_EP)));
    }
  }
  if (wg == 2) {
    uint32_t wf[16][2][4];
    {
      const uint32_t wb = sb + OFF_S + 16384 * (wp & 1) + ((lane & 7) + ((lane >> 4) << 3)) * 128 + ((((lane >> 3) & 1) ^ (lane & 7)) << 4);
      if (f < NFFN) mbar_wait(sb + B_WD + 8 * wp, 0);
      #pragma unroll
      for (int i = 0; i < 32; i++) ldsm4t((wb ^ (((i >> 1) & 3) << 5)) + (i >> 3) * 4096 + (i & 1) * 2048, wf[i >> 1][i & 1][0], wf[i >> 1][i & 1][1], wf[i >> 1][i & 1][2], wf[i >> 1][i & 1][3]);
      fence_async_smem();
      __syncwarp();
      if (lane == 0) mbar_arrive(sb + B_WC + 8 * wp);
    }
    bar_sync(NB_G2E, 384);
    {
      uint32_t cur = 0;
      uint4 v;
      #pragma unroll 1
      for (uint32_t it = 0; it < POLL_LIMIT; it++) {
        const uint32_t kx = ld32_rlx(&G->key[(c & 15) * 128 + 8 * (lane & 15)]);
        v = ld128_rlx(&G->cand[((~cur >> 7) & 15) * 512 + 4 * t]);
        uint32_t best;
        asm volatile("redux.sync.max.u32 %0, %1, 0xffffffff;" : "=r"(best) : "r"(kx));
        if (!__any_sync(~0u, kx == 0 || v.w == ~0u) && best == cur) break;
        cur = best;
      }
      sts128(sb + OFF_XSEL + 16 * t, v.x, v.y, v.z, v.w);
      sts32(sb + OFF_KEY, cur);
      bar_arrive(NB_XS, 384);
    }
    float4* yd = &G->yacc[(f & 3) * 384 + 32 * wp + 8 * q + g];
    asm volatile("" : "+l"(yd));
    if (f >= NFFN) { bar_arrive(NB_ACT, 384); cluster_wait(); return; }
    bar_sync(NB_ACT, 384);
    float gu[2];
    #pragma unroll
    for (int i = 0; i < 2; i++) {
      const uint4 v0 = lds128(sb + OFF_GU + (32 * i + lane) * 48), v1 = lds128(sb + OFF_GU + (32 * i + lane) * 48 + 16);
      gu[i] = ((__uint_as_float(v0.x) + __uint_as_float(v0.y)) + (__uint_as_float(v0.z) + __uint_as_float(v0.w))) +
              ((__uint_as_float(v1.x) + __uint_as_float(v1.y)) + (__uint_as_float(v1.z) + __uint_as_float(v1.w)));
    }
    const float act = gu[0] * gu[1] * rcp(1.f + ex2(-LOG2E * gu[0]));
    const uint32_t ap = pack_bf16(act, __shfl_down_sync(~0u, act, 1));
    uint32_t bf[4];
    #pragma unroll
    for (int i = 0; i < 4; i++) bf[i] = __shfl_sync(~0u, ap, 2 * q + 8 * i);
    float d[16][4];
    #pragma unroll
    for (int k = 0; k < 2; k++)
      #pragma unroll
      for (int i = 0; i < 16; i++) {
        if (k == 0) { d[i][0] = 0.f; d[i][1] = 0.f; d[i][2] = 0.f; d[i][3] = 0.f; }
        mma16816(d[i][0], d[i][1], d[i][2], d[i][3], wf[i][k][0], wf[i][k][1], wf[i][k][2], wf[i][k][3], bf[2*k], bf[2*k+1]);
      }
    float y[9];
    #pragma unroll
    for (int e = 0; e < 8; e++) {
      const int n = 2 * (e & 4) + (e & 1);
      const float lo = (q & 1) ? d[n + 2][e & 2] : d[n][e & 2], hi = (q & 1) ? d[n + 6][e & 2] : d[n + 4][e & 2];
      y[e] = (q & 2) ? hi : lo;
    }
    y[8] = 0.f;
    #pragma unroll
    for (int i = 0; i < 3; i++) red_add_f32x4(yd + 128 * i, y[3*i], y[3*i+1], y[3*i+2], 1.f);
  }
  }
  cluster_wait();
}

typedef CUresult (*EncodeFn)(CUtensorMap*, CUtensorMapDataType, cuuint32_t, void*, const cuuint64_t*, const cuuint64_t*,
                             const cuuint32_t*, const cuuint32_t*, CUtensorMapInterleave, CUtensorMapSwizzle,
                             CUtensorMapL2promotion, CUtensorMapFloatOOBfill);

void make_map(EncodeFn enc, CUtensorMap* m, const void* p, int n, const cuuint64_t* dims, const cuuint64_t* str, const cuuint32_t* box,
              CUtensorMapSwizzle sw, CUtensorMapL2promotion promo) {
  cuuint32_t es[5] = {1, 1, 1, 1, 1};
  enc(m, CU_TENSOR_MAP_DATA_TYPE_BFLOAT16, n, const_cast<void*>(p), dims, str, box, es, CU_TENSOR_MAP_INTERLEAVE_NONE, sw, promo,
      CU_TENSOR_MAP_FLOAT_OOB_FILL_NONE);
}
void map2(EncodeFn enc, CUtensorMap* m, const void* p, uint64_t cols, uint64_t rows, uint32_t bc, uint32_t br, CUtensorMapSwizzle sw,
          CUtensorMapL2promotion promo) {
  const cuuint64_t dims[2] = {cols, rows}, str[1] = {cols * 2};
  const cuuint32_t box[2] = {bc, br};
  make_map(enc, m, p, 2, dims, str, box, sw, promo);
}
void map3(EncodeFn enc, CUtensorMap* m, const void* p, uint64_t cols, uint64_t rows, uint32_t br, uint32_t nb) {
  const cuuint64_t dims[3] = {64, rows, cols / 64}, str[2] = {cols * 2, 128};
  const cuuint32_t box[3] = {64, br, nb};
  make_map(enc, m, p, 3, dims, str, box, CU_TENSOR_MAP_SWIZZLE_128B, CU_TENSOR_MAP_L2_PROMOTION_L2_128B);
}

}

extern "C" void kernel_launch(void* const* d_in, const int* in_sizes, int n_in, void* d_out, int out_size) {
  (void)in_sizes; (void)n_in; (void)out_size;
  static EncodeFn enc = nullptr;
  static void* o_ptr = nullptr;
  if (!enc) {
    void* f = nullptr; cudaDriverEntryPointQueryResult qr;
    cudaGetDriverEntryPoint("cuTensorMapEncodeTiled", &f, cudaEnableDefault, &qr);
    enc = (EncodeFn)f;
    cudaGetSymbolAddress(&o_ptr, g_scr);
    cudaFuncSetAttribute(fused_kernel, cudaFuncAttributeMaxDynamicSharedMemorySize, SMEM_BYTES);
  }
  const bf16* x = (const bf16*)d_in[0];
  const bf16* wqkv = (const bf16*)d_in[1];
  const bf16* wphi = (const bf16*)d_in[2];
  const bf16* wo = (const bf16*)d_in[3];
  const bf16* wr = (const bf16*)d_in[5];
  const bf16* wgate = (const bf16*)d_in[6];
  const bf16* wup = (const bf16*)d_in[7];
  const bf16* wdown = (const bf16*)d_in[8];
  Params P;
  const CUtensorMapSwizzle S128 = CU_TENSOR_MAP_SWIZZLE_128B, S64 = CU_TENSOR_MAP_SWIZZLE_64B;
  const CUtensorMapL2promotion L128 = CU_TENSOR_MAP_L2_PROMOTION_L2_128B, L256 = CU_TENSOR_MAP_L2_PROMOTION_L2_256B,
                               L64 = CU_TENSOR_MAP_L2_PROMOTION_L2_64B;
  map2(enc, &P.x128, x, DM, SEQ, 64, 128, S128, L128);
  map2(enc, &P.x64, x, DM, SEQ, 64, 64, S128, L128);
  {
    const cuuint64_t dims[4] = {64, DM, 16, 3}, str[3] = {6 * DM, 128, 2 * DM};
    const cuuint32_t box[4] = {64, 64, 1, 2};
    make_map(enc, &P.wkv, wqkv, 4, dims, str, box, S128, L128);
  }
  map3(enc, &P.wq, wqkv, 3 * DM, DM, 64, 2);
  for (int i = 0; i < 2; i++) {
    const cuuint64_t dims[5] = {DM, (cuuint64_t)(DM - 94 - 64 * i), 4, 4, 2}, str[4] = {2 * DM, 16 * DM, 4 * DM, (cuuint64_t)(128 * DM) << i};
    const cuuint32_t box[5] = {64, 2, 4, 4, 2};
    make_map(enc, &P.wo[i], wo, 5, dims, str, box, S128, L128);
  }
  map3(enc, &P.wd, wdown, DM, FF, 32, 4);
  map2(enc, &P.wg, wgate, FF, DM, 32, 128, S64, L64);
  map2(enc, &P.wu, wup, FF, DM, 32, 128, S64, L64);
  map2(enc, &P.tg, wgate, FF, DM, 8, 16, CU_TENSOR_MAP_SWIZZLE_NONE, L128);
  map2(enc, &P.tu, wup, FF, DM, 8, 16, CU_TENSOR_MAP_SWIZZLE_NONE, L128);
  map2(enc, &P.td, wdown, 128, FF * 8, 8, 16, CU_TENSOR_MAP_SWIZZLE_NONE, L256);
  map2(enc, &P.xs, x, DM, SEQ, 128, 16, CU_TENSOR_MAP_SWIZZLE_NONE, L256);
  map2(enc, &P.ws, wqkv, 3 * DM, DM, 16, 128, CU_TENSOR_MAP_SWIZZLE_NONE, L128);
  map2(enc, &P.qs, wqkv, 3 * DM, DM, 32, 128, CU_TENSOR_MAP_SWIZZLE_NONE, L64);
  map2(enc, &P.out, d_out, DM, SEQ, 64, 16, S128, L128);
  map2(enc, &P.o, o_ptr, 256, SEQ * DM / 256, 256, 16, CU_TENSOR_MAP_SWIZZLE_NONE, L128);
  map2(enc, &P.phi, wphi, 32, 1024, 32, 32, S64, L64);
  P.x = x; P.wqkv = wqkv; P.wo_p = wo; P.wr = wr; P.out_p = (bf16*)d_out; P.g = (Scratch*)o_ptr; P.zero = 0;

  fused_kernel<<<128, 512, SMEM_BYTES, cudaStreamPerThread>>>(P);
}
```
